```python
import torch

def _softmax(x, axis=-1):
    return torch.softmax(x, dim=axis)
def _gelu(x):
    return torch.nn.functional.gelu(x, approximate="tanh")
def _silu(x):
    return torch.nn.functional.silu(x)
def _sigmoid(x):
    return torch.sigmoid(x)
def _layernorm(x, axis=-1, eps=1e-5):
    m = x.mean(dim=axis, keepdim=True)
    v = x.var(dim=axis, keepdim=True, unbiased=False)
    return (x - m) / torch.sqrt(v + eps)
def _scatter_add(tgt, idx, src, axis=0):
    return tgt.clone().index_add_(axis, idx, src)
def _segment_sum(src, seg, n):
    out = torch.zeros((n,) + src.shape[1:], dtype=src.dtype)
    return out.index_add_(0, seg, src)
def _pad(x, pw):
    flat = tuple(v for pair in reversed(pw) for v in pair)
    return torch.nn.functional.pad(x, flat)

kernel_name = 'recurrent_scan__ssm_conv_h3__mixer_token_mlp__prompt'

def setup_inputs():

    _w = (lambda a: (lambda t: t.to(torch.bfloat16) if t.is_floating_point() else t)(torch.as_tensor(a)))
    def _A_setup():
        B, S, D = 1, 2048, 576
        ks = 4
        return {
            "q": _w((lambda *s: torch.randn(*s, dtype=torch.bfloat16) * 0.05)(B, S, D)),
            "k": _w((lambda *s: torch.randn(*s, dtype=torch.bfloat16) * 0.8)(B, S, D)),
            "v": _w((lambda *s: torch.randn(*s, dtype=torch.bfloat16) * 0.8)(B, S, D)),
            "shift_k": _w((lambda *s: torch.randn(*s, dtype=torch.bfloat16) * 0.8)(D, ks) * 0.5),
            "ssm_k": _w((lambda *s: torch.randn(*s, dtype=torch.bfloat16) * 0.8)(D, S) * (1.0 / S ** 0.5)),
            "ssm_D": _w((lambda *s: torch.randn(*s, dtype=torch.bfloat16) * 0.8)(D)),
        }
    _A_in = _A_setup()

    def _B_setup():
        B, S, D, F = 1, 2048, 576, 4608
        return {
            "x": _w((lambda *s: torch.randn(*s, dtype=torch.bfloat16) * 0.05)(B, S, D)),
            "w1": _w((lambda *s: torch.randn(*s, dtype=torch.bfloat16) * 0.8)(S, F) * (S ** -0.5)),
            "b1": _w((lambda *s: torch.randn(*s, dtype=torch.bfloat16) * 12.8)(F) * 0.02),
            "w2": _w((lambda *s: torch.randn(*s, dtype=torch.bfloat16) * 0.2)(F, S) * (F ** -0.5)),
            "b2": _w((lambda *s: torch.randn(*s, dtype=torch.bfloat16) * 3.2)(S) * 0.02),
        }
    _B_in = _B_setup()

    return {
        "A_q": _A_in["q"],
        "A_k": _A_in["k"],
        "A_v": _A_in["v"],
        "A_shift_k": _A_in["shift_k"],
        "A_ssm_k": _A_in["ssm_k"],
        "A_ssm_D": _A_in["ssm_D"],
        "B_x": _B_in["x"],
        "B_w1": _B_in["w1"],
        "B_b1": _B_in["b1"],
        "B_w2": _B_in["w2"],
        "B_b2": _B_in["b2"],
    }

def reference(A_q, A_k, A_v, A_shift_k, A_ssm_k, A_ssm_D, B_x, B_w1, B_b1, B_w2, B_b2):
    def _A_ref(q, k, v, shift_k, ssm_k, ssm_D):
        B, S, D = q.shape
        ks = shift_k.shape[-1]
        k_pad = _pad(k, ((0, 0), (ks - 1, 0), (0, 0)))
        k_shift = torch.zeros_like(k)
        for t in range(ks):
            k_shift = k_shift + k_pad[:, t:t + S, :] * shift_k[:, ks - 1 - t][None, None, :]
        kv = k_shift * v
        L = 2 * S
        kv_pad = _pad(kv, ((0, 0), (0, S), (0, 0)))
        kf_pad = _pad(ssm_k, ((0, 0), (0, S)))
        kv_f = (lambda x, axes=(-2,-1): torch.fft.rfft2(x.float(), dim=axes))(kv_pad[:, None, :, :], axes=(1, 2))
        kf_f = (lambda x, axes=(-2,-1): torch.fft.rfft2(x.float(), dim=axes))(kf_pad[:, None, :], axes=(1, 2))
        kf_f = (lambda x, *d: x.permute(*d))(kf_f, 1, 2, 0)
        y_f = kv_f * kf_f[None, :, :, :]
        y = (lambda x, s, axes=(-2,-1): torch.fft.irfft2(x, s=s, dim=axes).to(torch.bfloat16))(y_f, (1, L), axes=(1, 2))[:, 0, :S, :]
        y = y + kv * ssm_D[None, None, :]
        return q * y

    def _B_ref(x, w1, b1, w2, b2):
        B, S, D = x.shape
        h = _layernorm(x, axis=-1)
        u = torch.einsum("bsd,sf->bdf", h, w1) + b1
        u = _gelu(u)
        y = torch.einsum("bdf,fs->bds", u, w2) + b2
        return (lambda x, *d: x.permute(*d))(y, 0, 2, 1)

    x = A_q
    xn = _layernorm(x, axis=-1)
    s = _A_ref(xn, A_k, A_v, A_shift_k, A_ssm_k, A_ssm_D)
    g = _silu(_B_ref(xn, B_w1, B_b1, B_w2, B_b2))
    return x + s * g
```

```cpp
#include <cuda_runtime.h>
#include <cuda.h>
#include <cuda_bf16.h>
#include <stdint.h>

namespace {

constexpr int S_ = 2048, D_ = 576, F_ = 4608;
constexpr int NSTAGE = 5, SLOT = 40960;
constexpr int G1_KB = 32, G2_KB = 36;
constexpr int G1_BYTES = 40960, G2_BYTES = 16384 + 18432;
constexpr int N_CONV_CTA = 24, N_SHORT = 22, N_LONG_EXTRA = 12;
static_assert(N_CONV_CTA * N_SHORT + 4 * N_LONG_EXTRA == D_, "conv split");
constexpr int KV_ROUNDS = 6;
constexpr int G2_PF_KB = 30;

constexpr int SM_OUT = NSTAGE * SLOT;
constexpr int SM_BAR = SM_OUT + 18432;
constexpr int SM_TOTAL = SM_BAR + 256 + 1024;
constexpr int CV_BASE = 2 * SLOT;
constexpr int CV_NSLOT = 4, CV_KOFF = 8192, CV_SLOT = 8192 + 4224;
constexpr int CV_RED = CV_BASE + CV_NSLOT * CV_SLOT, CV_REDW = 2112 * 4, CV_REDWG = 4 * CV_REDW;
static_assert(CV_RED + 2 * CV_REDWG <= SM_OUT, "conv overlay");
constexpr int B_FULL = 0, B_EMPTY = NSTAGE, B_CFULL = 2 * NSTAGE, B_CEMPTY = B_CFULL + CV_NSLOT,
              B_CDONE = B_CEMPTY + CV_NSLOT, B_XRDY = B_CDONE + 1, B_XFULL = B_CDONE + 2;

struct Roles {
  int8_t g1m[66];
  int8_t g1n[66];
  int8_t cv[66];
  int8_t g2m[66];
  int8_t g2n[66];
  int8_t p0[66];
};

struct Params {
  CUtensorMap m_w1, m_h, m_ust, m_w2, m_uld, m_out;
  const __nv_bfloat16 *x, *k, *v, *shift_k, *ssm_k, *ssm_D, *b1, *b2;
  Roles roles;
};

__device__ __align__(1024) __nv_bfloat16 g_h[S_ * D_];
__device__ __align__(1024) __nv_bfloat16 g_p2[S_ * D_];
__device__ __align__(1024) __nv_bfloat16 g_ub[D_ * 4096];
__device__ __align__(1024) __nv_bfloat16 g_y[D_ * S_];
__device__ __align__(1024) __nv_bfloat16 g_u[D_ * F_];
__device__ __align__(128) float2 g_stats[S_];
__device__ __align__(128) uint32_t g_hflag[128];
__device__ __align__(128) uint32_t g_kvflag[KV_ROUNDS * 128];
__device__ __align__(128) uint32_t g_uflag[3 * 96];
__device__ __align__(128) uint32_t g_yflag[64];
__device__ __align__(128) uint32_t g_epoch;
#define TLREC(i) do { } while (0)

__device__ __forceinline__ uint32_t smem_u32(const void* p) { return (uint32_t)__cvta_generic_to_shared(p); }
__device__ __forceinline__ void mbar_init(uint32_t bar, uint32_t cnt) { asm volatile("mbarrier.init.shared::cta.b64 [%0], %1;" :: "r"(bar), "r"(cnt) : "memory"); }
__device__ __forceinline__ void mbar_expect_tx(uint32_t bar, uint32_t bytes) { asm volatile("mbarrier.arrive.expect_tx.shared::cta.b64 _, [%0], %1;" :: "r"(bar), "r"(bytes) : "memory"); }
__device__ __forceinline__ void mbar_arrive(uint32_t bar) { asm volatile("mbarrier.arrive.shared::cta.b64 _, [%0];" :: "r"(bar) : "memory"); }
__device__ __forceinline__ uint32_t mapa(uint32_t addr, uint32_t cta) { uint32_t r; asm volatile("mapa.shared::cluster.u32 %0, %1, %2;" : "=r"(r) : "r"(addr), "r"(cta)); return r; }
__device__ __forceinline__ void mbar_arrive_remote(uint32_t rbar) { asm volatile("mbarrier.arrive.release.cluster.shared::cluster.b64 _, [%0];" :: "r"(rbar) : "memory"); }
__device__ __forceinline__ void mbar_wait(uint32_t bar, uint32_t parity) {
  asm volatile("{\n .reg .pred p;\n .reg .u32 c;\n mov.u32 c, 0;\n"
               "W_%=:\n mbarrier.try_wait.parity.shared::cta.b64 p, [%0], %1;\n @p bra D_%=;\n"
               " add.u32 c, c, 1;\n setp.lt.u32 p, c, 2000000;\n @p bra W_%=;\n trap;\n D_%=:\n }" :: "r"(bar), "r"(parity) : "memory");
}
__device__ __forceinline__ void mbar_wait_cluster(uint32_t bar, uint32_t parity) {
  asm volatile("{\n .reg .pred p;\n .reg .u32 c;\n mov.u32 c, 0;\n"
               "W_%=:\n mbarrier.try_wait.parity.acquire.cluster.shared::cta.b64 p, [%0], %1;\n @p bra D_%=;\n"
               " add.u32 c, c, 1;\n setp.lt.u32 p, c, 2000000;\n @p bra W_%=;\n trap;\n D_%=:\n }" :: "r"(bar), "r"(parity) : "memory");
}
__device__ __forceinline__ void tma2d(uint32_t dst, const CUtensorMap* m, int c0, int c1, uint32_t bar) {
  asm volatile("cp.async.bulk.tensor.2d.shared::cluster.global.mbarrier::complete_tx::bytes [%0], [%1, {%3, %4}], [%2];"
               :: "r"(dst), "l"(m), "r"(bar), "r"(c0), "r"(c1) : "memory");
}
__device__ __forceinline__ void tma3d(uint32_t dst, const CUtensorMap* m, int c0, int c1, int c2, uint32_t bar) {
  asm volatile("cp.async.bulk.tensor.3d.shared::cluster.global.mbarrier::complete_tx::bytes [%0], [%1, {%3, %4, %5}], [%2];"
               :: "r"(dst), "l"(m), "r"(bar), "r"(c0), "r"(c1), "r"(c2) : "memory");
}
__device__ __forceinline__ void tma2d_store(const CUtensorMap* m, uint32_t src, int c0, int c1) {
  asm volatile("cp.async.bulk.tensor.2d.global.shared::cta.bulk_group [%0, {%2, %3}], [%1];" :: "l"(m), "r"(src), "r"(c0), "r"(c1) : "memory");
}
__device__ __forceinline__ void bulk_load(uint32_t dst, const void* src, uint32_t bytes, uint32_t bar) {
  asm volatile("cp.async.bulk.shared::cluster.global.mbarrier::complete_tx::bytes [%0], [%1], %2, [%3];" :: "r"(dst), "l"(src), "r"(bytes), "r"(bar) : "memory");
}
__device__ __forceinline__ void bulk_commit() { asm volatile("cp.async.bulk.commit_group;" ::: "memory"); }
__device__ __forceinline__ void bulk_wait_all() { asm volatile("cp.async.bulk.wait_group 0;" ::: "memory"); }
__device__ __forceinline__ void bulk_wait_read() { asm volatile("cp.async.bulk.wait_group.read 0;" ::: "memory"); }
__device__ __forceinline__ void fence_async_smem() { asm volatile("fence.proxy.async.shared::cta;" ::: "memory"); }
__device__ __forceinline__ void fence_async_global() { asm volatile("fence.proxy.async.global;" ::: "memory"); }
__device__ __forceinline__ void fence_gpu() { asm volatile("fence.acq_rel.gpu;" ::: "memory"); }
__device__ __forceinline__ void st_flag(uint32_t* p, uint32_t v) { asm volatile("st.relaxed.gpu.global.u32 [%0], %1;" :: "l"(p), "r"(v) : "memory"); }
__device__ __forceinline__ uint32_t ld_flag(const uint32_t* p) { uint32_t v; asm volatile("ld.relaxed.gpu.global.u32 %0, [%1];" : "=r"(v) : "l"(p) : "memory"); return v; }
__device__ __forceinline__ uint4 ld_flag4(const uint32_t* p) {
  uint4 v; asm volatile("ld.relaxed.gpu.global.v4.u32 {%0,%1,%2,%3}, [%4];" : "=r"(v.x), "=r"(v.y), "=r"(v.z), "=r"(v.w) : "l"(p) : "memory"); return v;
}
__device__ __forceinline__ void bar_sync(int id, int n) { asm volatile("bar.sync %0, %1;" :: "r"(id), "r"(n) : "memory"); }
__device__ __forceinline__ void bar_arrive(int id, int n) { asm volatile("bar.arrive %0, %1;" :: "r"(id), "r"(n) : "memory"); }
__device__ __forceinline__ void wg_fence() { asm volatile("wgmma.fence.sync.aligned;" ::: "memory"); }
__device__ __forceinline__ void wg_commit() { asm volatile("wgmma.commit_group.sync.aligned;" ::: "memory"); }
template <int N> __device__ __forceinline__ void wg_wait() { asm volatile("wgmma.wait_group.sync.aligned %0;" :: "n"(N) : "memory"); }
template <int N> __device__ __forceinline__ void pin_regs(float* a) {
#pragma unroll
  for (int i = 0; i < N; i++) asm volatile("" : "+f"(a[i]) :: "memory");
}
__device__ __forceinline__ uint64_t make_desc(uint32_t addr, uint32_t lbo, uint32_t sbo, uint32_t swz) {
  return (uint64_t)((addr & 0x3FFFF) >> 4) | ((uint64_t)(lbo >> 4) << 16) | ((uint64_t)(sbo >> 4) << 32) | ((uint64_t)swz << 62);
}
__device__ __forceinline__ uint32_t pack_bf16(float lo, float hi) { uint32_t r; asm("cvt.rn.bf16x2.f32 %0, %1, %2;" : "=r"(r) : "f"(hi), "f"(lo)); return r; }
__device__ __forceinline__ float bf_lo(uint32_t p) { return __uint_as_float(p << 16); }
__device__ __forceinline__ float bf_hi(uint32_t p) { return __uint_as_float(p & 0xffff0000u); }
__device__ __forceinline__ float round_bf16(float v) { return bf_lo(pack_bf16(v, 0.f)); }
__device__ __forceinline__ uint32_t bmul2(uint32_t a, uint32_t b) { uint32_t r; asm("mul.rn.bf16x2 %0, %1, %2;" : "=r"(r) : "r"(a), "r"(b)); return r; }
__device__ __forceinline__ uint32_t badd2(uint32_t a, uint32_t b) { uint32_t r; asm("add.rn.bf16x2 %0, %1, %2;" : "=r"(r) : "r"(a), "r"(b)); return r; }
__device__ __forceinline__ uint32_t bsub2(uint32_t a, uint32_t b) { uint32_t r; asm("sub.rn.bf16x2 %0, %1, %2;" : "=r"(r) : "r"(a), "r"(b)); return r; }
__device__ __forceinline__ float tanh_fast(float v) { float r; asm("tanh.approx.f32 %0, %1;" : "=f"(r) : "f"(v)); return r; }
__device__ __forceinline__ float gelu_tanh(float v) {
  float z = v * fmaf(v * v, 0.7978845608028654f * 0.044715f, 0.7978845608028654f);
  float hv = 0.5f * v;
  return fmaf(hv, tanh_fast(z), hv);
}
__device__ __forceinline__ float silu(float v) { float hv = 0.5f * v; return fmaf(hv, tanh_fast(hv), hv); }
__device__ __forceinline__ uint32_t ldg32(const void* p) { uint32_t v; asm volatile("ld.global.nc.u32 %0, [%1];" : "=r"(v) : "l"(p)); return v; }
__device__ __forceinline__ uint32_t ldg32_cg(const void* p) { uint32_t v; asm volatile("ld.global.cg.u32 %0, [%1];" : "=r"(v) : "l"(p) : "memory"); return v; }
__device__ __forceinline__ uint32_t lds32(uint32_t a) { uint32_t v; asm volatile("ld.shared.u32 %0, [%1];" : "=r"(v) : "r"(a) : "memory"); return v; }
__device__ __forceinline__ float4 lds128f(uint32_t a) { float4 v; asm volatile("ld.shared.v4.f32 {%0,%1,%2,%3}, [%4];" : "=f"(v.x), "=f"(v.y), "=f"(v.z), "=f"(v.w) : "r"(a) : "memory"); return v; }
__device__ __forceinline__ void sts64f(uint32_t a, float x, float y) { asm volatile("st.shared.v2.f32 [%0], {%1,%2};" :: "r"(a), "f"(x), "f"(y) : "memory"); }
__device__ __forceinline__ void stsm4(uint32_t a, uint32_t r0, uint32_t r1, uint32_t r2, uint32_t r3) {
  asm volatile("stmatrix.sync.aligned.m8n8.x4.shared.b16 [%0], {%1,%2,%3,%4};" :: "r"(a), "r"(r0), "r"(r1), "r"(r2), "r"(r3) : "memory");
}
__device__ __forceinline__ void stsm2(uint32_t a, uint32_t r0, uint32_t r1) {
  asm volatile("stmatrix.sync.aligned.m8n8.x2.shared.b16 [%0], {%1,%2};" :: "r"(a), "r"(r0), "r"(r1) : "memory");
}
__device__ __forceinline__ void stsm4t(uint32_t a, uint32_t r0, uint32_t r1, uint32_t r2, uint32_t r3) {
  asm volatile("stmatrix.sync.aligned.m8n8.x4.trans.shared.b16 [%0], {%1,%2,%3,%4};" :: "r"(a), "r"(r0), "r"(r1), "r"(r2), "r"(r3) : "memory");
}
__device__ __forceinline__ uint32_t movmt(uint32_t a) { uint32_t d; asm volatile("movmatrix.sync.aligned.m8n8.trans.b16 %0, %1;" : "=r"(d) : "r"(a)); return d; }
__device__ __forceinline__ void spin_guard(uint32_t& c) { if (++c > 4000000u) __trap(); }

__device__ __forceinline__ void wgmma_ss_n144_t10(float* d, uint64_t da, uint64_t db, int sd) {
  asm volatile("{ .reg .pred p; setp.ne.b32 p, %74, 0;\n"
      "wgmma.mma_async.sync.aligned.m64n144k16.f32.bf16.bf16 {"
      "%0,%1,%2,%3,%4,%5,%6,%7,%8,%9,%10,%11,%12,%13,%14,%15,"
      "%16,%17,%18,%19,%20,%21,%22,%23,%24,%25,%26,%27,%28,%29,%30,%31,"
      "%32,%33,%34,%35,%36,%37,%38,%39,%40,%41,%42,%43,%44,%45,%46,%47,"
      "%48,%49,%50,%51,%52,%53,%54,%55,%56,%57,%58,%59,%60,%61,%62,%63,"
      "%64,%65,%66,%67,%68,%69,%70,%71"
      "}, %72, %73, p, 1, 1, 1, 0; }"
    : "+f"(d[0]), "+f"(d[1]), "+f"(d[2]), "+f"(d[3]), "+f"(d[4]), "+f"(d[5]), "+f"(d[6]), "+f"(d[7]),
      "+f"(d[8]), "+f"(d[9]), "+f"(d[10]), "+f"(d[11]), "+f"(d[12]), "+f"(d[13]), "+f"(d[14]), "+f"(d[15]),
      "+f"(d[16]), "+f"(d[17]), "+f"(d[18]), "+f"(d[19]), "+f"(d[20]), "+f"(d[21]), "+f"(d[22]), "+f"(d[23]),
      "+f"(d[24]), "+f"(d[25]), "+f"(d[26]), "+f"(d[27]), "+f"(d[28]), "+f"(d[29]), "+f"(d[30]), "+f"(d[31]),
      "+f"(d[32]), "+f"(d[33]), "+f"(d[34]), "+f"(d[35]), "+f"(d[36]), "+f"(d[37]), "+f"(d[38]), "+f"(d[39]),
      "+f"(d[40]), "+f"(d[41]), "+f"(d[42]), "+f"(d[43]), "+f"(d[44]), "+f"(d[45]), "+f"(d[46]), "+f"(d[47]),
      "+f"(d[48]), "+f"(d[49]), "+f"(d[50]), "+f"(d[51]), "+f"(d[52]), "+f"(d[53]), "+f"(d[54]), "+f"(d[55]),
      "+f"(d[56]), "+f"(d[57]), "+f"(d[58]), "+f"(d[59]), "+f"(d[60]), "+f"(d[61]), "+f"(d[62]), "+f"(d[63]),
      "+f"(d[64]), "+f"(d[65]), "+f"(d[66]), "+f"(d[67]), "+f"(d[68]), "+f"(d[69]), "+f"(d[70]), "+f"(d[71])
    : "l"(da), "l"(db), "r"(sd));
}

__device__ __forceinline__ void wgmma_ss_n192_t11(float* d, uint64_t da, uint64_t db, int sd) {
  asm volatile("{ .reg .pred p; setp.ne.b32 p, %98, 0;\n"
      "wgmma.mma_async.sync.aligned.m64n192k16.f32.bf16.bf16 {"
      "%0,%1,%2,%3,%4,%5,%6,%7,%8,%9,%10,%11,%12,%13,%14,%15,"
      "%16,%17,%18,%19,%20,%21,%22,%23,%24,%25,%26,%27,%28,%29,%30,%31,"
      "%32,%33,%34,%35,%36,%37,%38,%39,%40,%41,%42,%43,%44,%45,%46,%47,"
      "%48,%49,%50,%51,%52,%53,%54,%55,%56,%57,%58,%59,%60,%61,%62,%63,"
      "%64,%65,%66,%67,%68,%69,%70,%71,%72,%73,%74,%75,%76,%77,%78,%79,"
      "%80,%81,%82,%83,%84,%85,%86,%87,%88,%89,%90,%91,%92,%93,%94,%95"
      "}, %96, %97, p, 1, 1, 1, 1; }"
    : "+f"(d[0]), "+f"(d[1]), "+f"(d[2]), "+f"(d[3]), "+f"(d[4]), "+f"(d[5]), "+f"(d[6]), "+f"(d[7]),
      "+f"(d[8]), "+f"(d[9]), "+f"(d[10]), "+f"(d[11]), "+f"(d[12]), "+f"(d[13]), "+f"(d[14]), "+f"(d[15]),
      "+f"(d[16]), "+f"(d[17]), "+f"(d[18]), "+f"(d[19]), "+f"(d[20]), "+f"(d[21]), "+f"(d[22]), "+f"(d[23]),
      "+f"(d[24]), "+f"(d[25]), "+f"(d[26]), "+f"(d[27]), "+f"(d[28]), "+f"(d[29]), "+f"(d[30]), "+f"(d[31]),
      "+f"(d[32]), "+f"(d[33]), "+f"(d[34]), "+f"(d[35]), "+f"(d[36]), "+f"(d[37]), "+f"(d[38]), "+f"(d[39]),
      "+f"(d[40]), "+f"(d[41]), "+f"(d[42]), "+f"(d[43]), "+f"(d[44]), "+f"(d[45]), "+f"(d[46]), "+f"(d[47]),
      "+f"(d[48]), "+f"(d[49]), "+f"(d[50]), "+f"(d[51]), "+f"(d[52]), "+f"(d[53]), "+f"(d[54]), "+f"(d[55]),
      "+f"(d[56]), "+f"(d[57]), "+f"(d[58]), "+f"(d[59]), "+f"(d[60]), "+f"(d[61]), "+f"(d[62]), "+f"(d[63]),
      "+f"(d[64]), "+f"(d[65]), "+f"(d[66]), "+f"(d[67]), "+f"(d[68]), "+f"(d[69]), "+f"(d[70]), "+f"(d[71]),
      "+f"(d[72]), "+f"(d[73]), "+f"(d[74]), "+f"(d[75]), "+f"(d[76]), "+f"(d[77]), "+f"(d[78]), "+f"(d[79]),
      "+f"(d[80]), "+f"(d[81]), "+f"(d[82]), "+f"(d[83]), "+f"(d[84]), "+f"(d[85]), "+f"(d[86]), "+f"(d[87]),
      "+f"(d[88]), "+f"(d[89]), "+f"(d[90]), "+f"(d[91]), "+f"(d[92]), "+f"(d[93]), "+f"(d[94]), "+f"(d[95])
    : "l"(da), "l"(db), "r"(sd));
}

__device__ __forceinline__ void wgmma_rs_n16(float* d, const uint32_t* a, uint64_t db, int sd) {
  asm volatile("{ .reg .pred p; setp.ne.b32 p, %13, 0;\n"
      "wgmma.mma_async.sync.aligned.m64n16k16.f32.bf16.bf16 {"
      "%0,%1,%2,%3,%4,%5,%6,%7"
      "}, {%8,%9,%10,%11}, %12, p, 1, 1, 0; }"
    : "+f"(d[0]), "+f"(d[1]), "+f"(d[2]), "+f"(d[3]), "+f"(d[4]), "+f"(d[5]), "+f"(d[6]), "+f"(d[7])
    : "r"(a[0]), "r"(a[1]), "r"(a[2]), "r"(a[3]), "l"(db), "r"(sd));
}

__device__ __forceinline__ void wgmma_rs_n32(float* d, const uint32_t* a, uint64_t db, int sd) {
  asm volatile("{ .reg .pred p; setp.ne.b32 p, %21, 0;\n"
      "wgmma.mma_async.sync.aligned.m64n32k16.f32.bf16.bf16 {"
      "%0,%1,%2,%3,%4,%5,%6,%7,%8,%9,%10,%11,%12,%13,%14,%15"
      "}, {%16,%17,%18,%19}, %20, p, 1, 1, 0; }"
    : "+f"(d[0]), "+f"(d[1]), "+f"(d[2]), "+f"(d[3]), "+f"(d[4]), "+f"(d[5]), "+f"(d[6]), "+f"(d[7]),
      "+f"(d[8]), "+f"(d[9]), "+f"(d[10]), "+f"(d[11]), "+f"(d[12]), "+f"(d[13]), "+f"(d[14]), "+f"(d[15])
    : "r"(a[0]), "r"(a[1]), "r"(a[2]), "r"(a[3]), "l"(db), "r"(sd));
}

__device__ __forceinline__ void wgmma_rs_n48(float* d, const uint32_t* a, uint64_t db, int sd) {
  asm volatile("{ .reg .pred p; setp.ne.b32 p, %29, 0;\n"
      "wgmma.mma_async.sync.aligned.m64n48k16.f32.bf16.bf16 {"
      "%0,%1,%2,%3,%4,%5,%6,%7,%8,%9,%10,%11,%12,%13,%14,%15,"
      "%16,%17,%18,%19,%20,%21,%22,%23"
      "}, {%24,%25,%26,%27}, %28, p, 1, 1, 0; }"
    : "+f"(d[0]), "+f"(d[1]), "+f"(d[2]), "+f"(d[3]), "+f"(d[4]), "+f"(d[5]), "+f"(d[6]), "+f"(d[7]),
      "+f"(d[8]), "+f"(d[9]), "+f"(d[10]), "+f"(d[11]), "+f"(d[12]), "+f"(d[13]), "+f"(d[14]), "+f"(d[15]),
      "+f"(d[16]), "+f"(d[17]), "+f"(d[18]), "+f"(d[19]), "+f"(d[20]), "+f"(d[21]), "+f"(d[22]), "+f"(d[23])
    : "r"(a[0]), "r"(a[1]), "r"(a[2]), "r"(a[3]), "l"(db), "r"(sd));
}

__device__ __forceinline__ void wgmma_rs_n64(float* d, const uint32_t* a, uint64_t db, int sd) {
  asm volatile("{ .reg .pred p; setp.ne.b32 p, %37, 0;\n"
      "wgmma.mma_async.sync.aligned.m64n64k16.f32.bf16.bf16 {"
      "%0,%1,%2,%3,%4,%5,%6,%7,%8,%9,%10,%11,%12,%13,%14,%15,"
      "%16,%17,%18,%19,%20,%21,%22,%23,%24,%25,%26,%27,%28,%29,%30,%31"
      "}, {%32,%33,%34,%35}, %36, p, 1, 1, 0; }"
    : "+f"(d[0]), "+f"(d[1]), "+f"(d[2]), "+f"(d[3]), "+f"(d[4]), "+f"(d[5]), "+f"(d[6]), "+f"(d[7]),
      "+f"(d[8]), "+f"(d[9]), "+f"(d[10]), "+f"(d[11]), "+f"(d[12]), "+f"(d[13]), "+f"(d[14]), "+f"(d[15]),
      "+f"(d[16]), "+f"(d[17]), "+f"(d[18]), "+f"(d[19]), "+f"(d[20]), "+f"(d[21]), "+f"(d[22]), "+f"(d[23]),
      "+f"(d[24]), "+f"(d[25]), "+f"(d[26]), "+f"(d[27]), "+f"(d[28]), "+f"(d[29]), "+f"(d[30]), "+f"(d[31])
    : "r"(a[0]), "r"(a[1]), "r"(a[2]), "r"(a[3]), "l"(db), "r"(sd));
}

__device__ __forceinline__ void wgmma_rs_n80(float* d, const uint32_t* a, uint64_t db, int sd) {
  asm volatile("{ .reg .pred p; setp.ne.b32 p, %45, 0;\n"
      "wgmma.mma_async.sync.aligned.m64n80k16.f32.bf16.bf16 {"
      "%0,%1,%2,%3,%4,%5,%6,%7,%8,%9,%10,%11,%12,%13,%14,%15,"
      "%16,%17,%18,%19,%20,%21,%22,%23,%24,%25,%26,%27,%28,%29,%30,%31,"
      "%32,%33,%34,%35,%36,%37,%38,%39"
      "}, {%40,%41,%42,%43}, %44, p, 1, 1, 0; }"
    : "+f"(d[0]), "+f"(d[1]), "+f"(d[2]), "+f"(d[3]), "+f"(d[4]), "+f"(d[5]), "+f"(d[6]), "+f"(d[7]),
      "+f"(d[8]), "+f"(d[9]), "+f"(d[10]), "+f"(d[11]), "+f"(d[12]), "+f"(d[13]), "+f"(d[14]), "+f"(d[15]),
      "+f"(d[16]), "+f"(d[17]), "+f"(d[18]), "+f"(d[19]), "+f"(d[20]), "+f"(d[21]), "+f"(d[22]), "+f"(d[23]),
      "+f"(d[24]), "+f"(d[25]), "+f"(d[26]), "+f"(d[27]), "+f"(d[28]), "+f"(d[29]), "+f"(d[30]), "+f"(d[31]),
      "+f"(d[32]), "+f"(d[33]), "+f"(d[34]), "+f"(d[35]), "+f"(d[36]), "+f"(d[37]), "+f"(d[38]), "+f"(d[39])
    : "r"(a[0]), "r"(a[1]), "r"(a[2]), "r"(a[3]), "l"(db), "r"(sd));
}

__device__ __forceinline__ void wgmma_rs_n96(float* d, const uint32_t* a, uint64_t db, int sd) {
  asm volatile("{ .reg .pred p; setp.ne.b32 p, %53, 0;\n"
      "wgmma.mma_async.sync.aligned.m64n96k16.f32.bf16.bf16 {"
      "%0,%1,%2,%3,%4,%5,%6,%7,%8,%9,%10,%11,%12,%13,%14,%15,"
      "%16,%17,%18,%19,%20,%21,%22,%23,%24,%25,%26,%27,%28,%29,%30,%31,"
      "%32,%33,%34,%35,%36,%37,%38,%39,%40,%41,%42,%43,%44,%45,%46,%47"
      "}, {%48,%49,%50,%51}, %52, p, 1, 1, 0; }"
    : "+f"(d[0]), "+f"(d[1]), "+f"(d[2]), "+f"(d[3]), "+f"(d[4]), "+f"(d[5]), "+f"(d[6]), "+f"(d[7]),
      "+f"(d[8]), "+f"(d[9]), "+f"(d[10]), "+f"(d[11]), "+f"(d[12]), "+f"(d[13]), "+f"(d[14]), "+f"(d[15]),
      "+f"(d[16]), "+f"(d[17]), "+f"(d[18]), "+f"(d[19]), "+f"(d[20]), "+f"(d[21]), "+f"(d[22]), "+f"(d[23]),
      "+f"(d[24]), "+f"(d[25]), "+f"(d[26]), "+f"(d[27]), "+f"(d[28]), "+f"(d[29]), "+f"(d[30]), "+f"(d[31]),
      "+f"(d[32]), "+f"(d[33]), "+f"(d[34]), "+f"(d[35]), "+f"(d[36]), "+f"(d[37]), "+f"(d[38]), "+f"(d[39]),
      "+f"(d[40]), "+f"(d[41]), "+f"(d[42]), "+f"(d[43]), "+f"(d[44]), "+f"(d[45]), "+f"(d[46]), "+f"(d[47])
    : "r"(a[0]), "r"(a[1]), "r"(a[2]), "r"(a[3]), "l"(db), "r"(sd));
}

__device__ __forceinline__ void wgmma_rs_n112(float* d, const uint32_t* a, uint64_t db, int sd) {
  asm volatile("{ .reg .pred p; setp.ne.b32 p, %61, 0;\n"
      "wgmma.mma_async.sync.aligned.m64n112k16.f32.bf16.bf16 {"
      "%0,%1,%2,%3,%4,%5,%6,%7,%8,%9,%10,%11,%12,%13,%14,%15,"
      "%16,%17,%18,%19,%20,%21,%22,%23,%24,%25,%26,%27,%28,%29,%30,%31,"
      "%32,%33,%34,%35,%36,%37,%38,%39,%40,%41,%42,%43,%44,%45,%46,%47,"
      "%48,%49,%50,%51,%52,%53,%54,%55"
      "}, {%56,%57,%58,%59}, %60, p, 1, 1, 0; }"
    : "+f"(d[0]), "+f"(d[1]), "+f"(d[2]), "+f"(d[3]), "+f"(d[4]), "+f"(d[5]), "+f"(d[6]), "+f"(d[7]),
      "+f"(d[8]), "+f"(d[9]), "+f"(d[10]), "+f"(d[11]), "+f"(d[12]), "+f"(d[13]), "+f"(d[14]), "+f"(d[15]),
      "+f"(d[16]), "+f"(d[17]), "+f"(d[18]), "+f"(d[19]), "+f"(d[20]), "+f"(d[21]), "+f"(d[22]), "+f"(d[23]),
      "+f"(d[24]), "+f"(d[25]), "+f"(d[26]), "+f"(d[27]), "+f"(d[28]), "+f"(d[29]), "+f"(d[30]), "+f"(d[31]),
      "+f"(d[32]), "+f"(d[33]), "+f"(d[34]), "+f"(d[35]), "+f"(d[36]), "+f"(d[37]), "+f"(d[38]), "+f"(d[39]),
      "+f"(d[40]), "+f"(d[41]), "+f"(d[42]), "+f"(d[43]), "+f"(d[44]), "+f"(d[45]), "+f"(d[46]), "+f"(d[47]),
      "+f"(d[48]), "+f"(d[49]), "+f"(d[50]), "+f"(d[51]), "+f"(d[52]), "+f"(d[53]), "+f"(d[54]), "+f"(d[55])
    : "r"(a[0]), "r"(a[1]), "r"(a[2]), "r"(a[3]), "l"(db), "r"(sd));
}

__device__ __forceinline__ void wgmma_rs_n128(float* d, const uint32_t* a, uint64_t db, int sd) {
  asm volatile("{ .reg .pred p; setp.ne.b32 p, %69, 0;\n"
      "wgmma.mma_async.sync.aligned.m64n128k16.f32.bf16.bf16 {"
      "%0,%1,%2,%3,%4,%5,%6,%7,%8,%9,%10,%11,%12,%13,%14,%15,"
      "%16,%17,%18,%19,%20,%21,%22,%23,%24,%25,%26,%27,%28,%29,%30,%31,"
      "%32,%33,%34,%35,%36,%37,%38,%39,%40,%41,%42,%43,%44,%45,%46,%47,"
      "%48,%49,%50,%51,%52,%53,%54,%55,%56,%57,%58,%59,%60,%61,%62,%63"
      "}, {%64,%65,%66,%67}, %68, p, 1, 1, 0; }"
    : "+f"(d[0]), "+f"(d[1]), "+f"(d[2]), "+f"(d[3]), "+f"(d[4]), "+f"(d[5]), "+f"(d[6]), "+f"(d[7]),
      "+f"(d[8]), "+f"(d[9]), "+f"(d[10]), "+f"(d[11]), "+f"(d[12]), "+f"(d[13]), "+f"(d[14]), "+f"(d[15]),
      "+f"(d[16]), "+f"(d[17]), "+f"(d[18]), "+f"(d[19]), "+f"(d[20]), "+f"(d[21]), "+f"(d[22]), "+f"(d[23]),
      "+f"(d[24]), "+f"(d[25]), "+f"(d[26]), "+f"(d[27]), "+f"(d[28]), "+f"(d[29]), "+f"(d[30]), "+f"(d[31]),
      "+f"(d[32]), "+f"(d[33]), "+f"(d[34]), "+f"(d[35]), "+f"(d[36]), "+f"(d[37]), "+f"(d[38]), "+f"(d[39]),
      "+f"(d[40]), "+f"(d[41]), "+f"(d[42]), "+f"(d[43]), "+f"(d[44]), "+f"(d[45]), "+f"(d[46]), "+f"(d[47]),
      "+f"(d[48]), "+f"(d[49]), "+f"(d[50]), "+f"(d[51]), "+f"(d[52]), "+f"(d[53]), "+f"(d[54]), "+f"(d[55]),
      "+f"(d[56]), "+f"(d[57]), "+f"(d[58]), "+f"(d[59]), "+f"(d[60]), "+f"(d[61]), "+f"(d[62]), "+f"(d[63])
    : "r"(a[0]), "r"(a[1]), "r"(a[2]), "r"(a[3]), "l"(db), "r"(sd));
}

__device__ __forceinline__ void wgmma_rs_n144(float* d, const uint32_t* a, uint64_t db, int sd) {
  asm volatile("{ .reg .pred p; setp.ne.b32 p, %77, 0;\n"
      "wgmma.mma_async.sync.aligned.m64n144k16.f32.bf16.bf16 {"
      "%0,%1,%2,%3,%4,%5,%6,%7,%8,%9,%10,%11,%12,%13,%14,%15,"
      "%16,%17,%18,%19,%20,%21,%22,%23,%24,%25,%26,%27,%28,%29,%30,%31,"
      "%32,%33,%34,%35,%36,%37,%38,%39,%40,%41,%42,%43,%44,%45,%46,%47,"
      "%48,%49,%50,%51,%52,%53,%54,%55,%56,%57,%58,%59,%60,%61,%62,%63,"
      "%64,%65,%66,%67,%68,%69,%70,%71"
      "}, {%72,%73,%74,%75}, %76, p, 1, 1, 0; }"
    : "+f"(d[0]), "+f"(d[1]), "+f"(d[2]), "+f"(d[3]), "+f"(d[4]), "+f"(d[5]), "+f"(d[6]), "+f"(d[7]),
      "+f"(d[8]), "+f"(d[9]), "+f"(d[10]), "+f"(d[11]), "+f"(d[12]), "+f"(d[13]), "+f"(d[14]), "+f"(d[15]),
      "+f"(d[16]), "+f"(d[17]), "+f"(d[18]), "+f"(d[19]), "+f"(d[20]), "+f"(d[21]), "+f"(d[22]), "+f"(d[23]),
      "+f"(d[24]), "+f"(d[25]), "+f"(d[26]), "+f"(d[27]), "+f"(d[28]), "+f"(d[29]), "+f"(d[30]), "+f"(d[31]),
      "+f"(d[32]), "+f"(d[33]), "+f"(d[34]), "+f"(d[35]), "+f"(d[36]), "+f"(d[37]), "+f"(d[38]), "+f"(d[39]),
      "+f"(d[40]), "+f"(d[41]), "+f"(d[42]), "+f"(d[43]), "+f"(d[44]), "+f"(d[45]), "+f"(d[46]), "+f"(d[47]),
      "+f"(d[48]), "+f"(d[49]), "+f"(d[50]), "+f"(d[51]), "+f"(d[52]), "+f"(d[53]), "+f"(d[54]), "+f"(d[55]),
      "+f"(d[56]), "+f"(d[57]), "+f"(d[58]), "+f"(d[59]), "+f"(d[60]), "+f"(d[61]), "+f"(d[62]), "+f"(d[63]),
      "+f"(d[64]), "+f"(d[65]), "+f"(d[66]), "+f"(d[67]), "+f"(d[68]), "+f"(d[69]), "+f"(d[70]), "+f"(d[71])
    : "r"(a[0]), "r"(a[1]), "r"(a[2]), "r"(a[3]), "l"(db), "r"(sd));
}

__device__ __forceinline__ void wgmma_rs_n160(float* d, const uint32_t* a, uint64_t db, int sd) {
  asm volatile("{ .reg .pred p; setp.ne.b32 p, %85, 0;\n"
      "wgmma.mma_async.sync.aligned.m64n160k16.f32.bf16.bf16 {"
      "%0,%1,%2,%3,%4,%5,%6,%7,%8,%9,%10,%11,%12,%13,%14,%15,"
      "%16,%17,%18,%19,%20,%21,%22,%23,%24,%25,%26,%27,%28,%29,%30,%31,"
      "%32,%33,%34,%35,%36,%37,%38,%39,%40,%41,%42,%43,%44,%45,%46,%47,"
      "%48,%49,%50,%51,%52,%53,%54,%55,%56,%57,%58,%59,%60,%61,%62,%63,"
      "%64,%65,%66,%67,%68,%69,%70,%71,%72,%73,%74,%75,%76,%77,%78,%79"
      "}, {%80,%81,%82,%83}, %84, p, 1, 1, 0; }"
    : "+f"(d[0]), "+f"(d[1]), "+f"(d[2]), "+f"(d[3]), "+f"(d[4]), "+f"(d[5]), "+f"(d[6]), "+f"(d[7]),
      "+f"(d[8]), "+f"(d[9]), "+f"(d[10]), "+f"(d[11]), "+f"(d[12]), "+f"(d[13]), "+f"(d[14]), "+f"(d[15]),
      "+f"(d[16]), "+f"(d[17]), "+f"(d[18]), "+f"(d[19]), "+f"(d[20]), "+f"(d[21]), "+f"(d[22]), "+f"(d[23]),
      "+f"(d[24]), "+f"(d[25]), "+f"(d[26]), "+f"(d[27]), "+f"(d[28]), "+f"(d[29]), "+f"(d[30]), "+f"(d[31]),
      "+f"(d[32]), "+f"(d[33]), "+f"(d[34]), "+f"(d[35]), "+f"(d[36]), "+f"(d[37]), "+f"(d[38]), "+f"(d[39]),
      "+f"(d[40]), "+f"(d[41]), "+f"(d[42]), "+f"(d[43]), "+f"(d[44]), "+f"(d[45]), "+f"(d[46]), "+f"(d[47]),
      "+f"(d[48]), "+f"(d[49]), "+f"(d[50]), "+f"(d[51]), "+f"(d[52]), "+f"(d[53]), "+f"(d[54]), "+f"(d[55]),
      "+f"(d[56]), "+f"(d[57]), "+f"(d[58]), "+f"(d[59]), "+f"(d[60]), "+f"(d[61]), "+f"(d[62]), "+f"(d[63]),
      "+f"(d[64]), "+f"(d[65]), "+f"(d[66]), "+f"(d[67]), "+f"(d[68]), "+f"(d[69]), "+f"(d[70]), "+f"(d[71]),
      "+f"(d[72]), "+f"(d[73]), "+f"(d[74]), "+f"(d[75]), "+f"(d[76]), "+f"(d[77]), "+f"(d[78]), "+f"(d[79])
    : "r"(a[0]), "r"(a[1]), "r"(a[2]), "r"(a[3]), "l"(db), "r"(sd));
}

__device__ __forceinline__ void wgmma_rs_n176(float* d, const uint32_t* a, uint64_t db, int sd) {
  asm volatile("{ .reg .pred p; setp.ne.b32 p, %93, 0;\n"
      "wgmma.mma_async.sync.aligned.m64n176k16.f32.bf16.bf16 {"
      "%0,%1,%2,%3,%4,%5,%6,%7,%8,%9,%10,%11,%12,%13,%14,%15,"
      "%16,%17,%18,%19,%20,%21,%22,%23,%24,%25,%26,%27,%28,%29,%30,%31,"
      "%32,%33,%34,%35,%36,%37,%38,%39,%40,%41,%42,%43,%44,%45,%46,%47,"
      "%48,%49,%50,%51,%52,%53,%54,%55,%56,%57,%58,%59,%60,%61,%62,%63,"
      "%64,%65,%66,%67,%68,%69,%70,%71,%72,%73,%74,%75,%76,%77,%78,%79,"
      "%80,%81,%82,%83,%84,%85,%86,%87"
      "}, {%88,%89,%90,%91}, %92, p, 1, 1, 0; }"
    : "+f"(d[0]), "+f"(d[1]), "+f"(d[2]), "+f"(d[3]), "+f"(d[4]), "+f"(d[5]), "+f"(d[6]), "+f"(d[7]),
      "+f"(d[8]), "+f"(d[9]), "+f"(d[10]), "+f"(d[11]), "+f"(d[12]), "+f"(d[13]), "+f"(d[14]), "+f"(d[15]),
      "+f"(d[16]), "+f"(d[17]), "+f"(d[18]), "+f"(d[19]), "+f"(d[20]), "+f"(d[21]), "+f"(d[22]), "+f"(d[23]),
      "+f"(d[24]), "+f"(d[25]), "+f"(d[26]), "+f"(d[27]), "+f"(d[28]), "+f"(d[29]), "+f"(d[30]), "+f"(d[31]),
      "+f"(d[32]), "+f"(d[33]), "+f"(d[34]), "+f"(d[35]), "+f"(d[36]), "+f"(d[37]), "+f"(d[38]), "+f"(d[39]),
      "+f"(d[40]), "+f"(d[41]), "+f"(d[42]), "+f"(d[43]), "+f"(d[44]), "+f"(d[45]), "+f"(d[46]), "+f"(d[47]),
      "+f"(d[48]), "+f"(d[49]), "+f"(d[50]), "+f"(d[51]), "+f"(d[52]), "+f"(d[53]), "+f"(d[54]), "+f"(d[55]),
      "+f"(d[56]), "+f"(d[57]), "+f"(d[58]), "+f"(d[59]), "+f"(d[60]), "+f"(d[61]), "+f"(d[62]), "+f"(d[63]),
      "+f"(d[64]), "+f"(d[65]), "+f"(d[66]), "+f"(d[67]), "+f"(d[68]), "+f"(d[69]), "+f"(d[70]), "+f"(d[71]),
      "+f"(d[72]), "+f"(d[73]), "+f"(d[74]), "+f"(d[75]), "+f"(d[76]), "+f"(d[77]), "+f"(d[78]), "+f"(d[79]),
      "+f"(d[80]), "+f"(d[81]), "+f"(d[82]), "+f"(d[83]), "+f"(d[84]), "+f"(d[85]), "+f"(d[86]), "+f"(d[87])
    : "r"(a[0]), "r"(a[1]), "r"(a[2]), "r"(a[3]), "l"(db), "r"(sd));
}

__device__ __forceinline__ void wgmma_rs_n192(float* d, const uint32_t* a, uint64_t db, int sd) {
  asm volatile("{ .reg .pred p; setp.ne.b32 p, %101, 0;\n"
      "wgmma.mma_async.sync.aligned.m64n192k16.f32.bf16.bf16 {"
      "%0,%1,%2,%3,%4,%5,%6,%7,%8,%9,%10,%11,%12,%13,%14,%15,"
      "%16,%17,%18,%19,%20,%21,%22,%23,%24,%25,%26,%27,%28,%29,%30,%31,"
      "%32,%33,%34,%35,%36,%37,%38,%39,%40,%41,%42,%43,%44,%45,%46,%47,"
      "%48,%49,%50,%51,%52,%53,%54,%55,%56,%57,%58,%59,%60,%61,%62,%63,"
      "%64,%65,%66,%67,%68,%69,%70,%71,%72,%73,%74,%75,%76,%77,%78,%79,"
      "%80,%81,%82,%83,%84,%85,%86,%87,%88,%89,%90,%91,%92,%93,%94,%95"
      "}, {%96,%97,%98,%99}, %100, p, 1, 1, 0; }"
    : "+f"(d[0]), "+f"(d[1]), "+f"(d[2]), "+f"(d[3]), "+f"(d[4]), "+f"(d[5]), "+f"(d[6]), "+f"(d[7]),
      "+f"(d[8]), "+f"(d[9]), "+f"(d[10]), "+f"(d[11]), "+f"(d[12]), "+f"(d[13]), "+f"(d[14]), "+f"(d[15]),
      "+f"(d[16]), "+f"(d[17]), "+f"(d[18]), "+f"(d[19]), "+f"(d[20]), "+f"(d[21]), "+f"(d[22]), "+f"(d[23]),
      "+f"(d[24]), "+f"(d[25]), "+f"(d[26]), "+f"(d[27]), "+f"(d[28]), "+f"(d[29]), "+f"(d[30]), "+f"(d[31]),
      "+f"(d[32]), "+f"(d[33]), "+f"(d[34]), "+f"(d[35]), "+f"(d[36]), "+f"(d[37]), "+f"(d[38]), "+f"(d[39]),
      "+f"(d[40]), "+f"(d[41]), "+f"(d[42]), "+f"(d[43]), "+f"(d[44]), "+f"(d[45]), "+f"(d[46]), "+f"(d[47]),
      "+f"(d[48]), "+f"(d[49]), "+f"(d[50]), "+f"(d[51]), "+f"(d[52]), "+f"(d[53]), "+f"(d[54]), "+f"(d[55]),
      "+f"(d[56]), "+f"(d[57]), "+f"(d[58]), "+f"(d[59]), "+f"(d[60]), "+f"(d[61]), "+f"(d[62]), "+f"(d[63]),
      "+f"(d[64]), "+f"(d[65]), "+f"(d[66]), "+f"(d[67]), "+f"(d[68]), "+f"(d[69]), "+f"(d[70]), "+f"(d[71]),
      "+f"(d[72]), "+f"(d[73]), "+f"(d[74]), "+f"(d[75]), "+f"(d[76]), "+f"(d[77]), "+f"(d[78]), "+f"(d[79]),
      "+f"(d[80]), "+f"(d[81]), "+f"(d[82]), "+f"(d[83]), "+f"(d[84]), "+f"(d[85]), "+f"(d[86]), "+f"(d[87]),
      "+f"(d[88]), "+f"(d[89]), "+f"(d[90]), "+f"(d[91]), "+f"(d[92]), "+f"(d[93]), "+f"(d[94]), "+f"(d[95])
    : "r"(a[0]), "r"(a[1]), "r"(a[2]), "r"(a[3]), "l"(db), "r"(sd));
}

__device__ __forceinline__ void wgmma_rs_n208(float* d, const uint32_t* a, uint64_t db, int sd) {
  asm volatile("{ .reg .pred p; setp.ne.b32 p, %109, 0;\n"
      "wgmma.mma_async.sync.aligned.m64n208k16.f32.bf16.bf16 {"
      "%0,%1,%2,%3,%4,%5,%6,%7,%8,%9,%10,%11,%12,%13,%14,%15,"
      "%16,%17,%18,%19,%20,%21,%22,%23,%24,%25,%26,%27,%28,%29,%30,%31,"
      "%32,%33,%34,%35,%36,%37,%38,%39,%40,%41,%42,%43,%44,%45,%46,%47,"
      "%48,%49,%50,%51,%52,%53,%54,%55,%56,%57,%58,%59,%60,%61,%62,%63,"
      "%64,%65,%66,%67,%68,%69,%70,%71,%72,%73,%74,%75,%76,%77,%78,%79,"
      "%80,%81,%82,%83,%84,%85,%86,%87,%88,%89,%90,%91,%92,%93,%94,%95,"
      "%96,%97,%98,%99,%100,%101,%102,%103"
      "}, {%104,%105,%106,%107}, %108, p, 1, 1, 0; }"
    : "+f"(d[0]), "+f"(d[1]), "+f"(d[2]), "+f"(d[3]), "+f"(d[4]), "+f"(d[5]), "+f"(d[6]), "+f"(d[7]),
      "+f"(d[8]), "+f"(d[9]), "+f"(d[10]), "+f"(d[11]), "+f"(d[12]), "+f"(d[13]), "+f"(d[14]), "+f"(d[15]),
      "+f"(d[16]), "+f"(d[17]), "+f"(d[18]), "+f"(d[19]), "+f"(d[20]), "+f"(d[21]), "+f"(d[22]), "+f"(d[23]),
      "+f"(d[24]), "+f"(d[25]), "+f"(d[26]), "+f"(d[27]), "+f"(d[28]), "+f"(d[29]), "+f"(d[30]), "+f"(d[31]),
      "+f"(d[32]), "+f"(d[33]), "+f"(d[34]), "+f"(d[35]), "+f"(d[36]), "+f"(d[37]), "+f"(d[38]), "+f"(d[39]),
      "+f"(d[40]), "+f"(d[41]), "+f"(d[42]), "+f"(d[43]), "+f"(d[44]), "+f"(d[45]), "+f"(d[46]), "+f"(d[47]),
      "+f"(d[48]), "+f"(d[49]), "+f"(d[50]), "+f"(d[51]), "+f"(d[52]), "+f"(d[53]), "+f"(d[54]), "+f"(d[55]),
      "+f"(d[56]), "+f"(d[57]), "+f"(d[58]), "+f"(d[59]), "+f"(d[60]), "+f"(d[61]), "+f"(d[62]), "+f"(d[63]),
      "+f"(d[64]), "+f"(d[65]), "+f"(d[66]), "+f"(d[67]), "+f"(d[68]), "+f"(d[69]), "+f"(d[70]), "+f"(d[71]),
      "+f"(d[72]), "+f"(d[73]), "+f"(d[74]), "+f"(d[75]), "+f"(d[76]), "+f"(d[77]), "+f"(d[78]), "+f"(d[79]),
      "+f"(d[80]), "+f"(d[81]), "+f"(d[82]), "+f"(d[83]), "+f"(d[84]), "+f"(d[85]), "+f"(d[86]), "+f"(d[87]),
      "+f"(d[88]), "+f"(d[89]), "+f"(d[90]), "+f"(d[91]), "+f"(d[92]), "+f"(d[93]), "+f"(d[94]), "+f"(d[95]),
      "+f"(d[96]), "+f"(d[97]), "+f"(d[98]), "+f"(d[99]), "+f"(d[100]), "+f"(d[101]), "+f"(d[102]), "+f"(d[103])
    : "r"(a[0]), "r"(a[1]), "r"(a[2]), "r"(a[3]), "l"(db), "r"(sd));
}

__device__ __forceinline__ void wgmma_rs_n224(float* d, const uint32_t* a, uint64_t db, int sd) {
  asm volatile("{ .reg .pred p; setp.ne.b32 p, %117, 0;\n"
      "wgmma.mma_async.sync.aligned.m64n224k16.f32.bf16.bf16 {"
      "%0,%1,%2,%3,%4,%5,%6,%7,%8,%9,%10,%11,%12,%13,%14,%15,"
      "%16,%17,%18,%19,%20,%21,%22,%23,%24,%25,%26,%27,%28,%29,%30,%31,"
      "%32,%33,%34,%35,%36,%37,%38,%39,%40,%41,%42,%43,%44,%45,%46,%47,"
      "%48,%49,%50,%51,%52,%53,%54,%55,%56,%57,%58,%59,%60,%61,%62,%63,"
      "%64,%65,%66,%67,%68,%69,%70,%71,%72,%73,%74,%75,%76,%77,%78,%79,"
      "%80,%81,%82,%83,%84,%85,%86,%87,%88,%89,%90,%91,%92,%93,%94,%95,"
      "%96,%97,%98,%99,%100,%101,%102,%103,%104,%105,%106,%107,%108,%109,%110,%111"
      "}, {%112,%113,%114,%115}, %116, p, 1, 1, 0; }"
    : "+f"(d[0]), "+f"(d[1]), "+f"(d[2]), "+f"(d[3]), "+f"(d[4]), "+f"(d[5]), "+f"(d[6]), "+f"(d[7]),
      "+f"(d[8]), "+f"(d[9]), "+f"(d[10]), "+f"(d[11]), "+f"(d[12]), "+f"(d[13]), "+f"(d[14]), "+f"(d[15]),
      "+f"(d[16]), "+f"(d[17]), "+f"(d[18]), "+f"(d[19]), "+f"(d[20]), "+f"(d[21]), "+f"(d[22]), "+f"(d[23]),
      "+f"(d[24]), "+f"(d[25]), "+f"(d[26]), "+f"(d[27]), "+f"(d[28]), "+f"(d[29]), "+f"(d[30]), "+f"(d[31]),
      "+f"(d[32]), "+f"(d[33]), "+f"(d[34]), "+f"(d[35]), "+f"(d[36]), "+f"(d[37]), "+f"(d[38]), "+f"(d[39]),
      "+f"(d[40]), "+f"(d[41]), "+f"(d[42]), "+f"(d[43]), "+f"(d[44]), "+f"(d[45]), "+f"(d[46]), "+f"(d[47]),
      "+f"(d[48]), "+f"(d[49]), "+f"(d[50]), "+f"(d[51]), "+f"(d[52]), "+f"(d[53]), "+f"(d[54]), "+f"(d[55]),
      "+f"(d[56]), "+f"(d[57]), "+f"(d[58]), "+f"(d[59]), "+f"(d[60]), "+f"(d[61]), "+f"(d[62]), "+f"(d[63]),
      "+f"(d[64]), "+f"(d[65]), "+f"(d[66]), "+f"(d[67]), "+f"(d[68]), "+f"(d[69]), "+f"(d[70]), "+f"(d[71]),
      "+f"(d[72]), "+f"(d[73]), "+f"(d[74]), "+f"(d[75]), "+f"(d[76]), "+f"(d[77]), "+f"(d[78]), "+f"(d[79]),
      "+f"(d[80]), "+f"(d[81]), "+f"(d[82]), "+f"(d[83]), "+f"(d[84]), "+f"(d[85]), "+f"(d[86]), "+f"(d[87]),
      "+f"(d[88]), "+f"(d[89]), "+f"(d[90]), "+f"(d[91]), "+f"(d[92]), "+f"(d[93]), "+f"(d[94]), "+f"(d[95]),
      "+f"(d[96]), "+f"(d[97]), "+f"(d[98]), "+f"(d[99]), "+f"(d[100]), "+f"(d[101]), "+f"(d[102]), "+f"(d[103]),
      "+f"(d[104]), "+f"(d[105]), "+f"(d[106]), "+f"(d[107]), "+f"(d[108]), "+f"(d[109]), "+f"(d[110]), "+f"(d[111])
    : "r"(a[0]), "r"(a[1]), "r"(a[2]), "r"(a[3]), "l"(db), "r"(sd));
}

__device__ __forceinline__ void wgmma_rs_n240(float* d, const uint32_t* a, uint64_t db, int sd) {
  asm volatile("{ .reg .pred p; setp.ne.b32 p, %125, 0;\n"
      "wgmma.mma_async.sync.aligned.m64n240k16.f32.bf16.bf16 {"
      "%0,%1,%2,%3,%4,%5,%6,%7,%8,%9,%10,%11,%12,%13,%14,%15,"
      "%16,%17,%18,%19,%20,%21,%22,%23,%24,%25,%26,%27,%28,%29,%30,%31,"
      "%32,%33,%34,%35,%36,%37,%38,%39,%40,%41,%42,%43,%44,%45,%46,%47,"
      "%48,%49,%50,%51,%52,%53,%54,%55,%56,%57,%58,%59,%60,%61,%62,%63,"
      "%64,%65,%66,%67,%68,%69,%70,%71,%72,%73,%74,%75,%76,%77,%78,%79,"
      "%80,%81,%82,%83,%84,%85,%86,%87,%88,%89,%90,%91,%92,%93,%94,%95,"
      "%96,%97,%98,%99,%100,%101,%102,%103,%104,%105,%106,%107,%108,%109,%110,%111,"
      "%112,%113,%114,%115,%116,%117,%118,%119"
      "}, {%120,%121,%122,%123}, %124, p, 1, 1, 0; }"
    : "+f"(d[0]), "+f"(d[1]), "+f"(d[2]), "+f"(d[3]), "+f"(d[4]), "+f"(d[5]), "+f"(d[6]), "+f"(d[7]),
      "+f"(d[8]), "+f"(d[9]), "+f"(d[10]), "+f"(d[11]), "+f"(d[12]), "+f"(d[13]), "+f"(d[14]), "+f"(d[15]),
      "+f"(d[16]), "+f"(d[17]), "+f"(d[18]), "+f"(d[19]), "+f"(d[20]), "+f"(d[21]), "+f"(d[22]), "+f"(d[23]),
      "+f"(d[24]), "+f"(d[25]), "+f"(d[26]), "+f"(d[27]), "+f"(d[28]), "+f"(d[29]), "+f"(d[30]), "+f"(d[31]),
      "+f"(d[32]), "+f"(d[33]), "+f"(d[34]), "+f"(d[35]), "+f"(d[36]), "+f"(d[37]), "+f"(d[38]), "+f"(d[39]),
      "+f"(d[40]), "+f"(d[41]), "+f"(d[42]), "+f"(d[43]), "+f"(d[44]), "+f"(d[45]), "+f"(d[46]), "+f"(d[47]),
      "+f"(d[48]), "+f"(d[49]), "+f"(d[50]), "+f"(d[51]), "+f"(d[52]), "+f"(d[53]), "+f"(d[54]), "+f"(d[55]),
      "+f"(d[56]), "+f"(d[57]), "+f"(d[58]), "+f"(d[59]), "+f"(d[60]), "+f"(d[61]), "+f"(d[62]), "+f"(d[63]),
      "+f"(d[64]), "+f"(d[65]), "+f"(d[66]), "+f"(d[67]), "+f"(d[68]), "+f"(d[69]), "+f"(d[70]), "+f"(d[71]),
      "+f"(d[72]), "+f"(d[73]), "+f"(d[74]), "+f"(d[75]), "+f"(d[76]), "+f"(d[77]), "+f"(d[78]), "+f"(d[79]),
      "+f"(d[80]), "+f"(d[81]), "+f"(d[82]), "+f"(d[83]), "+f"(d[84]), "+f"(d[85]), "+f"(d[86]), "+f"(d[87]),
      "+f"(d[88]), "+f"(d[89]), "+f"(d[90]), "+f"(d[91]), "+f"(d[92]), "+f"(d[93]), "+f"(d[94]), "+f"(d[95]),
      "+f"(d[96]), "+f"(d[97]), "+f"(d[98]), "+f"(d[99]), "+f"(d[100]), "+f"(d[101]), "+f"(d[102]), "+f"(d[103]),
      "+f"(d[104]), "+f"(d[105]), "+f"(d[106]), "+f"(d[107]), "+f"(d[108]), "+f"(d[109]), "+f"(d[110]), "+f"(d[111]),
      "+f"(d[112]), "+f"(d[113]), "+f"(d[114]), "+f"(d[115]), "+f"(d[116]), "+f"(d[117]), "+f"(d[118]), "+f"(d[119])
    : "r"(a[0]), "r"(a[1]), "r"(a[2]), "r"(a[3]), "l"(db), "r"(sd));
}

__device__ __forceinline__ void wgmma_rs_n256(float* d, const uint32_t* a, uint64_t db, int sd) {
  asm volatile("{ .reg .pred p; setp.ne.b32 p, %133, 0;\n"
      "wgmma.mma_async.sync.aligned.m64n256k16.f32.bf16.bf16 {"
      "%0,%1,%2,%3,%4,%5,%6,%7,%8,%9,%10,%11,%12,%13,%14,%15,"
      "%16,%17,%18,%19,%20,%21,%22,%23,%24,%25,%26,%27,%28,%29,%30,%31,"
      "%32,%33,%34,%35,%36,%37,%38,%39,%40,%41,%42,%43,%44,%45,%46,%47,"
      "%48,%49,%50,%51,%52,%53,%54,%55,%56,%57,%58,%59,%60,%61,%62,%63,"
      "%64,%65,%66,%67,%68,%69,%70,%71,%72,%73,%74,%75,%76,%77,%78,%79,"
      "%80,%81,%82,%83,%84,%85,%86,%87,%88,%89,%90,%91,%92,%93,%94,%95,"
      "%96,%97,%98,%99,%100,%101,%102,%103,%104,%105,%106,%107,%108,%109,%110,%111,"
      "%112,%113,%114,%115,%116,%117,%118,%119,%120,%121,%122,%123,%124,%125,%126,%127"
      "}, {%128,%129,%130,%131}, %132, p, 1, 1, 0; }"
    : "+f"(d[0]), "+f"(d[1]), "+f"(d[2]), "+f"(d[3]), "+f"(d[4]), "+f"(d[5]), "+f"(d[6]), "+f"(d[7]),
      "+f"(d[8]), "+f"(d[9]), "+f"(d[10]), "+f"(d[11]), "+f"(d[12]), "+f"(d[13]), "+f"(d[14]), "+f"(d[15]),
      "+f"(d[16]), "+f"(d[17]), "+f"(d[18]), "+f"(d[19]), "+f"(d[20]), "+f"(d[21]), "+f"(d[22]), "+f"(d[23]),
      "+f"(d[24]), "+f"(d[25]), "+f"(d[26]), "+f"(d[27]), "+f"(d[28]), "+f"(d[29]), "+f"(d[30]), "+f"(d[31]),
      "+f"(d[32]), "+f"(d[33]), "+f"(d[34]), "+f"(d[35]), "+f"(d[36]), "+f"(d[37]), "+f"(d[38]), "+f"(d[39]),
      "+f"(d[40]), "+f"(d[41]), "+f"(d[42]), "+f"(d[43]), "+f"(d[44]), "+f"(d[45]), "+f"(d[46]), "+f"(d[47]),
      "+f"(d[48]), "+f"(d[49]), "+f"(d[50]), "+f"(d[51]), "+f"(d[52]), "+f"(d[53]), "+f"(d[54]), "+f"(d[55]),
      "+f"(d[56]), "+f"(d[57]), "+f"(d[58]), "+f"(d[59]), "+f"(d[60]), "+f"(d[61]), "+f"(d[62]), "+f"(d[63]),
      "+f"(d[64]), "+f"(d[65]), "+f"(d[66]), "+f"(d[67]), "+f"(d[68]), "+f"(d[69]), "+f"(d[70]), "+f"(d[71]),
      "+f"(d[72]), "+f"(d[73]), "+f"(d[74]), "+f"(d[75]), "+f"(d[76]), "+f"(d[77]), "+f"(d[78]), "+f"(d[79]),
      "+f"(d[80]), "+f"(d[81]), "+f"(d[82]), "+f"(d[83]), "+f"(d[84]), "+f"(d[85]), "+f"(d[86]), "+f"(d[87]),
      "+f"(d[88]), "+f"(d[89]), "+f"(d[90]), "+f"(d[91]), "+f"(d[92]), "+f"(d[93]), "+f"(d[94]), "+f"(d[95]),
      "+f"(d[96]), "+f"(d[97]), "+f"(d[98]), "+f"(d[99]), "+f"(d[100]), "+f"(d[101]), "+f"(d[102]), "+f"(d[103]),
      "+f"(d[104]), "+f"(d[105]), "+f"(d[106]), "+f"(d[107]), "+f"(d[108]), "+f"(d[109]), "+f"(d[110]), "+f"(d[111]),
      "+f"(d[112]), "+f"(d[113]), "+f"(d[114]), "+f"(d[115]), "+f"(d[116]), "+f"(d[117]), "+f"(d[118]), "+f"(d[119]),
      "+f"(d[120]), "+f"(d[121]), "+f"(d[122]), "+f"(d[123]), "+f"(d[124]), "+f"(d[125]), "+f"(d[126]), "+f"(d[127])
    : "r"(a[0]), "r"(a[1]), "r"(a[2]), "r"(a[3]), "l"(db), "r"(sd));
}

__device__ __forceinline__ void ln_finish(float mean, float var, float& mb, float& rinv) {
  mb = round_bf16(mean);
  float den = round_bf16(sqrtf(round_bf16(round_bf16(var) + 1e-5f)));
  rinv = 1.0f / den;
}
__device__ __forceinline__ uint32_t ln_apply(uint32_t x2, uint32_t mb2, float rinv) {
  uint32_t c = bsub2(x2, mb2);
  return pack_bf16(bf_lo(c) * rinv, bf_hi(c) * rinv);
}
__device__ __forceinline__ void row_stats(const uint32_t* r, float& mean, float& var) {
  float s0 = 0.f, s1 = 0.f;
#pragma unroll
  for (int i = 0; i < 18; i++) { s0 += bf_lo(r[i]); s1 += bf_hi(r[i]); }
  float m = (s0 + s1) * (1.0f / 36.0f);
  float q0 = 0.f, q1 = 0.f;
#pragma unroll
  for (int i = 0; i < 18; i++) { float a = bf_lo(r[i]) - m, b = bf_hi(r[i]) - m; q0 = fmaf(a, a, q0); q1 = fmaf(b, b, q1); }
  float q = q0 + q1, n2 = 18.f;
#pragma unroll
  for (int o = 1; o < 16; o <<= 1) {
    float mo = __shfl_xor_sync(0xffffffffu, m, o), qo = __shfl_xor_sync(0xffffffffu, q, o);
    float dl = m - mo;
    q = fmaf(dl * dl, n2, q + qo);
    m = 0.5f * (m + mo);
    n2 *= 2.f;
  }
  mean = m; var = q * (1.0f / 576.0f);
}

__device__ __forceinline__ int conv_channel(int cta, int i) {
  return i < N_SHORT ? i * N_CONV_CTA + cta : N_SHORT * N_CONV_CTA + (i - N_SHORT) * 4 + cta;
}

__global__ void __cluster_dims__(2, 1, 1) __launch_bounds__(384, 1) fused_kernel(const __grid_constant__ Params P) {
  extern __shared__ uint8_t smem_raw[];
  const uint32_t sb = (smem_u32(smem_raw) + 1023) & ~1023u;
  const uint32_t bars = sb + SM_BAR;
  const int tid = threadIdx.x, warp = tid >> 5, lane = tid & 31;
  const int cl = blockIdx.x >> 1, rank = blockIdx.x & 1;
  const int g1m = P.roles.g1m[cl], g1n = P.roles.g1n[cl], cv = P.roles.cv[cl], g2m = P.roles.g2m[cl], g2n = P.roles.g2n[cl], p0 = P.roles.p0[cl];
  const int p0b = 2 * p0 + rank, cvc = 2 * cv + rank;
  const int n_conv = cv < 0 ? 0 : (cv < 2 ? N_SHORT + N_LONG_EXTRA : N_SHORT);
  const uint32_t tag = ld_flag(&g_epoch) + 1;
  if (tid == 0) TLREC(0);

  uint32_t xr[18];
  const int ln_row = p0b * 16 + warp * 2 + (lane >> 4);
  if (warp < 8 && p0 >= 0) {
    const uint2* src = reinterpret_cast<const uint2*>(P.x + (size_t)ln_row * D_) + (lane & 15);
#pragma unroll
    for (int j = 0; j < 9; j++) asm volatile("ld.global.nc.v2.u32 {%0,%1}, [%2];" : "=r"(xr[2 * j]), "=r"(xr[2 * j + 1]) : "l"(src + 16 * j));
  }
  if (tid == 256) {
    for (int s = 0; s < NSTAGE; s++) { mbar_init(bars + 8 * (B_FULL + s), 1); mbar_init(bars + 8 * (B_EMPTY + s), 2); }
    for (int s = 0; s < CV_NSLOT; s++) { mbar_init(bars + 8 * (B_CFULL + s), 1); mbar_init(bars + 8 * (B_CEMPTY + s), 1); }
    mbar_init(bars + 8 * B_CDONE, 2); mbar_init(bars + 8 * B_XRDY, 1); mbar_init(bars + 8 * B_XFULL, 1);
    asm volatile("fence.mbarrier_init.release.cluster;" ::: "memory");
  }
  __syncthreads();
  asm volatile("barrier.cluster.arrive.relaxed.aligned;" ::: "memory");

  if (warp >= 8) {
    asm volatile("setmaxnreg.dec.sync.aligned.u32 56;");
    if (warp == 8) {
      int it = 0;
      if (g1m >= 0) {
        const int fg = (2 * g1m + rank) * 2, dg = g1n * 3;
        if (lane == 0) {
          for (int s = 0; s < NSTAGE; s++) {
            mbar_expect_tx(bars + 8 * (B_FULL + s), G1_BYTES);
            tma3d(sb + s * SLOT, &P.m_w1, 0, s * 64, fg, bars + 8 * (B_FULL + s));
          }
        }
        uint32_t c = 0;
        while (true) {
          uint4 f = ld_flag4(g_hflag + 4 * lane);
          if (__all_sync(0xffffffffu, f.x == tag && f.y == tag && f.z == tag && f.w == tag)) break;
          spin_guard(c);
        }
        if (lane == 0) {
          TLREC(2);
          fence_gpu(); fence_async_global();
          for (int s = 0; s < NSTAGE; s++) tma3d(sb + s * SLOT + 16384, &P.m_h, 0, s * 64, dg, bars + 8 * (B_FULL + s));
          for (int kb = NSTAGE; kb < G1_KB; kb++) {
            const int s = kb % NSTAGE;
            mbar_wait(bars + 8 * (B_EMPTY + s), ((kb / NSTAGE) - 1) & 1);
            mbar_expect_tx(bars + 8 * (B_FULL + s), G1_BYTES);
            tma3d(sb + s * SLOT, &P.m_w1, 0, kb * 64, fg, bars + 8 * (B_FULL + s));
            tma3d(sb + s * SLOT + 16384, &P.m_h, 0, kb * 64, dg, bars + 8 * (B_FULL + s));
          }
        }
        it = G1_KB;
      } else {
        int ready = -1;
        for (int i = 0; i < n_conv; i++) {
          const int ch = conv_channel(cvc, i), s = i % CV_NSLOT;
          const uint32_t slot = sb + CV_BASE + s * CV_SLOT, fb = bars + 8 * (B_CFULL + s);
          if (lane == 0) {
            if (i >= CV_NSLOT) mbar_wait(bars + 8 * (B_CEMPTY + s), ((i / CV_NSLOT) - 1) & 1);
            mbar_expect_tx(fb, 8192 + 4096);
            bulk_load(slot + CV_KOFF + 32, P.ssm_k + (size_t)ch * S_, 4096, fb);
          }
          const int r = ch / 96;
          if (r > ready) {
            uint32_t c = 0;
            while (true) {
              uint4 f = ld_flag4(g_kvflag + r * 128 + 4 * lane);
              if (__all_sync(0xffffffffu, f.x == tag && f.y == tag && f.z == tag && f.w == tag)) break;
              spin_guard(c);
            }
            ready = r;
            if (lane == 0) { TLREC(12 + r); fence_gpu(); fence_async_global(); }
          }
          if (lane == 0) bulk_load(slot, g_ub + (size_t)ch * 4096, 8192, fb);
          __syncwarp();
        }
      }
      __syncwarp();
      asm volatile("barrier.cluster.wait.aligned;" ::: "memory");
      if (g2m >= 0) {
        const int sg = g2m * 2, k0 = rank * G2_KB * 64;
        const int dk = g2n * 144 + rank * 72, ds = g2n * 144 + (rank ^ 1) * 72;
        const int npre = g1m >= 0 ? 3 : 2;
        if (lane == 0) {
          for (int kb = 0; kb < npre; kb++) {
            const int p = it + kb, s = p % NSTAGE;
            if (p >= NSTAGE) mbar_wait(bars + 8 * (B_EMPTY + s), ((p / NSTAGE) - 1) & 1);
            mbar_expect_tx(bars + 8 * (B_FULL + s), G2_BYTES);
            tma3d(sb + s * SLOT, &P.m_w2, 0, k0 + kb * 64, sg, bars + 8 * (B_FULL + s));
          }
        }
        __syncwarp();
        {
          const int dt0 = (g2n * 144) / 192, dt1 = (g2n * 144 + 143) / 192;
          const uint32_t* fp = g_uflag + ((lane < 9) ? dt0 : dt1) * 96 + rank * G2_KB + 4 * (lane % 9);
          uint32_t c = 0;
          while (true) {
            bool ok = true;
            if (lane < 18) { uint4 f = ld_flag4(fp); ok = f.x == tag && f.y == tag && f.z == tag && f.w == tag; }
            if (__all_sync(0xffffffffu, ok)) break;
            spin_guard(c);
          }
        }
        if (lane == 0) {
          TLREC(6);
          fence_gpu(); fence_async_global();
          for (int kb = 0; kb < G2_KB; kb++) {
            const int p = it + kb, s = p % NSTAGE;
            const uint32_t fb = bars + 8 * (B_FULL + s);
            if (kb >= npre) {
              if (p >= NSTAGE) mbar_wait(bars + 8 * (B_EMPTY + s), ((p / NSTAGE) - 1) & 1);
              else if (kb == npre) { mbar_wait(bars + 8 * B_CDONE, 0); fence_async_smem(); }
              mbar_expect_tx(fb, G2_BYTES);
              tma3d(sb + s * SLOT, &P.m_w2, 0, k0 + kb * 64, sg, fb);
            }
            tma2d(sb + s * SLOT + 16384, &P.m_uld, k0 + kb * 64, dk, fb);
            tma2d(sb + s * SLOT + 16384 + 9216, &P.m_uld, k0 + kb * 64, ds, fb);
          }
          const int p = it + G2_KB, s = p % NSTAGE;
          mbar_wait(bars + 8 * (B_EMPTY + s), ((p / NSTAGE) - 1) & 1);
          mbar_expect_tx(bars + 8 * B_XFULL, 36 * 256 * 4);
          mbar_arrive_remote(mapa(bars + 8 * B_XRDY, rank ^ 1));
        }
      }
    } else {
      if (p0 >= 0) {
        const int hf = (tid - 288) / 48, pr = (tid - 288) % 48;
        const int s0 = p0b * 16 + hf * 8;
        const bool first = s0 == 0;
        for (int r = 0; r < KV_ROUNDS; r++) {
          const int d = r * 96 + 2 * pr;
          const __nv_bfloat16* kp = P.k + (ptrdiff_t)(s0 - 4) * D_ + d;
          const __nv_bfloat16* vp = P.v + (ptrdiff_t)(s0 - 1) * D_ + d;
          uint32_t kk[12], vv[9];
#pragma unroll
          for (int j = 0; j < 12; j++) kk[j] = (j < 4 && first) ? 0u : ldg32(kp + j * D_);
#pragma unroll
          for (int j = 0; j < 9; j++) vv[j] = (j < 1 && first) ? 0u : ldg32(vp + j * D_);
          const uint4 w = __ldg(reinterpret_cast<const uint4*>(P.shift_k + d * 4));
          const uint32_t dd = ldg32(P.ssm_D + d);
          const uint32_t w0 = __byte_perm(w.x, w.z, 0x5410), w1 = __byte_perm(w.x, w.z, 0x7632);
          const uint32_t w2 = __byte_perm(w.y, w.w, 0x5410), w3 = __byte_perm(w.y, w.w, 0x7632);
#pragma unroll
          for (int j = 0; j < 9; j++) {
            uint32_t a = bmul2(kk[j], w3);
            a = badd2(a, bmul2(kk[j + 1], w2));
            a = badd2(a, bmul2(kk[j + 2], w1));
            a = badd2(a, bmul2(kk[j + 3], w0));
            vv[j] = bmul2(a, vv[j]);
          }
#pragma unroll
          for (int c = 0; c < 2; c++) {
            const uint32_t sel = c ? 0x7632 : 0x5410;
            uint4* dst = reinterpret_cast<uint4*>(g_ub + (size_t)(d + c) * 4096) + (1 - hf) * 256 + 2 * (127 - p0b);
#pragma unroll
            for (int pi = 0; pi < 2; pi++)
              dst[pi] = make_uint4(__byte_perm(vv[7 + pi], vv[6 + pi], sel), __byte_perm(vv[5 + pi], vv[4 + pi], sel),
                                   __byte_perm(vv[3 + pi], vv[2 + pi], sel), __byte_perm(vv[1 + pi], vv[pi], sel));
          }
#pragma unroll
          for (int j = 0; j < 8; j++) *reinterpret_cast<uint32_t*>(g_p2 + (size_t)(s0 + j) * D_ + d) = bmul2(vv[j + 1], dd);
          bar_sync(1, 96);
          if (tid == 288) { fence_async_global(); fence_gpu(); st_flag(g_kvflag + r * 128 + p0b, tag); TLREC(22 + r); }
        }
      }
      __syncwarp();
      asm volatile("barrier.cluster.wait.aligned;" ::: "memory");
    }
  } else {
    asm volatile("setmaxnreg.inc.sync.aligned.u32 224;");
    const int wg = warp >> 2, w = warp & 3, g = lane >> 2, t = lane & 3, wtid = tid & 127;
    if (p0 >= 0) {
      float mean, var, mb, rinv;
      row_stats(xr, mean, var);
      ln_finish(mean, var, mb, rinv);
      if ((lane & 15) == 0) g_stats[ln_row] = make_float2(mb, rinv);
      uint32_t mb2 = pack_bf16(mb, mb);
#pragma unroll
      for (int i = 0; i < 18; i++) xr[i] = ln_apply(xr[i], mb2, rinv);
      row_stats(xr, mean, var);
      ln_finish(mean, var, mb, rinv);
      mb2 = pack_bf16(mb, mb);
      uint2* dst = reinterpret_cast<uint2*>(g_h + (size_t)ln_row * D_) + (lane & 15);
#pragma unroll
      for (int j = 0; j < 9; j++) dst[16 * j] = make_uint2(ln_apply(xr[2 * j], mb2, rinv), ln_apply(xr[2 * j + 1], mb2, rinv));
      bar_sync(2, 256);
      if (tid == 0) { fence_async_global(); fence_gpu(); st_flag(g_hflag + p0b, tag); TLREC(1); }
    }
    __syncwarp();
    asm volatile("barrier.cluster.wait.aligned;" ::: "memory");
    int it = 0;
    if (g1m >= 0) {
      const int fb64 = (2 * g1m + rank) * 2 + wg;
      const int frow = fb64 * 64 + w * 16 + g;
      const uint32_t bias0 = __byte_perm((uint32_t)__bfloat16_as_ushort(P.b1[frow]), 0, 0x1010);
      const uint32_t bias1 = __byte_perm((uint32_t)__bfloat16_as_ushort(P.b1[frow + 8]), 0, 0x1010);
      float acc[96];
      for (int kb = 0; kb < G1_KB; kb++) {
        const int s = kb % NSTAGE;
        mbar_wait(bars + 8 * (B_FULL + s), (kb / NSTAGE) & 1);
        if (kb == 0 && tid == 0) TLREC(3);
        const uint64_t da = make_desc(sb + s * SLOT + wg * 8192, 8192, 1024, 1), db = make_desc(sb + s * SLOT + 16384, 8192, 1024, 1);
        wg_fence();
#pragma unroll
        for (int k = 0; k < 4; k++) wgmma_ss_n192_t11(acc, da + k * 128, db + k * 128, (kb | k) != 0);
        wg_commit();
        wg_wait<1>();
        if (kb > 0 && kb < G1_KB - 1 && wtid == 0) mbar_arrive(bars + 8 * (B_EMPTY + (kb - 1) % NSTAGE));
      }
      wg_wait<0>();
      pin_regs<96>(acc);
      if (tid == 0) TLREC(4);
      const int sst = (G1_KB - 2 + wg) % NSTAGE;
      const uint32_t stg = sb + sst * SLOT;
      const uint32_t sa = stg + ((lane >> 4) * 8 + (lane & 7)) * 128 + (((2 * w + ((lane >> 3) & 1)) ^ (lane & 7)) << 4);
      uint32_t pk[48];
#pragma unroll
      for (int i = 0; i < 48; i++) {
        uint32_t p = badd2(pack_bf16(acc[2 * i], acc[2 * i + 1]), (i & 1) ? bias1 : bias0);
        pk[i] = pack_bf16(gelu_tanh(bf_lo(p)), gelu_tanh(bf_hi(p)));
      }
      bar_sync(2, 256);
#pragma unroll
      for (int q = 0; q < 24; q += 2) stsm4t(sa + q * 1024, pk[2 * q], pk[2 * q + 1], pk[2 * q + 2], pk[2 * q + 3]);
      fence_async_smem();
      bar_sync(3 + wg, 128);
      if (wtid == 0) {
        tma2d_store(&P.m_ust, stg, fb64 * 64, g1n * 192);
        bulk_commit();
        bulk_wait_read();
        asm volatile("mbarrier.arrive.shared::cta.b64 _, [%0], 2;" :: "r"(bars + 8 * (B_EMPTY + sst)) : "memory");
        bulk_wait_all();
        fence_gpu();
        st_flag(g_uflag + g1n * 96 + fb64, tag);
        if (wg == 0) TLREC(5);
      }
      __syncwarp();
      it = G1_KB;
    } else {
      const uint32_t red = sb + CV_RED + wg * CV_REDWG;
      if (wtid < 8 * CV_NSLOT / 2) {
        const int sl = wg * (CV_NSLOT / 2) + (wtid >> 3);
        asm volatile("st.shared.u32 [%0], %1;" :: "r"(sb + CV_BASE + sl * CV_SLOT + CV_KOFF + (wtid & 7) * 4), "r"(0) : "memory");
      }
      sts64f(red + w * CV_REDW + lane * 8, 0.f, 0.f);
      bar_sync(2, 256);
      const int px = 3 - t + w;
      const uint32_t wr = red + w * CV_REDW + ((16 * px + 2 * g) ^ (((px >> 1) & 1) << 3)) * 4;
      const uint32_t rd = red + ((4 * wtid) ^ (((wtid >> 3) & 1) << 3)) * 4;
      if (wg == 1) bar_arrive(5, 256);
      for (int i = wg; i < n_conv; i += 2) {
        const int ch = conv_channel(cvc, i), s = i % CV_NSLOT;
        const uint32_t slot = sb + CV_BASE + s * CV_SLOT;
        mbar_wait(bars + 8 * (B_CFULL + s), (i / CV_NSLOT) & 1);
        if (i == 0 && tid == 0) TLREC(5);
        uint32_t a[64];
        const uint32_t ka = slot + CV_KOFF + (8 * w + g + t + 1) * 4;
#pragma unroll
        for (int j = 0; j < 16; j++) {
          a[4 * j] = lds32(ka + j * 256); a[4 * j + 1] = lds32(ka + j * 256 + 128);
          a[4 * j + 2] = lds32(ka + j * 256 + 16); a[4 * j + 3] = lds32(ka + j * 256 + 144);
        }
        const uint64_t db = make_desc(slot, 4096, 128, 0);
        float acc[128];
        bar_sync(5 + wg, 256);
        wg_fence();
        wgmma_rs_n256(acc, a, db, 0);
        wgmma_rs_n240(acc, a + 4, db + 16, 1);
        wgmma_rs_n224(acc, a + 8, db + 32, 1);
        wgmma_rs_n208(acc, a + 12, db + 48, 1);
        wgmma_rs_n192(acc, a + 16, db + 64, 1);
        wgmma_rs_n176(acc, a + 20, db + 80, 1);
        wgmma_rs_n160(acc, a + 24, db + 96, 1);
        wgmma_rs_n144(acc, a + 28, db + 112, 1);
        wgmma_rs_n128(acc, a + 32, db + 128, 1);
        wgmma_rs_n112(acc, a + 36, db + 144, 1);
        wgmma_rs_n96(acc, a + 40, db + 160, 1);
        wgmma_rs_n80(acc, a + 44, db + 176, 1);
        wgmma_rs_n64(acc, a + 48, db + 192, 1);
        wgmma_rs_n48(acc, a + 52, db + 208, 1);
        wgmma_rs_n32(acc, a + 56, db + 224, 1);
        wgmma_rs_n16(acc, a + 60, db + 240, 1);
        wg_commit();
        if (i + 1 < n_conv) bar_arrive(5 + (wg ^ 1), 256);
        wg_wait<0>();
        pin_regs<128>(acc);
        bar_sync(3 + wg, 128);
        if (wtid == 0) mbar_arrive(bars + 8 * (B_CEMPTY + s));
        sts64f(wr, acc[124], acc[125]);
#pragma unroll
        for (int q = 30; q >= 0; q--) sts64f(wr + (31 - q) * 256, acc[4 * q] + acc[4 * q + 6], acc[4 * q + 1] + acc[4 * q + 7]);
        bar_sync(3 + wg, 128);
        uint2* yo = reinterpret_cast<uint2*>(g_y + (size_t)ch * S_) + wtid;
#pragma unroll
        for (int j = 0; j < 4; j++) {
          float4 v0 = lds128f(rd + j * 2048), v1 = lds128f(rd + j * 2048 + CV_REDW), v2 = lds128f(rd + j * 2048 + 2 * CV_REDW), v3 = lds128f(rd + j * 2048 + 3 * CV_REDW);
          yo[j * 128] = make_uint2(pack_bf16((v0.x + v1.x) + (v2.x + v3.x), (v0.y + v1.y) + (v2.y + v3.y)),
                                   pack_bf16((v0.z + v1.z) + (v2.z + v3.z), (v0.w + v1.w) + (v2.w + v3.w)));
        }
      }
      bar_sync(3 + wg, 128);
      if (wtid == 0) {
        mbar_arrive(bars + 8 * B_CDONE);
        fence_gpu();
        st_flag(g_yflag + cvc * 2 + wg, tag);
        TLREC(20 + wg);
      }
      __syncwarp();
    }
    if (g2m >= 0) {
      const int srow = g2m * 128 + wg * 64 + w * 16 + g;
      const int dk = g2n * 144 + rank * 72;
      float acc[72];
      uint32_t xx[18], ss[18], yy[18];
      uint32_t bias0, bias1;
      float2 st0, st1;
      auto step = [&](int kb) {
        const int p = it + kb, s = p % NSTAGE;
        mbar_wait(bars + 8 * (B_FULL + s), (p / NSTAGE) & 1);
        if (kb == 0 && tid == 0) TLREC(7);
        const uint64_t da = make_desc(sb + s * SLOT + wg * 8192, 8192, 1024, 1), db = make_desc(sb + s * SLOT + 16384, 16, 1024, 1);
        wg_fence();
#pragma unroll
        for (int k = 0; k < 4; k++) wgmma_ss_n144_t10(acc, da + k * 128, db + k * 2, (kb | k) != 0);
        wg_commit();
        wg_wait<1>();
        if (kb > 0 && wtid == 0) mbar_arrive(bars + 8 * (B_EMPTY + (p - 1) % NSTAGE));
      };
      for (int kb = 0; kb < G2_PF_KB; kb++) step(kb);
      {
        uint32_t c = 0;
        while (true) {
          bool ok = true;
          if (lane < 12) { uint4 f = ld_flag4(g_yflag + 4 * lane); ok = f.x == tag && f.y == tag && f.z == tag && f.w == tag; }
          if (__all_sync(0xffffffffu, ok)) break;
          spin_guard(c);
        }
        fence_gpu();
        if (tid == 0) TLREC(8);
        const size_t o0 = (size_t)srow * D_ + dk + 2 * t;
        const size_t oy = (size_t)(dk + g) * S_ + (srow - g) + 2 * t;
#pragma unroll
        for (int q = 0; q < 9; q++) {
          xx[2 * q] = ldg32(P.x + o0 + 8 * q); xx[2 * q + 1] = ldg32(P.x + o0 + 8 * D_ + 8 * q);
          ss[2 * q] = ldg32_cg(g_p2 + o0 + 8 * q); ss[2 * q + 1] = ldg32_cg(g_p2 + o0 + 8 * D_ + 8 * q);
          yy[2 * q] = ldg32_cg(g_y + oy + (size_t)8 * q * S_); yy[2 * q + 1] = ldg32_cg(g_y + oy + (size_t)8 * q * S_ + 8);
        }
        st0 = __ldcg(g_stats + srow); st1 = __ldcg(g_stats + srow + 8);
        bias0 = __byte_perm((uint32_t)__bfloat16_as_ushort(P.b2[srow]), 0, 0x1010);
        bias1 = __byte_perm((uint32_t)__bfloat16_as_ushort(P.b2[srow + 8]), 0, 0x1010);
      }
      for (int kb = G2_PF_KB; kb < G2_PF_KB + 3; kb++) step(kb);
      {
        const uint32_t m0 = pack_bf16(st0.x, st0.x), m1 = pack_bf16(st1.x, st1.x);
#pragma unroll
        for (int i = 0; i < 18; i++)
          ss[i] = bmul2(ln_apply(xx[i], (i & 1) ? m1 : m0, (i & 1) ? st1.y : st0.y), badd2(movmt(yy[i]), ss[i]));
      }
      for (int kb = G2_PF_KB + 3; kb < G2_KB; kb++) step(kb);
      wg_wait<0>();
      pin_regs<72>(acc);
      if (tid == 0) TLREC(9);
      const uint32_t xz = sb + ((it + G2_KB) % NSTAGE) * SLOT + tid * 16;
      mbar_wait_cluster(bars + 8 * B_XRDY, 0);
      {
        const uint32_t rz = mapa(xz, rank ^ 1), rb = mapa(bars + 8 * B_XFULL, rank ^ 1);
#pragma unroll
        for (int q = 0; q < 9; q++)
          asm volatile("st.async.weak.shared::cluster.mbarrier::complete_tx::bytes.v4.f32 [%0], {%1,%2,%3,%4}, [%5];"
                       :: "r"(rz + q * 4096), "f"(acc[36 + 4 * q]), "f"(acc[37 + 4 * q]), "f"(acc[38 + 4 * q]), "f"(acc[39 + 4 * q]), "r"(rb) : "memory");
      }
      mbar_wait_cluster(bars + 8 * B_XFULL, 0);
      if (tid == 0) TLREC(10);
      uint32_t ob[18];
#pragma unroll
      for (int q = 0; q < 9; q++) {
        const float4 pv = lds128f(xz + q * 4096);
        const uint32_t y0 = badd2(pack_bf16(acc[4 * q] + pv.x, acc[4 * q + 1] + pv.y), bias0);
        const uint32_t y1 = badd2(pack_bf16(acc[4 * q + 2] + pv.z, acc[4 * q + 3] + pv.w), bias1);
        ob[2 * q] = badd2(xx[2 * q], bmul2(ss[2 * q], pack_bf16(silu(bf_lo(y0)), silu(bf_hi(y0)))));
        ob[2 * q + 1] = badd2(xx[2 * q + 1], bmul2(ss[2 * q + 1], pack_bf16(silu(bf_lo(y1)), silu(bf_hi(y1)))));
      }
      const uint32_t so = sb + SM_OUT + warp * 2304;
      const uint32_t sa = so + (lane & 15) * 144 + (lane >> 4) * 16;
#pragma unroll
      for (int q = 0; q < 8; q += 2) stsm4(sa + q * 16, ob[2 * q], ob[2 * q + 1], ob[2 * q + 2], ob[2 * q + 3]);
      stsm2(so + (lane & 15) * 144 + 128, ob[16], ob[17]);
      fence_async_smem();
      __syncwarp();
      if (lane == 0) {
        tma2d_store(&P.m_out, so, dk, srow);
        bulk_commit();
        bulk_wait_read();
      }
      if (tid == 0) {
        TLREC(11);
        if (g1m == 0 && g1n == 0 && rank == 0) st_flag(&g_epoch, tag);
      }
    }
  }
}

typedef CUresult (*EncodeFn)(CUtensorMap*, CUtensorMapDataType, cuuint32_t, void*, const cuuint64_t*, const cuuint64_t*, const cuuint32_t*,
                             const cuuint32_t*, CUtensorMapInterleave, CUtensorMapSwizzle, CUtensorMapL2promotion, CUtensorMapFloatOOBfill);

void make_map(EncodeFn fn, CUtensorMap* m, const void* ptr, int rank, const cuuint64_t* dims, const cuuint64_t* strides, const cuuint32_t* box,
              CUtensorMapSwizzle sw) {
  const cuuint32_t es[3] = {1, 1, 1};
  fn(m, CU_TENSOR_MAP_DATA_TYPE_BFLOAT16, rank, const_cast<void*>(ptr), dims, strides, box, es, CU_TENSOR_MAP_INTERLEAVE_NONE, sw,
     CU_TENSOR_MAP_L2_PROMOTION_L2_256B, CU_TENSOR_MAP_FLOAT_OOB_FILL_NONE);
}

void make_roles(Roles& R) {
  int c1 = 0, ncv = 2, np0 = 0;
  for (int g = 0; g < 8; g++)
    for (int c = 0; c < 66; c++) {
      const int tp = (c + 62) % 66;
      int gg, idx;
      if (tp < 32) { gg = tp % 8; idx = tp / 8; }
      else if (tp < 60) { gg = 1 + (tp - 32) % 7; idx = 4 + (tp - 32) / 7; }
      else if (tp < 62) { gg = 6 + tp - 60; idx = 8; }
      else { gg = 0; idx = 4 + tp - 62; }
      if (gg != g) continue;
      if (idx < 8) { R.g2m[c] = (int8_t)(2 * g + idx / 4); R.g2n[c] = (int8_t)(idx % 4); R.p0[c] = (int8_t)np0++; }
      else { R.g2m[c] = -1; R.g2n[c] = 0; R.p0[c] = -1; }
      if (idx < (g < 2 ? 6 : 7)) { R.g1m[c] = (int8_t)(c1 / 3); R.g1n[c] = (int8_t)(c1 % 3); R.cv[c] = -1; c1++; }
      else { R.g1m[c] = -1; R.g1n[c] = 0; R.cv[c] = (int8_t)(idx == 8 ? tp - 60 : ncv++); }
    }
}

}

extern "C" void kernel_launch(void* const* d_in, const int* in_sizes, int n_in, void* d_out, int out_size) {
  static Params P;
  static const void* cached[3] = {nullptr, nullptr, nullptr};
  if (cached[0] != d_in[7] || cached[1] != d_in[9] || cached[2] != d_out) {
    void* fp = nullptr;
    cudaDriverEntryPointQueryResult qr;
    cudaGetDriverEntryPoint("cuTensorMapEncodeTiled", &fp, cudaEnableDefault, &qr);
    EncodeFn fn = (EncodeFn)fp;
    void *ph, *pu;
    cudaGetSymbolAddress(&ph, g_h);
    cudaGetSymbolAddress(&pu, g_u);
    { cuuint64_t d[3] = {64, S_, F_ / 64}, s[2] = {F_ * 2, 128}; cuuint32_t b[3] = {64, 64, 2}; make_map(fn, &P.m_w1, d_in[7], 3, d, s, b, CU_TENSOR_MAP_SWIZZLE_128B); }
    { cuuint64_t d[3] = {64, S_, D_ / 64}, s[2] = {D_ * 2, 128}; cuuint32_t b[3] = {64, 64, 3}; make_map(fn, &P.m_h, ph, 3, d, s, b, CU_TENSOR_MAP_SWIZZLE_128B); }
    { cuuint64_t d[2] = {F_, D_}, s[1] = {F_ * 2}; cuuint32_t b[2] = {64, 192}; make_map(fn, &P.m_ust, pu, 2, d, s, b, CU_TENSOR_MAP_SWIZZLE_128B); }
    { cuuint64_t d[3] = {64, F_, S_ / 64}, s[2] = {S_ * 2, 128}; cuuint32_t b[3] = {64, 64, 2}; make_map(fn, &P.m_w2, d_in[9], 3, d, s, b, CU_TENSOR_MAP_SWIZZLE_128B); }
    { cuuint64_t d[2] = {F_, D_}, s[1] = {F_ * 2}; cuuint32_t b[2] = {64, 72}; make_map(fn, &P.m_uld, pu, 2, d, s, b, CU_TENSOR_MAP_SWIZZLE_128B); }
    { cuuint64_t d[2] = {D_, S_}, s[1] = {D_ * 2}; cuuint32_t b[2] = {72, 16}; make_map(fn, &P.m_out, d_out, 2, d, s, b, CU_TENSOR_MAP_SWIZZLE_NONE); }
    make_roles(P.roles);
    cudaFuncSetAttribute(fused_kernel, cudaFuncAttributeMaxDynamicSharedMemorySize, SM_TOTAL);
    cached[0] = d_in[7]; cached[1] = d_in[9]; cached[2] = d_out;
  }
  P.x = (const __nv_bfloat16*)d_in[0]; P.k = (const __nv_bfloat16*)d_in[1]; P.v = (const __nv_bfloat16*)d_in[2];
  P.shift_k = (const __nv_bfloat16*)d_in[3]; P.ssm_k = (const __nv_bfloat16*)d_in[4]; P.ssm_D = (const __nv_bfloat16*)d_in[5];
  P.b1 = (const __nv_bfloat16*)d_in[8]; P.b2 = (const __nv_bfloat16*)d_in[10];
  fused_kernel<<<132, 384, SM_TOTAL>>>(P);
}
```

```cpp
#include <cuda_runtime.h>
#include <cuda.h>
#include <cuda_bf16.h>
#include <stdint.h>

namespace {

constexpr int S_ = 2048, D_ = 576, F_ = 4608;
constexpr int NSTAGE = 5, SLOT = 40960;
constexpr int G1_KB = 32, G2_KB = 36;
constexpr int G1_BYTES = 40960, G2_BYTES = 16384 + 18432;
constexpr int N_CONV_CTA = 24, N_SHORT = 22, N_LONG_EXTRA = 12;
static_assert(N_CONV_CTA * N_SHORT + 4 * N_LONG_EXTRA == D_, "conv split");
constexpr int KV_ROUNDS = 6;
constexpr int G1_TAIL = 5, G2_TAIL = 4;

constexpr int SM_DED = NSTAGE * SLOT;
constexpr int SM_BAR = SM_DED + 24576;
constexpr int SM_TOTAL = SM_BAR + 256 + 1024;
constexpr int CV_BASE = 3 * SLOT;
constexpr int CV_NSLOT = 6, CV_KOFF = 8192, CV_SLOT = 8192 + 4224;
static_assert(CV_BASE + CV_NSLOT * CV_SLOT <= SM_DED, "conv overlay");
constexpr int B_FULL = 0, B_EMPTY = NSTAGE, B_CFULL = 2 * NSTAGE, B_CEMPTY = B_CFULL + CV_NSLOT, B_CDONE = B_CEMPTY + CV_NSLOT,
              B_XRDY = B_CDONE + 1, B_XFULL = B_CDONE + 2  , B_XT = B_CDONE + 4, B_Y2 = B_CDONE + 5;
constexpr int C_H = 0, C_KV = 1, C_U = C_KV + KV_ROUNDS  , C_YA = C_U + 12, C_YB = C_YA + 1, C_COUNT = C_YB + 1;

struct Roles {
  int8_t g1m[66];
  int8_t g1n[66];
  int8_t cv[66];
  int8_t g2m[66];
  int8_t g2n[66];
  int8_t p0[66];
};

struct Params {
  CUtensorMap m_w1, m_h, m_ust, m_w2, m_uld, m_out, m_x;
  const __nv_bfloat16 *x, *k, *v, *shift_k, *ssm_k, *ssm_D, *b1, *b2;
  Roles roles;
};

__device__ __align__(1024) __nv_bfloat16 g_h[S_ * D_];
__device__ __align__(1024) __nv_bfloat16 g_ub[D_ * 4096];
__device__ __align__(1024) __nv_bfloat16 g_yp[D_ * 4 * S_];
__device__ __align__(1024) __nv_bfloat16 g_u[D_ * F_];
__device__ __align__(128) float2 g_stats[S_];
__device__ __align__(128) uint32_t g_cnt[C_COUNT * 32];
__device__ __align__(128) uint32_t g_epoch;
#define TLREC(i) do { } while (0)

__device__ __forceinline__ uint32_t smem_u32(const void* p) { return (uint32_t)__cvta_generic_to_shared(p); }
__device__ __forceinline__ void mbar_init(uint32_t bar, uint32_t cnt) { asm volatile("mbarrier.init.shared::cta.b64 [%0], %1;" :: "r"(bar), "r"(cnt) : "memory"); }
__device__ __forceinline__ void mbar_expect_tx(uint32_t bar, uint32_t bytes) { asm volatile("mbarrier.arrive.expect_tx.shared::cta.b64 _, [%0], %1;" :: "r"(bar), "r"(bytes) : "memory"); }
__device__ __forceinline__ void mbar_arrive(uint32_t bar) { asm volatile("mbarrier.arrive.shared::cta.b64 _, [%0];" :: "r"(bar) : "memory"); }
__device__ __forceinline__ uint32_t mapa(uint32_t addr, uint32_t cta) { uint32_t r; asm volatile("mapa.shared::cluster.u32 %0, %1, %2;" : "=r"(r) : "r"(addr), "r"(cta)); return r; }
__device__ __forceinline__ void mbar_arrive_remote(uint32_t rbar) { asm volatile("mbarrier.arrive.release.cluster.shared::cluster.b64 _, [%0];" :: "r"(rbar) : "memory"); }
__device__ __forceinline__ void mbar_wait(uint32_t bar, uint32_t parity) {
  asm volatile("{\n .reg .pred p;\n .reg .u32 c;\n mov.u32 c, 0;\n"
               "W_%=:\n mbarrier.try_wait.parity.shared::cta.b64 p, [%0], %1;\n @p bra D_%=;\n"
               " add.u32 c, c, 1;\n setp.lt.u32 p, c, 2000000;\n @p bra W_%=;\n trap;\n D_%=:\n }" :: "r"(bar), "r"(parity) : "memory");
}
__device__ __forceinline__ void mbar_wait_cluster(uint32_t bar, uint32_t parity) {
  asm volatile("{\n .reg .pred p;\n .reg .u32 c;\n mov.u32 c, 0;\n"
               "W_%=:\n mbarrier.try_wait.parity.acquire.cluster.shared::cta.b64 p, [%0], %1;\n @p bra D_%=;\n"
               " add.u32 c, c, 1;\n setp.lt.u32 p, c, 2000000;\n @p bra W_%=;\n trap;\n D_%=:\n }" :: "r"(bar), "r"(parity) : "memory");
}
__device__ __forceinline__ void tma2d(uint32_t dst, const CUtensorMap* m, int c0, int c1, uint32_t bar) {
  asm volatile("cp.async.bulk.tensor.2d.shared::cluster.global.mbarrier::complete_tx::bytes [%0], [%1, {%3, %4}], [%2];"
               :: "r"(dst), "l"(m), "r"(bar), "r"(c0), "r"(c1) : "memory");
}
__device__ __forceinline__ void tma3d(uint32_t dst, const CUtensorMap* m, int c0, int c1, int c2, uint32_t bar) {
  asm volatile("cp.async.bulk.tensor.3d.shared::cluster.global.mbarrier::complete_tx::bytes [%0], [%1, {%3, %4, %5}], [%2];"
               :: "r"(dst), "l"(m), "r"(bar), "r"(c0), "r"(c1), "r"(c2) : "memory");
}
__device__ __forceinline__ void tma2d_store(const CUtensorMap* m, uint32_t src, int c0, int c1) {
  asm volatile("cp.async.bulk.tensor.2d.global.shared::cta.bulk_group [%0, {%2, %3}], [%1];" :: "l"(m), "r"(src), "r"(c0), "r"(c1) : "memory");
}
__device__ __forceinline__ void bulk_load(uint32_t dst, const void* src, uint32_t bytes, uint32_t bar) {
  asm volatile("cp.async.bulk.shared::cluster.global.mbarrier::complete_tx::bytes [%0], [%1], %2, [%3];" :: "r"(dst), "l"(src), "r"(bytes), "r"(bar) : "memory");
}
__device__ __forceinline__ void bulk_commit() { asm volatile("cp.async.bulk.commit_group;" ::: "memory"); }
__device__ __forceinline__ void bulk_wait_all() { asm volatile("cp.async.bulk.wait_group 0;" ::: "memory"); }
__device__ __forceinline__ void bulk_wait_read() { asm volatile("cp.async.bulk.wait_group.read 0;" ::: "memory"); }
__device__ __forceinline__ void fence_async_smem() { asm volatile("fence.proxy.async.shared::cta;" ::: "memory"); }
__device__ __forceinline__ void fence_async_global() { asm volatile("fence.proxy.async.global;" ::: "memory"); }
__device__ __forceinline__ void st_flag(uint32_t* p, uint32_t v) { asm volatile("st.relaxed.gpu.global.u32 [%0], %1;" :: "l"(p), "r"(v) : "memory"); }
__device__ __forceinline__ uint32_t ld_flag(const uint32_t* p) { uint32_t v; asm volatile("ld.relaxed.gpu.global.u32 %0, [%1];" : "=r"(v) : "l"(p) : "memory"); return v; }
__device__ __forceinline__ void signal(int c) { asm volatile("red.release.gpu.global.add.u32 [%0], 1;" :: "l"(g_cnt + c * 32) : "memory"); }
__device__ __forceinline__ void await(int c, uint32_t target) {
  uint32_t n = 0;
  while (true) {
    uint32_t v; asm volatile("ld.acquire.gpu.global.u32 %0, [%1];" : "=r"(v) : "l"(g_cnt + c * 32) : "memory");
    if ((int32_t)(v - target) >= 0) break;
    if (++n > 4000000u) __trap();
  }
}
__device__ __forceinline__ void bar_sync(int id, int n) { asm volatile("bar.sync %0, %1;" :: "r"(id), "r"(n) : "memory"); }
__device__ __forceinline__ void bar_arrive(int id, int n) { asm volatile("bar.arrive %0, %1;" :: "r"(id), "r"(n) : "memory"); }
__device__ __forceinline__ void wg_fence() { asm volatile("wgmma.fence.sync.aligned;" ::: "memory"); }
__device__ __forceinline__ void wg_commit() { asm volatile("wgmma.commit_group.sync.aligned;" ::: "memory"); }
template <int N> __device__ __forceinline__ void wg_wait() { asm volatile("wgmma.wait_group.sync.aligned %0;" :: "n"(N) : "memory"); }
template <int N> __device__ __forceinline__ void pin_regs(float* a) {
#pragma unroll
  for (int i = 0; i < N; i++) asm volatile("" : "+f"(a[i]) :: "memory");
}
__device__ __forceinline__ uint64_t make_desc(uint32_t addr, uint32_t lbo, uint32_t sbo, uint32_t swz) {
  return (uint64_t)((addr & 0x3FFFF) >> 4) | ((uint64_t)(lbo >> 4) << 16) | ((uint64_t)(sbo >> 4) << 32) | ((uint64_t)swz << 62);
}
__device__ __forceinline__ uint32_t pack_bf16(float lo, float hi) { uint32_t r; asm("cvt.rn.bf16x2.f32 %0, %1, %2;" : "=r"(r) : "f"(hi), "f"(lo)); return r; }
__device__ __forceinline__ float bf_lo(uint32_t p) { return __uint_as_float(p << 16); }
__device__ __forceinline__ float bf_hi(uint32_t p) { return __uint_as_float(p & 0xffff0000u); }
__device__ __forceinline__ float round_bf16(float v) { return bf_lo(pack_bf16(v, 0.f)); }
__device__ __forceinline__ uint32_t bmul2(uint32_t a, uint32_t b) { uint32_t r; asm("mul.rn.bf16x2 %0, %1, %2;" : "=r"(r) : "r"(a), "r"(b)); return r; }
__device__ __forceinline__ uint32_t badd2(uint32_t a, uint32_t b) { uint32_t r; asm("add.rn.bf16x2 %0, %1, %2;" : "=r"(r) : "r"(a), "r"(b)); return r; }
__device__ __forceinline__ uint32_t bsub2(uint32_t a, uint32_t b) { uint32_t r; asm("sub.rn.bf16x2 %0, %1, %2;" : "=r"(r) : "r"(a), "r"(b)); return r; }
__device__ __forceinline__ float tanh_fast(float v) { float r; asm("tanh.approx.f32 %0, %1;" : "=f"(r) : "f"(v)); return r; }
__device__ __forceinline__ float gelu_tanh(float v) {
  float z = v * fmaf(v * v, 0.7978845608028654f * 0.044715f, 0.7978845608028654f);
  float hv = 0.5f * v;
  return fmaf(hv, tanh_fast(z), hv);
}
__device__ __forceinline__ float silu(float v) { float hv = 0.5f * v; return fmaf(hv, tanh_fast(hv), hv); }
__device__ __forceinline__ uint32_t ldg32(const void* p) { uint32_t v; asm volatile("ld.global.nc.u32 %0, [%1];" : "=r"(v) : "l"(p)); return v; }
__device__ __forceinline__ uint4 ldg128_cg(const void* p) {
  uint4 v; asm volatile("ld.global.cg.v4.u32 {%0,%1,%2,%3}, [%4];" : "=r"(v.x), "=r"(v.y), "=r"(v.z), "=r"(v.w) : "l"(p) : "memory"); return v;
}
__device__ __forceinline__ void stg32(void* p, uint32_t v) { asm volatile("st.global.u32 [%0], %1;" :: "l"(p), "r"(v) : "memory"); }
__device__ __forceinline__ uint32_t lds32(uint32_t a) { uint32_t v; asm volatile("ld.shared.u32 %0, [%1];" : "=r"(v) : "r"(a) : "memory"); return v; }
__device__ __forceinline__ float4 lds128f(uint32_t a) { float4 v; asm volatile("ld.shared.v4.f32 {%0,%1,%2,%3}, [%4];" : "=f"(v.x), "=f"(v.y), "=f"(v.z), "=f"(v.w) : "r"(a) : "memory"); return v; }
__device__ __forceinline__ void sts128(uint32_t a, uint4 v) { asm volatile("st.shared.v4.u32 [%0], {%1,%2,%3,%4};" :: "r"(a), "r"(v.x), "r"(v.y), "r"(v.z), "r"(v.w) : "memory"); }
__device__ __forceinline__ void ldsm4(uint32_t* r, uint32_t a) {
  asm volatile("ldmatrix.sync.aligned.m8n8.x4.shared.b16 {%0,%1,%2,%3}, [%4];" : "=r"(r[0]), "=r"(r[1]), "=r"(r[2]), "=r"(r[3]) : "r"(a) : "memory");
}
__device__ __forceinline__ void ldsm2(uint32_t* r, uint32_t a) {
  asm volatile("ldmatrix.sync.aligned.m8n8.x2.shared.b16 {%0,%1}, [%2];" : "=r"(r[0]), "=r"(r[1]) : "r"(a) : "memory");
}
__device__ __forceinline__ void ldsm4t(uint32_t* r, uint32_t a) {
  asm volatile("ldmatrix.sync.aligned.m8n8.x4.trans.shared.b16 {%0,%1,%2,%3}, [%4];" : "=r"(r[0]), "=r"(r[1]), "=r"(r[2]), "=r"(r[3]) : "r"(a) : "memory");
}
__device__ __forceinline__ void ldsm2t(uint32_t* r, uint32_t a) {
  asm volatile("ldmatrix.sync.aligned.m8n8.x2.trans.shared.b16 {%0,%1}, [%2];" : "=r"(r[0]), "=r"(r[1]) : "r"(a) : "memory");
}
__device__ __forceinline__ void stsm4(uint32_t a, uint32_t r0, uint32_t r1, uint32_t r2, uint32_t r3) {
  asm volatile("stmatrix.sync.aligned.m8n8.x4.shared.b16 [%0], {%1,%2,%3,%4};" :: "r"(a), "r"(r0), "r"(r1), "r"(r2), "r"(r3) : "memory");
}
__device__ __forceinline__ void stsm2(uint32_t a, uint32_t r0, uint32_t r1) {
  asm volatile("stmatrix.sync.aligned.m8n8.x2.shared.b16 [%0], {%1,%2};" :: "r"(a), "r"(r0), "r"(r1) : "memory");
}
__device__ __forceinline__ void stsm4t(uint32_t a, uint32_t r0, uint32_t r1, uint32_t r2, uint32_t r3) {
  asm volatile("stmatrix.sync.aligned.m8n8.x4.trans.shared.b16 [%0], {%1,%2,%3,%4};" :: "r"(a), "r"(r0), "r"(r1), "r"(r2), "r"(r3) : "memory");
}

__device__ __forceinline__ void wgmma_ss_n144_t10(float* d, uint64_t da, uint64_t db, int sd) {
  asm volatile("{ .reg .pred p; setp.ne.b32 p, %74, 0;\n"
      "wgmma.mma_async.sync.aligned.m64n144k16.f32.bf16.bf16 {"
      "%0,%1,%2,%3,%4,%5,%6,%7,%8,%9,%10,%11,%12,%13,%14,%15,"
      "%16,%17,%18,%19,%20,%21,%22,%23,%24,%25,%26,%27,%28,%29,%30,%31,"
      "%32,%33,%34,%35,%36,%37,%38,%39,%40,%41,%42,%43,%44,%45,%46,%47,"
      "%48,%49,%50,%51,%52,%53,%54,%55,%56,%57,%58,%59,%60,%61,%62,%63,"
      "%64,%65,%66,%67,%68,%69,%70,%71"
      "}, %72, %73, p, 1, 1, 1, 0; }"
    : "+f"(d[0]), "+f"(d[1]), "+f"(d[2]), "+f"(d[3]), "+f"(d[4]), "+f"(d[5]), "+f"(d[6]), "+f"(d[7]),
      "+f"(d[8]), "+f"(d[9]), "+f"(d[10]), "+f"(d[11]), "+f"(d[12]), "+f"(d[13]), "+f"(d[14]), "+f"(d[15]),
      "+f"(d[16]), "+f"(d[17]), "+f"(d[18]), "+f"(d[19]), "+f"(d[20]), "+f"(d[21]), "+f"(d[22]), "+f"(d[23]),
      "+f"(d[24]), "+f"(d[25]), "+f"(d[26]), "+f"(d[27]), "+f"(d[28]), "+f"(d[29]), "+f"(d[30]), "+f"(d[31]),
      "+f"(d[32]), "+f"(d[33]), "+f"(d[34]), "+f"(d[35]), "+f"(d[36]), "+f"(d[37]), "+f"(d[38]), "+f"(d[39]),
      "+f"(d[40]), "+f"(d[41]), "+f"(d[42]), "+f"(d[43]), "+f"(d[44]), "+f"(d[45]), "+f"(d[46]), "+f"(d[47]),
      "+f"(d[48]), "+f"(d[49]), "+f"(d[50]), "+f"(d[51]), "+f"(d[52]), "+f"(d[53]), "+f"(d[54]), "+f"(d[55]),
      "+f"(d[56]), "+f"(d[57]), "+f"(d[58]), "+f"(d[59]), "+f"(d[60]), "+f"(d[61]), "+f"(d[62]), "+f"(d[63]),
      "+f"(d[64]), "+f"(d[65]), "+f"(d[66]), "+f"(d[67]), "+f"(d[68]), "+f"(d[69]), "+f"(d[70]), "+f"(d[71])
    : "l"(da), "l"(db), "r"(sd));
}

__device__ __forceinline__ void wgmma_ss_n192_t11(float* d, uint64_t da, uint64_t db, int sd) {
  asm volatile("{ .reg .pred p; setp.ne.b32 p, %98, 0;\n"
      "wgmma.mma_async.sync.aligned.m64n192k16.f32.bf16.bf16 {"
      "%0,%1,%2,%3,%4,%5,%6,%7,%8,%9,%10,%11,%12,%13,%14,%15,"
      "%16,%17,%18,%19,%20,%21,%22,%23,%24,%25,%26,%27,%28,%29,%30,%31,"
      "%32,%33,%34,%35,%36,%37,%38,%39,%40,%41,%42,%43,%44,%45,%46,%47,"
      "%48,%49,%50,%51,%52,%53,%54,%55,%56,%57,%58,%59,%60,%61,%62,%63,"
      "%64,%65,%66,%67,%68,%69,%70,%71,%72,%73,%74,%75,%76,%77,%78,%79,"
      "%80,%81,%82,%83,%84,%85,%86,%87,%88,%89,%90,%91,%92,%93,%94,%95"
      "}, %96, %97, p, 1, 1, 1, 1; }"
    : "+f"(d[0]), "+f"(d[1]), "+f"(d[2]), "+f"(d[3]), "+f"(d[4]), "+f"(d[5]), "+f"(d[6]), "+f"(d[7]),
      "+f"(d[8]), "+f"(d[9]), "+f"(d[10]), "+f"(d[11]), "+f"(d[12]), "+f"(d[13]), "+f"(d[14]), "+f"(d[15]),
      "+f"(d[16]), "+f"(d[17]), "+f"(d[18]), "+f"(d[19]), "+f"(d[20]), "+f"(d[21]), "+f"(d[22]), "+f"(d[23]),
      "+f"(d[24]), "+f"(d[25]), "+f"(d[26]), "+f"(d[27]), "+f"(d[28]), "+f"(d[29]), "+f"(d[30]), "+f"(d[31]),
      "+f"(d[32]), "+f"(d[33]), "+f"(d[34]), "+f"(d[35]), "+f"(d[36]), "+f"(d[37]), "+f"(d[38]), "+f"(d[39]),
      "+f"(d[40]), "+f"(d[41]), "+f"(d[42]), "+f"(d[43]), "+f"(d[44]), "+f"(d[45]), "+f"(d[46]), "+f"(d[47]),
      "+f"(d[48]), "+f"(d[49]), "+f"(d[50]), "+f"(d[51]), "+f"(d[52]), "+f"(d[53]), "+f"(d[54]), "+f"(d[55]),
      "+f"(d[56]), "+f"(d[57]), "+f"(d[58]), "+f"(d[59]), "+f"(d[60]), "+f"(d[61]), "+f"(d[62]), "+f"(d[63]),
      "+f"(d[64]), "+f"(d[65]), "+f"(d[66]), "+f"(d[67]), "+f"(d[68]), "+f"(d[69]), "+f"(d[70]), "+f"(d[71]),
      "+f"(d[72]), "+f"(d[73]), "+f"(d[74]), "+f"(d[75]), "+f"(d[76]), "+f"(d[77]), "+f"(d[78]), "+f"(d[79]),
      "+f"(d[80]), "+f"(d[81]), "+f"(d[82]), "+f"(d[83]), "+f"(d[84]), "+f"(d[85]), "+f"(d[86]), "+f"(d[87]),
      "+f"(d[88]), "+f"(d[89]), "+f"(d[90]), "+f"(d[91]), "+f"(d[92]), "+f"(d[93]), "+f"(d[94]), "+f"(d[95])
    : "l"(da), "l"(db), "r"(sd));
}

__device__ __forceinline__ void wgmma_ss_n72_t10(float* d, uint64_t da, uint64_t db, int sd) {
  asm volatile("{ .reg .pred p; setp.ne.b32 p, %38, 0;\n"
      "wgmma.mma_async.sync.aligned.m64n72k16.f32.bf16.bf16 {"
      "%0,%1,%2,%3,%4,%5,%6,%7,%8,%9,%10,%11,%12,%13,%14,%15,"
      "%16,%17,%18,%19,%20,%21,%22,%23,%24,%25,%26,%27,%28,%29,%30,%31,"
      "%32,%33,%34,%35"
      "}, %36, %37, p, 1, 1, 1, 0; }"
    : "+f"(d[0]), "+f"(d[1]), "+f"(d[2]), "+f"(d[3]), "+f"(d[4]), "+f"(d[5]), "+f"(d[6]), "+f"(d[7]),
      "+f"(d[8]), "+f"(d[9]), "+f"(d[10]), "+f"(d[11]), "+f"(d[12]), "+f"(d[13]), "+f"(d[14]), "+f"(d[15]),
      "+f"(d[16]), "+f"(d[17]), "+f"(d[18]), "+f"(d[19]), "+f"(d[20]), "+f"(d[21]), "+f"(d[22]), "+f"(d[23]),
      "+f"(d[24]), "+f"(d[25]), "+f"(d[26]), "+f"(d[27]), "+f"(d[28]), "+f"(d[29]), "+f"(d[30]), "+f"(d[31]),
      "+f"(d[32]), "+f"(d[33]), "+f"(d[34]), "+f"(d[35])
    : "l"(da), "l"(db), "r"(sd));
}

__device__ __forceinline__ void wgmma_rs_n16(float* d, const uint32_t* a, uint64_t db, int sd) {
  asm volatile("{ .reg .pred p; setp.ne.b32 p, %13, 0;\n"
      "wgmma.mma_async.sync.aligned.m64n16k16.f32.bf16.bf16 {"
      "%0,%1,%2,%3,%4,%5,%6,%7"
      "}, {%8,%9,%10,%11}, %12, p, 1, 1, 0; }"
    : "+f"(d[0]), "+f"(d[1]), "+f"(d[2]), "+f"(d[3]), "+f"(d[4]), "+f"(d[5]), "+f"(d[6]), "+f"(d[7])
    : "r"(a[0]), "r"(a[1]), "r"(a[2]), "r"(a[3]), "l"(db), "r"(sd));
}

__device__ __forceinline__ void wgmma_rs_n32(float* d, const uint32_t* a, uint64_t db, int sd) {
  asm volatile("{ .reg .pred p; setp.ne.b32 p, %21, 0;\n"
      "wgmma.mma_async.sync.aligned.m64n32k16.f32.bf16.bf16 {"
      "%0,%1,%2,%3,%4,%5,%6,%7,%8,%9,%10,%11,%12,%13,%14,%15"
      "}, {%16,%17,%18,%19}, %20, p, 1, 1, 0; }"
    : "+f"(d[0]), "+f"(d[1]), "+f"(d[2]), "+f"(d[3]), "+f"(d[4]), "+f"(d[5]), "+f"(d[6]), "+f"(d[7]),
      "+f"(d[8]), "+f"(d[9]), "+f"(d[10]), "+f"(d[11]), "+f"(d[12]), "+f"(d[13]), "+f"(d[14]), "+f"(d[15])
    : "r"(a[0]), "r"(a[1]), "r"(a[2]), "r"(a[3]), "l"(db), "r"(sd));
}

__device__ __forceinline__ void wgmma_rs_n48(float* d, const uint32_t* a, uint64_t db, int sd) {
  asm volatile("{ .reg .pred p; setp.ne.b32 p, %29, 0;\n"
      "wgmma.mma_async.sync.aligned.m64n48k16.f32.bf16.bf16 {"
      "%0,%1,%2,%3,%4,%5,%6,%7,%8,%9,%10,%11,%12,%13,%14,%15,"
      "%16,%17,%18,%19,%20,%21,%22,%23"
      "}, {%24,%25,%26,%27}, %28, p, 1, 1, 0; }"
    : "+f"(d[0]), "+f"(d[1]), "+f"(d[2]), "+f"(d[3]), "+f"(d[4]), "+f"(d[5]), "+f"(d[6]), "+f"(d[7]),
      "+f"(d[8]), "+f"(d[9]), "+f"(d[10]), "+f"(d[11]), "+f"(d[12]), "+f"(d[13]), "+f"(d[14]), "+f"(d[15]),
      "+f"(d[16]), "+f"(d[17]), "+f"(d[18]), "+f"(d[19]), "+f"(d[20]), "+f"(d[21]), "+f"(d[22]), "+f"(d[23])
    : "r"(a[0]), "r"(a[1]), "r"(a[2]), "r"(a[3]), "l"(db), "r"(sd));
}

__device__ __forceinline__ void wgmma_rs_n64(float* d, const uint32_t* a, uint64_t db, int sd) {
  asm volatile("{ .reg .pred p; setp.ne.b32 p, %37, 0;\n"
      "wgmma.mma_async.sync.aligned.m64n64k16.f32.bf16.bf16 {"
      "%0,%1,%2,%3,%4,%5,%6,%7,%8,%9,%10,%11,%12,%13,%14,%15,"
      "%16,%17,%18,%19,%20,%21,%22,%23,%24,%25,%26,%27,%28,%29,%30,%31"
      "}, {%32,%33,%34,%35}, %36, p, 1, 1, 0; }"
    : "+f"(d[0]), "+f"(d[1]), "+f"(d[2]), "+f"(d[3]), "+f"(d[4]), "+f"(d[5]), "+f"(d[6]), "+f"(d[7]),
      "+f"(d[8]), "+f"(d[9]), "+f"(d[10]), "+f"(d[11]), "+f"(d[12]), "+f"(d[13]), "+f"(d[14]), "+f"(d[15]),
      "+f"(d[16]), "+f"(d[17]), "+f"(d[18]), "+f"(d[19]), "+f"(d[20]), "+f"(d[21]), "+f"(d[22]), "+f"(d[23]),
      "+f"(d[24]), "+f"(d[25]), "+f"(d[26]), "+f"(d[27]), "+f"(d[28]), "+f"(d[29]), "+f"(d[30]), "+f"(d[31])
    : "r"(a[0]), "r"(a[1]), "r"(a[2]), "r"(a[3]), "l"(db), "r"(sd));
}

__device__ __forceinline__ void wgmma_rs_n80(float* d, const uint32_t* a, uint64_t db, int sd) {
  asm volatile("{ .reg .pred p; setp.ne.b32 p, %45, 0;\n"
      "wgmma.mma_async.sync.aligned.m64n80k16.f32.bf16.bf16 {"
      "%0,%1,%2,%3,%4,%5,%6,%7,%8,%9,%10,%11,%12,%13,%14,%15,"
      "%16,%17,%18,%19,%20,%21,%22,%23,%24,%25,%26,%27,%28,%29,%30,%31,"
      "%32,%33,%34,%35,%36,%37,%38,%39"
      "}, {%40,%41,%42,%43}, %44, p, 1, 1, 0; }"
    : "+f"(d[0]), "+f"(d[1]), "+f"(d[2]), "+f"(d[3]), "+f"(d[4]), "+f"(d[5]), "+f"(d[6]), "+f"(d[7]),
      "+f"(d[8]), "+f"(d[9]), "+f"(d[10]), "+f"(d[11]), "+f"(d[12]), "+f"(d[13]), "+f"(d[14]), "+f"(d[15]),
      "+f"(d[16]), "+f"(d[17]), "+f"(d[18]), "+f"(d[19]), "+f"(d[20]), "+f"(d[21]), "+f"(d[22]), "+f"(d[23]),
      "+f"(d[24]), "+f"(d[25]), "+f"(d[26]), "+f"(d[27]), "+f"(d[28]), "+f"(d[29]), "+f"(d[30]), "+f"(d[31]),
      "+f"(d[32]), "+f"(d[33]), "+f"(d[34]), "+f"(d[35]), "+f"(d[36]), "+f"(d[37]), "+f"(d[38]), "+f"(d[39])
    : "r"(a[0]), "r"(a[1]), "r"(a[2]), "r"(a[3]), "l"(db), "r"(sd));
}

__device__ __forceinline__ void wgmma_rs_n96(float* d, const uint32_t* a, uint64_t db, int sd) {
  asm volatile("{ .reg .pred p; setp.ne.b32 p, %53, 0;\n"
      "wgmma.mma_async.sync.aligned.m64n96k16.f32.bf16.bf16 {"
      "%0,%1,%2,%3,%4,%5,%6,%7,%8,%9,%10,%11,%12,%13,%14,%15,"
      "%16,%17,%18,%19,%20,%21,%22,%23,%24,%25,%26,%27,%28,%29,%30,%31,"
      "%32,%33,%34,%35,%36,%37,%38,%39,%40,%41,%42,%43,%44,%45,%46,%47"
      "}, {%48,%49,%50,%51}, %52, p, 1, 1, 0; }"
    : "+f"(d[0]), "+f"(d[1]), "+f"(d[2]), "+f"(d[3]), "+f"(d[4]), "+f"(d[5]), "+f"(d[6]), "+f"(d[7]),
      "+f"(d[8]), "+f"(d[9]), "+f"(d[10]), "+f"(d[11]), "+f"(d[12]), "+f"(d[13]), "+f"(d[14]), "+f"(d[15]),
      "+f"(d[16]), "+f"(d[17]), "+f"(d[18]), "+f"(d[19]), "+f"(d[20]), "+f"(d[21]), "+f"(d[22]), "+f"(d[23]),
      "+f"(d[24]), "+f"(d[25]), "+f"(d[26]), "+f"(d[27]), "+f"(d[28]), "+f"(d[29]), "+f"(d[30]), "+f"(d[31]),
      "+f"(d[32]), "+f"(d[33]), "+f"(d[34]), "+f"(d[35]), "+f"(d[36]), "+f"(d[37]), "+f"(d[38]), "+f"(d[39]),
      "+f"(d[40]), "+f"(d[41]), "+f"(d[42]), "+f"(d[43]), "+f"(d[44]), "+f"(d[45]), "+f"(d[46]), "+f"(d[47])
    : "r"(a[0]), "r"(a[1]), "r"(a[2]), "r"(a[3]), "l"(db), "r"(sd));
}

__device__ __forceinline__ void wgmma_rs_n112(float* d, const uint32_t* a, uint64_t db, int sd) {
  asm volatile("{ .reg .pred p; setp.ne.b32 p, %61, 0;\n"
      "wgmma.mma_async.sync.aligned.m64n112k16.f32.bf16.bf16 {"
      "%0,%1,%2,%3,%4,%5,%6,%7,%8,%9,%10,%11,%12,%13,%14,%15,"
      "%16,%17,%18,%19,%20,%21,%22,%23,%24,%25,%26,%27,%28,%29,%30,%31,"
      "%32,%33,%34,%35,%36,%37,%38,%39,%40,%41,%42,%43,%44,%45,%46,%47,"
      "%48,%49,%50,%51,%52,%53,%54,%55"
      "}, {%56,%57,%58,%59}, %60, p, 1, 1, 0; }"
    : "+f"(d[0]), "+f"(d[1]), "+f"(d[2]), "+f"(d[3]), "+f"(d[4]), "+f"(d[5]), "+f"(d[6]), "+f"(d[7]),
      "+f"(d[8]), "+f"(d[9]), "+f"(d[10]), "+f"(d[11]), "+f"(d[12]), "+f"(d[13]), "+f"(d[14]), "+f"(d[15]),
      "+f"(d[16]), "+f"(d[17]), "+f"(d[18]), "+f"(d[19]), "+f"(d[20]), "+f"(d[21]), "+f"(d[22]), "+f"(d[23]),
      "+f"(d[24]), "+f"(d[25]), "+f"(d[26]), "+f"(d[27]), "+f"(d[28]), "+f"(d[29]), "+f"(d[30]), "+f"(d[31]),
      "+f"(d[32]), "+f"(d[33]), "+f"(d[34]), "+f"(d[35]), "+f"(d[36]), "+f"(d[37]), "+f"(d[38]), "+f"(d[39]),
      "+f"(d[40]), "+f"(d[41]), "+f"(d[42]), "+f"(d[43]), "+f"(d[44]), "+f"(d[45]), "+f"(d[46]), "+f"(d[47]),
      "+f"(d[48]), "+f"(d[49]), "+f"(d[50]), "+f"(d[51]), "+f"(d[52]), "+f"(d[53]), "+f"(d[54]), "+f"(d[55])
    : "r"(a[0]), "r"(a[1]), "r"(a[2]), "r"(a[3]), "l"(db), "r"(sd));
}

__device__ __forceinline__ void wgmma_rs_n128(float* d, const uint32_t* a, uint64_t db, int sd) {
  asm volatile("{ .reg .pred p; setp.ne.b32 p, %69, 0;\n"
      "wgmma.mma_async.sync.aligned.m64n128k16.f32.bf16.bf16 {"
      "%0,%1,%2,%3,%4,%5,%6,%7,%8,%9,%10,%11,%12,%13,%14,%15,"
      "%16,%17,%18,%19,%20,%21,%22,%23,%24,%25,%26,%27,%28,%29,%30,%31,"
      "%32,%33,%34,%35,%36,%37,%38,%39,%40,%41,%42,%43,%44,%45,%46,%47,"
      "%48,%49,%50,%51,%52,%53,%54,%55,%56,%57,%58,%59,%60,%61,%62,%63"
      "}, {%64,%65,%66,%67}, %68, p, 1, 1, 0; }"
    : "+f"(d[0]), "+f"(d[1]), "+f"(d[2]), "+f"(d[3]), "+f"(d[4]), "+f"(d[5]), "+f"(d[6]), "+f"(d[7]),
      "+f"(d[8]), "+f"(d[9]), "+f"(d[10]), "+f"(d[11]), "+f"(d[12]), "+f"(d[13]), "+f"(d[14]), "+f"(d[15]),
      "+f"(d[16]), "+f"(d[17]), "+f"(d[18]), "+f"(d[19]), "+f"(d[20]), "+f"(d[21]), "+f"(d[22]), "+f"(d[23]),
      "+f"(d[24]), "+f"(d[25]), "+f"(d[26]), "+f"(d[27]), "+f"(d[28]), "+f"(d[29]), "+f"(d[30]), "+f"(d[31]),
      "+f"(d[32]), "+f"(d[33]), "+f"(d[34]), "+f"(d[35]), "+f"(d[36]), "+f"(d[37]), "+f"(d[38]), "+f"(d[39]),
      "+f"(d[40]), "+f"(d[41]), "+f"(d[42]), "+f"(d[43]), "+f"(d[44]), "+f"(d[45]), "+f"(d[46]), "+f"(d[47]),
      "+f"(d[48]), "+f"(d[49]), "+f"(d[50]), "+f"(d[51]), "+f"(d[52]), "+f"(d[53]), "+f"(d[54]), "+f"(d[55]),
      "+f"(d[56]), "+f"(d[57]), "+f"(d[58]), "+f"(d[59]), "+f"(d[60]), "+f"(d[61]), "+f"(d[62]), "+f"(d[63])
    : "r"(a[0]), "r"(a[1]), "r"(a[2]), "r"(a[3]), "l"(db), "r"(sd));
}

__device__ __forceinline__ void wgmma_rs_n144(float* d, const uint32_t* a, uint64_t db, int sd) {
  asm volatile("{ .reg .pred p; setp.ne.b32 p, %77, 0;\n"
      "wgmma.mma_async.sync.aligned.m64n144k16.f32.bf16.bf16 {"
      "%0,%1,%2,%3,%4,%5,%6,%7,%8,%9,%10,%11,%12,%13,%14,%15,"
      "%16,%17,%18,%19,%20,%21,%22,%23,%24,%25,%26,%27,%28,%29,%30,%31,"
      "%32,%33,%34,%35,%36,%37,%38,%39,%40,%41,%42,%43,%44,%45,%46,%47,"
      "%48,%49,%50,%51,%52,%53,%54,%55,%56,%57,%58,%59,%60,%61,%62,%63,"
      "%64,%65,%66,%67,%68,%69,%70,%71"
      "}, {%72,%73,%74,%75}, %76, p, 1, 1, 0; }"
    : "+f"(d[0]), "+f"(d[1]), "+f"(d[2]), "+f"(d[3]), "+f"(d[4]), "+f"(d[5]), "+f"(d[6]), "+f"(d[7]),
      "+f"(d[8]), "+f"(d[9]), "+f"(d[10]), "+f"(d[11]), "+f"(d[12]), "+f"(d[13]), "+f"(d[14]), "+f"(d[15]),
      "+f"(d[16]), "+f"(d[17]), "+f"(d[18]), "+f"(d[19]), "+f"(d[20]), "+f"(d[21]), "+f"(d[22]), "+f"(d[23]),
      "+f"(d[24]), "+f"(d[25]), "+f"(d[26]), "+f"(d[27]), "+f"(d[28]), "+f"(d[29]), "+f"(d[30]), "+f"(d[31]),
      "+f"(d[32]), "+f"(d[33]), "+f"(d[34]), "+f"(d[35]), "+f"(d[36]), "+f"(d[37]), "+f"(d[38]), "+f"(d[39]),
      "+f"(d[40]), "+f"(d[41]), "+f"(d[42]), "+f"(d[43]), "+f"(d[44]), "+f"(d[45]), "+f"(d[46]), "+f"(d[47]),
      "+f"(d[48]), "+f"(d[49]), "+f"(d[50]), "+f"(d[51]), "+f"(d[52]), "+f"(d[53]), "+f"(d[54]), "+f"(d[55]),
      "+f"(d[56]), "+f"(d[57]), "+f"(d[58]), "+f"(d[59]), "+f"(d[60]), "+f"(d[61]), "+f"(d[62]), "+f"(d[63]),
      "+f"(d[64]), "+f"(d[65]), "+f"(d[66]), "+f"(d[67]), "+f"(d[68]), "+f"(d[69]), "+f"(d[70]), "+f"(d[71])
    : "r"(a[0]), "r"(a[1]), "r"(a[2]), "r"(a[3]), "l"(db), "r"(sd));
}

__device__ __forceinline__ void wgmma_rs_n160(float* d, const uint32_t* a, uint64_t db, int sd) {
  asm volatile("{ .reg .pred p; setp.ne.b32 p, %85, 0;\n"
      "wgmma.mma_async.sync.aligned.m64n160k16.f32.bf16.bf16 {"
      "%0,%1,%2,%3,%4,%5,%6,%7,%8,%9,%10,%11,%12,%13,%14,%15,"
      "%16,%17,%18,%19,%20,%21,%22,%23,%24,%25,%26,%27,%28,%29,%30,%31,"
      "%32,%33,%34,%35,%36,%37,%38,%39,%40,%41,%42,%43,%44,%45,%46,%47,"
      "%48,%49,%50,%51,%52,%53,%54,%55,%56,%57,%58,%59,%60,%61,%62,%63,"
      "%64,%65,%66,%67,%68,%69,%70,%71,%72,%73,%74,%75,%76,%77,%78,%79"
      "}, {%80,%81,%82,%83}, %84, p, 1, 1, 0; }"
    : "+f"(d[0]), "+f"(d[1]), "+f"(d[2]), "+f"(d[3]), "+f"(d[4]), "+f"(d[5]), "+f"(d[6]), "+f"(d[7]),
      "+f"(d[8]), "+f"(d[9]), "+f"(d[10]), "+f"(d[11]), "+f"(d[12]), "+f"(d[13]), "+f"(d[14]), "+f"(d[15]),
      "+f"(d[16]), "+f"(d[17]), "+f"(d[18]), "+f"(d[19]), "+f"(d[20]), "+f"(d[21]), "+f"(d[22]), "+f"(d[23]),
      "+f"(d[24]), "+f"(d[25]), "+f"(d[26]), "+f"(d[27]), "+f"(d[28]), "+f"(d[29]), "+f"(d[30]), "+f"(d[31]),
      "+f"(d[32]), "+f"(d[33]), "+f"(d[34]), "+f"(d[35]), "+f"(d[36]), "+f"(d[37]), "+f"(d[38]), "+f"(d[39]),
      "+f"(d[40]), "+f"(d[41]), "+f"(d[42]), "+f"(d[43]), "+f"(d[44]), "+f"(d[45]), "+f"(d[46]), "+f"(d[47]),
      "+f"(d[48]), "+f"(d[49]), "+f"(d[50]), "+f"(d[51]), "+f"(d[52]), "+f"(d[53]), "+f"(d[54]), "+f"(d[55]),
      "+f"(d[56]), "+f"(d[57]), "+f"(d[58]), "+f"(d[59]), "+f"(d[60]), "+f"(d[61]), "+f"(d[62]), "+f"(d[63]),
      "+f"(d[64]), "+f"(d[65]), "+f"(d[66]), "+f"(d[67]), "+f"(d[68]), "+f"(d[69]), "+f"(d[70]), "+f"(d[71]),
      "+f"(d[72]), "+f"(d[73]), "+f"(d[74]), "+f"(d[75]), "+f"(d[76]), "+f"(d[77]), "+f"(d[78]), "+f"(d[79])
    : "r"(a[0]), "r"(a[1]), "r"(a[2]), "r"(a[3]), "l"(db), "r"(sd));
}

__device__ __forceinline__ void wgmma_rs_n176(float* d, const uint32_t* a, uint64_t db, int sd) {
  asm volatile("{ .reg .pred p; setp.ne.b32 p, %93, 0;\n"
      "wgmma.mma_async.sync.aligned.m64n176k16.f32.bf16.bf16 {"
      "%0,%1,%2,%3,%4,%5,%6,%7,%8,%9,%10,%11,%12,%13,%14,%15,"
      "%16,%17,%18,%19,%20,%21,%22,%23,%24,%25,%26,%27,%28,%29,%30,%31,"
      "%32,%33,%34,%35,%36,%37,%38,%39,%40,%41,%42,%43,%44,%45,%46,%47,"
      "%48,%49,%50,%51,%52,%53,%54,%55,%56,%57,%58,%59,%60,%61,%62,%63,"
      "%64,%65,%66,%67,%68,%69,%70,%71,%72,%73,%74,%75,%76,%77,%78,%79,"
      "%80,%81,%82,%83,%84,%85,%86,%87"
      "}, {%88,%89,%90,%91}, %92, p, 1, 1, 0; }"
    : "+f"(d[0]), "+f"(d[1]), "+f"(d[2]), "+f"(d[3]), "+f"(d[4]), "+f"(d[5]), "+f"(d[6]), "+f"(d[7]),
      "+f"(d[8]), "+f"(d[9]), "+f"(d[10]), "+f"(d[11]), "+f"(d[12]), "+f"(d[13]), "+f"(d[14]), "+f"(d[15]),
      "+f"(d[16]), "+f"(d[17]), "+f"(d[18]), "+f"(d[19]), "+f"(d[20]), "+f"(d[21]), "+f"(d[22]), "+f"(d[23]),
      "+f"(d[24]), "+f"(d[25]), "+f"(d[26]), "+f"(d[27]), "+f"(d[28]), "+f"(d[29]), "+f"(d[30]), "+f"(d[31]),
      "+f"(d[32]), "+f"(d[33]), "+f"(d[34]), "+f"(d[35]), "+f"(d[36]), "+f"(d[37]), "+f"(d[38]), "+f"(d[39]),
      "+f"(d[40]), "+f"(d[41]), "+f"(d[42]), "+f"(d[43]), "+f"(d[44]), "+f"(d[45]), "+f"(d[46]), "+f"(d[47]),
      "+f"(d[48]), "+f"(d[49]), "+f"(d[50]), "+f"(d[51]), "+f"(d[52]), "+f"(d[53]), "+f"(d[54]), "+f"(d[55]),
      "+f"(d[56]), "+f"(d[57]), "+f"(d[58]), "+f"(d[59]), "+f"(d[60]), "+f"(d[61]), "+f"(d[62]), "+f"(d[63]),
      "+f"(d[64]), "+f"(d[65]), "+f"(d[66]), "+f"(d[67]), "+f"(d[68]), "+f"(d[69]), "+f"(d[70]), "+f"(d[71]),
      "+f"(d[72]), "+f"(d[73]), "+f"(d[74]), "+f"(d[75]), "+f"(d[76]), "+f"(d[77]), "+f"(d[78]), "+f"(d[79]),
      "+f"(d[80]), "+f"(d[81]), "+f"(d[82]), "+f"(d[83]), "+f"(d[84]), "+f"(d[85]), "+f"(d[86]), "+f"(d[87])
    : "r"(a[0]), "r"(a[1]), "r"(a[2]), "r"(a[3]), "l"(db), "r"(sd));
}

__device__ __forceinline__ void wgmma_rs_n192(float* d, const uint32_t* a, uint64_t db, int sd) {
  asm volatile("{ .reg .pred p; setp.ne.b32 p, %101, 0;\n"
      "wgmma.mma_async.sync.aligned.m64n192k16.f32.bf16.bf16 {"
      "%0,%1,%2,%3,%4,%5,%6,%7,%8,%9,%10,%11,%12,%13,%14,%15,"
      "%16,%17,%18,%19,%20,%21,%22,%23,%24,%25,%26,%27,%28,%29,%30,%31,"
      "%32,%33,%34,%35,%36,%37,%38,%39,%40,%41,%42,%43,%44,%45,%46,%47,"
      "%48,%49,%50,%51,%52,%53,%54,%55,%56,%57,%58,%59,%60,%61,%62,%63,"
      "%64,%65,%66,%67,%68,%69,%70,%71,%72,%73,%74,%75,%76,%77,%78,%79,"
      "%80,%81,%82,%83,%84,%85,%86,%87,%88,%89,%90,%91,%92,%93,%94,%95"
      "}, {%96,%97,%98,%99}, %100, p, 1, 1, 0; }"
    : "+f"(d[0]), "+f"(d[1]), "+f"(d[2]), "+f"(d[3]), "+f"(d[4]), "+f"(d[5]), "+f"(d[6]), "+f"(d[7]),
      "+f"(d[8]), "+f"(d[9]), "+f"(d[10]), "+f"(d[11]), "+f"(d[12]), "+f"(d[13]), "+f"(d[14]), "+f"(d[15]),
      "+f"(d[16]), "+f"(d[17]), "+f"(d[18]), "+f"(d[19]), "+f"(d[20]), "+f"(d[21]), "+f"(d[22]), "+f"(d[23]),
      "+f"(d[24]), "+f"(d[25]), "+f"(d[26]), "+f"(d[27]), "+f"(d[28]), "+f"(d[29]), "+f"(d[30]), "+f"(d[31]),
      "+f"(d[32]), "+f"(d[33]), "+f"(d[34]), "+f"(d[35]), "+f"(d[36]), "+f"(d[37]), "+f"(d[38]), "+f"(d[39]),
      "+f"(d[40]), "+f"(d[41]), "+f"(d[42]), "+f"(d[43]), "+f"(d[44]), "+f"(d[45]), "+f"(d[46]), "+f"(d[47]),
      "+f"(d[48]), "+f"(d[49]), "+f"(d[50]), "+f"(d[51]), "+f"(d[52]), "+f"(d[53]), "+f"(d[54]), "+f"(d[55]),
      "+f"(d[56]), "+f"(d[57]), "+f"(d[58]), "+f"(d[59]), "+f"(d[60]), "+f"(d[61]), "+f"(d[62]), "+f"(d[63]),
      "+f"(d[64]), "+f"(d[65]), "+f"(d[66]), "+f"(d[67]), "+f"(d[68]), "+f"(d[69]), "+f"(d[70]), "+f"(d[71]),
      "+f"(d[72]), "+f"(d[73]), "+f"(d[74]), "+f"(d[75]), "+f"(d[76]), "+f"(d[77]), "+f"(d[78]), "+f"(d[79]),
      "+f"(d[80]), "+f"(d[81]), "+f"(d[82]), "+f"(d[83]), "+f"(d[84]), "+f"(d[85]), "+f"(d[86]), "+f"(d[87]),
      "+f"(d[88]), "+f"(d[89]), "+f"(d[90]), "+f"(d[91]), "+f"(d[92]), "+f"(d[93]), "+f"(d[94]), "+f"(d[95])
    : "r"(a[0]), "r"(a[1]), "r"(a[2]), "r"(a[3]), "l"(db), "r"(sd));
}

__device__ __forceinline__ void wgmma_rs_n208(float* d, const uint32_t* a, uint64_t db, int sd) {
  asm volatile("{ .reg .pred p; setp.ne.b32 p, %109, 0;\n"
      "wgmma.mma_async.sync.aligned.m64n208k16.f32.bf16.bf16 {"
      "%0,%1,%2,%3,%4,%5,%6,%7,%8,%9,%10,%11,%12,%13,%14,%15,"
      "%16,%17,%18,%19,%20,%21,%22,%23,%24,%25,%26,%27,%28,%29,%30,%31,"
      "%32,%33,%34,%35,%36,%37,%38,%39,%40,%41,%42,%43,%44,%45,%46,%47,"
      "%48,%49,%50,%51,%52,%53,%54,%55,%56,%57,%58,%59,%60,%61,%62,%63,"
      "%64,%65,%66,%67,%68,%69,%70,%71,%72,%73,%74,%75,%76,%77,%78,%79,"
      "%80,%81,%82,%83,%84,%85,%86,%87,%88,%89,%90,%91,%92,%93,%94,%95,"
      "%96,%97,%98,%99,%100,%101,%102,%103"
      "}, {%104,%105,%106,%107}, %108, p, 1, 1, 0; }"
    : "+f"(d[0]), "+f"(d[1]), "+f"(d[2]), "+f"(d[3]), "+f"(d[4]), "+f"(d[5]), "+f"(d[6]), "+f"(d[7]),
      "+f"(d[8]), "+f"(d[9]), "+f"(d[10]), "+f"(d[11]), "+f"(d[12]), "+f"(d[13]), "+f"(d[14]), "+f"(d[15]),
      "+f"(d[16]), "+f"(d[17]), "+f"(d[18]), "+f"(d[19]), "+f"(d[20]), "+f"(d[21]), "+f"(d[22]), "+f"(d[23]),
      "+f"(d[24]), "+f"(d[25]), "+f"(d[26]), "+f"(d[27]), "+f"(d[28]), "+f"(d[29]), "+f"(d[30]), "+f"(d[31]),
      "+f"(d[32]), "+f"(d[33]), "+f"(d[34]), "+f"(d[35]), "+f"(d[36]), "+f"(d[37]), "+f"(d[38]), "+f"(d[39]),
      "+f"(d[40]), "+f"(d[41]), "+f"(d[42]), "+f"(d[43]), "+f"(d[44]), "+f"(d[45]), "+f"(d[46]), "+f"(d[47]),
      "+f"(d[48]), "+f"(d[49]), "+f"(d[50]), "+f"(d[51]), "+f"(d[52]), "+f"(d[53]), "+f"(d[54]), "+f"(d[55]),
      "+f"(d[56]), "+f"(d[57]), "+f"(d[58]), "+f"(d[59]), "+f"(d[60]), "+f"(d[61]), "+f"(d[62]), "+f"(d[63]),
      "+f"(d[64]), "+f"(d[65]), "+f"(d[66]), "+f"(d[67]), "+f"(d[68]), "+f"(d[69]), "+f"(d[70]), "+f"(d[71]),
      "+f"(d[72]), "+f"(d[73]), "+f"(d[74]), "+f"(d[75]), "+f"(d[76]), "+f"(d[77]), "+f"(d[78]), "+f"(d[79]),
      "+f"(d[80]), "+f"(d[81]), "+f"(d[82]), "+f"(d[83]), "+f"(d[84]), "+f"(d[85]), "+f"(d[86]), "+f"(d[87]),
      "+f"(d[88]), "+f"(d[89]), "+f"(d[90]), "+f"(d[91]), "+f"(d[92]), "+f"(d[93]), "+f"(d[94]), "+f"(d[95]),
      "+f"(d[96]), "+f"(d[97]), "+f"(d[98]), "+f"(d[99]), "+f"(d[100]), "+f"(d[101]), "+f"(d[102]), "+f"(d[103])
    : "r"(a[0]), "r"(a[1]), "r"(a[2]), "r"(a[3]), "l"(db), "r"(sd));
}

__device__ __forceinline__ void wgmma_rs_n224(float* d, const uint32_t* a, uint64_t db, int sd) {
  asm volatile("{ .reg .pred p; setp.ne.b32 p, %117, 0;\n"
      "wgmma.mma_async.sync.aligned.m64n224k16.f32.bf16.bf16 {"
      "%0,%1,%2,%3,%4,%5,%6,%7,%8,%9,%10,%11,%12,%13,%14,%15,"
      "%16,%17,%18,%19,%20,%21,%22,%23,%24,%25,%26,%27,%28,%29,%30,%31,"
      "%32,%33,%34,%35,%36,%37,%38,%39,%40,%41,%42,%43,%44,%45,%46,%47,"
      "%48,%49,%50,%51,%52,%53,%54,%55,%56,%57,%58,%59,%60,%61,%62,%63,"
      "%64,%65,%66,%67,%68,%69,%70,%71,%72,%73,%74,%75,%76,%77,%78,%79,"
      "%80,%81,%82,%83,%84,%85,%86,%87,%88,%89,%90,%91,%92,%93,%94,%95,"
      "%96,%97,%98,%99,%100,%101,%102,%103,%104,%105,%106,%107,%108,%109,%110,%111"
      "}, {%112,%113,%114,%115}, %116, p, 1, 1, 0; }"
    : "+f"(d[0]), "+f"(d[1]), "+f"(d[2]), "+f"(d[3]), "+f"(d[4]), "+f"(d[5]), "+f"(d[6]), "+f"(d[7]),
      "+f"(d[8]), "+f"(d[9]), "+f"(d[10]), "+f"(d[11]), "+f"(d[12]), "+f"(d[13]), "+f"(d[14]), "+f"(d[15]),
      "+f"(d[16]), "+f"(d[17]), "+f"(d[18]), "+f"(d[19]), "+f"(d[20]), "+f"(d[21]), "+f"(d[22]), "+f"(d[23]),
      "+f"(d[24]), "+f"(d[25]), "+f"(d[26]), "+f"(d[27]), "+f"(d[28]), "+f"(d[29]), "+f"(d[30]), "+f"(d[31]),
      "+f"(d[32]), "+f"(d[33]), "+f"(d[34]), "+f"(d[35]), "+f"(d[36]), "+f"(d[37]), "+f"(d[38]), "+f"(d[39]),
      "+f"(d[40]), "+f"(d[41]), "+f"(d[42]), "+f"(d[43]), "+f"(d[44]), "+f"(d[45]), "+f"(d[46]), "+f"(d[47]),
      "+f"(d[48]), "+f"(d[49]), "+f"(d[50]), "+f"(d[51]), "+f"(d[52]), "+f"(d[53]), "+f"(d[54]), "+f"(d[55]),
      "+f"(d[56]), "+f"(d[57]), "+f"(d[58]), "+f"(d[59]), "+f"(d[60]), "+f"(d[61]), "+f"(d[62]), "+f"(d[63]),
      "+f"(d[64]), "+f"(d[65]), "+f"(d[66]), "+f"(d[67]), "+f"(d[68]), "+f"(d[69]), "+f"(d[70]), "+f"(d[71]),
      "+f"(d[72]), "+f"(d[73]), "+f"(d[74]), "+f"(d[75]), "+f"(d[76]), "+f"(d[77]), "+f"(d[78]), "+f"(d[79]),
      "+f"(d[80]), "+f"(d[81]), "+f"(d[82]), "+f"(d[83]), "+f"(d[84]), "+f"(d[85]), "+f"(d[86]), "+f"(d[87]),
      "+f"(d[88]), "+f"(d[89]), "+f"(d[90]), "+f"(d[91]), "+f"(d[92]), "+f"(d[93]), "+f"(d[94]), "+f"(d[95]),
      "+f"(d[96]), "+f"(d[97]), "+f"(d[98]), "+f"(d[99]), "+f"(d[100]), "+f"(d[101]), "+f"(d[102]), "+f"(d[103]),
      "+f"(d[104]), "+f"(d[105]), "+f"(d[106]), "+f"(d[107]), "+f"(d[108]), "+f"(d[109]), "+f"(d[110]), "+f"(d[111])
    : "r"(a[0]), "r"(a[1]), "r"(a[2]), "r"(a[3]), "l"(db), "r"(sd));
}

__device__ __forceinline__ void wgmma_rs_n240(float* d, const uint32_t* a, uint64_t db, int sd) {
  asm volatile("{ .reg .pred p; setp.ne.b32 p, %125, 0;\n"
      "wgmma.mma_async.sync.aligned.m64n240k16.f32.bf16.bf16 {"
      "%0,%1,%2,%3,%4,%5,%6,%7,%8,%9,%10,%11,%12,%13,%14,%15,"
      "%16,%17,%18,%19,%20,%21,%22,%23,%24,%25,%26,%27,%28,%29,%30,%31,"
      "%32,%33,%34,%35,%36,%37,%38,%39,%40,%41,%42,%43,%44,%45,%46,%47,"
      "%48,%49,%50,%51,%52,%53,%54,%55,%56,%57,%58,%59,%60,%61,%62,%63,"
      "%64,%65,%66,%67,%68,%69,%70,%71,%72,%73,%74,%75,%76,%77,%78,%79,"
      "%80,%81,%82,%83,%84,%85,%86,%87,%88,%89,%90,%91,%92,%93,%94,%95,"
      "%96,%97,%98,%99,%100,%101,%102,%103,%104,%105,%106,%107,%108,%109,%110,%111,"
      "%112,%113,%114,%115,%116,%117,%118,%119"
      "}, {%120,%121,%122,%123}, %124, p, 1, 1, 0; }"
    : "+f"(d[0]), "+f"(d[1]), "+f"(d[2]), "+f"(d[3]), "+f"(d[4]), "+f"(d[5]), "+f"(d[6]), "+f"(d[7]),
      "+f"(d[8]), "+f"(d[9]), "+f"(d[10]), "+f"(d[11]), "+f"(d[12]), "+f"(d[13]), "+f"(d[14]), "+f"(d[15]),
      "+f"(d[16]), "+f"(d[17]), "+f"(d[18]), "+f"(d[19]), "+f"(d[20]), "+f"(d[21]), "+f"(d[22]), "+f"(d[23]),
      "+f"(d[24]), "+f"(d[25]), "+f"(d[26]), "+f"(d[27]), "+f"(d[28]), "+f"(d[29]), "+f"(d[30]), "+f"(d[31]),
      "+f"(d[32]), "+f"(d[33]), "+f"(d[34]), "+f"(d[35]), "+f"(d[36]), "+f"(d[37]), "+f"(d[38]), "+f"(d[39]),
      "+f"(d[40]), "+f"(d[41]), "+f"(d[42]), "+f"(d[43]), "+f"(d[44]), "+f"(d[45]), "+f"(d[46]), "+f"(d[47]),
      "+f"(d[48]), "+f"(d[49]), "+f"(d[50]), "+f"(d[51]), "+f"(d[52]), "+f"(d[53]), "+f"(d[54]), "+f"(d[55]),
      "+f"(d[56]), "+f"(d[57]), "+f"(d[58]), "+f"(d[59]), "+f"(d[60]), "+f"(d[61]), "+f"(d[62]), "+f"(d[63]),
      "+f"(d[64]), "+f"(d[65]), "+f"(d[66]), "+f"(d[67]), "+f"(d[68]), "+f"(d[69]), "+f"(d[70]), "+f"(d[71]),
      "+f"(d[72]), "+f"(d[73]), "+f"(d[74]), "+f"(d[75]), "+f"(d[76]), "+f"(d[77]), "+f"(d[78]), "+f"(d[79]),
      "+f"(d[80]), "+f"(d[81]), "+f"(d[82]), "+f"(d[83]), "+f"(d[84]), "+f"(d[85]), "+f"(d[86]), "+f"(d[87]),
      "+f"(d[88]), "+f"(d[89]), "+f"(d[90]), "+f"(d[91]), "+f"(d[92]), "+f"(d[93]), "+f"(d[94]), "+f"(d[95]),
      "+f"(d[96]), "+f"(d[97]), "+f"(d[98]), "+f"(d[99]), "+f"(d[100]), "+f"(d[101]), "+f"(d[102]), "+f"(d[103]),
      "+f"(d[104]), "+f"(d[105]), "+f"(d[106]), "+f"(d[107]), "+f"(d[108]), "+f"(d[109]), "+f"(d[110]), "+f"(d[111]),
      "+f"(d[112]), "+f"(d[113]), "+f"(d[114]), "+f"(d[115]), "+f"(d[116]), "+f"(d[117]), "+f"(d[118]), "+f"(d[119])
    : "r"(a[0]), "r"(a[1]), "r"(a[2]), "r"(a[3]), "l"(db), "r"(sd));
}

__device__ __forceinline__ void wgmma_rs_n256(float* d, const uint32_t* a, uint64_t db, int sd) {
  asm volatile("{ .reg .pred p; setp.ne.b32 p, %133, 0;\n"
      "wgmma.mma_async.sync.aligned.m64n256k16.f32.bf16.bf16 {"
      "%0,%1,%2,%3,%4,%5,%6,%7,%8,%9,%10,%11,%12,%13,%14,%15,"
      "%16,%17,%18,%19,%20,%21,%22,%23,%24,%25,%26,%27,%28,%29,%30,%31,"
      "%32,%33,%34,%35,%36,%37,%38,%39,%40,%41,%42,%43,%44,%45,%46,%47,"
      "%48,%49,%50,%51,%52,%53,%54,%55,%56,%57,%58,%59,%60,%61,%62,%63,"
      "%64,%65,%66,%67,%68,%69,%70,%71,%72,%73,%74,%75,%76,%77,%78,%79,"
      "%80,%81,%82,%83,%84,%85,%86,%87,%88,%89,%90,%91,%92,%93,%94,%95,"
      "%96,%97,%98,%99,%100,%101,%102,%103,%104,%105,%106,%107,%108,%109,%110,%111,"
      "%112,%113,%114,%115,%116,%117,%118,%119,%120,%121,%122,%123,%124,%125,%126,%127"
      "}, {%128,%129,%130,%131}, %132, p, 1, 1, 0; }"
    : "+f"(d[0]), "+f"(d[1]), "+f"(d[2]), "+f"(d[3]), "+f"(d[4]), "+f"(d[5]), "+f"(d[6]), "+f"(d[7]),
      "+f"(d[8]), "+f"(d[9]), "+f"(d[10]), "+f"(d[11]), "+f"(d[12]), "+f"(d[13]), "+f"(d[14]), "+f"(d[15]),
      "+f"(d[16]), "+f"(d[17]), "+f"(d[18]), "+f"(d[19]), "+f"(d[20]), "+f"(d[21]), "+f"(d[22]), "+f"(d[23]),
      "+f"(d[24]), "+f"(d[25]), "+f"(d[26]), "+f"(d[27]), "+f"(d[28]), "+f"(d[29]), "+f"(d[30]), "+f"(d[31]),
      "+f"(d[32]), "+f"(d[33]), "+f"(d[34]), "+f"(d[35]), "+f"(d[36]), "+f"(d[37]), "+f"(d[38]), "+f"(d[39]),
      "+f"(d[40]), "+f"(d[41]), "+f"(d[42]), "+f"(d[43]), "+f"(d[44]), "+f"(d[45]), "+f"(d[46]), "+f"(d[47]),
      "+f"(d[48]), "+f"(d[49]), "+f"(d[50]), "+f"(d[51]), "+f"(d[52]), "+f"(d[53]), "+f"(d[54]), "+f"(d[55]),
      "+f"(d[56]), "+f"(d[57]), "+f"(d[58]), "+f"(d[59]), "+f"(d[60]), "+f"(d[61]), "+f"(d[62]), "+f"(d[63]),
      "+f"(d[64]), "+f"(d[65]), "+f"(d[66]), "+f"(d[67]), "+f"(d[68]), "+f"(d[69]), "+f"(d[70]), "+f"(d[71]),
      "+f"(d[72]), "+f"(d[73]), "+f"(d[74]), "+f"(d[75]), "+f"(d[76]), "+f"(d[77]), "+f"(d[78]), "+f"(d[79]),
      "+f"(d[80]), "+f"(d[81]), "+f"(d[82]), "+f"(d[83]), "+f"(d[84]), "+f"(d[85]), "+f"(d[86]), "+f"(d[87]),
      "+f"(d[88]), "+f"(d[89]), "+f"(d[90]), "+f"(d[91]), "+f"(d[92]), "+f"(d[93]), "+f"(d[94]), "+f"(d[95]),
      "+f"(d[96]), "+f"(d[97]), "+f"(d[98]), "+f"(d[99]), "+f"(d[100]), "+f"(d[101]), "+f"(d[102]), "+f"(d[103]),
      "+f"(d[104]), "+f"(d[105]), "+f"(d[106]), "+f"(d[107]), "+f"(d[108]), "+f"(d[109]), "+f"(d[110]), "+f"(d[111]),
      "+f"(d[112]), "+f"(d[113]), "+f"(d[114]), "+f"(d[115]), "+f"(d[116]), "+f"(d[117]), "+f"(d[118]), "+f"(d[119]),
      "+f"(d[120]), "+f"(d[121]), "+f"(d[122]), "+f"(d[123]), "+f"(d[124]), "+f"(d[125]), "+f"(d[126]), "+f"(d[127])
    : "r"(a[0]), "r"(a[1]), "r"(a[2]), "r"(a[3]), "l"(db), "r"(sd));
}

__device__ __forceinline__ void ln_finish(float mean, float var, float& mb, float& rinv) {
  mb = round_bf16(mean);
  float den = round_bf16(sqrtf(round_bf16(round_bf16(var) + 1e-5f)));
  rinv = 1.0f / den;
}
__device__ __forceinline__ uint32_t ln_apply(uint32_t x2, uint32_t mb2, float rinv) {
  uint32_t c = bsub2(x2, mb2);
  return pack_bf16(bf_lo(c) * rinv, bf_hi(c) * rinv);
}
__device__ __forceinline__ int conv_channel(int cta, int i) {
  if (i < N_SHORT) { const int e = i * N_CONV_CTA + cta; return (e / 66) * 72 + e % 66; }
  const int l = (i - N_SHORT) * 4 + cta;
  return (l / 6) * 72 + 66 + l % 6;
}

__global__ void __cluster_dims__(2, 1, 1) __launch_bounds__(384, 1) fused_kernel(const __grid_constant__ Params P) {
  extern __shared__ uint8_t smem_raw[];
  const uint32_t sb = (smem_u32(smem_raw) + 1023) & ~1023u;
  const uint32_t bars = sb + SM_BAR;
  const int tid = threadIdx.x, warp = tid >> 5, lane = tid & 31;
  const int cl = blockIdx.x >> 1, rank = blockIdx.x & 1;
  const int p0 = P.roles.p0[cl], p0b = 2 * p0 + rank;
  if (tid == 0) TLREC(0);

  uint32_t xr[18];
  const int ln_row = p0b * 16 + warp * 2 + (lane >> 4);
  if (warp < 8 && p0 >= 0) {
    const uint2* src = reinterpret_cast<const uint2*>(P.x + (size_t)ln_row * D_) + (lane & 15);
#pragma unroll
    for (int j = 0; j < 9; j++) asm volatile("ld.global.nc.v2.u32 {%0,%1}, [%2];" : "=r"(xr[2 * j]), "=r"(xr[2 * j + 1]) : "l"(src + 16 * j));
  }
  const uint32_t tag = ld_flag(&g_epoch) + 1;
  const int g1m = P.roles.g1m[cl], g1n = P.roles.g1n[cl], cv = P.roles.cv[cl], g2m = P.roles.g2m[cl], g2n = P.roles.g2n[cl];
  const int cvc = 2 * cv + rank;
  const int n_conv = cv < 0 ? 0 : (cv < 2 ? N_SHORT + N_LONG_EXTRA : N_SHORT);
  const int it2 = g1m >= 0 ? G1_KB : 0;
  const int xslot = (it2 + G2_KB) % NSTAGE;
  const int dk = g2n * 144 + rank * 72;
  if (tid == 256) {
    for (int s = 0; s < NSTAGE; s++) { mbar_init(bars + 8 * (B_FULL + s), 1); mbar_init(bars + 8 * (B_EMPTY + s), 2); }
    for (int s = 0; s < CV_NSLOT; s++) { mbar_init(bars + 8 * (B_CFULL + s), 1); mbar_init(bars + 8 * (B_CEMPTY + s), 4); }
    mbar_init(bars + 8 * B_CDONE, 8); mbar_init(bars + 8 * B_XRDY, 1); mbar_init(bars + 8 * B_XFULL, 1); mbar_init(bars + 8 * (B_XFULL + 1), 1);
    mbar_init(bars + 8 * B_XT, 1); mbar_init(bars + 8 * B_Y2, 3);
    asm volatile("fence.mbarrier_init.release.cluster;" ::: "memory");
  }
  __syncthreads();
  asm volatile("barrier.cluster.arrive.relaxed.aligned;" ::: "memory");

  if (warp >= 8) {
    asm volatile("setmaxnreg.dec.sync.aligned.u32 56;");
    if (warp == 8) {
      asm volatile("barrier.cluster.wait.aligned;" ::: "memory");
      if (lane == 0) {
        if (g1m >= 0) {
          const int fg = (2 * g1m + rank) * 2, dg = g1n * 3;
          for (int s = 0; s < NSTAGE; s++) {
            mbar_expect_tx(bars + 8 * (B_FULL + s), G1_BYTES);
            tma3d(sb + s * SLOT, &P.m_w1, 0, s * 64, fg, bars + 8 * (B_FULL + s));
          }
          await(C_H, tag * 128);
          TLREC(2);
          fence_async_global();
          for (int s = 0; s < NSTAGE; s++) tma3d(sb + s * SLOT + 16384, &P.m_h, 0, s * 64, dg, bars + 8 * (B_FULL + s));
          for (int kb = NSTAGE; kb < G1_KB; kb++) {
            const int s = kb % NSTAGE;
            mbar_wait(bars + 8 * (B_EMPTY + s), ((kb / NSTAGE) - 1) & 1);
            mbar_expect_tx(bars + 8 * (B_FULL + s), G1_BYTES);
            tma3d(sb + s * SLOT, &P.m_w1, 0, kb * 64, fg, bars + 8 * (B_FULL + s));
            tma3d(sb + s * SLOT + 16384, &P.m_h, 0, kb * 64, dg, bars + 8 * (B_FULL + s));
          }
        } else {
          for (int i = 0; i < CV_NSLOT; i++) {
            mbar_expect_tx(bars + 8 * (B_CFULL + i), 8192 + 4096);
            bulk_load(sb + CV_BASE + i * CV_SLOT + CV_KOFF + 32, P.ssm_k + (size_t)conv_channel(cvc, i) * S_, 4096, bars + 8 * (B_CFULL + i));
          }
          int ready = -1;
          for (int i = 0; i < n_conv; i++) {
            const int ch = conv_channel(cvc, i), s = i % CV_NSLOT;
            const uint32_t slot = sb + CV_BASE + s * CV_SLOT, fb = bars + 8 * (B_CFULL + s);
            if (i >= CV_NSLOT) {
              mbar_wait(bars + 8 * (B_CEMPTY + s), ((i / CV_NSLOT) - 1) & 1);
              mbar_expect_tx(fb, 8192 + 4096);
              bulk_load(slot + CV_KOFF + 32, P.ssm_k + (size_t)ch * S_, 4096, fb);
            }
            const int r = ch / 96;
            if (r > ready) {
              await(C_KV + r, tag * 128);
              fence_async_global();
              if (r == 0) TLREC(18);
              ready = r;
            }
            bulk_load(slot, g_ub + (size_t)ch * 4096, 8192, fb);
          }
        }
        if (g2m >= 0) {
          const int sg = g2m * 2, ds = g2n * 144 + (rank ^ 1) * 72;
          const int cu0 = C_U + ((g2n * 144) / 192) * 4 + rank * 2, cu1 = C_U + ((g2n * 144 + 143) / 192) * 4 + rank * 2;
          const int npre = g1m >= 0 ? 4 : 3;
          for (int kb = 0; kb < npre; kb++) {
            const int p = it2 + kb, s = p % NSTAGE;
            if (p >= NSTAGE) mbar_wait(bars + 8 * (B_EMPTY + s), ((p / NSTAGE) - 1) & 1);
            mbar_expect_tx(bars + 8 * (B_FULL + s), G2_BYTES);
            tma3d(sb + s * SLOT, &P.m_w2, 0, (rank * G2_KB + 2 * kb) * 64, sg, bars + 8 * (B_FULL + s));
          }
          for (int kb = 0; kb < G2_KB; kb++) {
            const int p = it2 + kb, s = p % NSTAGE;
            const int k0 = (rank * G2_KB + (kb < 18 ? 2 * kb : 2 * kb - 35)) * 64;
            const uint32_t fb = bars + 8 * (B_FULL + s);
            if (kb == 0 || kb == 18) {
              await(cu0 + (kb != 0), tag * 18);
              await(cu1 + (kb != 0), tag * 18);
              fence_async_global();
              if (kb == 0) TLREC(6);
            }
            if (kb >= npre) {
              if (p >= NSTAGE) mbar_wait(bars + 8 * (B_EMPTY + s), ((p / NSTAGE) - 1) & 1);
              else if (kb == npre) { mbar_wait(bars + 8 * B_CDONE, 0); fence_async_smem(); }
              mbar_expect_tx(fb, G2_BYTES);
              tma3d(sb + s * SLOT, &P.m_w2, 0, k0, sg, fb);
            }
            tma2d(sb + s * SLOT + 16384, &P.m_uld, k0, ds, fb);
            tma2d(sb + s * SLOT + 16384 + 9216, &P.m_uld, k0, dk, fb);
            if (kb == 10) {
              mbar_expect_tx(bars + 8 * B_XT, 18432);
              for (int j = 0; j < 8; j++)
                tma2d(sb + ((xslot + 1 + (j >> 1)) % NSTAGE) * SLOT + G2_BYTES + (j & 1) * 2304, &P.m_x, dk, g2m * 128 + j * 16, bars + 8 * B_XT);
            }
          }
          mbar_expect_tx(bars + 8 * B_XFULL, 18432);
          mbar_expect_tx(bars + 8 * (B_XFULL + 1), 18432);
          mbar_wait(bars + 8 * (B_EMPTY + xslot), (((it2 + G2_KB) / NSTAGE) - 1) & 1);
          mbar_arrive_remote(mapa(bars + 8 * B_XRDY, rank ^ 1));
        }
      }
    } else {
      const int ht = tid - 288;
      if (p0 >= 0) {
        const int hf = ht / 48, pr = ht % 48;
        const int s0 = p0b * 16 + hf * 8;
        const bool first = s0 == 0, odd = lane & 1;
        for (int r = 0; r < KV_ROUNDS; r++) {
          const int d = r * 96 + 2 * pr;
          const __nv_bfloat16* kp = P.k + (ptrdiff_t)(s0 - 4) * D_ + d;
          const __nv_bfloat16* vp = P.v + (ptrdiff_t)(s0 - 1) * D_ + d;
          uint32_t kk[12], vv[9];
#pragma unroll
          for (int j = 0; j < 12; j++) kk[j] = (j < 4 && first) ? 0u : ldg32(kp + j * D_);
#pragma unroll
          for (int j = 0; j < 9; j++) vv[j] = (j < 1 && first) ? 0u : ldg32(vp + j * D_);
          const uint4 w = __ldg(reinterpret_cast<const uint4*>(P.shift_k + d * 4));
          const uint32_t w0 = __byte_perm(w.x, w.z, 0x5410), w1 = __byte_perm(w.x, w.z, 0x7632);
          const uint32_t w2 = __byte_perm(w.y, w.w, 0x5410), w3 = __byte_perm(w.y, w.w, 0x7632);
#pragma unroll
          for (int j = 0; j < 9; j++) {
            uint32_t a = bmul2(kk[j], w3);
            a = badd2(a, bmul2(kk[j + 1], w2));
            a = badd2(a, bmul2(kk[j + 2], w1));
            a = badd2(a, bmul2(kk[j + 3], w0));
            vv[j] = bmul2(a, vv[j]);
          }
          uint32_t da[8], db[8];
#pragma unroll
          for (int j = 0; j < 8; j++) {
            const uint32_t o = __shfl_xor_sync(0xffffffffu, odd ? vv[j] : vv[j + 1], 1);
            da[j] = odd ? o : vv[j];
            db[j] = odd ? vv[j + 1] : o;
          }
          uint4* dst = reinterpret_cast<uint4*>(g_ub + (size_t)(d & ~3) * 4096) + (1 - hf) * 256 + 2 * (127 - p0b) + odd;
#pragma unroll
          for (int c = 0; c < 2; c++) {
            const uint32_t sel = c ? 0x7632 : 0x5410;
            dst[c * 512] = make_uint4(__byte_perm(da[7], da[6], sel), __byte_perm(da[5], da[4], sel), __byte_perm(da[3], da[2], sel), __byte_perm(da[1], da[0], sel));
            dst[(c + 2) * 512] = make_uint4(__byte_perm(db[7], db[6], sel), __byte_perm(db[5], db[4], sel), __byte_perm(db[3], db[2], sel), __byte_perm(db[1], db[0], sel));
          }
          fence_async_global();
          bar_sync(1, 96);
          if (ht == 0) { signal(C_KV + r); TLREC(22 + r); }
          __syncwarp();
        }
      }
      __syncwarp();
      asm volatile("barrier.cluster.wait.aligned;" ::: "memory");
      if (g1m >= 0 && warp < 11 && lane == 0) {
        const int wg = warp - 9, fb64 = (2 * g1m + rank) * 2 + wg;
        const uint32_t stg = wg == 0 ? sb + SM_DED : sb + ((G1_KB - 1) % NSTAGE) * SLOT;
        for (int c = 0; c < 3; c++) {
          mbar_wait(bars + 8 * (B_CEMPTY + wg * 3 + c), 0);
          tma2d_store(&P.m_ust, stg + c * 8192, fb64 * 64, g1n * 192 + c * 64);
        }
        TLREC(13 + wg);
        bulk_commit();
        if (wg == 1) { bulk_wait_read(); mbar_arrive(bars + 8 * (B_EMPTY + (G1_KB - 1) % NSTAGE)); }
        bulk_wait_all();
        signal(C_U + g1n * 4 + (fb64 / G2_KB) * 2 + wg);
        TLREC(15 + wg);
      }
      __syncwarp();
      if (g2m >= 0) {
        const int s = g2m * 128 + (ht & 15) * 8;
        const __nv_bfloat16* up = g_ub + ((1 - (ht & 1)) * 256 + 2 * (127 - (s >> 4)) + 1) * 8;
        for (int i = 0; i < 12; i++) {
          if (i == 0 || i == 11) {
            if (ht == 64) await(i == 0 ? C_YA : C_YB, tag * (i == 0 ? 2 * N_CONV_CTA : 8));
            __syncwarp();
            bar_sync(1, 96);
            if (ht == 64) TLREC(i == 0 ? 8 : 19);
          }
          const int dl = 6 * i + (ht >> 4), d = dk + dl;
          const __nv_bfloat16* yp = g_yp + (size_t)d * 4 * S_ + s;
          uint4 pv[4];
#pragma unroll
          for (int w = 0; w < 4; w++) pv[w] = s >= 16 * w ? ldg128_cg(yp + w * (S_ - 16)) : make_uint4(0, 0, 0, 0);
          const uint4 uu = ldg128_cg(up + (size_t)d * 4096);
          const uint32_t dd = __byte_perm((uint32_t)__bfloat16_as_ushort(P.ssm_D[d]), 0, 0x1010);
          auto comb = [&](uint32_t a, uint32_t b, uint32_t c, uint32_t e, uint32_t u) {
            return badd2(pack_bf16((bf_lo(a) + bf_lo(b)) + (bf_lo(c) + bf_lo(e)), (bf_hi(a) + bf_hi(b)) + (bf_hi(c) + bf_hi(e))),
                         bmul2(__byte_perm(u, 0, 0x1032), dd));
          };
          sts128(sb + SM_DED + dl * 256 + (((ht & 15) ^ (dl & 7)) << 4),
                 make_uint4(comb(pv[0].x, pv[1].x, pv[2].x, pv[3].x, uu.w), comb(pv[0].y, pv[1].y, pv[2].y, pv[3].y, uu.z),
                            comb(pv[0].z, pv[1].z, pv[2].z, pv[3].z, uu.y), comb(pv[0].w, pv[1].w, pv[2].w, pv[3].w, uu.x)));
        }
        __syncwarp();
        if (lane == 0) mbar_arrive(bars + 8 * B_Y2);
        if (ht == 64) TLREC(31);
      }
    }
  } else {
    asm volatile("setmaxnreg.inc.sync.aligned.u32 224;");
    const int wg = warp >> 2, w = warp & 3, g = lane >> 2, t = lane & 3, wtid = tid & 127;
    if (p0 >= 0) {
      float c[36];
      float s0 = 0.f, s1 = 0.f;
#pragma unroll
      for (int i = 0; i < 18; i++) { c[2 * i] = bf_lo(xr[i]); c[2 * i + 1] = bf_hi(xr[i]); s0 += c[2 * i]; s1 += c[2 * i + 1]; }
      const float ml = (s0 + s1) * (1.0f / 36.0f);
      if (tid == 0 && ml != 123.456f) TLREC(28);
      s0 = 0.f; s1 = 0.f;
#pragma unroll
      for (int i = 0; i < 18; i++) { c[2 * i] -= ml; c[2 * i + 1] -= ml; s0 = fmaf(c[2 * i], c[2 * i], s0); s1 = fmaf(c[2 * i + 1], c[2 * i + 1], s1); }
      float m = ml, q = s0 + s1, n2 = 18.f;
#pragma unroll
      for (int o = 1; o < 16; o <<= 1) {
        const float mo = __shfl_xor_sync(0xffffffffu, m, o), qo = __shfl_xor_sync(0xffffffffu, q, o);
        const float dl = m - mo;
        q = fmaf(dl * dl, n2, q + qo);
        m = 0.5f * (m + mo);
        n2 *= 2.f;
      }
      const float var = q * (1.0f / 576.0f);
      float mb, rinv, mb2, rinv2;
      ln_finish(m, var, mb, rinv);
      ln_finish((m - mb) * rinv, var * rinv * rinv, mb2, rinv2);
      const float ca = rinv * rinv2, cb = fmaf(ml - mb, rinv, -mb2) * rinv2;
      uint2* dst = reinterpret_cast<uint2*>(g_h + (size_t)ln_row * D_) + (lane & 15);
#pragma unroll
      for (int j = 0; j < 9; j++)
        dst[16 * j] = make_uint2(pack_bf16(fmaf(c[4 * j], ca, cb), fmaf(c[4 * j + 1], ca, cb)), pack_bf16(fmaf(c[4 * j + 2], ca, cb), fmaf(c[4 * j + 3], ca, cb)));
      if ((lane & 15) == 0) g_stats[ln_row] = make_float2(mb, rinv);
      fence_async_global();
      bar_sync(2, 256);
      if (tid == 0) { TLREC(29); signal(C_H); TLREC(1); }
    }
    __syncwarp();
    asm volatile("barrier.cluster.wait.aligned;" ::: "memory");
    if (g1m >= 0) {
      const int frow = ((2 * g1m + rank) * 2 + wg) * 64 + w * 16 + g;
      const uint32_t bias0 = __byte_perm((uint32_t)__bfloat16_as_ushort(P.b1[frow]), 0, 0x1010);
      const uint32_t bias1 = __byte_perm((uint32_t)__bfloat16_as_ushort(P.b1[frow + 8]), 0, 0x1010);
      float acc[96];
#pragma unroll 1
      for (int kb = 0; kb < G1_KB; kb++) {
        const int s = kb % NSTAGE;
        const bool yield = wg == 1 && kb == G1_KB - G1_TAIL;
        if (yield) {
          wg_wait<0>();
          if (wtid == 0) mbar_arrive(bars + 8 * (B_EMPTY + (kb - 1) % NSTAGE));
          bar_sync(5, 256);
        }
        mbar_wait(bars + 8 * (B_FULL + s), (kb / NSTAGE) & 1);
        if (kb == 0 && tid == 0) TLREC(3);
        const uint64_t da = make_desc(sb + s * SLOT + wg * 8192, 8192, 1024, 1), db = make_desc(sb + s * SLOT + 16384, 8192, 1024, 1);
        wg_fence();
#pragma unroll
        for (int k = 0; k < 4; k++) wgmma_ss_n192_t11(acc, da + k * 128, db + k * 128, (kb | k) != 0);
        wg_commit();
        if (wg == 0 && kb == G1_KB - 1) bar_arrive(5, 256);
        wg_wait<1>();
        if (kb > 0 && !yield && wtid == 0) mbar_arrive(bars + 8 * (B_EMPTY + (kb - 1) % NSTAGE));
      }
      wg_wait<0>();
      pin_regs<96>(acc);
      if (wtid == 0) TLREC(4 + wg);
      if (wg == 0) { if (wtid == 0) mbar_arrive(bars + 8 * (B_EMPTY + (G1_KB - 1) % NSTAGE)); bar_arrive(6, 256); }
      else bar_sync(6, 256);
      const uint32_t stg = wg == 0 ? sb + SM_DED : sb + ((G1_KB - 1) % NSTAGE) * SLOT;
      const uint32_t sa = stg + ((lane >> 4) * 8 + (lane & 7)) * 128 + (((2 * w + ((lane >> 3) & 1)) ^ (lane & 7)) << 4);
#pragma unroll
      for (int q = 0; q < 24; q += 2) {
        uint32_t pk[4];
#pragma unroll
        for (int i = 0; i < 4; i++) {
          const uint32_t p = badd2(pack_bf16(acc[4 * q + 2 * i], acc[4 * q + 2 * i + 1]), (i & 1) ? bias1 : bias0);
          pk[i] = pack_bf16(gelu_tanh(bf_lo(p)), gelu_tanh(bf_hi(p)));
        }
        stsm4t(sa + q * 1024, pk[0], pk[1], pk[2], pk[3]);
        if ((q & 7) == 6) {
          fence_async_smem();
          __syncwarp();
          if (lane == 0) mbar_arrive(bars + 8 * (B_CEMPTY + wg * 3 + (q >> 3)));
        }
      }
    } else {
      if (wtid < 8 * CV_NSLOT / 2) {
        const int sl = 2 * (wtid >> 3) + wg;
        asm volatile("st.shared.u32 [%0], %1;" :: "r"(sb + CV_BASE + sl * CV_SLOT + CV_KOFF + (wtid & 7) * 4), "r"(0) : "memory");
      }
      bar_sync(3 + wg, 128);
      const uint32_t ko = sb + CV_BASE + CV_KOFF + (8 * w + g + t + 1) * 4;
      uint32_t a[64];
      mbar_wait(bars + 8 * (B_CFULL + wg), 0);
      if (tid == 0) TLREC(17);
#pragma unroll
      for (int j = 0; j < 32; j++) { a[2 * j] = lds32(ko + wg * CV_SLOT + (j >> 1) * 256 + (j & 1) * 16); a[2 * j + 1] = lds32(ko + wg * CV_SLOT + (j >> 1) * 256 + (j & 1) * 16 + 128); }
      if (wg == 1) bar_arrive(5, 256);
#pragma unroll 1
      for (int i = wg; i < n_conv; i += 2) {
        const int s = i % CV_NSLOT;
        const uint64_t db = make_desc(sb + CV_BASE + s * CV_SLOT, 4096, 128, 0);
        float acc[128];
        bar_sync(5 + wg, 256);
        wg_fence();
        wgmma_rs_n256(acc, a, db, 0);
        wgmma_rs_n240(acc, a + 4, db + 16, 1);
        wgmma_rs_n224(acc, a + 8, db + 32, 1);
        wgmma_rs_n208(acc, a + 12, db + 48, 1);
        wgmma_rs_n192(acc, a + 16, db + 64, 1);
        wgmma_rs_n176(acc, a + 20, db + 80, 1);
        wgmma_rs_n160(acc, a + 24, db + 96, 1);
        wgmma_rs_n144(acc, a + 28, db + 112, 1);
        wgmma_rs_n128(acc, a + 32, db + 128, 1);
        wgmma_rs_n112(acc, a + 36, db + 144, 1);
        wgmma_rs_n96(acc, a + 40, db + 160, 1);
        wgmma_rs_n80(acc, a + 44, db + 176, 1);
        wgmma_rs_n64(acc, a + 48, db + 192, 1);
        wgmma_rs_n48(acc, a + 52, db + 208, 1);
        wgmma_rs_n32(acc, a + 56, db + 224, 1);
        wgmma_rs_n16(acc, a + 60, db + 240, 1);
        wg_commit();
        if (i + 1 < n_conv) bar_arrive(5 + (wg ^ 1), 256);
        wg_wait<0>();
        pin_regs<128>(acc);
        if (lane == 0) mbar_arrive(bars + 8 * (B_CEMPTY + s));
        const int in = i + 2 < n_conv ? i + 2 : i, sn = in % CV_NSLOT;
        mbar_wait(bars + 8 * (B_CFULL + sn), (in / CV_NSLOT) & 1);
        const uint32_t ka = ko + sn * CV_SLOT;
        __nv_bfloat16* yo = g_yp + ((size_t)conv_channel(cvc, i) * 4 + w) * S_ + 16 * (3 - t) + 2 * g;
#pragma unroll
        for (int j = 0; j < 32; j++) {
          const int q = 31 - j;
          a[2 * j] = lds32(ka + (j >> 1) * 256 + (j & 1) * 16); a[2 * j + 1] = lds32(ka + (j >> 1) * 256 + (j & 1) * 16 + 128);
          stg32(yo + 64 * j, q == 31 ? pack_bf16(acc[124], acc[125]) : pack_bf16(acc[4 * q] + acc[(4 * q + 6) & 127], acc[4 * q + 1] + acc[(4 * q + 7) & 127]));
        }
        if (i == N_SHORT - 2 + wg || i + 2 >= n_conv) {
          bar_sync(3 + wg, 128);
          if (wtid == 0) { signal(i < N_SHORT ? C_YA : C_YB); TLREC(20 + wg); }
          __syncwarp();
        }
      }
      __syncwarp();
      if (lane == 0) mbar_arrive(bars + 8 * B_CDONE);
    }
    if (g2m >= 0) {
      const int srow = g2m * 128 + wg * 64 + w * 16 + g;
      float acc[72], acc2[36];
#pragma unroll 1
      for (int kb = 0; kb < G2_KB - G2_TAIL; kb++) {
        const int p = it2 + kb, s = p % NSTAGE;
        mbar_wait(bars + 8 * (B_FULL + s), (p / NSTAGE) & 1);
        if (kb == 0 && tid == 0) TLREC(7);
        const uint64_t da = make_desc(sb + s * SLOT + wg * 8192, 8192, 1024, 1), db = make_desc(sb + s * SLOT + 16384, 16, 1024, 1);
        wg_fence();
#pragma unroll
        for (int k = 0; k < 4; k++) wgmma_ss_n144_t10(acc, da + k * 128, db + k * 2, (kb | k) != 0);
        wg_commit();
        wg_wait<1>();
        if (kb > 0 && wtid == 0) mbar_arrive(bars + 8 * (B_EMPTY + (p - 1) % NSTAGE));
      }
      const float2 st0 = __ldcg(g_stats + srow), st1 = __ldcg(g_stats + srow + 8);
      const uint32_t bias0 = __byte_perm((uint32_t)__bfloat16_as_ushort(P.b2[srow]), 0, 0x1010);
      const uint32_t bias1 = __byte_perm((uint32_t)__bfloat16_as_ushort(P.b2[srow + 8]), 0, 0x1010);
      const uint32_t xo = sb + ((xslot + 1 + (warp >> 1)) % NSTAGE) * SLOT + G2_BYTES + (warp & 1) * 2304;
      const uint32_t xa = xo + (lane & 15) * 144 + (lane >> 4) * 16;
      uint32_t xx[18], ss[18];
      auto prep = [&]() {
        mbar_wait(bars + 8 * B_XT, 0);
        mbar_wait(bars + 8 * B_Y2, 0);
        const uint32_t ya = sb + SM_DED + ((lane >> 4) * 8 + (lane & 7)) * 256 + (((2 * warp + ((lane >> 3) & 1)) ^ (lane & 7)) << 4);
#pragma unroll
        for (int q = 0; q < 8; q += 2) { ldsm4(xx + 2 * q, xa + q * 16); ldsm4t(ss + 2 * q, ya + q * 2048); }
        ldsm2(xx + 16, xo + (lane & 15) * 144 + 128);
        ldsm2t(ss + 16, ya - (lane >> 4) * 2048 + 8 * 2048);
        const uint32_t m0 = pack_bf16(st0.x, st0.x), m1 = pack_bf16(st1.x, st1.x);
#pragma unroll
        for (int i = 0; i < 18; i++) ss[i] = bmul2(ln_apply(xx[i], (i & 1) ? m1 : m0, (i & 1) ? st1.y : st0.y), ss[i]);
      };
      if (wg == 1) {
        wg_wait<0>();
        if (wtid == 0) mbar_arrive(bars + 8 * (B_EMPTY + xslot));
        prep();
        bar_sync(5, 256);
      }
#pragma unroll
      for (int kb = G2_KB - G2_TAIL; kb < G2_KB; kb++) {
        const int p = it2 + kb, s = p % NSTAGE;
        mbar_wait(bars + 8 * (B_FULL + s), (p / NSTAGE) & 1);
        const uint64_t da = make_desc(sb + s * SLOT + wg * 8192, 8192, 1024, 1), db = make_desc(sb + s * SLOT + 16384, 16, 1024, 1);
        wg_fence();
#pragma unroll
        for (int k = 0; k < 4; k++) wgmma_ss_n72_t10(acc, da + k * 128, db + k * 2, 1);
        wg_commit();
        if (kb == G2_KB - G2_TAIL) { wg_wait<1>(); if (tid == 0) mbar_arrive(bars + 8 * (B_EMPTY + xslot)); }
      }
      bar_arrive(5 + wg, 256);
      wg_wait<0>();
      pin_regs<72>(acc);
      const uint32_t xz = sb + xslot * SLOT + wg * 18432 + wtid * 16;
      mbar_wait_cluster(bars + 8 * B_XRDY, 0);
      {
        const uint32_t rz = mapa(xz, rank ^ 1), rb = mapa(bars + 8 * (B_XFULL + wg), rank ^ 1);
#pragma unroll
        for (int q = 0; q < 9; q++)
          asm volatile("st.async.weak.shared::cluster.mbarrier::complete_tx::bytes.v4.f32 [%0], {%1,%2,%3,%4}, [%5];"
                       :: "r"(rz + q * 2048), "f"(acc[4 * q]), "f"(acc[4 * q + 1]), "f"(acc[4 * q + 2]), "f"(acc[4 * q + 3]), "r"(rb) : "memory");
      }
      if (wg == 0) prep();
      bar_sync(6 - wg, 256);
      wg_fence();
#pragma unroll
      for (int kb = G2_KB - G2_TAIL; kb < G2_KB; kb++) {
        const int s = (it2 + kb) % NSTAGE;
        const uint64_t da = make_desc(sb + s * SLOT + wg * 8192, 8192, 1024, 1), db = make_desc(sb + s * SLOT + 16384 + 9216, 16, 1024, 1);
#pragma unroll
        for (int k = 0; k < 4; k++) wgmma_ss_n72_t10(acc2, da + k * 128, db + k * 2, kb != G2_KB - G2_TAIL || k != 0);
      }
      wg_commit();
      if (wg == 0) bar_arrive(5, 256);
      mbar_wait_cluster(bars + 8 * (B_XFULL + wg), 0);
#pragma unroll
      for (int q = 0; q < 9; q++) {
        const float4 pv = lds128f(xz + q * 2048);
        acc[36 + 4 * q] += pv.x; acc[37 + 4 * q] += pv.y; acc[38 + 4 * q] += pv.z; acc[39 + 4 * q] += pv.w;
      }
      wg_wait<0>();
      pin_regs<36>(acc2);
      if (wtid == 0) TLREC(9 + wg);
      uint32_t ob[18];
#pragma unroll
      for (int i = 0; i < 18; i++) {
        const uint32_t y = badd2(pack_bf16(acc[36 + 2 * i] + acc2[2 * i], acc[37 + 2 * i] + acc2[2 * i + 1]), (i & 1) ? bias1 : bias0);
        ob[i] = badd2(xx[i], bmul2(ss[i], pack_bf16(silu(bf_lo(y)), silu(bf_hi(y)))));
      }
#pragma unroll
      for (int q = 0; q < 8; q += 2) stsm4(xa + q * 16, ob[2 * q], ob[2 * q + 1], ob[2 * q + 2], ob[2 * q + 3]);
      stsm2(xo + (lane & 15) * 144 + 128, ob[16], ob[17]);
      fence_async_smem();
      __syncwarp();
      if (lane == 0) {
        tma2d_store(&P.m_out, xo, dk, srow);
        bulk_commit();
        bulk_wait_read();
      }
      if (wtid == 0) {
        TLREC(11 + wg);
        if (g1m == 0 && g1n == 0 && rank == 0 && wg == 0) st_flag(&g_epoch, tag);
      }
    }
  }
}

typedef CUresult (*EncodeFn)(CUtensorMap*, CUtensorMapDataType, cuuint32_t, void*, const cuuint64_t*, const cuuint64_t*, const cuuint32_t*,
                             const cuuint32_t*, CUtensorMapInterleave, CUtensorMapSwizzle, CUtensorMapL2promotion, CUtensorMapFloatOOBfill);

void make_map(EncodeFn fn, CUtensorMap* m, const void* ptr, int rank, const cuuint64_t* dims, const cuuint64_t* strides, const cuuint32_t* box,
              CUtensorMapSwizzle sw) {
  const cuuint32_t es[3] = {1, 1, 1};
  fn(m, CU_TENSOR_MAP_DATA_TYPE_BFLOAT16, rank, const_cast<void*>(ptr), dims, strides, box, es, CU_TENSOR_MAP_INTERLEAVE_NONE, sw,
     CU_TENSOR_MAP_L2_PROMOTION_L2_256B, CU_TENSOR_MAP_FLOAT_OOB_FILL_NONE);
}

void make_roles(Roles& R) {
  int c1 = 0, ncv = 2, np0 = 0;
  for (int g = 0; g < 8; g++)
    for (int c = 0; c < 66; c++) {
      const int tp = (c + 62) % 66;
      int gg, idx;
      if (tp < 32) { gg = tp % 8; idx = tp / 8; }
      else if (tp < 60) { gg = 1 + (tp - 32) % 7; idx = 4 + (tp - 32) / 7; }
      else if (tp < 62) { gg = 6 + tp - 60; idx = 8; }
      else { gg = 0; idx = 4 + tp - 62; }
      if (gg != g) continue;
      if (idx < 8) { R.g2m[c] = (int8_t)(2 * g + idx / 4); R.g2n[c] = (int8_t)(idx % 4); R.p0[c] = (int8_t)np0++; }
      else { R.g2m[c] = -1; R.g2n[c] = 0; R.p0[c] = -1; }
      if (idx < (g < 2 ? 6 : 7)) { R.g1m[c] = (int8_t)(c1 / 3); R.g1n[c] = (int8_t)(c1 % 3); R.cv[c] = -1; c1++; }
      else { R.g1m[c] = -1; R.g1n[c] = 0; R.cv[c] = (int8_t)(idx == 8 ? tp - 60 : ncv++); }
    }
}

}

extern "C" void kernel_launch(void* const* d_in, const int* in_sizes, int n_in, void* d_out, int out_size) {
  static Params P;
  static const void* cached[4] = {nullptr, nullptr, nullptr, nullptr};
  if (cached[0] != d_in[7] || cached[1] != d_in[9] || cached[2] != d_out || cached[3] != d_in[0]) {
    void* fp = nullptr;
    cudaDriverEntryPointQueryResult qr;
    cudaGetDriverEntryPoint("cuTensorMapEncodeTiled", &fp, cudaEnableDefault, &qr);
    EncodeFn fn = (EncodeFn)fp;
    void *ph, *pu;
    cudaGetSymbolAddress(&ph, g_h);
    cudaGetSymbolAddress(&pu, g_u);
    { cuuint64_t d[3] = {64, S_, F_ / 64}, s[2] = {F_ * 2, 128}; cuuint32_t b[3] = {64, 64, 2}; make_map(fn, &P.m_w1, d_in[7], 3, d, s, b, CU_TENSOR_MAP_SWIZZLE_128B); }
    { cuuint64_t d[3] = {64, S_, D_ / 64}, s[2] = {D_ * 2, 128}; cuuint32_t b[3] = {64, 64, 3}; make_map(fn, &P.m_h, ph, 3, d, s, b, CU_TENSOR_MAP_SWIZZLE_128B); }
    { cuuint64_t d[2] = {F_, D_}, s[1] = {F_ * 2}; cuuint32_t b[2] = {64, 64}; make_map(fn, &P.m_ust, pu, 2, d, s, b, CU_TENSOR_MAP_SWIZZLE_128B); }
    { cuuint64_t d[3] = {64, F_, S_ / 64}, s[2] = {S_ * 2, 128}; cuuint32_t b[3] = {64, 64, 2}; make_map(fn, &P.m_w2, d_in[9], 3, d, s, b, CU_TENSOR_MAP_SWIZZLE_128B); }
    { cuuint64_t d[2] = {F_, D_}, s[1] = {F_ * 2}; cuuint32_t b[2] = {64, 72}; make_map(fn, &P.m_uld, pu, 2, d, s, b, CU_TENSOR_MAP_SWIZZLE_128B); }
    { cuuint64_t d[2] = {D_, S_}, s[1] = {D_ * 2}; cuuint32_t b[2] = {72, 16}; make_map(fn, &P.m_out, d_out, 2, d, s, b, CU_TENSOR_MAP_SWIZZLE_NONE);
      make_map(fn, &P.m_x, d_in[0], 2, d, s, b, CU_TENSOR_MAP_SWIZZLE_NONE); }
    make_roles(P.roles);
    cudaFuncSetAttribute(fused_kernel, cudaFuncAttributeMaxDynamicSharedMemorySize, SM_TOTAL);
    cached[0] = d_in[7]; cached[1] = d_in[9]; cached[2] = d_out; cached[3] = d_in[0];
  }
  P.x = (const __nv_bfloat16*)d_in[0]; P.k = (const __nv_bfloat16*)d_in[1]; P.v = (const __nv_bfloat16*)d_in[2];
  P.shift_k = (const __nv_bfloat16*)d_in[3]; P.ssm_k = (const __nv_bfloat16*)d_in[4]; P.ssm_D = (const __nv_bfloat16*)d_in[5];
  P.b1 = (const __nv_bfloat16*)d_in[8]; P.b2 = (const __nv_bfloat16*)d_in[10];
  fused_kernel<<<132, 384, SM_TOTAL>>>(P);
}
```

```cpp
#include <cuda_runtime.h>
#include <cuda.h>
#include <cuda_bf16.h>
#include <stdint.h>

namespace {

constexpr int S_ = 2048, D_ = 576, F_ = 4608;
constexpr int NSTAGE = 5, SLOT = 40960;
constexpr int G1_KB = 32, G2_KB = 36;
constexpr int G1_BYTES = 40960, G2_BYTES = 16384 + 18432;
constexpr int N_CONV_CTA = 24, N_SHORT = 22, N_LONG_EXTRA = 12;
static_assert(N_CONV_CTA * N_SHORT + 4 * N_LONG_EXTRA == D_, "conv split");
constexpr int KV_ROUNDS = 6;
#define G1T 5
constexpr int G1_TAIL = G1T, G2_TAIL = 4;

constexpr int SM_DED = NSTAGE * SLOT;
constexpr int SM_BAR = SM_DED + 24576;
constexpr int SM_TOTAL = SM_BAR + 256 + 1024;
constexpr int CV_BASE = 3 * SLOT;
constexpr int CV_NSLOT = 6, CV_KOFF = 8192, CV_SLOT = 8192 + 4224;
static_assert(CV_BASE + CV_NSLOT * CV_SLOT <= SM_DED, "conv overlay");
constexpr int B_FULL = 0, B_EMPTY = NSTAGE, B_CFULL = 2 * NSTAGE, B_CEMPTY = B_CFULL + CV_NSLOT, B_CDONE = B_CEMPTY + CV_NSLOT,
              B_XRDY = B_CDONE + 1, B_XFULL = B_CDONE + 2  , B_XT = B_CDONE + 4, B_Y2 = B_CDONE + 5;
constexpr int C_H = 0, C_KV = 1, C_U = C_KV + KV_ROUNDS  , C_YA = C_U + 12, C_YB = C_YA + 1, C_COUNT = C_YB + 1;

struct Roles {
  int8_t g1m[66];
  int8_t g1n[66];
  int8_t cv[66];
  int8_t g2m[66];
  int8_t g2n[66];
  int8_t p0[66];
};

struct Params {
  CUtensorMap m_w1, m_h, m_ust, m_w2, m_uld, m_out, m_x;
  const __nv_bfloat16 *x, *k, *v, *shift_k, *ssm_k, *ssm_D, *b1, *b2;
  Roles roles;
};

__device__ __align__(1024) __nv_bfloat16 g_h[S_ * D_];
__device__ __align__(1024) __nv_bfloat16 g_ub[D_ * 4096];
__device__ __align__(1024) __nv_bfloat16 g_yp[D_ * 4 * S_];
__device__ __align__(1024) __nv_bfloat16 g_u[D_ * F_];
__device__ __align__(128) float4 g_stats[S_];
__device__ __align__(128) uint32_t g_cnt[C_COUNT * 32];
__device__ __align__(128) uint32_t g_epoch;
#define TLREC(i) do { } while (0)
#define TLEND() do { } while (0)

__device__ __forceinline__ uint32_t smem_u32(const void* p) { return (uint32_t)__cvta_generic_to_shared(p); }
__device__ __forceinline__ void mbar_init(uint32_t bar, uint32_t cnt) { asm volatile("mbarrier.init.shared::cta.b64 [%0], %1;" :: "r"(bar), "r"(cnt) : "memory"); }
__device__ __forceinline__ void mbar_expect_tx(uint32_t bar, uint32_t bytes) { asm volatile("mbarrier.arrive.expect_tx.shared::cta.b64 _, [%0], %1;" :: "r"(bar), "r"(bytes) : "memory"); }
__device__ __forceinline__ void mbar_arrive(uint32_t bar) { asm volatile("mbarrier.arrive.shared::cta.b64 _, [%0];" :: "r"(bar) : "memory"); }
__device__ __forceinline__ uint32_t mapa(uint32_t addr, uint32_t cta) { uint32_t r; asm volatile("mapa.shared::cluster.u32 %0, %1, %2;" : "=r"(r) : "r"(addr), "r"(cta)); return r; }
__device__ __forceinline__ void mbar_arrive_remote(uint32_t rbar) { asm volatile("mbarrier.arrive.release.cluster.shared::cluster.b64 _, [%0];" :: "r"(rbar) : "memory"); }
__device__ __forceinline__ void mbar_wait(uint32_t bar, uint32_t parity) {
  asm volatile("{\n .reg .pred p;\n .reg .u32 c;\n mov.u32 c, 0;\n"
               "W_%=:\n mbarrier.try_wait.parity.shared::cta.b64 p, [%0], %1;\n @p bra D_%=;\n"
               " add.u32 c, c, 1;\n setp.lt.u32 p, c, 2000000;\n @p bra W_%=;\n trap;\n D_%=:\n }" :: "r"(bar), "r"(parity) : "memory");
}
__device__ __forceinline__ void mbar_wait_cluster(uint32_t bar, uint32_t parity) {
  asm volatile("{\n .reg .pred p;\n .reg .u32 c;\n mov.u32 c, 0;\n"
               "W_%=:\n mbarrier.try_wait.parity.acquire.cluster.shared::cta.b64 p, [%0], %1;\n @p bra D_%=;\n"
               " add.u32 c, c, 1;\n setp.lt.u32 p, c, 2000000;\n @p bra W_%=;\n trap;\n D_%=:\n }" :: "r"(bar), "r"(parity) : "memory");
}
__device__ __forceinline__ void tma2d(uint32_t dst, const CUtensorMap* m, int c0, int c1, uint32_t bar) {
  asm volatile("cp.async.bulk.tensor.2d.shared::cluster.global.mbarrier::complete_tx::bytes [%0], [%1, {%3, %4}], [%2];"
               :: "r"(dst), "l"(m), "r"(bar), "r"(c0), "r"(c1) : "memory");
}
__device__ __forceinline__ void tma3d(uint32_t dst, const CUtensorMap* m, int c0, int c1, int c2, uint32_t bar) {
  asm volatile("cp.async.bulk.tensor.3d.shared::cluster.global.mbarrier::complete_tx::bytes [%0], [%1, {%3, %4, %5}], [%2];"
               :: "r"(dst), "l"(m), "r"(bar), "r"(c0), "r"(c1), "r"(c2) : "memory");
}
__device__ __forceinline__ void tma2d_store(const CUtensorMap* m, uint32_t src, int c0, int c1) {
  asm volatile("cp.async.bulk.tensor.2d.global.shared::cta.bulk_group [%0, {%2, %3}], [%1];" :: "l"(m), "r"(src), "r"(c0), "r"(c1) : "memory");
}
__device__ __forceinline__ void bulk_load(uint32_t dst, const void* src, uint32_t bytes, uint32_t bar) {
  asm volatile("cp.async.bulk.shared::cluster.global.mbarrier::complete_tx::bytes [%0], [%1], %2, [%3];" :: "r"(dst), "l"(src), "r"(bytes), "r"(bar) : "memory");
}
__device__ __forceinline__ void bulk_commit() { asm volatile("cp.async.bulk.commit_group;" ::: "memory"); }
__device__ __forceinline__ void bulk_wait_all() { asm volatile("cp.async.bulk.wait_group 0;" ::: "memory"); }
__device__ __forceinline__ void bulk_wait_read() { asm volatile("cp.async.bulk.wait_group.read 0;" ::: "memory"); }
__device__ __forceinline__ void fence_async_smem() { asm volatile("fence.proxy.async.shared::cta;" ::: "memory"); }
__device__ __forceinline__ void fence_async_global() { asm volatile("fence.proxy.async.global;" ::: "memory"); }
__device__ __forceinline__ void st_flag(uint32_t* p, uint32_t v) { asm volatile("st.relaxed.gpu.global.u32 [%0], %1;" :: "l"(p), "r"(v) : "memory"); }
__device__ __forceinline__ uint32_t ld_flag(const uint32_t* p) { uint32_t v; asm volatile("ld.relaxed.gpu.global.u32 %0, [%1];" : "=r"(v) : "l"(p) : "memory"); return v; }
__device__ __forceinline__ void signal(int c) { asm volatile("red.release.gpu.global.add.u32 [%0], 1;" :: "l"(g_cnt + c * 32) : "memory"); }
__device__ __forceinline__ void await(int c, uint32_t target) {
  uint32_t n = 0;
  while (true) {
    uint32_t v; asm volatile("ld.acquire.gpu.global.u32 %0, [%1];" : "=r"(v) : "l"(g_cnt + c * 32) : "memory");
    if ((int32_t)(v - target) >= 0) break;
    if (++n > 4000000u) __trap();
  }
}
__device__ __forceinline__ void bar_sync(int id, int n) { asm volatile("bar.sync %0, %1;" :: "r"(id), "r"(n) : "memory"); }
__device__ __forceinline__ void bar_arrive(int id, int n) { asm volatile("bar.arrive %0, %1;" :: "r"(id), "r"(n) : "memory"); }
__device__ __forceinline__ void wg_fence() { asm volatile("wgmma.fence.sync.aligned;" ::: "memory"); }
__device__ __forceinline__ void wg_commit() { asm volatile("wgmma.commit_group.sync.aligned;" ::: "memory"); }
template <int N> __device__ __forceinline__ void wg_wait() { asm volatile("wgmma.wait_group.sync.aligned %0;" :: "n"(N) : "memory"); }
template <int N> __device__ __forceinline__ void pin_regs(float* a) {
#pragma unroll
  for (int i = 0; i < N; i++) asm volatile("" : "+f"(a[i]) :: "memory");
}
__device__ __forceinline__ uint64_t make_desc(uint32_t addr, uint32_t lbo, uint32_t sbo, uint32_t swz) {
  return (uint64_t)((addr & 0x3FFFF) >> 4) | ((uint64_t)(lbo >> 4) << 16) | ((uint64_t)(sbo >> 4) << 32) | ((uint64_t)swz << 62);
}
__device__ __forceinline__ uint32_t pack_bf16(float lo, float hi) { uint32_t r; asm("cvt.rn.bf16x2.f32 %0, %1, %2;" : "=r"(r) : "f"(hi), "f"(lo)); return r; }
__device__ __forceinline__ float bf_lo(uint32_t p) { return __uint_as_float(p << 16); }
__device__ __forceinline__ float bf_hi(uint32_t p) { return __uint_as_float(p & 0xffff0000u); }
__device__ __forceinline__ float round_bf16(float v) { return bf_lo(pack_bf16(v, 0.f)); }
__device__ __forceinline__ uint32_t bmul2(uint32_t a, uint32_t b) { uint32_t r; asm("mul.rn.bf16x2 %0, %1, %2;" : "=r"(r) : "r"(a), "r"(b)); return r; }
__device__ __forceinline__ uint32_t badd2(uint32_t a, uint32_t b) { uint32_t r; asm("add.rn.bf16x2 %0, %1, %2;" : "=r"(r) : "r"(a), "r"(b)); return r; }
__device__ __forceinline__ uint32_t bsub2(uint32_t a, uint32_t b) { uint32_t r; asm("sub.rn.bf16x2 %0, %1, %2;" : "=r"(r) : "r"(a), "r"(b)); return r; }
__device__ __forceinline__ float tanh_fast(float v) { float r; asm("tanh.approx.f32 %0, %1;" : "=f"(r) : "f"(v)); return r; }
__device__ __forceinline__ float gelu_tanh(float v) {
  float z = v * fmaf(v * v, 0.7978845608028654f * 0.044715f, 0.7978845608028654f);
  float hv = 0.5f * v;
  return fmaf(hv, tanh_fast(z), hv);
}
__device__ __forceinline__ float silu(float v) { float hv = 0.5f * v; return fmaf(hv, tanh_fast(hv), hv); }
__device__ __forceinline__ uint32_t ldg32(const void* p) { uint32_t v; asm volatile("ld.global.nc.u32 %0, [%1];" : "=r"(v) : "l"(p)); return v; }
__device__ __forceinline__ uint4 ldg128_cg(const void* p) {
  uint4 v; asm volatile("ld.global.cg.v4.u32 {%0,%1,%2,%3}, [%4];" : "=r"(v.x), "=r"(v.y), "=r"(v.z), "=r"(v.w) : "l"(p) : "memory"); return v;
}
__device__ __forceinline__ void stg32(void* p, uint32_t v) { asm volatile("st.global.u32 [%0], %1;" :: "l"(p), "r"(v) : "memory"); }
__device__ __forceinline__ uint32_t lds32(uint32_t a) { uint32_t v; asm volatile("ld.shared.u32 %0, [%1];" : "=r"(v) : "r"(a) : "memory"); return v; }
__device__ __forceinline__ float4 lds128f(uint32_t a) { float4 v; asm volatile("ld.shared.v4.f32 {%0,%1,%2,%3}, [%4];" : "=f"(v.x), "=f"(v.y), "=f"(v.z), "=f"(v.w) : "r"(a) : "memory"); return v; }
__device__ __forceinline__ void sts128(uint32_t a, uint4 v) { asm volatile("st.shared.v4.u32 [%0], {%1,%2,%3,%4};" :: "r"(a), "r"(v.x), "r"(v.y), "r"(v.z), "r"(v.w) : "memory"); }
__device__ __forceinline__ void ldsm4(uint32_t* r, uint32_t a) {
  asm volatile("ldmatrix.sync.aligned.m8n8.x4.shared.b16 {%0,%1,%2,%3}, [%4];" : "=r"(r[0]), "=r"(r[1]), "=r"(r[2]), "=r"(r[3]) : "r"(a) : "memory");
}
__device__ __forceinline__ void ldsm2(uint32_t* r, uint32_t a) {
  asm volatile("ldmatrix.sync.aligned.m8n8.x2.shared.b16 {%0,%1}, [%2];" : "=r"(r[0]), "=r"(r[1]) : "r"(a) : "memory");
}
__device__ __forceinline__ void ldsm4t(uint32_t* r, uint32_t a) {
  asm volatile("ldmatrix.sync.aligned.m8n8.x4.trans.shared.b16 {%0,%1,%2,%3}, [%4];" : "=r"(r[0]), "=r"(r[1]), "=r"(r[2]), "=r"(r[3]) : "r"(a) : "memory");
}
__device__ __forceinline__ void ldsm2t(uint32_t* r, uint32_t a) {
  asm volatile("ldmatrix.sync.aligned.m8n8.x2.trans.shared.b16 {%0,%1}, [%2];" : "=r"(r[0]), "=r"(r[1]) : "r"(a) : "memory");
}
__device__ __forceinline__ void stsm4(uint32_t a, uint32_t r0, uint32_t r1, uint32_t r2, uint32_t r3) {
  asm volatile("stmatrix.sync.aligned.m8n8.x4.shared.b16 [%0], {%1,%2,%3,%4};" :: "r"(a), "r"(r0), "r"(r1), "r"(r2), "r"(r3) : "memory");
}
__device__ __forceinline__ void stsm2(uint32_t a, uint32_t r0, uint32_t r1) {
  asm volatile("stmatrix.sync.aligned.m8n8.x2.shared.b16 [%0], {%1,%2};" :: "r"(a), "r"(r0), "r"(r1) : "memory");
}
__device__ __forceinline__ void stsm4t(uint32_t a, uint32_t r0, uint32_t r1, uint32_t r2, uint32_t r3) {
  asm volatile("stmatrix.sync.aligned.m8n8.x4.trans.shared.b16 [%0], {%1,%2,%3,%4};" :: "r"(a), "r"(r0), "r"(r1), "r"(r2), "r"(r3) : "memory");
}

__device__ __forceinline__ void wgmma_ss_n144_t10(float* d, uint64_t da, uint64_t db, int sd) {
  asm volatile("{ .reg .pred p; setp.ne.b32 p, %74, 0;\n"
      "wgmma.mma_async.sync.aligned.m64n144k16.f32.bf16.bf16 {"
      "%0,%1,%2,%3,%4,%5,%6,%7,%8,%9,%10,%11,%12,%13,%14,%15,"
      "%16,%17,%18,%19,%20,%21,%22,%23,%24,%25,%26,%27,%28,%29,%30,%31,"
      "%32,%33,%34,%35,%36,%37,%38,%39,%40,%41,%42,%43,%44,%45,%46,%47,"
      "%48,%49,%50,%51,%52,%53,%54,%55,%56,%57,%58,%59,%60,%61,%62,%63,"
      "%64,%65,%66,%67,%68,%69,%70,%71"
      "}, %72, %73, p, 1, 1, 1, 0; }"
    : "+f"(d[0]), "+f"(d[1]), "+f"(d[2]), "+f"(d[3]), "+f"(d[4]), "+f"(d[5]), "+f"(d[6]), "+f"(d[7]),
      "+f"(d[8]), "+f"(d[9]), "+f"(d[10]), "+f"(d[11]), "+f"(d[12]), "+f"(d[13]), "+f"(d[14]), "+f"(d[15]),
      "+f"(d[16]), "+f"(d[17]), "+f"(d[18]), "+f"(d[19]), "+f"(d[20]), "+f"(d[21]), "+f"(d[22]), "+f"(d[23]),
      "+f"(d[24]), "+f"(d[25]), "+f"(d[26]), "+f"(d[27]), "+f"(d[28]), "+f"(d[29]), "+f"(d[30]), "+f"(d[31]),
      "+f"(d[32]), "+f"(d[33]), "+f"(d[34]), "+f"(d[35]), "+f"(d[36]), "+f"(d[37]), "+f"(d[38]), "+f"(d[39]),
      "+f"(d[40]), "+f"(d[41]), "+f"(d[42]), "+f"(d[43]), "+f"(d[44]), "+f"(d[45]), "+f"(d[46]), "+f"(d[47]),
      "+f"(d[48]), "+f"(d[49]), "+f"(d[50]), "+f"(d[51]), "+f"(d[52]), "+f"(d[53]), "+f"(d[54]), "+f"(d[55]),
      "+f"(d[56]), "+f"(d[57]), "+f"(d[58]), "+f"(d[59]), "+f"(d[60]), "+f"(d[61]), "+f"(d[62]), "+f"(d[63]),
      "+f"(d[64]), "+f"(d[65]), "+f"(d[66]), "+f"(d[67]), "+f"(d[68]), "+f"(d[69]), "+f"(d[70]), "+f"(d[71])
    : "l"(da), "l"(db), "r"(sd));
}

__device__ __forceinline__ void wgmma_ss_n192_t11(float* d, uint64_t da, uint64_t db, int sd) {
  asm volatile("{ .reg .pred p; setp.ne.b32 p, %98, 0;\n"
      "wgmma.mma_async.sync.aligned.m64n192k16.f32.bf16.bf16 {"
      "%0,%1,%2,%3,%4,%5,%6,%7,%8,%9,%10,%11,%12,%13,%14,%15,"
      "%16,%17,%18,%19,%20,%21,%22,%23,%24,%25,%26,%27,%28,%29,%30,%31,"
      "%32,%33,%34,%35,%36,%37,%38,%39,%40,%41,%42,%43,%44,%45,%46,%47,"
      "%48,%49,%50,%51,%52,%53,%54,%55,%56,%57,%58,%59,%60,%61,%62,%63,"
      "%64,%65,%66,%67,%68,%69,%70,%71,%72,%73,%74,%75,%76,%77,%78,%79,"
      "%80,%81,%82,%83,%84,%85,%86,%87,%88,%89,%90,%91,%92,%93,%94,%95"
      "}, %96, %97, p, 1, 1, 1, 1; }"
    : "+f"(d[0]), "+f"(d[1]), "+f"(d[2]), "+f"(d[3]), "+f"(d[4]), "+f"(d[5]), "+f"(d[6]), "+f"(d[7]),
      "+f"(d[8]), "+f"(d[9]), "+f"(d[10]), "+f"(d[11]), "+f"(d[12]), "+f"(d[13]), "+f"(d[14]), "+f"(d[15]),
      "+f"(d[16]), "+f"(d[17]), "+f"(d[18]), "+f"(d[19]), "+f"(d[20]), "+f"(d[21]), "+f"(d[22]), "+f"(d[23]),
      "+f"(d[24]), "+f"(d[25]), "+f"(d[26]), "+f"(d[27]), "+f"(d[28]), "+f"(d[29]), "+f"(d[30]), "+f"(d[31]),
      "+f"(d[32]), "+f"(d[33]), "+f"(d[34]), "+f"(d[35]), "+f"(d[36]), "+f"(d[37]), "+f"(d[38]), "+f"(d[39]),
      "+f"(d[40]), "+f"(d[41]), "+f"(d[42]), "+f"(d[43]), "+f"(d[44]), "+f"(d[45]), "+f"(d[46]), "+f"(d[47]),
      "+f"(d[48]), "+f"(d[49]), "+f"(d[50]), "+f"(d[51]), "+f"(d[52]), "+f"(d[53]), "+f"(d[54]), "+f"(d[55]),
      "+f"(d[56]), "+f"(d[57]), "+f"(d[58]), "+f"(d[59]), "+f"(d[60]), "+f"(d[61]), "+f"(d[62]), "+f"(d[63]),
      "+f"(d[64]), "+f"(d[65]), "+f"(d[66]), "+f"(d[67]), "+f"(d[68]), "+f"(d[69]), "+f"(d[70]), "+f"(d[71]),
      "+f"(d[72]), "+f"(d[73]), "+f"(d[74]), "+f"(d[75]), "+f"(d[76]), "+f"(d[77]), "+f"(d[78]), "+f"(d[79]),
      "+f"(d[80]), "+f"(d[81]), "+f"(d[82]), "+f"(d[83]), "+f"(d[84]), "+f"(d[85]), "+f"(d[86]), "+f"(d[87]),
      "+f"(d[88]), "+f"(d[89]), "+f"(d[90]), "+f"(d[91]), "+f"(d[92]), "+f"(d[93]), "+f"(d[94]), "+f"(d[95])
    : "l"(da), "l"(db), "r"(sd));
}

__device__ __forceinline__ void wgmma_ss_n72_t10(float* d, uint64_t da, uint64_t db, int sd) {
  asm volatile("{ .reg .pred p; setp.ne.b32 p, %38, 0;\n"
      "wgmma.mma_async.sync.aligned.m64n72k16.f32.bf16.bf16 {"
      "%0,%1,%2,%3,%4,%5,%6,%7,%8,%9,%10,%11,%12,%13,%14,%15,"
      "%16,%17,%18,%19,%20,%21,%22,%23,%24,%25,%26,%27,%28,%29,%30,%31,"
      "%32,%33,%34,%35"
      "}, %36, %37, p, 1, 1, 1, 0; }"
    : "+f"(d[0]), "+f"(d[1]), "+f"(d[2]), "+f"(d[3]), "+f"(d[4]), "+f"(d[5]), "+f"(d[6]), "+f"(d[7]),
      "+f"(d[8]), "+f"(d[9]), "+f"(d[10]), "+f"(d[11]), "+f"(d[12]), "+f"(d[13]), "+f"(d[14]), "+f"(d[15]),
      "+f"(d[16]), "+f"(d[17]), "+f"(d[18]), "+f"(d[19]), "+f"(d[20]), "+f"(d[21]), "+f"(d[22]), "+f"(d[23]),
      "+f"(d[24]), "+f"(d[25]), "+f"(d[26]), "+f"(d[27]), "+f"(d[28]), "+f"(d[29]), "+f"(d[30]), "+f"(d[31]),
      "+f"(d[32]), "+f"(d[33]), "+f"(d[34]), "+f"(d[35])
    : "l"(da), "l"(db), "r"(sd));
}

__device__ __forceinline__ void wgmma_rs_n16(float* d, const uint32_t* a, uint64_t db, int sd) {
  asm volatile("{ .reg .pred p; setp.ne.b32 p, %13, 0;\n"
      "wgmma.mma_async.sync.aligned.m64n16k16.f32.bf16.bf16 {"
      "%0,%1,%2,%3,%4,%5,%6,%7"
      "}, {%8,%9,%10,%11}, %12, p, 1, 1, 0; }"
    : "+f"(d[0]), "+f"(d[1]), "+f"(d[2]), "+f"(d[3]), "+f"(d[4]), "+f"(d[5]), "+f"(d[6]), "+f"(d[7])
    : "r"(a[0]), "r"(a[1]), "r"(a[2]), "r"(a[3]), "l"(db), "r"(sd));
}

__device__ __forceinline__ void wgmma_rs_n32(float* d, const uint32_t* a, uint64_t db, int sd) {
  asm volatile("{ .reg .pred p; setp.ne.b32 p, %21, 0;\n"
      "wgmma.mma_async.sync.aligned.m64n32k16.f32.bf16.bf16 {"
      "%0,%1,%2,%3,%4,%5,%6,%7,%8,%9,%10,%11,%12,%13,%14,%15"
      "}, {%16,%17,%18,%19}, %20, p, 1, 1, 0; }"
    : "+f"(d[0]), "+f"(d[1]), "+f"(d[2]), "+f"(d[3]), "+f"(d[4]), "+f"(d[5]), "+f"(d[6]), "+f"(d[7]),
      "+f"(d[8]), "+f"(d[9]), "+f"(d[10]), "+f"(d[11]), "+f"(d[12]), "+f"(d[13]), "+f"(d[14]), "+f"(d[15])
    : "r"(a[0]), "r"(a[1]), "r"(a[2]), "r"(a[3]), "l"(db), "r"(sd));
}

__device__ __forceinline__ void wgmma_rs_n48(float* d, const uint32_t* a, uint64_t db, int sd) {
  asm volatile("{ .reg .pred p; setp.ne.b32 p, %29, 0;\n"
      "wgmma.mma_async.sync.aligned.m64n48k16.f32.bf16.bf16 {"
      "%0,%1,%2,%3,%4,%5,%6,%7,%8,%9,%10,%11,%12,%13,%14,%15,"
      "%16,%17,%18,%19,%20,%21,%22,%23"
      "}, {%24,%25,%26,%27}, %28, p, 1, 1, 0; }"
    : "+f"(d[0]), "+f"(d[1]), "+f"(d[2]), "+f"(d[3]), "+f"(d[4]), "+f"(d[5]), "+f"(d[6]), "+f"(d[7]),
      "+f"(d[8]), "+f"(d[9]), "+f"(d[10]), "+f"(d[11]), "+f"(d[12]), "+f"(d[13]), "+f"(d[14]), "+f"(d[15]),
      "+f"(d[16]), "+f"(d[17]), "+f"(d[18]), "+f"(d[19]), "+f"(d[20]), "+f"(d[21]), "+f"(d[22]), "+f"(d[23])
    : "r"(a[0]), "r"(a[1]), "r"(a[2]), "r"(a[3]), "l"(db), "r"(sd));
}

__device__ __forceinline__ void wgmma_rs_n64(float* d, const uint32_t* a, uint64_t db, int sd) {
  asm volatile("{ .reg .pred p; setp.ne.b32 p, %37, 0;\n"
      "wgmma.mma_async.sync.aligned.m64n64k16.f32.bf16.bf16 {"
      "%0,%1,%2,%3,%4,%5,%6,%7,%8,%9,%10,%11,%12,%13,%14,%15,"
      "%16,%17,%18,%19,%20,%21,%22,%23,%24,%25,%26,%27,%28,%29,%30,%31"
      "}, {%32,%33,%34,%35}, %36, p, 1, 1, 0; }"
    : "+f"(d[0]), "+f"(d[1]), "+f"(d[2]), "+f"(d[3]), "+f"(d[4]), "+f"(d[5]), "+f"(d[6]), "+f"(d[7]),
      "+f"(d[8]), "+f"(d[9]), "+f"(d[10]), "+f"(d[11]), "+f"(d[12]), "+f"(d[13]), "+f"(d[14]), "+f"(d[15]),
      "+f"(d[16]), "+f"(d[17]), "+f"(d[18]), "+f"(d[19]), "+f"(d[20]), "+f"(d[21]), "+f"(d[22]), "+f"(d[23]),
      "+f"(d[24]), "+f"(d[25]), "+f"(d[26]), "+f"(d[27]), "+f"(d[28]), "+f"(d[29]), "+f"(d[30]), "+f"(d[31])
    : "r"(a[0]), "r"(a[1]), "r"(a[2]), "r"(a[3]), "l"(db), "r"(sd));
}

__device__ __forceinline__ void wgmma_rs_n80(float* d, const uint32_t* a, uint64_t db, int sd) {
  asm volatile("{ .reg .pred p; setp.ne.b32 p, %45, 0;\n"
      "wgmma.mma_async.sync.aligned.m64n80k16.f32.bf16.bf16 {"
      "%0,%1,%2,%3,%4,%5,%6,%7,%8,%9,%10,%11,%12,%13,%14,%15,"
      "%16,%17,%18,%19,%20,%21,%22,%23,%24,%25,%26,%27,%28,%29,%30,%31,"
      "%32,%33,%34,%35,%36,%37,%38,%39"
      "}, {%40,%41,%42,%43}, %44, p, 1, 1, 0; }"
    : "+f"(d[0]), "+f"(d[1]), "+f"(d[2]), "+f"(d[3]), "+f"(d[4]), "+f"(d[5]), "+f"(d[6]), "+f"(d[7]),
      "+f"(d[8]), "+f"(d[9]), "+f"(d[10]), "+f"(d[11]), "+f"(d[12]), "+f"(d[13]), "+f"(d[14]), "+f"(d[15]),
      "+f"(d[16]), "+f"(d[17]), "+f"(d[18]), "+f"(d[19]), "+f"(d[20]), "+f"(d[21]), "+f"(d[22]), "+f"(d[23]),
      "+f"(d[24]), "+f"(d[25]), "+f"(d[26]), "+f"(d[27]), "+f"(d[28]), "+f"(d[29]), "+f"(d[30]), "+f"(d[31]),
      "+f"(d[32]), "+f"(d[33]), "+f"(d[34]), "+f"(d[35]), "+f"(d[36]), "+f"(d[37]), "+f"(d[38]), "+f"(d[39])
    : "r"(a[0]), "r"(a[1]), "r"(a[2]), "r"(a[3]), "l"(db), "r"(sd));
}

__device__ __forceinline__ void wgmma_rs_n96(float* d, const uint32_t* a, uint64_t db, int sd) {
  asm volatile("{ .reg .pred p; setp.ne.b32 p, %53, 0;\n"
      "wgmma.mma_async.sync.aligned.m64n96k16.f32.bf16.bf16 {"
      "%0,%1,%2,%3,%4,%5,%6,%7,%8,%9,%10,%11,%12,%13,%14,%15,"
      "%16,%17,%18,%19,%20,%21,%22,%23,%24,%25,%26,%27,%28,%29,%30,%31,"
      "%32,%33,%34,%35,%36,%37,%38,%39,%40,%41,%42,%43,%44,%45,%46,%47"
      "}, {%48,%49,%50,%51}, %52, p, 1, 1, 0; }"
    : "+f"(d[0]), "+f"(d[1]), "+f"(d[2]), "+f"(d[3]), "+f"(d[4]), "+f"(d[5]), "+f"(d[6]), "+f"(d[7]),
      "+f"(d[8]), "+f"(d[9]), "+f"(d[10]), "+f"(d[11]), "+f"(d[12]), "+f"(d[13]), "+f"(d[14]), "+f"(d[15]),
      "+f"(d[16]), "+f"(d[17]), "+f"(d[18]), "+f"(d[19]), "+f"(d[20]), "+f"(d[21]), "+f"(d[22]), "+f"(d[23]),
      "+f"(d[24]), "+f"(d[25]), "+f"(d[26]), "+f"(d[27]), "+f"(d[28]), "+f"(d[29]), "+f"(d[30]), "+f"(d[31]),
      "+f"(d[32]), "+f"(d[33]), "+f"(d[34]), "+f"(d[35]), "+f"(d[36]), "+f"(d[37]), "+f"(d[38]), "+f"(d[39]),
      "+f"(d[40]), "+f"(d[41]), "+f"(d[42]), "+f"(d[43]), "+f"(d[44]), "+f"(d[45]), "+f"(d[46]), "+f"(d[47])
    : "r"(a[0]), "r"(a[1]), "r"(a[2]), "r"(a[3]), "l"(db), "r"(sd));
}

__device__ __forceinline__ void wgmma_rs_n112(float* d, const uint32_t* a, uint64_t db, int sd) {
  asm volatile("{ .reg .pred p; setp.ne.b32 p, %61, 0;\n"
      "wgmma.mma_async.sync.aligned.m64n112k16.f32.bf16.bf16 {"
      "%0,%1,%2,%3,%4,%5,%6,%7,%8,%9,%10,%11,%12,%13,%14,%15,"
      "%16,%17,%18,%19,%20,%21,%22,%23,%24,%25,%26,%27,%28,%29,%30,%31,"
      "%32,%33,%34,%35,%36,%37,%38,%39,%40,%41,%42,%43,%44,%45,%46,%47,"
      "%48,%49,%50,%51,%52,%53,%54,%55"
      "}, {%56,%57,%58,%59}, %60, p, 1, 1, 0; }"
    : "+f"(d[0]), "+f"(d[1]), "+f"(d[2]), "+f"(d[3]), "+f"(d[4]), "+f"(d[5]), "+f"(d[6]), "+f"(d[7]),
      "+f"(d[8]), "+f"(d[9]), "+f"(d[10]), "+f"(d[11]), "+f"(d[12]), "+f"(d[13]), "+f"(d[14]), "+f"(d[15]),
      "+f"(d[16]), "+f"(d[17]), "+f"(d[18]), "+f"(d[19]), "+f"(d[20]), "+f"(d[21]), "+f"(d[22]), "+f"(d[23]),
      "+f"(d[24]), "+f"(d[25]), "+f"(d[26]), "+f"(d[27]), "+f"(d[28]), "+f"(d[29]), "+f"(d[30]), "+f"(d[31]),
      "+f"(d[32]), "+f"(d[33]), "+f"(d[34]), "+f"(d[35]), "+f"(d[36]), "+f"(d[37]), "+f"(d[38]), "+f"(d[39]),
      "+f"(d[40]), "+f"(d[41]), "+f"(d[42]), "+f"(d[43]), "+f"(d[44]), "+f"(d[45]), "+f"(d[46]), "+f"(d[47]),
      "+f"(d[48]), "+f"(d[49]), "+f"(d[50]), "+f"(d[51]), "+f"(d[52]), "+f"(d[53]), "+f"(d[54]), "+f"(d[55])
    : "r"(a[0]), "r"(a[1]), "r"(a[2]), "r"(a[3]), "l"(db), "r"(sd));
}

__device__ __forceinline__ void wgmma_rs_n128(float* d, const uint32_t* a, uint64_t db, int sd) {
  asm volatile("{ .reg .pred p; setp.ne.b32 p, %69, 0;\n"
      "wgmma.mma_async.sync.aligned.m64n128k16.f32.bf16.bf16 {"
      "%0,%1,%2,%3,%4,%5,%6,%7,%8,%9,%10,%11,%12,%13,%14,%15,"
      "%16,%17,%18,%19,%20,%21,%22,%23,%24,%25,%26,%27,%28,%29,%30,%31,"
      "%32,%33,%34,%35,%36,%37,%38,%39,%40,%41,%42,%43,%44,%45,%46,%47,"
      "%48,%49,%50,%51,%52,%53,%54,%55,%56,%57,%58,%59,%60,%61,%62,%63"
      "}, {%64,%65,%66,%67}, %68, p, 1, 1, 0; }"
    : "+f"(d[0]), "+f"(d[1]), "+f"(d[2]), "+f"(d[3]), "+f"(d[4]), "+f"(d[5]), "+f"(d[6]), "+f"(d[7]),
      "+f"(d[8]), "+f"(d[9]), "+f"(d[10]), "+f"(d[11]), "+f"(d[12]), "+f"(d[13]), "+f"(d[14]), "+f"(d[15]),
      "+f"(d[16]), "+f"(d[17]), "+f"(d[18]), "+f"(d[19]), "+f"(d[20]), "+f"(d[21]), "+f"(d[22]), "+f"(d[23]),
      "+f"(d[24]), "+f"(d[25]), "+f"(d[26]), "+f"(d[27]), "+f"(d[28]), "+f"(d[29]), "+f"(d[30]), "+f"(d[31]),
      "+f"(d[32]), "+f"(d[33]), "+f"(d[34]), "+f"(d[35]), "+f"(d[36]), "+f"(d[37]), "+f"(d[38]), "+f"(d[39]),
      "+f"(d[40]), "+f"(d[41]), "+f"(d[42]), "+f"(d[43]), "+f"(d[44]), "+f"(d[45]), "+f"(d[46]), "+f"(d[47]),
      "+f"(d[48]), "+f"(d[49]), "+f"(d[50]), "+f"(d[51]), "+f"(d[52]), "+f"(d[53]), "+f"(d[54]), "+f"(d[55]),
      "+f"(d[56]), "+f"(d[57]), "+f"(d[58]), "+f"(d[59]), "+f"(d[60]), "+f"(d[61]), "+f"(d[62]), "+f"(d[63])
    : "r"(a[0]), "r"(a[1]), "r"(a[2]), "r"(a[3]), "l"(db), "r"(sd));
}

__device__ __forceinline__ void wgmma_rs_n144(float* d, const uint32_t* a, uint64_t db, int sd) {
  asm volatile("{ .reg .pred p; setp.ne.b32 p, %77, 0;\n"
      "wgmma.mma_async.sync.aligned.m64n144k16.f32.bf16.bf16 {"
      "%0,%1,%2,%3,%4,%5,%6,%7,%8,%9,%10,%11,%12,%13,%14,%15,"
      "%16,%17,%18,%19,%20,%21,%22,%23,%24,%25,%26,%27,%28,%29,%30,%31,"
      "%32,%33,%34,%35,%36,%37,%38,%39,%40,%41,%42,%43,%44,%45,%46,%47,"
      "%48,%49,%50,%51,%52,%53,%54,%55,%56,%57,%58,%59,%60,%61,%62,%63,"
      "%64,%65,%66,%67,%68,%69,%70,%71"
      "}, {%72,%73,%74,%75}, %76, p, 1, 1, 0; }"
    : "+f"(d[0]), "+f"(d[1]), "+f"(d[2]), "+f"(d[3]), "+f"(d[4]), "+f"(d[5]), "+f"(d[6]), "+f"(d[7]),
      "+f"(d[8]), "+f"(d[9]), "+f"(d[10]), "+f"(d[11]), "+f"(d[12]), "+f"(d[13]), "+f"(d[14]), "+f"(d[15]),
      "+f"(d[16]), "+f"(d[17]), "+f"(d[18]), "+f"(d[19]), "+f"(d[20]), "+f"(d[21]), "+f"(d[22]), "+f"(d[23]),
      "+f"(d[24]), "+f"(d[25]), "+f"(d[26]), "+f"(d[27]), "+f"(d[28]), "+f"(d[29]), "+f"(d[30]), "+f"(d[31]),
      "+f"(d[32]), "+f"(d[33]), "+f"(d[34]), "+f"(d[35]), "+f"(d[36]), "+f"(d[37]), "+f"(d[38]), "+f"(d[39]),
      "+f"(d[40]), "+f"(d[41]), "+f"(d[42]), "+f"(d[43]), "+f"(d[44]), "+f"(d[45]), "+f"(d[46]), "+f"(d[47]),
      "+f"(d[48]), "+f"(d[49]), "+f"(d[50]), "+f"(d[51]), "+f"(d[52]), "+f"(d[53]), "+f"(d[54]), "+f"(d[55]),
      "+f"(d[56]), "+f"(d[57]), "+f"(d[58]), "+f"(d[59]), "+f"(d[60]), "+f"(d[61]), "+f"(d[62]), "+f"(d[63]),
      "+f"(d[64]), "+f"(d[65]), "+f"(d[66]), "+f"(d[67]), "+f"(d[68]), "+f"(d[69]), "+f"(d[70]), "+f"(d[71])
    : "r"(a[0]), "r"(a[1]), "r"(a[2]), "r"(a[3]), "l"(db), "r"(sd));
}

__device__ __forceinline__ void wgmma_rs_n160(float* d, const uint32_t* a, uint64_t db, int sd) {
  asm volatile("{ .reg .pred p; setp.ne.b32 p, %85, 0;\n"
      "wgmma.mma_async.sync.aligned.m64n160k16.f32.bf16.bf16 {"
      "%0,%1,%2,%3,%4,%5,%6,%7,%8,%9,%10,%11,%12,%13,%14,%15,"
      "%16,%17,%18,%19,%20,%21,%22,%23,%24,%25,%26,%27,%28,%29,%30,%31,"
      "%32,%33,%34,%35,%36,%37,%38,%39,%40,%41,%42,%43,%44,%45,%46,%47,"
      "%48,%49,%50,%51,%52,%53,%54,%55,%56,%57,%58,%59,%60,%61,%62,%63,"
      "%64,%65,%66,%67,%68,%69,%70,%71,%72,%73,%74,%75,%76,%77,%78,%79"
      "}, {%80,%81,%82,%83}, %84, p, 1, 1, 0; }"
    : "+f"(d[0]), "+f"(d[1]), "+f"(d[2]), "+f"(d[3]), "+f"(d[4]), "+f"(d[5]), "+f"(d[6]), "+f"(d[7]),
      "+f"(d[8]), "+f"(d[9]), "+f"(d[10]), "+f"(d[11]), "+f"(d[12]), "+f"(d[13]), "+f"(d[14]), "+f"(d[15]),
      "+f"(d[16]), "+f"(d[17]), "+f"(d[18]), "+f"(d[19]), "+f"(d[20]), "+f"(d[21]), "+f"(d[22]), "+f"(d[23]),
      "+f"(d[24]), "+f"(d[25]), "+f"(d[26]), "+f"(d[27]), "+f"(d[28]), "+f"(d[29]), "+f"(d[30]), "+f"(d[31]),
      "+f"(d[32]), "+f"(d[33]), "+f"(d[34]), "+f"(d[35]), "+f"(d[36]), "+f"(d[37]), "+f"(d[38]), "+f"(d[39]),
      "+f"(d[40]), "+f"(d[41]), "+f"(d[42]), "+f"(d[43]), "+f"(d[44]), "+f"(d[45]), "+f"(d[46]), "+f"(d[47]),
      "+f"(d[48]), "+f"(d[49]), "+f"(d[50]), "+f"(d[51]), "+f"(d[52]), "+f"(d[53]), "+f"(d[54]), "+f"(d[55]),
      "+f"(d[56]), "+f"(d[57]), "+f"(d[58]), "+f"(d[59]), "+f"(d[60]), "+f"(d[61]), "+f"(d[62]), "+f"(d[63]),
      "+f"(d[64]), "+f"(d[65]), "+f"(d[66]), "+f"(d[67]), "+f"(d[68]), "+f"(d[69]), "+f"(d[70]), "+f"(d[71]),
      "+f"(d[72]), "+f"(d[73]), "+f"(d[74]), "+f"(d[75]), "+f"(d[76]), "+f"(d[77]), "+f"(d[78]), "+f"(d[79])
    : "r"(a[0]), "r"(a[1]), "r"(a[2]), "r"(a[3]), "l"(db), "r"(sd));
}

__device__ __forceinline__ void wgmma_rs_n176(float* d, const uint32_t* a, uint64_t db, int sd) {
  asm volatile("{ .reg .pred p; setp.ne.b32 p, %93, 0;\n"
      "wgmma.mma_async.sync.aligned.m64n176k16.f32.bf16.bf16 {"
      "%0,%1,%2,%3,%4,%5,%6,%7,%8,%9,%10,%11,%12,%13,%14,%15,"
      "%16,%17,%18,%19,%20,%21,%22,%23,%24,%25,%26,%27,%28,%29,%30,%31,"
      "%32,%33,%34,%35,%36,%37,%38,%39,%40,%41,%42,%43,%44,%45,%46,%47,"
      "%48,%49,%50,%51,%52,%53,%54,%55,%56,%57,%58,%59,%60,%61,%62,%63,"
      "%64,%65,%66,%67,%68,%69,%70,%71,%72,%73,%74,%75,%76,%77,%78,%79,"
      "%80,%81,%82,%83,%84,%85,%86,%87"
      "}, {%88,%89,%90,%91}, %92, p, 1, 1, 0; }"
    : "+f"(d[0]), "+f"(d[1]), "+f"(d[2]), "+f"(d[3]), "+f"(d[4]), "+f"(d[5]), "+f"(d[6]), "+f"(d[7]),
      "+f"(d[8]), "+f"(d[9]), "+f"(d[10]), "+f"(d[11]), "+f"(d[12]), "+f"(d[13]), "+f"(d[14]), "+f"(d[15]),
      "+f"(d[16]), "+f"(d[17]), "+f"(d[18]), "+f"(d[19]), "+f"(d[20]), "+f"(d[21]), "+f"(d[22]), "+f"(d[23]),
      "+f"(d[24]), "+f"(d[25]), "+f"(d[26]), "+f"(d[27]), "+f"(d[28]), "+f"(d[29]), "+f"(d[30]), "+f"(d[31]),
      "+f"(d[32]), "+f"(d[33]), "+f"(d[34]), "+f"(d[35]), "+f"(d[36]), "+f"(d[37]), "+f"(d[38]), "+f"(d[39]),
      "+f"(d[40]), "+f"(d[41]), "+f"(d[42]), "+f"(d[43]), "+f"(d[44]), "+f"(d[45]), "+f"(d[46]), "+f"(d[47]),
      "+f"(d[48]), "+f"(d[49]), "+f"(d[50]), "+f"(d[51]), "+f"(d[52]), "+f"(d[53]), "+f"(d[54]), "+f"(d[55]),
      "+f"(d[56]), "+f"(d[57]), "+f"(d[58]), "+f"(d[59]), "+f"(d[60]), "+f"(d[61]), "+f"(d[62]), "+f"(d[63]),
      "+f"(d[64]), "+f"(d[65]), "+f"(d[66]), "+f"(d[67]), "+f"(d[68]), "+f"(d[69]), "+f"(d[70]), "+f"(d[71]),
      "+f"(d[72]), "+f"(d[73]), "+f"(d[74]), "+f"(d[75]), "+f"(d[76]), "+f"(d[77]), "+f"(d[78]), "+f"(d[79]),
      "+f"(d[80]), "+f"(d[81]), "+f"(d[82]), "+f"(d[83]), "+f"(d[84]), "+f"(d[85]), "+f"(d[86]), "+f"(d[87])
    : "r"(a[0]), "r"(a[1]), "r"(a[2]), "r"(a[3]), "l"(db), "r"(sd));
}

__device__ __forceinline__ void wgmma_rs_n192(float* d, const uint32_t* a, uint64_t db, int sd) {
  asm volatile("{ .reg .pred p; setp.ne.b32 p, %101, 0;\n"
      "wgmma.mma_async.sync.aligned.m64n192k16.f32.bf16.bf16 {"
      "%0,%1,%2,%3,%4,%5,%6,%7,%8,%9,%10,%11,%12,%13,%14,%15,"
      "%16,%17,%18,%19,%20,%21,%22,%23,%24,%25,%26,%27,%28,%29,%30,%31,"
      "%32,%33,%34,%35,%36,%37,%38,%39,%40,%41,%42,%43,%44,%45,%46,%47,"
      "%48,%49,%50,%51,%52,%53,%54,%55,%56,%57,%58,%59,%60,%61,%62,%63,"
      "%64,%65,%66,%67,%68,%69,%70,%71,%72,%73,%74,%75,%76,%77,%78,%79,"
      "%80,%81,%82,%83,%84,%85,%86,%87,%88,%89,%90,%91,%92,%93,%94,%95"
      "}, {%96,%97,%98,%99}, %100, p, 1, 1, 0; }"
    : "+f"(d[0]), "+f"(d[1]), "+f"(d[2]), "+f"(d[3]), "+f"(d[4]), "+f"(d[5]), "+f"(d[6]), "+f"(d[7]),
      "+f"(d[8]), "+f"(d[9]), "+f"(d[10]), "+f"(d[11]), "+f"(d[12]), "+f"(d[13]), "+f"(d[14]), "+f"(d[15]),
      "+f"(d[16]), "+f"(d[17]), "+f"(d[18]), "+f"(d[19]), "+f"(d[20]), "+f"(d[21]), "+f"(d[22]), "+f"(d[23]),
      "+f"(d[24]), "+f"(d[25]), "+f"(d[26]), "+f"(d[27]), "+f"(d[28]), "+f"(d[29]), "+f"(d[30]), "+f"(d[31]),
      "+f"(d[32]), "+f"(d[33]), "+f"(d[34]), "+f"(d[35]), "+f"(d[36]), "+f"(d[37]), "+f"(d[38]), "+f"(d[39]),
      "+f"(d[40]), "+f"(d[41]), "+f"(d[42]), "+f"(d[43]), "+f"(d[44]), "+f"(d[45]), "+f"(d[46]), "+f"(d[47]),
      "+f"(d[48]), "+f"(d[49]), "+f"(d[50]), "+f"(d[51]), "+f"(d[52]), "+f"(d[53]), "+f"(d[54]), "+f"(d[55]),
      "+f"(d[56]), "+f"(d[57]), "+f"(d[58]), "+f"(d[59]), "+f"(d[60]), "+f"(d[61]), "+f"(d[62]), "+f"(d[63]),
      "+f"(d[64]), "+f"(d[65]), "+f"(d[66]), "+f"(d[67]), "+f"(d[68]), "+f"(d[69]), "+f"(d[70]), "+f"(d[71]),
      "+f"(d[72]), "+f"(d[73]), "+f"(d[74]), "+f"(d[75]), "+f"(d[76]), "+f"(d[77]), "+f"(d[78]), "+f"(d[79]),
      "+f"(d[80]), "+f"(d[81]), "+f"(d[82]), "+f"(d[83]), "+f"(d[84]), "+f"(d[85]), "+f"(d[86]), "+f"(d[87]),
      "+f"(d[88]), "+f"(d[89]), "+f"(d[90]), "+f"(d[91]), "+f"(d[92]), "+f"(d[93]), "+f"(d[94]), "+f"(d[95])
    : "r"(a[0]), "r"(a[1]), "r"(a[2]), "r"(a[3]), "l"(db), "r"(sd));
}

__device__ __forceinline__ void wgmma_rs_n208(float* d, const uint32_t* a, uint64_t db, int sd) {
  asm volatile("{ .reg .pred p; setp.ne.b32 p, %109, 0;\n"
      "wgmma.mma_async.sync.aligned.m64n208k16.f32.bf16.bf16 {"
      "%0,%1,%2,%3,%4,%5,%6,%7,%8,%9,%10,%11,%12,%13,%14,%15,"
      "%16,%17,%18,%19,%20,%21,%22,%23,%24,%25,%26,%27,%28,%29,%30,%31,"
      "%32,%33,%34,%35,%36,%37,%38,%39,%40,%41,%42,%43,%44,%45,%46,%47,"
      "%48,%49,%50,%51,%52,%53,%54,%55,%56,%57,%58,%59,%60,%61,%62,%63,"
      "%64,%65,%66,%67,%68,%69,%70,%71,%72,%73,%74,%75,%76,%77,%78,%79,"
      "%80,%81,%82,%83,%84,%85,%86,%87,%88,%89,%90,%91,%92,%93,%94,%95,"
      "%96,%97,%98,%99,%100,%101,%102,%103"
      "}, {%104,%105,%106,%107}, %108, p, 1, 1, 0; }"
    : "+f"(d[0]), "+f"(d[1]), "+f"(d[2]), "+f"(d[3]), "+f"(d[4]), "+f"(d[5]), "+f"(d[6]), "+f"(d[7]),
      "+f"(d[8]), "+f"(d[9]), "+f"(d[10]), "+f"(d[11]), "+f"(d[12]), "+f"(d[13]), "+f"(d[14]), "+f"(d[15]),
      "+f"(d[16]), "+f"(d[17]), "+f"(d[18]), "+f"(d[19]), "+f"(d[20]), "+f"(d[21]), "+f"(d[22]), "+f"(d[23]),
      "+f"(d[24]), "+f"(d[25]), "+f"(d[26]), "+f"(d[27]), "+f"(d[28]), "+f"(d[29]), "+f"(d[30]), "+f"(d[31]),
      "+f"(d[32]), "+f"(d[33]), "+f"(d[34]), "+f"(d[35]), "+f"(d[36]), "+f"(d[37]), "+f"(d[38]), "+f"(d[39]),
      "+f"(d[40]), "+f"(d[41]), "+f"(d[42]), "+f"(d[43]), "+f"(d[44]), "+f"(d[45]), "+f"(d[46]), "+f"(d[47]),
      "+f"(d[48]), "+f"(d[49]), "+f"(d[50]), "+f"(d[51]), "+f"(d[52]), "+f"(d[53]), "+f"(d[54]), "+f"(d[55]),
      "+f"(d[56]), "+f"(d[57]), "+f"(d[58]), "+f"(d[59]), "+f"(d[60]), "+f"(d[61]), "+f"(d[62]), "+f"(d[63]),
      "+f"(d[64]), "+f"(d[65]), "+f"(d[66]), "+f"(d[67]), "+f"(d[68]), "+f"(d[69]), "+f"(d[70]), "+f"(d[71]),
      "+f"(d[72]), "+f"(d[73]), "+f"(d[74]), "+f"(d[75]), "+f"(d[76]), "+f"(d[77]), "+f"(d[78]), "+f"(d[79]),
      "+f"(d[80]), "+f"(d[81]), "+f"(d[82]), "+f"(d[83]), "+f"(d[84]), "+f"(d[85]), "+f"(d[86]), "+f"(d[87]),
      "+f"(d[88]), "+f"(d[89]), "+f"(d[90]), "+f"(d[91]), "+f"(d[92]), "+f"(d[93]), "+f"(d[94]), "+f"(d[95]),
      "+f"(d[96]), "+f"(d[97]), "+f"(d[98]), "+f"(d[99]), "+f"(d[100]), "+f"(d[101]), "+f"(d[102]), "+f"(d[103])
    : "r"(a[0]), "r"(a[1]), "r"(a[2]), "r"(a[3]), "l"(db), "r"(sd));
}

__device__ __forceinline__ void wgmma_rs_n224(float* d, const uint32_t* a, uint64_t db, int sd) {
  asm volatile("{ .reg .pred p; setp.ne.b32 p, %117, 0;\n"
      "wgmma.mma_async.sync.aligned.m64n224k16.f32.bf16.bf16 {"
      "%0,%1,%2,%3,%4,%5,%6,%7,%8,%9,%10,%11,%12,%13,%14,%15,"
      "%16,%17,%18,%19,%20,%21,%22,%23,%24,%25,%26,%27,%28,%29,%30,%31,"
      "%32,%33,%34,%35,%36,%37,%38,%39,%40,%41,%42,%43,%44,%45,%46,%47,"
      "%48,%49,%50,%51,%52,%53,%54,%55,%56,%57,%58,%59,%60,%61,%62,%63,"
      "%64,%65,%66,%67,%68,%69,%70,%71,%72,%73,%74,%75,%76,%77,%78,%79,"
      "%80,%81,%82,%83,%84,%85,%86,%87,%88,%89,%90,%91,%92,%93,%94,%95,"
      "%96,%97,%98,%99,%100,%101,%102,%103,%104,%105,%106,%107,%108,%109,%110,%111"
      "}, {%112,%113,%114,%115}, %116, p, 1, 1, 0; }"
    : "+f"(d[0]), "+f"(d[1]), "+f"(d[2]), "+f"(d[3]), "+f"(d[4]), "+f"(d[5]), "+f"(d[6]), "+f"(d[7]),
      "+f"(d[8]), "+f"(d[9]), "+f"(d[10]), "+f"(d[11]), "+f"(d[12]), "+f"(d[13]), "+f"(d[14]), "+f"(d[15]),
      "+f"(d[16]), "+f"(d[17]), "+f"(d[18]), "+f"(d[19]), "+f"(d[20]), "+f"(d[21]), "+f"(d[22]), "+f"(d[23]),
      "+f"(d[24]), "+f"(d[25]), "+f"(d[26]), "+f"(d[27]), "+f"(d[28]), "+f"(d[29]), "+f"(d[30]), "+f"(d[31]),
      "+f"(d[32]), "+f"(d[33]), "+f"(d[34]), "+f"(d[35]), "+f"(d[36]), "+f"(d[37]), "+f"(d[38]), "+f"(d[39]),
      "+f"(d[40]), "+f"(d[41]), "+f"(d[42]), "+f"(d[43]), "+f"(d[44]), "+f"(d[45]), "+f"(d[46]), "+f"(d[47]),
      "+f"(d[48]), "+f"(d[49]), "+f"(d[50]), "+f"(d[51]), "+f"(d[52]), "+f"(d[53]), "+f"(d[54]), "+f"(d[55]),
      "+f"(d[56]), "+f"(d[57]), "+f"(d[58]), "+f"(d[59]), "+f"(d[60]), "+f"(d[61]), "+f"(d[62]), "+f"(d[63]),
      "+f"(d[64]), "+f"(d[65]), "+f"(d[66]), "+f"(d[67]), "+f"(d[68]), "+f"(d[69]), "+f"(d[70]), "+f"(d[71]),
      "+f"(d[72]), "+f"(d[73]), "+f"(d[74]), "+f"(d[75]), "+f"(d[76]), "+f"(d[77]), "+f"(d[78]), "+f"(d[79]),
      "+f"(d[80]), "+f"(d[81]), "+f"(d[82]), "+f"(d[83]), "+f"(d[84]), "+f"(d[85]), "+f"(d[86]), "+f"(d[87]),
      "+f"(d[88]), "+f"(d[89]), "+f"(d[90]), "+f"(d[91]), "+f"(d[92]), "+f"(d[93]), "+f"(d[94]), "+f"(d[95]),
      "+f"(d[96]), "+f"(d[97]), "+f"(d[98]), "+f"(d[99]), "+f"(d[100]), "+f"(d[101]), "+f"(d[102]), "+f"(d[103]),
      "+f"(d[104]), "+f"(d[105]), "+f"(d[106]), "+f"(d[107]), "+f"(d[108]), "+f"(d[109]), "+f"(d[110]), "+f"(d[111])
    : "r"(a[0]), "r"(a[1]), "r"(a[2]), "r"(a[3]), "l"(db), "r"(sd));
}

__device__ __forceinline__ void wgmma_rs_n240(float* d, const uint32_t* a, uint64_t db, int sd) {
  asm volatile("{ .reg .pred p; setp.ne.b32 p, %125, 0;\n"
      "wgmma.mma_async.sync.aligned.m64n240k16.f32.bf16.bf16 {"
      "%0,%1,%2,%3,%4,%5,%6,%7,%8,%9,%10,%11,%12,%13,%14,%15,"
      "%16,%17,%18,%19,%20,%21,%22,%23,%24,%25,%26,%27,%28,%29,%30,%31,"
      "%32,%33,%34,%35,%36,%37,%38,%39,%40,%41,%42,%43,%44,%45,%46,%47,"
      "%48,%49,%50,%51,%52,%53,%54,%55,%56,%57,%58,%59,%60,%61,%62,%63,"
      "%64,%65,%66,%67,%68,%69,%70,%71,%72,%73,%74,%75,%76,%77,%78,%79,"
      "%80,%81,%82,%83,%84,%85,%86,%87,%88,%89,%90,%91,%92,%93,%94,%95,"
      "%96,%97,%98,%99,%100,%101,%102,%103,%104,%105,%106,%107,%108,%109,%110,%111,"
      "%112,%113,%114,%115,%116,%117,%118,%119"
      "}, {%120,%121,%122,%123}, %124, p, 1, 1, 0; }"
    : "+f"(d[0]), "+f"(d[1]), "+f"(d[2]), "+f"(d[3]), "+f"(d[4]), "+f"(d[5]), "+f"(d[6]), "+f"(d[7]),
      "+f"(d[8]), "+f"(d[9]), "+f"(d[10]), "+f"(d[11]), "+f"(d[12]), "+f"(d[13]), "+f"(d[14]), "+f"(d[15]),
      "+f"(d[16]), "+f"(d[17]), "+f"(d[18]), "+f"(d[19]), "+f"(d[20]), "+f"(d[21]), "+f"(d[22]), "+f"(d[23]),
      "+f"(d[24]), "+f"(d[25]), "+f"(d[26]), "+f"(d[27]), "+f"(d[28]), "+f"(d[29]), "+f"(d[30]), "+f"(d[31]),
      "+f"(d[32]), "+f"(d[33]), "+f"(d[34]), "+f"(d[35]), "+f"(d[36]), "+f"(d[37]), "+f"(d[38]), "+f"(d[39]),
      "+f"(d[40]), "+f"(d[41]), "+f"(d[42]), "+f"(d[43]), "+f"(d[44]), "+f"(d[45]), "+f"(d[46]), "+f"(d[47]),
      "+f"(d[48]), "+f"(d[49]), "+f"(d[50]), "+f"(d[51]), "+f"(d[52]), "+f"(d[53]), "+f"(d[54]), "+f"(d[55]),
      "+f"(d[56]), "+f"(d[57]), "+f"(d[58]), "+f"(d[59]), "+f"(d[60]), "+f"(d[61]), "+f"(d[62]), "+f"(d[63]),
      "+f"(d[64]), "+f"(d[65]), "+f"(d[66]), "+f"(d[67]), "+f"(d[68]), "+f"(d[69]), "+f"(d[70]), "+f"(d[71]),
      "+f"(d[72]), "+f"(d[73]), "+f"(d[74]), "+f"(d[75]), "+f"(d[76]), "+f"(d[77]), "+f"(d[78]), "+f"(d[79]),
      "+f"(d[80]), "+f"(d[81]), "+f"(d[82]), "+f"(d[83]), "+f"(d[84]), "+f"(d[85]), "+f"(d[86]), "+f"(d[87]),
      "+f"(d[88]), "+f"(d[89]), "+f"(d[90]), "+f"(d[91]), "+f"(d[92]), "+f"(d[93]), "+f"(d[94]), "+f"(d[95]),
      "+f"(d[96]), "+f"(d[97]), "+f"(d[98]), "+f"(d[99]), "+f"(d[100]), "+f"(d[101]), "+f"(d[102]), "+f"(d[103]),
      "+f"(d[104]), "+f"(d[105]), "+f"(d[106]), "+f"(d[107]), "+f"(d[108]), "+f"(d[109]), "+f"(d[110]), "+f"(d[111]),
      "+f"(d[112]), "+f"(d[113]), "+f"(d[114]), "+f"(d[115]), "+f"(d[116]), "+f"(d[117]), "+f"(d[118]), "+f"(d[119])
    : "r"(a[0]), "r"(a[1]), "r"(a[2]), "r"(a[3]), "l"(db), "r"(sd));
}

__device__ __forceinline__ void wgmma_rs_n256(float* d, const uint32_t* a, uint64_t db, int sd) {
  asm volatile("{ .reg .pred p; setp.ne.b32 p, %133, 0;\n"
      "wgmma.mma_async.sync.aligned.m64n256k16.f32.bf16.bf16 {"
      "%0,%1,%2,%3,%4,%5,%6,%7,%8,%9,%10,%11,%12,%13,%14,%15,"
      "%16,%17,%18,%19,%20,%21,%22,%23,%24,%25,%26,%27,%28,%29,%30,%31,"
      "%32,%33,%34,%35,%36,%37,%38,%39,%40,%41,%42,%43,%44,%45,%46,%47,"
      "%48,%49,%50,%51,%52,%53,%54,%55,%56,%57,%58,%59,%60,%61,%62,%63,"
      "%64,%65,%66,%67,%68,%69,%70,%71,%72,%73,%74,%75,%76,%77,%78,%79,"
      "%80,%81,%82,%83,%84,%85,%86,%87,%88,%89,%90,%91,%92,%93,%94,%95,"
      "%96,%97,%98,%99,%100,%101,%102,%103,%104,%105,%106,%107,%108,%109,%110,%111,"
      "%112,%113,%114,%115,%116,%117,%118,%119,%120,%121,%122,%123,%124,%125,%126,%127"
      "}, {%128,%129,%130,%131}, %132, p, 1, 1, 0; }"
    : "+f"(d[0]), "+f"(d[1]), "+f"(d[2]), "+f"(d[3]), "+f"(d[4]), "+f"(d[5]), "+f"(d[6]), "+f"(d[7]),
      "+f"(d[8]), "+f"(d[9]), "+f"(d[10]), "+f"(d[11]), "+f"(d[12]), "+f"(d[13]), "+f"(d[14]), "+f"(d[15]),
      "+f"(d[16]), "+f"(d[17]), "+f"(d[18]), "+f"(d[19]), "+f"(d[20]), "+f"(d[21]), "+f"(d[22]), "+f"(d[23]),
      "+f"(d[24]), "+f"(d[25]), "+f"(d[26]), "+f"(d[27]), "+f"(d[28]), "+f"(d[29]), "+f"(d[30]), "+f"(d[31]),
      "+f"(d[32]), "+f"(d[33]), "+f"(d[34]), "+f"(d[35]), "+f"(d[36]), "+f"(d[37]), "+f"(d[38]), "+f"(d[39]),
      "+f"(d[40]), "+f"(d[41]), "+f"(d[42]), "+f"(d[43]), "+f"(d[44]), "+f"(d[45]), "+f"(d[46]), "+f"(d[47]),
      "+f"(d[48]), "+f"(d[49]), "+f"(d[50]), "+f"(d[51]), "+f"(d[52]), "+f"(d[53]), "+f"(d[54]), "+f"(d[55]),
      "+f"(d[56]), "+f"(d[57]), "+f"(d[58]), "+f"(d[59]), "+f"(d[60]), "+f"(d[61]), "+f"(d[62]), "+f"(d[63]),
      "+f"(d[64]), "+f"(d[65]), "+f"(d[66]), "+f"(d[67]), "+f"(d[68]), "+f"(d[69]), "+f"(d[70]), "+f"(d[71]),
      "+f"(d[72]), "+f"(d[73]), "+f"(d[74]), "+f"(d[75]), "+f"(d[76]), "+f"(d[77]), "+f"(d[78]), "+f"(d[79]),
      "+f"(d[80]), "+f"(d[81]), "+f"(d[82]), "+f"(d[83]), "+f"(d[84]), "+f"(d[85]), "+f"(d[86]), "+f"(d[87]),
      "+f"(d[88]), "+f"(d[89]), "+f"(d[90]), "+f"(d[91]), "+f"(d[92]), "+f"(d[93]), "+f"(d[94]), "+f"(d[95]),
      "+f"(d[96]), "+f"(d[97]), "+f"(d[98]), "+f"(d[99]), "+f"(d[100]), "+f"(d[101]), "+f"(d[102]), "+f"(d[103]),
      "+f"(d[104]), "+f"(d[105]), "+f"(d[106]), "+f"(d[107]), "+f"(d[108]), "+f"(d[109]), "+f"(d[110]), "+f"(d[111]),
      "+f"(d[112]), "+f"(d[113]), "+f"(d[114]), "+f"(d[115]), "+f"(d[116]), "+f"(d[117]), "+f"(d[118]), "+f"(d[119]),
      "+f"(d[120]), "+f"(d[121]), "+f"(d[122]), "+f"(d[123]), "+f"(d[124]), "+f"(d[125]), "+f"(d[126]), "+f"(d[127])
    : "r"(a[0]), "r"(a[1]), "r"(a[2]), "r"(a[3]), "l"(db), "r"(sd));
}

__device__ __forceinline__ void ln_finish(float mean, float var, float& mb, float& rinv) {
  mb = round_bf16(mean);
  float den = round_bf16(sqrtf(round_bf16(round_bf16(var) + 1e-5f)));
  rinv = 1.0f / den;
}
__device__ __forceinline__ uint32_t ln_apply(uint32_t x2, uint32_t mb2, float rinv) {
  uint32_t c = bsub2(x2, mb2);
  return pack_bf16(bf_lo(c) * rinv, bf_hi(c) * rinv);
}
__device__ __forceinline__ int conv_channel(int cta, int i) {
  if (i < N_SHORT) { const int e = i * N_CONV_CTA + cta; return (e / 66) * 72 + e % 66; }
  const int l = (i - N_SHORT) * 4 + cta;
  return (l / 6) * 72 + 66 + l % 6;
}

__global__ void __cluster_dims__(2, 1, 1) __launch_bounds__(384, 1) fused_kernel(const __grid_constant__ Params P) {
  extern __shared__ uint8_t smem_raw[];
  const uint32_t sb = (smem_u32(smem_raw) + 1023) & ~1023u;
  const uint32_t bars = sb + SM_BAR;
  const int tid = threadIdx.x, warp = tid >> 5, lane = tid & 31;
  const int cl = blockIdx.x >> 1, rank = blockIdx.x & 1;
  const int p0 = P.roles.p0[cl], p0b = 2 * p0 + rank;

  uint32_t xr[18];
  const int ln_row = p0b * 16 + warp * 2 + (lane >> 4);
  if (warp < 8 && p0 >= 0) {
    const uint2* src = reinterpret_cast<const uint2*>(P.x + (size_t)ln_row * D_) + (lane & 15);
#pragma unroll
    for (int j = 0; j < 9; j++) asm volatile("ld.global.nc.v2.u32 {%0,%1}, [%2];" : "=r"(xr[2 * j]), "=r"(xr[2 * j + 1]) : "l"(src + 16 * j));
  }
  const uint32_t tag = ld_flag(&g_epoch) + 1;
  const int g1m = P.roles.g1m[cl], g1n = P.roles.g1n[cl], cv = P.roles.cv[cl], g2m = P.roles.g2m[cl], g2n = P.roles.g2n[cl];
  const int cvc = 2 * cv + rank;
  const int n_conv = cv < 0 ? 0 : (cv < 2 ? N_SHORT + N_LONG_EXTRA : N_SHORT);
  const int it2 = g1m >= 0 ? G1_KB : 0;
  const int xslot = (it2 + G2_KB) % NSTAGE;
  const int dk = g2n * 144 + rank * 72;
  if (tid == 256) {
    for (int s = 0; s < NSTAGE; s++) { mbar_init(bars + 8 * (B_FULL + s), 1); mbar_init(bars + 8 * (B_EMPTY + s), 2); }
    for (int s = 0; s < CV_NSLOT; s++) { mbar_init(bars + 8 * (B_CFULL + s), 1); mbar_init(bars + 8 * (B_CEMPTY + s), 4); }
    mbar_init(bars + 8 * B_CDONE, 8); mbar_init(bars + 8 * B_XRDY, 1); mbar_init(bars + 8 * B_XFULL, 1); mbar_init(bars + 8 * (B_XFULL + 1), 1);
    mbar_init(bars + 8 * B_XT, 1); mbar_init(bars + 8 * B_Y2, 3);
    asm volatile("fence.mbarrier_init.release.cluster;" ::: "memory");
  }
  __syncthreads();
  asm volatile("barrier.cluster.arrive.relaxed.aligned;" ::: "memory");

  if (warp >= 8) {
    asm volatile("setmaxnreg.dec.sync.aligned.u32 56;");
    if (warp == 8) {
      asm volatile("barrier.cluster.wait.aligned;" ::: "memory");
      if (lane == 0) {
        if (g1m >= 0) {
          const int fg = (2 * g1m + rank) * 2, dg = g1n * 3;
          for (int s = 0; s < NSTAGE; s++) {
            mbar_expect_tx(bars + 8 * (B_FULL + s), G1_BYTES);
            tma3d(sb + s * SLOT, &P.m_w1, 0, s * 64, fg, bars + 8 * (B_FULL + s));
          }
          await(C_H, tag * 128);
          TLREC(2);
          fence_async_global();
          for (int s = 0; s < NSTAGE; s++) tma3d(sb + s * SLOT + 16384, &P.m_h, 0, s * 64, dg, bars + 8 * (B_FULL + s));
          for (int kb = NSTAGE; kb < G1_KB; kb++) {
            const int s = kb % NSTAGE;
            mbar_wait(bars + 8 * (B_EMPTY + s), ((kb / NSTAGE) - 1) & 1);
            mbar_expect_tx(bars + 8 * (B_FULL + s), G1_BYTES);
            tma3d(sb + s * SLOT, &P.m_w1, 0, kb * 64, fg, bars + 8 * (B_FULL + s));
            tma3d(sb + s * SLOT + 16384, &P.m_h, 0, kb * 64, dg, bars + 8 * (B_FULL + s));
          }
        } else {
          for (int i = 0; i < CV_NSLOT; i++) {
            mbar_expect_tx(bars + 8 * (B_CFULL + i), 8192 + 4096);
            bulk_load(sb + CV_BASE + i * CV_SLOT + CV_KOFF + 32, P.ssm_k + (size_t)conv_channel(cvc, i) * S_, 4096, bars + 8 * (B_CFULL + i));
          }
          int ready = -1;
          for (int i = 0; i < n_conv; i++) {
            const int ch = conv_channel(cvc, i), s = i % CV_NSLOT;
            const uint32_t slot = sb + CV_BASE + s * CV_SLOT, fb = bars + 8 * (B_CFULL + s);
            if (i >= CV_NSLOT) {
              mbar_wait(bars + 8 * (B_CEMPTY + s), ((i / CV_NSLOT) - 1) & 1);
              mbar_expect_tx(fb, 8192 + 4096);
              bulk_load(slot + CV_KOFF + 32, P.ssm_k + (size_t)ch * S_, 4096, fb);
            }
            const int r = ch / 96;
            if (r > ready) {
              await(C_KV + r, tag * 128);
              fence_async_global();
              if (r == 0) TLREC(18);
              ready = r;
            }
            bulk_load(slot, g_ub + (size_t)ch * 4096, 8192, fb);
          }
        }
        if (g2m >= 0) {
          const int sg = g2m * 2, ds = g2n * 144 + (rank ^ 1) * 72;
          const int cu0 = C_U + ((g2n * 144) / 192) * 4 + rank * 2, cu1 = C_U + ((g2n * 144 + 143) / 192) * 4 + rank * 2;
          const int npre = g1m >= 0 ? 4 : 3;
          for (int kb = 0; kb < npre; kb++) {
            const int p = it2 + kb, s = p % NSTAGE;
            if (p >= NSTAGE) mbar_wait(bars + 8 * (B_EMPTY + s), ((p / NSTAGE) - 1) & 1);
            mbar_expect_tx(bars + 8 * (B_FULL + s), G2_BYTES);
            tma3d(sb + s * SLOT, &P.m_w2, 0, (rank * G2_KB + 2 * kb) * 64, sg, bars + 8 * (B_FULL + s));
          }
          for (int kb = 0; kb < G2_KB; kb++) {
            const int p = it2 + kb, s = p % NSTAGE;
            const int k0 = (rank * G2_KB + (kb < 18 ? 2 * kb : 2 * kb - 35)) * 64;
            const uint32_t fb = bars + 8 * (B_FULL + s);
            if (kb == 0 || kb == 18) {
              await(cu0 + (kb != 0), tag * 18);
              await(cu1 + (kb != 0), tag * 18);
              fence_async_global();
              if (kb == 0) TLREC(6);
            }
            if (kb >= npre) {
              if (p >= NSTAGE) mbar_wait(bars + 8 * (B_EMPTY + s), ((p / NSTAGE) - 1) & 1);
              else if (kb == npre) { mbar_wait(bars + 8 * B_CDONE, 0); fence_async_smem(); }
              mbar_expect_tx(fb, G2_BYTES);
              tma3d(sb + s * SLOT, &P.m_w2, 0, k0, sg, fb);
            }
            tma2d(sb + s * SLOT + 16384, &P.m_uld, k0, ds, fb);
            tma2d(sb + s * SLOT + 16384 + 9216, &P.m_uld, k0, dk, fb);
            if (kb == 10) {
              mbar_expect_tx(bars + 8 * B_XT, 18432);
              for (int j = 0; j < 8; j++)
                tma2d(sb + ((xslot + 1 + (j >> 1)) % NSTAGE) * SLOT + G2_BYTES + (j & 1) * 2304, &P.m_x, dk, g2m * 128 + j * 16, bars + 8 * B_XT);
            }
          }
          mbar_expect_tx(bars + 8 * B_XFULL, 18432);
          mbar_expect_tx(bars + 8 * (B_XFULL + 1), 18432);
          mbar_wait(bars + 8 * (B_EMPTY + xslot), (((it2 + G2_KB) / NSTAGE) - 1) & 1);
          mbar_arrive_remote(mapa(bars + 8 * B_XRDY, rank ^ 1));
        }
      }
    } else {
      const int ht = tid - 288;
      if (p0 >= 0) {
        const int hf = ht / 48, pr = ht % 48;
        const int s0 = p0b * 16 + hf * 8;
        const bool first = s0 == 0, odd = lane & 1;
        for (int r = 0; r < KV_ROUNDS; r++) {
          const int d = r * 96 + 2 * pr;
          const __nv_bfloat16* kp = P.k + (ptrdiff_t)(s0 - 4) * D_ + d;
          const __nv_bfloat16* vp = P.v + (ptrdiff_t)(s0 - 1) * D_ + d;
          uint32_t kk[12], vv[9];
#pragma unroll
          for (int j = 0; j < 12; j++) kk[j] = (j < 4 && first) ? 0u : ldg32(kp + j * D_);
#pragma unroll
          for (int j = 0; j < 9; j++) vv[j] = (j < 1 && first) ? 0u : ldg32(vp + j * D_);
          const uint4 w = __ldg(reinterpret_cast<const uint4*>(P.shift_k + d * 4));
          const uint32_t w0 = __byte_perm(w.x, w.z, 0x5410), w1 = __byte_perm(w.x, w.z, 0x7632);
          const uint32_t w2 = __byte_perm(w.y, w.w, 0x5410), w3 = __byte_perm(w.y, w.w, 0x7632);
#pragma unroll
          for (int j = 0; j < 9; j++) {
            uint32_t a = bmul2(kk[j], w3);
            a = badd2(a, bmul2(kk[j + 1], w2));
            a = badd2(a, bmul2(kk[j + 2], w1));
            a = badd2(a, bmul2(kk[j + 3], w0));
            vv[j] = bmul2(a, vv[j]);
          }
          uint32_t da[8], db[8];
#pragma unroll
          for (int j = 0; j < 8; j++) {
            const uint32_t o = __shfl_xor_sync(0xffffffffu, odd ? vv[j] : vv[j + 1], 1);
            da[j] = odd ? o : vv[j];
            db[j] = odd ? vv[j + 1] : o;
          }
          uint4* dst = reinterpret_cast<uint4*>(g_ub + (size_t)(d & ~3) * 4096) + (1 - hf) * 256 + 2 * (127 - p0b) + odd;
#pragma unroll
          for (int c = 0; c < 2; c++) {
            const uint32_t sel = c ? 0x7632 : 0x5410;
            dst[c * 512] = make_uint4(__byte_perm(da[7], da[6], sel), __byte_perm(da[5], da[4], sel), __byte_perm(da[3], da[2], sel), __byte_perm(da[1], da[0], sel));
            dst[(c + 2) * 512] = make_uint4(__byte_perm(db[7], db[6], sel), __byte_perm(db[5], db[4], sel), __byte_perm(db[3], db[2], sel), __byte_perm(db[1], db[0], sel));
          }
          fence_async_global();
          bar_sync(1, 96);
          if (ht == 0) { signal(C_KV + r); TLREC(22 + r); }
          __syncwarp();
        }
      }
      __syncwarp();
      asm volatile("barrier.cluster.wait.aligned;" ::: "memory");
      if (g1m >= 0 && warp < 11 && lane == 0) {
        const int wg = warp - 9, fb64 = (2 * g1m + rank) * 2 + wg;
        const uint32_t stg = wg == 0 ? sb + SM_DED : sb + ((G1_KB - 1) % NSTAGE) * SLOT;
        for (int c = 0; c < 3; c++) {
          mbar_wait(bars + 8 * (B_CEMPTY + wg * 3 + c), 0);
          tma2d_store(&P.m_ust, stg + c * 8192, fb64 * 64, g1n * 192 + c * 64);
        }
        TLREC(13 + wg);
        bulk_commit();
        if (wg == 1) { bulk_wait_read(); mbar_arrive(bars + 8 * (B_EMPTY + (G1_KB - 1) % NSTAGE)); }
        bulk_wait_all();
        signal(C_U + g1n * 4 + (fb64 / G2_KB) * 2 + wg);
        TLREC(15 + wg);
      }
      __syncwarp();
      if (g2m >= 0) {
        const int s = g2m * 128 + (ht & 15) * 8;
        const __nv_bfloat16* up = g_ub + ((1 - (ht & 1)) * 256 + 2 * (127 - (s >> 4)) + 1) * 8;
        for (int i = 0; i < 12; i++) {
          if (i == 0 || i == 11) {
            if (ht == 64) await(i == 0 ? C_YA : C_YB, tag * (i == 0 ? 2 * N_CONV_CTA : 8));
            __syncwarp();
            bar_sync(1, 96);
            if (ht == 64) TLREC(i == 0 ? 8 : 19);
          }
          const int dl = 6 * i + (ht >> 4), d = dk + dl;
          const __nv_bfloat16* yp = g_yp + (size_t)d * 4 * S_ + s;
          uint4 pv[4];
#pragma unroll
          for (int w = 0; w < 4; w++) pv[w] = s >= 16 * w ? ldg128_cg(yp + w * (S_ - 16)) : make_uint4(0, 0, 0, 0);
          const uint4 uu = ldg128_cg(up + (size_t)d * 4096);
          const uint32_t dd = __byte_perm((uint32_t)__bfloat16_as_ushort(P.ssm_D[d]), 0, 0x1010);
          auto comb = [&](uint32_t a, uint32_t b, uint32_t c, uint32_t e, uint32_t u) {
            return badd2(pack_bf16((bf_lo(a) + bf_lo(b)) + (bf_lo(c) + bf_lo(e)), (bf_hi(a) + bf_hi(b)) + (bf_hi(c) + bf_hi(e))),
                         bmul2(__byte_perm(u, 0, 0x1032), dd));
          };
          sts128(sb + SM_DED + dl * 256 + (((ht & 15) ^ (dl & 7)) << 4),
                 make_uint4(comb(pv[0].x, pv[1].x, pv[2].x, pv[3].x, uu.w), comb(pv[0].y, pv[1].y, pv[2].y, pv[3].y, uu.z),
                            comb(pv[0].z, pv[1].z, pv[2].z, pv[3].z, uu.y), comb(pv[0].w, pv[1].w, pv[2].w, pv[3].w, uu.x)));
        }
        __syncwarp();
        if (lane == 0) mbar_arrive(bars + 8 * B_Y2);
        if (ht == 64) TLREC(31);
      }
    }
    TLEND();
  } else {
    asm volatile("setmaxnreg.inc.sync.aligned.u32 224;");
    const int wg = warp >> 2, w = warp & 3, g = lane >> 2, t = lane & 3, wtid = tid & 127;
    if (p0 >= 0) {
      float c[36];
      float s0 = 0.f, s1 = 0.f;
#pragma unroll
      for (int i = 0; i < 18; i++) { c[2 * i] = bf_lo(xr[i]); c[2 * i + 1] = bf_hi(xr[i]); s0 += c[2 * i]; s1 += c[2 * i + 1]; }
      const float ml = (s0 + s1) * (1.0f / 36.0f);
      if (tid == 0 && ml != 123.456f) TLREC(28);
      s0 = 0.f; s1 = 0.f;
#pragma unroll
      for (int i = 0; i < 18; i++) { c[2 * i] -= ml; c[2 * i + 1] -= ml; s0 = fmaf(c[2 * i], c[2 * i], s0); s1 = fmaf(c[2 * i + 1], c[2 * i + 1], s1); }
      float m = ml, q = s0 + s1, n2 = 18.f;
#pragma unroll
      for (int o = 1; o < 16; o <<= 1) {
        const float mo = __shfl_xor_sync(0xffffffffu, m, o), qo = __shfl_xor_sync(0xffffffffu, q, o);
        const float dl = m - mo;
        q = fmaf(dl * dl, n2, q + qo);
        m = 0.5f * (m + mo);
        n2 *= 2.f;
      }
      const float var = q * (1.0f / 576.0f);
      float mb, rinv, mb2, rinv2;
      ln_finish(m, var, mb, rinv);
      ln_finish((m - mb) * rinv, var * rinv * rinv, mb2, rinv2);
      const float ca = rinv * rinv2, cb = fmaf(ml - mb, rinv, -mb2) * rinv2;
      uint2* dst = reinterpret_cast<uint2*>(g_h + (size_t)ln_row * D_) + (lane & 15);
#pragma unroll
      for (int j = 0; j < 9; j++)
        dst[16 * j] = make_uint2(pack_bf16(fmaf(c[4 * j], ca, cb), fmaf(c[4 * j + 1], ca, cb)), pack_bf16(fmaf(c[4 * j + 2], ca, cb), fmaf(c[4 * j + 3], ca, cb)));
      if ((lane & 15) == 0) g_stats[ln_row] = make_float4(mb, rinv, 0.f, 0.f);
      fence_async_global();
      bar_sync(2, 256);
      if (tid == 0) { TLREC(29); signal(C_H); TLREC(1); }
    }
    __syncwarp();
    asm volatile("barrier.cluster.wait.aligned;" ::: "memory");
    if (g1m >= 0) {
      const int frow = ((2 * g1m + rank) * 2 + wg) * 64 + w * 16 + g;
      const uint32_t bias0 = __byte_perm((uint32_t)__bfloat16_as_ushort(P.b1[frow]), 0, 0x1010);
      const uint32_t bias1 = __byte_perm((uint32_t)__bfloat16_as_ushort(P.b1[frow + 8]), 0, 0x1010);
      float acc[96];
#pragma unroll 1
      for (int kb = 0; kb < G1_KB; kb++) {
        const int s = kb % NSTAGE;
        const bool yield = wg == 1 && kb == G1_KB - G1_TAIL;
        if (yield) {
          wg_wait<0>();
          if (wtid == 0) mbar_arrive(bars + 8 * (B_EMPTY + (kb - 1) % NSTAGE));
          bar_sync(5, 256);
        }
        mbar_wait(bars + 8 * (B_FULL + s), (kb / NSTAGE) & 1);
        if (kb == 0 && tid == 0) TLREC(3);
        if (kb == 27 && wtid == 0) TLREC(20 + wg);
        if (kb == 31 && tid == 0) TLREC(30);
        const uint64_t da = make_desc(sb + s * SLOT + wg * 8192, 8192, 1024, 1), db = make_desc(sb + s * SLOT + 16384, 8192, 1024, 1);
        wg_fence();
#pragma unroll
        for (int k = 0; k < 4; k++) wgmma_ss_n192_t11(acc, da + k * 128, db + k * 128, (kb | k) != 0);
        wg_commit();
        if (G1_TAIL > 0 && wg == 0 && kb == G1_KB - 1) bar_arrive(5, 256);
        wg_wait<1>();
        if (kb > 0 && !yield && wtid == 0) mbar_arrive(bars + 8 * (B_EMPTY + (kb - 1) % NSTAGE));
      }
      wg_wait<0>();
      pin_regs<96>(acc);
      if (wtid == 0) TLREC(4 + wg);
      if (wg == 0) { if (wtid == 0) mbar_arrive(bars + 8 * (B_EMPTY + (G1_KB - 1) % NSTAGE)); bar_arrive(6, 256); }
      else bar_sync(6, 256);
      const uint32_t stg = wg == 0 ? sb + SM_DED : sb + ((G1_KB - 1) % NSTAGE) * SLOT;
      const uint32_t sa = stg + ((lane >> 4) * 8 + (lane & 7)) * 128 + (((2 * w + ((lane >> 3) & 1)) ^ (lane & 7)) << 4);
#pragma unroll
      for (int q = 0; q < 24; q += 2) {
        uint32_t pk[4];
#pragma unroll
        for (int i = 0; i < 4; i++) {
          const uint32_t p = badd2(pack_bf16(acc[4 * q + 2 * i], acc[4 * q + 2 * i + 1]), (i & 1) ? bias1 : bias0);
          pk[i] = pack_bf16(gelu_tanh(bf_lo(p)), gelu_tanh(bf_hi(p)));
        }
        stsm4t(sa + q * 1024, pk[0], pk[1], pk[2], pk[3]);
        if ((q & 7) == 6) {
          fence_async_smem();
          __syncwarp();
          if (lane == 0) mbar_arrive(bars + 8 * (B_CEMPTY + wg * 3 + (q >> 3)));
        }
      }
    } else {
      if (wtid < 8 * CV_NSLOT / 2) {
        const int sl = 2 * (wtid >> 3) + wg;
        asm volatile("st.shared.u32 [%0], %1;" :: "r"(sb + CV_BASE + sl * CV_SLOT + CV_KOFF + (wtid & 7) * 4), "r"(0) : "memory");
      }
      bar_sync(3 + wg, 128);
      const uint32_t ko = sb + CV_BASE + CV_KOFF + (8 * w + g + t + 1) * 4;
      uint32_t a[64];
      mbar_wait(bars + 8 * (B_CFULL + wg), 0);
      if (tid == 0) TLREC(17);
#pragma unroll
      for (int j = 0; j < 32; j++) { a[2 * j] = lds32(ko + wg * CV_SLOT + (j >> 1) * 256 + (j & 1) * 16); a[2 * j + 1] = lds32(ko + wg * CV_SLOT + (j >> 1) * 256 + (j & 1) * 16 + 128); }
      if (wg == 1) bar_arrive(5, 256);
#pragma unroll 1
      for (int i = wg; i < n_conv; i += 2) {
        const int s = i % CV_NSLOT;
        const uint64_t db = make_desc(sb + CV_BASE + s * CV_SLOT, 4096, 128, 0);
        float acc[128];
        bar_sync(5 + wg, 256);
        wg_fence();
        wgmma_rs_n256(acc, a, db, 0);
        wgmma_rs_n240(acc, a + 4, db + 16, 1);
        wgmma_rs_n224(acc, a + 8, db + 32, 1);
        wgmma_rs_n208(acc, a + 12, db + 48, 1);
        wgmma_rs_n192(acc, a + 16, db + 64, 1);
        wgmma_rs_n176(acc, a + 20, db + 80, 1);
        wgmma_rs_n160(acc, a + 24, db + 96, 1);
        wgmma_rs_n144(acc, a + 28, db + 112, 1);
        wgmma_rs_n128(acc, a + 32, db + 128, 1);
        wgmma_rs_n112(acc, a + 36, db + 144, 1);
        wgmma_rs_n96(acc, a + 40, db + 160, 1);
        wgmma_rs_n80(acc, a + 44, db + 176, 1);
        wgmma_rs_n64(acc, a + 48, db + 192, 1);
        wgmma_rs_n48(acc, a + 52, db + 208, 1);
        wgmma_rs_n32(acc, a + 56, db + 224, 1);
        wgmma_rs_n16(acc, a + 60, db + 240, 1);
        wg_commit();
        if (i + 1 < n_conv) bar_arrive(5 + (wg ^ 1), 256);
        wg_wait<0>();
        pin_regs<128>(acc);
        if (lane == 0) mbar_arrive(bars + 8 * (B_CEMPTY + s));
        const int in = i + 2 < n_conv ? i + 2 : i, sn = in % CV_NSLOT;
        mbar_wait(bars + 8 * (B_CFULL + sn), (in / CV_NSLOT) & 1);
        const uint32_t ka = ko + sn * CV_SLOT;
        __nv_bfloat16* yo = g_yp + ((size_t)conv_channel(cvc, i) * 4 + w) * S_ + 16 * (3 - t) + 2 * g;
#pragma unroll
        for (int j = 0; j < 32; j++) {
          const int q = 31 - j;
          a[2 * j] = lds32(ka + (j >> 1) * 256 + (j & 1) * 16); a[2 * j + 1] = lds32(ka + (j >> 1) * 256 + (j & 1) * 16 + 128);
          stg32(yo + 64 * j, q == 31 ? pack_bf16(acc[124], acc[125]) : pack_bf16(acc[4 * q] + acc[(4 * q + 6) & 127], acc[4 * q + 1] + acc[(4 * q + 7) & 127]));
        }
        if (i == N_SHORT - 2 + wg || i + 2 >= n_conv) {
          bar_sync(3 + wg, 128);
          if (wtid == 0) { signal(i < N_SHORT ? C_YA : C_YB); TLREC(20 + wg); }
          __syncwarp();
        }
      }
      __syncwarp();
      if (lane == 0) mbar_arrive(bars + 8 * B_CDONE);
    }
    if (g2m >= 0) {
      const int srow = g2m * 128 + wg * 64 + w * 16 + g;
      float acc[72], acc2[36];
#pragma unroll 1
      for (int kb = 0; kb < G2_KB - G2_TAIL; kb++) {
        const int p = it2 + kb, s = p % NSTAGE;
        mbar_wait(bars + 8 * (B_FULL + s), (p / NSTAGE) & 1);
        if (kb == 0 && tid == 0) TLREC(7);
        const uint64_t da = make_desc(sb + s * SLOT + wg * 8192, 8192, 1024, 1), db = make_desc(sb + s * SLOT + 16384, 16, 1024, 1);
        wg_fence();
#pragma unroll
        for (int k = 0; k < 4; k++) wgmma_ss_n144_t10(acc, da + k * 128, db + k * 2, (kb | k) != 0);
        wg_commit();
        wg_wait<1>();
        if (kb > 0 && wtid == 0) mbar_arrive(bars + 8 * (B_EMPTY + (p - 1) % NSTAGE));
      }
      const float2 st0 = __ldcg(reinterpret_cast<const float2*>(g_stats + srow)), st1 = __ldcg(reinterpret_cast<const float2*>(g_stats + srow + 8));
      const uint32_t bias0 = __byte_perm((uint32_t)__bfloat16_as_ushort(P.b2[srow]), 0, 0x1010);
      const uint32_t bias1 = __byte_perm((uint32_t)__bfloat16_as_ushort(P.b2[srow + 8]), 0, 0x1010);
      const uint32_t xo = sb + ((xslot + 1 + (warp >> 1)) % NSTAGE) * SLOT + G2_BYTES + (warp & 1) * 2304;
      const uint32_t xa = xo + (lane & 15) * 144 + (lane >> 4) * 16;
      uint32_t xx[18], ss[18];
      auto prep = [&]() {
        mbar_wait(bars + 8 * B_XT, 0);
        mbar_wait(bars + 8 * B_Y2, 0);
        const uint32_t ya = sb + SM_DED + ((lane >> 4) * 8 + (lane & 7)) * 256 + (((2 * warp + ((lane >> 3) & 1)) ^ (lane & 7)) << 4);
#pragma unroll
        for (int q = 0; q < 8; q += 2) { ldsm4(xx + 2 * q, xa + q * 16); ldsm4t(ss + 2 * q, ya + q * 2048); }
        ldsm2(xx + 16, xo + (lane & 15) * 144 + 128);
        ldsm2t(ss + 16, ya - (lane >> 4) * 2048 + 8 * 2048);
        const uint32_t m0 = pack_bf16(st0.x, st0.x), m1 = pack_bf16(st1.x, st1.x);
#pragma unroll
        for (int i = 0; i < 18; i++) ss[i] = bmul2(ln_apply(xx[i], (i & 1) ? m1 : m0, (i & 1) ? st1.y : st0.y), ss[i]);
      };
      if (wg == 1) {
        wg_wait<0>();
        if (wtid == 0) mbar_arrive(bars + 8 * (B_EMPTY + xslot));
        prep();
        bar_sync(5, 256);
      }
#pragma unroll
      for (int kb = G2_KB - G2_TAIL; kb < G2_KB; kb++) {
        const int p = it2 + kb, s = p % NSTAGE;
        mbar_wait(bars + 8 * (B_FULL + s), (p / NSTAGE) & 1);
        const uint64_t da = make_desc(sb + s * SLOT + wg * 8192, 8192, 1024, 1), db = make_desc(sb + s * SLOT + 16384, 16, 1024, 1);
        wg_fence();
#pragma unroll
        for (int k = 0; k < 4; k++) wgmma_ss_n72_t10(acc, da + k * 128, db + k * 2, 1);
        wg_commit();
        if (kb == G2_KB - G2_TAIL) { wg_wait<1>(); if (tid == 0) mbar_arrive(bars + 8 * (B_EMPTY + xslot)); }
      }
      bar_arrive(5 + wg, 256);
      wg_wait<0>();
      pin_regs<72>(acc);
      const uint32_t xz = sb + xslot * SLOT + wg * 18432 + wtid * 16;
      mbar_wait_cluster(bars + 8 * B_XRDY, 0);
      {
        const uint32_t rz = mapa(xz, rank ^ 1), rb = mapa(bars + 8 * (B_XFULL + wg), rank ^ 1);
#pragma unroll
        for (int q = 0; q < 9; q++)
          asm volatile("st.async.weak.shared::cluster.mbarrier::complete_tx::bytes.v4.f32 [%0], {%1,%2,%3,%4}, [%5];"
                       :: "r"(rz + q * 2048), "f"(acc[4 * q]), "f"(acc[4 * q + 1]), "f"(acc[4 * q + 2]), "f"(acc[4 * q + 3]), "r"(rb) : "memory");
      }
      if (wg == 0) prep();
      bar_sync(6 - wg, 256);
      wg_fence();
#pragma unroll
      for (int kb = G2_KB - G2_TAIL; kb < G2_KB; kb++) {
        const int s = (it2 + kb) % NSTAGE;
        const uint64_t da = make_desc(sb + s * SLOT + wg * 8192, 8192, 1024, 1), db = make_desc(sb + s * SLOT + 16384 + 9216, 16, 1024, 1);
#pragma unroll
        for (int k = 0; k < 4; k++) wgmma_ss_n72_t10(acc2, da + k * 128, db + k * 2, kb != G2_KB - G2_TAIL || k != 0);
      }
      wg_commit();
      if (wg == 0) bar_arrive(5, 256);
      mbar_wait_cluster(bars + 8 * (B_XFULL + wg), 0);
#pragma unroll
      for (int q = 0; q < 9; q++) {
        const float4 pv = lds128f(xz + q * 2048);
        acc[36 + 4 * q] += pv.x; acc[37 + 4 * q] += pv.y; acc[38 + 4 * q] += pv.z; acc[39 + 4 * q] += pv.w;
      }
      wg_wait<0>();
      pin_regs<36>(acc2);
      if (wtid == 0) TLREC(9 + wg);
      uint32_t ob[18];
#pragma unroll
      for (int i = 0; i < 18; i++) {
        const uint32_t y = badd2(pack_bf16(acc[36 + 2 * i] + acc2[2 * i], acc[37 + 2 * i] + acc2[2 * i + 1]), (i & 1) ? bias1 : bias0);
        ob[i] = badd2(xx[i], bmul2(ss[i], pack_bf16(silu(bf_lo(y)), silu(bf_hi(y)))));
      }
#pragma unroll
      for (int q = 0; q < 8; q += 2) stsm4(xa + q * 16, ob[2 * q], ob[2 * q + 1], ob[2 * q + 2], ob[2 * q + 3]);
      stsm2(xo + (lane & 15) * 144 + 128, ob[16], ob[17]);
      fence_async_smem();
      __syncwarp();
      if (lane == 0) {
        tma2d_store(&P.m_out, xo, dk, srow);
        bulk_commit();
        bulk_wait_read();
      }
      if (wtid == 0) {
        TLREC(11 + wg);
        if (g1m == 0 && g1n == 0 && rank == 0 && wg == 0) st_flag(&g_epoch, tag);
      }
    }
    TLEND();
  }
}

typedef CUresult (*EncodeFn)(CUtensorMap*, CUtensorMapDataType, cuuint32_t, void*, const cuuint64_t*, const cuuint64_t*, const cuuint32_t*,
                             const cuuint32_t*, CUtensorMapInterleave, CUtensorMapSwizzle, CUtensorMapL2promotion, CUtensorMapFloatOOBfill);

void make_map(EncodeFn fn, CUtensorMap* m, const void* ptr, int rank, const cuuint64_t* dims, const cuuint64_t* strides, const cuuint32_t* box,
              CUtensorMapSwizzle sw) {
  const cuuint32_t es[3] = {1, 1, 1};
  fn(m, CU_TENSOR_MAP_DATA_TYPE_BFLOAT16, rank, const_cast<void*>(ptr), dims, strides, box, es, CU_TENSOR_MAP_INTERLEAVE_NONE, sw,
     CU_TENSOR_MAP_L2_PROMOTION_L2_256B, CU_TENSOR_MAP_FLOAT_OOB_FILL_NONE);
}

void make_roles(Roles& R) {
  int c1 = 0, ncv = 2, np0 = 0;
  for (int g = 0; g < 8; g++)
    for (int c = 0; c < 66; c++) {
      const int tp = (c + 62) % 66;
      int gg, idx;
      if (tp < 32) { gg = tp % 8; idx = tp / 8; }
      else if (tp < 60) { gg = 1 + (tp - 32) % 7; idx = 4 + (tp - 32) / 7; }
      else if (tp < 62) { gg = 6 + tp - 60; idx = 8; }
      else { gg = 0; idx = 4 + tp - 62; }
      if (gg != g) continue;
      if (idx < 8) { R.g2m[c] = (int8_t)(2 * g + idx / 4); R.g2n[c] = (int8_t)(idx % 4); R.p0[c] = (int8_t)np0++; }
      else { R.g2m[c] = -1; R.g2n[c] = 0; R.p0[c] = -1; }
      if (idx < (g < 2 ? 6 : 7)) { R.g1m[c] = (int8_t)(c1 / 3); R.g1n[c] = (int8_t)(c1 % 3); R.cv[c] = -1; c1++; }
      else { R.g1m[c] = -1; R.g1n[c] = 0; R.cv[c] = (int8_t)(idx == 8 ? tp - 60 : ncv++); }
    }
}

}

extern "C" void kernel_launch(void* const* d_in, const int* in_sizes, int n_in, void* d_out, int out_size) {
  static Params P;
  static const void* cached[4] = {nullptr, nullptr, nullptr, nullptr};
  if (cached[0] != d_in[7] || cached[1] != d_in[9] || cached[2] != d_out || cached[3] != d_in[0]) {
    void* fp = nullptr;
    cudaDriverEntryPointQueryResult qr;
    cudaGetDriverEntryPoint("cuTensorMapEncodeTiled", &fp, cudaEnableDefault, &qr);
    EncodeFn fn = (EncodeFn)fp;
    void *ph, *pu;
    cudaGetSymbolAddress(&ph, g_h);
    cudaGetSymbolAddress(&pu, g_u);
    { cuuint64_t d[3] = {64, S_, F_ / 64}, s[2] = {F_ * 2, 128}; cuuint32_t b[3] = {64, 64, 2}; make_map(fn, &P.m_w1, d_in[7], 3, d, s, b, CU_TENSOR_MAP_SWIZZLE_128B); }
    { cuuint64_t d[3] = {64, S_, D_ / 64}, s[2] = {D_ * 2, 128}; cuuint32_t b[3] = {64, 64, 3}; make_map(fn, &P.m_h, ph, 3, d, s, b, CU_TENSOR_MAP_SWIZZLE_128B); }
    { cuuint64_t d[2] = {F_, D_}, s[1] = {F_ * 2}; cuuint32_t b[2] = {64, 64}; make_map(fn, &P.m_ust, pu, 2, d, s, b, CU_TENSOR_MAP_SWIZZLE_128B); }
    { cuuint64_t d[3] = {64, F_, S_ / 64}, s[2] = {S_ * 2, 128}; cuuint32_t b[3] = {64, 64, 2}; make_map(fn, &P.m_w2, d_in[9], 3, d, s, b, CU_TENSOR_MAP_SWIZZLE_128B); }
    { cuuint64_t d[2] = {F_, D_}, s[1] = {F_ * 2}; cuuint32_t b[2] = {64, 72}; make_map(fn, &P.m_uld, pu, 2, d, s, b, CU_TENSOR_MAP_SWIZZLE_128B); }
    { cuuint64_t d[2] = {D_, S_}, s[1] = {D_ * 2}; cuuint32_t b[2] = {72, 16}; make_map(fn, &P.m_out, d_out, 2, d, s, b, CU_TENSOR_MAP_SWIZZLE_NONE);
      make_map(fn, &P.m_x, d_in[0], 2, d, s, b, CU_TENSOR_MAP_SWIZZLE_NONE); }
    make_roles(P.roles);
    cudaFuncSetAttribute(fused_kernel, cudaFuncAttributeMaxDynamicSharedMemorySize, SM_TOTAL);
    cached[0] = d_in[7]; cached[1] = d_in[9]; cached[2] = d_out; cached[3] = d_in[0];
  }
  P.x = (const __nv_bfloat16*)d_in[0]; P.k = (const __nv_bfloat16*)d_in[1]; P.v = (const __nv_bfloat16*)d_in[2];
  P.shift_k = (const __nv_bfloat16*)d_in[3]; P.ssm_k = (const __nv_bfloat16*)d_in[4]; P.ssm_D = (const __nv_bfloat16*)d_in[5];
  P.b1 = (const __nv_bfloat16*)d_in[8]; P.b2 = (const __nv_bfloat16*)d_in[10];
  fused_kernel<<<132, 384, SM_TOTAL>>>(P);
}
```

```cpp
#include <cuda_runtime.h>
#include <cuda.h>
#include <cuda_bf16.h>
#include <stdint.h>

namespace {

constexpr int S_ = 2048, D_ = 576, F_ = 4608;
constexpr int NSTAGE = 5, SLOT = 40960;
constexpr int G1_KB = 32, G2_KB = 36;
constexpr int G1_BYTES = 40960, G2_BYTES = 16384 + 18432;
constexpr int N_CONV_CTA = 24, N_SHORT = 22, N_LONG_EXTRA = 12;
static_assert(N_CONV_CTA * N_SHORT + 4 * N_LONG_EXTRA == D_, "conv split");
constexpr int KV_ROUNDS = 6;
#define G1T 5
constexpr int G1_TAIL = G1T, G2_TAIL = 4;

constexpr int SM_DED = NSTAGE * SLOT;
constexpr int SM_BAR = SM_DED + 24576;
constexpr int SM_TOTAL = SM_BAR + 256 + 1024;
constexpr int CV_NSLOT = 4, CV_KOFF = 8192, CV_SLOT = 8192 + 4224;
constexpr int CV_REDW = 2112 * 2, CV_RED1 = CV_NSLOT * CV_SLOT;
static_assert(CV_RED1 + 4 * CV_REDW <= 2 * SLOT, "conv overlay");
constexpr int XSLOT = (G1_KB + G2_KB) % NSTAGE;
constexpr int B_FULL = 0, B_EMPTY = NSTAGE, B_CFULL = 2 * NSTAGE, B_CEMPTY = B_CFULL + CV_NSLOT, B_STG = B_CEMPTY + CV_NSLOT  ,
              B_XRDY = B_STG + 6, B_XFULL = B_XRDY + 1  , B_XT = B_XFULL + 2, B_Y2 = B_XT + 1;
constexpr int C_H = 0, C_KV = 1, C_U = C_KV + KV_ROUNDS  , C_Y = C_U + 12, C_COUNT = C_Y + 1;

struct Roles {
  int8_t g1m[66];
  int8_t g1n[66];
  int8_t cv[66];
  int8_t g2m[66];
  int8_t g2n[66];
  int8_t p0[66];
};

struct Params {
  CUtensorMap m_w1, m_h, m_ust, m_w2, m_uld, m_out, m_x, m_y;
  const __nv_bfloat16 *x, *k, *v, *shift_k, *ssm_k, *ssm_D, *b1, *b2;
  Roles roles;
};

__device__ __align__(1024) __nv_bfloat16 g_h[S_ * D_];
__device__ __align__(1024) __nv_bfloat16 g_ub[D_ * 4096];
__device__ __align__(1024) __nv_bfloat16 g_y[D_ * S_];
__device__ __align__(1024) __nv_bfloat16 g_u[D_ * F_];
__device__ __align__(128) float4 g_stats[S_];
__device__ __align__(128) uint32_t g_cnt[C_COUNT * 32];
__device__ __align__(128) uint32_t g_epoch;
#define TLREC(i) do { } while (0)
#define TLEND() do { } while (0)

__device__ __forceinline__ uint32_t smem_u32(const void* p) { return (uint32_t)__cvta_generic_to_shared(p); }
__device__ __forceinline__ void mbar_init(uint32_t bar, uint32_t cnt) { asm volatile("mbarrier.init.shared::cta.b64 [%0], %1;" :: "r"(bar), "r"(cnt) : "memory"); }
__device__ __forceinline__ void mbar_expect_tx(uint32_t bar, uint32_t bytes) { asm volatile("mbarrier.arrive.expect_tx.shared::cta.b64 _, [%0], %1;" :: "r"(bar), "r"(bytes) : "memory"); }
__device__ __forceinline__ void mbar_arrive(uint32_t bar) { asm volatile("mbarrier.arrive.shared::cta.b64 _, [%0];" :: "r"(bar) : "memory"); }
__device__ __forceinline__ uint32_t mapa(uint32_t addr, uint32_t cta) { uint32_t r; asm volatile("mapa.shared::cluster.u32 %0, %1, %2;" : "=r"(r) : "r"(addr), "r"(cta)); return r; }
__device__ __forceinline__ void mbar_arrive_remote(uint32_t rbar) { asm volatile("mbarrier.arrive.release.cluster.shared::cluster.b64 _, [%0];" :: "r"(rbar) : "memory"); }
__device__ __forceinline__ void mbar_wait(uint32_t bar, uint32_t parity) {
  asm volatile("{\n .reg .pred p;\n .reg .u32 c;\n mov.u32 c, 0;\n"
               "W_%=:\n mbarrier.try_wait.parity.shared::cta.b64 p, [%0], %1;\n @p bra D_%=;\n"
               " add.u32 c, c, 1;\n setp.lt.u32 p, c, 2000000;\n @p bra W_%=;\n trap;\n D_%=:\n }" :: "r"(bar), "r"(parity) : "memory");
}
__device__ __forceinline__ void mbar_wait_cluster(uint32_t bar, uint32_t parity) {
  asm volatile("{\n .reg .pred p;\n .reg .u32 c;\n mov.u32 c, 0;\n"
               "W_%=:\n mbarrier.try_wait.parity.acquire.cluster.shared::cta.b64 p, [%0], %1;\n @p bra D_%=;\n"
               " add.u32 c, c, 1;\n setp.lt.u32 p, c, 2000000;\n @p bra W_%=;\n trap;\n D_%=:\n }" :: "r"(bar), "r"(parity) : "memory");
}
__device__ __forceinline__ void tma2d(uint32_t dst, const CUtensorMap* m, int c0, int c1, uint32_t bar) {
  asm volatile("cp.async.bulk.tensor.2d.shared::cluster.global.mbarrier::complete_tx::bytes [%0], [%1, {%3, %4}], [%2];"
               :: "r"(dst), "l"(m), "r"(bar), "r"(c0), "r"(c1) : "memory");
}
__device__ __forceinline__ void tma3d(uint32_t dst, const CUtensorMap* m, int c0, int c1, int c2, uint32_t bar) {
  asm volatile("cp.async.bulk.tensor.3d.shared::cluster.global.mbarrier::complete_tx::bytes [%0], [%1, {%3, %4, %5}], [%2];"
               :: "r"(dst), "l"(m), "r"(bar), "r"(c0), "r"(c1), "r"(c2) : "memory");
}
__device__ __forceinline__ void tma2d_store(const CUtensorMap* m, uint32_t src, int c0, int c1) {
  asm volatile("cp.async.bulk.tensor.2d.global.shared::cta.bulk_group [%0, {%2, %3}], [%1];" :: "l"(m), "r"(src), "r"(c0), "r"(c1) : "memory");
}
__device__ __forceinline__ void bulk_load(uint32_t dst, const void* src, uint32_t bytes, uint32_t bar) {
  asm volatile("cp.async.bulk.shared::cluster.global.mbarrier::complete_tx::bytes [%0], [%1], %2, [%3];" :: "r"(dst), "l"(src), "r"(bytes), "r"(bar) : "memory");
}
__device__ __forceinline__ void bulk_commit() { asm volatile("cp.async.bulk.commit_group;" ::: "memory"); }
__device__ __forceinline__ void bulk_wait_all() { asm volatile("cp.async.bulk.wait_group 0;" ::: "memory"); }
__device__ __forceinline__ void bulk_wait_read() { asm volatile("cp.async.bulk.wait_group.read 0;" ::: "memory"); }
__device__ __forceinline__ void fence_async_smem() { asm volatile("fence.proxy.async.shared::cta;" ::: "memory"); }
__device__ __forceinline__ void fence_async_global() { asm volatile("fence.proxy.async.global;" ::: "memory"); }
__device__ __forceinline__ void st_flag(uint32_t* p, uint32_t v) { asm volatile("st.relaxed.gpu.global.u32 [%0], %1;" :: "l"(p), "r"(v) : "memory"); }
__device__ __forceinline__ uint32_t ld_flag(const uint32_t* p) { uint32_t v; asm volatile("ld.relaxed.gpu.global.u32 %0, [%1];" : "=r"(v) : "l"(p) : "memory"); return v; }
__device__ __forceinline__ void signal(int c) { asm volatile("red.release.gpu.global.add.u32 [%0], 1;" :: "l"(g_cnt + c * 32) : "memory"); }
__device__ __forceinline__ void await(int c, uint32_t target) {
  uint32_t n = 0;
  while (true) {
    uint32_t v; asm volatile("ld.acquire.gpu.global.u32 %0, [%1];" : "=r"(v) : "l"(g_cnt + c * 32) : "memory");
    if ((int32_t)(v - target) >= 0) break;
    if (++n > 4000000u) __trap();
  }
}
__device__ __forceinline__ void bar_sync(int id, int n) { asm volatile("bar.sync %0, %1;" :: "r"(id), "r"(n) : "memory"); }
__device__ __forceinline__ void bar_arrive(int id, int n) { asm volatile("bar.arrive %0, %1;" :: "r"(id), "r"(n) : "memory"); }
__device__ __forceinline__ void wg_fence() { asm volatile("wgmma.fence.sync.aligned;" ::: "memory"); }
__device__ __forceinline__ void wg_commit() { asm volatile("wgmma.commit_group.sync.aligned;" ::: "memory"); }
template <int N> __device__ __forceinline__ void wg_wait() { asm volatile("wgmma.wait_group.sync.aligned %0;" :: "n"(N) : "memory"); }
template <int N> __device__ __forceinline__ void pin_regs(float* a) {
#pragma unroll
  for (int i = 0; i < N; i++) asm volatile("" : "+f"(a[i]) :: "memory");
}
__device__ __forceinline__ uint64_t make_desc(uint32_t addr, uint32_t lbo, uint32_t sbo, uint32_t swz) {
  return (uint64_t)((addr & 0x3FFFF) >> 4) | ((uint64_t)(lbo >> 4) << 16) | ((uint64_t)(sbo >> 4) << 32) | ((uint64_t)swz << 62);
}
__device__ __forceinline__ uint32_t pack_bf16(float lo, float hi) { uint32_t r; asm("cvt.rn.bf16x2.f32 %0, %1, %2;" : "=r"(r) : "f"(hi), "f"(lo)); return r; }
__device__ __forceinline__ float bf_lo(uint32_t p) { return __uint_as_float(p << 16); }
__device__ __forceinline__ float bf_hi(uint32_t p) { return __uint_as_float(p & 0xffff0000u); }
__device__ __forceinline__ float round_bf16(float v) { return bf_lo(pack_bf16(v, 0.f)); }
__device__ __forceinline__ uint32_t bmul2(uint32_t a, uint32_t b) { uint32_t r; asm("mul.rn.bf16x2 %0, %1, %2;" : "=r"(r) : "r"(a), "r"(b)); return r; }
__device__ __forceinline__ uint32_t badd2(uint32_t a, uint32_t b) { uint32_t r; asm("add.rn.bf16x2 %0, %1, %2;" : "=r"(r) : "r"(a), "r"(b)); return r; }
__device__ __forceinline__ uint32_t bfma2(uint32_t a, uint32_t b, uint32_t c) { uint32_t r; asm("fma.rn.bf16x2 %0, %1, %2, %3;" : "=r"(r) : "r"(a), "r"(b), "r"(c)); return r; }
__device__ __forceinline__ uint32_t bsub2(uint32_t a, uint32_t b) { uint32_t r; asm("sub.rn.bf16x2 %0, %1, %2;" : "=r"(r) : "r"(a), "r"(b)); return r; }
__device__ __forceinline__ float tanh_fast(float v) { float r; asm("tanh.approx.f32 %0, %1;" : "=f"(r) : "f"(v)); return r; }
__device__ __forceinline__ float gelu_half(float h) {
  const float z = h * fmaf(h * h, 8.0f * 0.7978845608028654f * 0.044715f, 2.0f * 0.7978845608028654f);
  return fmaf(h, tanh_fast(z), h);
}
__device__ __forceinline__ float silu_half(float h) { return fmaf(h, tanh_fast(h), h); }
__device__ __forceinline__ uint32_t ldg32(const void* p) { uint32_t v; asm volatile("ld.global.nc.u32 %0, [%1];" : "=r"(v) : "l"(p)); return v; }
__device__ __forceinline__ uint32_t lds32(uint32_t a) { uint32_t v; asm volatile("ld.shared.u32 %0, [%1];" : "=r"(v) : "r"(a) : "memory"); return v; }
__device__ __forceinline__ float4 lds128f(uint32_t a) { float4 v; asm volatile("ld.shared.v4.f32 {%0,%1,%2,%3}, [%4];" : "=f"(v.x), "=f"(v.y), "=f"(v.z), "=f"(v.w) : "r"(a) : "memory"); return v; }
__device__ __forceinline__ uint4 lds128(uint32_t a) { uint4 v; asm volatile("ld.shared.v4.u32 {%0,%1,%2,%3}, [%4];" : "=r"(v.x), "=r"(v.y), "=r"(v.z), "=r"(v.w) : "r"(a) : "memory"); return v; }
__device__ __forceinline__ void sts32(uint32_t a, uint32_t v) { asm volatile("st.shared.u32 [%0], %1;" :: "r"(a), "r"(v) : "memory"); }
__device__ __forceinline__ void ldsm4(uint32_t* r, uint32_t a) {
  asm volatile("ldmatrix.sync.aligned.m8n8.x4.shared.b16 {%0,%1,%2,%3}, [%4];" : "=r"(r[0]), "=r"(r[1]), "=r"(r[2]), "=r"(r[3]) : "r"(a) : "memory");
}
__device__ __forceinline__ void ldsm2(uint32_t* r, uint32_t a) {
  asm volatile("ldmatrix.sync.aligned.m8n8.x2.shared.b16 {%0,%1}, [%2];" : "=r"(r[0]), "=r"(r[1]) : "r"(a) : "memory");
}
__device__ __forceinline__ void ldsm4t(uint32_t* r, uint32_t a) {
  asm volatile("ldmatrix.sync.aligned.m8n8.x4.trans.shared.b16 {%0,%1,%2,%3}, [%4];" : "=r"(r[0]), "=r"(r[1]), "=r"(r[2]), "=r"(r[3]) : "r"(a) : "memory");
}
__device__ __forceinline__ void ldsm2t(uint32_t* r, uint32_t a) {
  asm volatile("ldmatrix.sync.aligned.m8n8.x2.trans.shared.b16 {%0,%1}, [%2];" : "=r"(r[0]), "=r"(r[1]) : "r"(a) : "memory");
}
__device__ __forceinline__ void stsm4(uint32_t a, uint32_t r0, uint32_t r1, uint32_t r2, uint32_t r3) {
  asm volatile("stmatrix.sync.aligned.m8n8.x4.shared.b16 [%0], {%1,%2,%3,%4};" :: "r"(a), "r"(r0), "r"(r1), "r"(r2), "r"(r3) : "memory");
}
__device__ __forceinline__ void stsm2(uint32_t a, uint32_t r0, uint32_t r1) {
  asm volatile("stmatrix.sync.aligned.m8n8.x2.shared.b16 [%0], {%1,%2};" :: "r"(a), "r"(r0), "r"(r1) : "memory");
}
__device__ __forceinline__ void stsm4t(uint32_t a, uint32_t r0, uint32_t r1, uint32_t r2, uint32_t r3) {
  asm volatile("stmatrix.sync.aligned.m8n8.x4.trans.shared.b16 [%0], {%1,%2,%3,%4};" :: "r"(a), "r"(r0), "r"(r1), "r"(r2), "r"(r3) : "memory");
}

__device__ __forceinline__ void wgmma_ss_n144_t10(float* d, uint64_t da, uint64_t db, int sd) {
  asm volatile("{ .reg .pred p; setp.ne.b32 p, %74, 0;\n"
      "wgmma.mma_async.sync.aligned.m64n144k16.f32.bf16.bf16 {"
      "%0,%1,%2,%3,%4,%5,%6,%7,%8,%9,%10,%11,%12,%13,%14,%15,"
      "%16,%17,%18,%19,%20,%21,%22,%23,%24,%25,%26,%27,%28,%29,%30,%31,"
      "%32,%33,%34,%35,%36,%37,%38,%39,%40,%41,%42,%43,%44,%45,%46,%47,"
      "%48,%49,%50,%51,%52,%53,%54,%55,%56,%57,%58,%59,%60,%61,%62,%63,"
      "%64,%65,%66,%67,%68,%69,%70,%71"
      "}, %72, %73, p, 1, 1, 1, 0; }"
    : "+f"(d[0]), "+f"(d[1]), "+f"(d[2]), "+f"(d[3]), "+f"(d[4]), "+f"(d[5]), "+f"(d[6]), "+f"(d[7]),
      "+f"(d[8]), "+f"(d[9]), "+f"(d[10]), "+f"(d[11]), "+f"(d[12]), "+f"(d[13]), "+f"(d[14]), "+f"(d[15]),
      "+f"(d[16]), "+f"(d[17]), "+f"(d[18]), "+f"(d[19]), "+f"(d[20]), "+f"(d[21]), "+f"(d[22]), "+f"(d[23]),
      "+f"(d[24]), "+f"(d[25]), "+f"(d[26]), "+f"(d[27]), "+f"(d[28]), "+f"(d[29]), "+f"(d[30]), "+f"(d[31]),
      "+f"(d[32]), "+f"(d[33]), "+f"(d[34]), "+f"(d[35]), "+f"(d[36]), "+f"(d[37]), "+f"(d[38]), "+f"(d[39]),
      "+f"(d[40]), "+f"(d[41]), "+f"(d[42]), "+f"(d[43]), "+f"(d[44]), "+f"(d[45]), "+f"(d[46]), "+f"(d[47]),
      "+f"(d[48]), "+f"(d[49]), "+f"(d[50]), "+f"(d[51]), "+f"(d[52]), "+f"(d[53]), "+f"(d[54]), "+f"(d[55]),
      "+f"(d[56]), "+f"(d[57]), "+f"(d[58]), "+f"(d[59]), "+f"(d[60]), "+f"(d[61]), "+f"(d[62]), "+f"(d[63]),
      "+f"(d[64]), "+f"(d[65]), "+f"(d[66]), "+f"(d[67]), "+f"(d[68]), "+f"(d[69]), "+f"(d[70]), "+f"(d[71])
    : "l"(da), "l"(db), "r"(sd));
}

__device__ __forceinline__ void wgmma_ss_n192_t11(float* d, uint64_t da, uint64_t db, int sd) {
  asm volatile("{ .reg .pred p; setp.ne.b32 p, %98, 0;\n"
      "wgmma.mma_async.sync.aligned.m64n192k16.f32.bf16.bf16 {"
      "%0,%1,%2,%3,%4,%5,%6,%7,%8,%9,%10,%11,%12,%13,%14,%15,"
      "%16,%17,%18,%19,%20,%21,%22,%23,%24,%25,%26,%27,%28,%29,%30,%31,"
      "%32,%33,%34,%35,%36,%37,%38,%39,%40,%41,%42,%43,%44,%45,%46,%47,"
      "%48,%49,%50,%51,%52,%53,%54,%55,%56,%57,%58,%59,%60,%61,%62,%63,"
      "%64,%65,%66,%67,%68,%69,%70,%71,%72,%73,%74,%75,%76,%77,%78,%79,"
      "%80,%81,%82,%83,%84,%85,%86,%87,%88,%89,%90,%91,%92,%93,%94,%95"
      "}, %96, %97, p, 1, 1, 1, 1; }"
    : "+f"(d[0]), "+f"(d[1]), "+f"(d[2]), "+f"(d[3]), "+f"(d[4]), "+f"(d[5]), "+f"(d[6]), "+f"(d[7]),
      "+f"(d[8]), "+f"(d[9]), "+f"(d[10]), "+f"(d[11]), "+f"(d[12]), "+f"(d[13]), "+f"(d[14]), "+f"(d[15]),
      "+f"(d[16]), "+f"(d[17]), "+f"(d[18]), "+f"(d[19]), "+f"(d[20]), "+f"(d[21]), "+f"(d[22]), "+f"(d[23]),
      "+f"(d[24]), "+f"(d[25]), "+f"(d[26]), "+f"(d[27]), "+f"(d[28]), "+f"(d[29]), "+f"(d[30]), "+f"(d[31]),
      "+f"(d[32]), "+f"(d[33]), "+f"(d[34]), "+f"(d[35]), "+f"(d[36]), "+f"(d[37]), "+f"(d[38]), "+f"(d[39]),
      "+f"(d[40]), "+f"(d[41]), "+f"(d[42]), "+f"(d[43]), "+f"(d[44]), "+f"(d[45]), "+f"(d[46]), "+f"(d[47]),
      "+f"(d[48]), "+f"(d[49]), "+f"(d[50]), "+f"(d[51]), "+f"(d[52]), "+f"(d[53]), "+f"(d[54]), "+f"(d[55]),
      "+f"(d[56]), "+f"(d[57]), "+f"(d[58]), "+f"(d[59]), "+f"(d[60]), "+f"(d[61]), "+f"(d[62]), "+f"(d[63]),
      "+f"(d[64]), "+f"(d[65]), "+f"(d[66]), "+f"(d[67]), "+f"(d[68]), "+f"(d[69]), "+f"(d[70]), "+f"(d[71]),
      "+f"(d[72]), "+f"(d[73]), "+f"(d[74]), "+f"(d[75]), "+f"(d[76]), "+f"(d[77]), "+f"(d[78]), "+f"(d[79]),
      "+f"(d[80]), "+f"(d[81]), "+f"(d[82]), "+f"(d[83]), "+f"(d[84]), "+f"(d[85]), "+f"(d[86]), "+f"(d[87]),
      "+f"(d[88]), "+f"(d[89]), "+f"(d[90]), "+f"(d[91]), "+f"(d[92]), "+f"(d[93]), "+f"(d[94]), "+f"(d[95])
    : "l"(da), "l"(db), "r"(sd));
}

__device__ __forceinline__ void wgmma_ss_n72_t10(float* d, uint64_t da, uint64_t db, int sd) {
  asm volatile("{ .reg .pred p; setp.ne.b32 p, %38, 0;\n"
      "wgmma.mma_async.sync.aligned.m64n72k16.f32.bf16.bf16 {"
      "%0,%1,%2,%3,%4,%5,%6,%7,%8,%9,%10,%11,%12,%13,%14,%15,"
      "%16,%17,%18,%19,%20,%21,%22,%23,%24,%25,%26,%27,%28,%29,%30,%31,"
      "%32,%33,%34,%35"
      "}, %36, %37, p, 1, 1, 1, 0; }"
    : "+f"(d[0]), "+f"(d[1]), "+f"(d[2]), "+f"(d[3]), "+f"(d[4]), "+f"(d[5]), "+f"(d[6]), "+f"(d[7]),
      "+f"(d[8]), "+f"(d[9]), "+f"(d[10]), "+f"(d[11]), "+f"(d[12]), "+f"(d[13]), "+f"(d[14]), "+f"(d[15]),
      "+f"(d[16]), "+f"(d[17]), "+f"(d[18]), "+f"(d[19]), "+f"(d[20]), "+f"(d[21]), "+f"(d[22]), "+f"(d[23]),
      "+f"(d[24]), "+f"(d[25]), "+f"(d[26]), "+f"(d[27]), "+f"(d[28]), "+f"(d[29]), "+f"(d[30]), "+f"(d[31]),
      "+f"(d[32]), "+f"(d[33]), "+f"(d[34]), "+f"(d[35])
    : "l"(da), "l"(db), "r"(sd));
}

__device__ __forceinline__ void wgmma_rs_n16(float* d, const uint32_t* a, uint64_t db, int sd) {
  asm volatile("{ .reg .pred p; setp.ne.b32 p, %13, 0;\n"
      "wgmma.mma_async.sync.aligned.m64n16k16.f32.bf16.bf16 {"
      "%0,%1,%2,%3,%4,%5,%6,%7"
      "}, {%8,%9,%10,%11}, %12, p, 1, 1, 0; }"
    : "+f"(d[0]), "+f"(d[1]), "+f"(d[2]), "+f"(d[3]), "+f"(d[4]), "+f"(d[5]), "+f"(d[6]), "+f"(d[7])
    : "r"(a[0]), "r"(a[1]), "r"(a[2]), "r"(a[3]), "l"(db), "r"(sd));
}

__device__ __forceinline__ void wgmma_rs_n32(float* d, const uint32_t* a, uint64_t db, int sd) {
  asm volatile("{ .reg .pred p; setp.ne.b32 p, %21, 0;\n"
      "wgmma.mma_async.sync.aligned.m64n32k16.f32.bf16.bf16 {"
      "%0,%1,%2,%3,%4,%5,%6,%7,%8,%9,%10,%11,%12,%13,%14,%15"
      "}, {%16,%17,%18,%19}, %20, p, 1, 1, 0; }"
    : "+f"(d[0]), "+f"(d[1]), "+f"(d[2]), "+f"(d[3]), "+f"(d[4]), "+f"(d[5]), "+f"(d[6]), "+f"(d[7]),
      "+f"(d[8]), "+f"(d[9]), "+f"(d[10]), "+f"(d[11]), "+f"(d[12]), "+f"(d[13]), "+f"(d[14]), "+f"(d[15])
    : "r"(a[0]), "r"(a[1]), "r"(a[2]), "r"(a[3]), "l"(db), "r"(sd));
}

__device__ __forceinline__ void wgmma_rs_n48(float* d, const uint32_t* a, uint64_t db, int sd) {
  asm volatile("{ .reg .pred p; setp.ne.b32 p, %29, 0;\n"
      "wgmma.mma_async.sync.aligned.m64n48k16.f32.bf16.bf16 {"
      "%0,%1,%2,%3,%4,%5,%6,%7,%8,%9,%10,%11,%12,%13,%14,%15,"
      "%16,%17,%18,%19,%20,%21,%22,%23"
      "}, {%24,%25,%26,%27}, %28, p, 1, 1, 0; }"
    : "+f"(d[0]), "+f"(d[1]), "+f"(d[2]), "+f"(d[3]), "+f"(d[4]), "+f"(d[5]), "+f"(d[6]), "+f"(d[7]),
      "+f"(d[8]), "+f"(d[9]), "+f"(d[10]), "+f"(d[11]), "+f"(d[12]), "+f"(d[13]), "+f"(d[14]), "+f"(d[15]),
      "+f"(d[16]), "+f"(d[17]), "+f"(d[18]), "+f"(d[19]), "+f"(d[20]), "+f"(d[21]), "+f"(d[22]), "+f"(d[23])
    : "r"(a[0]), "r"(a[1]), "r"(a[2]), "r"(a[3]), "l"(db), "r"(sd));
}

__device__ __forceinline__ void wgmma_rs_n64(float* d, const uint32_t* a, uint64_t db, int sd) {
  asm volatile("{ .reg .pred p; setp.ne.b32 p, %37, 0;\n"
      "wgmma.mma_async.sync.aligned.m64n64k16.f32.bf16.bf16 {"
      "%0,%1,%2,%3,%4,%5,%6,%7,%8,%9,%10,%11,%12,%13,%14,%15,"
      "%16,%17,%18,%19,%20,%21,%22,%23,%24,%25,%26,%27,%28,%29,%30,%31"
      "}, {%32,%33,%34,%35}, %36, p, 1, 1, 0; }"
    : "+f"(d[0]), "+f"(d[1]), "+f"(d[2]), "+f"(d[3]), "+f"(d[4]), "+f"(d[5]), "+f"(d[6]), "+f"(d[7]),
      "+f"(d[8]), "+f"(d[9]), "+f"(d[10]), "+f"(d[11]), "+f"(d[12]), "+f"(d[13]), "+f"(d[14]), "+f"(d[15]),
      "+f"(d[16]), "+f"(d[17]), "+f"(d[18]), "+f"(d[19]), "+f"(d[20]), "+f"(d[21]), "+f"(d[22]), "+f"(d[23]),
      "+f"(d[24]), "+f"(d[25]), "+f"(d[26]), "+f"(d[27]), "+f"(d[28]), "+f"(d[29]), "+f"(d[30]), "+f"(d[31])
    : "r"(a[0]), "r"(a[1]), "r"(a[2]), "r"(a[3]), "l"(db), "r"(sd));
}

__device__ __forceinline__ void wgmma_rs_n80(float* d, const uint32_t* a, uint64_t db, int sd) {
  asm volatile("{ .reg .pred p; setp.ne.b32 p, %45, 0;\n"
      "wgmma.mma_async.sync.aligned.m64n80k16.f32.bf16.bf16 {"
      "%0,%1,%2,%3,%4,%5,%6,%7,%8,%9,%10,%11,%12,%13,%14,%15,"
      "%16,%17,%18,%19,%20,%21,%22,%23,%24,%25,%26,%27,%28,%29,%30,%31,"
      "%32,%33,%34,%35,%36,%37,%38,%39"
      "}, {%40,%41,%42,%43}, %44, p, 1, 1, 0; }"
    : "+f"(d[0]), "+f"(d[1]), "+f"(d[2]), "+f"(d[3]), "+f"(d[4]), "+f"(d[5]), "+f"(d[6]), "+f"(d[7]),
      "+f"(d[8]), "+f"(d[9]), "+f"(d[10]), "+f"(d[11]), "+f"(d[12]), "+f"(d[13]), "+f"(d[14]), "+f"(d[15]),
      "+f"(d[16]), "+f"(d[17]), "+f"(d[18]), "+f"(d[19]), "+f"(d[20]), "+f"(d[21]), "+f"(d[22]), "+f"(d[23]),
      "+f"(d[24]), "+f"(d[25]), "+f"(d[26]), "+f"(d[27]), "+f"(d[28]), "+f"(d[29]), "+f"(d[30]), "+f"(d[31]),
      "+f"(d[32]), "+f"(d[33]), "+f"(d[34]), "+f"(d[35]), "+f"(d[36]), "+f"(d[37]), "+f"(d[38]), "+f"(d[39])
    : "r"(a[0]), "r"(a[1]), "r"(a[2]), "r"(a[3]), "l"(db), "r"(sd));
}

__device__ __forceinline__ void wgmma_rs_n96(float* d, const uint32_t* a, uint64_t db, int sd) {
  asm volatile("{ .reg .pred p; setp.ne.b32 p, %53, 0;\n"
      "wgmma.mma_async.sync.aligned.m64n96k16.f32.bf16.bf16 {"
      "%0,%1,%2,%3,%4,%5,%6,%7,%8,%9,%10,%11,%12,%13,%14,%15,"
      "%16,%17,%18,%19,%20,%21,%22,%23,%24,%25,%26,%27,%28,%29,%30,%31,"
      "%32,%33,%34,%35,%36,%37,%38,%39,%40,%41,%42,%43,%44,%45,%46,%47"
      "}, {%48,%49,%50,%51}, %52, p, 1, 1, 0; }"
    : "+f"(d[0]), "+f"(d[1]), "+f"(d[2]), "+f"(d[3]), "+f"(d[4]), "+f"(d[5]), "+f"(d[6]), "+f"(d[7]),
      "+f"(d[8]), "+f"(d[9]), "+f"(d[10]), "+f"(d[11]), "+f"(d[12]), "+f"(d[13]), "+f"(d[14]), "+f"(d[15]),
      "+f"(d[16]), "+f"(d[17]), "+f"(d[18]), "+f"(d[19]), "+f"(d[20]), "+f"(d[21]), "+f"(d[22]), "+f"(d[23]),
      "+f"(d[24]), "+f"(d[25]), "+f"(d[26]), "+f"(d[27]), "+f"(d[28]), "+f"(d[29]), "+f"(d[30]), "+f"(d[31]),
      "+f"(d[32]), "+f"(d[33]), "+f"(d[34]), "+f"(d[35]), "+f"(d[36]), "+f"(d[37]), "+f"(d[38]), "+f"(d[39]),
      "+f"(d[40]), "+f"(d[41]), "+f"(d[42]), "+f"(d[43]), "+f"(d[44]), "+f"(d[45]), "+f"(d[46]), "+f"(d[47])
    : "r"(a[0]), "r"(a[1]), "r"(a[2]), "r"(a[3]), "l"(db), "r"(sd));
}

__device__ __forceinline__ void wgmma_rs_n112(float* d, const uint32_t* a, uint64_t db, int sd) {
  asm volatile("{ .reg .pred p; setp.ne.b32 p, %61, 0;\n"
      "wgmma.mma_async.sync.aligned.m64n112k16.f32.bf16.bf16 {"
      "%0,%1,%2,%3,%4,%5,%6,%7,%8,%9,%10,%11,%12,%13,%14,%15,"
      "%16,%17,%18,%19,%20,%21,%22,%23,%24,%25,%26,%27,%28,%29,%30,%31,"
      "%32,%33,%34,%35,%36,%37,%38,%39,%40,%41,%42,%43,%44,%45,%46,%47,"
      "%48,%49,%50,%51,%52,%53,%54,%55"
      "}, {%56,%57,%58,%59}, %60, p, 1, 1, 0; }"
    : "+f"(d[0]), "+f"(d[1]), "+f"(d[2]), "+f"(d[3]), "+f"(d[4]), "+f"(d[5]), "+f"(d[6]), "+f"(d[7]),
      "+f"(d[8]), "+f"(d[9]), "+f"(d[10]), "+f"(d[11]), "+f"(d[12]), "+f"(d[13]), "+f"(d[14]), "+f"(d[15]),
      "+f"(d[16]), "+f"(d[17]), "+f"(d[18]), "+f"(d[19]), "+f"(d[20]), "+f"(d[21]), "+f"(d[22]), "+f"(d[23]),
      "+f"(d[24]), "+f"(d[25]), "+f"(d[26]), "+f"(d[27]), "+f"(d[28]), "+f"(d[29]), "+f"(d[30]), "+f"(d[31]),
      "+f"(d[32]), "+f"(d[33]), "+f"(d[34]), "+f"(d[35]), "+f"(d[36]), "+f"(d[37]), "+f"(d[38]), "+f"(d[39]),
      "+f"(d[40]), "+f"(d[41]), "+f"(d[42]), "+f"(d[43]), "+f"(d[44]), "+f"(d[45]), "+f"(d[46]), "+f"(d[47]),
      "+f"(d[48]), "+f"(d[49]), "+f"(d[50]), "+f"(d[51]), "+f"(d[52]), "+f"(d[53]), "+f"(d[54]), "+f"(d[55])
    : "r"(a[0]), "r"(a[1]), "r"(a[2]), "r"(a[3]), "l"(db), "r"(sd));
}

__device__ __forceinline__ void wgmma_rs_n128(float* d, const uint32_t* a, uint64_t db, int sd) {
  asm volatile("{ .reg .pred p; setp.ne.b32 p, %69, 0;\n"
      "wgmma.mma_async.sync.aligned.m64n128k16.f32.bf16.bf16 {"
      "%0,%1,%2,%3,%4,%5,%6,%7,%8,%9,%10,%11,%12,%13,%14,%15,"
      "%16,%17,%18,%19,%20,%21,%22,%23,%24,%25,%26,%27,%28,%29,%30,%31,"
      "%32,%33,%34,%35,%36,%37,%38,%39,%40,%41,%42,%43,%44,%45,%46,%47,"
      "%48,%49,%50,%51,%52,%53,%54,%55,%56,%57,%58,%59,%60,%61,%62,%63"
      "}, {%64,%65,%66,%67}, %68, p, 1, 1, 0; }"
    : "+f"(d[0]), "+f"(d[1]), "+f"(d[2]), "+f"(d[3]), "+f"(d[4]), "+f"(d[5]), "+f"(d[6]), "+f"(d[7]),
      "+f"(d[8]), "+f"(d[9]), "+f"(d[10]), "+f"(d[11]), "+f"(d[12]), "+f"(d[13]), "+f"(d[14]), "+f"(d[15]),
      "+f"(d[16]), "+f"(d[17]), "+f"(d[18]), "+f"(d[19]), "+f"(d[20]), "+f"(d[21]), "+f"(d[22]), "+f"(d[23]),
      "+f"(d[24]), "+f"(d[25]), "+f"(d[26]), "+f"(d[27]), "+f"(d[28]), "+f"(d[29]), "+f"(d[30]), "+f"(d[31]),
      "+f"(d[32]), "+f"(d[33]), "+f"(d[34]), "+f"(d[35]), "+f"(d[36]), "+f"(d[37]), "+f"(d[38]), "+f"(d[39]),
      "+f"(d[40]), "+f"(d[41]), "+f"(d[42]), "+f"(d[43]), "+f"(d[44]), "+f"(d[45]), "+f"(d[46]), "+f"(d[47]),
      "+f"(d[48]), "+f"(d[49]), "+f"(d[50]), "+f"(d[51]), "+f"(d[52]), "+f"(d[53]), "+f"(d[54]), "+f"(d[55]),
      "+f"(d[56]), "+f"(d[57]), "+f"(d[58]), "+f"(d[59]), "+f"(d[60]), "+f"(d[61]), "+f"(d[62]), "+f"(d[63])
    : "r"(a[0]), "r"(a[1]), "r"(a[2]), "r"(a[3]), "l"(db), "r"(sd));
}

__device__ __forceinline__ void wgmma_rs_n144(float* d, const uint32_t* a, uint64_t db, int sd) {
  asm volatile("{ .reg .pred p; setp.ne.b32 p, %77, 0;\n"
      "wgmma.mma_async.sync.aligned.m64n144k16.f32.bf16.bf16 {"
      "%0,%1,%2,%3,%4,%5,%6,%7,%8,%9,%10,%11,%12,%13,%14,%15,"
      "%16,%17,%18,%19,%20,%21,%22,%23,%24,%25,%26,%27,%28,%29,%30,%31,"
      "%32,%33,%34,%35,%36,%37,%38,%39,%40,%41,%42,%43,%44,%45,%46,%47,"
      "%48,%49,%50,%51,%52,%53,%54,%55,%56,%57,%58,%59,%60,%61,%62,%63,"
      "%64,%65,%66,%67,%68,%69,%70,%71"
      "}, {%72,%73,%74,%75}, %76, p, 1, 1, 0; }"
    : "+f"(d[0]), "+f"(d[1]), "+f"(d[2]), "+f"(d[3]), "+f"(d[4]), "+f"(d[5]), "+f"(d[6]), "+f"(d[7]),
      "+f"(d[8]), "+f"(d[9]), "+f"(d[10]), "+f"(d[11]), "+f"(d[12]), "+f"(d[13]), "+f"(d[14]), "+f"(d[15]),
      "+f"(d[16]), "+f"(d[17]), "+f"(d[18]), "+f"(d[19]), "+f"(d[20]), "+f"(d[21]), "+f"(d[22]), "+f"(d[23]),
      "+f"(d[24]), "+f"(d[25]), "+f"(d[26]), "+f"(d[27]), "+f"(d[28]), "+f"(d[29]), "+f"(d[30]), "+f"(d[31]),
      "+f"(d[32]), "+f"(d[33]), "+f"(d[34]), "+f"(d[35]), "+f"(d[36]), "+f"(d[37]), "+f"(d[38]), "+f"(d[39]),
      "+f"(d[40]), "+f"(d[41]), "+f"(d[42]), "+f"(d[43]), "+f"(d[44]), "+f"(d[45]), "+f"(d[46]), "+f"(d[47]),
      "+f"(d[48]), "+f"(d[49]), "+f"(d[50]), "+f"(d[51]), "+f"(d[52]), "+f"(d[53]), "+f"(d[54]), "+f"(d[55]),
      "+f"(d[56]), "+f"(d[57]), "+f"(d[58]), "+f"(d[59]), "+f"(d[60]), "+f"(d[61]), "+f"(d[62]), "+f"(d[63]),
      "+f"(d[64]), "+f"(d[65]), "+f"(d[66]), "+f"(d[67]), "+f"(d[68]), "+f"(d[69]), "+f"(d[70]), "+f"(d[71])
    : "r"(a[0]), "r"(a[1]), "r"(a[2]), "r"(a[3]), "l"(db), "r"(sd));
}

__device__ __forceinline__ void wgmma_rs_n160(float* d, const uint32_t* a, uint64_t db, int sd) {
  asm volatile("{ .reg .pred p; setp.ne.b32 p, %85, 0;\n"
      "wgmma.mma_async.sync.aligned.m64n160k16.f32.bf16.bf16 {"
      "%0,%1,%2,%3,%4,%5,%6,%7,%8,%9,%10,%11,%12,%13,%14,%15,"
      "%16,%17,%18,%19,%20,%21,%22,%23,%24,%25,%26,%27,%28,%29,%30,%31,"
      "%32,%33,%34,%35,%36,%37,%38,%39,%40,%41,%42,%43,%44,%45,%46,%47,"
      "%48,%49,%50,%51,%52,%53,%54,%55,%56,%57,%58,%59,%60,%61,%62,%63,"
      "%64,%65,%66,%67,%68,%69,%70,%71,%72,%73,%74,%75,%76,%77,%78,%79"
      "}, {%80,%81,%82,%83}, %84, p, 1, 1, 0; }"
    : "+f"(d[0]), "+f"(d[1]), "+f"(d[2]), "+f"(d[3]), "+f"(d[4]), "+f"(d[5]), "+f"(d[6]), "+f"(d[7]),
      "+f"(d[8]), "+f"(d[9]), "+f"(d[10]), "+f"(d[11]), "+f"(d[12]), "+f"(d[13]), "+f"(d[14]), "+f"(d[15]),
      "+f"(d[16]), "+f"(d[17]), "+f"(d[18]), "+f"(d[19]), "+f"(d[20]), "+f"(d[21]), "+f"(d[22]), "+f"(d[23]),
      "+f"(d[24]), "+f"(d[25]), "+f"(d[26]), "+f"(d[27]), "+f"(d[28]), "+f"(d[29]), "+f"(d[30]), "+f"(d[31]),
      "+f"(d[32]), "+f"(d[33]), "+f"(d[34]), "+f"(d[35]), "+f"(d[36]), "+f"(d[37]), "+f"(d[38]), "+f"(d[39]),
      "+f"(d[40]), "+f"(d[41]), "+f"(d[42]), "+f"(d[43]), "+f"(d[44]), "+f"(d[45]), "+f"(d[46]), "+f"(d[47]),
      "+f"(d[48]), "+f"(d[49]), "+f"(d[50]), "+f"(d[51]), "+f"(d[52]), "+f"(d[53]), "+f"(d[54]), "+f"(d[55]),
      "+f"(d[56]), "+f"(d[57]), "+f"(d[58]), "+f"(d[59]), "+f"(d[60]), "+f"(d[61]), "+f"(d[62]), "+f"(d[63]),
      "+f"(d[64]), "+f"(d[65]), "+f"(d[66]), "+f"(d[67]), "+f"(d[68]), "+f"(d[69]), "+f"(d[70]), "+f"(d[71]),
      "+f"(d[72]), "+f"(d[73]), "+f"(d[74]), "+f"(d[75]), "+f"(d[76]), "+f"(d[77]), "+f"(d[78]), "+f"(d[79])
    : "r"(a[0]), "r"(a[1]), "r"(a[2]), "r"(a[3]), "l"(db), "r"(sd));
}

__device__ __forceinline__ void wgmma_rs_n176(float* d, const uint32_t* a, uint64_t db, int sd) {
  asm volatile("{ .reg .pred p; setp.ne.b32 p, %93, 0;\n"
      "wgmma.mma_async.sync.aligned.m64n176k16.f32.bf16.bf16 {"
      "%0,%1,%2,%3,%4,%5,%6,%7,%8,%9,%10,%11,%12,%13,%14,%15,"
      "%16,%17,%18,%19,%20,%21,%22,%23,%24,%25,%26,%27,%28,%29,%30,%31,"
      "%32,%33,%34,%35,%36,%37,%38,%39,%40,%41,%42,%43,%44,%45,%46,%47,"
      "%48,%49,%50,%51,%52,%53,%54,%55,%56,%57,%58,%59,%60,%61,%62,%63,"
      "%64,%65,%66,%67,%68,%69,%70,%71,%72,%73,%74,%75,%76,%77,%78,%79,"
      "%80,%81,%82,%83,%84,%85,%86,%87"
      "}, {%88,%89,%90,%91}, %92, p, 1, 1, 0; }"
    : "+f"(d[0]), "+f"(d[1]), "+f"(d[2]), "+f"(d[3]), "+f"(d[4]), "+f"(d[5]), "+f"(d[6]), "+f"(d[7]),
      "+f"(d[8]), "+f"(d[9]), "+f"(d[10]), "+f"(d[11]), "+f"(d[12]), "+f"(d[13]), "+f"(d[14]), "+f"(d[15]),
      "+f"(d[16]), "+f"(d[17]), "+f"(d[18]), "+f"(d[19]), "+f"(d[20]), "+f"(d[21]), "+f"(d[22]), "+f"(d[23]),
      "+f"(d[24]), "+f"(d[25]), "+f"(d[26]), "+f"(d[27]), "+f"(d[28]), "+f"(d[29]), "+f"(d[30]), "+f"(d[31]),
      "+f"(d[32]), "+f"(d[33]), "+f"(d[34]), "+f"(d[35]), "+f"(d[36]), "+f"(d[37]), "+f"(d[38]), "+f"(d[39]),
      "+f"(d[40]), "+f"(d[41]), "+f"(d[42]), "+f"(d[43]), "+f"(d[44]), "+f"(d[45]), "+f"(d[46]), "+f"(d[47]),
      "+f"(d[48]), "+f"(d[49]), "+f"(d[50]), "+f"(d[51]), "+f"(d[52]), "+f"(d[53]), "+f"(d[54]), "+f"(d[55]),
      "+f"(d[56]), "+f"(d[57]), "+f"(d[58]), "+f"(d[59]), "+f"(d[60]), "+f"(d[61]), "+f"(d[62]), "+f"(d[63]),
      "+f"(d[64]), "+f"(d[65]), "+f"(d[66]), "+f"(d[67]), "+f"(d[68]), "+f"(d[69]), "+f"(d[70]), "+f"(d[71]),
      "+f"(d[72]), "+f"(d[73]), "+f"(d[74]), "+f"(d[75]), "+f"(d[76]), "+f"(d[77]), "+f"(d[78]), "+f"(d[79]),
      "+f"(d[80]), "+f"(d[81]), "+f"(d[82]), "+f"(d[83]), "+f"(d[84]), "+f"(d[85]), "+f"(d[86]), "+f"(d[87])
    : "r"(a[0]), "r"(a[1]), "r"(a[2]), "r"(a[3]), "l"(db), "r"(sd));
}

__device__ __forceinline__ void wgmma_rs_n192(float* d, const uint32_t* a, uint64_t db, int sd) {
  asm volatile("{ .reg .pred p; setp.ne.b32 p, %101, 0;\n"
      "wgmma.mma_async.sync.aligned.m64n192k16.f32.bf16.bf16 {"
      "%0,%1,%2,%3,%4,%5,%6,%7,%8,%9,%10,%11,%12,%13,%14,%15,"
      "%16,%17,%18,%19,%20,%21,%22,%23,%24,%25,%26,%27,%28,%29,%30,%31,"
      "%32,%33,%34,%35,%36,%37,%38,%39,%40,%41,%42,%43,%44,%45,%46,%47,"
      "%48,%49,%50,%51,%52,%53,%54,%55,%56,%57,%58,%59,%60,%61,%62,%63,"
      "%64,%65,%66,%67,%68,%69,%70,%71,%72,%73,%74,%75,%76,%77,%78,%79,"
      "%80,%81,%82,%83,%84,%85,%86,%87,%88,%89,%90,%91,%92,%93,%94,%95"
      "}, {%96,%97,%98,%99}, %100, p, 1, 1, 0; }"
    : "+f"(d[0]), "+f"(d[1]), "+f"(d[2]), "+f"(d[3]), "+f"(d[4]), "+f"(d[5]), "+f"(d[6]), "+f"(d[7]),
      "+f"(d[8]), "+f"(d[9]), "+f"(d[10]), "+f"(d[11]), "+f"(d[12]), "+f"(d[13]), "+f"(d[14]), "+f"(d[15]),
      "+f"(d[16]), "+f"(d[17]), "+f"(d[18]), "+f"(d[19]), "+f"(d[20]), "+f"(d[21]), "+f"(d[22]), "+f"(d[23]),
      "+f"(d[24]), "+f"(d[25]), "+f"(d[26]), "+f"(d[27]), "+f"(d[28]), "+f"(d[29]), "+f"(d[30]), "+f"(d[31]),
      "+f"(d[32]), "+f"(d[33]), "+f"(d[34]), "+f"(d[35]), "+f"(d[36]), "+f"(d[37]), "+f"(d[38]), "+f"(d[39]),
      "+f"(d[40]), "+f"(d[41]), "+f"(d[42]), "+f"(d[43]), "+f"(d[44]), "+f"(d[45]), "+f"(d[46]), "+f"(d[47]),
      "+f"(d[48]), "+f"(d[49]), "+f"(d[50]), "+f"(d[51]), "+f"(d[52]), "+f"(d[53]), "+f"(d[54]), "+f"(d[55]),
      "+f"(d[56]), "+f"(d[57]), "+f"(d[58]), "+f"(d[59]), "+f"(d[60]), "+f"(d[61]), "+f"(d[62]), "+f"(d[63]),
      "+f"(d[64]), "+f"(d[65]), "+f"(d[66]), "+f"(d[67]), "+f"(d[68]), "+f"(d[69]), "+f"(d[70]), "+f"(d[71]),
      "+f"(d[72]), "+f"(d[73]), "+f"(d[74]), "+f"(d[75]), "+f"(d[76]), "+f"(d[77]), "+f"(d[78]), "+f"(d[79]),
      "+f"(d[80]), "+f"(d[81]), "+f"(d[82]), "+f"(d[83]), "+f"(d[84]), "+f"(d[85]), "+f"(d[86]), "+f"(d[87]),
      "+f"(d[88]), "+f"(d[89]), "+f"(d[90]), "+f"(d[91]), "+f"(d[92]), "+f"(d[93]), "+f"(d[94]), "+f"(d[95])
    : "r"(a[0]), "r"(a[1]), "r"(a[2]), "r"(a[3]), "l"(db), "r"(sd));
}

__device__ __forceinline__ void wgmma_rs_n208(float* d, const uint32_t* a, uint64_t db, int sd) {
  asm volatile("{ .reg .pred p; setp.ne.b32 p, %109, 0;\n"
      "wgmma.mma_async.sync.aligned.m64n208k16.f32.bf16.bf16 {"
      "%0,%1,%2,%3,%4,%5,%6,%7,%8,%9,%10,%11,%12,%13,%14,%15,"
      "%16,%17,%18,%19,%20,%21,%22,%23,%24,%25,%26,%27,%28,%29,%30,%31,"
      "%32,%33,%34,%35,%36,%37,%38,%39,%40,%41,%42,%43,%44,%45,%46,%47,"
      "%48,%49,%50,%51,%52,%53,%54,%55,%56,%57,%58,%59,%60,%61,%62,%63,"
      "%64,%65,%66,%67,%68,%69,%70,%71,%72,%73,%74,%75,%76,%77,%78,%79,"
      "%80,%81,%82,%83,%84,%85,%86,%87,%88,%89,%90,%91,%92,%93,%94,%95,"
      "%96,%97,%98,%99,%100,%101,%102,%103"
      "}, {%104,%105,%106,%107}, %108, p, 1, 1, 0; }"
    : "+f"(d[0]), "+f"(d[1]), "+f"(d[2]), "+f"(d[3]), "+f"(d[4]), "+f"(d[5]), "+f"(d[6]), "+f"(d[7]),
      "+f"(d[8]), "+f"(d[9]), "+f"(d[10]), "+f"(d[11]), "+f"(d[12]), "+f"(d[13]), "+f"(d[14]), "+f"(d[15]),
      "+f"(d[16]), "+f"(d[17]), "+f"(d[18]), "+f"(d[19]), "+f"(d[20]), "+f"(d[21]), "+f"(d[22]), "+f"(d[23]),
      "+f"(d[24]), "+f"(d[25]), "+f"(d[26]), "+f"(d[27]), "+f"(d[28]), "+f"(d[29]), "+f"(d[30]), "+f"(d[31]),
      "+f"(d[32]), "+f"(d[33]), "+f"(d[34]), "+f"(d[35]), "+f"(d[36]), "+f"(d[37]), "+f"(d[38]), "+f"(d[39]),
      "+f"(d[40]), "+f"(d[41]), "+f"(d[42]), "+f"(d[43]), "+f"(d[44]), "+f"(d[45]), "+f"(d[46]), "+f"(d[47]),
      "+f"(d[48]), "+f"(d[49]), "+f"(d[50]), "+f"(d[51]), "+f"(d[52]), "+f"(d[53]), "+f"(d[54]), "+f"(d[55]),
      "+f"(d[56]), "+f"(d[57]), "+f"(d[58]), "+f"(d[59]), "+f"(d[60]), "+f"(d[61]), "+f"(d[62]), "+f"(d[63]),
      "+f"(d[64]), "+f"(d[65]), "+f"(d[66]), "+f"(d[67]), "+f"(d[68]), "+f"(d[69]), "+f"(d[70]), "+f"(d[71]),
      "+f"(d[72]), "+f"(d[73]), "+f"(d[74]), "+f"(d[75]), "+f"(d[76]), "+f"(d[77]), "+f"(d[78]), "+f"(d[79]),
      "+f"(d[80]), "+f"(d[81]), "+f"(d[82]), "+f"(d[83]), "+f"(d[84]), "+f"(d[85]), "+f"(d[86]), "+f"(d[87]),
      "+f"(d[88]), "+f"(d[89]), "+f"(d[90]), "+f"(d[91]), "+f"(d[92]), "+f"(d[93]), "+f"(d[94]), "+f"(d[95]),
      "+f"(d[96]), "+f"(d[97]), "+f"(d[98]), "+f"(d[99]), "+f"(d[100]), "+f"(d[101]), "+f"(d[102]), "+f"(d[103])
    : "r"(a[0]), "r"(a[1]), "r"(a[2]), "r"(a[3]), "l"(db), "r"(sd));
}

__device__ __forceinline__ void wgmma_rs_n224(float* d, const uint32_t* a, uint64_t db, int sd) {
  asm volatile("{ .reg .pred p; setp.ne.b32 p, %117, 0;\n"
      "wgmma.mma_async.sync.aligned.m64n224k16.f32.bf16.bf16 {"
      "%0,%1,%2,%3,%4,%5,%6,%7,%8,%9,%10,%11,%12,%13,%14,%15,"
      "%16,%17,%18,%19,%20,%21,%22,%23,%24,%25,%26,%27,%28,%29,%30,%31,"
      "%32,%33,%34,%35,%36,%37,%38,%39,%40,%41,%42,%43,%44,%45,%46,%47,"
      "%48,%49,%50,%51,%52,%53,%54,%55,%56,%57,%58,%59,%60,%61,%62,%63,"
      "%64,%65,%66,%67,%68,%69,%70,%71,%72,%73,%74,%75,%76,%77,%78,%79,"
      "%80,%81,%82,%83,%84,%85,%86,%87,%88,%89,%90,%91,%92,%93,%94,%95,"
      "%96,%97,%98,%99,%100,%101,%102,%103,%104,%105,%106,%107,%108,%109,%110,%111"
      "}, {%112,%113,%114,%115}, %116, p, 1, 1, 0; }"
    : "+f"(d[0]), "+f"(d[1]), "+f"(d[2]), "+f"(d[3]), "+f"(d[4]), "+f"(d[5]), "+f"(d[6]), "+f"(d[7]),
      "+f"(d[8]), "+f"(d[9]), "+f"(d[10]), "+f"(d[11]), "+f"(d[12]), "+f"(d[13]), "+f"(d[14]), "+f"(d[15]),
      "+f"(d[16]), "+f"(d[17]), "+f"(d[18]), "+f"(d[19]), "+f"(d[20]), "+f"(d[21]), "+f"(d[22]), "+f"(d[23]),
      "+f"(d[24]), "+f"(d[25]), "+f"(d[26]), "+f"(d[27]), "+f"(d[28]), "+f"(d[29]), "+f"(d[30]), "+f"(d[31]),
      "+f"(d[32]), "+f"(d[33]), "+f"(d[34]), "+f"(d[35]), "+f"(d[36]), "+f"(d[37]), "+f"(d[38]), "+f"(d[39]),
      "+f"(d[40]), "+f"(d[41]), "+f"(d[42]), "+f"(d[43]), "+f"(d[44]), "+f"(d[45]), "+f"(d[46]), "+f"(d[47]),
      "+f"(d[48]), "+f"(d[49]), "+f"(d[50]), "+f"(d[51]), "+f"(d[52]), "+f"(d[53]), "+f"(d[54]), "+f"(d[55]),
      "+f"(d[56]), "+f"(d[57]), "+f"(d[58]), "+f"(d[59]), "+f"(d[60]), "+f"(d[61]), "+f"(d[62]), "+f"(d[63]),
      "+f"(d[64]), "+f"(d[65]), "+f"(d[66]), "+f"(d[67]), "+f"(d[68]), "+f"(d[69]), "+f"(d[70]), "+f"(d[71]),
      "+f"(d[72]), "+f"(d[73]), "+f"(d[74]), "+f"(d[75]), "+f"(d[76]), "+f"(d[77]), "+f"(d[78]), "+f"(d[79]),
      "+f"(d[80]), "+f"(d[81]), "+f"(d[82]), "+f"(d[83]), "+f"(d[84]), "+f"(d[85]), "+f"(d[86]), "+f"(d[87]),
      "+f"(d[88]), "+f"(d[89]), "+f"(d[90]), "+f"(d[91]), "+f"(d[92]), "+f"(d[93]), "+f"(d[94]), "+f"(d[95]),
      "+f"(d[96]), "+f"(d[97]), "+f"(d[98]), "+f"(d[99]), "+f"(d[100]), "+f"(d[101]), "+f"(d[102]), "+f"(d[103]),
      "+f"(d[104]), "+f"(d[105]), "+f"(d[106]), "+f"(d[107]), "+f"(d[108]), "+f"(d[109]), "+f"(d[110]), "+f"(d[111])
    : "r"(a[0]), "r"(a[1]), "r"(a[2]), "r"(a[3]), "l"(db), "r"(sd));
}

__device__ __forceinline__ void wgmma_rs_n240(float* d, const uint32_t* a, uint64_t db, int sd) {
  asm volatile("{ .reg .pred p; setp.ne.b32 p, %125, 0;\n"
      "wgmma.mma_async.sync.aligned.m64n240k16.f32.bf16.bf16 {"
      "%0,%1,%2,%3,%4,%5,%6,%7,%8,%9,%10,%11,%12,%13,%14,%15,"
      "%16,%17,%18,%19,%20,%21,%22,%23,%24,%25,%26,%27,%28,%29,%30,%31,"
      "%32,%33,%34,%35,%36,%37,%38,%39,%40,%41,%42,%43,%44,%45,%46,%47,"
      "%48,%49,%50,%51,%52,%53,%54,%55,%56,%57,%58,%59,%60,%61,%62,%63,"
      "%64,%65,%66,%67,%68,%69,%70,%71,%72,%73,%74,%75,%76,%77,%78,%79,"
      "%80,%81,%82,%83,%84,%85,%86,%87,%88,%89,%90,%91,%92,%93,%94,%95,"
      "%96,%97,%98,%99,%100,%101,%102,%103,%104,%105,%106,%107,%108,%109,%110,%111,"
      "%112,%113,%114,%115,%116,%117,%118,%119"
      "}, {%120,%121,%122,%123}, %124, p, 1, 1, 0; }"
    : "+f"(d[0]), "+f"(d[1]), "+f"(d[2]), "+f"(d[3]), "+f"(d[4]), "+f"(d[5]), "+f"(d[6]), "+f"(d[7]),
      "+f"(d[8]), "+f"(d[9]), "+f"(d[10]), "+f"(d[11]), "+f"(d[12]), "+f"(d[13]), "+f"(d[14]), "+f"(d[15]),
      "+f"(d[16]), "+f"(d[17]), "+f"(d[18]), "+f"(d[19]), "+f"(d[20]), "+f"(d[21]), "+f"(d[22]), "+f"(d[23]),
      "+f"(d[24]), "+f"(d[25]), "+f"(d[26]), "+f"(d[27]), "+f"(d[28]), "+f"(d[29]), "+f"(d[30]), "+f"(d[31]),
      "+f"(d[32]), "+f"(d[33]), "+f"(d[34]), "+f"(d[35]), "+f"(d[36]), "+f"(d[37]), "+f"(d[38]), "+f"(d[39]),
      "+f"(d[40]), "+f"(d[41]), "+f"(d[42]), "+f"(d[43]), "+f"(d[44]), "+f"(d[45]), "+f"(d[46]), "+f"(d[47]),
      "+f"(d[48]), "+f"(d[49]), "+f"(d[50]), "+f"(d[51]), "+f"(d[52]), "+f"(d[53]), "+f"(d[54]), "+f"(d[55]),
      "+f"(d[56]), "+f"(d[57]), "+f"(d[58]), "+f"(d[59]), "+f"(d[60]), "+f"(d[61]), "+f"(d[62]), "+f"(d[63]),
      "+f"(d[64]), "+f"(d[65]), "+f"(d[66]), "+f"(d[67]), "+f"(d[68]), "+f"(d[69]), "+f"(d[70]), "+f"(d[71]),
      "+f"(d[72]), "+f"(d[73]), "+f"(d[74]), "+f"(d[75]), "+f"(d[76]), "+f"(d[77]), "+f"(d[78]), "+f"(d[79]),
      "+f"(d[80]), "+f"(d[81]), "+f"(d[82]), "+f"(d[83]), "+f"(d[84]), "+f"(d[85]), "+f"(d[86]), "+f"(d[87]),
      "+f"(d[88]), "+f"(d[89]), "+f"(d[90]), "+f"(d[91]), "+f"(d[92]), "+f"(d[93]), "+f"(d[94]), "+f"(d[95]),
      "+f"(d[96]), "+f"(d[97]), "+f"(d[98]), "+f"(d[99]), "+f"(d[100]), "+f"(d[101]), "+f"(d[102]), "+f"(d[103]),
      "+f"(d[104]), "+f"(d[105]), "+f"(d[106]), "+f"(d[107]), "+f"(d[108]), "+f"(d[109]), "+f"(d[110]), "+f"(d[111]),
      "+f"(d[112]), "+f"(d[113]), "+f"(d[114]), "+f"(d[115]), "+f"(d[116]), "+f"(d[117]), "+f"(d[118]), "+f"(d[119])
    : "r"(a[0]), "r"(a[1]), "r"(a[2]), "r"(a[3]), "l"(db), "r"(sd));
}

__device__ __forceinline__ void wgmma_rs_n256(float* d, const uint32_t* a, uint64_t db, int sd) {
  asm volatile("{ .reg .pred p; setp.ne.b32 p, %133, 0;\n"
      "wgmma.mma_async.sync.aligned.m64n256k16.f32.bf16.bf16 {"
      "%0,%1,%2,%3,%4,%5,%6,%7,%8,%9,%10,%11,%12,%13,%14,%15,"
      "%16,%17,%18,%19,%20,%21,%22,%23,%24,%25,%26,%27,%28,%29,%30,%31,"
      "%32,%33,%34,%35,%36,%37,%38,%39,%40,%41,%42,%43,%44,%45,%46,%47,"
      "%48,%49,%50,%51,%52,%53,%54,%55,%56,%57,%58,%59,%60,%61,%62,%63,"
      "%64,%65,%66,%67,%68,%69,%70,%71,%72,%73,%74,%75,%76,%77,%78,%79,"
      "%80,%81,%82,%83,%84,%85,%86,%87,%88,%89,%90,%91,%92,%93,%94,%95,"
      "%96,%97,%98,%99,%100,%101,%102,%103,%104,%105,%106,%107,%108,%109,%110,%111,"
      "%112,%113,%114,%115,%116,%117,%118,%119,%120,%121,%122,%123,%124,%125,%126,%127"
      "}, {%128,%129,%130,%131}, %132, p, 1, 1, 0; }"
    : "+f"(d[0]), "+f"(d[1]), "+f"(d[2]), "+f"(d[3]), "+f"(d[4]), "+f"(d[5]), "+f"(d[6]), "+f"(d[7]),
      "+f"(d[8]), "+f"(d[9]), "+f"(d[10]), "+f"(d[11]), "+f"(d[12]), "+f"(d[13]), "+f"(d[14]), "+f"(d[15]),
      "+f"(d[16]), "+f"(d[17]), "+f"(d[18]), "+f"(d[19]), "+f"(d[20]), "+f"(d[21]), "+f"(d[22]), "+f"(d[23]),
      "+f"(d[24]), "+f"(d[25]), "+f"(d[26]), "+f"(d[27]), "+f"(d[28]), "+f"(d[29]), "+f"(d[30]), "+f"(d[31]),
      "+f"(d[32]), "+f"(d[33]), "+f"(d[34]), "+f"(d[35]), "+f"(d[36]), "+f"(d[37]), "+f"(d[38]), "+f"(d[39]),
      "+f"(d[40]), "+f"(d[41]), "+f"(d[42]), "+f"(d[43]), "+f"(d[44]), "+f"(d[45]), "+f"(d[46]), "+f"(d[47]),
      "+f"(d[48]), "+f"(d[49]), "+f"(d[50]), "+f"(d[51]), "+f"(d[52]), "+f"(d[53]), "+f"(d[54]), "+f"(d[55]),
      "+f"(d[56]), "+f"(d[57]), "+f"(d[58]), "+f"(d[59]), "+f"(d[60]), "+f"(d[61]), "+f"(d[62]), "+f"(d[63]),
      "+f"(d[64]), "+f"(d[65]), "+f"(d[66]), "+f"(d[67]), "+f"(d[68]), "+f"(d[69]), "+f"(d[70]), "+f"(d[71]),
      "+f"(d[72]), "+f"(d[73]), "+f"(d[74]), "+f"(d[75]), "+f"(d[76]), "+f"(d[77]), "+f"(d[78]), "+f"(d[79]),
      "+f"(d[80]), "+f"(d[81]), "+f"(d[82]), "+f"(d[83]), "+f"(d[84]), "+f"(d[85]), "+f"(d[86]), "+f"(d[87]),
      "+f"(d[88]), "+f"(d[89]), "+f"(d[90]), "+f"(d[91]), "+f"(d[92]), "+f"(d[93]), "+f"(d[94]), "+f"(d[95]),
      "+f"(d[96]), "+f"(d[97]), "+f"(d[98]), "+f"(d[99]), "+f"(d[100]), "+f"(d[101]), "+f"(d[102]), "+f"(d[103]),
      "+f"(d[104]), "+f"(d[105]), "+f"(d[106]), "+f"(d[107]), "+f"(d[108]), "+f"(d[109]), "+f"(d[110]), "+f"(d[111]),
      "+f"(d[112]), "+f"(d[113]), "+f"(d[114]), "+f"(d[115]), "+f"(d[116]), "+f"(d[117]), "+f"(d[118]), "+f"(d[119]),
      "+f"(d[120]), "+f"(d[121]), "+f"(d[122]), "+f"(d[123]), "+f"(d[124]), "+f"(d[125]), "+f"(d[126]), "+f"(d[127])
    : "r"(a[0]), "r"(a[1]), "r"(a[2]), "r"(a[3]), "l"(db), "r"(sd));
}

__device__ __forceinline__ void ln_finish(float mean, float var, float& mb, float& rinv) {
  mb = round_bf16(mean);
  float den = round_bf16(sqrtf(round_bf16(round_bf16(var) + 1e-5f)));
  rinv = 1.0f / den;
}
__device__ __forceinline__ uint32_t ln_apply(uint32_t x2, uint32_t mb2, float rinv) {
  uint32_t c = bsub2(x2, mb2);
  return pack_bf16(bf_lo(c) * rinv, bf_hi(c) * rinv);
}
__device__ __forceinline__ int conv_channel(int cta, int i) {
  return i < N_SHORT ? i * N_CONV_CTA + cta : N_SHORT * N_CONV_CTA + (i - N_SHORT) * 4 + cta;
}
__device__ __forceinline__ uint32_t sum4(uint32_t a, uint32_t b, uint32_t c, uint32_t d) {
  return pack_bf16((bf_lo(a) + bf_lo(b)) + (bf_lo(c) + bf_lo(d)), (bf_hi(a) + bf_hi(b)) + (bf_hi(c) + bf_hi(d)));
}
struct Ring {
  uint32_t s, ph;
  __device__ __forceinline__ void next() { if (++s == NSTAGE) { s = 0; ph ^= 1; } }
};

__global__ void __cluster_dims__(2, 1, 1) __launch_bounds__(384, 1) fused_kernel(const __grid_constant__ Params P) {
  extern __shared__ uint8_t smem_raw[];
  const uint32_t sb = (smem_u32(smem_raw) + 1023) & ~1023u;
  const uint32_t bars = sb + SM_BAR;
  const int tid = threadIdx.x, warp = __shfl_sync(0xffffffffu, tid >> 5, 0), lane = tid & 31;
  const int cl = blockIdx.x >> 1, rank = blockIdx.x & 1;
  const int p0 = P.roles.p0[cl], p0b = 2 * p0 + rank;

  uint32_t xr[18];
  const int ln_row = p0b * 16 + warp * 2 + (lane >> 4);
  if (warp < 8 && p0 >= 0) {
    const uint2* src = reinterpret_cast<const uint2*>(P.x + (size_t)ln_row * D_) + (lane & 15);
#pragma unroll
    for (int j = 0; j < 9; j++) asm volatile("ld.global.nc.v2.u32 {%0,%1}, [%2];" : "=r"(xr[2 * j]), "=r"(xr[2 * j + 1]) : "l"(src + 16 * j));
  }
  const uint32_t tag = ld_flag(&g_epoch) + 1;
  const int g1m = P.roles.g1m[cl], g1n = P.roles.g1n[cl], cv = P.roles.cv[cl], g2m = P.roles.g2m[cl], g2n = P.roles.g2n[cl];
  const int cvc = 2 * cv + rank;
  const int n_conv = cv < 0 ? 0 : (cv < 2 ? N_SHORT + N_LONG_EXTRA : N_SHORT);
  const int dk = g2n * 144 + rank * 72;
  if (warp == 8) {
    if (lane <= B_Y2) mbar_init(bars + 8 * lane, lane >= B_EMPTY && lane < B_CFULL ? 2 : (lane >= B_CEMPTY && lane < B_XRDY ? 4 : 1));
    if (g1m < 0 && lane < G1_KB % NSTAGE) mbar_arrive(bars + 8 * (B_FULL + lane));
    asm volatile("fence.mbarrier_init.release.cluster;" ::: "memory");
  }
  __syncthreads();
  asm volatile("barrier.cluster.arrive.relaxed.aligned;" ::: "memory");

  if (warp >= 8) {
    asm volatile("setmaxnreg.dec.sync.aligned.u32 56;");
    if (warp == 8) {
      if (lane == 0) {
        if (g1m >= 0) {
          const int fg = (2 * g1m + rank) * 2, dg = g1n * 3;
          for (int s = 0; s < NSTAGE; s++) {
            mbar_expect_tx(bars + 8 * (B_FULL + s), G1_BYTES);
            tma3d(sb + s * SLOT, &P.m_w1, 0, s * 64, fg, bars + 8 * (B_FULL + s));
          }
          await(C_H, tag * 128);
          TLREC(2);
          fence_async_global();
          for (int s = 0; s < NSTAGE; s++) tma3d(sb + s * SLOT + 16384, &P.m_h, 0, s * 64, dg, bars + 8 * (B_FULL + s));
          Ring r{0, 0};
#pragma unroll 1
          for (int kb = NSTAGE; kb < G1_KB; kb++, r.next()) {
            mbar_wait(bars + 8 * (B_EMPTY + r.s), r.ph);
            mbar_expect_tx(bars + 8 * (B_FULL + r.s), G1_BYTES);
            tma3d(sb + r.s * SLOT, &P.m_w1, 0, kb * 64, fg, bars + 8 * (B_FULL + r.s));
            tma3d(sb + r.s * SLOT + 16384, &P.m_h, 0, kb * 64, dg, bars + 8 * (B_FULL + r.s));
          }
        } else {
          for (int i = 0; i < CV_NSLOT; i++) {
            mbar_expect_tx(bars + 8 * (B_CFULL + i), 8192 + 4096);
            bulk_load(sb + i * CV_SLOT + CV_KOFF + 32, P.ssm_k + (size_t)conv_channel(cvc, i) * S_, 4096, bars + 8 * (B_CFULL + i));
          }
          int ready = -1;
#pragma unroll 1
          for (int i = 0; i < n_conv; i++) {
            const int ch = conv_channel(cvc, i), s = i % CV_NSLOT;
            const uint32_t slot = sb + s * CV_SLOT, fb = bars + 8 * (B_CFULL + s);
            if (i >= CV_NSLOT) {
              mbar_wait(bars + 8 * (B_CEMPTY + s), ((i / CV_NSLOT) - 1) & 1);
              mbar_expect_tx(fb, 8192 + 4096);
              bulk_load(slot + CV_KOFF + 32, P.ssm_k + (size_t)ch * S_, 4096, fb);
            }
            const int r = ch / 96;
            if (r > ready) {
              await(C_KV + r, tag * 128);
              fence_async_global();
              if (r == 0) TLREC(18);
              ready = r;
            }
            bulk_load(slot, g_ub + (size_t)ch * 4096, 8192, fb);
          }
        }
        if (g2m >= 0) {
          const int sg = g2m * 2, ds = g2n * 144 + (rank ^ 1) * 72;
          const int cu0 = C_U + ((g2n * 144) / 192) * 4 + rank * 2, cu1 = C_U + ((g2n * 144 + 143) / 192) * 4 + rank * 2;
          constexpr int NPRE = 3;
          for (int kb = 0; kb < NPRE; kb++) {
            const int s = (G1_KB + kb) % NSTAGE;
            mbar_wait(bars + 8 * (B_EMPTY + s), (((G1_KB + kb) / NSTAGE) - 1) & 1);
            mbar_expect_tx(bars + 8 * (B_FULL + s), G2_BYTES);
            tma3d(sb + s * SLOT, &P.m_w2, 0, (rank * G2_KB + 2 * kb) * 64, sg, bars + 8 * (B_FULL + s));
          }
          Ring r{G1_KB % NSTAGE, ((G1_KB / NSTAGE) - 1) & 1};
#pragma unroll 1
          for (int kb = 0; kb < G2_KB; kb++, r.next()) {
            const int k0 = (rank * G2_KB + (kb < 18 ? 2 * kb : 2 * kb - 35)) * 64;
            const uint32_t fb = bars + 8 * (B_FULL + r.s), slot = sb + r.s * SLOT;
            if (kb == 0 || kb == 18) {
              await(cu0 + (kb != 0), tag * 18);
              await(cu1 + (kb != 0), tag * 18);
              fence_async_global();
              if (kb == 0) TLREC(6);
            }
            if (kb >= NPRE) {
              mbar_wait(bars + 8 * (B_EMPTY + r.s), r.ph);
              mbar_expect_tx(fb, G2_BYTES);
              tma3d(slot, &P.m_w2, 0, k0, sg, fb);
            }
            tma2d(slot + 16384, &P.m_uld, k0, ds, fb);
            tma2d(slot + 16384 + 9216, &P.m_uld, k0, dk, fb);
            if (kb == 10) {
              mbar_expect_tx(bars + 8 * B_XT, 18432);
              for (int j = 0; j < 8; j++)
                tma2d(sb + ((XSLOT + 1 + (j >> 1)) % NSTAGE) * SLOT + G2_BYTES + (j & 1) * 2304, &P.m_x, dk, g2m * 128 + j * 16, bars + 8 * B_XT);
            }
          }
          mbar_expect_tx(bars + 8 * B_XFULL, 18432);
          mbar_expect_tx(bars + 8 * (B_XFULL + 1), 18432);
          mbar_wait(bars + 8 * (B_EMPTY + XSLOT), r.ph);
        }
      }
      __syncwarp();
      asm volatile("barrier.cluster.wait.aligned;" ::: "memory");
      if (lane == 0 && g2m >= 0) mbar_arrive_remote(mapa(bars + 8 * B_XRDY, rank ^ 1));
    } else {
      const int ht = tid - 288;
      if (p0 >= 0) {
        const int hf = ht / 48, pr = ht % 48;
        const int s0 = p0b * 16 + hf * 8;
        const bool first = s0 == 0, odd = lane & 1;
#pragma unroll 1
        for (int r = 0; r < KV_ROUNDS; r++) {
          const int d = r * 96 + 2 * pr;
          const __nv_bfloat16* kp = P.k + (ptrdiff_t)(s0 - 4) * D_ + d;
          const __nv_bfloat16* vp = P.v + (ptrdiff_t)(s0 - 1) * D_ + d;
          uint32_t kk[12], vv[9];
#pragma unroll
          for (int j = 0; j < 12; j++) kk[j] = (j < 4 && first) ? 0u : ldg32(kp + j * D_);
#pragma unroll
          for (int j = 0; j < 9; j++) vv[j] = (j < 1 && first) ? 0u : ldg32(vp + j * D_);
          const uint4 w = __ldg(reinterpret_cast<const uint4*>(P.shift_k + d * 4));
          const uint32_t w0 = __byte_perm(w.x, w.z, 0x5410), w1 = __byte_perm(w.x, w.z, 0x7632);
          const uint32_t w2 = __byte_perm(w.y, w.w, 0x5410), w3 = __byte_perm(w.y, w.w, 0x7632);
#pragma unroll
          for (int j = 0; j < 9; j++)
            vv[j] = bmul2(bfma2(kk[j + 3], w0, bfma2(kk[j + 2], w1, bfma2(kk[j + 1], w2, bmul2(kk[j], w3)))), vv[j]);
          uint32_t da[8], db[8];
#pragma unroll
          for (int j = 0; j < 8; j++) {
            const uint32_t o = __shfl_xor_sync(0xffffffffu, odd ? vv[j] : vv[j + 1], 1);
            da[j] = odd ? o : vv[j];
            db[j] = odd ? vv[j + 1] : o;
          }
          uint4* dst = reinterpret_cast<uint4*>(g_ub + (size_t)(d & ~3) * 4096) + (1 - hf) * 256 + 2 * (127 - p0b) + odd;
#pragma unroll
          for (int c = 0; c < 2; c++) {
            const uint32_t sel = c ? 0x7632 : 0x5410;
            dst[c * 512] = make_uint4(__byte_perm(da[7], da[6], sel), __byte_perm(da[5], da[4], sel), __byte_perm(da[3], da[2], sel), __byte_perm(da[1], da[0], sel));
            dst[(c + 2) * 512] = make_uint4(__byte_perm(db[7], db[6], sel), __byte_perm(db[5], db[4], sel), __byte_perm(db[3], db[2], sel), __byte_perm(db[1], db[0], sel));
          }
          bar_sync(1, 96);
          if (ht == 0) { signal(C_KV + r); TLREC(22 + r); }
          __syncwarp();
        }
      }
      asm volatile("barrier.cluster.wait.aligned;" ::: "memory");
      if (lane == 0) {
        if (g1m >= 0 && warp < 11) {
          const int wg = warp - 9, fb64 = (2 * g1m + rank) * 2 + wg;
          const uint32_t stg = wg == 0 ? sb + SM_DED : sb + ((G1_KB - 1) % NSTAGE) * SLOT;
          for (int c = 0; c < 3; c++) {
            mbar_wait(bars + 8 * (B_STG + wg * 3 + c), 0);
            tma2d_store(&P.m_ust, stg + c * 8192, fb64 * 64, g1n * 192 + c * 64);
          }
          TLREC(13 + wg);
          bulk_commit();
          if (wg == 1) { bulk_wait_read(); mbar_arrive(bars + 8 * (B_EMPTY + (G1_KB - 1) % NSTAGE)); }
          bulk_wait_all();
          if (wg == 0) TLREC(19);
          signal(C_U + g1n * 4 + (fb64 / G2_KB) * 2 + wg);
          TLREC(15 + wg);
        }
        if (g2m >= 0 && warp == 9) {
          await(C_Y, tag * 2 * N_CONV_CTA);
          asm volatile("fence.proxy.async;" ::: "memory");
          TLREC(8);
          mbar_expect_tx(bars + 8 * B_Y2, 18432);
          tma2d(sb + SM_DED, &P.m_y, g2m * 128, dk, bars + 8 * B_Y2);
          tma2d(sb + SM_DED + 9216, &P.m_y, g2m * 128 + 64, dk, bars + 8 * B_Y2);
        }
      }
    }
    TLEND();
  } else {
    asm volatile("setmaxnreg.inc.sync.aligned.u32 224;");
    const int wg = warp >> 2, w = warp & 3, g = lane >> 2, t = lane & 3, wtid = tid & 127;
    const bool elect = w == 0 && lane == 0;
    if (p0 >= 0) {
      float c[36];
      float s0 = 0.f, s1 = 0.f;
#pragma unroll
      for (int i = 0; i < 18; i++) { c[2 * i] = bf_lo(xr[i]); c[2 * i + 1] = bf_hi(xr[i]); s0 += c[2 * i]; s1 += c[2 * i + 1]; }
      const float ml = (s0 + s1) * (1.0f / 36.0f);
      if (tid == 0 && ml != 123.456f) TLREC(28);
      s0 = 0.f; s1 = 0.f;
#pragma unroll
      for (int i = 0; i < 18; i++) { c[2 * i] -= ml; c[2 * i + 1] -= ml; s0 = fmaf(c[2 * i], c[2 * i], s0); s1 = fmaf(c[2 * i + 1], c[2 * i + 1], s1); }
      float m = ml, q = s0 + s1, n2 = 18.f;
#pragma unroll
      for (int o = 1; o < 16; o <<= 1) {
        const float mo = __shfl_xor_sync(0xffffffffu, m, o), qo = __shfl_xor_sync(0xffffffffu, q, o);
        const float dl = m - mo;
        q = fmaf(dl * dl, n2, q + qo);
        m = 0.5f * (m + mo);
        n2 *= 2.f;
      }
      const float var = q * (1.0f / 576.0f);
      float mb, rinv, mb2, rinv2;
      ln_finish(m, var, mb, rinv);
      ln_finish((m - mb) * rinv, var * rinv * rinv, mb2, rinv2);
      const float ca = rinv * rinv2, cb = fmaf(ml - mb, rinv, -mb2) * rinv2;
      uint2* dst = reinterpret_cast<uint2*>(g_h + (size_t)ln_row * D_) + (lane & 15);
#pragma unroll
      for (int j = 0; j < 9; j++)
        dst[16 * j] = make_uint2(pack_bf16(fmaf(c[4 * j], ca, cb), fmaf(c[4 * j + 1], ca, cb)), pack_bf16(fmaf(c[4 * j + 2], ca, cb), fmaf(c[4 * j + 3], ca, cb)));
      if ((lane & 15) == 0) g_stats[ln_row] = make_float4(mb, rinv, 0.f, 0.f);
      bar_sync(2, 256);
      if (tid == 0) { TLREC(29); signal(C_H); TLREC(1); }
      __syncwarp();
    }
    asm volatile("barrier.cluster.wait.aligned;" ::: "memory");
    const uint64_t da0 = make_desc(sb + wg * 8192, 8192, 1024, 1);
    if (g1m >= 0) {
      const int frow = ((2 * g1m + rank) * 2 + wg) * 64 + w * 16 + g;
      const float hb0 = 0.5f * __bfloat162float(P.b1[frow]), hb1 = 0.5f * __bfloat162float(P.b1[frow + 8]);
      const uint64_t db0 = make_desc(sb + 16384, 8192, 1024, 1);
      float acc[96];
      Ring r{0, 0};
      uint32_t prev = 0;
      auto step = [&](int first, bool release) {
        mbar_wait(bars + 8 * (B_FULL + r.s), r.ph);
        const uint64_t da = da0 + r.s * (SLOT >> 4), db = db0 + r.s * (SLOT >> 4);
        wg_fence();
        wgmma_ss_n192_t11(acc, da, db, !first);
#pragma unroll
        for (int k = 1; k < 4; k++) wgmma_ss_n192_t11(acc, da + k * 128, db + k * 128, 1);
        wg_commit();
        if (release) { wg_wait<1>(); if (elect) mbar_arrive(bars + 8 * (B_EMPTY + prev)); }
        prev = r.s;
        r.next();
      };
      step(1, false);
      if (tid == 0) TLREC(3);
#pragma unroll 1
      for (int kb = 1; kb < G1_KB - G1_TAIL; kb++) step(0, true);
      if (elect) TLREC(20 + wg);
      if (wg == 1) {
        wg_wait<0>();
        if (elect) mbar_arrive(bars + 8 * (B_EMPTY + prev));
        bar_sync(5, 256);
      }
      step(0, wg == 0);
#pragma unroll 1
      for (int kb = G1_KB - G1_TAIL + 1; kb < G1_KB - 1; kb++) step(0, true);
      step(0, false);
      if (wg == 0) bar_arrive(5, 256);
      wg_wait<1>();
      if (elect) mbar_arrive(bars + 8 * (B_EMPTY + (G1_KB - 2) % NSTAGE));
      wg_wait<0>();
      pin_regs<96>(acc);
      if (elect) TLREC(4 + wg);
      if (wg == 0) { if (elect) mbar_arrive(bars + 8 * (B_EMPTY + (G1_KB - 1) % NSTAGE)); bar_arrive(6, 256); }
      else bar_sync(6, 256);
      const uint32_t stg = wg == 0 ? sb + SM_DED : sb + ((G1_KB - 1) % NSTAGE) * SLOT;
      const uint32_t sa = stg + ((lane >> 4) * 8 + (lane & 7)) * 128 + (((2 * w + ((lane >> 3) & 1)) ^ (lane & 7)) << 4);
#pragma unroll
      for (int c = 0; c < 3; c++) {
        mbar_wait(bars + 8 * B_XFULL, 1);
#pragma unroll
        for (int q = 8 * c; q < 8 * c + 8; q += 2) {
          uint32_t pk[4];
#pragma unroll
          for (int i = 0; i < 4; i++) {
            const float hb = (i & 1) ? hb1 : hb0;
            pk[i] = pack_bf16(gelu_half(fmaf(acc[4 * q + 2 * i], 0.5f, hb)), gelu_half(fmaf(acc[4 * q + 2 * i + 1], 0.5f, hb)));
          }
          stsm4t(sa + q * 1024, pk[0], pk[1], pk[2], pk[3]);
        }
        fence_async_smem();
        __syncwarp();
        if (lane == 0) mbar_arrive(bars + 8 * (B_STG + wg * 3 + c));
      }
    } else {
      const uint32_t red = wg == 0 ? sb + SM_DED : sb + CV_RED1;
      if (wtid < 8 * CV_NSLOT / 2) sts32(sb + (2 * (wtid >> 3) + wg) * CV_SLOT + CV_KOFF + (wtid & 7) * 4, 0);
      sts32(red + w * CV_REDW + lane * 4, 0);
      bar_sync(3 + wg, 128);
      const uint32_t ko = sb + CV_KOFF + (8 * w + g + t + 1) * 4;
      const uint32_t wr = red + w * CV_REDW + (8 * (3 - t + w) + g) * 4;
      const uint32_t dm0 = (w == 0 && g + t == 7) ? 0xffffu : 0u, dm2 = (w == 0 && g + t == 3) ? 0xffffu : 0u;
      uint32_t a[64];
      uint32_t dd = __bfloat16_as_ushort(P.ssm_D[conv_channel(cvc, wg)]);
      mbar_wait(bars + 8 * (B_CFULL + wg), 0);
      if (tid == 0) TLREC(17);
#define LDA(j, base) { a[2 * (j)] = lds32((base) + ((j) >> 1) * 256 + ((j) & 1) * 16); a[2 * (j) + 1] = lds32((base) + ((j) >> 1) * 256 + ((j) & 1) * 16 + 128); }
#pragma unroll
      for (int j = 0; j < 32; j++) LDA(j, ko + wg * CV_SLOT)
      if (wg == 1) bar_arrive(5, 256);
#pragma unroll 1
      for (int i = wg; i < n_conv; i += 2) {
        const int s = i % CV_NSLOT;
        const int in = i + 2 < n_conv ? i + 2 : i, sn = in % CV_NSLOT;
        const uint64_t db = make_desc(sb + s * CV_SLOT, 4096, 128, 0);
        a[0] = badd2(a[0], dd & dm0); a[2] = badd2(a[2], dd & dm2);
        dd = __bfloat16_as_ushort(P.ssm_D[conv_channel(cvc, in)]);
        float acc[128];
        bar_sync(5 + wg, 256);
        wg_fence();
        wgmma_rs_n256(acc, a, db, 0);
        wgmma_rs_n240(acc, a + 4, db + 16, 1);
        wgmma_rs_n224(acc, a + 8, db + 32, 1);
        wgmma_rs_n208(acc, a + 12, db + 48, 1);
        wgmma_rs_n192(acc, a + 16, db + 64, 1);
        wgmma_rs_n176(acc, a + 20, db + 80, 1);
        wgmma_rs_n160(acc, a + 24, db + 96, 1);
        wgmma_rs_n144(acc, a + 28, db + 112, 1);
        wgmma_rs_n128(acc, a + 32, db + 128, 1);
        wgmma_rs_n112(acc, a + 36, db + 144, 1);
        wgmma_rs_n96(acc, a + 40, db + 160, 1);
        wgmma_rs_n80(acc, a + 44, db + 176, 1);
        wgmma_rs_n64(acc, a + 48, db + 192, 1);
        wgmma_rs_n48(acc, a + 52, db + 208, 1);
        wgmma_rs_n32(acc, a + 56, db + 224, 1);
        wgmma_rs_n16(acc, a + 60, db + 240, 1);
        wg_commit();
        if (i + 1 < n_conv) bar_arrive(5 + (wg ^ 1), 256);
        wg_wait<0>();
        pin_regs<128>(acc);
        if (lane == 0) mbar_arrive(bars + 8 * (B_CEMPTY + s));
        mbar_wait(bars + 8 * (B_CFULL + sn), (in / CV_NSLOT) & 1);
        const uint32_t ka = ko + sn * CV_SLOT;
#pragma unroll
        for (int j = 0; j < 32; j++) {
          const int q = 31 - j;
          if (j < 24) LDA(j, ka)
          sts32(wr + j * 128, q == 31 ? pack_bf16(acc[124], acc[125]) : pack_bf16(acc[4 * q] + acc[(4 * q + 6) & 127], acc[4 * q + 1] + acc[(4 * q + 7) & 127]));
        }
        bar_sync(3 + wg, 128);
        uint4 p[2][4];
#pragma unroll
        for (int c = 0; c < 2; c++)
#pragma unroll
          for (int x = 0; x < 4; x++) p[c][x] = lds128(red + x * CV_REDW + (wtid + 128 * c) * 16);
#pragma unroll
        for (int j = 24; j < 32; j++) LDA(j, ka)
        uint4* yo = reinterpret_cast<uint4*>(g_y + (size_t)conv_channel(cvc, i) * S_) + wtid;
#pragma unroll
        for (int c = 0; c < 2; c++)
          yo[128 * c] = make_uint4(sum4(p[c][0].x, p[c][1].x, p[c][2].x, p[c][3].x), sum4(p[c][0].y, p[c][1].y, p[c][2].y, p[c][3].y),
                                   sum4(p[c][0].z, p[c][1].z, p[c][2].z, p[c][3].z), sum4(p[c][0].w, p[c][1].w, p[c][2].w, p[c][3].w));
      }
#undef LDA
      fence_async_smem();
      bar_sync(3 + wg, 128);
      if (elect) {
        mbar_arrive(bars + 8 * B_EMPTY); mbar_arrive(bars + 8 * (B_EMPTY + 1));
        signal(C_Y);
        TLREC(20 + wg);
      }
      __syncwarp();
    }
    if (g2m >= 0) {
      const int srow = g2m * 128 + wg * 64 + w * 16 + g;
      const uint64_t db0 = make_desc(sb + 16384, 16, 1024, 1);
      float acc[72], acc2[36];
      Ring r{G1_KB % NSTAGE, (G1_KB / NSTAGE) & 1};
      uint32_t prev = 0;
      auto step = [&](int first) {
        mbar_wait(bars + 8 * (B_FULL + r.s), r.ph);
        const uint64_t da = da0 + r.s * (SLOT >> 4), db = db0 + r.s * (SLOT >> 4);
        wg_fence();
        wgmma_ss_n144_t10(acc, da, db, !first);
#pragma unroll
        for (int k = 1; k < 4; k++) wgmma_ss_n144_t10(acc, da + k * 128, db + k * 2, 1);
        wg_commit();
        if (!first) { wg_wait<1>(); if (elect) mbar_arrive(bars + 8 * (B_EMPTY + prev)); }
        prev = r.s;
        r.next();
      };
      step(1);
      if (tid == 0) TLREC(7);
      const float2 st0 = __ldcg(reinterpret_cast<const float2*>(g_stats + srow)), st1 = __ldcg(reinterpret_cast<const float2*>(g_stats + srow + 8));
      const float hb0 = 0.5f * __bfloat162float(P.b2[srow]), hb1 = 0.5f * __bfloat162float(P.b2[srow + 8]);
#pragma unroll 1
      for (int kb = 1; kb < G2_KB - G2_TAIL; kb++) step(0);
      if (elect) TLREC(30 + wg);
      const uint32_t xo = sb + ((XSLOT + 1 + (warp >> 1)) % NSTAGE) * SLOT + G2_BYTES + (warp & 1) * 2304;
      const uint32_t xa = xo + (lane & 15) * 144 + (lane >> 4) * 16;
      uint32_t xx[18], ss[18];
      auto prep = [&]() {
        mbar_wait(bars + 8 * B_XT, 0);
        mbar_wait(bars + 8 * B_Y2, 0);
        const uint32_t ya = sb + SM_DED + wg * 9216 + ((lane >> 4) * 8 + (lane & 7)) * 128 + (((2 * w + ((lane >> 3) & 1)) ^ (lane & 7)) << 4);
#pragma unroll
        for (int q = 0; q < 8; q += 2) { ldsm4(xx + 2 * q, xa + q * 16); ldsm4t(ss + 2 * q, ya + q * 1024); }
        ldsm2(xx + 16, xo + (lane & 15) * 144 + 128);
        ldsm2t(ss + 16, ya - (lane >> 4) * 1024 + 8 * 1024);
        const uint32_t m0 = pack_bf16(st0.x, st0.x), m1 = pack_bf16(st1.x, st1.x);
#pragma unroll
        for (int i = 0; i < 18; i++) ss[i] = bmul2(ln_apply(xx[i], (i & 1) ? m1 : m0, (i & 1) ? st1.y : st0.y), ss[i]);
      };
      if (wg == 1) {
        wg_wait<0>();
        if (elect) mbar_arrive(bars + 8 * (B_EMPTY + XSLOT));
        prep();
        bar_sync(5, 256);
      }
#pragma unroll
      for (int kb = G2_KB - G2_TAIL; kb < G2_KB; kb++) {
        const int p = G1_KB + kb, s = p % NSTAGE;
        mbar_wait(bars + 8 * (B_FULL + s), (p / NSTAGE) & 1);
        wg_fence();
#pragma unroll
        for (int k = 0; k < 4; k++) wgmma_ss_n72_t10(acc, da0 + s * (SLOT >> 4) + k * 128, db0 + s * (SLOT >> 4) + k * 2, 1);
        wg_commit();
        if (kb == G2_KB - G2_TAIL) { wg_wait<1>(); if (tid == 0) mbar_arrive(bars + 8 * (B_EMPTY + XSLOT)); }
      }
      bar_arrive(5 + wg, 256);
      wg_wait<0>();
      pin_regs<72>(acc);
      const uint32_t xz = sb + XSLOT * SLOT + wg * 18432 + wtid * 16;
      mbar_wait_cluster(bars + 8 * B_XRDY, 0);
      {
        const uint32_t rz = mapa(xz, rank ^ 1), rb = mapa(bars + 8 * (B_XFULL + wg), rank ^ 1);
#pragma unroll
        for (int q = 0; q < 9; q++)
          asm volatile("st.async.weak.shared::cluster.mbarrier::complete_tx::bytes.v4.f32 [%0], {%1,%2,%3,%4}, [%5];"
                       :: "r"(rz + q * 2048), "f"(acc[4 * q]), "f"(acc[4 * q + 1]), "f"(acc[4 * q + 2]), "f"(acc[4 * q + 3]), "r"(rb) : "memory");
      }
      if (wg == 0) prep();
      bar_sync(6 - wg, 256);
      wg_fence();
#pragma unroll
      for (int kb = G2_KB - G2_TAIL; kb < G2_KB; kb++) {
        const int s = (G1_KB + kb) % NSTAGE;
#pragma unroll
        for (int k = 0; k < 4; k++)
          wgmma_ss_n72_t10(acc2, da0 + s * (SLOT >> 4) + k * 128, db0 + s * (SLOT >> 4) + (9216 >> 4) + k * 2, kb != G2_KB - G2_TAIL || k != 0);
      }
      wg_commit();
      if (wg == 0) bar_arrive(5, 256);
      mbar_wait_cluster(bars + 8 * (B_XFULL + wg), 0);
#pragma unroll
      for (int q = 0; q < 9; q++) {
        const float4 pv = lds128f(xz + q * 2048);
        acc[36 + 4 * q] = fmaf(acc[36 + 4 * q] + pv.x, 0.5f, hb0); acc[37 + 4 * q] = fmaf(acc[37 + 4 * q] + pv.y, 0.5f, hb0);
        acc[38 + 4 * q] = fmaf(acc[38 + 4 * q] + pv.z, 0.5f, hb1); acc[39 + 4 * q] = fmaf(acc[39 + 4 * q] + pv.w, 0.5f, hb1);
      }
      wg_wait<0>();
      pin_regs<36>(acc2);
      if (elect) TLREC(9 + wg);
      uint32_t ob[18];
#pragma unroll
      for (int i = 0; i < 18; i++)
        ob[i] = bfma2(ss[i], pack_bf16(silu_half(fmaf(acc2[2 * i], 0.5f, acc[36 + 2 * i])), silu_half(fmaf(acc2[2 * i + 1], 0.5f, acc[37 + 2 * i]))), xx[i]);
#pragma unroll
      for (int q = 0; q < 8; q += 2) stsm4(xa + q * 16, ob[2 * q], ob[2 * q + 1], ob[2 * q + 2], ob[2 * q + 3]);
      stsm2(xo + (lane & 15) * 144 + 128, ob[16], ob[17]);
      fence_async_smem();
      __syncwarp();
      if (lane == 0) {
        tma2d_store(&P.m_out, xo, dk, srow);
        bulk_commit();
        bulk_wait_read();
      }
      if (elect) {
        TLREC(11 + wg);
        if (g1m == 0 && g1n == 0 && rank == 0 && wg == 0) st_flag(&g_epoch, tag);
      }
    }
    TLEND();
  }
}

typedef CUresult (*EncodeFn)(CUtensorMap*, CUtensorMapDataType, cuuint32_t, void*, const cuuint64_t*, const cuuint64_t*, const cuuint32_t*,
                             const cuuint32_t*, CUtensorMapInterleave, CUtensorMapSwizzle, CUtensorMapL2promotion, CUtensorMapFloatOOBfill);

void make_map(EncodeFn fn, CUtensorMap* m, const void* ptr, int rank, const cuuint64_t* dims, const cuuint64_t* strides, const cuuint32_t* box,
              CUtensorMapSwizzle sw) {
  const cuuint32_t es[3] = {1, 1, 1};
  fn(m, CU_TENSOR_MAP_DATA_TYPE_BFLOAT16, rank, const_cast<void*>(ptr), dims, strides, box, es, CU_TENSOR_MAP_INTERLEAVE_NONE, sw,
     CU_TENSOR_MAP_L2_PROMOTION_L2_256B, CU_TENSOR_MAP_FLOAT_OOB_FILL_NONE);
}

void make_roles(Roles& R) {
  int c1 = 0, ncv = 2, np0 = 0;
  for (int g = 0; g < 8; g++)
    for (int c = 0; c < 66; c++) {
      const int tp = (c + 62) % 66;
      int gg, idx;
      if (tp < 32) { gg = tp % 8; idx = tp / 8; }
      else if (tp < 60) { gg = 1 + (tp - 32) % 7; idx = 4 + (tp - 32) / 7; }
      else if (tp < 62) { gg = 6 + tp - 60; idx = 8; }
      else { gg = 0; idx = 4 + tp - 62; }
      if (gg != g) continue;
      if (idx < 8) { R.g2m[c] = (int8_t)(2 * g + idx / 4); R.g2n[c] = (int8_t)(idx % 4); R.p0[c] = (int8_t)np0++; }
      else { R.g2m[c] = -1; R.g2n[c] = 0; R.p0[c] = -1; }
      if (idx < (g < 2 ? 6 : 7)) { R.g1m[c] = (int8_t)(c1 / 3); R.g1n[c] = (int8_t)(c1 % 3); R.cv[c] = -1; c1++; }
      else { R.g1m[c] = -1; R.g1n[c] = 0; R.cv[c] = (int8_t)(idx == 8 ? tp - 60 : ncv++); }
    }
}

}

extern "C" void kernel_launch(void* const* d_in, const int* in_sizes, int n_in, void* d_out, int out_size) {
  static Params P;
  static const void* cached[4] = {nullptr, nullptr, nullptr, nullptr};
  if (cached[0] != d_in[7] || cached[1] != d_in[9] || cached[2] != d_out || cached[3] != d_in[0]) {
    void* fp = nullptr;
    cudaDriverEntryPointQueryResult qr;
    cudaGetDriverEntryPoint("cuTensorMapEncodeTiled", &fp, cudaEnableDefault, &qr);
    EncodeFn fn = (EncodeFn)fp;
    void *ph, *pu, *py;
    cudaGetSymbolAddress(&py, g_y);
    cudaGetSymbolAddress(&ph, g_h);
    cudaGetSymbolAddress(&pu, g_u);
    { cuuint64_t d[3] = {64, S_, F_ / 64}, s[2] = {F_ * 2, 128}; cuuint32_t b[3] = {64, 64, 2}; make_map(fn, &P.m_w1, d_in[7], 3, d, s, b, CU_TENSOR_MAP_SWIZZLE_128B); }
    { cuuint64_t d[3] = {64, S_, D_ / 64}, s[2] = {D_ * 2, 128}; cuuint32_t b[3] = {64, 64, 3}; make_map(fn, &P.m_h, ph, 3, d, s, b, CU_TENSOR_MAP_SWIZZLE_128B); }
    { cuuint64_t d[2] = {F_, D_}, s[1] = {F_ * 2}; cuuint32_t b[2] = {64, 64}; make_map(fn, &P.m_ust, pu, 2, d, s, b, CU_TENSOR_MAP_SWIZZLE_128B); }
    { cuuint64_t d[3] = {64, F_, S_ / 64}, s[2] = {S_ * 2, 128}; cuuint32_t b[3] = {64, 64, 2}; make_map(fn, &P.m_w2, d_in[9], 3, d, s, b, CU_TENSOR_MAP_SWIZZLE_128B); }
    { cuuint64_t d[2] = {F_, D_}, s[1] = {F_ * 2}; cuuint32_t b[2] = {64, 72}; make_map(fn, &P.m_uld, pu, 2, d, s, b, CU_TENSOR_MAP_SWIZZLE_128B); }
    { cuuint64_t d[2] = {D_, S_}, s[1] = {D_ * 2}; cuuint32_t b[2] = {72, 16}; make_map(fn, &P.m_out, d_out, 2, d, s, b, CU_TENSOR_MAP_SWIZZLE_NONE);
      make_map(fn, &P.m_x, d_in[0], 2, d, s, b, CU_TENSOR_MAP_SWIZZLE_NONE); }
    { cuuint64_t d[2] = {S_, D_}, s[1] = {S_ * 2}; cuuint32_t b[2] = {64, 72}; make_map(fn, &P.m_y, py, 2, d, s, b, CU_TENSOR_MAP_SWIZZLE_128B); }
    make_roles(P.roles);
    cudaFuncSetAttribute(fused_kernel, cudaFuncAttributeMaxDynamicSharedMemorySize, SM_TOTAL);
    cached[0] = d_in[7]; cached[1] = d_in[9]; cached[2] = d_out; cached[3] = d_in[0];
  }
  P.x = (const __nv_bfloat16*)d_in[0]; P.k = (const __nv_bfloat16*)d_in[1]; P.v = (const __nv_bfloat16*)d_in[2];
  P.shift_k = (const __nv_bfloat16*)d_in[3]; P.ssm_k = (const __nv_bfloat16*)d_in[4]; P.ssm_D = (const __nv_bfloat16*)d_in[5];
  P.b1 = (const __nv_bfloat16*)d_in[8]; P.b2 = (const __nv_bfloat16*)d_in[10];
  fused_kernel<<<132, 384, SM_TOTAL>>>(P);
}
```

```cpp
#include <cuda_runtime.h>
#include <cuda.h>
#include <cuda_bf16.h>
#include <stdint.h>

namespace {

constexpr int S_ = 2048, D_ = 576, F_ = 4608;
constexpr int NSTAGE = 5, SLOT = 40960;
constexpr int G1_KB = 32, G2_KB = 36;
constexpr int G1_BYTES = 40960, G2_BYTES = 16384 + 18432;
constexpr int N_CONV_CTA = 24, N_SHORT = 22, N_LONG_EXTRA = 12;
static_assert(N_CONV_CTA * N_SHORT + 4 * N_LONG_EXTRA == D_, "conv split");
constexpr int KV_ROUNDS = 6;
#define GELU_DIST 6
#define G1T 5
constexpr int G1_TAIL = G1T, G2_TAIL = 4;

constexpr int SM_DED = NSTAGE * SLOT;
constexpr int SM_BAR = SM_DED + 24576;
constexpr int SM_TOTAL = SM_BAR + 256 + 1024;
constexpr int CV_NSLOT = 4, CV_KOFF = 8192, CV_SLOT = 8192 + 4224;
constexpr int CV_REDW = 2112 * 2, CV_RED1 = CV_NSLOT * CV_SLOT;
static_assert(CV_RED1 + 4 * CV_REDW <= 2 * SLOT, "conv overlay");
constexpr int XSLOT = (G1_KB + G2_KB) % NSTAGE;
constexpr int B_FULL = 0, B_EMPTY = NSTAGE, B_CFULL = 2 * NSTAGE, B_STG = B_CFULL + CV_NSLOT  , B_CEMPTY = B_STG,
              B_XRDY = B_STG + 6, B_XFULL = B_XRDY + 1  , B_XT = B_XFULL + 2, B_Y2 = B_XT + 1;
constexpr int C_H = 0, C_KV = 1, C_U = C_KV + KV_ROUNDS  , C_Y = C_U + 12, C_COUNT = C_Y + 1;

struct Role {
  int8_t g1m;
  int8_t g1n;
  int8_t g2m;
  int8_t g2n;
};
struct Roles { Role r[66]; };

struct Params {
  const __nv_bfloat16 *x, *k, *v, *shift_k, *ssm_k, *ssm_D, *b1, *b2;
  Roles roles;
  CUtensorMap m_w1, m_h, m_ust, m_w2, m_uld, m_out, m_x, m_y;
};

__device__ __align__(1024) __nv_bfloat16 g_h[S_ * D_];
__device__ __align__(1024) __nv_bfloat16 g_ub[D_ * 4096];
__device__ __align__(1024) __nv_bfloat16 g_y[D_ * S_];
__device__ __align__(1024) __nv_bfloat16 g_u[D_ * F_];
__device__ __align__(128) float4 g_stats[S_];
__device__ __align__(128) uint32_t g_cnt[C_COUNT * 32];
__device__ __align__(128) uint32_t g_epoch;
#define TLREC(i) do { } while (0)
#define TLEND() do { } while (0)

__device__ __forceinline__ uint32_t smem_u32(const void* p) { return (uint32_t)__cvta_generic_to_shared(p); }
__device__ __forceinline__ void mbar_init(uint32_t bar, uint32_t cnt) { asm volatile("mbarrier.init.shared::cta.b64 [%0], %1;" :: "r"(bar), "r"(cnt) : "memory"); }
__device__ __forceinline__ void mbar_expect_tx(uint32_t bar, uint32_t bytes) { asm volatile("mbarrier.arrive.expect_tx.shared::cta.b64 _, [%0], %1;" :: "r"(bar), "r"(bytes) : "memory"); }
__device__ __forceinline__ void mbar_arrive(uint32_t bar) { asm volatile("mbarrier.arrive.shared::cta.b64 _, [%0];" :: "r"(bar) : "memory"); }
__device__ __forceinline__ uint32_t mapa(uint32_t addr, uint32_t cta) { uint32_t r; asm volatile("mapa.shared::cluster.u32 %0, %1, %2;" : "=r"(r) : "r"(addr), "r"(cta)); return r; }
__device__ __forceinline__ void mbar_arrive_remote(uint32_t rbar) { asm volatile("mbarrier.arrive.shared::cluster.b64 _, [%0];" :: "r"(rbar) : "memory"); }
__device__ __forceinline__ void mbar_wait(uint32_t bar, uint32_t parity) {
  asm volatile("{\n .reg .pred p;\n .reg .u32 c;\n mov.u32 c, 0;\n"
               "W_%=:\n mbarrier.try_wait.parity.shared::cta.b64 p, [%0], %1;\n @p bra D_%=;\n"
               " add.u32 c, c, 1;\n setp.lt.u32 p, c, 2000000;\n @p bra W_%=;\n trap;\n D_%=:\n }" :: "r"(bar), "r"(parity) : "memory");
}
__device__ __forceinline__ void mbar_wait_cluster(uint32_t bar, uint32_t parity) {
  asm volatile("{\n .reg .pred p;\n .reg .u32 c;\n mov.u32 c, 0;\n"
               "W_%=:\n mbarrier.try_wait.parity.acquire.cluster.shared::cta.b64 p, [%0], %1;\n @p bra D_%=;\n"
               " add.u32 c, c, 1;\n setp.lt.u32 p, c, 2000000;\n @p bra W_%=;\n trap;\n D_%=:\n }" :: "r"(bar), "r"(parity) : "memory");
}
__device__ __forceinline__ void tma2d(uint32_t dst, const CUtensorMap* m, int c0, int c1, uint32_t bar) {
  asm volatile("cp.async.bulk.tensor.2d.shared::cluster.global.mbarrier::complete_tx::bytes [%0], [%1, {%3, %4}], [%2];"
               :: "r"(dst), "l"(m), "r"(bar), "r"(c0), "r"(c1) : "memory");
}
__device__ __forceinline__ void tma3d(uint32_t dst, const CUtensorMap* m, int c0, int c1, int c2, uint32_t bar) {
  asm volatile("cp.async.bulk.tensor.3d.shared::cluster.global.mbarrier::complete_tx::bytes [%0], [%1, {%3, %4, %5}], [%2];"
               :: "r"(dst), "l"(m), "r"(bar), "r"(c0), "r"(c1), "r"(c2) : "memory");
}
__device__ __forceinline__ void tma2d_store(const CUtensorMap* m, uint32_t src, int c0, int c1) {
  asm volatile("cp.async.bulk.tensor.2d.global.shared::cta.bulk_group [%0, {%2, %3}], [%1];" :: "l"(m), "r"(src), "r"(c0), "r"(c1) : "memory");
}
__device__ __forceinline__ void bulk_load(uint32_t dst, const void* src, uint32_t bytes, uint32_t bar) {
  asm volatile("cp.async.bulk.shared::cluster.global.mbarrier::complete_tx::bytes [%0], [%1], %2, [%3];" :: "r"(dst), "l"(src), "r"(bytes), "r"(bar) : "memory");
}
__device__ __forceinline__ void bulk_commit() { asm volatile("cp.async.bulk.commit_group;" ::: "memory"); }
__device__ __forceinline__ void bulk_wait_all() { asm volatile("cp.async.bulk.wait_group 0;" ::: "memory"); }
__device__ __forceinline__ void bulk_wait_read() { asm volatile("cp.async.bulk.wait_group.read 0;" ::: "memory"); }
__device__ __forceinline__ void fence_async_smem() { asm volatile("fence.proxy.async.shared::cta;" ::: "memory"); }
__device__ __forceinline__ void fence_async_global() { asm volatile("fence.proxy.async.global;" ::: "memory"); }
__device__ __forceinline__ void st_flag(uint32_t* p, uint32_t v) { asm volatile("st.relaxed.gpu.global.u32 [%0], %1;" :: "l"(p), "r"(v) : "memory"); }
__device__ __forceinline__ uint32_t ld_flag(const uint32_t* p) { uint32_t v; asm volatile("ld.relaxed.gpu.global.u32 %0, [%1];" : "=r"(v) : "l"(p) : "memory"); return v; }
__device__ __forceinline__ void signal(int c) { asm volatile("red.release.gpu.global.add.u32 [%0], 1;" :: "l"(g_cnt + c * 32) : "memory"); }
template <bool SLOW = false> __device__ __forceinline__ void await(int c, uint32_t target) {
  uint32_t n = 0;
  while (true) {
    uint32_t v; asm volatile("ld.acquire.gpu.global.u32 %0, [%1];" : "=r"(v) : "l"(g_cnt + c * 32) : "memory");
    if ((int32_t)(v - target) >= 0) break;
    if (SLOW) __nanosleep(300);
    if (++n > 4000000u) __trap();
  }
}
__device__ __forceinline__ void bar_sync(int id, int n) { asm volatile("bar.sync %0, %1;" :: "r"(id), "r"(n) : "memory"); }
__device__ __forceinline__ void bar_arrive(int id, int n) { asm volatile("bar.arrive %0, %1;" :: "r"(id), "r"(n) : "memory"); }
__device__ __forceinline__ void wg_fence() { asm volatile("wgmma.fence.sync.aligned;" ::: "memory"); }
__device__ __forceinline__ void wg_commit() { asm volatile("wgmma.commit_group.sync.aligned;" ::: "memory"); }
template <int N> __device__ __forceinline__ void wg_wait() { asm volatile("wgmma.wait_group.sync.aligned %0;" :: "n"(N) : "memory"); }
template <int N> __device__ __forceinline__ void pin_regs(float* a) {
#pragma unroll
  for (int i = 0; i < N; i++) asm volatile("" : "+f"(a[i]) :: "memory");
}
__device__ __forceinline__ uint64_t make_desc(uint32_t addr, uint32_t lbo, uint32_t sbo, uint32_t swz) {
  return (uint64_t)((addr & 0x3FFFF) >> 4) | ((uint64_t)(lbo >> 4) << 16) | ((uint64_t)(sbo >> 4) << 32) | ((uint64_t)swz << 62);
}
__device__ __forceinline__ uint32_t pack_bf16(float lo, float hi) { uint32_t r; asm("cvt.rn.bf16x2.f32 %0, %1, %2;" : "=r"(r) : "f"(hi), "f"(lo)); return r; }
__device__ __forceinline__ float bf_lo(uint32_t p) { return __uint_as_float(p << 16); }
__device__ __forceinline__ float bf_hi(uint32_t p) { return __uint_as_float(p & 0xffff0000u); }
__device__ __forceinline__ float round_bf16(float v) { return bf_lo(pack_bf16(v, 0.f)); }
__device__ __forceinline__ uint32_t bmul2(uint32_t a, uint32_t b) { uint32_t r; asm("mul.rn.bf16x2 %0, %1, %2;" : "=r"(r) : "r"(a), "r"(b)); return r; }
__device__ __forceinline__ uint32_t badd2(uint32_t a, uint32_t b) { uint32_t r; asm("add.rn.bf16x2 %0, %1, %2;" : "=r"(r) : "r"(a), "r"(b)); return r; }
__device__ __forceinline__ uint32_t bfma2(uint32_t a, uint32_t b, uint32_t c) { uint32_t r; asm("fma.rn.bf16x2 %0, %1, %2, %3;" : "=r"(r) : "r"(a), "r"(b), "r"(c)); return r; }
__device__ __forceinline__ uint32_t bsub2(uint32_t a, uint32_t b) { uint32_t r; asm("sub.rn.bf16x2 %0, %1, %2;" : "=r"(r) : "r"(a), "r"(b)); return r; }
__device__ __forceinline__ float tanh_fast(float v) { float r; asm("tanh.approx.f32 %0, %1;" : "=f"(r) : "f"(v)); return r; }
__device__ __forceinline__ float gelu_half(float h) {
  return fmaf(h, tanh_fast(h * fmaf(h * h, 8.0f * 0.7978845608028654f * 0.044715f, 2.0f * 0.7978845608028654f)), h);
}
__device__ __forceinline__ float silu_half(float h) { return fmaf(h, tanh_fast(h), h); }
__device__ __forceinline__ uint32_t ldg32(const void* p) { uint32_t v; asm volatile("ld.global.nc.u32 %0, [%1];" : "=r"(v) : "l"(p)); return v; }
__device__ __forceinline__ uint32_t lds32(uint32_t a) { uint32_t v; asm volatile("ld.shared.u32 %0, [%1];" : "=r"(v) : "r"(a) : "memory"); return v; }
__device__ __forceinline__ float4 lds128f(uint32_t a) { float4 v; asm volatile("ld.shared.v4.f32 {%0,%1,%2,%3}, [%4];" : "=f"(v.x), "=f"(v.y), "=f"(v.z), "=f"(v.w) : "r"(a) : "memory"); return v; }
__device__ __forceinline__ uint4 lds128(uint32_t a) { uint4 v; asm volatile("ld.shared.v4.u32 {%0,%1,%2,%3}, [%4];" : "=r"(v.x), "=r"(v.y), "=r"(v.z), "=r"(v.w) : "r"(a) : "memory"); return v; }
__device__ __forceinline__ void sts32(uint32_t a, uint32_t v) { asm volatile("st.shared.u32 [%0], %1;" :: "r"(a), "r"(v) : "memory"); }
__device__ __forceinline__ void ldsm4(uint32_t* r, uint32_t a) {
  asm volatile("ldmatrix.sync.aligned.m8n8.x4.shared.b16 {%0,%1,%2,%3}, [%4];" : "=r"(r[0]), "=r"(r[1]), "=r"(r[2]), "=r"(r[3]) : "r"(a) : "memory");
}
__device__ __forceinline__ void ldsm2(uint32_t* r, uint32_t a) {
  asm volatile("ldmatrix.sync.aligned.m8n8.x2.shared.b16 {%0,%1}, [%2];" : "=r"(r[0]), "=r"(r[1]) : "r"(a) : "memory");
}
__device__ __forceinline__ void ldsm4t(uint32_t* r, uint32_t a) {
  asm volatile("ldmatrix.sync.aligned.m8n8.x4.trans.shared.b16 {%0,%1,%2,%3}, [%4];" : "=r"(r[0]), "=r"(r[1]), "=r"(r[2]), "=r"(r[3]) : "r"(a) : "memory");
}
__device__ __forceinline__ void ldsm2t(uint32_t* r, uint32_t a) {
  asm volatile("ldmatrix.sync.aligned.m8n8.x2.trans.shared.b16 {%0,%1}, [%2];" : "=r"(r[0]), "=r"(r[1]) : "r"(a) : "memory");
}
__device__ __forceinline__ void stsm4(uint32_t a, uint32_t r0, uint32_t r1, uint32_t r2, uint32_t r3) {
  asm volatile("stmatrix.sync.aligned.m8n8.x4.shared.b16 [%0], {%1,%2,%3,%4};" :: "r"(a), "r"(r0), "r"(r1), "r"(r2), "r"(r3) : "memory");
}
__device__ __forceinline__ void stsm2(uint32_t a, uint32_t r0, uint32_t r1) {
  asm volatile("stmatrix.sync.aligned.m8n8.x2.shared.b16 [%0], {%1,%2};" :: "r"(a), "r"(r0), "r"(r1) : "memory");
}
__device__ __forceinline__ void stsm4t(uint32_t a, uint32_t r0, uint32_t r1, uint32_t r2, uint32_t r3) {
  asm volatile("stmatrix.sync.aligned.m8n8.x4.trans.shared.b16 [%0], {%1,%2,%3,%4};" :: "r"(a), "r"(r0), "r"(r1), "r"(r2), "r"(r3) : "memory");
}

__device__ __forceinline__ void wgmma_ss_n144_t10(float* d, uint64_t da, uint64_t db, int sd) {
  asm volatile("{ .reg .pred p; setp.ne.b32 p, %74, 0;\n"
      "wgmma.mma_async.sync.aligned.m64n144k16.f32.bf16.bf16 {"
      "%0,%1,%2,%3,%4,%5,%6,%7,%8,%9,%10,%11,%12,%13,%14,%15,"
      "%16,%17,%18,%19,%20,%21,%22,%23,%24,%25,%26,%27,%28,%29,%30,%31,"
      "%32,%33,%34,%35,%36,%37,%38,%39,%40,%41,%42,%43,%44,%45,%46,%47,"
      "%48,%49,%50,%51,%52,%53,%54,%55,%56,%57,%58,%59,%60,%61,%62,%63,"
      "%64,%65,%66,%67,%68,%69,%70,%71"
      "}, %72, %73, p, 1, 1, 1, 0; }"
    : "+f"(d[0]), "+f"(d[1]), "+f"(d[2]), "+f"(d[3]), "+f"(d[4]), "+f"(d[5]), "+f"(d[6]), "+f"(d[7]),
      "+f"(d[8]), "+f"(d[9]), "+f"(d[10]), "+f"(d[11]), "+f"(d[12]), "+f"(d[13]), "+f"(d[14]), "+f"(d[15]),
      "+f"(d[16]), "+f"(d[17]), "+f"(d[18]), "+f"(d[19]), "+f"(d[20]), "+f"(d[21]), "+f"(d[22]), "+f"(d[23]),
      "+f"(d[24]), "+f"(d[25]), "+f"(d[26]), "+f"(d[27]), "+f"(d[28]), "+f"(d[29]), "+f"(d[30]), "+f"(d[31]),
      "+f"(d[32]), "+f"(d[33]), "+f"(d[34]), "+f"(d[35]), "+f"(d[36]), "+f"(d[37]), "+f"(d[38]), "+f"(d[39]),
      "+f"(d[40]), "+f"(d[41]), "+f"(d[42]), "+f"(d[43]), "+f"(d[44]), "+f"(d[45]), "+f"(d[46]), "+f"(d[47]),
      "+f"(d[48]), "+f"(d[49]), "+f"(d[50]), "+f"(d[51]), "+f"(d[52]), "+f"(d[53]), "+f"(d[54]), "+f"(d[55]),
      "+f"(d[56]), "+f"(d[57]), "+f"(d[58]), "+f"(d[59]), "+f"(d[60]), "+f"(d[61]), "+f"(d[62]), "+f"(d[63]),
      "+f"(d[64]), "+f"(d[65]), "+f"(d[66]), "+f"(d[67]), "+f"(d[68]), "+f"(d[69]), "+f"(d[70]), "+f"(d[71])
    : "l"(da), "l"(db), "r"(sd));
}

__device__ __forceinline__ void wgmma_ss_n192_t11(float* d, uint64_t da, uint64_t db, int sd) {
  asm volatile("{ .reg .pred p; setp.ne.b32 p, %98, 0;\n"
      "wgmma.mma_async.sync.aligned.m64n192k16.f32.bf16.bf16 {"
      "%0,%1,%2,%3,%4,%5,%6,%7,%8,%9,%10,%11,%12,%13,%14,%15,"
      "%16,%17,%18,%19,%20,%21,%22,%23,%24,%25,%26,%27,%28,%29,%30,%31,"
      "%32,%33,%34,%35,%36,%37,%38,%39,%40,%41,%42,%43,%44,%45,%46,%47,"
      "%48,%49,%50,%51,%52,%53,%54,%55,%56,%57,%58,%59,%60,%61,%62,%63,"
      "%64,%65,%66,%67,%68,%69,%70,%71,%72,%73,%74,%75,%76,%77,%78,%79,"
      "%80,%81,%82,%83,%84,%85,%86,%87,%88,%89,%90,%91,%92,%93,%94,%95"
      "}, %96, %97, p, 1, 1, 1, 1; }"
    : "+f"(d[0]), "+f"(d[1]), "+f"(d[2]), "+f"(d[3]), "+f"(d[4]), "+f"(d[5]), "+f"(d[6]), "+f"(d[7]),
      "+f"(d[8]), "+f"(d[9]), "+f"(d[10]), "+f"(d[11]), "+f"(d[12]), "+f"(d[13]), "+f"(d[14]), "+f"(d[15]),
      "+f"(d[16]), "+f"(d[17]), "+f"(d[18]), "+f"(d[19]), "+f"(d[20]), "+f"(d[21]), "+f"(d[22]), "+f"(d[23]),
      "+f"(d[24]), "+f"(d[25]), "+f"(d[26]), "+f"(d[27]), "+f"(d[28]), "+f"(d[29]), "+f"(d[30]), "+f"(d[31]),
      "+f"(d[32]), "+f"(d[33]), "+f"(d[34]), "+f"(d[35]), "+f"(d[36]), "+f"(d[37]), "+f"(d[38]), "+f"(d[39]),
      "+f"(d[40]), "+f"(d[41]), "+f"(d[42]), "+f"(d[43]), "+f"(d[44]), "+f"(d[45]), "+f"(d[46]), "+f"(d[47]),
      "+f"(d[48]), "+f"(d[49]), "+f"(d[50]), "+f"(d[51]), "+f"(d[52]), "+f"(d[53]), "+f"(d[54]), "+f"(d[55]),
      "+f"(d[56]), "+f"(d[57]), "+f"(d[58]), "+f"(d[59]), "+f"(d[60]), "+f"(d[61]), "+f"(d[62]), "+f"(d[63]),
      "+f"(d[64]), "+f"(d[65]), "+f"(d[66]), "+f"(d[67]), "+f"(d[68]), "+f"(d[69]), "+f"(d[70]), "+f"(d[71]),
      "+f"(d[72]), "+f"(d[73]), "+f"(d[74]), "+f"(d[75]), "+f"(d[76]), "+f"(d[77]), "+f"(d[78]), "+f"(d[79]),
      "+f"(d[80]), "+f"(d[81]), "+f"(d[82]), "+f"(d[83]), "+f"(d[84]), "+f"(d[85]), "+f"(d[86]), "+f"(d[87]),
      "+f"(d[88]), "+f"(d[89]), "+f"(d[90]), "+f"(d[91]), "+f"(d[92]), "+f"(d[93]), "+f"(d[94]), "+f"(d[95])
    : "l"(da), "l"(db), "r"(sd));
}

__device__ __forceinline__ void wgmma_ss_n72_t10(float* d, uint64_t da, uint64_t db, int sd) {
  asm volatile("{ .reg .pred p; setp.ne.b32 p, %38, 0;\n"
      "wgmma.mma_async.sync.aligned.m64n72k16.f32.bf16.bf16 {"
      "%0,%1,%2,%3,%4,%5,%6,%7,%8,%9,%10,%11,%12,%13,%14,%15,"
      "%16,%17,%18,%19,%20,%21,%22,%23,%24,%25,%26,%27,%28,%29,%30,%31,"
      "%32,%33,%34,%35"
      "}, %36, %37, p, 1, 1, 1, 0; }"
    : "+f"(d[0]), "+f"(d[1]), "+f"(d[2]), "+f"(d[3]), "+f"(d[4]), "+f"(d[5]), "+f"(d[6]), "+f"(d[7]),
      "+f"(d[8]), "+f"(d[9]), "+f"(d[10]), "+f"(d[11]), "+f"(d[12]), "+f"(d[13]), "+f"(d[14]), "+f"(d[15]),
      "+f"(d[16]), "+f"(d[17]), "+f"(d[18]), "+f"(d[19]), "+f"(d[20]), "+f"(d[21]), "+f"(d[22]), "+f"(d[23]),
      "+f"(d[24]), "+f"(d[25]), "+f"(d[26]), "+f"(d[27]), "+f"(d[28]), "+f"(d[29]), "+f"(d[30]), "+f"(d[31]),
      "+f"(d[32]), "+f"(d[33]), "+f"(d[34]), "+f"(d[35])
    : "l"(da), "l"(db), "r"(sd));
}

__device__ __forceinline__ void wgmma_rs_n16(float* d, const uint32_t* a, uint64_t db, int sd) {
  asm volatile("{ .reg .pred p; setp.ne.b32 p, %13, 0;\n"
      "wgmma.mma_async.sync.aligned.m64n16k16.f32.bf16.bf16 {"
      "%0,%1,%2,%3,%4,%5,%6,%7"
      "}, {%8,%9,%10,%11}, %12, p, 1, 1, 0; }"
    : "+f"(d[0]), "+f"(d[1]), "+f"(d[2]), "+f"(d[3]), "+f"(d[4]), "+f"(d[5]), "+f"(d[6]), "+f"(d[7])
    : "r"(a[0]), "r"(a[1]), "r"(a[2]), "r"(a[3]), "l"(db), "r"(sd));
}

__device__ __forceinline__ void wgmma_rs_n32(float* d, const uint32_t* a, uint64_t db, int sd) {
  asm volatile("{ .reg .pred p; setp.ne.b32 p, %21, 0;\n"
      "wgmma.mma_async.sync.aligned.m64n32k16.f32.bf16.bf16 {"
      "%0,%1,%2,%3,%4,%5,%6,%7,%8,%9,%10,%11,%12,%13,%14,%15"
      "}, {%16,%17,%18,%19}, %20, p, 1, 1, 0; }"
    : "+f"(d[0]), "+f"(d[1]), "+f"(d[2]), "+f"(d[3]), "+f"(d[4]), "+f"(d[5]), "+f"(d[6]), "+f"(d[7]),
      "+f"(d[8]), "+f"(d[9]), "+f"(d[10]), "+f"(d[11]), "+f"(d[12]), "+f"(d[13]), "+f"(d[14]), "+f"(d[15])
    : "r"(a[0]), "r"(a[1]), "r"(a[2]), "r"(a[3]), "l"(db), "r"(sd));
}

__device__ __forceinline__ void wgmma_rs_n48(float* d, const uint32_t* a, uint64_t db, int sd) {
  asm volatile("{ .reg .pred p; setp.ne.b32 p, %29, 0;\n"
      "wgmma.mma_async.sync.aligned.m64n48k16.f32.bf16.bf16 {"
      "%0,%1,%2,%3,%4,%5,%6,%7,%8,%9,%10,%11,%12,%13,%14,%15,"
      "%16,%17,%18,%19,%20,%21,%22,%23"
      "}, {%24,%25,%26,%27}, %28, p, 1, 1, 0; }"
    : "+f"(d[0]), "+f"(d[1]), "+f"(d[2]), "+f"(d[3]), "+f"(d[4]), "+f"(d[5]), "+f"(d[6]), "+f"(d[7]),
      "+f"(d[8]), "+f"(d[9]), "+f"(d[10]), "+f"(d[11]), "+f"(d[12]), "+f"(d[13]), "+f"(d[14]), "+f"(d[15]),
      "+f"(d[16]), "+f"(d[17]), "+f"(d[18]), "+f"(d[19]), "+f"(d[20]), "+f"(d[21]), "+f"(d[22]), "+f"(d[23])
    : "r"(a[0]), "r"(a[1]), "r"(a[2]), "r"(a[3]), "l"(db), "r"(sd));
}

__device__ __forceinline__ void wgmma_rs_n64(float* d, const uint32_t* a, uint64_t db, int sd) {
  asm volatile("{ .reg .pred p; setp.ne.b32 p, %37, 0;\n"
      "wgmma.mma_async.sync.aligned.m64n64k16.f32.bf16.bf16 {"
      "%0,%1,%2,%3,%4,%5,%6,%7,%8,%9,%10,%11,%12,%13,%14,%15,"
      "%16,%17,%18,%19,%20,%21,%22,%23,%24,%25,%26,%27,%28,%29,%30,%31"
      "}, {%32,%33,%34,%35}, %36, p, 1, 1, 0; }"
    : "+f"(d[0]), "+f"(d[1]), "+f"(d[2]), "+f"(d[3]), "+f"(d[4]), "+f"(d[5]), "+f"(d[6]), "+f"(d[7]),
      "+f"(d[8]), "+f"(d[9]), "+f"(d[10]), "+f"(d[11]), "+f"(d[12]), "+f"(d[13]), "+f"(d[14]), "+f"(d[15]),
      "+f"(d[16]), "+f"(d[17]), "+f"(d[18]), "+f"(d[19]), "+f"(d[20]), "+f"(d[21]), "+f"(d[22]), "+f"(d[23]),
      "+f"(d[24]), "+f"(d[25]), "+f"(d[26]), "+f"(d[27]), "+f"(d[28]), "+f"(d[29]), "+f"(d[30]), "+f"(d[31])
    : "r"(a[0]), "r"(a[1]), "r"(a[2]), "r"(a[3]), "l"(db), "r"(sd));
}

__device__ __forceinline__ void wgmma_rs_n80(float* d, const uint32_t* a, uint64_t db, int sd) {
  asm volatile("{ .reg .pred p; setp.ne.b32 p, %45, 0;\n"
      "wgmma.mma_async.sync.aligned.m64n80k16.f32.bf16.bf16 {"
      "%0,%1,%2,%3,%4,%5,%6,%7,%8,%9,%10,%11,%12,%13,%14,%15,"
      "%16,%17,%18,%19,%20,%21,%22,%23,%24,%25,%26,%27,%28,%29,%30,%31,"
      "%32,%33,%34,%35,%36,%37,%38,%39"
      "}, {%40,%41,%42,%43}, %44, p, 1, 1, 0; }"
    : "+f"(d[0]), "+f"(d[1]), "+f"(d[2]), "+f"(d[3]), "+f"(d[4]), "+f"(d[5]), "+f"(d[6]), "+f"(d[7]),
      "+f"(d[8]), "+f"(d[9]), "+f"(d[10]), "+f"(d[11]), "+f"(d[12]), "+f"(d[13]), "+f"(d[14]), "+f"(d[15]),
      "+f"(d[16]), "+f"(d[17]), "+f"(d[18]), "+f"(d[19]), "+f"(d[20]), "+f"(d[21]), "+f"(d[22]), "+f"(d[23]),
      "+f"(d[24]), "+f"(d[25]), "+f"(d[26]), "+f"(d[27]), "+f"(d[28]), "+f"(d[29]), "+f"(d[30]), "+f"(d[31]),
      "+f"(d[32]), "+f"(d[33]), "+f"(d[34]), "+f"(d[35]), "+f"(d[36]), "+f"(d[37]), "+f"(d[38]), "+f"(d[39])
    : "r"(a[0]), "r"(a[1]), "r"(a[2]), "r"(a[3]), "l"(db), "r"(sd));
}

__device__ __forceinline__ void wgmma_rs_n96(float* d, const uint32_t* a, uint64_t db, int sd) {
  asm volatile("{ .reg .pred p; setp.ne.b32 p, %53, 0;\n"
      "wgmma.mma_async.sync.aligned.m64n96k16.f32.bf16.bf16 {"
      "%0,%1,%2,%3,%4,%5,%6,%7,%8,%9,%10,%11,%12,%13,%14,%15,"
      "%16,%17,%18,%19,%20,%21,%22,%23,%24,%25,%26,%27,%28,%29,%30,%31,"
      "%32,%33,%34,%35,%36,%37,%38,%39,%40,%41,%42,%43,%44,%45,%46,%47"
      "}, {%48,%49,%50,%51}, %52, p, 1, 1, 0; }"
    : "+f"(d[0]), "+f"(d[1]), "+f"(d[2]), "+f"(d[3]), "+f"(d[4]), "+f"(d[5]), "+f"(d[6]), "+f"(d[7]),
      "+f"(d[8]), "+f"(d[9]), "+f"(d[10]), "+f"(d[11]), "+f"(d[12]), "+f"(d[13]), "+f"(d[14]), "+f"(d[15]),
      "+f"(d[16]), "+f"(d[17]), "+f"(d[18]), "+f"(d[19]), "+f"(d[20]), "+f"(d[21]), "+f"(d[22]), "+f"(d[23]),
      "+f"(d[24]), "+f"(d[25]), "+f"(d[26]), "+f"(d[27]), "+f"(d[28]), "+f"(d[29]), "+f"(d[30]), "+f"(d[31]),
      "+f"(d[32]), "+f"(d[33]), "+f"(d[34]), "+f"(d[35]), "+f"(d[36]), "+f"(d[37]), "+f"(d[38]), "+f"(d[39]),
      "+f"(d[40]), "+f"(d[41]), "+f"(d[42]), "+f"(d[43]), "+f"(d[44]), "+f"(d[45]), "+f"(d[46]), "+f"(d[47])
    : "r"(a[0]), "r"(a[1]), "r"(a[2]), "r"(a[3]), "l"(db), "r"(sd));
}

__device__ __forceinline__ void wgmma_rs_n112(float* d, const uint32_t* a, uint64_t db, int sd) {
  asm volatile("{ .reg .pred p; setp.ne.b32 p, %61, 0;\n"
      "wgmma.mma_async.sync.aligned.m64n112k16.f32.bf16.bf16 {"
      "%0,%1,%2,%3,%4,%5,%6,%7,%8,%9,%10,%11,%12,%13,%14,%15,"
      "%16,%17,%18,%19,%20,%21,%22,%23,%24,%25,%26,%27,%28,%29,%30,%31,"
      "%32,%33,%34,%35,%36,%37,%38,%39,%40,%41,%42,%43,%44,%45,%46,%47,"
      "%48,%49,%50,%51,%52,%53,%54,%55"
      "}, {%56,%57,%58,%59}, %60, p, 1, 1, 0; }"
    : "+f"(d[0]), "+f"(d[1]), "+f"(d[2]), "+f"(d[3]), "+f"(d[4]), "+f"(d[5]), "+f"(d[6]), "+f"(d[7]),
      "+f"(d[8]), "+f"(d[9]), "+f"(d[10]), "+f"(d[11]), "+f"(d[12]), "+f"(d[13]), "+f"(d[14]), "+f"(d[15]),
      "+f"(d[16]), "+f"(d[17]), "+f"(d[18]), "+f"(d[19]), "+f"(d[20]), "+f"(d[21]), "+f"(d[22]), "+f"(d[23]),
      "+f"(d[24]), "+f"(d[25]), "+f"(d[26]), "+f"(d[27]), "+f"(d[28]), "+f"(d[29]), "+f"(d[30]), "+f"(d[31]),
      "+f"(d[32]), "+f"(d[33]), "+f"(d[34]), "+f"(d[35]), "+f"(d[36]), "+f"(d[37]), "+f"(d[38]), "+f"(d[39]),
      "+f"(d[40]), "+f"(d[41]), "+f"(d[42]), "+f"(d[43]), "+f"(d[44]), "+f"(d[45]), "+f"(d[46]), "+f"(d[47]),
      "+f"(d[48]), "+f"(d[49]), "+f"(d[50]), "+f"(d[51]), "+f"(d[52]), "+f"(d[53]), "+f"(d[54]), "+f"(d[55])
    : "r"(a[0]), "r"(a[1]), "r"(a[2]), "r"(a[3]), "l"(db), "r"(sd));
}

__device__ __forceinline__ void wgmma_rs_n128(float* d, const uint32_t* a, uint64_t db, int sd) {
  asm volatile("{ .reg .pred p; setp.ne.b32 p, %69, 0;\n"
      "wgmma.mma_async.sync.aligned.m64n128k16.f32.bf16.bf16 {"
      "%0,%1,%2,%3,%4,%5,%6,%7,%8,%9,%10,%11,%12,%13,%14,%15,"
      "%16,%17,%18,%19,%20,%21,%22,%23,%24,%25,%26,%27,%28,%29,%30,%31,"
      "%32,%33,%34,%35,%36,%37,%38,%39,%40,%41,%42,%43,%44,%45,%46,%47,"
      "%48,%49,%50,%51,%52,%53,%54,%55,%56,%57,%58,%59,%60,%61,%62,%63"
      "}, {%64,%65,%66,%67}, %68, p, 1, 1, 0; }"
    : "+f"(d[0]), "+f"(d[1]), "+f"(d[2]), "+f"(d[3]), "+f"(d[4]), "+f"(d[5]), "+f"(d[6]), "+f"(d[7]),
      "+f"(d[8]), "+f"(d[9]), "+f"(d[10]), "+f"(d[11]), "+f"(d[12]), "+f"(d[13]), "+f"(d[14]), "+f"(d[15]),
      "+f"(d[16]), "+f"(d[17]), "+f"(d[18]), "+f"(d[19]), "+f"(d[20]), "+f"(d[21]), "+f"(d[22]), "+f"(d[23]),
      "+f"(d[24]), "+f"(d[25]), "+f"(d[26]), "+f"(d[27]), "+f"(d[28]), "+f"(d[29]), "+f"(d[30]), "+f"(d[31]),
      "+f"(d[32]), "+f"(d[33]), "+f"(d[34]), "+f"(d[35]), "+f"(d[36]), "+f"(d[37]), "+f"(d[38]), "+f"(d[39]),
      "+f"(d[40]), "+f"(d[41]), "+f"(d[42]), "+f"(d[43]), "+f"(d[44]), "+f"(d[45]), "+f"(d[46]), "+f"(d[47]),
      "+f"(d[48]), "+f"(d[49]), "+f"(d[50]), "+f"(d[51]), "+f"(d[52]), "+f"(d[53]), "+f"(d[54]), "+f"(d[55]),
      "+f"(d[56]), "+f"(d[57]), "+f"(d[58]), "+f"(d[59]), "+f"(d[60]), "+f"(d[61]), "+f"(d[62]), "+f"(d[63])
    : "r"(a[0]), "r"(a[1]), "r"(a[2]), "r"(a[3]), "l"(db), "r"(sd));
}

__device__ __forceinline__ void wgmma_rs_n144(float* d, const uint32_t* a, uint64_t db, int sd) {
  asm volatile("{ .reg .pred p; setp.ne.b32 p, %77, 0;\n"
      "wgmma.mma_async.sync.aligned.m64n144k16.f32.bf16.bf16 {"
      "%0,%1,%2,%3,%4,%5,%6,%7,%8,%9,%10,%11,%12,%13,%14,%15,"
      "%16,%17,%18,%19,%20,%21,%22,%23,%24,%25,%26,%27,%28,%29,%30,%31,"
      "%32,%33,%34,%35,%36,%37,%38,%39,%40,%41,%42,%43,%44,%45,%46,%47,"
      "%48,%49,%50,%51,%52,%53,%54,%55,%56,%57,%58,%59,%60,%61,%62,%63,"
      "%64,%65,%66,%67,%68,%69,%70,%71"
      "}, {%72,%73,%74,%75}, %76, p, 1, 1, 0; }"
    : "+f"(d[0]), "+f"(d[1]), "+f"(d[2]), "+f"(d[3]), "+f"(d[4]), "+f"(d[5]), "+f"(d[6]), "+f"(d[7]),
      "+f"(d[8]), "+f"(d[9]), "+f"(d[10]), "+f"(d[11]), "+f"(d[12]), "+f"(d[13]), "+f"(d[14]), "+f"(d[15]),
      "+f"(d[16]), "+f"(d[17]), "+f"(d[18]), "+f"(d[19]), "+f"(d[20]), "+f"(d[21]), "+f"(d[22]), "+f"(d[23]),
      "+f"(d[24]), "+f"(d[25]), "+f"(d[26]), "+f"(d[27]), "+f"(d[28]), "+f"(d[29]), "+f"(d[30]), "+f"(d[31]),
      "+f"(d[32]), "+f"(d[33]), "+f"(d[34]), "+f"(d[35]), "+f"(d[36]), "+f"(d[37]), "+f"(d[38]), "+f"(d[39]),
      "+f"(d[40]), "+f"(d[41]), "+f"(d[42]), "+f"(d[43]), "+f"(d[44]), "+f"(d[45]), "+f"(d[46]), "+f"(d[47]),
      "+f"(d[48]), "+f"(d[49]), "+f"(d[50]), "+f"(d[51]), "+f"(d[52]), "+f"(d[53]), "+f"(d[54]), "+f"(d[55]),
      "+f"(d[56]), "+f"(d[57]), "+f"(d[58]), "+f"(d[59]), "+f"(d[60]), "+f"(d[61]), "+f"(d[62]), "+f"(d[63]),
      "+f"(d[64]), "+f"(d[65]), "+f"(d[66]), "+f"(d[67]), "+f"(d[68]), "+f"(d[69]), "+f"(d[70]), "+f"(d[71])
    : "r"(a[0]), "r"(a[1]), "r"(a[2]), "r"(a[3]), "l"(db), "r"(sd));
}

__device__ __forceinline__ void wgmma_rs_n160(float* d, const uint32_t* a, uint64_t db, int sd) {
  asm volatile("{ .reg .pred p; setp.ne.b32 p, %85, 0;\n"
      "wgmma.mma_async.sync.aligned.m64n160k16.f32.bf16.bf16 {"
      "%0,%1,%2,%3,%4,%5,%6,%7,%8,%9,%10,%11,%12,%13,%14,%15,"
      "%16,%17,%18,%19,%20,%21,%22,%23,%24,%25,%26,%27,%28,%29,%30,%31,"
      "%32,%33,%34,%35,%36,%37,%38,%39,%40,%41,%42,%43,%44,%45,%46,%47,"
      "%48,%49,%50,%51,%52,%53,%54,%55,%56,%57,%58,%59,%60,%61,%62,%63,"
      "%64,%65,%66,%67,%68,%69,%70,%71,%72,%73,%74,%75,%76,%77,%78,%79"
      "}, {%80,%81,%82,%83}, %84, p, 1, 1, 0; }"
    : "+f"(d[0]), "+f"(d[1]), "+f"(d[2]), "+f"(d[3]), "+f"(d[4]), "+f"(d[5]), "+f"(d[6]), "+f"(d[7]),
      "+f"(d[8]), "+f"(d[9]), "+f"(d[10]), "+f"(d[11]), "+f"(d[12]), "+f"(d[13]), "+f"(d[14]), "+f"(d[15]),
      "+f"(d[16]), "+f"(d[17]), "+f"(d[18]), "+f"(d[19]), "+f"(d[20]), "+f"(d[21]), "+f"(d[22]), "+f"(d[23]),
      "+f"(d[24]), "+f"(d[25]), "+f"(d[26]), "+f"(d[27]), "+f"(d[28]), "+f"(d[29]), "+f"(d[30]), "+f"(d[31]),
      "+f"(d[32]), "+f"(d[33]), "+f"(d[34]), "+f"(d[35]), "+f"(d[36]), "+f"(d[37]), "+f"(d[38]), "+f"(d[39]),
      "+f"(d[40]), "+f"(d[41]), "+f"(d[42]), "+f"(d[43]), "+f"(d[44]), "+f"(d[45]), "+f"(d[46]), "+f"(d[47]),
      "+f"(d[48]), "+f"(d[49]), "+f"(d[50]), "+f"(d[51]), "+f"(d[52]), "+f"(d[53]), "+f"(d[54]), "+f"(d[55]),
      "+f"(d[56]), "+f"(d[57]), "+f"(d[58]), "+f"(d[59]), "+f"(d[60]), "+f"(d[61]), "+f"(d[62]), "+f"(d[63]),
      "+f"(d[64]), "+f"(d[65]), "+f"(d[66]), "+f"(d[67]), "+f"(d[68]), "+f"(d[69]), "+f"(d[70]), "+f"(d[71]),
      "+f"(d[72]), "+f"(d[73]), "+f"(d[74]), "+f"(d[75]), "+f"(d[76]), "+f"(d[77]), "+f"(d[78]), "+f"(d[79])
    : "r"(a[0]), "r"(a[1]), "r"(a[2]), "r"(a[3]), "l"(db), "r"(sd));
}

__device__ __forceinline__ void wgmma_rs_n176(float* d, const uint32_t* a, uint64_t db, int sd) {
  asm volatile("{ .reg .pred p; setp.ne.b32 p, %93, 0;\n"
      "wgmma.mma_async.sync.aligned.m64n176k16.f32.bf16.bf16 {"
      "%0,%1,%2,%3,%4,%5,%6,%7,%8,%9,%10,%11,%12,%13,%14,%15,"
      "%16,%17,%18,%19,%20,%21,%22,%23,%24,%25,%26,%27,%28,%29,%30,%31,"
      "%32,%33,%34,%35,%36,%37,%38,%39,%40,%41,%42,%43,%44,%45,%46,%47,"
      "%48,%49,%50,%51,%52,%53,%54,%55,%56,%57,%58,%59,%60,%61,%62,%63,"
      "%64,%65,%66,%67,%68,%69,%70,%71,%72,%73,%74,%75,%76,%77,%78,%79,"
      "%80,%81,%82,%83,%84,%85,%86,%87"
      "}, {%88,%89,%90,%91}, %92, p, 1, 1, 0; }"
    : "+f"(d[0]), "+f"(d[1]), "+f"(d[2]), "+f"(d[3]), "+f"(d[4]), "+f"(d[5]), "+f"(d[6]), "+f"(d[7]),
      "+f"(d[8]), "+f"(d[9]), "+f"(d[10]), "+f"(d[11]), "+f"(d[12]), "+f"(d[13]), "+f"(d[14]), "+f"(d[15]),
      "+f"(d[16]), "+f"(d[17]), "+f"(d[18]), "+f"(d[19]), "+f"(d[20]), "+f"(d[21]), "+f"(d[22]), "+f"(d[23]),
      "+f"(d[24]), "+f"(d[25]), "+f"(d[26]), "+f"(d[27]), "+f"(d[28]), "+f"(d[29]), "+f"(d[30]), "+f"(d[31]),
      "+f"(d[32]), "+f"(d[33]), "+f"(d[34]), "+f"(d[35]), "+f"(d[36]), "+f"(d[37]), "+f"(d[38]), "+f"(d[39]),
      "+f"(d[40]), "+f"(d[41]), "+f"(d[42]), "+f"(d[43]), "+f"(d[44]), "+f"(d[45]), "+f"(d[46]), "+f"(d[47]),
      "+f"(d[48]), "+f"(d[49]), "+f"(d[50]), "+f"(d[51]), "+f"(d[52]), "+f"(d[53]), "+f"(d[54]), "+f"(d[55]),
      "+f"(d[56]), "+f"(d[57]), "+f"(d[58]), "+f"(d[59]), "+f"(d[60]), "+f"(d[61]), "+f"(d[62]), "+f"(d[63]),
      "+f"(d[64]), "+f"(d[65]), "+f"(d[66]), "+f"(d[67]), "+f"(d[68]), "+f"(d[69]), "+f"(d[70]), "+f"(d[71]),
      "+f"(d[72]), "+f"(d[73]), "+f"(d[74]), "+f"(d[75]), "+f"(d[76]), "+f"(d[77]), "+f"(d[78]), "+f"(d[79]),
      "+f"(d[80]), "+f"(d[81]), "+f"(d[82]), "+f"(d[83]), "+f"(d[84]), "+f"(d[85]), "+f"(d[86]), "+f"(d[87])
    : "r"(a[0]), "r"(a[1]), "r"(a[2]), "r"(a[3]), "l"(db), "r"(sd));
}

__device__ __forceinline__ void wgmma_rs_n192(float* d, const uint32_t* a, uint64_t db, int sd) {
  asm volatile("{ .reg .pred p; setp.ne.b32 p, %101, 0;\n"
      "wgmma.mma_async.sync.aligned.m64n192k16.f32.bf16.bf16 {"
      "%0,%1,%2,%3,%4,%5,%6,%7,%8,%9,%10,%11,%12,%13,%14,%15,"
      "%16,%17,%18,%19,%20,%21,%22,%23,%24,%25,%26,%27,%28,%29,%30,%31,"
      "%32,%33,%34,%35,%36,%37,%38,%39,%40,%41,%42,%43,%44,%45,%46,%47,"
      "%48,%49,%50,%51,%52,%53,%54,%55,%56,%57,%58,%59,%60,%61,%62,%63,"
      "%64,%65,%66,%67,%68,%69,%70,%71,%72,%73,%74,%75,%76,%77,%78,%79,"
      "%80,%81,%82,%83,%84,%85,%86,%87,%88,%89,%90,%91,%92,%93,%94,%95"
      "}, {%96,%97,%98,%99}, %100, p, 1, 1, 0; }"
    : "+f"(d[0]), "+f"(d[1]), "+f"(d[2]), "+f"(d[3]), "+f"(d[4]), "+f"(d[5]), "+f"(d[6]), "+f"(d[7]),
      "+f"(d[8]), "+f"(d[9]), "+f"(d[10]), "+f"(d[11]), "+f"(d[12]), "+f"(d[13]), "+f"(d[14]), "+f"(d[15]),
      "+f"(d[16]), "+f"(d[17]), "+f"(d[18]), "+f"(d[19]), "+f"(d[20]), "+f"(d[21]), "+f"(d[22]), "+f"(d[23]),
      "+f"(d[24]), "+f"(d[25]), "+f"(d[26]), "+f"(d[27]), "+f"(d[28]), "+f"(d[29]), "+f"(d[30]), "+f"(d[31]),
      "+f"(d[32]), "+f"(d[33]), "+f"(d[34]), "+f"(d[35]), "+f"(d[36]), "+f"(d[37]), "+f"(d[38]), "+f"(d[39]),
      "+f"(d[40]), "+f"(d[41]), "+f"(d[42]), "+f"(d[43]), "+f"(d[44]), "+f"(d[45]), "+f"(d[46]), "+f"(d[47]),
      "+f"(d[48]), "+f"(d[49]), "+f"(d[50]), "+f"(d[51]), "+f"(d[52]), "+f"(d[53]), "+f"(d[54]), "+f"(d[55]),
      "+f"(d[56]), "+f"(d[57]), "+f"(d[58]), "+f"(d[59]), "+f"(d[60]), "+f"(d[61]), "+f"(d[62]), "+f"(d[63]),
      "+f"(d[64]), "+f"(d[65]), "+f"(d[66]), "+f"(d[67]), "+f"(d[68]), "+f"(d[69]), "+f"(d[70]), "+f"(d[71]),
      "+f"(d[72]), "+f"(d[73]), "+f"(d[74]), "+f"(d[75]), "+f"(d[76]), "+f"(d[77]), "+f"(d[78]), "+f"(d[79]),
      "+f"(d[80]), "+f"(d[81]), "+f"(d[82]), "+f"(d[83]), "+f"(d[84]), "+f"(d[85]), "+f"(d[86]), "+f"(d[87]),
      "+f"(d[88]), "+f"(d[89]), "+f"(d[90]), "+f"(d[91]), "+f"(d[92]), "+f"(d[93]), "+f"(d[94]), "+f"(d[95])
    : "r"(a[0]), "r"(a[1]), "r"(a[2]), "r"(a[3]), "l"(db), "r"(sd));
}

__device__ __forceinline__ void wgmma_rs_n208(float* d, const uint32_t* a, uint64_t db, int sd) {
  asm volatile("{ .reg .pred p; setp.ne.b32 p, %109, 0;\n"
      "wgmma.mma_async.sync.aligned.m64n208k16.f32.bf16.bf16 {"
      "%0,%1,%2,%3,%4,%5,%6,%7,%8,%9,%10,%11,%12,%13,%14,%15,"
      "%16,%17,%18,%19,%20,%21,%22,%23,%24,%25,%26,%27,%28,%29,%30,%31,"
      "%32,%33,%34,%35,%36,%37,%38,%39,%40,%41,%42,%43,%44,%45,%46,%47,"
      "%48,%49,%50,%51,%52,%53,%54,%55,%56,%57,%58,%59,%60,%61,%62,%63,"
      "%64,%65,%66,%67,%68,%69,%70,%71,%72,%73,%74,%75,%76,%77,%78,%79,"
      "%80,%81,%82,%83,%84,%85,%86,%87,%88,%89,%90,%91,%92,%93,%94,%95,"
      "%96,%97,%98,%99,%100,%101,%102,%103"
      "}, {%104,%105,%106,%107}, %108, p, 1, 1, 0; }"
    : "+f"(d[0]), "+f"(d[1]), "+f"(d[2]), "+f"(d[3]), "+f"(d[4]), "+f"(d[5]), "+f"(d[6]), "+f"(d[7]),
      "+f"(d[8]), "+f"(d[9]), "+f"(d[10]), "+f"(d[11]), "+f"(d[12]), "+f"(d[13]), "+f"(d[14]), "+f"(d[15]),
      "+f"(d[16]), "+f"(d[17]), "+f"(d[18]), "+f"(d[19]), "+f"(d[20]), "+f"(d[21]), "+f"(d[22]), "+f"(d[23]),
      "+f"(d[24]), "+f"(d[25]), "+f"(d[26]), "+f"(d[27]), "+f"(d[28]), "+f"(d[29]), "+f"(d[30]), "+f"(d[31]),
      "+f"(d[32]), "+f"(d[33]), "+f"(d[34]), "+f"(d[35]), "+f"(d[36]), "+f"(d[37]), "+f"(d[38]), "+f"(d[39]),
      "+f"(d[40]), "+f"(d[41]), "+f"(d[42]), "+f"(d[43]), "+f"(d[44]), "+f"(d[45]), "+f"(d[46]), "+f"(d[47]),
      "+f"(d[48]), "+f"(d[49]), "+f"(d[50]), "+f"(d[51]), "+f"(d[52]), "+f"(d[53]), "+f"(d[54]), "+f"(d[55]),
      "+f"(d[56]), "+f"(d[57]), "+f"(d[58]), "+f"(d[59]), "+f"(d[60]), "+f"(d[61]), "+f"(d[62]), "+f"(d[63]),
      "+f"(d[64]), "+f"(d[65]), "+f"(d[66]), "+f"(d[67]), "+f"(d[68]), "+f"(d[69]), "+f"(d[70]), "+f"(d[71]),
      "+f"(d[72]), "+f"(d[73]), "+f"(d[74]), "+f"(d[75]), "+f"(d[76]), "+f"(d[77]), "+f"(d[78]), "+f"(d[79]),
      "+f"(d[80]), "+f"(d[81]), "+f"(d[82]), "+f"(d[83]), "+f"(d[84]), "+f"(d[85]), "+f"(d[86]), "+f"(d[87]),
      "+f"(d[88]), "+f"(d[89]), "+f"(d[90]), "+f"(d[91]), "+f"(d[92]), "+f"(d[93]), "+f"(d[94]), "+f"(d[95]),
      "+f"(d[96]), "+f"(d[97]), "+f"(d[98]), "+f"(d[99]), "+f"(d[100]), "+f"(d[101]), "+f"(d[102]), "+f"(d[103])
    : "r"(a[0]), "r"(a[1]), "r"(a[2]), "r"(a[3]), "l"(db), "r"(sd));
}

__device__ __forceinline__ void wgmma_rs_n224(float* d, const uint32_t* a, uint64_t db, int sd) {
  asm volatile("{ .reg .pred p; setp.ne.b32 p, %117, 0;\n"
      "wgmma.mma_async.sync.aligned.m64n224k16.f32.bf16.bf16 {"
      "%0,%1,%2,%3,%4,%5,%6,%7,%8,%9,%10,%11,%12,%13,%14,%15,"
      "%16,%17,%18,%19,%20,%21,%22,%23,%24,%25,%26,%27,%28,%29,%30,%31,"
      "%32,%33,%34,%35,%36,%37,%38,%39,%40,%41,%42,%43,%44,%45,%46,%47,"
      "%48,%49,%50,%51,%52,%53,%54,%55,%56,%57,%58,%59,%60,%61,%62,%63,"
      "%64,%65,%66,%67,%68,%69,%70,%71,%72,%73,%74,%75,%76,%77,%78,%79,"
      "%80,%81,%82,%83,%84,%85,%86,%87,%88,%89,%90,%91,%92,%93,%94,%95,"
      "%96,%97,%98,%99,%100,%101,%102,%103,%104,%105,%106,%107,%108,%109,%110,%111"
      "}, {%112,%113,%114,%115}, %116, p, 1, 1, 0; }"
    : "+f"(d[0]), "+f"(d[1]), "+f"(d[2]), "+f"(d[3]), "+f"(d[4]), "+f"(d[5]), "+f"(d[6]), "+f"(d[7]),
      "+f"(d[8]), "+f"(d[9]), "+f"(d[10]), "+f"(d[11]), "+f"(d[12]), "+f"(d[13]), "+f"(d[14]), "+f"(d[15]),
      "+f"(d[16]), "+f"(d[17]), "+f"(d[18]), "+f"(d[19]), "+f"(d[20]), "+f"(d[21]), "+f"(d[22]), "+f"(d[23]),
      "+f"(d[24]), "+f"(d[25]), "+f"(d[26]), "+f"(d[27]), "+f"(d[28]), "+f"(d[29]), "+f"(d[30]), "+f"(d[31]),
      "+f"(d[32]), "+f"(d[33]), "+f"(d[34]), "+f"(d[35]), "+f"(d[36]), "+f"(d[37]), "+f"(d[38]), "+f"(d[39]),
      "+f"(d[40]), "+f"(d[41]), "+f"(d[42]), "+f"(d[43]), "+f"(d[44]), "+f"(d[45]), "+f"(d[46]), "+f"(d[47]),
      "+f"(d[48]), "+f"(d[49]), "+f"(d[50]), "+f"(d[51]), "+f"(d[52]), "+f"(d[53]), "+f"(d[54]), "+f"(d[55]),
      "+f"(d[56]), "+f"(d[57]), "+f"(d[58]), "+f"(d[59]), "+f"(d[60]), "+f"(d[61]), "+f"(d[62]), "+f"(d[63]),
      "+f"(d[64]), "+f"(d[65]), "+f"(d[66]), "+f"(d[67]), "+f"(d[68]), "+f"(d[69]), "+f"(d[70]), "+f"(d[71]),
      "+f"(d[72]), "+f"(d[73]), "+f"(d[74]), "+f"(d[75]), "+f"(d[76]), "+f"(d[77]), "+f"(d[78]), "+f"(d[79]),
      "+f"(d[80]), "+f"(d[81]), "+f"(d[82]), "+f"(d[83]), "+f"(d[84]), "+f"(d[85]), "+f"(d[86]), "+f"(d[87]),
      "+f"(d[88]), "+f"(d[89]), "+f"(d[90]), "+f"(d[91]), "+f"(d[92]), "+f"(d[93]), "+f"(d[94]), "+f"(d[95]),
      "+f"(d[96]), "+f"(d[97]), "+f"(d[98]), "+f"(d[99]), "+f"(d[100]), "+f"(d[101]), "+f"(d[102]), "+f"(d[103]),
      "+f"(d[104]), "+f"(d[105]), "+f"(d[106]), "+f"(d[107]), "+f"(d[108]), "+f"(d[109]), "+f"(d[110]), "+f"(d[111])
    : "r"(a[0]), "r"(a[1]), "r"(a[2]), "r"(a[3]), "l"(db), "r"(sd));
}

__device__ __forceinline__ void wgmma_rs_n240(float* d, const uint32_t* a, uint64_t db, int sd) {
  asm volatile("{ .reg .pred p; setp.ne.b32 p, %125, 0;\n"
      "wgmma.mma_async.sync.aligned.m64n240k16.f32.bf16.bf16 {"
      "%0,%1,%2,%3,%4,%5,%6,%7,%8,%9,%10,%11,%12,%13,%14,%15,"
      "%16,%17,%18,%19,%20,%21,%22,%23,%24,%25,%26,%27,%28,%29,%30,%31,"
      "%32,%33,%34,%35,%36,%37,%38,%39,%40,%41,%42,%43,%44,%45,%46,%47,"
      "%48,%49,%50,%51,%52,%53,%54,%55,%56,%57,%58,%59,%60,%61,%62,%63,"
      "%64,%65,%66,%67,%68,%69,%70,%71,%72,%73,%74,%75,%76,%77,%78,%79,"
      "%80,%81,%82,%83,%84,%85,%86,%87,%88,%89,%90,%91,%92,%93,%94,%95,"
      "%96,%97,%98,%99,%100,%101,%102,%103,%104,%105,%106,%107,%108,%109,%110,%111,"
      "%112,%113,%114,%115,%116,%117,%118,%119"
      "}, {%120,%121,%122,%123}, %124, p, 1, 1, 0; }"
    : "+f"(d[0]), "+f"(d[1]), "+f"(d[2]), "+f"(d[3]), "+f"(d[4]), "+f"(d[5]), "+f"(d[6]), "+f"(d[7]),
      "+f"(d[8]), "+f"(d[9]), "+f"(d[10]), "+f"(d[11]), "+f"(d[12]), "+f"(d[13]), "+f"(d[14]), "+f"(d[15]),
      "+f"(d[16]), "+f"(d[17]), "+f"(d[18]), "+f"(d[19]), "+f"(d[20]), "+f"(d[21]), "+f"(d[22]), "+f"(d[23]),
      "+f"(d[24]), "+f"(d[25]), "+f"(d[26]), "+f"(d[27]), "+f"(d[28]), "+f"(d[29]), "+f"(d[30]), "+f"(d[31]),
      "+f"(d[32]), "+f"(d[33]), "+f"(d[34]), "+f"(d[35]), "+f"(d[36]), "+f"(d[37]), "+f"(d[38]), "+f"(d[39]),
      "+f"(d[40]), "+f"(d[41]), "+f"(d[42]), "+f"(d[43]), "+f"(d[44]), "+f"(d[45]), "+f"(d[46]), "+f"(d[47]),
      "+f"(d[48]), "+f"(d[49]), "+f"(d[50]), "+f"(d[51]), "+f"(d[52]), "+f"(d[53]), "+f"(d[54]), "+f"(d[55]),
      "+f"(d[56]), "+f"(d[57]), "+f"(d[58]), "+f"(d[59]), "+f"(d[60]), "+f"(d[61]), "+f"(d[62]), "+f"(d[63]),
      "+f"(d[64]), "+f"(d[65]), "+f"(d[66]), "+f"(d[67]), "+f"(d[68]), "+f"(d[69]), "+f"(d[70]), "+f"(d[71]),
      "+f"(d[72]), "+f"(d[73]), "+f"(d[74]), "+f"(d[75]), "+f"(d[76]), "+f"(d[77]), "+f"(d[78]), "+f"(d[79]),
      "+f"(d[80]), "+f"(d[81]), "+f"(d[82]), "+f"(d[83]), "+f"(d[84]), "+f"(d[85]), "+f"(d[86]), "+f"(d[87]),
      "+f"(d[88]), "+f"(d[89]), "+f"(d[90]), "+f"(d[91]), "+f"(d[92]), "+f"(d[93]), "+f"(d[94]), "+f"(d[95]),
      "+f"(d[96]), "+f"(d[97]), "+f"(d[98]), "+f"(d[99]), "+f"(d[100]), "+f"(d[101]), "+f"(d[102]), "+f"(d[103]),
      "+f"(d[104]), "+f"(d[105]), "+f"(d[106]), "+f"(d[107]), "+f"(d[108]), "+f"(d[109]), "+f"(d[110]), "+f"(d[111]),
      "+f"(d[112]), "+f"(d[113]), "+f"(d[114]), "+f"(d[115]), "+f"(d[116]), "+f"(d[117]), "+f"(d[118]), "+f"(d[119])
    : "r"(a[0]), "r"(a[1]), "r"(a[2]), "r"(a[3]), "l"(db), "r"(sd));
}

__device__ __forceinline__ void wgmma_rs_n256(float* d, const uint32_t* a, uint64_t db, int sd) {
  asm volatile("{ .reg .pred p; setp.ne.b32 p, %133, 0;\n"
      "wgmma.mma_async.sync.aligned.m64n256k16.f32.bf16.bf16 {"
      "%0,%1,%2,%3,%4,%5,%6,%7,%8,%9,%10,%11,%12,%13,%14,%15,"
      "%16,%17,%18,%19,%20,%21,%22,%23,%24,%25,%26,%27,%28,%29,%30,%31,"
      "%32,%33,%34,%35,%36,%37,%38,%39,%40,%41,%42,%43,%44,%45,%46,%47,"
      "%48,%49,%50,%51,%52,%53,%54,%55,%56,%57,%58,%59,%60,%61,%62,%63,"
      "%64,%65,%66,%67,%68,%69,%70,%71,%72,%73,%74,%75,%76,%77,%78,%79,"
      "%80,%81,%82,%83,%84,%85,%86,%87,%88,%89,%90,%91,%92,%93,%94,%95,"
      "%96,%97,%98,%99,%100,%101,%102,%103,%104,%105,%106,%107,%108,%109,%110,%111,"
      "%112,%113,%114,%115,%116,%117,%118,%119,%120,%121,%122,%123,%124,%125,%126,%127"
      "}, {%128,%129,%130,%131}, %132, p, 1, 1, 0; }"
    : "+f"(d[0]), "+f"(d[1]), "+f"(d[2]), "+f"(d[3]), "+f"(d[4]), "+f"(d[5]), "+f"(d[6]), "+f"(d[7]),
      "+f"(d[8]), "+f"(d[9]), "+f"(d[10]), "+f"(d[11]), "+f"(d[12]), "+f"(d[13]), "+f"(d[14]), "+f"(d[15]),
      "+f"(d[16]), "+f"(d[17]), "+f"(d[18]), "+f"(d[19]), "+f"(d[20]), "+f"(d[21]), "+f"(d[22]), "+f"(d[23]),
      "+f"(d[24]), "+f"(d[25]), "+f"(d[26]), "+f"(d[27]), "+f"(d[28]), "+f"(d[29]), "+f"(d[30]), "+f"(d[31]),
      "+f"(d[32]), "+f"(d[33]), "+f"(d[34]), "+f"(d[35]), "+f"(d[36]), "+f"(d[37]), "+f"(d[38]), "+f"(d[39]),
      "+f"(d[40]), "+f"(d[41]), "+f"(d[42]), "+f"(d[43]), "+f"(d[44]), "+f"(d[45]), "+f"(d[46]), "+f"(d[47]),
      "+f"(d[48]), "+f"(d[49]), "+f"(d[50]), "+f"(d[51]), "+f"(d[52]), "+f"(d[53]), "+f"(d[54]), "+f"(d[55]),
      "+f"(d[56]), "+f"(d[57]), "+f"(d[58]), "+f"(d[59]), "+f"(d[60]), "+f"(d[61]), "+f"(d[62]), "+f"(d[63]),
      "+f"(d[64]), "+f"(d[65]), "+f"(d[66]), "+f"(d[67]), "+f"(d[68]), "+f"(d[69]), "+f"(d[70]), "+f"(d[71]),
      "+f"(d[72]), "+f"(d[73]), "+f"(d[74]), "+f"(d[75]), "+f"(d[76]), "+f"(d[77]), "+f"(d[78]), "+f"(d[79]),
      "+f"(d[80]), "+f"(d[81]), "+f"(d[82]), "+f"(d[83]), "+f"(d[84]), "+f"(d[85]), "+f"(d[86]), "+f"(d[87]),
      "+f"(d[88]), "+f"(d[89]), "+f"(d[90]), "+f"(d[91]), "+f"(d[92]), "+f"(d[93]), "+f"(d[94]), "+f"(d[95]),
      "+f"(d[96]), "+f"(d[97]), "+f"(d[98]), "+f"(d[99]), "+f"(d[100]), "+f"(d[101]), "+f"(d[102]), "+f"(d[103]),
      "+f"(d[104]), "+f"(d[105]), "+f"(d[106]), "+f"(d[107]), "+f"(d[108]), "+f"(d[109]), "+f"(d[110]), "+f"(d[111]),
      "+f"(d[112]), "+f"(d[113]), "+f"(d[114]), "+f"(d[115]), "+f"(d[116]), "+f"(d[117]), "+f"(d[118]), "+f"(d[119]),
      "+f"(d[120]), "+f"(d[121]), "+f"(d[122]), "+f"(d[123]), "+f"(d[124]), "+f"(d[125]), "+f"(d[126]), "+f"(d[127])
    : "r"(a[0]), "r"(a[1]), "r"(a[2]), "r"(a[3]), "l"(db), "r"(sd));
}

__device__ __forceinline__ void ln_finish(float mean, float var, float& mb, float& rinv) {
  mb = round_bf16(mean);
  float den = round_bf16(sqrtf(round_bf16(round_bf16(var) + 1e-5f)));
  rinv = 1.0f / den;
}
__device__ __forceinline__ uint32_t ln_apply(uint32_t x2, uint32_t mb2, float rinv) {
  uint32_t c = bsub2(x2, mb2);
  return pack_bf16(bf_lo(c) * rinv, bf_hi(c) * rinv);
}
__device__ __forceinline__ int conv_channel(int cta, int i) {
  return i < N_SHORT ? i * N_CONV_CTA + cta : N_SHORT * N_CONV_CTA + (i - N_SHORT) * 4 + cta;
}
__device__ __forceinline__ uint32_t sum4(uint32_t a, uint32_t b, uint32_t c, uint32_t d) {
  return pack_bf16((bf_lo(a) + bf_lo(b)) + (bf_lo(c) + bf_lo(d)), (bf_hi(a) + bf_hi(b)) + (bf_hi(c) + bf_hi(d)));
}
struct Ring {
  uint32_t s, ph;
  __device__ __forceinline__ void next() { if (++s == NSTAGE) { s = 0; ph ^= 1; } }
};

__global__ void __cluster_dims__(2, 1, 1) __launch_bounds__(384, 1) fused_kernel(const __grid_constant__ Params P) {
  extern __shared__ uint8_t smem_raw[];
  const uint32_t sb = (smem_u32(smem_raw) + 1023) & ~1023u;
  const uint32_t bars = sb + SM_BAR;
  const int tid = threadIdx.x, warp = __shfl_sync(0xffffffffu, tid >> 5, 0), lane = tid & 31;
  const int rank = blockIdx.x & 1, p0b = blockIdx.x;
  const bool p0 = p0b < 128;

  uint32_t xr[18];
  const int ln_row = p0b * 16 + warp * 2 + (lane >> 4);
  if (warp < 8 && p0) {
    const uint2* src = reinterpret_cast<const uint2*>(P.x + (size_t)ln_row * D_) + (lane & 15);
#pragma unroll
    for (int j = 0; j < 9; j++) asm volatile("ld.global.nc.v2.u32 {%0,%1}, [%2];" : "=r"(xr[2 * j]), "=r"(xr[2 * j + 1]) : "l"(src + 16 * j));
  }
  const Role role = P.roles.r[blockIdx.x >> 1];
  const int g1m = role.g1m, g1n = role.g1n, g2m = role.g2m, g2n = role.g2n;
  const int cvc = 2 * (-1 - g1m) + rank;
  const int n_conv = g2m < 0 ? N_SHORT + N_LONG_EXTRA : N_SHORT;
  const int dk = g2n * 144 + rank * 72;

  if (warp >= 8) {
    asm volatile("setmaxnreg.dec.sync.aligned.u32 56;");
    const uint32_t tag = ld_flag(&g_epoch) + 1;
    if (lane == 0) {
      if (warp == 8) {
        for (int s = 0; s < NSTAGE; s++) mbar_init(bars + 8 * (B_FULL + s), 1);
        if (g1m < 0) {
          for (int s = 0; s < CV_NSLOT; s++) mbar_init(bars + 8 * (B_CFULL + s), 1);
          for (int s = 0; s < G1_KB % NSTAGE; s++) mbar_arrive(bars + 8 * (B_FULL + s));
        }
      } else if (warp == 9) {
        for (int s = 0; s < NSTAGE; s++) mbar_init(bars + 8 * (B_EMPTY + s), 2);
      } else if (warp == 10) {
        for (int s = 0; s < 6; s++) mbar_init(bars + 8 * (B_STG + s), 4);
      } else {
        for (int s = B_XRDY; s <= B_Y2; s++) mbar_init(bars + 8 * s, 1);
      }
      asm volatile("fence.mbarrier_init.release.cluster;" ::: "memory");
    }
    __syncwarp();
    asm volatile("barrier.cluster.arrive.relaxed.aligned;" ::: "memory");
    if (warp == 8) {
      const int fg = (2 * g1m + rank) * 2, dg = g1n * 3;
      if (lane == 0) {
        if (g1m >= 0) {
          for (int s = 0; s < NSTAGE; s++) {
            mbar_expect_tx(bars + 8 * (B_FULL + s), G1_BYTES);
            tma3d(sb + s * SLOT, &P.m_w1, 0, s * 64, fg, bars + 8 * (B_FULL + s));
          }
        } else {
          for (int i = 0; i < CV_NSLOT; i++) {
            mbar_expect_tx(bars + 8 * (B_CFULL + i), 8192 + 4096);
            bulk_load(sb + i * CV_SLOT + CV_KOFF + 32, P.ssm_k + (size_t)conv_channel(cvc, i) * S_, 4096, bars + 8 * (B_CFULL + i));
          }
        }
      }
      __syncwarp();
      asm volatile("barrier.cluster.wait.aligned;" ::: "memory");
      if (lane == 0) {
        if (g1m >= 0) {
          await(C_H, tag * 128);
          TLREC(2);
          fence_async_global();
          for (int s = 0; s < NSTAGE; s++) tma3d(sb + s * SLOT + 16384, &P.m_h, 0, s * 64, dg, bars + 8 * (B_FULL + s));
          Ring r{0, 0};
#pragma unroll 1
          for (int kb = NSTAGE; kb < G1_KB; kb++, r.next()) {
            mbar_wait(bars + 8 * (B_EMPTY + r.s), r.ph);
            mbar_expect_tx(bars + 8 * (B_FULL + r.s), G1_BYTES);
            tma3d(sb + r.s * SLOT, &P.m_w1, 0, kb * 64, fg, bars + 8 * (B_FULL + r.s));
            tma3d(sb + r.s * SLOT + 16384, &P.m_h, 0, kb * 64, dg, bars + 8 * (B_FULL + r.s));
          }
        } else {
          int ready = -1;
#pragma unroll 1
          for (int i = 0; i < n_conv; i++) {
            const int ch = conv_channel(cvc, i), s = i % CV_NSLOT;
            const uint32_t slot = sb + s * CV_SLOT, fb = bars + 8 * (B_CFULL + s);
            if (i >= CV_NSLOT) {
              mbar_wait(bars + 8 * (B_CEMPTY + s), ((i / CV_NSLOT) - 1) & 1);
              mbar_expect_tx(fb, 8192 + 4096);
              bulk_load(slot + CV_KOFF + 32, P.ssm_k + (size_t)ch * S_, 4096, fb);
            }
            const int r = ch / 96;
            if (r > ready) {
              await(C_KV + r, tag * 128);
              fence_async_global();
              if (r == 0) TLREC(18);
              ready = r;
            }
            bulk_load(slot, g_ub + (size_t)ch * 4096, 8192, fb);
          }
        }
        if (g2m >= 0) {
          const int sg = g2m * 2, ds = g2n * 144 + (rank ^ 1) * 72;
          const int cu0 = C_U + ((g2n * 144) / 192) * 4 + rank * 2, cu1 = C_U + ((g2n * 144 + 143) / 192) * 4 + rank * 2;
          constexpr int NPRE = 3;
          for (int kb = 0; kb < NPRE; kb++) {
            const int s = (G1_KB + kb) % NSTAGE;
            mbar_wait(bars + 8 * (B_EMPTY + s), (((G1_KB + kb) / NSTAGE) - 1) & 1);
            mbar_expect_tx(bars + 8 * (B_FULL + s), G2_BYTES);
            tma3d(sb + s * SLOT, &P.m_w2, 0, (rank * G2_KB + 2 * kb) * 64, sg, bars + 8 * (B_FULL + s));
          }
          Ring r{G1_KB % NSTAGE, ((G1_KB / NSTAGE) - 1) & 1};
#pragma unroll 1
          for (int kb = 0; kb < G2_KB; kb++, r.next()) {
            const int k0 = (rank * G2_KB + (kb < 18 ? 2 * kb : 2 * kb - 35)) * 64;
            const uint32_t fb = bars + 8 * (B_FULL + r.s), slot = sb + r.s * SLOT;
            if (kb == 0 || kb == 18) {
              await(cu0 + (kb != 0), tag * 18);
              await(cu1 + (kb != 0), tag * 18);
              fence_async_global();
              if (kb == 0) TLREC(6);
            }
            if (kb >= NPRE) {
              mbar_wait(bars + 8 * (B_EMPTY + r.s), r.ph);
              mbar_expect_tx(fb, G2_BYTES);
              tma3d(slot, &P.m_w2, 0, k0, sg, fb);
            }
            tma2d(slot + 16384, &P.m_uld, k0, ds, fb);
            tma2d(slot + 16384 + 9216, &P.m_uld, k0, dk, fb);
            if (kb == 10) {
              mbar_expect_tx(bars + 8 * B_XT, 18432);
              for (int j = 0; j < 8; j++)
                tma2d(sb + ((XSLOT + 1 + (j >> 1)) % NSTAGE) * SLOT + G2_BYTES + (j & 1) * 2304, &P.m_x, dk, g2m * 128 + j * 16, bars + 8 * B_XT);
            }
          }
          mbar_expect_tx(bars + 8 * B_XFULL, 18432);
          mbar_expect_tx(bars + 8 * (B_XFULL + 1), 18432);
          mbar_wait(bars + 8 * (B_EMPTY + XSLOT), r.ph);
          mbar_arrive_remote(mapa(bars + 8 * B_XRDY, rank ^ 1));
        }
      }
    } else {
      const int ht = tid - 288;
      if (p0) {
        const int hf = ht / 48, pr = ht % 48;
        const int s0 = p0b * 16 + hf * 8;
        const bool first = s0 == 0, odd = lane & 1;
#pragma unroll 1
        for (int r = 0; r < KV_ROUNDS; r++) {
          const int d = r * 96 + 2 * pr;
          const __nv_bfloat16* kp = P.k + (ptrdiff_t)(s0 - 4) * D_ + d;
          const __nv_bfloat16* vp = P.v + (ptrdiff_t)(s0 - 1) * D_ + d;
          uint32_t kk[12], vv[9];
#pragma unroll
          for (int j = 0; j < 12; j++) kk[j] = (j < 4 && first) ? 0u : ldg32(kp + j * D_);
#pragma unroll
          for (int j = 0; j < 9; j++) vv[j] = (j < 1 && first) ? 0u : ldg32(vp + j * D_);
          const uint4 w = __ldg(reinterpret_cast<const uint4*>(P.shift_k + d * 4));
          const uint32_t w0 = __byte_perm(w.x, w.z, 0x5410), w1 = __byte_perm(w.x, w.z, 0x7632);
          const uint32_t w2 = __byte_perm(w.y, w.w, 0x5410), w3 = __byte_perm(w.y, w.w, 0x7632);
#pragma unroll
          for (int j = 0; j < 9; j++)
            vv[j] = bmul2(bfma2(kk[j + 3], w0, bfma2(kk[j + 2], w1, bfma2(kk[j + 1], w2, bmul2(kk[j], w3)))), vv[j]);
          uint32_t da[8], db[8];
#pragma unroll
          for (int j = 0; j < 8; j++) {
            const uint32_t o = __shfl_xor_sync(0xffffffffu, odd ? vv[j] : vv[j + 1], 1);
            da[j] = odd ? o : vv[j];
            db[j] = odd ? vv[j + 1] : o;
          }
          uint4* dst = reinterpret_cast<uint4*>(g_ub + (size_t)(d & ~3) * 4096) + (1 - hf) * 256 + 2 * (127 - p0b) + odd;
#pragma unroll
          for (int c = 0; c < 2; c++) {
            const uint32_t sel = c ? 0x7632 : 0x5410;
            dst[c * 512] = make_uint4(__byte_perm(da[7], da[6], sel), __byte_perm(da[5], da[4], sel), __byte_perm(da[3], da[2], sel), __byte_perm(da[1], da[0], sel));
            dst[(c + 2) * 512] = make_uint4(__byte_perm(db[7], db[6], sel), __byte_perm(db[5], db[4], sel), __byte_perm(db[3], db[2], sel), __byte_perm(db[1], db[0], sel));
          }
          bar_sync(1, 96);
          if (ht == 0) { signal(C_KV + r); TLREC(22 + r); }
          __syncwarp();
        }
      }
      asm volatile("barrier.cluster.wait.aligned;" ::: "memory");
      if (lane == 0) {
        if (g1m >= 0 && warp < 11) {
          const int wg = warp - 9, fb64 = (2 * g1m + rank) * 2 + wg;
          const uint32_t stg = wg == 0 ? sb + SM_DED : sb + ((G1_KB - 1) % NSTAGE) * SLOT;
          for (int c = 0; c < 3; c++) {
            mbar_wait(bars + 8 * (B_STG + wg * 3 + c), 0);
            fence_async_smem();
            tma2d_store(&P.m_ust, stg + c * 8192, fb64 * 64, g1n * 192 + c * 64);
          }
          TLREC(13 + wg);
          bulk_commit();
          if (wg == 1) { bulk_wait_read(); mbar_arrive(bars + 8 * (B_EMPTY + (G1_KB - 1) % NSTAGE)); }
          bulk_wait_all();
          if (wg == 0) TLREC(19);
          signal(C_U + g1n * 4 + (fb64 / G2_KB) * 2 + wg);
          TLREC(15 + wg);
        }
        if (g2m >= 0 && warp == 9) {
          await<true>(C_Y, tag * 2 * N_CONV_CTA);
          fence_async_global(); fence_async_smem();
          if (g1m == 0 && g1n == 0 && rank == 0) st_flag(&g_epoch, tag);
          TLREC(8);
          mbar_expect_tx(bars + 8 * B_Y2, 18432);
          tma2d(sb + SM_DED, &P.m_y, g2m * 128, dk, bars + 8 * B_Y2);
          tma2d(sb + SM_DED + 9216, &P.m_y, g2m * 128 + 64, dk, bars + 8 * B_Y2);
        }
      }
    }
    TLEND();
  } else {
    asm volatile("barrier.cluster.arrive.relaxed.aligned;" ::: "memory");
    const int wg = warp >> 2, w = warp & 3, g = lane >> 2, t = lane & 3, wtid = tid & 127;
    const bool elect = w == 0 && lane == 0;
    if (p0) {
      float c[36];
      float s0 = 0.f, s1 = 0.f;
#pragma unroll
      for (int i = 0; i < 18; i++) { c[2 * i] = bf_lo(xr[i]); c[2 * i + 1] = bf_hi(xr[i]); s0 += c[2 * i]; s1 += c[2 * i + 1]; }
      const float ml = (s0 + s1) * (1.0f / 36.0f);
      if (tid == 0 && ml != 123.456f) TLREC(28);
      s0 = 0.f; s1 = 0.f;
#pragma unroll
      for (int i = 0; i < 18; i++) { c[2 * i] -= ml; c[2 * i + 1] -= ml; s0 = fmaf(c[2 * i], c[2 * i], s0); s1 = fmaf(c[2 * i + 1], c[2 * i + 1], s1); }
      float m = ml, q = s0 + s1, n2 = 18.f;
#pragma unroll
      for (int o = 1; o < 16; o <<= 1) {
        const float mo = __shfl_xor_sync(0xffffffffu, m, o), qo = __shfl_xor_sync(0xffffffffu, q, o);
        const float dl = m - mo;
        q = fmaf(dl * dl, n2, q + qo);
        m = 0.5f * (m + mo);
        n2 *= 2.f;
      }
      const float var = q * (1.0f / 576.0f);
      float mb, rinv, mb2, rinv2;
      ln_finish(m, var, mb, rinv);
      ln_finish((m - mb) * rinv, var * rinv * rinv, mb2, rinv2);
      const float ca = rinv * rinv2, cb = fmaf(ml - mb, rinv, -mb2) * rinv2;
      uint2* dst = reinterpret_cast<uint2*>(g_h + (size_t)ln_row * D_) + (lane & 15);
#pragma unroll
      for (int j = 0; j < 9; j++)
        dst[16 * j] = make_uint2(pack_bf16(fmaf(c[4 * j], ca, cb), fmaf(c[4 * j + 1], ca, cb)), pack_bf16(fmaf(c[4 * j + 2], ca, cb), fmaf(c[4 * j + 3], ca, cb)));
      if ((lane & 15) == 0) g_stats[ln_row] = make_float4(mb, rinv, 0.f, 0.f);
      bar_sync(2, 256);
      if (tid == 0) { TLREC(29); signal(C_H); TLREC(1); }
      __syncwarp();
    }
    asm volatile("setmaxnreg.inc.sync.aligned.u32 224;");
    asm volatile("barrier.cluster.wait.aligned;" ::: "memory");
    const uint64_t da0 = make_desc(sb + wg * 8192, 8192, 1024, 1);
    if (g1m >= 0) {
      const int frow = ((2 * g1m + rank) * 2 + wg) * 64 + w * 16 + g;
      const float hb0 = 0.5f * __bfloat162float(P.b1[frow]), hb1 = 0.5f * __bfloat162float(P.b1[frow + 8]);
      const uint64_t db0 = make_desc(sb + 16384, 8192, 1024, 1);
      float acc[96];
      Ring r{0, 0};
      uint32_t prev = 0;
      auto step = [&](int first, bool release) {
        mbar_wait(bars + 8 * (B_FULL + r.s), r.ph);
        const uint64_t da = da0 + r.s * (SLOT >> 4), db = db0 + r.s * (SLOT >> 4);
        wg_fence();
        wgmma_ss_n192_t11(acc, da, db, !first);
#pragma unroll
        for (int k = 1; k < 4; k++) wgmma_ss_n192_t11(acc, da + k * 128, db + k * 128, 1);
        wg_commit();
        if (release) { wg_wait<1>(); if (elect) mbar_arrive(bars + 8 * (B_EMPTY + prev)); }
        prev = r.s;
        r.next();
      };
      step(1, false);
      if (tid == 0) TLREC(3);
#pragma unroll 1
      for (int kb = 1; kb < G1_KB - G1_TAIL; kb++) step(0, true);
      if (elect) TLREC(20 + wg);
      if (wg == 1) {
        wg_wait<0>();
        if (elect) mbar_arrive(bars + 8 * (B_EMPTY + prev));
        bar_sync(5, 256);
      }
      step(0, wg == 0);
#pragma unroll 1
      for (int kb = G1_KB - G1_TAIL + 1; kb < G1_KB - 1; kb++) step(0, true);
      step(0, false);
      if (wg == 0) bar_arrive(5, 256);
      wg_wait<1>();
      if (elect) mbar_arrive(bars + 8 * (B_EMPTY + (G1_KB - 2) % NSTAGE));
      wg_wait<0>();
      pin_regs<96>(acc);
      if (elect) TLREC(4 + wg);
      if (wg == 0) { if (elect) mbar_arrive(bars + 8 * (B_EMPTY + (G1_KB - 1) % NSTAGE)); bar_arrive(6, 256); }
      else bar_sync(6, 256);
      const uint32_t stg = wg == 0 ? sb + SM_DED : sb + ((G1_KB - 1) % NSTAGE) * SLOT;
      const uint32_t sa = stg + ((lane >> 4) * 8 + (lane & 7)) * 128 + (((2 * w + ((lane >> 3) & 1)) ^ (lane & 7)) << 4);
      const uint32_t zero = blockIdx.y;
      uint32_t pk[48];
#pragma unroll
      for (int i = 0; i < 48; i++) {
        float hb = (i & 1) ? hb1 : hb0;
        if (i >= GELU_DIST) asm("lop3.b32 %0, %1, %2, %3, 0xea;" : "=f"(hb) : "r"(pk[i - GELU_DIST]), "r"(zero), "f"((i & 1) ? hb1 : hb0));
        pk[i] = pack_bf16(gelu_half(fmaf(acc[2 * i], 0.5f, hb)), gelu_half(fmaf(acc[2 * i + 1], 0.5f, hb)));
        if ((i & 3) == 3) stsm4t(sa + (i >> 2) * 2048, pk[i - 3], pk[i - 2], pk[i - 1], pk[i]);
        if ((i & 15) == 15) { __syncwarp(); if (lane == 0) mbar_arrive(bars + 8 * (B_STG + wg * 3 + (i >> 4))); }
      }
    } else {
      const uint32_t red = wg == 0 ? sb + SM_DED : sb + CV_RED1;
      if (wtid < 8 * CV_NSLOT / 2) sts32(sb + (2 * (wtid >> 3) + wg) * CV_SLOT + CV_KOFF + (wtid & 7) * 4, 0);
      sts32(red + w * CV_REDW + lane * 4, 0);
      bar_sync(3 + wg, 128);
      const uint32_t ko = sb + CV_KOFF + (8 * w + g + t + 1) * 4;
      const uint32_t wr = red + w * CV_REDW + (8 * (3 - t + w) + g) * 4;
      const uint32_t dm0 = (w == 0 && g + t == 7) ? 0xffffu : 0u, dm2 = (w == 0 && g + t == 3) ? 0xffffu : 0u;
      uint32_t a[64];
      uint32_t dd = __bfloat16_as_ushort(P.ssm_D[conv_channel(cvc, wg)]);
      mbar_wait(bars + 8 * (B_CFULL + wg), 0);
      if (tid == 0) TLREC(17);
#define LDA(j, base) { a[2 * (j)] = lds32((base) + ((j) >> 1) * 256 + ((j) & 1) * 16); a[2 * (j) + 1] = lds32((base) + ((j) >> 1) * 256 + ((j) & 1) * 16 + 128); }
#pragma unroll
      for (int j = 0; j < 32; j++) LDA(j, ko + wg * CV_SLOT)
      if (wg == 1) bar_arrive(5, 256);
#pragma unroll 1
      for (int i = wg; i < n_conv; i += 2) {
        const int s = i % CV_NSLOT;
        const int in = i + 2 < n_conv ? i + 2 : i, sn = in % CV_NSLOT;
        const uint64_t db = make_desc(sb + s * CV_SLOT, 4096, 128, 0);
        a[0] = badd2(a[0], dd & dm0); a[2] = badd2(a[2], dd & dm2);
        dd = __bfloat16_as_ushort(P.ssm_D[conv_channel(cvc, in)]);
        float acc[128];
        bar_sync(5 + wg, 256);
        wg_fence();
        wgmma_rs_n256(acc, a, db, 0);
        wgmma_rs_n240(acc, a + 4, db + 16, 1);
        wgmma_rs_n224(acc, a + 8, db + 32, 1);
        wgmma_rs_n208(acc, a + 12, db + 48, 1);
        wgmma_rs_n192(acc, a + 16, db + 64, 1);
        wgmma_rs_n176(acc, a + 20, db + 80, 1);
        wgmma_rs_n160(acc, a + 24, db + 96, 1);
        wgmma_rs_n144(acc, a + 28, db + 112, 1);
        wgmma_rs_n128(acc, a + 32, db + 128, 1);
        wgmma_rs_n112(acc, a + 36, db + 144, 1);
        wgmma_rs_n96(acc, a + 40, db + 160, 1);
        wgmma_rs_n80(acc, a + 44, db + 176, 1);
        wgmma_rs_n64(acc, a + 48, db + 192, 1);
        wgmma_rs_n48(acc, a + 52, db + 208, 1);
        wgmma_rs_n32(acc, a + 56, db + 224, 1);
        wgmma_rs_n16(acc, a + 60, db + 240, 1);
        wg_commit();
        if (i + 1 < n_conv) bar_arrive(5 + (wg ^ 1), 256);
        wg_wait<0>();
        pin_regs<128>(acc);
        if (lane == 0) mbar_arrive(bars + 8 * (B_CEMPTY + s));
        mbar_wait(bars + 8 * (B_CFULL + sn), (in / CV_NSLOT) & 1);
        const uint32_t ka = ko + sn * CV_SLOT;
#pragma unroll
        for (int j = 0; j < 32; j++) {
          const int q = 31 - j;
          if (j < 24) LDA(j, ka)
          sts32(wr + j * 128, q == 31 ? pack_bf16(acc[124], acc[125]) : pack_bf16(acc[4 * q] + acc[(4 * q + 6) & 127], acc[4 * q + 1] + acc[(4 * q + 7) & 127]));
        }
        bar_sync(3 + wg, 128);
        uint4 p[2][4];
#pragma unroll
        for (int c = 0; c < 2; c++)
#pragma unroll
          for (int x = 0; x < 4; x++) p[c][x] = lds128(red + x * CV_REDW + (wtid + 128 * c) * 16);
#pragma unroll
        for (int j = 24; j < 32; j++) LDA(j, ka)
        uint4* yo = reinterpret_cast<uint4*>(g_y + (size_t)conv_channel(cvc, i) * S_) + wtid;
#pragma unroll
        for (int c = 0; c < 2; c++)
          yo[128 * c] = make_uint4(sum4(p[c][0].x, p[c][1].x, p[c][2].x, p[c][3].x), sum4(p[c][0].y, p[c][1].y, p[c][2].y, p[c][3].y),
                                   sum4(p[c][0].z, p[c][1].z, p[c][2].z, p[c][3].z), sum4(p[c][0].w, p[c][1].w, p[c][2].w, p[c][3].w));
      }
#undef LDA
      fence_async_smem();
      bar_sync(3 + wg, 128);
      if (elect) {
        mbar_arrive(bars + 8 * B_EMPTY); mbar_arrive(bars + 8 * (B_EMPTY + 1));
        signal(C_Y);
        TLREC(20 + wg);
      }
      __syncwarp();
    }
    if (g2m >= 0) {
      const int srow = g2m * 128 + wg * 64 + w * 16 + g;
      const uint64_t db0 = make_desc(sb + 16384, 16, 1024, 1);
      float acc[72], acc2[36];
      Ring r{G1_KB % NSTAGE, (G1_KB / NSTAGE) & 1};
      uint32_t prev = 0;
      auto step = [&](int first) {
        mbar_wait(bars + 8 * (B_FULL + r.s), r.ph);
        const uint64_t da = da0 + r.s * (SLOT >> 4), db = db0 + r.s * (SLOT >> 4);
        wg_fence();
        wgmma_ss_n144_t10(acc, da, db, !first);
#pragma unroll
        for (int k = 1; k < 4; k++) wgmma_ss_n144_t10(acc, da + k * 128, db + k * 2, 1);
        wg_commit();
        if (!first) { wg_wait<1>(); if (elect) mbar_arrive(bars + 8 * (B_EMPTY + prev)); }
        prev = r.s;
        r.next();
      };
      step(1);
      if (tid == 0) TLREC(7);
      const float2 st0 = __ldcg(reinterpret_cast<const float2*>(g_stats + srow)), st1 = __ldcg(reinterpret_cast<const float2*>(g_stats + srow + 8));
      const float hb0 = 0.5f * __bfloat162float(P.b2[srow]), hb1 = 0.5f * __bfloat162float(P.b2[srow + 8]);
#pragma unroll 1
      for (int kb = 1; kb < G2_KB - G2_TAIL; kb++) step(0);
      if (elect) TLREC(30 + wg);
      const uint32_t xo = sb + ((XSLOT + 1 + (warp >> 1)) % NSTAGE) * SLOT + G2_BYTES + (warp & 1) * 2304;
      const uint32_t xa = xo + (lane & 15) * 144 + (lane >> 4) * 16;
      uint32_t xx[18], ss[18];
      auto prep = [&]() {
        mbar_wait(bars + 8 * B_XT, 0);
        mbar_wait(bars + 8 * B_Y2, 0);
        const uint32_t ya = sb + SM_DED + wg * 9216 + ((lane >> 4) * 8 + (lane & 7)) * 128 + (((2 * w + ((lane >> 3) & 1)) ^ (lane & 7)) << 4);
#pragma unroll
        for (int q = 0; q < 8; q += 2) { ldsm4(xx + 2 * q, xa + q * 16); ldsm4t(ss + 2 * q, ya + q * 1024); }
        ldsm2(xx + 16, xo + (lane & 15) * 144 + 128);
        ldsm2t(ss + 16, ya - (lane >> 4) * 1024 + 8 * 1024);
        const uint32_t m0 = pack_bf16(st0.x, st0.x), m1 = pack_bf16(st1.x, st1.x);
#pragma unroll
        for (int i = 0; i < 18; i++) ss[i] = bmul2(ln_apply(xx[i], (i & 1) ? m1 : m0, (i & 1) ? st1.y : st0.y), ss[i]);
      };
      if (wg == 1) {
        wg_wait<0>();
        if (elect) mbar_arrive(bars + 8 * (B_EMPTY + XSLOT));
        prep();
        bar_sync(5, 256);
      }
#pragma unroll
      for (int kb = G2_KB - G2_TAIL; kb < G2_KB; kb++) {
        const int p = G1_KB + kb, s = p % NSTAGE;
        mbar_wait(bars + 8 * (B_FULL + s), (p / NSTAGE) & 1);
        wg_fence();
#pragma unroll
        for (int k = 0; k < 4; k++) wgmma_ss_n72_t10(acc, da0 + s * (SLOT >> 4) + k * 128, db0 + s * (SLOT >> 4) + k * 2, 1);
        wg_commit();
        if (kb == G2_KB - G2_TAIL) { wg_wait<1>(); if (tid == 0) mbar_arrive(bars + 8 * (B_EMPTY + XSLOT)); }
      }
      bar_arrive(5 + wg, 256);
      wg_wait<0>();
      pin_regs<72>(acc);
      const uint32_t xz = sb + XSLOT * SLOT + wg * 18432 + wtid * 16;
      mbar_wait(bars + 8 * B_XRDY, 0);
      {
        const uint32_t rz = mapa(xz, rank ^ 1), rb = mapa(bars + 8 * (B_XFULL + wg), rank ^ 1);
#pragma unroll
        for (int q = 0; q < 9; q++)
          asm volatile("st.async.weak.shared::cluster.mbarrier::complete_tx::bytes.v4.f32 [%0], {%1,%2,%3,%4}, [%5];"
                       :: "r"(rz + q * 2048), "f"(acc[4 * q]), "f"(acc[4 * q + 1]), "f"(acc[4 * q + 2]), "f"(acc[4 * q + 3]), "r"(rb) : "memory");
      }
      if (wg == 0) prep();
      bar_sync(6 - wg, 256);
      wg_fence();
#pragma unroll
      for (int kb = G2_KB - G2_TAIL; kb < G2_KB; kb++) {
        const int s = (G1_KB + kb) % NSTAGE;
#pragma unroll
        for (int k = 0; k < 4; k++)
          wgmma_ss_n72_t10(acc2, da0 + s * (SLOT >> 4) + k * 128, db0 + s * (SLOT >> 4) + (9216 >> 4) + k * 2, kb != G2_KB - G2_TAIL || k != 0);
      }
      wg_commit();
      if (wg == 0) bar_arrive(5, 256);
      mbar_wait_cluster(bars + 8 * (B_XFULL + wg), 0);
#pragma unroll
      for (int q = 0; q < 9; q++) {
        const float4 pv = lds128f(xz + q * 2048);
        acc[36 + 4 * q] = fmaf(acc[36 + 4 * q] + pv.x, 0.5f, hb0); acc[37 + 4 * q] = fmaf(acc[37 + 4 * q] + pv.y, 0.5f, hb0);
        acc[38 + 4 * q] = fmaf(acc[38 + 4 * q] + pv.z, 0.5f, hb1); acc[39 + 4 * q] = fmaf(acc[39 + 4 * q] + pv.w, 0.5f, hb1);
      }
      wg_wait<0>();
      pin_regs<36>(acc2);
      if (elect) TLREC(9 + wg);
      uint32_t ob[18];
#pragma unroll
      for (int i = 0; i < 18; i++)
        ob[i] = bfma2(ss[i], pack_bf16(silu_half(fmaf(acc2[2 * i], 0.5f, acc[36 + 2 * i])), silu_half(fmaf(acc2[2 * i + 1], 0.5f, acc[37 + 2 * i]))), xx[i]);
#pragma unroll
      for (int q = 0; q < 8; q += 2) stsm4(xa + q * 16, ob[2 * q], ob[2 * q + 1], ob[2 * q + 2], ob[2 * q + 3]);
      stsm2(xo + (lane & 15) * 144 + 128, ob[16], ob[17]);
      fence_async_smem();
      __syncwarp();
      if (lane == 0) {
        tma2d_store(&P.m_out, xo, dk, srow);
        bulk_commit();
        bulk_wait_read();
      }
      if (elect) TLREC(11 + wg);
    }
    TLEND();
  }
}

typedef CUresult (*EncodeFn)(CUtensorMap*, CUtensorMapDataType, cuuint32_t, void*, const cuuint64_t*, const cuuint64_t*, const cuuint32_t*,
                             const cuuint32_t*, CUtensorMapInterleave, CUtensorMapSwizzle, CUtensorMapL2promotion, CUtensorMapFloatOOBfill);

void make_map(EncodeFn fn, CUtensorMap* m, const void* ptr, int rank, const cuuint64_t* dims, const cuuint64_t* strides, const cuuint32_t* box,
              CUtensorMapSwizzle sw) {
  const cuuint32_t es[3] = {1, 1, 1};
  fn(m, CU_TENSOR_MAP_DATA_TYPE_BFLOAT16, rank, const_cast<void*>(ptr), dims, strides, box, es, CU_TENSOR_MAP_INTERLEAVE_NONE, sw,
     CU_TENSOR_MAP_L2_PROMOTION_L2_256B, CU_TENSOR_MAP_FLOAT_OOB_FILL_NONE);
}

void make_roles(Roles& R) {
  int c1 = 0, ncv = 2;
  for (int g = 0; g < 8; g++)
    for (int c = 0; c < 66; c++) {
      const int tp = (c + 62) % 66;
      int gg, idx;
      if (tp < 32) { gg = tp % 8; idx = tp / 8; }
      else if (tp < 60) { gg = 1 + (tp - 32) % 7; idx = 4 + (tp - 32) / 7; }
      else if (tp < 62) { gg = 6 + tp - 60; idx = 8; }
      else { gg = 0; idx = 4 + tp - 62; }
      if (gg != g) continue;
      Role& r = R.r[c];
      if (idx < 8) { r.g2m = (int8_t)(2 * g + idx / 4); r.g2n = (int8_t)(idx % 4); }
      else { r.g2m = -1; r.g2n = 0; }
      if (idx < (g < 2 ? 6 : 7)) { r.g1m = (int8_t)(c1 / 3); r.g1n = (int8_t)(c1 % 3); c1++; }
      else { r.g1m = (int8_t)(-1 - (idx == 8 ? tp - 60 : ncv++)); r.g1n = 0; }
    }
}

}

extern "C" void kernel_launch(void* const* d_in, const int* in_sizes, int n_in, void* d_out, int out_size) {
  static Params P;
  static const void* cached[4] = {nullptr, nullptr, nullptr, nullptr};
  if (cached[0] != d_in[7] || cached[1] != d_in[9] || cached[2] != d_out || cached[3] != d_in[0]) {
    void* fp = nullptr;
    cudaDriverEntryPointQueryResult qr;
    cudaGetDriverEntryPoint("cuTensorMapEncodeTiled", &fp, cudaEnableDefault, &qr);
    EncodeFn fn = (EncodeFn)fp;
    void *ph, *pu, *py;
    cudaGetSymbolAddress(&py, g_y);
    cudaGetSymbolAddress(&ph, g_h);
    cudaGetSymbolAddress(&pu, g_u);
    { cuuint64_t d[3] = {64, S_, F_ / 64}, s[2] = {F_ * 2, 128}; cuuint32_t b[3] = {64, 64, 2}; make_map(fn, &P.m_w1, d_in[7], 3, d, s, b, CU_TENSOR_MAP_SWIZZLE_128B); }
    { cuuint64_t d[3] = {64, S_, D_ / 64}, s[2] = {D_ * 2, 128}; cuuint32_t b[3] = {64, 64, 3}; make_map(fn, &P.m_h, ph, 3, d, s, b, CU_TENSOR_MAP_SWIZZLE_128B); }
    { cuuint64_t d[2] = {F_, D_}, s[1] = {F_ * 2}; cuuint32_t b[2] = {64, 64}; make_map(fn, &P.m_ust, pu, 2, d, s, b, CU_TENSOR_MAP_SWIZZLE_128B); }
    { cuuint64_t d[3] = {64, F_, S_ / 64}, s[2] = {S_ * 2, 128}; cuuint32_t b[3] = {64, 64, 2}; make_map(fn, &P.m_w2, d_in[9], 3, d, s, b, CU_TENSOR_MAP_SWIZZLE_128B); }
    { cuuint64_t d[2] = {F_, D_}, s[1] = {F_ * 2}; cuuint32_t b[2] = {64, 72}; make_map(fn, &P.m_uld, pu, 2, d, s, b, CU_TENSOR_MAP_SWIZZLE_128B); }
    { cuuint64_t d[2] = {D_, S_}, s[1] = {D_ * 2}; cuuint32_t b[2] = {72, 16}; make_map(fn, &P.m_out, d_out, 2, d, s, b, CU_TENSOR_MAP_SWIZZLE_NONE);
      make_map(fn, &P.m_x, d_in[0], 2, d, s, b, CU_TENSOR_MAP_SWIZZLE_NONE); }
    { cuuint64_t d[2] = {S_, D_}, s[1] = {S_ * 2}; cuuint32_t b[2] = {64, 72}; make_map(fn, &P.m_y, py, 2, d, s, b, CU_TENSOR_MAP_SWIZZLE_128B); }
    make_roles(P.roles);
    cudaFuncSetAttribute(fused_kernel, cudaFuncAttributeMaxDynamicSharedMemorySize, SM_TOTAL);
    cached[0] = d_in[7]; cached[1] = d_in[9]; cached[2] = d_out; cached[3] = d_in[0];
  }
  P.x = (const __nv_bfloat16*)d_in[0]; P.k = (const __nv_bfloat16*)d_in[1]; P.v = (const __nv_bfloat16*)d_in[2];
  P.shift_k = (const __nv_bfloat16*)d_in[3]; P.ssm_k = (const __nv_bfloat16*)d_in[4]; P.ssm_D = (const __nv_bfloat16*)d_in[5];
  P.b1 = (const __nv_bfloat16*)d_in[8]; P.b2 = (const __nv_bfloat16*)d_in[10];
  fused_kernel<<<132, 384, SM_TOTAL>>>(P);
}
```

```cpp
#include <cuda_runtime.h>
#include <cuda.h>
#include <cuda_bf16.h>
#include <stdint.h>

namespace {

constexpr int S_ = 2048, D_ = 576, F_ = 4608;
constexpr int NSTAGE = 5, SLOT = 40960;
constexpr int G1_KB = 32, G2_KB = 36;
constexpr int G1_BYTES = 40960, G2_BYTES = 16384 + 18432;
constexpr int N_CONV_CTA = 24, N_SHORT = 18, N_LONG_EXTRA = 9, CH_FILL = N_CONV_CTA * N_SHORT + 4 * N_LONG_EXTRA;
static_assert(CH_FILL + 108 == D_, "conv split");
constexpr int KV_ROUNDS = 6;
#define G1T 5
constexpr int G1_TAIL = G1T, G2_TAIL = 4;
#define XD0 300
#define XD 300
#define W1T0 200
#define W1D 900
#define KVT0 200
#define PF1 0
#define PF2 0

constexpr int SM_DED = NSTAGE * SLOT;
constexpr int SM_KVS = SM_DED + 18944;
constexpr int SM_BAR = SM_KVS + 6144;
constexpr int SM_TOTAL = SM_BAR + 256 + 1024;
constexpr int CV_NSLOT = 4, CV_KOFF = 8192, CV_SLOT = 8192 + 4224;
constexpr int CV_REDW = 2112 * 2, CV_RED1 = CV_NSLOT * CV_SLOT;
static_assert(CV_RED1 + 4 * CV_REDW <= 2 * SLOT, "conv overlay");
static_assert(G1_KB % NSTAGE == 2, "slots 0 and 1 hold the last two GEMM1 k-blocks");
constexpr int XSLOT = (G1_KB + G2_KB) % NSTAGE;
constexpr int B_FULL = 0, B_EMPTY = NSTAGE, B_CFULL = 2 * NSTAGE, B_STG = B_CFULL + CV_NSLOT  , B_CEMPTY = B_STG,
              B_FILL = B_STG + 6, B_YDONE = B_FILL + 1, B_XRDY = B_YDONE + 1, B_XFULL = B_XRDY + 1  , B_XT = B_XFULL + 2,
              B_Y2 = B_XT + 1, B_KVDONE = B_Y2 + 1, B_DED = B_KVDONE + 1, B_GO = B_DED + 1;
static_assert(B_GO < 32, "barrier page");
constexpr int C_H = 0  , C_KV = 8, C_U = C_KV + KV_ROUNDS  , C_Y = C_U + 12, C_COUNT = C_Y + 1;

struct Role {
  int8_t g1m;
  int8_t g1n;
  int8_t g2m;
  int8_t g2n;
};
struct Roles { Role r[66]; };

struct Params {
  const __nv_bfloat16 *x, *k, *v, *shift_k, *ssm_k, *ssm_D, *b1, *b2;
  Roles roles;
  CUtensorMap m_w1, m_h, m_ust, m_w2, m_uld, m_out, m_x, m_y, m_ub;
};

__device__ __align__(1024) __nv_bfloat16 g_h[S_ * D_];
__device__ __align__(1024) __nv_bfloat16 g_ub[D_ * 4096];
__device__ __align__(1024) __nv_bfloat16 g_y[D_ * S_];
__device__ __align__(1024) __nv_bfloat16 g_u[D_ * F_];
__device__ __align__(128) float4 g_stats[S_];
__device__ __align__(128) uint32_t g_cnt[C_COUNT * 32];
__device__ __align__(128) uint32_t g_epoch;
#define TLREC(i) do { } while (0)
#define TLEND() do { } while (0)

__device__ __forceinline__ uint32_t smem_u32(const void* p) { return (uint32_t)__cvta_generic_to_shared(p); }
__device__ __forceinline__ void mbar_init(uint32_t bar, uint32_t cnt) { asm volatile("mbarrier.init.shared::cta.b64 [%0], %1;" :: "r"(bar), "r"(cnt) : "memory"); }
__device__ __forceinline__ void mbar_expect_tx(uint32_t bar, uint32_t bytes) { asm volatile("mbarrier.arrive.expect_tx.shared::cta.b64 _, [%0], %1;" :: "r"(bar), "r"(bytes) : "memory"); }
__device__ __forceinline__ void mbar_arrive(uint32_t bar) { asm volatile("mbarrier.arrive.shared::cta.b64 _, [%0];" :: "r"(bar) : "memory"); }
__device__ __forceinline__ uint32_t mapa(uint32_t addr, uint32_t cta) { uint32_t r; asm volatile("mapa.shared::cluster.u32 %0, %1, %2;" : "=r"(r) : "r"(addr), "r"(cta)); return r; }
__device__ __forceinline__ void mbar_arrive_remote(uint32_t rbar) { asm volatile("mbarrier.arrive.shared::cluster.b64 _, [%0];" :: "r"(rbar) : "memory"); }
__device__ __forceinline__ void mbar_wait(uint32_t bar, uint32_t parity) {
  asm volatile("{\n .reg .pred p;\n .reg .u32 c;\n mov.u32 c, 0;\n"
               "W_%=:\n mbarrier.try_wait.parity.shared::cta.b64 p, [%0], %1;\n @p bra D_%=;\n"
               " add.u32 c, c, 1;\n setp.lt.u32 p, c, 2000000;\n @p bra W_%=;\n trap;\n D_%=:\n }" :: "r"(bar), "r"(parity) : "memory");
}
__device__ __forceinline__ void mbar_wait_cluster(uint32_t bar, uint32_t parity) {
  asm volatile("{\n .reg .pred p;\n .reg .u32 c;\n mov.u32 c, 0;\n"
               "W_%=:\n mbarrier.try_wait.parity.acquire.cluster.shared::cta.b64 p, [%0], %1;\n @p bra D_%=;\n"
               " add.u32 c, c, 1;\n setp.lt.u32 p, c, 2000000;\n @p bra W_%=;\n trap;\n D_%=:\n }" :: "r"(bar), "r"(parity) : "memory");
}
__device__ __forceinline__ void tma2d(uint32_t dst, const CUtensorMap* m, int c0, int c1, uint32_t bar) {
  asm volatile("cp.async.bulk.tensor.2d.shared::cluster.global.mbarrier::complete_tx::bytes [%0], [%1, {%3, %4}], [%2];"
               :: "r"(dst), "l"(m), "r"(bar), "r"(c0), "r"(c1) : "memory");
}
__device__ __forceinline__ void tma3d(uint32_t dst, const CUtensorMap* m, int c0, int c1, int c2, uint32_t bar) {
  asm volatile("cp.async.bulk.tensor.3d.shared::cluster.global.mbarrier::complete_tx::bytes [%0], [%1, {%3, %4, %5}], [%2];"
               :: "r"(dst), "l"(m), "r"(bar), "r"(c0), "r"(c1), "r"(c2) : "memory");
}
__device__ __forceinline__ void pf3d(const CUtensorMap* m, int c0, int c1, int c2) {
  asm volatile("cp.async.bulk.prefetch.tensor.3d.L2.global [%0, {%1, %2, %3}];" :: "l"(m), "r"(c0), "r"(c1), "r"(c2) : "memory");
}
__device__ __forceinline__ void tma2d_store(const CUtensorMap* m, uint32_t src, int c0, int c1) {
  asm volatile("cp.async.bulk.tensor.2d.global.shared::cta.bulk_group [%0, {%2, %3}], [%1];" :: "l"(m), "r"(src), "r"(c0), "r"(c1) : "memory");
}
__device__ __forceinline__ void bulk_load(uint32_t dst, const void* src, uint32_t bytes, uint32_t bar) {
  asm volatile("cp.async.bulk.shared::cluster.global.mbarrier::complete_tx::bytes [%0], [%1], %2, [%3];" :: "r"(dst), "l"(src), "r"(bytes), "r"(bar) : "memory");
}
__device__ __forceinline__ void bulk_store(void* dst, uint32_t src, uint32_t bytes) {
  asm volatile("cp.async.bulk.global.shared::cta.bulk_group [%0], [%1], %2;" :: "l"(dst), "r"(src), "r"(bytes) : "memory");
}
__device__ __forceinline__ void tma3d_store(const CUtensorMap* m, uint32_t src, int c0, int c1, int c2) {
  asm volatile("cp.async.bulk.tensor.3d.global.shared::cta.bulk_group [%0, {%2, %3, %4}], [%1];" :: "l"(m), "r"(src), "r"(c0), "r"(c1), "r"(c2) : "memory");
}
__device__ __forceinline__ void bulk_commit() { asm volatile("cp.async.bulk.commit_group;" ::: "memory"); }
__device__ __forceinline__ void bulk_wait_all() { asm volatile("cp.async.bulk.wait_group 0;" ::: "memory"); }
__device__ __forceinline__ void bulk_wait_read() { asm volatile("cp.async.bulk.wait_group.read 0;" ::: "memory"); }
__device__ __forceinline__ void fence_async_smem() { asm volatile("fence.proxy.async.shared::cta;" ::: "memory"); }
__device__ __forceinline__ void fence_async_global() { asm volatile("fence.proxy.async.global;" ::: "memory"); }
__device__ __forceinline__ void st_flag(uint32_t* p, uint32_t v) { asm volatile("st.relaxed.gpu.global.u32 [%0], %1;" :: "l"(p), "r"(v) : "memory"); }
__device__ __forceinline__ uint32_t ld_flag(const uint32_t* p) { uint32_t v; asm volatile("ld.relaxed.gpu.global.u32 %0, [%1];" : "=r"(v) : "l"(p) : "memory"); return v; }
__device__ __forceinline__ void signal(int c) { asm volatile("red.release.gpu.global.add.u32 [%0], 1;" :: "l"(g_cnt + c * 32) : "memory"); }
__device__ __forceinline__ void signal_stored(int c) { asm volatile("red.relaxed.gpu.global.add.u32 [%0], 1;" :: "l"(g_cnt + c * 32) : "memory"); }
__device__ __forceinline__ bool reached(int c, uint32_t target) {
  uint32_t v; asm volatile("ld.acquire.gpu.global.u32 %0, [%1];" : "=r"(v) : "l"(g_cnt + c * 32) : "memory");
  return (int32_t)(v - target) >= 0;
}
__device__ __forceinline__ uint32_t clk() { uint32_t c; asm volatile("mov.u32 %0, %%clock;" : "=r"(c)); return c; }
__device__ __forceinline__ void pace(uint32_t t0, uint32_t dt) { while (clk() - t0 < dt) { } }
__device__ __forceinline__ int cta_id() { int c; asm volatile("mov.u32 %0, %%ctaid.x;" : "=r"(c)); return c; }
template <bool SLOW = false> __device__ __forceinline__ void await(int c, uint32_t target) {
  uint32_t n = 0;
  while (true) {
    uint32_t v; asm volatile("ld.acquire.gpu.global.u32 %0, [%1];" : "=r"(v) : "l"(g_cnt + c * 32) : "memory");
    if ((int32_t)(v - target) >= 0) break;
    if (SLOW) __nanosleep(300);
    if (++n > 4000000u) __trap();
  }
}
__device__ __forceinline__ void bar_sync(int id, int n) { asm volatile("bar.sync %0, %1;" :: "r"(id), "r"(n) : "memory"); }
__device__ __forceinline__ void bar_arrive(int id, int n) { asm volatile("bar.arrive %0, %1;" :: "r"(id), "r"(n) : "memory"); }
__device__ __forceinline__ void wg_fence() { asm volatile("wgmma.fence.sync.aligned;" ::: "memory"); }
__device__ __forceinline__ void wg_commit() { asm volatile("wgmma.commit_group.sync.aligned;" ::: "memory"); }
template <int N> __device__ __forceinline__ void wg_wait() { asm volatile("wgmma.wait_group.sync.aligned %0;" :: "n"(N) : "memory"); }
template <int N> __device__ __forceinline__ void pin_regs(float* a) {
#pragma unroll
  for (int i = 0; i < N; i++) asm volatile("" : "+f"(a[i]) :: "memory");
}
__device__ __forceinline__ uint64_t make_desc(uint32_t addr, uint32_t lbo, uint32_t sbo, uint32_t swz) {
  return (uint64_t)((addr & 0x3FFFF) >> 4) | ((uint64_t)(lbo >> 4) << 16) | ((uint64_t)(sbo >> 4) << 32) | ((uint64_t)swz << 62);
}
__device__ __forceinline__ uint32_t pack_bf16(float lo, float hi) { uint32_t r; asm("cvt.rn.bf16x2.f32 %0, %1, %2;" : "=r"(r) : "f"(hi), "f"(lo)); return r; }
__device__ __forceinline__ float bf_lo(uint32_t p) { return __uint_as_float(p << 16); }
__device__ __forceinline__ float bf_hi(uint32_t p) { return __uint_as_float(p & 0xffff0000u); }
__device__ __forceinline__ float round_bf16(float v) { return bf_lo(pack_bf16(v, 0.f)); }
__device__ __forceinline__ uint32_t bmul2(uint32_t a, uint32_t b) { uint32_t r; asm("mul.rn.bf16x2 %0, %1, %2;" : "=r"(r) : "r"(a), "r"(b)); return r; }
__device__ __forceinline__ uint32_t badd2(uint32_t a, uint32_t b) { uint32_t r; asm("add.rn.bf16x2 %0, %1, %2;" : "=r"(r) : "r"(a), "r"(b)); return r; }
__device__ __forceinline__ uint32_t bfma2(uint32_t a, uint32_t b, uint32_t c) { uint32_t r; asm("fma.rn.bf16x2 %0, %1, %2, %3;" : "=r"(r) : "r"(a), "r"(b), "r"(c)); return r; }
__device__ __forceinline__ uint32_t bsub2(uint32_t a, uint32_t b) { uint32_t r; asm("sub.rn.bf16x2 %0, %1, %2;" : "=r"(r) : "r"(a), "r"(b)); return r; }
__device__ __forceinline__ float tanh_fast(float v) { float r; asm("tanh.approx.f32 %0, %1;" : "=f"(r) : "f"(v)); return r; }
__device__ __forceinline__ float gelu_half(float h) {
  return fmaf(h, tanh_fast(h * fmaf(h * h, 8.0f * 0.7978845608028654f * 0.044715f, 2.0f * 0.7978845608028654f)), h);
}
__device__ __forceinline__ float silu_half(float h) { return fmaf(h, tanh_fast(h), h); }
__device__ __forceinline__ uint32_t ldg32(const void* p) { uint32_t v; asm volatile("ld.global.nc.u32 %0, [%1];" : "=r"(v) : "l"(p)); return v; }
__device__ __forceinline__ uint32_t lds32(uint32_t a) { uint32_t v; asm volatile("ld.shared.u32 %0, [%1];" : "=r"(v) : "r"(a) : "memory"); return v; }
__device__ __forceinline__ float4 lds128f(uint32_t a) { float4 v; asm volatile("ld.shared.v4.f32 {%0,%1,%2,%3}, [%4];" : "=f"(v.x), "=f"(v.y), "=f"(v.z), "=f"(v.w) : "r"(a) : "memory"); return v; }
__device__ __forceinline__ uint4 lds128(uint32_t a) { uint4 v; asm volatile("ld.shared.v4.u32 {%0,%1,%2,%3}, [%4];" : "=r"(v.x), "=r"(v.y), "=r"(v.z), "=r"(v.w) : "r"(a) : "memory"); return v; }
__device__ __forceinline__ void sts64(uint32_t a, uint32_t x, uint32_t y) { asm volatile("st.shared.v2.u32 [%0], {%1,%2};" :: "r"(a), "r"(x), "r"(y) : "memory"); }
__device__ __forceinline__ void sts128(uint32_t a, uint32_t x, uint32_t y, uint32_t z, uint32_t w) {
  asm volatile("st.shared.v4.u32 [%0], {%1,%2,%3,%4};" :: "r"(a), "r"(x), "r"(y), "r"(z), "r"(w) : "memory");
}
__device__ __forceinline__ void sts32(uint32_t a, uint32_t v) { asm volatile("st.shared.u32 [%0], %1;" :: "r"(a), "r"(v) : "memory"); }
__device__ __forceinline__ void ldsm4(uint32_t* r, uint32_t a) {
  asm volatile("ldmatrix.sync.aligned.m8n8.x4.shared.b16 {%0,%1,%2,%3}, [%4];" : "=r"(r[0]), "=r"(r[1]), "=r"(r[2]), "=r"(r[3]) : "r"(a) : "memory");
}
__device__ __forceinline__ void ldsm2(uint32_t* r, uint32_t a) {
  asm volatile("ldmatrix.sync.aligned.m8n8.x2.shared.b16 {%0,%1}, [%2];" : "=r"(r[0]), "=r"(r[1]) : "r"(a) : "memory");
}
__device__ __forceinline__ void ldsm4t(uint32_t* r, uint32_t a) {
  asm volatile("ldmatrix.sync.aligned.m8n8.x4.trans.shared.b16 {%0,%1,%2,%3}, [%4];" : "=r"(r[0]), "=r"(r[1]), "=r"(r[2]), "=r"(r[3]) : "r"(a) : "memory");
}
__device__ __forceinline__ void ldsm2t(uint32_t* r, uint32_t a) {
  asm volatile("ldmatrix.sync.aligned.m8n8.x2.trans.shared.b16 {%0,%1}, [%2];" : "=r"(r[0]), "=r"(r[1]) : "r"(a) : "memory");
}
__device__ __forceinline__ void stsm4(uint32_t a, uint32_t r0, uint32_t r1, uint32_t r2, uint32_t r3) {
  asm volatile("stmatrix.sync.aligned.m8n8.x4.shared.b16 [%0], {%1,%2,%3,%4};" :: "r"(a), "r"(r0), "r"(r1), "r"(r2), "r"(r3) : "memory");
}
__device__ __forceinline__ void stsm2(uint32_t a, uint32_t r0, uint32_t r1) {
  asm volatile("stmatrix.sync.aligned.m8n8.x2.shared.b16 [%0], {%1,%2};" :: "r"(a), "r"(r0), "r"(r1) : "memory");
}
__device__ __forceinline__ void stsm4t(uint32_t a, uint32_t r0, uint32_t r1, uint32_t r2, uint32_t r3) {
  asm volatile("stmatrix.sync.aligned.m8n8.x4.trans.shared.b16 [%0], {%1,%2,%3,%4};" :: "r"(a), "r"(r0), "r"(r1), "r"(r2), "r"(r3) : "memory");
}

__device__ __forceinline__ void wgmma_ss_n144_t10(float* d, uint64_t da, uint64_t db, int sd) {
  asm volatile("{ .reg .pred p; setp.ne.b32 p, %74, 0;\n"
      "wgmma.mma_async.sync.aligned.m64n144k16.f32.bf16.bf16 {"
      "%0,%1,%2,%3,%4,%5,%6,%7,%8,%9,%10,%11,%12,%13,%14,%15,"
      "%16,%17,%18,%19,%20,%21,%22,%23,%24,%25,%26,%27,%28,%29,%30,%31,"
      "%32,%33,%34,%35,%36,%37,%38,%39,%40,%41,%42,%43,%44,%45,%46,%47,"
      "%48,%49,%50,%51,%52,%53,%54,%55,%56,%57,%58,%59,%60,%61,%62,%63,"
      "%64,%65,%66,%67,%68,%69,%70,%71"
      "}, %72, %73, p, 1, 1, 1, 0; }"
    : "+f"(d[0]), "+f"(d[1]), "+f"(d[2]), "+f"(d[3]), "+f"(d[4]), "+f"(d[5]), "+f"(d[6]), "+f"(d[7]),
      "+f"(d[8]), "+f"(d[9]), "+f"(d[10]), "+f"(d[11]), "+f"(d[12]), "+f"(d[13]), "+f"(d[14]), "+f"(d[15]),
      "+f"(d[16]), "+f"(d[17]), "+f"(d[18]), "+f"(d[19]), "+f"(d[20]), "+f"(d[21]), "+f"(d[22]), "+f"(d[23]),
      "+f"(d[24]), "+f"(d[25]), "+f"(d[26]), "+f"(d[27]), "+f"(d[28]), "+f"(d[29]), "+f"(d[30]), "+f"(d[31]),
      "+f"(d[32]), "+f"(d[33]), "+f"(d[34]), "+f"(d[35]), "+f"(d[36]), "+f"(d[37]), "+f"(d[38]), "+f"(d[39]),
      "+f"(d[40]), "+f"(d[41]), "+f"(d[42]), "+f"(d[43]), "+f"(d[44]), "+f"(d[45]), "+f"(d[46]), "+f"(d[47]),
      "+f"(d[48]), "+f"(d[49]), "+f"(d[50]), "+f"(d[51]), "+f"(d[52]), "+f"(d[53]), "+f"(d[54]), "+f"(d[55]),
      "+f"(d[56]), "+f"(d[57]), "+f"(d[58]), "+f"(d[59]), "+f"(d[60]), "+f"(d[61]), "+f"(d[62]), "+f"(d[63]),
      "+f"(d[64]), "+f"(d[65]), "+f"(d[66]), "+f"(d[67]), "+f"(d[68]), "+f"(d[69]), "+f"(d[70]), "+f"(d[71])
    : "l"(da), "l"(db), "r"(sd));
}

__device__ __forceinline__ void wgmma_ss_n192_t11(float* d, uint64_t da, uint64_t db, int sd) {
  asm volatile("{ .reg .pred p; setp.ne.b32 p, %98, 0;\n"
      "wgmma.mma_async.sync.aligned.m64n192k16.f32.bf16.bf16 {"
      "%0,%1,%2,%3,%4,%5,%6,%7,%8,%9,%10,%11,%12,%13,%14,%15,"
      "%16,%17,%18,%19,%20,%21,%22,%23,%24,%25,%26,%27,%28,%29,%30,%31,"
      "%32,%33,%34,%35,%36,%37,%38,%39,%40,%41,%42,%43,%44,%45,%46,%47,"
      "%48,%49,%50,%51,%52,%53,%54,%55,%56,%57,%58,%59,%60,%61,%62,%63,"
      "%64,%65,%66,%67,%68,%69,%70,%71,%72,%73,%74,%75,%76,%77,%78,%79,"
      "%80,%81,%82,%83,%84,%85,%86,%87,%88,%89,%90,%91,%92,%93,%94,%95"
      "}, %96, %97, p, 1, 1, 1, 1; }"
    : "+f"(d[0]), "+f"(d[1]), "+f"(d[2]), "+f"(d[3]), "+f"(d[4]), "+f"(d[5]), "+f"(d[6]), "+f"(d[7]),
      "+f"(d[8]), "+f"(d[9]), "+f"(d[10]), "+f"(d[11]), "+f"(d[12]), "+f"(d[13]), "+f"(d[14]), "+f"(d[15]),
      "+f"(d[16]), "+f"(d[17]), "+f"(d[18]), "+f"(d[19]), "+f"(d[20]), "+f"(d[21]), "+f"(d[22]), "+f"(d[23]),
      "+f"(d[24]), "+f"(d[25]), "+f"(d[26]), "+f"(d[27]), "+f"(d[28]), "+f"(d[29]), "+f"(d[30]), "+f"(d[31]),
      "+f"(d[32]), "+f"(d[33]), "+f"(d[34]), "+f"(d[35]), "+f"(d[36]), "+f"(d[37]), "+f"(d[38]), "+f"(d[39]),
      "+f"(d[40]), "+f"(d[41]), "+f"(d[42]), "+f"(d[43]), "+f"(d[44]), "+f"(d[45]), "+f"(d[46]), "+f"(d[47]),
      "+f"(d[48]), "+f"(d[49]), "+f"(d[50]), "+f"(d[51]), "+f"(d[52]), "+f"(d[53]), "+f"(d[54]), "+f"(d[55]),
      "+f"(d[56]), "+f"(d[57]), "+f"(d[58]), "+f"(d[59]), "+f"(d[60]), "+f"(d[61]), "+f"(d[62]), "+f"(d[63]),
      "+f"(d[64]), "+f"(d[65]), "+f"(d[66]), "+f"(d[67]), "+f"(d[68]), "+f"(d[69]), "+f"(d[70]), "+f"(d[71]),
      "+f"(d[72]), "+f"(d[73]), "+f"(d[74]), "+f"(d[75]), "+f"(d[76]), "+f"(d[77]), "+f"(d[78]), "+f"(d[79]),
      "+f"(d[80]), "+f"(d[81]), "+f"(d[82]), "+f"(d[83]), "+f"(d[84]), "+f"(d[85]), "+f"(d[86]), "+f"(d[87]),
      "+f"(d[88]), "+f"(d[89]), "+f"(d[90]), "+f"(d[91]), "+f"(d[92]), "+f"(d[93]), "+f"(d[94]), "+f"(d[95])
    : "l"(da), "l"(db), "r"(sd));
}

__device__ __forceinline__ void wgmma_ss_n72_t10(float* d, uint64_t da, uint64_t db, int sd) {
  asm volatile("{ .reg .pred p; setp.ne.b32 p, %38, 0;\n"
      "wgmma.mma_async.sync.aligned.m64n72k16.f32.bf16.bf16 {"
      "%0,%1,%2,%3,%4,%5,%6,%7,%8,%9,%10,%11,%12,%13,%14,%15,"
      "%16,%17,%18,%19,%20,%21,%22,%23,%24,%25,%26,%27,%28,%29,%30,%31,"
      "%32,%33,%34,%35"
      "}, %36, %37, p, 1, 1, 1, 0; }"
    : "+f"(d[0]), "+f"(d[1]), "+f"(d[2]), "+f"(d[3]), "+f"(d[4]), "+f"(d[5]), "+f"(d[6]), "+f"(d[7]),
      "+f"(d[8]), "+f"(d[9]), "+f"(d[10]), "+f"(d[11]), "+f"(d[12]), "+f"(d[13]), "+f"(d[14]), "+f"(d[15]),
      "+f"(d[16]), "+f"(d[17]), "+f"(d[18]), "+f"(d[19]), "+f"(d[20]), "+f"(d[21]), "+f"(d[22]), "+f"(d[23]),
      "+f"(d[24]), "+f"(d[25]), "+f"(d[26]), "+f"(d[27]), "+f"(d[28]), "+f"(d[29]), "+f"(d[30]), "+f"(d[31]),
      "+f"(d[32]), "+f"(d[33]), "+f"(d[34]), "+f"(d[35])
    : "l"(da), "l"(db), "r"(sd));
}

__device__ __forceinline__ void wgmma_rs_n16(float* d, const uint32_t* a, uint64_t db, int sd) {
  asm volatile("{ .reg .pred p; setp.ne.b32 p, %13, 0;\n"
      "wgmma.mma_async.sync.aligned.m64n16k16.f32.bf16.bf16 {"
      "%0,%1,%2,%3,%4,%5,%6,%7"
      "}, {%8,%9,%10,%11}, %12, p, 1, 1, 0; }"
    : "+f"(d[0]), "+f"(d[1]), "+f"(d[2]), "+f"(d[3]), "+f"(d[4]), "+f"(d[5]), "+f"(d[6]), "+f"(d[7])
    : "r"(a[0]), "r"(a[1]), "r"(a[2]), "r"(a[3]), "l"(db), "r"(sd));
}

__device__ __forceinline__ void wgmma_rs_n32(float* d, const uint32_t* a, uint64_t db, int sd) {
  asm volatile("{ .reg .pred p; setp.ne.b32 p, %21, 0;\n"
      "wgmma.mma_async.sync.aligned.m64n32k16.f32.bf16.bf16 {"
      "%0,%1,%2,%3,%4,%5,%6,%7,%8,%9,%10,%11,%12,%13,%14,%15"
      "}, {%16,%17,%18,%19}, %20, p, 1, 1, 0; }"
    : "+f"(d[0]), "+f"(d[1]), "+f"(d[2]), "+f"(d[3]), "+f"(d[4]), "+f"(d[5]), "+f"(d[6]), "+f"(d[7]),
      "+f"(d[8]), "+f"(d[9]), "+f"(d[10]), "+f"(d[11]), "+f"(d[12]), "+f"(d[13]), "+f"(d[14]), "+f"(d[15])
    : "r"(a[0]), "r"(a[1]), "r"(a[2]), "r"(a[3]), "l"(db), "r"(sd));
}

__device__ __forceinline__ void wgmma_rs_n48(float* d, const uint32_t* a, uint64_t db, int sd) {
  asm volatile("{ .reg .pred p; setp.ne.b32 p, %29, 0;\n"
      "wgmma.mma_async.sync.aligned.m64n48k16.f32.bf16.bf16 {"
      "%0,%1,%2,%3,%4,%5,%6,%7,%8,%9,%10,%11,%12,%13,%14,%15,"
      "%16,%17,%18,%19,%20,%21,%22,%23"
      "}, {%24,%25,%26,%27}, %28, p, 1, 1, 0; }"
    : "+f"(d[0]), "+f"(d[1]), "+f"(d[2]), "+f"(d[3]), "+f"(d[4]), "+f"(d[5]), "+f"(d[6]), "+f"(d[7]),
      "+f"(d[8]), "+f"(d[9]), "+f"(d[10]), "+f"(d[11]), "+f"(d[12]), "+f"(d[13]), "+f"(d[14]), "+f"(d[15]),
      "+f"(d[16]), "+f"(d[17]), "+f"(d[18]), "+f"(d[19]), "+f"(d[20]), "+f"(d[21]), "+f"(d[22]), "+f"(d[23])
    : "r"(a[0]), "r"(a[1]), "r"(a[2]), "r"(a[3]), "l"(db), "r"(sd));
}

__device__ __forceinline__ void wgmma_rs_n64(float* d, const uint32_t* a, uint64_t db, int sd) {
  asm volatile("{ .reg .pred p; setp.ne.b32 p, %37, 0;\n"
      "wgmma.mma_async.sync.aligned.m64n64k16.f32.bf16.bf16 {"
      "%0,%1,%2,%3,%4,%5,%6,%7,%8,%9,%10,%11,%12,%13,%14,%15,"
      "%16,%17,%18,%19,%20,%21,%22,%23,%24,%25,%26,%27,%28,%29,%30,%31"
      "}, {%32,%33,%34,%35}, %36, p, 1, 1, 0; }"
    : "+f"(d[0]), "+f"(d[1]), "+f"(d[2]), "+f"(d[3]), "+f"(d[4]), "+f"(d[5]), "+f"(d[6]), "+f"(d[7]),
      "+f"(d[8]), "+f"(d[9]), "+f"(d[10]), "+f"(d[11]), "+f"(d[12]), "+f"(d[13]), "+f"(d[14]), "+f"(d[15]),
      "+f"(d[16]), "+f"(d[17]), "+f"(d[18]), "+f"(d[19]), "+f"(d[20]), "+f"(d[21]), "+f"(d[22]), "+f"(d[23]),
      "+f"(d[24]), "+f"(d[25]), "+f"(d[26]), "+f"(d[27]), "+f"(d[28]), "+f"(d[29]), "+f"(d[30]), "+f"(d[31])
    : "r"(a[0]), "r"(a[1]), "r"(a[2]), "r"(a[3]), "l"(db), "r"(sd));
}

__device__ __forceinline__ void wgmma_rs_n80(float* d, const uint32_t* a, uint64_t db, int sd) {
  asm volatile("{ .reg .pred p; setp.ne.b32 p, %45, 0;\n"
      "wgmma.mma_async.sync.aligned.m64n80k16.f32.bf16.bf16 {"
      "%0,%1,%2,%3,%4,%5,%6,%7,%8,%9,%10,%11,%12,%13,%14,%15,"
      "%16,%17,%18,%19,%20,%21,%22,%23,%24,%25,%26,%27,%28,%29,%30,%31,"
      "%32,%33,%34,%35,%36,%37,%38,%39"
      "}, {%40,%41,%42,%43}, %44, p, 1, 1, 0; }"
    : "+f"(d[0]), "+f"(d[1]), "+f"(d[2]), "+f"(d[3]), "+f"(d[4]), "+f"(d[5]), "+f"(d[6]), "+f"(d[7]),
      "+f"(d[8]), "+f"(d[9]), "+f"(d[10]), "+f"(d[11]), "+f"(d[12]), "+f"(d[13]), "+f"(d[14]), "+f"(d[15]),
      "+f"(d[16]), "+f"(d[17]), "+f"(d[18]), "+f"(d[19]), "+f"(d[20]), "+f"(d[21]), "+f"(d[22]), "+f"(d[23]),
      "+f"(d[24]), "+f"(d[25]), "+f"(d[26]), "+f"(d[27]), "+f"(d[28]), "+f"(d[29]), "+f"(d[30]), "+f"(d[31]),
      "+f"(d[32]), "+f"(d[33]), "+f"(d[34]), "+f"(d[35]), "+f"(d[36]), "+f"(d[37]), "+f"(d[38]), "+f"(d[39])
    : "r"(a[0]), "r"(a[1]), "r"(a[2]), "r"(a[3]), "l"(db), "r"(sd));
}

__device__ __forceinline__ void wgmma_rs_n96(float* d, const uint32_t* a, uint64_t db, int sd) {
  asm volatile("{ .reg .pred p; setp.ne.b32 p, %53, 0;\n"
      "wgmma.mma_async.sync.aligned.m64n96k16.f32.bf16.bf16 {"
      "%0,%1,%2,%3,%4,%5,%6,%7,%8,%9,%10,%11,%12,%13,%14,%15,"
      "%16,%17,%18,%19,%20,%21,%22,%23,%24,%25,%26,%27,%28,%29,%30,%31,"
      "%32,%33,%34,%35,%36,%37,%38,%39,%40,%41,%42,%43,%44,%45,%46,%47"
      "}, {%48,%49,%50,%51}, %52, p, 1, 1, 0; }"
    : "+f"(d[0]), "+f"(d[1]), "+f"(d[2]), "+f"(d[3]), "+f"(d[4]), "+f"(d[5]), "+f"(d[6]), "+f"(d[7]),
      "+f"(d[8]), "+f"(d[9]), "+f"(d[10]), "+f"(d[11]), "+f"(d[12]), "+f"(d[13]), "+f"(d[14]), "+f"(d[15]),
      "+f"(d[16]), "+f"(d[17]), "+f"(d[18]), "+f"(d[19]), "+f"(d[20]), "+f"(d[21]), "+f"(d[22]), "+f"(d[23]),
      "+f"(d[24]), "+f"(d[25]), "+f"(d[26]), "+f"(d[27]), "+f"(d[28]), "+f"(d[29]), "+f"(d[30]), "+f"(d[31]),
      "+f"(d[32]), "+f"(d[33]), "+f"(d[34]), "+f"(d[35]), "+f"(d[36]), "+f"(d[37]), "+f"(d[38]), "+f"(d[39]),
      "+f"(d[40]), "+f"(d[41]), "+f"(d[42]), "+f"(d[43]), "+f"(d[44]), "+f"(d[45]), "+f"(d[46]), "+f"(d[47])
    : "r"(a[0]), "r"(a[1]), "r"(a[2]), "r"(a[3]), "l"(db), "r"(sd));
}

__device__ __forceinline__ void wgmma_rs_n112(float* d, const uint32_t* a, uint64_t db, int sd) {
  asm volatile("{ .reg .pred p; setp.ne.b32 p, %61, 0;\n"
      "wgmma.mma_async.sync.aligned.m64n112k16.f32.bf16.bf16 {"
      "%0,%1,%2,%3,%4,%5,%6,%7,%8,%9,%10,%11,%12,%13,%14,%15,"
      "%16,%17,%18,%19,%20,%21,%22,%23,%24,%25,%26,%27,%28,%29,%30,%31,"
      "%32,%33,%34,%35,%36,%37,%38,%39,%40,%41,%42,%43,%44,%45,%46,%47,"
      "%48,%49,%50,%51,%52,%53,%54,%55"
      "}, {%56,%57,%58,%59}, %60, p, 1, 1, 0; }"
    : "+f"(d[0]), "+f"(d[1]), "+f"(d[2]), "+f"(d[3]), "+f"(d[4]), "+f"(d[5]), "+f"(d[6]), "+f"(d[7]),
      "+f"(d[8]), "+f"(d[9]), "+f"(d[10]), "+f"(d[11]), "+f"(d[12]), "+f"(d[13]), "+f"(d[14]), "+f"(d[15]),
      "+f"(d[16]), "+f"(d[17]), "+f"(d[18]), "+f"(d[19]), "+f"(d[20]), "+f"(d[21]), "+f"(d[22]), "+f"(d[23]),
      "+f"(d[24]), "+f"(d[25]), "+f"(d[26]), "+f"(d[27]), "+f"(d[28]), "+f"(d[29]), "+f"(d[30]), "+f"(d[31]),
      "+f"(d[32]), "+f"(d[33]), "+f"(d[34]), "+f"(d[35]), "+f"(d[36]), "+f"(d[37]), "+f"(d[38]), "+f"(d[39]),
      "+f"(d[40]), "+f"(d[41]), "+f"(d[42]), "+f"(d[43]), "+f"(d[44]), "+f"(d[45]), "+f"(d[46]), "+f"(d[47]),
      "+f"(d[48]), "+f"(d[49]), "+f"(d[50]), "+f"(d[51]), "+f"(d[52]), "+f"(d[53]), "+f"(d[54]), "+f"(d[55])
    : "r"(a[0]), "r"(a[1]), "r"(a[2]), "r"(a[3]), "l"(db), "r"(sd));
}

__device__ __forceinline__ void wgmma_rs_n128(float* d, const uint32_t* a, uint64_t db, int sd) {
  asm volatile("{ .reg .pred p; setp.ne.b32 p, %69, 0;\n"
      "wgmma.mma_async.sync.aligned.m64n128k16.f32.bf16.bf16 {"
      "%0,%1,%2,%3,%4,%5,%6,%7,%8,%9,%10,%11,%12,%13,%14,%15,"
      "%16,%17,%18,%19,%20,%21,%22,%23,%24,%25,%26,%27,%28,%29,%30,%31,"
      "%32,%33,%34,%35,%36,%37,%38,%39,%40,%41,%42,%43,%44,%45,%46,%47,"
      "%48,%49,%50,%51,%52,%53,%54,%55,%56,%57,%58,%59,%60,%61,%62,%63"
      "}, {%64,%65,%66,%67}, %68, p, 1, 1, 0; }"
    : "+f"(d[0]), "+f"(d[1]), "+f"(d[2]), "+f"(d[3]), "+f"(d[4]), "+f"(d[5]), "+f"(d[6]), "+f"(d[7]),
      "+f"(d[8]), "+f"(d[9]), "+f"(d[10]), "+f"(d[11]), "+f"(d[12]), "+f"(d[13]), "+f"(d[14]), "+f"(d[15]),
      "+f"(d[16]), "+f"(d[17]), "+f"(d[18]), "+f"(d[19]), "+f"(d[20]), "+f"(d[21]), "+f"(d[22]), "+f"(d[23]),
      "+f"(d[24]), "+f"(d[25]), "+f"(d[26]), "+f"(d[27]), "+f"(d[28]), "+f"(d[29]), "+f"(d[30]), "+f"(d[31]),
      "+f"(d[32]), "+f"(d[33]), "+f"(d[34]), "+f"(d[35]), "+f"(d[36]), "+f"(d[37]), "+f"(d[38]), "+f"(d[39]),
      "+f"(d[40]), "+f"(d[41]), "+f"(d[42]), "+f"(d[43]), "+f"(d[44]), "+f"(d[45]), "+f"(d[46]), "+f"(d[47]),
      "+f"(d[48]), "+f"(d[49]), "+f"(d[50]), "+f"(d[51]), "+f"(d[52]), "+f"(d[53]), "+f"(d[54]), "+f"(d[55]),
      "+f"(d[56]), "+f"(d[57]), "+f"(d[58]), "+f"(d[59]), "+f"(d[60]), "+f"(d[61]), "+f"(d[62]), "+f"(d[63])
    : "r"(a[0]), "r"(a[1]), "r"(a[2]), "r"(a[3]), "l"(db), "r"(sd));
}

__device__ __forceinline__ void wgmma_rs_n144(float* d, const uint32_t* a, uint64_t db, int sd) {
  asm volatile("{ .reg .pred p; setp.ne.b32 p, %77, 0;\n"
      "wgmma.mma_async.sync.aligned.m64n144k16.f32.bf16.bf16 {"
      "%0,%1,%2,%3,%4,%5,%6,%7,%8,%9,%10,%11,%12,%13,%14,%15,"
      "%16,%17,%18,%19,%20,%21,%22,%23,%24,%25,%26,%27,%28,%29,%30,%31,"
      "%32,%33,%34,%35,%36,%37,%38,%39,%40,%41,%42,%43,%44,%45,%46,%47,"
      "%48,%49,%50,%51,%52,%53,%54,%55,%56,%57,%58,%59,%60,%61,%62,%63,"
      "%64,%65,%66,%67,%68,%69,%70,%71"
      "}, {%72,%73,%74,%75}, %76, p, 1, 1, 0; }"
    : "+f"(d[0]), "+f"(d[1]), "+f"(d[2]), "+f"(d[3]), "+f"(d[4]), "+f"(d[5]), "+f"(d[6]), "+f"(d[7]),
      "+f"(d[8]), "+f"(d[9]), "+f"(d[10]), "+f"(d[11]), "+f"(d[12]), "+f"(d[13]), "+f"(d[14]), "+f"(d[15]),
      "+f"(d[16]), "+f"(d[17]), "+f"(d[18]), "+f"(d[19]), "+f"(d[20]), "+f"(d[21]), "+f"(d[22]), "+f"(d[23]),
      "+f"(d[24]), "+f"(d[25]), "+f"(d[26]), "+f"(d[27]), "+f"(d[28]), "+f"(d[29]), "+f"(d[30]), "+f"(d[31]),
      "+f"(d[32]), "+f"(d[33]), "+f"(d[34]), "+f"(d[35]), "+f"(d[36]), "+f"(d[37]), "+f"(d[38]), "+f"(d[39]),
      "+f"(d[40]), "+f"(d[41]), "+f"(d[42]), "+f"(d[43]), "+f"(d[44]), "+f"(d[45]), "+f"(d[46]), "+f"(d[47]),
      "+f"(d[48]), "+f"(d[49]), "+f"(d[50]), "+f"(d[51]), "+f"(d[52]), "+f"(d[53]), "+f"(d[54]), "+f"(d[55]),
      "+f"(d[56]), "+f"(d[57]), "+f"(d[58]), "+f"(d[59]), "+f"(d[60]), "+f"(d[61]), "+f"(d[62]), "+f"(d[63]),
      "+f"(d[64]), "+f"(d[65]), "+f"(d[66]), "+f"(d[67]), "+f"(d[68]), "+f"(d[69]), "+f"(d[70]), "+f"(d[71])
    : "r"(a[0]), "r"(a[1]), "r"(a[2]), "r"(a[3]), "l"(db), "r"(sd));
}

__device__ __forceinline__ void wgmma_rs_n160(float* d, const uint32_t* a, uint64_t db, int sd) {
  asm volatile("{ .reg .pred p; setp.ne.b32 p, %85, 0;\n"
      "wgmma.mma_async.sync.aligned.m64n160k16.f32.bf16.bf16 {"
      "%0,%1,%2,%3,%4,%5,%6,%7,%8,%9,%10,%11,%12,%13,%14,%15,"
      "%16,%17,%18,%19,%20,%21,%22,%23,%24,%25,%26,%27,%28,%29,%30,%31,"
      "%32,%33,%34,%35,%36,%37,%38,%39,%40,%41,%42,%43,%44,%45,%46,%47,"
      "%48,%49,%50,%51,%52,%53,%54,%55,%56,%57,%58,%59,%60,%61,%62,%63,"
      "%64,%65,%66,%67,%68,%69,%70,%71,%72,%73,%74,%75,%76,%77,%78,%79"
      "}, {%80,%81,%82,%83}, %84, p, 1, 1, 0; }"
    : "+f"(d[0]), "+f"(d[1]), "+f"(d[2]), "+f"(d[3]), "+f"(d[4]), "+f"(d[5]), "+f"(d[6]), "+f"(d[7]),
      "+f"(d[8]), "+f"(d[9]), "+f"(d[10]), "+f"(d[11]), "+f"(d[12]), "+f"(d[13]), "+f"(d[14]), "+f"(d[15]),
      "+f"(d[16]), "+f"(d[17]), "+f"(d[18]), "+f"(d[19]), "+f"(d[20]), "+f"(d[21]), "+f"(d[22]), "+f"(d[23]),
      "+f"(d[24]), "+f"(d[25]), "+f"(d[26]), "+f"(d[27]), "+f"(d[28]), "+f"(d[29]), "+f"(d[30]), "+f"(d[31]),
      "+f"(d[32]), "+f"(d[33]), "+f"(d[34]), "+f"(d[35]), "+f"(d[36]), "+f"(d[37]), "+f"(d[38]), "+f"(d[39]),
      "+f"(d[40]), "+f"(d[41]), "+f"(d[42]), "+f"(d[43]), "+f"(d[44]), "+f"(d[45]), "+f"(d[46]), "+f"(d[47]),
      "+f"(d[48]), "+f"(d[49]), "+f"(d[50]), "+f"(d[51]), "+f"(d[52]), "+f"(d[53]), "+f"(d[54]), "+f"(d[55]),
      "+f"(d[56]), "+f"(d[57]), "+f"(d[58]), "+f"(d[59]), "+f"(d[60]), "+f"(d[61]), "+f"(d[62]), "+f"(d[63]),
      "+f"(d[64]), "+f"(d[65]), "+f"(d[66]), "+f"(d[67]), "+f"(d[68]), "+f"(d[69]), "+f"(d[70]), "+f"(d[71]),
      "+f"(d[72]), "+f"(d[73]), "+f"(d[74]), "+f"(d[75]), "+f"(d[76]), "+f"(d[77]), "+f"(d[78]), "+f"(d[79])
    : "r"(a[0]), "r"(a[1]), "r"(a[2]), "r"(a[3]), "l"(db), "r"(sd));
}

__device__ __forceinline__ void wgmma_rs_n176(float* d, const uint32_t* a, uint64_t db, int sd) {
  asm volatile("{ .reg .pred p; setp.ne.b32 p, %93, 0;\n"
      "wgmma.mma_async.sync.aligned.m64n176k16.f32.bf16.bf16 {"
      "%0,%1,%2,%3,%4,%5,%6,%7,%8,%9,%10,%11,%12,%13,%14,%15,"
      "%16,%17,%18,%19,%20,%21,%22,%23,%24,%25,%26,%27,%28,%29,%30,%31,"
      "%32,%33,%34,%35,%36,%37,%38,%39,%40,%41,%42,%43,%44,%45,%46,%47,"
      "%48,%49,%50,%51,%52,%53,%54,%55,%56,%57,%58,%59,%60,%61,%62,%63,"
      "%64,%65,%66,%67,%68,%69,%70,%71,%72,%73,%74,%75,%76,%77,%78,%79,"
      "%80,%81,%82,%83,%84,%85,%86,%87"
      "}, {%88,%89,%90,%91}, %92, p, 1, 1, 0; }"
    : "+f"(d[0]), "+f"(d[1]), "+f"(d[2]), "+f"(d[3]), "+f"(d[4]), "+f"(d[5]), "+f"(d[6]), "+f"(d[7]),
      "+f"(d[8]), "+f"(d[9]), "+f"(d[10]), "+f"(d[11]), "+f"(d[12]), "+f"(d[13]), "+f"(d[14]), "+f"(d[15]),
      "+f"(d[16]), "+f"(d[17]), "+f"(d[18]), "+f"(d[19]), "+f"(d[20]), "+f"(d[21]), "+f"(d[22]), "+f"(d[23]),
      "+f"(d[24]), "+f"(d[25]), "+f"(d[26]), "+f"(d[27]), "+f"(d[28]), "+f"(d[29]), "+f"(d[30]), "+f"(d[31]),
      "+f"(d[32]), "+f"(d[33]), "+f"(d[34]), "+f"(d[35]), "+f"(d[36]), "+f"(d[37]), "+f"(d[38]), "+f"(d[39]),
      "+f"(d[40]), "+f"(d[41]), "+f"(d[42]), "+f"(d[43]), "+f"(d[44]), "+f"(d[45]), "+f"(d[46]), "+f"(d[47]),
      "+f"(d[48]), "+f"(d[49]), "+f"(d[50]), "+f"(d[51]), "+f"(d[52]), "+f"(d[53]), "+f"(d[54]), "+f"(d[55]),
      "+f"(d[56]), "+f"(d[57]), "+f"(d[58]), "+f"(d[59]), "+f"(d[60]), "+f"(d[61]), "+f"(d[62]), "+f"(d[63]),
      "+f"(d[64]), "+f"(d[65]), "+f"(d[66]), "+f"(d[67]), "+f"(d[68]), "+f"(d[69]), "+f"(d[70]), "+f"(d[71]),
      "+f"(d[72]), "+f"(d[73]), "+f"(d[74]), "+f"(d[75]), "+f"(d[76]), "+f"(d[77]), "+f"(d[78]), "+f"(d[79]),
      "+f"(d[80]), "+f"(d[81]), "+f"(d[82]), "+f"(d[83]), "+f"(d[84]), "+f"(d[85]), "+f"(d[86]), "+f"(d[87])
    : "r"(a[0]), "r"(a[1]), "r"(a[2]), "r"(a[3]), "l"(db), "r"(sd));
}

__device__ __forceinline__ void wgmma_rs_n192(float* d, const uint32_t* a, uint64_t db, int sd) {
  asm volatile("{ .reg .pred p; setp.ne.b32 p, %101, 0;\n"
      "wgmma.mma_async.sync.aligned.m64n192k16.f32.bf16.bf16 {"
      "%0,%1,%2,%3,%4,%5,%6,%7,%8,%9,%10,%11,%12,%13,%14,%15,"
      "%16,%17,%18,%19,%20,%21,%22,%23,%24,%25,%26,%27,%28,%29,%30,%31,"
      "%32,%33,%34,%35,%36,%37,%38,%39,%40,%41,%42,%43,%44,%45,%46,%47,"
      "%48,%49,%50,%51,%52,%53,%54,%55,%56,%57,%58,%59,%60,%61,%62,%63,"
      "%64,%65,%66,%67,%68,%69,%70,%71,%72,%73,%74,%75,%76,%77,%78,%79,"
      "%80,%81,%82,%83,%84,%85,%86,%87,%88,%89,%90,%91,%92,%93,%94,%95"
      "}, {%96,%97,%98,%99}, %100, p, 1, 1, 0; }"
    : "+f"(d[0]), "+f"(d[1]), "+f"(d[2]), "+f"(d[3]), "+f"(d[4]), "+f"(d[5]), "+f"(d[6]), "+f"(d[7]),
      "+f"(d[8]), "+f"(d[9]), "+f"(d[10]), "+f"(d[11]), "+f"(d[12]), "+f"(d[13]), "+f"(d[14]), "+f"(d[15]),
      "+f"(d[16]), "+f"(d[17]), "+f"(d[18]), "+f"(d[19]), "+f"(d[20]), "+f"(d[21]), "+f"(d[22]), "+f"(d[23]),
      "+f"(d[24]), "+f"(d[25]), "+f"(d[26]), "+f"(d[27]), "+f"(d[28]), "+f"(d[29]), "+f"(d[30]), "+f"(d[31]),
      "+f"(d[32]), "+f"(d[33]), "+f"(d[34]), "+f"(d[35]), "+f"(d[36]), "+f"(d[37]), "+f"(d[38]), "+f"(d[39]),
      "+f"(d[40]), "+f"(d[41]), "+f"(d[42]), "+f"(d[43]), "+f"(d[44]), "+f"(d[45]), "+f"(d[46]), "+f"(d[47]),
      "+f"(d[48]), "+f"(d[49]), "+f"(d[50]), "+f"(d[51]), "+f"(d[52]), "+f"(d[53]), "+f"(d[54]), "+f"(d[55]),
      "+f"(d[56]), "+f"(d[57]), "+f"(d[58]), "+f"(d[59]), "+f"(d[60]), "+f"(d[61]), "+f"(d[62]), "+f"(d[63]),
      "+f"(d[64]), "+f"(d[65]), "+f"(d[66]), "+f"(d[67]), "+f"(d[68]), "+f"(d[69]), "+f"(d[70]), "+f"(d[71]),
      "+f"(d[72]), "+f"(d[73]), "+f"(d[74]), "+f"(d[75]), "+f"(d[76]), "+f"(d[77]), "+f"(d[78]), "+f"(d[79]),
      "+f"(d[80]), "+f"(d[81]), "+f"(d[82]), "+f"(d[83]), "+f"(d[84]), "+f"(d[85]), "+f"(d[86]), "+f"(d[87]),
      "+f"(d[88]), "+f"(d[89]), "+f"(d[90]), "+f"(d[91]), "+f"(d[92]), "+f"(d[93]), "+f"(d[94]), "+f"(d[95])
    : "r"(a[0]), "r"(a[1]), "r"(a[2]), "r"(a[3]), "l"(db), "r"(sd));
}

__device__ __forceinline__ void wgmma_rs_n208(float* d, const uint32_t* a, uint64_t db, int sd) {
  asm volatile("{ .reg .pred p; setp.ne.b32 p, %109, 0;\n"
      "wgmma.mma_async.sync.aligned.m64n208k16.f32.bf16.bf16 {"
      "%0,%1,%2,%3,%4,%5,%6,%7,%8,%9,%10,%11,%12,%13,%14,%15,"
      "%16,%17,%18,%19,%20,%21,%22,%23,%24,%25,%26,%27,%28,%29,%30,%31,"
      "%32,%33,%34,%35,%36,%37,%38,%39,%40,%41,%42,%43,%44,%45,%46,%47,"
      "%48,%49,%50,%51,%52,%53,%54,%55,%56,%57,%58,%59,%60,%61,%62,%63,"
      "%64,%65,%66,%67,%68,%69,%70,%71,%72,%73,%74,%75,%76,%77,%78,%79,"
      "%80,%81,%82,%83,%84,%85,%86,%87,%88,%89,%90,%91,%92,%93,%94,%95,"
      "%96,%97,%98,%99,%100,%101,%102,%103"
      "}, {%104,%105,%106,%107}, %108, p, 1, 1, 0; }"
    : "+f"(d[0]), "+f"(d[1]), "+f"(d[2]), "+f"(d[3]), "+f"(d[4]), "+f"(d[5]), "+f"(d[6]), "+f"(d[7]),
      "+f"(d[8]), "+f"(d[9]), "+f"(d[10]), "+f"(d[11]), "+f"(d[12]), "+f"(d[13]), "+f"(d[14]), "+f"(d[15]),
      "+f"(d[16]), "+f"(d[17]), "+f"(d[18]), "+f"(d[19]), "+f"(d[20]), "+f"(d[21]), "+f"(d[22]), "+f"(d[23]),
      "+f"(d[24]), "+f"(d[25]), "+f"(d[26]), "+f"(d[27]), "+f"(d[28]), "+f"(d[29]), "+f"(d[30]), "+f"(d[31]),
      "+f"(d[32]), "+f"(d[33]), "+f"(d[34]), "+f"(d[35]), "+f"(d[36]), "+f"(d[37]), "+f"(d[38]), "+f"(d[39]),
      "+f"(d[40]), "+f"(d[41]), "+f"(d[42]), "+f"(d[43]), "+f"(d[44]), "+f"(d[45]), "+f"(d[46]), "+f"(d[47]),
      "+f"(d[48]), "+f"(d[49]), "+f"(d[50]), "+f"(d[51]), "+f"(d[52]), "+f"(d[53]), "+f"(d[54]), "+f"(d[55]),
      "+f"(d[56]), "+f"(d[57]), "+f"(d[58]), "+f"(d[59]), "+f"(d[60]), "+f"(d[61]), "+f"(d[62]), "+f"(d[63]),
      "+f"(d[64]), "+f"(d[65]), "+f"(d[66]), "+f"(d[67]), "+f"(d[68]), "+f"(d[69]), "+f"(d[70]), "+f"(d[71]),
      "+f"(d[72]), "+f"(d[73]), "+f"(d[74]), "+f"(d[75]), "+f"(d[76]), "+f"(d[77]), "+f"(d[78]), "+f"(d[79]),
      "+f"(d[80]), "+f"(d[81]), "+f"(d[82]), "+f"(d[83]), "+f"(d[84]), "+f"(d[85]), "+f"(d[86]), "+f"(d[87]),
      "+f"(d[88]), "+f"(d[89]), "+f"(d[90]), "+f"(d[91]), "+f"(d[92]), "+f"(d[93]), "+f"(d[94]), "+f"(d[95]),
      "+f"(d[96]), "+f"(d[97]), "+f"(d[98]), "+f"(d[99]), "+f"(d[100]), "+f"(d[101]), "+f"(d[102]), "+f"(d[103])
    : "r"(a[0]), "r"(a[1]), "r"(a[2]), "r"(a[3]), "l"(db), "r"(sd));
}

__device__ __forceinline__ void wgmma_rs_n224(float* d, const uint32_t* a, uint64_t db, int sd) {
  asm volatile("{ .reg .pred p; setp.ne.b32 p, %117, 0;\n"
      "wgmma.mma_async.sync.aligned.m64n224k16.f32.bf16.bf16 {"
      "%0,%1,%2,%3,%4,%5,%6,%7,%8,%9,%10,%11,%12,%13,%14,%15,"
      "%16,%17,%18,%19,%20,%21,%22,%23,%24,%25,%26,%27,%28,%29,%30,%31,"
      "%32,%33,%34,%35,%36,%37,%38,%39,%40,%41,%42,%43,%44,%45,%46,%47,"
      "%48,%49,%50,%51,%52,%53,%54,%55,%56,%57,%58,%59,%60,%61,%62,%63,"
      "%64,%65,%66,%67,%68,%69,%70,%71,%72,%73,%74,%75,%76,%77,%78,%79,"
      "%80,%81,%82,%83,%84,%85,%86,%87,%88,%89,%90,%91,%92,%93,%94,%95,"
      "%96,%97,%98,%99,%100,%101,%102,%103,%104,%105,%106,%107,%108,%109,%110,%111"
      "}, {%112,%113,%114,%115}, %116, p, 1, 1, 0; }"
    : "+f"(d[0]), "+f"(d[1]), "+f"(d[2]), "+f"(d[3]), "+f"(d[4]), "+f"(d[5]), "+f"(d[6]), "+f"(d[7]),
      "+f"(d[8]), "+f"(d[9]), "+f"(d[10]), "+f"(d[11]), "+f"(d[12]), "+f"(d[13]), "+f"(d[14]), "+f"(d[15]),
      "+f"(d[16]), "+f"(d[17]), "+f"(d[18]), "+f"(d[19]), "+f"(d[20]), "+f"(d[21]), "+f"(d[22]), "+f"(d[23]),
      "+f"(d[24]), "+f"(d[25]), "+f"(d[26]), "+f"(d[27]), "+f"(d[28]), "+f"(d[29]), "+f"(d[30]), "+f"(d[31]),
      "+f"(d[32]), "+f"(d[33]), "+f"(d[34]), "+f"(d[35]), "+f"(d[36]), "+f"(d[37]), "+f"(d[38]), "+f"(d[39]),
      "+f"(d[40]), "+f"(d[41]), "+f"(d[42]), "+f"(d[43]), "+f"(d[44]), "+f"(d[45]), "+f"(d[46]), "+f"(d[47]),
      "+f"(d[48]), "+f"(d[49]), "+f"(d[50]), "+f"(d[51]), "+f"(d[52]), "+f"(d[53]), "+f"(d[54]), "+f"(d[55]),
      "+f"(d[56]), "+f"(d[57]), "+f"(d[58]), "+f"(d[59]), "+f"(d[60]), "+f"(d[61]), "+f"(d[62]), "+f"(d[63]),
      "+f"(d[64]), "+f"(d[65]), "+f"(d[66]), "+f"(d[67]), "+f"(d[68]), "+f"(d[69]), "+f"(d[70]), "+f"(d[71]),
      "+f"(d[72]), "+f"(d[73]), "+f"(d[74]), "+f"(d[75]), "+f"(d[76]), "+f"(d[77]), "+f"(d[78]), "+f"(d[79]),
      "+f"(d[80]), "+f"(d[81]), "+f"(d[82]), "+f"(d[83]), "+f"(d[84]), "+f"(d[85]), "+f"(d[86]), "+f"(d[87]),
      "+f"(d[88]), "+f"(d[89]), "+f"(d[90]), "+f"(d[91]), "+f"(d[92]), "+f"(d[93]), "+f"(d[94]), "+f"(d[95]),
      "+f"(d[96]), "+f"(d[97]), "+f"(d[98]), "+f"(d[99]), "+f"(d[100]), "+f"(d[101]), "+f"(d[102]), "+f"(d[103]),
      "+f"(d[104]), "+f"(d[105]), "+f"(d[106]), "+f"(d[107]), "+f"(d[108]), "+f"(d[109]), "+f"(d[110]), "+f"(d[111])
    : "r"(a[0]), "r"(a[1]), "r"(a[2]), "r"(a[3]), "l"(db), "r"(sd));
}

__device__ __forceinline__ void wgmma_rs_n240(float* d, const uint32_t* a, uint64_t db, int sd) {
  asm volatile("{ .reg .pred p; setp.ne.b32 p, %125, 0;\n"
      "wgmma.mma_async.sync.aligned.m64n240k16.f32.bf16.bf16 {"
      "%0,%1,%2,%3,%4,%5,%6,%7,%8,%9,%10,%11,%12,%13,%14,%15,"
      "%16,%17,%18,%19,%20,%21,%22,%23,%24,%25,%26,%27,%28,%29,%30,%31,"
      "%32,%33,%34,%35,%36,%37,%38,%39,%40,%41,%42,%43,%44,%45,%46,%47,"
      "%48,%49,%50,%51,%52,%53,%54,%55,%56,%57,%58,%59,%60,%61,%62,%63,"
      "%64,%65,%66,%67,%68,%69,%70,%71,%72,%73,%74,%75,%76,%77,%78,%79,"
      "%80,%81,%82,%83,%84,%85,%86,%87,%88,%89,%90,%91,%92,%93,%94,%95,"
      "%96,%97,%98,%99,%100,%101,%102,%103,%104,%105,%106,%107,%108,%109,%110,%111,"
      "%112,%113,%114,%115,%116,%117,%118,%119"
      "}, {%120,%121,%122,%123}, %124, p, 1, 1, 0; }"
    : "+f"(d[0]), "+f"(d[1]), "+f"(d[2]), "+f"(d[3]), "+f"(d[4]), "+f"(d[5]), "+f"(d[6]), "+f"(d[7]),
      "+f"(d[8]), "+f"(d[9]), "+f"(d[10]), "+f"(d[11]), "+f"(d[12]), "+f"(d[13]), "+f"(d[14]), "+f"(d[15]),
      "+f"(d[16]), "+f"(d[17]), "+f"(d[18]), "+f"(d[19]), "+f"(d[20]), "+f"(d[21]), "+f"(d[22]), "+f"(d[23]),
      "+f"(d[24]), "+f"(d[25]), "+f"(d[26]), "+f"(d[27]), "+f"(d[28]), "+f"(d[29]), "+f"(d[30]), "+f"(d[31]),
      "+f"(d[32]), "+f"(d[33]), "+f"(d[34]), "+f"(d[35]), "+f"(d[36]), "+f"(d[37]), "+f"(d[38]), "+f"(d[39]),
      "+f"(d[40]), "+f"(d[41]), "+f"(d[42]), "+f"(d[43]), "+f"(d[44]), "+f"(d[45]), "+f"(d[46]), "+f"(d[47]),
      "+f"(d[48]), "+f"(d[49]), "+f"(d[50]), "+f"(d[51]), "+f"(d[52]), "+f"(d[53]), "+f"(d[54]), "+f"(d[55]),
      "+f"(d[56]), "+f"(d[57]), "+f"(d[58]), "+f"(d[59]), "+f"(d[60]), "+f"(d[61]), "+f"(d[62]), "+f"(d[63]),
      "+f"(d[64]), "+f"(d[65]), "+f"(d[66]), "+f"(d[67]), "+f"(d[68]), "+f"(d[69]), "+f"(d[70]), "+f"(d[71]),
      "+f"(d[72]), "+f"(d[73]), "+f"(d[74]), "+f"(d[75]), "+f"(d[76]), "+f"(d[77]), "+f"(d[78]), "+f"(d[79]),
      "+f"(d[80]), "+f"(d[81]), "+f"(d[82]), "+f"(d[83]), "+f"(d[84]), "+f"(d[85]), "+f"(d[86]), "+f"(d[87]),
      "+f"(d[88]), "+f"(d[89]), "+f"(d[90]), "+f"(d[91]), "+f"(d[92]), "+f"(d[93]), "+f"(d[94]), "+f"(d[95]),
      "+f"(d[96]), "+f"(d[97]), "+f"(d[98]), "+f"(d[99]), "+f"(d[100]), "+f"(d[101]), "+f"(d[102]), "+f"(d[103]),
      "+f"(d[104]), "+f"(d[105]), "+f"(d[106]), "+f"(d[107]), "+f"(d[108]), "+f"(d[109]), "+f"(d[110]), "+f"(d[111]),
      "+f"(d[112]), "+f"(d[113]), "+f"(d[114]), "+f"(d[115]), "+f"(d[116]), "+f"(d[117]), "+f"(d[118]), "+f"(d[119])
    : "r"(a[0]), "r"(a[1]), "r"(a[2]), "r"(a[3]), "l"(db), "r"(sd));
}

__device__ __forceinline__ void wgmma_rs_n256(float* d, const uint32_t* a, uint64_t db, int sd) {
  asm volatile("{ .reg .pred p; setp.ne.b32 p, %133, 0;\n"
      "wgmma.mma_async.sync.aligned.m64n256k16.f32.bf16.bf16 {"
      "%0,%1,%2,%3,%4,%5,%6,%7,%8,%9,%10,%11,%12,%13,%14,%15,"
      "%16,%17,%18,%19,%20,%21,%22,%23,%24,%25,%26,%27,%28,%29,%30,%31,"
      "%32,%33,%34,%35,%36,%37,%38,%39,%40,%41,%42,%43,%44,%45,%46,%47,"
      "%48,%49,%50,%51,%52,%53,%54,%55,%56,%57,%58,%59,%60,%61,%62,%63,"
      "%64,%65,%66,%67,%68,%69,%70,%71,%72,%73,%74,%75,%76,%77,%78,%79,"
      "%80,%81,%82,%83,%84,%85,%86,%87,%88,%89,%90,%91,%92,%93,%94,%95,"
      "%96,%97,%98,%99,%100,%101,%102,%103,%104,%105,%106,%107,%108,%109,%110,%111,"
      "%112,%113,%114,%115,%116,%117,%118,%119,%120,%121,%122,%123,%124,%125,%126,%127"
      "}, {%128,%129,%130,%131}, %132, p, 1, 1, 0; }"
    : "+f"(d[0]), "+f"(d[1]), "+f"(d[2]), "+f"(d[3]), "+f"(d[4]), "+f"(d[5]), "+f"(d[6]), "+f"(d[7]),
      "+f"(d[8]), "+f"(d[9]), "+f"(d[10]), "+f"(d[11]), "+f"(d[12]), "+f"(d[13]), "+f"(d[14]), "+f"(d[15]),
      "+f"(d[16]), "+f"(d[17]), "+f"(d[18]), "+f"(d[19]), "+f"(d[20]), "+f"(d[21]), "+f"(d[22]), "+f"(d[23]),
      "+f"(d[24]), "+f"(d[25]), "+f"(d[26]), "+f"(d[27]), "+f"(d[28]), "+f"(d[29]), "+f"(d[30]), "+f"(d[31]),
      "+f"(d[32]), "+f"(d[33]), "+f"(d[34]), "+f"(d[35]), "+f"(d[36]), "+f"(d[37]), "+f"(d[38]), "+f"(d[39]),
      "+f"(d[40]), "+f"(d[41]), "+f"(d[42]), "+f"(d[43]), "+f"(d[44]), "+f"(d[45]), "+f"(d[46]), "+f"(d[47]),
      "+f"(d[48]), "+f"(d[49]), "+f"(d[50]), "+f"(d[51]), "+f"(d[52]), "+f"(d[53]), "+f"(d[54]), "+f"(d[55]),
      "+f"(d[56]), "+f"(d[57]), "+f"(d[58]), "+f"(d[59]), "+f"(d[60]), "+f"(d[61]), "+f"(d[62]), "+f"(d[63]),
      "+f"(d[64]), "+f"(d[65]), "+f"(d[66]), "+f"(d[67]), "+f"(d[68]), "+f"(d[69]), "+f"(d[70]), "+f"(d[71]),
      "+f"(d[72]), "+f"(d[73]), "+f"(d[74]), "+f"(d[75]), "+f"(d[76]), "+f"(d[77]), "+f"(d[78]), "+f"(d[79]),
      "+f"(d[80]), "+f"(d[81]), "+f"(d[82]), "+f"(d[83]), "+f"(d[84]), "+f"(d[85]), "+f"(d[86]), "+f"(d[87]),
      "+f"(d[88]), "+f"(d[89]), "+f"(d[90]), "+f"(d[91]), "+f"(d[92]), "+f"(d[93]), "+f"(d[94]), "+f"(d[95]),
      "+f"(d[96]), "+f"(d[97]), "+f"(d[98]), "+f"(d[99]), "+f"(d[100]), "+f"(d[101]), "+f"(d[102]), "+f"(d[103]),
      "+f"(d[104]), "+f"(d[105]), "+f"(d[106]), "+f"(d[107]), "+f"(d[108]), "+f"(d[109]), "+f"(d[110]), "+f"(d[111]),
      "+f"(d[112]), "+f"(d[113]), "+f"(d[114]), "+f"(d[115]), "+f"(d[116]), "+f"(d[117]), "+f"(d[118]), "+f"(d[119]),
      "+f"(d[120]), "+f"(d[121]), "+f"(d[122]), "+f"(d[123]), "+f"(d[124]), "+f"(d[125]), "+f"(d[126]), "+f"(d[127])
    : "r"(a[0]), "r"(a[1]), "r"(a[2]), "r"(a[3]), "l"(db), "r"(sd));
}

__device__ __forceinline__ void ln_finish(float mean, float var, float& mb, float& rinv) {
  mb = round_bf16(mean);
  float den = round_bf16(sqrtf(round_bf16(round_bf16(var) + 1e-5f)));
  rinv = 1.0f / den;
}
__device__ __forceinline__ uint32_t ln_apply(uint32_t x2, uint32_t mb2, float rinv) {
  uint32_t c = bsub2(x2, mb2);
  return pack_bf16(bf_lo(c) * rinv, bf_hi(c) * rinv);
}
__device__ __forceinline__ int conv_channel(int cta, int i) {
  return i < N_SHORT ? i * N_CONV_CTA + cta : N_SHORT * N_CONV_CTA + (i - N_SHORT) * 4 + cta;
}
__device__ __forceinline__ uint32_t sum4(uint32_t a, uint32_t b, uint32_t c, uint32_t d) {
  return pack_bf16((bf_lo(a) + bf_lo(b)) + (bf_lo(c) + bf_lo(d)), (bf_hi(a) + bf_hi(b)) + (bf_hi(c) + bf_hi(d)));
}
struct Ring {
  uint32_t s, ph;
  __device__ __forceinline__ void next() { if (++s == NSTAGE) { s = 0; ph ^= 1; } }
};

struct Cta {
  int rank, g1m, g1n, g2m, g2n;
  __device__ __forceinline__ explicit Cta(const Params& P) {
    const int b = cta_id();
    const Role r = P.roles.r[b >> 1];
    rank = b & 1; g1m = r.g1m; g1n = r.g1n; g2m = r.g2m; g2n = r.g2n;
  }
  __device__ __forceinline__ int cvc() const { return 2 * (-1 - g1m) + rank; }
  __device__ __forceinline__ int n_conv() const { return g2m < 0 ? N_SHORT + N_LONG_EXTRA : N_SHORT; }
  __device__ __forceinline__ int fill() const { return CH_FILL + (g1m * 3 + g1n) * 2 + rank; }
  __device__ __forceinline__ int dk() const { return g2n * 144 + rank * 72; }
  __device__ __forceinline__ int g2k(int kb) const { return (rank * G2_KB + (kb < 18 ? 2 * kb : 2 * kb - 35)) * 64; }
};

#define CONV_LDA(j, base) { a[2 * (j)] = lds32((base) + ((j) >> 1) * 256 + ((j) & 1) * 16); a[2 * (j) + 1] = lds32((base) + ((j) >> 1) * 256 + ((j) & 1) * 16 + 128); }
__device__ __forceinline__ void conv_mma(float* acc, const uint32_t* a, uint64_t db) {
  wgmma_rs_n256(acc, a, db, 0);
  wgmma_rs_n240(acc, a + 4, db + 16, 1);
  wgmma_rs_n224(acc, a + 8, db + 32, 1);
  wgmma_rs_n208(acc, a + 12, db + 48, 1);
  wgmma_rs_n192(acc, a + 16, db + 64, 1);
  wgmma_rs_n176(acc, a + 20, db + 80, 1);
  wgmma_rs_n160(acc, a + 24, db + 96, 1);
  wgmma_rs_n144(acc, a + 28, db + 112, 1);
  wgmma_rs_n128(acc, a + 32, db + 128, 1);
  wgmma_rs_n112(acc, a + 36, db + 144, 1);
  wgmma_rs_n96(acc, a + 40, db + 160, 1);
  wgmma_rs_n80(acc, a + 44, db + 176, 1);
  wgmma_rs_n64(acc, a + 48, db + 192, 1);
  wgmma_rs_n48(acc, a + 52, db + 208, 1);
  wgmma_rs_n32(acc, a + 56, db + 224, 1);
  wgmma_rs_n16(acc, a + 60, db + 240, 1);
}
__device__ __forceinline__ uint32_t conv_part(const float* acc, int j) {
  const int q = 31 - j;
  return q == 31 ? pack_bf16(acc[124], acc[125]) : pack_bf16(acc[4 * q] + acc[(4 * q + 6) & 127], acc[4 * q + 1] + acc[(4 * q + 7) & 127]);
}
__device__ __forceinline__ void conv_out(const uint4 (*p)[4], int ch, int wtid) {
  uint4* yo = reinterpret_cast<uint4*>(g_y + (size_t)ch * S_) + wtid;
#pragma unroll
  for (int c = 0; c < 2; c++)
    yo[128 * c] = make_uint4(sum4(p[c][0].x, p[c][1].x, p[c][2].x, p[c][3].x), sum4(p[c][0].y, p[c][1].y, p[c][2].y, p[c][3].y),
                             sum4(p[c][0].z, p[c][1].z, p[c][2].z, p[c][3].z), sum4(p[c][0].w, p[c][1].w, p[c][2].w, p[c][3].w));
}

__global__ void __cluster_dims__(2, 1, 1) __launch_bounds__(384, 1) fused_kernel(const __grid_constant__ Params P) {
  extern __shared__ uint8_t smem_raw[];
  const uint32_t t0 = clk();
  const uint32_t sb = (smem_u32(smem_raw) + 1023) & ~1023u;
  const uint32_t bars = sb + SM_BAR;
  const int tid = threadIdx.x, warp = __shfl_sync(0xffffffffu, tid >> 5, 0), lane = tid & 31;
  const bool p0 = blockIdx.x < 128;

  if (warp >= 8) {
    asm volatile("setmaxnreg.dec.sync.aligned.u32 56;");
    const uint32_t tag = ld_flag(&g_epoch) + 1;
    if (lane == 0) {
      const bool g1 = Cta(P).g1m >= 0;
      if (warp == 8) {
        for (int s = 0; s < NSTAGE; s++) mbar_init(bars + 8 * (B_FULL + s), 1);
        for (int s = 0; s < CV_NSLOT; s++) mbar_init(bars + 8 * (B_CFULL + s), 1);
        if (!g1) { mbar_arrive(bars + 8 * B_FULL); mbar_arrive(bars + 8 * (B_FULL + 1)); }
      } else if (warp == 9) {
        for (int s = 0; s < NSTAGE; s++) mbar_init(bars + 8 * (B_EMPTY + s), 2);
        mbar_init(bars + 8 * B_YDONE, g1 ? 4 : 8);
      } else if (warp == 10) {
        for (int s = B_STG; s <= B_FILL; s++) mbar_init(bars + 8 * s, 4);
      } else {
        for (int s = B_XRDY; s <= B_GO; s++) mbar_init(bars + 8 * s, 1);
      }
      asm volatile("fence.mbarrier_init.release.cluster;" ::: "memory");
    }
    __syncwarp();
    asm volatile("barrier.cluster.arrive.relaxed.aligned;" ::: "memory");
    if (warp == 8) {
      asm volatile("barrier.cluster.wait.aligned;" ::: "memory");
      if (lane == 0) {
        const Cta c(P);
        if (c.g1m >= 0) {
          const int fg = (2 * c.g1m + c.rank) * 2, dg = c.g1n * 3;
          for (int s = 0; s < NSTAGE; s++) mbar_expect_tx(bars + 8 * (B_FULL + s), G1_BYTES);
          int nw = 0;
          for (uint32_t n = 0;; n++) {
            if (nw < NSTAGE && clk() - t0 >= W1T0 + nw * W1D) { tma3d(sb + nw * SLOT, &P.m_w1, 0, nw * 64, fg, bars + 8 * (B_FULL + nw)); nw++; }
            if (reached(C_H, tag * 128)) break;
            if (n > 4000000u) __trap();
          }
          TLREC(2);
          fence_async_global();
#pragma unroll 1
          for (int s = 0; s < NSTAGE; s++) {
            if (s >= nw) tma3d(sb + s * SLOT, &P.m_w1, 0, s * 64, fg, bars + 8 * (B_FULL + s));
            if (s == 4) { mbar_arrive(bars + 8 * B_GO); await(C_H + 1, tag * 128); fence_async_global(); }
            tma3d(sb + s * SLOT + 16384, &P.m_h, 0, s * 64, dg, bars + 8 * (B_FULL + s));
          }
          Ring r{0, 0};
#pragma unroll 1
          for (int kb = NSTAGE; kb < G1_KB; kb++, r.next()) {
            if (kb == 8) {
              for (uint32_t n = 0;; n++) {
                uint32_t v[6];
#pragma unroll
                for (int i = 0; i < 6; i++) v[i] = ld_flag(g_cnt + (C_H + 2 + i) * 32) - tag * 128;
                if ((int32_t)(v[0] | v[1] | v[2] | v[3] | v[4] | v[5]) >= 0) break;
                if (n > 4000000u) __trap();
              }
              fence_async_global();
              TLREC(8);
            }
            mbar_wait(bars + 8 * (B_EMPTY + r.s), r.ph);
            mbar_expect_tx(bars + 8 * (B_FULL + r.s), G1_BYTES);
            tma3d(sb + r.s * SLOT, &P.m_w1, 0, kb * 64, fg, bars + 8 * (B_FULL + r.s));
            tma3d(sb + r.s * SLOT + 16384, &P.m_h, 0, kb * 64, dg, bars + 8 * (B_FULL + r.s));
            if (PF1 && kb + PF1 < G1_KB && (kb + PF1) % 3 == c.g1n) pf3d(&P.m_w1, 0, (kb + PF1) * 64, fg);
            if (kb >= 12 && kb < 12 + PF2 && (kb & 3) == c.g2n) pf3d(&P.m_w2, 0, c.g2k(kb - 12), c.g2m * 2);
          }
        } else {
          const int cvc = c.cvc(), n_conv = c.n_conv();
          for (int i = 0; i < CV_NSLOT; i++) {
            mbar_expect_tx(bars + 8 * (B_CFULL + i), 8192 + 4096);
            bulk_load(sb + i * CV_SLOT + CV_KOFF + 32, P.ssm_k + (size_t)conv_channel(cvc, i) * S_, 4096, bars + 8 * (B_CFULL + i));
          }
          int ready = -1;
#pragma unroll 1
          for (int i = 0; i < n_conv; i++) {
            const int ch = conv_channel(cvc, i), s = i % CV_NSLOT;
            const uint32_t slot = sb + s * CV_SLOT, fb = bars + 8 * (B_CFULL + s);
            if (i >= CV_NSLOT) {
              mbar_wait(bars + 8 * (B_CEMPTY + s), ((i / CV_NSLOT) - 1) & 1);
              mbar_expect_tx(fb, 8192 + 4096);
              bulk_load(slot + CV_KOFF + 32, P.ssm_k + (size_t)ch * S_, 4096, fb);
            }
            const int r = ch / 96;
            if (r > ready) {
              await(C_KV + r, tag * 128);
              fence_async_global();
              if (r == 0) { mbar_arrive(bars + 8 * B_GO); TLREC(18); }
              ready = r;
            }
            bulk_load(slot, g_ub + (size_t)ch * 4096, 8192, fb);
            if (c.g2m >= 0 && i >= 8 && i < 8 + PF2 / 2 && !(i & 1)) pf3d(&P.m_w2, 0, c.g2k((i - 8) * 2 + c.g2n), c.g2m * 2);
          }
        }
        if (c.g2m >= 0) {
          const int sg = c.g2m * 2, dk = c.dk(), ds = c.g2n * 144 + (c.rank ^ 1) * 72;
          const int cu0 = C_U + ((c.g2n * 144) / 192) * 4 + c.rank * 2, cu1 = C_U + ((c.g2n * 144 + 143) / 192) * 4 + c.rank * 2;
          constexpr int NPRE = 3;
#pragma unroll 1
          for (int kb = 0; kb < NPRE; kb++) {
            const int s = G1_KB % NSTAGE + kb;
            mbar_wait(bars + 8 * (B_EMPTY + s), ((G1_KB / NSTAGE) - 1) & 1);
            mbar_expect_tx(bars + 8 * (B_FULL + s), G2_BYTES);
            tma3d(sb + s * SLOT, &P.m_w2, 0, c.g2k(kb), sg, bars + 8 * (B_FULL + s));
          }
          Ring r{G1_KB % NSTAGE, ((G1_KB / NSTAGE) - 1) & 1};
#pragma unroll 1
          for (int kb = 0; kb < G2_KB; kb++, r.next()) {
            const int k0 = c.g2k(kb);
            const uint32_t fb = bars + 8 * (B_FULL + r.s), slot = sb + r.s * SLOT;
            if (kb == 0 || kb == 18) {
              for (uint32_t n = 0;; n++) {
                const uint32_t v0 = ld_flag(g_cnt + (cu0 + (kb != 0)) * 32) - tag * 18, v1 = ld_flag(g_cnt + (cu1 + (kb != 0)) * 32) - tag * 18;
                if ((int32_t)(v0 | v1) >= 0) break;
                if (n > 4000000u) __trap();
              }
              fence_async_global();
              if (kb == 0) TLREC(6);
            }
            if (kb >= NPRE) {
              mbar_wait(bars + 8 * (B_EMPTY + r.s), r.ph);
              mbar_expect_tx(fb, G2_BYTES);
              tma3d(slot, &P.m_w2, 0, k0, sg, fb);
            }
            tma2d(slot + 16384, &P.m_uld, k0, ds, fb);
            tma2d(slot + 16384 + 9216, &P.m_uld, k0, dk, fb);
            if (PF2 && kb + PF2 < G2_KB && (kb & 3) == c.g2n) pf3d(&P.m_w2, 0, c.g2k(kb + PF2), sg);
            if (kb == 10) {
              mbar_expect_tx(bars + 8 * B_XT, 18432);
#pragma unroll 1
              for (int j = 0; j < 8; j++)
                tma2d(sb + ((XSLOT + 1 + (j >> 1)) % NSTAGE) * SLOT + G2_BYTES + (j & 1) * 2304, &P.m_x, dk, c.g2m * 128 + j * 16, bars + 8 * B_XT);
            }
          }
          mbar_expect_tx(bars + 8 * B_XFULL, 18432);
          mbar_expect_tx(bars + 8 * (B_XFULL + 1), 18432);
          mbar_wait(bars + 8 * (B_EMPTY + XSLOT), r.ph);
          mbar_arrive_remote(mapa(bars + 8 * B_XRDY, c.rank ^ 1));
        }
      }
    } else {
      const int ht = tid - 288;
      if (p0) {
        const int hf = ht / 48, pr = ht % 48;
        const int s0 = blockIdx.x * 16 + hf * 8;
        const bool first = s0 == 0;
        const __nv_bfloat16* kp = P.k + (ptrdiff_t)(s0 - 4) * D_ + 2 * pr;
        const __nv_bfloat16* vp = P.v + (ptrdiff_t)(s0 - 1) * D_ + 2 * pr;
        const uint4* wp = reinterpret_cast<const uint4*>(P.shift_k) + pr;
        const uint32_t st = sb + SM_KVS + (1 - hf) * 1536 + pr * 32;
        uint32_t kk[12], vv[9];
        uint4 w;
        auto load = [&](int r) {
#pragma unroll
          for (int j = 0; j < 12; j++) kk[j] = (j < 4 && first) ? 0u : ldg32(kp + r * 96 + j * D_);
#pragma unroll
          for (int j = 0; j < 9; j++) vv[j] = (j < 1 && first) ? 0u : ldg32(vp + r * 96 + j * D_);
          w = __ldg(wp + r * 48);
        };
        pace(t0, KVT0);
        load(0);
        asm volatile("barrier.cluster.wait.aligned;" ::: "memory");
#pragma unroll 1
        for (int r = 0; r < KV_ROUNDS; r++) {
          const uint32_t w0 = __byte_perm(w.x, w.z, 0x5410), w1 = __byte_perm(w.x, w.z, 0x7632);
          const uint32_t w2 = __byte_perm(w.y, w.w, 0x5410), w3 = __byte_perm(w.y, w.w, 0x7632);
#pragma unroll
          for (int j = 0; j < 9; j++)
            vv[j] = bmul2(bfma2(kk[j + 3], w0, bfma2(kk[j + 2], w1, bfma2(kk[j + 1], w2, bmul2(kk[j], w3)))), vv[j]);
#pragma unroll
          for (int c = 0; c < 2; c++)
#pragma unroll
            for (int pi = 0; pi < 2; pi++) {
              const uint32_t sel = c ? 0x7632 : 0x5410;
              sts128(st + c * 3072 + pi * 16, __byte_perm(vv[7 + pi], vv[6 + pi], sel), __byte_perm(vv[5 + pi], vv[4 + pi], sel),
                     __byte_perm(vv[3 + pi], vv[2 + pi], sel), __byte_perm(vv[1 + pi], vv[pi], sel));
            }
          bar_sync(1, 96);
          if (ht == 0) { fence_async_smem(); tma3d_store(&P.m_ub, sb + SM_KVS, 16 * (127 - blockIdx.x), r * 48, 0); bulk_commit(); }
          if (r > 0 && r + 1 < KV_ROUNDS) load(r + 1);
          if (ht == 0) { bulk_wait_all(); signal_stored(C_KV + r); TLREC(22 + r); }
          if (r == 0) { mbar_wait(bars + 8 * B_GO, 0); load(1); }
          __syncwarp();
          bar_sync(1, 96);
        }
        if (ht == 0) mbar_arrive(bars + 8 * B_KVDONE);
      } else {
        asm volatile("barrier.cluster.wait.aligned;" ::: "memory");
      }
      if (lane == 0) {
        const Cta c(P);
        if (warp < 11) {
          if (c.g1m >= 0) {
            const int wg = warp - 9, fb64 = (2 * c.g1m + c.rank) * 2 + wg;
            const uint32_t stg = wg == 0 ? sb + SM_DED : sb + SLOT + 16384;
#pragma unroll 1
            for (int ck = 0; ck < 3; ck++) {
              mbar_wait(bars + 8 * (B_STG + wg * 3 + ck), 0);
              fence_async_smem();
              tma2d_store(&P.m_ust, stg + ck * 8192, fb64 * 64, c.g1n * 192 + ck * 64);
            }
            TLREC(13 + wg);
            bulk_commit();
            bulk_wait_all();
            signal_stored(C_U + c.g1n * 4 + (fb64 / G2_KB) * 2 + wg);
            mbar_arrive(bars + 8 * (wg == 0 ? B_DED : B_EMPTY + 1));
            TLREC(15 + wg);
          }
        } else {
          if (c.g1m >= 0) {
            const int ch = c.fill();
            await(C_KV + ch / 96, tag * 128);
            fence_async_global();
            mbar_wait(bars + 8 * B_FILL, 0);
            sts128(sb + SLOT, 0, 0, 0, 0); sts128(sb + SLOT + 16, 0, 0, 0, 0);
            mbar_expect_tx(bars + 8 * B_CFULL, 8192 + 4096);
            bulk_load(sb + SLOT + 32, P.ssm_k + (size_t)ch * S_, 4096, bars + 8 * B_CFULL);
            bulk_load(sb, g_ub + (size_t)ch * 4096, 8192, bars + 8 * B_CFULL);
          }
          mbar_wait(bars + 8 * B_YDONE, 0);
          signal(C_Y);
          if (c.g2m >= 0) {
            await<true>(C_Y, tag * 132);
            fence_async_global(); fence_async_smem();
            if (blockIdx.x == 0) st_flag(&g_epoch, tag);
            TLREC(19);
            mbar_expect_tx(bars + 8 * B_Y2, 18432);
            tma2d(sb + SM_DED, &P.m_y, c.g2m * 128, c.dk(), bars + 8 * B_Y2);
            tma2d(sb + SM_DED + 9216, &P.m_y, c.g2m * 128 + 64, c.dk(), bars + 8 * B_Y2);
          }
        }
      }
    }
    TLEND();
  } else {
    asm volatile("barrier.cluster.arrive.relaxed.aligned;" ::: "memory");
    if (p0) {
      const int row = warp * 256 + blockIdx.x * 2 + (lane >> 4);
      const uint2* src = reinterpret_cast<const uint2*>(P.x + (size_t)row * D_) + (lane & 15);
      if (warp) pace(t0, XD0 + (warp - 1) * XD);
      uint32_t xr[18];
#pragma unroll
      for (int j = 0; j < 9; j++) asm volatile("ld.global.nc.v2.u32 {%0,%1}, [%2];" : "=r"(xr[2 * j]), "=r"(xr[2 * j + 1]) : "l"(src + 16 * j));
      float c[36];
      float s0 = 0.f, s1 = 0.f;
#pragma unroll
      for (int i = 0; i < 18; i++) { c[2 * i] = bf_lo(xr[i]); c[2 * i + 1] = bf_hi(xr[i]); s0 += c[2 * i]; s1 += c[2 * i + 1]; }
      const float ml = (s0 + s1) * (1.0f / 36.0f);
      if (tid == 0 && ml != 123.456f) TLREC(28);
      s0 = 0.f; s1 = 0.f;
#pragma unroll
      for (int i = 0; i < 18; i++) { c[2 * i] -= ml; c[2 * i + 1] -= ml; s0 = fmaf(c[2 * i], c[2 * i], s0); s1 = fmaf(c[2 * i + 1], c[2 * i + 1], s1); }
      float m = ml, q = s0 + s1, n2 = 18.f;
#pragma unroll
      for (int o = 1; o < 16; o <<= 1) {
        const float mo = __shfl_xor_sync(0xffffffffu, m, o), qo = __shfl_xor_sync(0xffffffffu, q, o);
        const float dl = m - mo;
        q = fmaf(dl * dl, n2, q + qo);
        m = 0.5f * (m + mo);
        n2 *= 2.f;
      }
      const float var = q * (1.0f / 576.0f);
      float mb, rinv, mb2, rinv2;
      ln_finish(m, var, mb, rinv);
      ln_finish((m - mb) * rinv, var * rinv * rinv, mb2, rinv2);
      const float ca = rinv * rinv2, cb = fmaf(ml - mb, rinv, -mb2) * rinv2;
      const uint32_t hs = sb + SM_DED + warp * 2304, ss = sb + SM_DED + 18432 + warp * 32;
#pragma unroll
      for (int j = 0; j < 9; j++)
        sts64(hs + (lane >> 4) * 1152 + (lane & 15) * 8 + j * 128, pack_bf16(fmaf(c[4 * j], ca, cb), fmaf(c[4 * j + 1], ca, cb)),
              pack_bf16(fmaf(c[4 * j + 2], ca, cb), fmaf(c[4 * j + 3], ca, cb)));
      if ((lane & 15) == 0) sts128(ss + lane, __float_as_uint(mb), __float_as_uint(rinv), 0, 0);
      __syncwarp();
      if (lane == 0) {
        if (tid == 0) TLREC(29);
        fence_async_smem();
        bulk_store(g_h + (size_t)row * D_, hs, 2304);
        bulk_store(g_stats + row, ss, 32);
        bulk_commit();
        bulk_wait_all();
        signal_stored(C_H + warp);
        if (tid == 0) TLREC(1);
        if (tid == 224) TLREC(31);
      }
      __syncwarp();
    }
    asm volatile("setmaxnreg.inc.sync.aligned.u32 224;");
    asm volatile("barrier.cluster.wait.aligned;" ::: "memory");
    const int wg = warp >> 2, w = warp & 3, g = lane >> 2, t = lane & 3, wtid = tid & 127;
    const bool elect = w == 0 && lane == 0;
    const uint64_t da0 = make_desc(sb + wg * 8192, 8192, 1024, 1);
    const uint32_t dm0 = (w == 0 && g + t == 7) ? 0xffffu : 0u, dm2 = (w == 0 && g + t == 3) ? 0xffffu : 0u;
    if (const Cta c(P); c.g1m >= 0) {
      const int frow = ((2 * c.g1m + c.rank) * 2 + wg) * 64 + w * 16 + g;
      const float hb0 = 0.5f * __bfloat162float(P.b1[frow]), hb1 = 0.5f * __bfloat162float(P.b1[frow + 8]);
      const uint32_t dd = __bfloat16_as_ushort(P.ssm_D[c.fill()]);
      {
        const uint64_t db0 = make_desc(sb + 16384, 8192, 1024, 1);
        float acc[96];
        Ring r{0, 0};
        uint32_t prev = 0;
        auto step = [&](int first, bool release) {
          mbar_wait(bars + 8 * (B_FULL + r.s), r.ph);
          const uint64_t da = da0 + r.s * (SLOT >> 4), db = db0 + r.s * (SLOT >> 4);
          wg_fence();
          wgmma_ss_n192_t11(acc, da, db, !first);
#pragma unroll
          for (int k = 1; k < 4; k++) wgmma_ss_n192_t11(acc, da + k * 128, db + k * 128, 1);
          wg_commit();
          if (release) { wg_wait<1>(); if (elect) mbar_arrive(bars + 8 * (B_EMPTY + prev)); }
          prev = r.s;
          r.next();
        };
        step(1, false);
        if (tid == 0) TLREC(3);
#pragma unroll 1
        for (int kb = 1; kb < G1_KB - G1_TAIL; kb++) step(0, true);
        if (elect) TLREC(20 + wg);
        if (wg == 1) {
          wg_wait<0>();
          if (elect) mbar_arrive(bars + 8 * (B_EMPTY + prev));
          bar_sync(5, 256);
        }
        step(0, wg == 0);
#pragma unroll 1
        for (int kb = G1_KB - G1_TAIL + 1; kb < G1_KB - 1; kb++) step(0, true);
        step(0, wg == 1);
        if (wg == 0) bar_arrive(5, 256);
        wg_wait<0>();
        pin_regs<96>(acc);
        if (elect) TLREC(4 + wg);
        if (wg == 0 && lane == 0) mbar_arrive(bars + 8 * B_FILL);
        mbar_wait(bars + 8 * (wg == 0 ? B_KVDONE : B_FILL), 0);
        const uint32_t stg = wg == 0 ? sb + SM_DED : sb + SLOT + 16384;
        const uint32_t sa = stg + ((lane >> 4) * 8 + (lane & 7)) * 128 + (((2 * w + ((lane >> 3) & 1)) ^ (lane & 7)) << 4);
#pragma unroll
        for (int ck = 0; ck < 3; ck++) {
          const uint32_t zero = blockIdx.y;
          uint32_t pk[16];
#pragma unroll
          for (int i = 0; i < 16; i++) {
            float hb = (i & 1) ? hb1 : hb0;
            if (i >= 6) asm("lop3.b32 %0, %1, %2, %3, 0xea;" : "=f"(hb) : "r"(pk[i - 6]), "r"(zero), "f"((i & 1) ? hb1 : hb0));
            pk[i] = pack_bf16(gelu_half(fmaf(acc[32 * ck + 2 * i], 0.5f, hb)), gelu_half(fmaf(acc[32 * ck + 2 * i + 1], 0.5f, hb)));
            if ((i & 3) == 3) stsm4t(sa + ck * 8192 + (i >> 2) * 2048, pk[i - 3], pk[i - 2], pk[i - 1], pk[i]);
          }
          __syncwarp();
          if (lane == 0) mbar_arrive(bars + 8 * (B_STG + wg * 3 + ck));
          if (ck < 2) mbar_wait(bars + 8 * B_KVDONE, 0);
        }
      }
      if (wg == 0) {
        uint32_t a[64];
        float acc[128];
        mbar_wait(bars + 8 * B_CFULL, 0);
#pragma unroll
        for (int j = 0; j < 32; j++) CONV_LDA(j, sb + SLOT + (8 * w + g + t + 1) * 4)
        a[0] = badd2(a[0], dd & dm0); a[2] = badd2(a[2], dd & dm2);
        wg_fence();
        conv_mma(acc, a, make_desc(sb, 4096, 128, 0));
        wg_commit();
        mbar_wait(bars + 8 * B_DED, 0);
        wg_wait<0>();
        pin_regs<128>(acc);
        if (elect) { TLREC(17); mbar_arrive(bars + 8 * B_EMPTY); mbar_arrive(bars + 8 * (B_EMPTY + 1)); }
        const uint32_t red = sb + SM_DED;
        if (lane < 8 * w) sts32(red + w * CV_REDW + lane * 4, 0);
#pragma unroll
        for (int j = 0; j < 32; j++) sts32(red + w * CV_REDW + (8 * (3 - t + w) + g) * 4 + j * 128, conv_part(acc, j));
        bar_sync(3, 128);
        uint4 p[2][4];
#pragma unroll
        for (int i = 0; i < 8; i++) p[i >> 2][i & 3] = lds128(red + (i & 3) * CV_REDW + (wtid + 128 * (i >> 2)) * 16);
        conv_out(p, Cta(P).fill(), wtid);
        __syncwarp();
        if (lane == 0) mbar_arrive(bars + 8 * B_YDONE);
        if (elect) TLREC(18);
      }
    } else {
      const int cvc = c.cvc(), n_conv = c.n_conv();
      const uint32_t red = wg == 0 ? sb + SM_DED : sb + CV_RED1;
      bar_sync(2, 256);
      if (wtid < 8 * CV_NSLOT / 2) sts32(sb + (2 * (wtid >> 3) + wg) * CV_SLOT + CV_KOFF + (wtid & 7) * 4, 0);
      sts32(red + w * CV_REDW + lane * 4, 0);
      bar_sync(3 + wg, 128);
      const uint32_t ko = sb + CV_KOFF + (8 * w + g + t + 1) * 4;
      const uint32_t wr = red + w * CV_REDW + (8 * (3 - t + w) + g) * 4;
      uint32_t a[64];
      uint32_t dd = __bfloat16_as_ushort(P.ssm_D[conv_channel(cvc, wg)]);
      mbar_wait(bars + 8 * (B_CFULL + wg), 0);
      if (tid == 0) TLREC(17);
#pragma unroll
      for (int j = 0; j < 32; j++) CONV_LDA(j, ko + wg * CV_SLOT)
      if (wg == 1) bar_arrive(5, 256);
#pragma unroll 1
      for (int i = wg; i < n_conv; i += 2) {
        const int s = i % CV_NSLOT;
        const int in = i + 2 < n_conv ? i + 2 : i, sn = in % CV_NSLOT;
        a[0] = badd2(a[0], dd & dm0); a[2] = badd2(a[2], dd & dm2);
        dd = __bfloat16_as_ushort(P.ssm_D[conv_channel(cvc, in)]);
        float acc[128];
        bar_sync(5 + wg, 256);
        wg_fence();
        conv_mma(acc, a, make_desc(sb + s * CV_SLOT, 4096, 128, 0));
        wg_commit();
        if (i + 1 < n_conv) bar_arrive(5 + (wg ^ 1), 256);
        wg_wait<0>();
        pin_regs<128>(acc);
        if (lane == 0) mbar_arrive(bars + 8 * (B_CEMPTY + s));
        mbar_wait(bars + 8 * (B_CFULL + sn), (in / CV_NSLOT) & 1);
        const uint32_t ka = ko + sn * CV_SLOT;
#pragma unroll
        for (int j = 0; j < 32; j++) {
          if (j < 24) CONV_LDA(j, ka)
          sts32(wr + j * 128, conv_part(acc, j));
        }
        bar_sync(3 + wg, 128);
        uint4 p[2][4];
#pragma unroll
        for (int x = 0; x < 8; x++) p[x >> 2][x & 3] = lds128(red + (x & 3) * CV_REDW + (wtid + 128 * (x >> 2)) * 16);
#pragma unroll
        for (int j = 24; j < 32; j++) CONV_LDA(j, ka)
        conv_out(p, conv_channel(cvc, i), wtid);
      }
      fence_async_smem();
      bar_sync(3 + wg, 128);
      if (elect) { mbar_arrive(bars + 8 * B_EMPTY); mbar_arrive(bars + 8 * (B_EMPTY + 1)); TLREC(20 + wg); }
      if (lane == 0) mbar_arrive(bars + 8 * B_YDONE);
      __syncwarp();
    }
    if (const Cta c(P); c.g2m >= 0) {
      const int srow = c.g2m * 128 + wg * 64 + w * 16 + g;
      const uint64_t db0 = make_desc(sb + 16384, 16, 1024, 1);
      float acc[72], acc2[36], acc3[36];
      Ring r{G1_KB % NSTAGE, (G1_KB / NSTAGE) & 1};
      uint32_t prev = 0;
      auto step = [&](int first) {
        mbar_wait(bars + 8 * (B_FULL + r.s), r.ph);
        const uint64_t da = da0 + r.s * (SLOT >> 4), db = db0 + r.s * (SLOT >> 4);
        wg_fence();
        wgmma_ss_n144_t10(acc, da, db, !first);
#pragma unroll
        for (int k = 1; k < 4; k++) wgmma_ss_n144_t10(acc, da + k * 128, db + k * 2, 1);
        wg_commit();
        if (!first) { wg_wait<1>(); if (elect) mbar_arrive(bars + 8 * (B_EMPTY + prev)); }
        prev = r.s;
        r.next();
      };
      step(1);
      if (tid == 128) TLREC(7);
      const float2 st0 = __ldcg(reinterpret_cast<const float2*>(g_stats + srow)), st1 = __ldcg(reinterpret_cast<const float2*>(g_stats + srow + 8));
      const float hb0 = 0.5f * __bfloat162float(P.b2[srow]), hb1 = 0.5f * __bfloat162float(P.b2[srow + 8]);
#pragma unroll 1
      for (int kb = 1; kb < G2_KB - G2_TAIL; kb++) step(0);
      if (tid == 0) TLREC(30);
      const uint32_t xo = sb + ((XSLOT + 1 + (warp >> 1)) % NSTAGE) * SLOT + G2_BYTES + (warp & 1) * 2304;
      const uint32_t xa = xo + (lane & 15) * 144 + (lane >> 4) * 16;
      uint32_t xx[18], ss[18];
      auto prep = [&]() {
        mbar_wait(bars + 8 * B_XT, 0);
        mbar_wait(bars + 8 * B_Y2, 0);
        const uint32_t ya = sb + SM_DED + wg * 9216 + ((lane >> 4) * 8 + (lane & 7)) * 128 + (((2 * w + ((lane >> 3) & 1)) ^ (lane & 7)) << 4);
#pragma unroll
        for (int q = 0; q < 8; q += 2) { ldsm4(xx + 2 * q, xa + q * 16); ldsm4t(ss + 2 * q, ya + q * 1024); }
        ldsm2(xx + 16, xo + (lane & 15) * 144 + 128);
        ldsm2t(ss + 16, ya - (lane >> 4) * 1024 + 8 * 1024);
        const uint32_t m0 = pack_bf16(st0.x, st0.x), m1 = pack_bf16(st1.x, st1.x);
#pragma unroll
        for (int i = 0; i < 18; i++) ss[i] = bmul2(ln_apply(xx[i], (i & 1) ? m1 : m0, (i & 1) ? st1.y : st0.y), ss[i]);
      };
      if (wg == 1) {
        wg_wait<0>();
        if (elect) mbar_arrive(bars + 8 * (B_EMPTY + XSLOT));
        prep();
        bar_sync(5, 256);
      }
#pragma unroll
      for (int kb = G2_KB - G2_TAIL; kb < G2_KB; kb++) {
        const int p = G1_KB + kb, s = p % NSTAGE;
        mbar_wait(bars + 8 * (B_FULL + s), (p / NSTAGE) & 1);
        wg_fence();
#pragma unroll
        for (int k = 0; k < 4; k++)
          wgmma_ss_n72_t10(acc3, da0 + s * (SLOT >> 4) + k * 128, db0 + s * (SLOT >> 4) + k * 2, kb != G2_KB - G2_TAIL || k != 0);
        wg_commit();
        if (kb == G2_KB - G2_TAIL) { wg_wait<1>(); if (tid == 0) mbar_arrive(bars + 8 * (B_EMPTY + XSLOT)); }
      }
      bar_arrive(5 + wg, 256);
      wg_wait<0>();
      pin_regs<72>(acc);
      pin_regs<36>(acc3);
      const uint32_t xz = sb + XSLOT * SLOT + wg * 18432 + wtid * 16;
      mbar_wait(bars + 8 * B_XRDY, 0);
      {
        const uint32_t rz = mapa(xz, c.rank ^ 1), rb = mapa(bars + 8 * (B_XFULL + wg), c.rank ^ 1);
#pragma unroll
        for (int q = 0; q < 9; q++)
          asm volatile("st.async.weak.shared::cluster.mbarrier::complete_tx::bytes.v4.f32 [%0], {%1,%2,%3,%4}, [%5];"
                       :: "r"(rz + q * 2048), "f"(acc[4 * q] + acc3[4 * q]), "f"(acc[4 * q + 1] + acc3[4 * q + 1]), "f"(acc[4 * q + 2] + acc3[4 * q + 2]),
                          "f"(acc[4 * q + 3] + acc3[4 * q + 3]), "r"(rb) : "memory");
      }
      if (wg == 0) prep();
      bar_sync(6 - wg, 256);
      wg_fence();
#pragma unroll
      for (int kb = G2_KB - G2_TAIL; kb < G2_KB; kb++) {
        const int s = (G1_KB + kb) % NSTAGE;
#pragma unroll
        for (int k = 0; k < 4; k++)
          wgmma_ss_n72_t10(acc2, da0 + s * (SLOT >> 4) + k * 128, db0 + s * (SLOT >> 4) + (9216 >> 4) + k * 2, kb != G2_KB - G2_TAIL || k != 0);
      }
      wg_commit();
      if (wg == 0) bar_arrive(5, 256);
      mbar_wait_cluster(bars + 8 * (B_XFULL + wg), 0);
#pragma unroll
      for (int q = 0; q < 9; q++) {
        const float4 pv = lds128f(xz + q * 2048);
        acc[36 + 4 * q] = fmaf(acc[36 + 4 * q] + pv.x, 0.5f, hb0); acc[37 + 4 * q] = fmaf(acc[37 + 4 * q] + pv.y, 0.5f, hb0);
        acc[38 + 4 * q] = fmaf(acc[38 + 4 * q] + pv.z, 0.5f, hb1); acc[39 + 4 * q] = fmaf(acc[39 + 4 * q] + pv.w, 0.5f, hb1);
      }
      wg_wait<0>();
      pin_regs<36>(acc2);
      if (elect) TLREC(9 + wg);
      uint32_t ob[18];
#pragma unroll
      for (int i = 0; i < 18; i++)
        ob[i] = bfma2(ss[i], pack_bf16(silu_half(fmaf(acc2[2 * i], 0.5f, acc[36 + 2 * i])), silu_half(fmaf(acc2[2 * i + 1], 0.5f, acc[37 + 2 * i]))), xx[i]);
#pragma unroll
      for (int q = 0; q < 8; q += 2) stsm4(xa + q * 16, ob[2 * q], ob[2 * q + 1], ob[2 * q + 2], ob[2 * q + 3]);
      stsm2(xo + (lane & 15) * 144 + 128, ob[16], ob[17]);
      __syncwarp();
      if (lane == 0) {
        fence_async_smem();
        tma2d_store(&P.m_out, xo, Cta(P).dk(), srow);
        bulk_commit();
        bulk_wait_read();
      }
      if (elect) TLREC(11 + wg);
    }
    TLEND();
  }
}

typedef CUresult (*EncodeFn)(CUtensorMap*, CUtensorMapDataType, cuuint32_t, void*, const cuuint64_t*, const cuuint64_t*, const cuuint32_t*,
                             const cuuint32_t*, CUtensorMapInterleave, CUtensorMapSwizzle, CUtensorMapL2promotion, CUtensorMapFloatOOBfill);

void make_map(EncodeFn fn, CUtensorMap* m, const void* ptr, int rank, const cuuint64_t* dims, const cuuint64_t* strides, const cuuint32_t* box,
              CUtensorMapSwizzle sw) {
  const cuuint32_t es[3] = {1, 1, 1};
  fn(m, CU_TENSOR_MAP_DATA_TYPE_BFLOAT16, rank, const_cast<void*>(ptr), dims, strides, box, es, CU_TENSOR_MAP_INTERLEAVE_NONE, sw,
     CU_TENSOR_MAP_L2_PROMOTION_L2_256B, CU_TENSOR_MAP_FLOAT_OOB_FILL_NONE);
}

void make_roles(Roles& R) {
  int c1 = 0, ncv = 2;
  for (int g = 0; g < 8; g++)
    for (int c = 0; c < 66; c++) {
      const int tp = (c + 62) % 66;
      int gg, idx;
      if (tp < 32) { gg = tp % 8; idx = tp / 8; }
      else if (tp < 60) { gg = 1 + (tp - 32) % 7; idx = 4 + (tp - 32) / 7; }
      else if (tp < 62) { gg = 6 + tp - 60; idx = 8; }
      else { gg = 0; idx = 4 + tp - 62; }
      if (gg != g) continue;
      Role& r = R.r[c];
      if (idx < 8) { r.g2m = (int8_t)(2 * g + idx / 4); r.g2n = (int8_t)(idx % 4); }
      else { r.g2m = -1; r.g2n = 0; }
      if (idx < (g < 2 ? 6 : 7)) { r.g1m = (int8_t)(c1 / 3); r.g1n = (int8_t)(c1 % 3); c1++; }
      else { r.g1m = (int8_t)(-1 - (idx == 8 ? tp - 60 : ncv++)); r.g1n = 0; }
    }
}

}

extern "C" void kernel_launch(void* const* d_in, const int* in_sizes, int n_in, void* d_out, int out_size) {
  static Params P;
  static const void* cached[4] = {nullptr, nullptr, nullptr, nullptr};
  if (cached[0] != d_in[7] || cached[1] != d_in[9] || cached[2] != d_out || cached[3] != d_in[0]) {
    void* fp = nullptr;
    cudaDriverEntryPointQueryResult qr;
    cudaGetDriverEntryPoint("cuTensorMapEncodeTiled", &fp, cudaEnableDefault, &qr);
    EncodeFn fn = (EncodeFn)fp;
    void *ph, *pu, *py, *pb;
    cudaGetSymbolAddress(&pb, g_ub);
    cudaGetSymbolAddress(&py, g_y);
    cudaGetSymbolAddress(&ph, g_h);
    cudaGetSymbolAddress(&pu, g_u);
    { cuuint64_t d[3] = {64, S_, F_ / 64}, s[2] = {F_ * 2, 128}; cuuint32_t b[3] = {64, 64, 2}; make_map(fn, &P.m_w1, d_in[7], 3, d, s, b, CU_TENSOR_MAP_SWIZZLE_128B); }
    { cuuint64_t d[3] = {64, S_, D_ / 64}, s[2] = {D_ * 2, 128}; cuuint32_t b[3] = {64, 64, 3}; make_map(fn, &P.m_h, ph, 3, d, s, b, CU_TENSOR_MAP_SWIZZLE_128B); }
    { cuuint64_t d[2] = {F_, D_}, s[1] = {F_ * 2}; cuuint32_t b[2] = {64, 64}; make_map(fn, &P.m_ust, pu, 2, d, s, b, CU_TENSOR_MAP_SWIZZLE_128B); }
    { cuuint64_t d[3] = {64, F_, S_ / 64}, s[2] = {S_ * 2, 128}; cuuint32_t b[3] = {64, 64, 2}; make_map(fn, &P.m_w2, d_in[9], 3, d, s, b, CU_TENSOR_MAP_SWIZZLE_128B); }
    { cuuint64_t d[2] = {F_, D_}, s[1] = {F_ * 2}; cuuint32_t b[2] = {64, 72}; make_map(fn, &P.m_uld, pu, 2, d, s, b, CU_TENSOR_MAP_SWIZZLE_128B); }
    { cuuint64_t d[2] = {D_, S_}, s[1] = {D_ * 2}; cuuint32_t b[2] = {72, 16}; make_map(fn, &P.m_out, d_out, 2, d, s, b, CU_TENSOR_MAP_SWIZZLE_NONE);
      make_map(fn, &P.m_x, d_in[0], 2, d, s, b, CU_TENSOR_MAP_SWIZZLE_NONE); }
    { cuuint64_t d[2] = {S_, D_}, s[1] = {S_ * 2}; cuuint32_t b[2] = {64, 72}; make_map(fn, &P.m_y, py, 2, d, s, b, CU_TENSOR_MAP_SWIZZLE_128B); }
    { cuuint64_t d[3] = {2048, D_ / 2, 4}, s[2] = {16384, 4096}; cuuint32_t b[3] = {16, 48, 4}; make_map(fn, &P.m_ub, pb, 3, d, s, b, CU_TENSOR_MAP_SWIZZLE_NONE); }
    make_roles(P.roles);
    cudaFuncSetAttribute(fused_kernel, cudaFuncAttributeMaxDynamicSharedMemorySize, SM_TOTAL);
    cached[0] = d_in[7]; cached[1] = d_in[9]; cached[2] = d_out; cached[3] = d_in[0];
  }
  P.x = (const __nv_bfloat16*)d_in[0]; P.k = (const __nv_bfloat16*)d_in[1]; P.v = (const __nv_bfloat16*)d_in[2];
  P.shift_k = (const __nv_bfloat16*)d_in[3]; P.ssm_k = (const __nv_bfloat16*)d_in[4]; P.ssm_D = (const __nv_bfloat16*)d_in[5];
  P.b1 = (const __nv_bfloat16*)d_in[8]; P.b2 = (const __nv_bfloat16*)d_in[10];
  fused_kernel<<<132, 384, SM_TOTAL>>>(P);
}
```

```cpp
#include <cuda_runtime.h>
#include <cuda.h>
#include <cuda_bf16.h>
#include <stdint.h>

namespace {

constexpr int S_ = 2048, D_ = 576, F_ = 4608;
constexpr int NSTAGE = 5, SLOT = 40960;
constexpr int G1_KB = 32, G2_KB = 36;
constexpr int G1_BYTES = 40960, G2_BYTES = 16384 + 18432;
constexpr int N_CONV_CTA = 24, N_SHORT = 18, N_LONG_EXTRA = 9, CH_FILL = N_CONV_CTA * N_SHORT + 4 * N_LONG_EXTRA;
static_assert(CH_FILL + 108 == D_, "conv split");
constexpr int KV_ROUNDS = 6;
#define G1T 5
constexpr int G1_TAIL = G1T, G2_TAIL = 4;
constexpr uint32_t XD0 = 200, XD = 0, W1T0 = 1800, W1D = 900, KVT0 = 2400, STAG = 60, CKT0 = 2400;
#define PF1 0
#define PF2 0

constexpr int SM_DED = NSTAGE * SLOT;
constexpr int SM_KVS = SM_DED + 18944;
constexpr int SM_BAR = SM_KVS + 6144;
constexpr int SM_TOTAL = SM_BAR + 256 + 1024;
constexpr int CV_NSLOT = 4, CV_KOFF = 8192, CV_SLOT = 8192 + 4224;
constexpr int CV_REDW = 2112 * 2, CV_RED1 = CV_NSLOT * CV_SLOT;
static_assert(CV_RED1 + 4 * CV_REDW <= 2 * SLOT, "conv overlay");
static_assert(G1_KB % NSTAGE == 2, "slots 0 and 1 hold the last two GEMM1 k-blocks");
constexpr int XSLOT = (G1_KB + G2_KB) % NSTAGE;
constexpr int B_FULL = 0, B_EMPTY = NSTAGE, B_CFULL = 2 * NSTAGE, B_STG = B_CFULL + CV_NSLOT  , B_CEMPTY = B_STG,
              B_FILL = B_STG + 6, B_YDONE = B_FILL + 1, B_XRDY = B_YDONE + 1, B_XFULL = B_XRDY + 1  , B_XT = B_XFULL + 2,
              B_Y2 = B_XT + 1, B_KVDONE = B_Y2 + 1, B_DED = B_KVDONE + 1, B_ULATE = B_DED + 1, B_GO = B_ULATE + 1;
static_assert(B_GO < 32, "barrier page");
constexpr int C_H = 0  , C_KV = 8, C_U = C_KV + KV_ROUNDS  , C_Y = C_U + 12, C_COUNT = C_Y + 1;

struct Role {
  int8_t g1m;
  int8_t g1n;
  int8_t g2m;
  int8_t g2n;
};
struct Roles { Role r[66]; };

struct Params {
  const __nv_bfloat16 *x, *k, *v, *shift_k, *ssm_k, *ssm_D, *b1, *b2;
  Roles roles;
  CUtensorMap m_w1, m_h, m_ust, m_w2, m_uld, m_out, m_x, m_y, m_ub;
};

__device__ __align__(1024) __nv_bfloat16 g_h[S_ * D_];
__device__ __align__(1024) __nv_bfloat16 g_ub[D_ * 4096];
__device__ __align__(1024) __nv_bfloat16 g_y[D_ * S_];
__device__ __align__(1024) __nv_bfloat16 g_u[D_ * F_];
__device__ __align__(128) float4 g_stats[S_];
__device__ __align__(128) uint32_t g_cnt[C_COUNT * 32];
__device__ __align__(128) uint32_t g_epoch;
#define TLREC(i) do { } while (0)
#define TLEND() do { } while (0)

__device__ __forceinline__ uint32_t smem_u32(const void* p) { return (uint32_t)__cvta_generic_to_shared(p); }
__device__ __forceinline__ void mbar_init(uint32_t bar, uint32_t cnt) { asm volatile("mbarrier.init.shared::cta.b64 [%0], %1;" :: "r"(bar), "r"(cnt) : "memory"); }
__device__ __forceinline__ void mbar_expect_tx(uint32_t bar, uint32_t bytes) { asm volatile("mbarrier.arrive.expect_tx.shared::cta.b64 _, [%0], %1;" :: "r"(bar), "r"(bytes) : "memory"); }
__device__ __forceinline__ void mbar_arrive(uint32_t bar) { asm volatile("mbarrier.arrive.shared::cta.b64 _, [%0];" :: "r"(bar) : "memory"); }
__device__ __forceinline__ uint32_t mapa(uint32_t addr, uint32_t cta) { uint32_t r; asm volatile("mapa.shared::cluster.u32 %0, %1, %2;" : "=r"(r) : "r"(addr), "r"(cta)); return r; }
__device__ __forceinline__ void mbar_arrive_remote(uint32_t rbar) { asm volatile("mbarrier.arrive.shared::cluster.b64 _, [%0];" :: "r"(rbar) : "memory"); }
__device__ __forceinline__ void mbar_wait(uint32_t bar, uint32_t parity) {
  asm volatile("{\n .reg .pred p;\n .reg .u32 c;\n mov.u32 c, 0;\n"
               "W_%=:\n mbarrier.try_wait.parity.shared::cta.b64 p, [%0], %1;\n @p bra D_%=;\n"
               " add.u32 c, c, 1;\n setp.lt.u32 p, c, 2000000;\n @p bra W_%=;\n trap;\n D_%=:\n }" :: "r"(bar), "r"(parity) : "memory");
}
__device__ __forceinline__ void mbar_wait_cluster(uint32_t bar, uint32_t parity) {
  asm volatile("{\n .reg .pred p;\n .reg .u32 c;\n mov.u32 c, 0;\n"
               "W_%=:\n mbarrier.try_wait.parity.acquire.cluster.shared::cta.b64 p, [%0], %1;\n @p bra D_%=;\n"
               " add.u32 c, c, 1;\n setp.lt.u32 p, c, 2000000;\n @p bra W_%=;\n trap;\n D_%=:\n }" :: "r"(bar), "r"(parity) : "memory");
}
__device__ __forceinline__ void tma2d(uint32_t dst, const CUtensorMap* m, int c0, int c1, uint32_t bar) {
  asm volatile("cp.async.bulk.tensor.2d.shared::cluster.global.mbarrier::complete_tx::bytes [%0], [%1, {%3, %4}], [%2];"
               :: "r"(dst), "l"(m), "r"(bar), "r"(c0), "r"(c1) : "memory");
}
__device__ __forceinline__ void tma3d(uint32_t dst, const CUtensorMap* m, int c0, int c1, int c2, uint32_t bar) {
  asm volatile("cp.async.bulk.tensor.3d.shared::cluster.global.mbarrier::complete_tx::bytes [%0], [%1, {%3, %4, %5}], [%2];"
               :: "r"(dst), "l"(m), "r"(bar), "r"(c0), "r"(c1), "r"(c2) : "memory");
}
__device__ __forceinline__ void tma3d_ef(uint32_t dst, const CUtensorMap* m, int c0, int c1, int c2, uint32_t bar) {
  tma3d(dst, m, c0, c1, c2, bar);
}
__device__ __forceinline__ void pf3d(const CUtensorMap* m, int c0, int c1, int c2) {
  asm volatile("cp.async.bulk.prefetch.tensor.3d.L2.global [%0, {%1, %2, %3}];" :: "l"(m), "r"(c0), "r"(c1), "r"(c2) : "memory");
}
__device__ __forceinline__ void tma2d_store(const CUtensorMap* m, uint32_t src, int c0, int c1) {
  asm volatile("cp.async.bulk.tensor.2d.global.shared::cta.bulk_group [%0, {%2, %3}], [%1];" :: "l"(m), "r"(src), "r"(c0), "r"(c1) : "memory");
}
__device__ __forceinline__ void bulk_load(uint32_t dst, const void* src, uint32_t bytes, uint32_t bar) {
  asm volatile("cp.async.bulk.shared::cluster.global.mbarrier::complete_tx::bytes [%0], [%1], %2, [%3];" :: "r"(dst), "l"(src), "r"(bytes), "r"(bar) : "memory");
}
__device__ __forceinline__ void bulk_store(void* dst, uint32_t src, uint32_t bytes) {
  asm volatile("cp.async.bulk.global.shared::cta.bulk_group [%0], [%1], %2;" :: "l"(dst), "r"(src), "r"(bytes) : "memory");
}
__device__ __forceinline__ void tma3d_store(const CUtensorMap* m, uint32_t src, int c0, int c1, int c2) {
  asm volatile("cp.async.bulk.tensor.3d.global.shared::cta.bulk_group [%0, {%2, %3, %4}], [%1];" :: "l"(m), "r"(src), "r"(c0), "r"(c1), "r"(c2) : "memory");
}
__device__ __forceinline__ void bulk_commit() { asm volatile("cp.async.bulk.commit_group;" ::: "memory"); }
__device__ __forceinline__ void bulk_wait_all() { asm volatile("cp.async.bulk.wait_group 0;" ::: "memory"); }
__device__ __forceinline__ void bulk_wait_read() { asm volatile("cp.async.bulk.wait_group.read 0;" ::: "memory"); }
__device__ __forceinline__ void fence_async_smem() { asm volatile("fence.proxy.async.shared::cta;" ::: "memory"); }
__device__ __forceinline__ void fence_async_global() { asm volatile("fence.proxy.async.global;" ::: "memory"); }
__device__ __forceinline__ void st_flag(uint32_t* p, uint32_t v) { asm volatile("st.relaxed.gpu.global.u32 [%0], %1;" :: "l"(p), "r"(v) : "memory"); }
__device__ __forceinline__ uint32_t ld_flag(const uint32_t* p) { uint32_t v; asm volatile("ld.relaxed.gpu.global.u32 %0, [%1];" : "=r"(v) : "l"(p) : "memory"); return v; }
__device__ __forceinline__ void signal(int c) { asm volatile("red.release.gpu.global.add.u32 [%0], 1;" :: "l"(g_cnt + c * 32) : "memory"); }
__device__ __forceinline__ void signal_stored(int c) { asm volatile("red.relaxed.gpu.global.add.u32 [%0], 1;" :: "l"(g_cnt + c * 32) : "memory"); }
__device__ __forceinline__ bool reached(int c, uint32_t target) {
  uint32_t v; asm volatile("ld.acquire.gpu.global.u32 %0, [%1];" : "=r"(v) : "l"(g_cnt + c * 32) : "memory");
  return (int32_t)(v - target) >= 0;
}
__device__ __forceinline__ uint32_t clk() { uint32_t c; asm volatile("mov.u32 %0, %%clock;" : "=r"(c)); return c; }
__device__ __forceinline__ void pace(uint32_t t0, uint32_t dt) { while (clk() - t0 < dt) { } }
__device__ __forceinline__ int cta_id() { int c; asm volatile("mov.u32 %0, %%ctaid.x;" : "=r"(c)); return c; }
template <bool SLOW = false> __device__ __forceinline__ void await(int c, uint32_t target) {
  uint32_t n = 0;
  while (true) {
    uint32_t v; asm volatile("ld.acquire.gpu.global.u32 %0, [%1];" : "=r"(v) : "l"(g_cnt + c * 32) : "memory");
    if ((int32_t)(v - target) >= 0) break;
#define SLEEPNS 300
    if (SLOW) __nanosleep(SLEEPNS);
    if (++n > 4000000u) __trap();
  }
}
__device__ __forceinline__ void bar_sync(int id, int n) { asm volatile("bar.sync %0, %1;" :: "r"(id), "r"(n) : "memory"); }
__device__ __forceinline__ void bar_arrive(int id, int n) { asm volatile("bar.arrive %0, %1;" :: "r"(id), "r"(n) : "memory"); }
__device__ __forceinline__ void wg_fence() { asm volatile("wgmma.fence.sync.aligned;" ::: "memory"); }
__device__ __forceinline__ void wg_commit() { asm volatile("wgmma.commit_group.sync.aligned;" ::: "memory"); }
template <int N> __device__ __forceinline__ void wg_wait() { asm volatile("wgmma.wait_group.sync.aligned %0;" :: "n"(N) : "memory"); }
template <int N> __device__ __forceinline__ void pin_regs(float* a) {
#pragma unroll
  for (int i = 0; i < N; i++) asm volatile("" : "+f"(a[i]) :: "memory");
}
__device__ __forceinline__ uint64_t make_desc(uint32_t addr, uint32_t lbo, uint32_t sbo, uint32_t swz) {
  return (uint64_t)((addr & 0x3FFFF) >> 4) | ((uint64_t)(lbo >> 4) << 16) | ((uint64_t)(sbo >> 4) << 32) | ((uint64_t)swz << 62);
}
__device__ __forceinline__ uint32_t pack_bf16(float lo, float hi) { uint32_t r; asm("cvt.rn.bf16x2.f32 %0, %1, %2;" : "=r"(r) : "f"(hi), "f"(lo)); return r; }
__device__ __forceinline__ float bf_lo(uint32_t p) { return __uint_as_float(p << 16); }
__device__ __forceinline__ float bf_hi(uint32_t p) { return __uint_as_float(p & 0xffff0000u); }
__device__ __forceinline__ float round_bf16(float v) { return bf_lo(pack_bf16(v, 0.f)); }
__device__ __forceinline__ uint32_t bmul2(uint32_t a, uint32_t b) { uint32_t r; asm("mul.rn.bf16x2 %0, %1, %2;" : "=r"(r) : "r"(a), "r"(b)); return r; }
__device__ __forceinline__ uint32_t badd2(uint32_t a, uint32_t b) { uint32_t r; asm("add.rn.bf16x2 %0, %1, %2;" : "=r"(r) : "r"(a), "r"(b)); return r; }
__device__ __forceinline__ uint32_t bfma2(uint32_t a, uint32_t b, uint32_t c) { uint32_t r; asm("fma.rn.bf16x2 %0, %1, %2, %3;" : "=r"(r) : "r"(a), "r"(b), "r"(c)); return r; }
__device__ __forceinline__ uint32_t bsub2(uint32_t a, uint32_t b) { uint32_t r; asm("sub.rn.bf16x2 %0, %1, %2;" : "=r"(r) : "r"(a), "r"(b)); return r; }
__device__ __forceinline__ float tanh_fast(float v) { float r; asm("tanh.approx.f32 %0, %1;" : "=f"(r) : "f"(v)); return r; }
__device__ __forceinline__ float gelu_half(float h) {
  return fmaf(h, tanh_fast(h * fmaf(h * h, 8.0f * 0.7978845608028654f * 0.044715f, 2.0f * 0.7978845608028654f)), h);
}
__device__ __forceinline__ float silu_half(float h) { return fmaf(h, tanh_fast(h), h); }
__device__ __forceinline__ uint32_t ldg32(const void* p) { uint32_t v; asm volatile("ld.global.nc.u32 %0, [%1];" : "=r"(v) : "l"(p)); return v; }
__device__ __forceinline__ uint32_t lds32(uint32_t a) { uint32_t v; asm volatile("ld.shared.u32 %0, [%1];" : "=r"(v) : "r"(a) : "memory"); return v; }
__device__ __forceinline__ float4 lds128f(uint32_t a) { float4 v; asm volatile("ld.shared.v4.f32 {%0,%1,%2,%3}, [%4];" : "=f"(v.x), "=f"(v.y), "=f"(v.z), "=f"(v.w) : "r"(a) : "memory"); return v; }
__device__ __forceinline__ uint4 lds128(uint32_t a) { uint4 v; asm volatile("ld.shared.v4.u32 {%0,%1,%2,%3}, [%4];" : "=r"(v.x), "=r"(v.y), "=r"(v.z), "=r"(v.w) : "r"(a) : "memory"); return v; }
__device__ __forceinline__ void sts64(uint32_t a, uint32_t x, uint32_t y) { asm volatile("st.shared.v2.u32 [%0], {%1,%2};" :: "r"(a), "r"(x), "r"(y) : "memory"); }
__device__ __forceinline__ void sts128(uint32_t a, uint32_t x, uint32_t y, uint32_t z, uint32_t w) {
  asm volatile("st.shared.v4.u32 [%0], {%1,%2,%3,%4};" :: "r"(a), "r"(x), "r"(y), "r"(z), "r"(w) : "memory");
}
__device__ __forceinline__ void sts32(uint32_t a, uint32_t v) { asm volatile("st.shared.u32 [%0], %1;" :: "r"(a), "r"(v) : "memory"); }
__device__ __forceinline__ void ldsm4(uint32_t* r, uint32_t a) {
  asm volatile("ldmatrix.sync.aligned.m8n8.x4.shared.b16 {%0,%1,%2,%3}, [%4];" : "=r"(r[0]), "=r"(r[1]), "=r"(r[2]), "=r"(r[3]) : "r"(a) : "memory");
}
__device__ __forceinline__ void ldsm2(uint32_t* r, uint32_t a) {
  asm volatile("ldmatrix.sync.aligned.m8n8.x2.shared.b16 {%0,%1}, [%2];" : "=r"(r[0]), "=r"(r[1]) : "r"(a) : "memory");
}
__device__ __forceinline__ void ldsm4t(uint32_t* r, uint32_t a) {
  asm volatile("ldmatrix.sync.aligned.m8n8.x4.trans.shared.b16 {%0,%1,%2,%3}, [%4];" : "=r"(r[0]), "=r"(r[1]), "=r"(r[2]), "=r"(r[3]) : "r"(a) : "memory");
}
__device__ __forceinline__ void ldsm2t(uint32_t* r, uint32_t a) {
  asm volatile("ldmatrix.sync.aligned.m8n8.x2.trans.shared.b16 {%0,%1}, [%2];" : "=r"(r[0]), "=r"(r[1]) : "r"(a) : "memory");
}
__device__ __forceinline__ void stsm4(uint32_t a, uint32_t r0, uint32_t r1, uint32_t r2, uint32_t r3) {
  asm volatile("stmatrix.sync.aligned.m8n8.x4.shared.b16 [%0], {%1,%2,%3,%4};" :: "r"(a), "r"(r0), "r"(r1), "r"(r2), "r"(r3) : "memory");
}
__device__ __forceinline__ void stsm2(uint32_t a, uint32_t r0, uint32_t r1) {
  asm volatile("stmatrix.sync.aligned.m8n8.x2.shared.b16 [%0], {%1,%2};" :: "r"(a), "r"(r0), "r"(r1) : "memory");
}
__device__ __forceinline__ void stsm4t(uint32_t a, uint32_t r0, uint32_t r1, uint32_t r2, uint32_t r3) {
  asm volatile("stmatrix.sync.aligned.m8n8.x4.trans.shared.b16 [%0], {%1,%2,%3,%4};" :: "r"(a), "r"(r0), "r"(r1), "r"(r2), "r"(r3) : "memory");
}

__device__ __forceinline__ void wgmma_ss_n144_t10(float* d, uint64_t da, uint64_t db, int sd) {
  asm volatile("{ .reg .pred p; setp.ne.b32 p, %74, 0;\n"
      "wgmma.mma_async.sync.aligned.m64n144k16.f32.bf16.bf16 {"
      "%0,%1,%2,%3,%4,%5,%6,%7,%8,%9,%10,%11,%12,%13,%14,%15,"
      "%16,%17,%18,%19,%20,%21,%22,%23,%24,%25,%26,%27,%28,%29,%30,%31,"
      "%32,%33,%34,%35,%36,%37,%38,%39,%40,%41,%42,%43,%44,%45,%46,%47,"
      "%48,%49,%50,%51,%52,%53,%54,%55,%56,%57,%58,%59,%60,%61,%62,%63,"
      "%64,%65,%66,%67,%68,%69,%70,%71"
      "}, %72, %73, p, 1, 1, 1, 0; }"
    : "+f"(d[0]), "+f"(d[1]), "+f"(d[2]), "+f"(d[3]), "+f"(d[4]), "+f"(d[5]), "+f"(d[6]), "+f"(d[7]),
      "+f"(d[8]), "+f"(d[9]), "+f"(d[10]), "+f"(d[11]), "+f"(d[12]), "+f"(d[13]), "+f"(d[14]), "+f"(d[15]),
      "+f"(d[16]), "+f"(d[17]), "+f"(d[18]), "+f"(d[19]), "+f"(d[20]), "+f"(d[21]), "+f"(d[22]), "+f"(d[23]),
      "+f"(d[24]), "+f"(d[25]), "+f"(d[26]), "+f"(d[27]), "+f"(d[28]), "+f"(d[29]), "+f"(d[30]), "+f"(d[31]),
      "+f"(d[32]), "+f"(d[33]), "+f"(d[34]), "+f"(d[35]), "+f"(d[36]), "+f"(d[37]), "+f"(d[38]), "+f"(d[39]),
      "+f"(d[40]), "+f"(d[41]), "+f"(d[42]), "+f"(d[43]), "+f"(d[44]), "+f"(d[45]), "+f"(d[46]), "+f"(d[47]),
      "+f"(d[48]), "+f"(d[49]), "+f"(d[50]), "+f"(d[51]), "+f"(d[52]), "+f"(d[53]), "+f"(d[54]), "+f"(d[55]),
      "+f"(d[56]), "+f"(d[57]), "+f"(d[58]), "+f"(d[59]), "+f"(d[60]), "+f"(d[61]), "+f"(d[62]), "+f"(d[63]),
      "+f"(d[64]), "+f"(d[65]), "+f"(d[66]), "+f"(d[67]), "+f"(d[68]), "+f"(d[69]), "+f"(d[70]), "+f"(d[71])
    : "l"(da), "l"(db), "r"(sd));
}

__device__ __forceinline__ void wgmma_ss_n192_t11(float* d, uint64_t da, uint64_t db, int sd) {
  asm volatile("{ .reg .pred p; setp.ne.b32 p, %98, 0;\n"
      "wgmma.mma_async.sync.aligned.m64n192k16.f32.bf16.bf16 {"
      "%0,%1,%2,%3,%4,%5,%6,%7,%8,%9,%10,%11,%12,%13,%14,%15,"
      "%16,%17,%18,%19,%20,%21,%22,%23,%24,%25,%26,%27,%28,%29,%30,%31,"
      "%32,%33,%34,%35,%36,%37,%38,%39,%40,%41,%42,%43,%44,%45,%46,%47,"
      "%48,%49,%50,%51,%52,%53,%54,%55,%56,%57,%58,%59,%60,%61,%62,%63,"
      "%64,%65,%66,%67,%68,%69,%70,%71,%72,%73,%74,%75,%76,%77,%78,%79,"
      "%80,%81,%82,%83,%84,%85,%86,%87,%88,%89,%90,%91,%92,%93,%94,%95"
      "}, %96, %97, p, 1, 1, 1, 1; }"
    : "+f"(d[0]), "+f"(d[1]), "+f"(d[2]), "+f"(d[3]), "+f"(d[4]), "+f"(d[5]), "+f"(d[6]), "+f"(d[7]),
      "+f"(d[8]), "+f"(d[9]), "+f"(d[10]), "+f"(d[11]), "+f"(d[12]), "+f"(d[13]), "+f"(d[14]), "+f"(d[15]),
      "+f"(d[16]), "+f"(d[17]), "+f"(d[18]), "+f"(d[19]), "+f"(d[20]), "+f"(d[21]), "+f"(d[22]), "+f"(d[23]),
      "+f"(d[24]), "+f"(d[25]), "+f"(d[26]), "+f"(d[27]), "+f"(d[28]), "+f"(d[29]), "+f"(d[30]), "+f"(d[31]),
      "+f"(d[32]), "+f"(d[33]), "+f"(d[34]), "+f"(d[35]), "+f"(d[36]), "+f"(d[37]), "+f"(d[38]), "+f"(d[39]),
      "+f"(d[40]), "+f"(d[41]), "+f"(d[42]), "+f"(d[43]), "+f"(d[44]), "+f"(d[45]), "+f"(d[46]), "+f"(d[47]),
      "+f"(d[48]), "+f"(d[49]), "+f"(d[50]), "+f"(d[51]), "+f"(d[52]), "+f"(d[53]), "+f"(d[54]), "+f"(d[55]),
      "+f"(d[56]), "+f"(d[57]), "+f"(d[58]), "+f"(d[59]), "+f"(d[60]), "+f"(d[61]), "+f"(d[62]), "+f"(d[63]),
      "+f"(d[64]), "+f"(d[65]), "+f"(d[66]), "+f"(d[67]), "+f"(d[68]), "+f"(d[69]), "+f"(d[70]), "+f"(d[71]),
      "+f"(d[72]), "+f"(d[73]), "+f"(d[74]), "+f"(d[75]), "+f"(d[76]), "+f"(d[77]), "+f"(d[78]), "+f"(d[79]),
      "+f"(d[80]), "+f"(d[81]), "+f"(d[82]), "+f"(d[83]), "+f"(d[84]), "+f"(d[85]), "+f"(d[86]), "+f"(d[87]),
      "+f"(d[88]), "+f"(d[89]), "+f"(d[90]), "+f"(d[91]), "+f"(d[92]), "+f"(d[93]), "+f"(d[94]), "+f"(d[95])
    : "l"(da), "l"(db), "r"(sd));
}

__device__ __forceinline__ void wgmma_ss_n72_t10(float* d, uint64_t da, uint64_t db, int sd) {
  asm volatile("{ .reg .pred p; setp.ne.b32 p, %38, 0;\n"
      "wgmma.mma_async.sync.aligned.m64n72k16.f32.bf16.bf16 {"
      "%0,%1,%2,%3,%4,%5,%6,%7,%8,%9,%10,%11,%12,%13,%14,%15,"
      "%16,%17,%18,%19,%20,%21,%22,%23,%24,%25,%26,%27,%28,%29,%30,%31,"
      "%32,%33,%34,%35"
      "}, %36, %37, p, 1, 1, 1, 0; }"
    : "+f"(d[0]), "+f"(d[1]), "+f"(d[2]), "+f"(d[3]), "+f"(d[4]), "+f"(d[5]), "+f"(d[6]), "+f"(d[7]),
      "+f"(d[8]), "+f"(d[9]), "+f"(d[10]), "+f"(d[11]), "+f"(d[12]), "+f"(d[13]), "+f"(d[14]), "+f"(d[15]),
      "+f"(d[16]), "+f"(d[17]), "+f"(d[18]), "+f"(d[19]), "+f"(d[20]), "+f"(d[21]), "+f"(d[22]), "+f"(d[23]),
      "+f"(d[24]), "+f"(d[25]), "+f"(d[26]), "+f"(d[27]), "+f"(d[28]), "+f"(d[29]), "+f"(d[30]), "+f"(d[31]),
      "+f"(d[32]), "+f"(d[33]), "+f"(d[34]), "+f"(d[35])
    : "l"(da), "l"(db), "r"(sd));
}

__device__ __forceinline__ void wgmma_rs_n16(float* d, const uint32_t* a, uint64_t db, int sd) {
  asm volatile("{ .reg .pred p; setp.ne.b32 p, %13, 0;\n"
      "wgmma.mma_async.sync.aligned.m64n16k16.f32.bf16.bf16 {"
      "%0,%1,%2,%3,%4,%5,%6,%7"
      "}, {%8,%9,%10,%11}, %12, p, 1, 1, 0; }"
    : "+f"(d[0]), "+f"(d[1]), "+f"(d[2]), "+f"(d[3]), "+f"(d[4]), "+f"(d[5]), "+f"(d[6]), "+f"(d[7])
    : "r"(a[0]), "r"(a[1]), "r"(a[2]), "r"(a[3]), "l"(db), "r"(sd));
}

__device__ __forceinline__ void wgmma_rs_n32(float* d, const uint32_t* a, uint64_t db, int sd) {
  asm volatile("{ .reg .pred p; setp.ne.b32 p, %21, 0;\n"
      "wgmma.mma_async.sync.aligned.m64n32k16.f32.bf16.bf16 {"
      "%0,%1,%2,%3,%4,%5,%6,%7,%8,%9,%10,%11,%12,%13,%14,%15"
      "}, {%16,%17,%18,%19}, %20, p, 1, 1, 0; }"
    : "+f"(d[0]), "+f"(d[1]), "+f"(d[2]), "+f"(d[3]), "+f"(d[4]), "+f"(d[5]), "+f"(d[6]), "+f"(d[7]),
      "+f"(d[8]), "+f"(d[9]), "+f"(d[10]), "+f"(d[11]), "+f"(d[12]), "+f"(d[13]), "+f"(d[14]), "+f"(d[15])
    : "r"(a[0]), "r"(a[1]), "r"(a[2]), "r"(a[3]), "l"(db), "r"(sd));
}

__device__ __forceinline__ void wgmma_rs_n48(float* d, const uint32_t* a, uint64_t db, int sd) {
  asm volatile("{ .reg .pred p; setp.ne.b32 p, %29, 0;\n"
      "wgmma.mma_async.sync.aligned.m64n48k16.f32.bf16.bf16 {"
      "%0,%1,%2,%3,%4,%5,%6,%7,%8,%9,%10,%11,%12,%13,%14,%15,"
      "%16,%17,%18,%19,%20,%21,%22,%23"
      "}, {%24,%25,%26,%27}, %28, p, 1, 1, 0; }"
    : "+f"(d[0]), "+f"(d[1]), "+f"(d[2]), "+f"(d[3]), "+f"(d[4]), "+f"(d[5]), "+f"(d[6]), "+f"(d[7]),
      "+f"(d[8]), "+f"(d[9]), "+f"(d[10]), "+f"(d[11]), "+f"(d[12]), "+f"(d[13]), "+f"(d[14]), "+f"(d[15]),
      "+f"(d[16]), "+f"(d[17]), "+f"(d[18]), "+f"(d[19]), "+f"(d[20]), "+f"(d[21]), "+f"(d[22]), "+f"(d[23])
    : "r"(a[0]), "r"(a[1]), "r"(a[2]), "r"(a[3]), "l"(db), "r"(sd));
}

__device__ __forceinline__ void wgmma_rs_n64(float* d, const uint32_t* a, uint64_t db, int sd) {
  asm volatile("{ .reg .pred p; setp.ne.b32 p, %37, 0;\n"
      "wgmma.mma_async.sync.aligned.m64n64k16.f32.bf16.bf16 {"
      "%0,%1,%2,%3,%4,%5,%6,%7,%8,%9,%10,%11,%12,%13,%14,%15,"
      "%16,%17,%18,%19,%20,%21,%22,%23,%24,%25,%26,%27,%28,%29,%30,%31"
      "}, {%32,%33,%34,%35}, %36, p, 1, 1, 0; }"
    : "+f"(d[0]), "+f"(d[1]), "+f"(d[2]), "+f"(d[3]), "+f"(d[4]), "+f"(d[5]), "+f"(d[6]), "+f"(d[7]),
      "+f"(d[8]), "+f"(d[9]), "+f"(d[10]), "+f"(d[11]), "+f"(d[12]), "+f"(d[13]), "+f"(d[14]), "+f"(d[15]),
      "+f"(d[16]), "+f"(d[17]), "+f"(d[18]), "+f"(d[19]), "+f"(d[20]), "+f"(d[21]), "+f"(d[22]), "+f"(d[23]),
      "+f"(d[24]), "+f"(d[25]), "+f"(d[26]), "+f"(d[27]), "+f"(d[28]), "+f"(d[29]), "+f"(d[30]), "+f"(d[31])
    : "r"(a[0]), "r"(a[1]), "r"(a[2]), "r"(a[3]), "l"(db), "r"(sd));
}

__device__ __forceinline__ void wgmma_rs_n80(float* d, const uint32_t* a, uint64_t db, int sd) {
  asm volatile("{ .reg .pred p; setp.ne.b32 p, %45, 0;\n"
      "wgmma.mma_async.sync.aligned.m64n80k16.f32.bf16.bf16 {"
      "%0,%1,%2,%3,%4,%5,%6,%7,%8,%9,%10,%11,%12,%13,%14,%15,"
      "%16,%17,%18,%19,%20,%21,%22,%23,%24,%25,%26,%27,%28,%29,%30,%31,"
      "%32,%33,%34,%35,%36,%37,%38,%39"
      "}, {%40,%41,%42,%43}, %44, p, 1, 1, 0; }"
    : "+f"(d[0]), "+f"(d[1]), "+f"(d[2]), "+f"(d[3]), "+f"(d[4]), "+f"(d[5]), "+f"(d[6]), "+f"(d[7]),
      "+f"(d[8]), "+f"(d[9]), "+f"(d[10]), "+f"(d[11]), "+f"(d[12]), "+f"(d[13]), "+f"(d[14]), "+f"(d[15]),
      "+f"(d[16]), "+f"(d[17]), "+f"(d[18]), "+f"(d[19]), "+f"(d[20]), "+f"(d[21]), "+f"(d[22]), "+f"(d[23]),
      "+f"(d[24]), "+f"(d[25]), "+f"(d[26]), "+f"(d[27]), "+f"(d[28]), "+f"(d[29]), "+f"(d[30]), "+f"(d[31]),
      "+f"(d[32]), "+f"(d[33]), "+f"(d[34]), "+f"(d[35]), "+f"(d[36]), "+f"(d[37]), "+f"(d[38]), "+f"(d[39])
    : "r"(a[0]), "r"(a[1]), "r"(a[2]), "r"(a[3]), "l"(db), "r"(sd));
}

__device__ __forceinline__ void wgmma_rs_n96(float* d, const uint32_t* a, uint64_t db, int sd) {
  asm volatile("{ .reg .pred p; setp.ne.b32 p, %53, 0;\n"
      "wgmma.mma_async.sync.aligned.m64n96k16.f32.bf16.bf16 {"
      "%0,%1,%2,%3,%4,%5,%6,%7,%8,%9,%10,%11,%12,%13,%14,%15,"
      "%16,%17,%18,%19,%20,%21,%22,%23,%24,%25,%26,%27,%28,%29,%30,%31,"
      "%32,%33,%34,%35,%36,%37,%38,%39,%40,%41,%42,%43,%44,%45,%46,%47"
      "}, {%48,%49,%50,%51}, %52, p, 1, 1, 0; }"
    : "+f"(d[0]), "+f"(d[1]), "+f"(d[2]), "+f"(d[3]), "+f"(d[4]), "+f"(d[5]), "+f"(d[6]), "+f"(d[7]),
      "+f"(d[8]), "+f"(d[9]), "+f"(d[10]), "+f"(d[11]), "+f"(d[12]), "+f"(d[13]), "+f"(d[14]), "+f"(d[15]),
      "+f"(d[16]), "+f"(d[17]), "+f"(d[18]), "+f"(d[19]), "+f"(d[20]), "+f"(d[21]), "+f"(d[22]), "+f"(d[23]),
      "+f"(d[24]), "+f"(d[25]), "+f"(d[26]), "+f"(d[27]), "+f"(d[28]), "+f"(d[29]), "+f"(d[30]), "+f"(d[31]),
      "+f"(d[32]), "+f"(d[33]), "+f"(d[34]), "+f"(d[35]), "+f"(d[36]), "+f"(d[37]), "+f"(d[38]), "+f"(d[39]),
      "+f"(d[40]), "+f"(d[41]), "+f"(d[42]), "+f"(d[43]), "+f"(d[44]), "+f"(d[45]), "+f"(d[46]), "+f"(d[47])
    : "r"(a[0]), "r"(a[1]), "r"(a[2]), "r"(a[3]), "l"(db), "r"(sd));
}

__device__ __forceinline__ void wgmma_rs_n112(float* d, const uint32_t* a, uint64_t db, int sd) {
  asm volatile("{ .reg .pred p; setp.ne.b32 p, %61, 0;\n"
      "wgmma.mma_async.sync.aligned.m64n112k16.f32.bf16.bf16 {"
      "%0,%1,%2,%3,%4,%5,%6,%7,%8,%9,%10,%11,%12,%13,%14,%15,"
      "%16,%17,%18,%19,%20,%21,%22,%23,%24,%25,%26,%27,%28,%29,%30,%31,"
      "%32,%33,%34,%35,%36,%37,%38,%39,%40,%41,%42,%43,%44,%45,%46,%47,"
      "%48,%49,%50,%51,%52,%53,%54,%55"
      "}, {%56,%57,%58,%59}, %60, p, 1, 1, 0; }"
    : "+f"(d[0]), "+f"(d[1]), "+f"(d[2]), "+f"(d[3]), "+f"(d[4]), "+f"(d[5]), "+f"(d[6]), "+f"(d[7]),
      "+f"(d[8]), "+f"(d[9]), "+f"(d[10]), "+f"(d[11]), "+f"(d[12]), "+f"(d[13]), "+f"(d[14]), "+f"(d[15]),
      "+f"(d[16]), "+f"(d[17]), "+f"(d[18]), "+f"(d[19]), "+f"(d[20]), "+f"(d[21]), "+f"(d[22]), "+f"(d[23]),
      "+f"(d[24]), "+f"(d[25]), "+f"(d[26]), "+f"(d[27]), "+f"(d[28]), "+f"(d[29]), "+f"(d[30]), "+f"(d[31]),
      "+f"(d[32]), "+f"(d[33]), "+f"(d[34]), "+f"(d[35]), "+f"(d[36]), "+f"(d[37]), "+f"(d[38]), "+f"(d[39]),
      "+f"(d[40]), "+f"(d[41]), "+f"(d[42]), "+f"(d[43]), "+f"(d[44]), "+f"(d[45]), "+f"(d[46]), "+f"(d[47]),
      "+f"(d[48]), "+f"(d[49]), "+f"(d[50]), "+f"(d[51]), "+f"(d[52]), "+f"(d[53]), "+f"(d[54]), "+f"(d[55])
    : "r"(a[0]), "r"(a[1]), "r"(a[2]), "r"(a[3]), "l"(db), "r"(sd));
}

__device__ __forceinline__ void wgmma_rs_n128(float* d, const uint32_t* a, uint64_t db, int sd) {
  asm volatile("{ .reg .pred p; setp.ne.b32 p, %69, 0;\n"
      "wgmma.mma_async.sync.aligned.m64n128k16.f32.bf16.bf16 {"
      "%0,%1,%2,%3,%4,%5,%6,%7,%8,%9,%10,%11,%12,%13,%14,%15,"
      "%16,%17,%18,%19,%20,%21,%22,%23,%24,%25,%26,%27,%28,%29,%30,%31,"
      "%32,%33,%34,%35,%36,%37,%38,%39,%40,%41,%42,%43,%44,%45,%46,%47,"
      "%48,%49,%50,%51,%52,%53,%54,%55,%56,%57,%58,%59,%60,%61,%62,%63"
      "}, {%64,%65,%66,%67}, %68, p, 1, 1, 0; }"
    : "+f"(d[0]), "+f"(d[1]), "+f"(d[2]), "+f"(d[3]), "+f"(d[4]), "+f"(d[5]), "+f"(d[6]), "+f"(d[7]),
      "+f"(d[8]), "+f"(d[9]), "+f"(d[10]), "+f"(d[11]), "+f"(d[12]), "+f"(d[13]), "+f"(d[14]), "+f"(d[15]),
      "+f"(d[16]), "+f"(d[17]), "+f"(d[18]), "+f"(d[19]), "+f"(d[20]), "+f"(d[21]), "+f"(d[22]), "+f"(d[23]),
      "+f"(d[24]), "+f"(d[25]), "+f"(d[26]), "+f"(d[27]), "+f"(d[28]), "+f"(d[29]), "+f"(d[30]), "+f"(d[31]),
      "+f"(d[32]), "+f"(d[33]), "+f"(d[34]), "+f"(d[35]), "+f"(d[36]), "+f"(d[37]), "+f"(d[38]), "+f"(d[39]),
      "+f"(d[40]), "+f"(d[41]), "+f"(d[42]), "+f"(d[43]), "+f"(d[44]), "+f"(d[45]), "+f"(d[46]), "+f"(d[47]),
      "+f"(d[48]), "+f"(d[49]), "+f"(d[50]), "+f"(d[51]), "+f"(d[52]), "+f"(d[53]), "+f"(d[54]), "+f"(d[55]),
      "+f"(d[56]), "+f"(d[57]), "+f"(d[58]), "+f"(d[59]), "+f"(d[60]), "+f"(d[61]), "+f"(d[62]), "+f"(d[63])
    : "r"(a[0]), "r"(a[1]), "r"(a[2]), "r"(a[3]), "l"(db), "r"(sd));
}

__device__ __forceinline__ void wgmma_rs_n144(float* d, const uint32_t* a, uint64_t db, int sd) {
  asm volatile("{ .reg .pred p; setp.ne.b32 p, %77, 0;\n"
      "wgmma.mma_async.sync.aligned.m64n144k16.f32.bf16.bf16 {"
      "%0,%1,%2,%3,%4,%5,%6,%7,%8,%9,%10,%11,%12,%13,%14,%15,"
      "%16,%17,%18,%19,%20,%21,%22,%23,%24,%25,%26,%27,%28,%29,%30,%31,"
      "%32,%33,%34,%35,%36,%37,%38,%39,%40,%41,%42,%43,%44,%45,%46,%47,"
      "%48,%49,%50,%51,%52,%53,%54,%55,%56,%57,%58,%59,%60,%61,%62,%63,"
      "%64,%65,%66,%67,%68,%69,%70,%71"
      "}, {%72,%73,%74,%75}, %76, p, 1, 1, 0; }"
    : "+f"(d[0]), "+f"(d[1]), "+f"(d[2]), "+f"(d[3]), "+f"(d[4]), "+f"(d[5]), "+f"(d[6]), "+f"(d[7]),
      "+f"(d[8]), "+f"(d[9]), "+f"(d[10]), "+f"(d[11]), "+f"(d[12]), "+f"(d[13]), "+f"(d[14]), "+f"(d[15]),
      "+f"(d[16]), "+f"(d[17]), "+f"(d[18]), "+f"(d[19]), "+f"(d[20]), "+f"(d[21]), "+f"(d[22]), "+f"(d[23]),
      "+f"(d[24]), "+f"(d[25]), "+f"(d[26]), "+f"(d[27]), "+f"(d[28]), "+f"(d[29]), "+f"(d[30]), "+f"(d[31]),
      "+f"(d[32]), "+f"(d[33]), "+f"(d[34]), "+f"(d[35]), "+f"(d[36]), "+f"(d[37]), "+f"(d[38]), "+f"(d[39]),
      "+f"(d[40]), "+f"(d[41]), "+f"(d[42]), "+f"(d[43]), "+f"(d[44]), "+f"(d[45]), "+f"(d[46]), "+f"(d[47]),
      "+f"(d[48]), "+f"(d[49]), "+f"(d[50]), "+f"(d[51]), "+f"(d[52]), "+f"(d[53]), "+f"(d[54]), "+f"(d[55]),
      "+f"(d[56]), "+f"(d[57]), "+f"(d[58]), "+f"(d[59]), "+f"(d[60]), "+f"(d[61]), "+f"(d[62]), "+f"(d[63]),
      "+f"(d[64]), "+f"(d[65]), "+f"(d[66]), "+f"(d[67]), "+f"(d[68]), "+f"(d[69]), "+f"(d[70]), "+f"(d[71])
    : "r"(a[0]), "r"(a[1]), "r"(a[2]), "r"(a[3]), "l"(db), "r"(sd));
}

__device__ __forceinline__ void wgmma_rs_n160(float* d, const uint32_t* a, uint64_t db, int sd) {
  asm volatile("{ .reg .pred p; setp.ne.b32 p, %85, 0;\n"
      "wgmma.mma_async.sync.aligned.m64n160k16.f32.bf16.bf16 {"
      "%0,%1,%2,%3,%4,%5,%6,%7,%8,%9,%10,%11,%12,%13,%14,%15,"
      "%16,%17,%18,%19,%20,%21,%22,%23,%24,%25,%26,%27,%28,%29,%30,%31,"
      "%32,%33,%34,%35,%36,%37,%38,%39,%40,%41,%42,%43,%44,%45,%46,%47,"
      "%48,%49,%50,%51,%52,%53,%54,%55,%56,%57,%58,%59,%60,%61,%62,%63,"
      "%64,%65,%66,%67,%68,%69,%70,%71,%72,%73,%74,%75,%76,%77,%78,%79"
      "}, {%80,%81,%82,%83}, %84, p, 1, 1, 0; }"
    : "+f"(d[0]), "+f"(d[1]), "+f"(d[2]), "+f"(d[3]), "+f"(d[4]), "+f"(d[5]), "+f"(d[6]), "+f"(d[7]),
      "+f"(d[8]), "+f"(d[9]), "+f"(d[10]), "+f"(d[11]), "+f"(d[12]), "+f"(d[13]), "+f"(d[14]), "+f"(d[15]),
      "+f"(d[16]), "+f"(d[17]), "+f"(d[18]), "+f"(d[19]), "+f"(d[20]), "+f"(d[21]), "+f"(d[22]), "+f"(d[23]),
      "+f"(d[24]), "+f"(d[25]), "+f"(d[26]), "+f"(d[27]), "+f"(d[28]), "+f"(d[29]), "+f"(d[30]), "+f"(d[31]),
      "+f"(d[32]), "+f"(d[33]), "+f"(d[34]), "+f"(d[35]), "+f"(d[36]), "+f"(d[37]), "+f"(d[38]), "+f"(d[39]),
      "+f"(d[40]), "+f"(d[41]), "+f"(d[42]), "+f"(d[43]), "+f"(d[44]), "+f"(d[45]), "+f"(d[46]), "+f"(d[47]),
      "+f"(d[48]), "+f"(d[49]), "+f"(d[50]), "+f"(d[51]), "+f"(d[52]), "+f"(d[53]), "+f"(d[54]), "+f"(d[55]),
      "+f"(d[56]), "+f"(d[57]), "+f"(d[58]), "+f"(d[59]), "+f"(d[60]), "+f"(d[61]), "+f"(d[62]), "+f"(d[63]),
      "+f"(d[64]), "+f"(d[65]), "+f"(d[66]), "+f"(d[67]), "+f"(d[68]), "+f"(d[69]), "+f"(d[70]), "+f"(d[71]),
      "+f"(d[72]), "+f"(d[73]), "+f"(d[74]), "+f"(d[75]), "+f"(d[76]), "+f"(d[77]), "+f"(d[78]), "+f"(d[79])
    : "r"(a[0]), "r"(a[1]), "r"(a[2]), "r"(a[3]), "l"(db), "r"(sd));
}

__device__ __forceinline__ void wgmma_rs_n176(float* d, const uint32_t* a, uint64_t db, int sd) {
  asm volatile("{ .reg .pred p; setp.ne.b32 p, %93, 0;\n"
      "wgmma.mma_async.sync.aligned.m64n176k16.f32.bf16.bf16 {"
      "%0,%1,%2,%3,%4,%5,%6,%7,%8,%9,%10,%11,%12,%13,%14,%15,"
      "%16,%17,%18,%19,%20,%21,%22,%23,%24,%25,%26,%27,%28,%29,%30,%31,"
      "%32,%33,%34,%35,%36,%37,%38,%39,%40,%41,%42,%43,%44,%45,%46,%47,"
      "%48,%49,%50,%51,%52,%53,%54,%55,%56,%57,%58,%59,%60,%61,%62,%63,"
      "%64,%65,%66,%67,%68,%69,%70,%71,%72,%73,%74,%75,%76,%77,%78,%79,"
      "%80,%81,%82,%83,%84,%85,%86,%87"
      "}, {%88,%89,%90,%91}, %92, p, 1, 1, 0; }"
    : "+f"(d[0]), "+f"(d[1]), "+f"(d[2]), "+f"(d[3]), "+f"(d[4]), "+f"(d[5]), "+f"(d[6]), "+f"(d[7]),
      "+f"(d[8]), "+f"(d[9]), "+f"(d[10]), "+f"(d[11]), "+f"(d[12]), "+f"(d[13]), "+f"(d[14]), "+f"(d[15]),
      "+f"(d[16]), "+f"(d[17]), "+f"(d[18]), "+f"(d[19]), "+f"(d[20]), "+f"(d[21]), "+f"(d[22]), "+f"(d[23]),
      "+f"(d[24]), "+f"(d[25]), "+f"(d[26]), "+f"(d[27]), "+f"(d[28]), "+f"(d[29]), "+f"(d[30]), "+f"(d[31]),
      "+f"(d[32]), "+f"(d[33]), "+f"(d[34]), "+f"(d[35]), "+f"(d[36]), "+f"(d[37]), "+f"(d[38]), "+f"(d[39]),
      "+f"(d[40]), "+f"(d[41]), "+f"(d[42]), "+f"(d[43]), "+f"(d[44]), "+f"(d[45]), "+f"(d[46]), "+f"(d[47]),
      "+f"(d[48]), "+f"(d[49]), "+f"(d[50]), "+f"(d[51]), "+f"(d[52]), "+f"(d[53]), "+f"(d[54]), "+f"(d[55]),
      "+f"(d[56]), "+f"(d[57]), "+f"(d[58]), "+f"(d[59]), "+f"(d[60]), "+f"(d[61]), "+f"(d[62]), "+f"(d[63]),
      "+f"(d[64]), "+f"(d[65]), "+f"(d[66]), "+f"(d[67]), "+f"(d[68]), "+f"(d[69]), "+f"(d[70]), "+f"(d[71]),
      "+f"(d[72]), "+f"(d[73]), "+f"(d[74]), "+f"(d[75]), "+f"(d[76]), "+f"(d[77]), "+f"(d[78]), "+f"(d[79]),
      "+f"(d[80]), "+f"(d[81]), "+f"(d[82]), "+f"(d[83]), "+f"(d[84]), "+f"(d[85]), "+f"(d[86]), "+f"(d[87])
    : "r"(a[0]), "r"(a[1]), "r"(a[2]), "r"(a[3]), "l"(db), "r"(sd));
}

__device__ __forceinline__ void wgmma_rs_n192(float* d, const uint32_t* a, uint64_t db, int sd) {
  asm volatile("{ .reg .pred p; setp.ne.b32 p, %101, 0;\n"
      "wgmma.mma_async.sync.aligned.m64n192k16.f32.bf16.bf16 {"
      "%0,%1,%2,%3,%4,%5,%6,%7,%8,%9,%10,%11,%12,%13,%14,%15,"
      "%16,%17,%18,%19,%20,%21,%22,%23,%24,%25,%26,%27,%28,%29,%30,%31,"
      "%32,%33,%34,%35,%36,%37,%38,%39,%40,%41,%42,%43,%44,%45,%46,%47,"
      "%48,%49,%50,%51,%52,%53,%54,%55,%56,%57,%58,%59,%60,%61,%62,%63,"
      "%64,%65,%66,%67,%68,%69,%70,%71,%72,%73,%74,%75,%76,%77,%78,%79,"
      "%80,%81,%82,%83,%84,%85,%86,%87,%88,%89,%90,%91,%92,%93,%94,%95"
      "}, {%96,%97,%98,%99}, %100, p, 1, 1, 0; }"
    : "+f"(d[0]), "+f"(d[1]), "+f"(d[2]), "+f"(d[3]), "+f"(d[4]), "+f"(d[5]), "+f"(d[6]), "+f"(d[7]),
      "+f"(d[8]), "+f"(d[9]), "+f"(d[10]), "+f"(d[11]), "+f"(d[12]), "+f"(d[13]), "+f"(d[14]), "+f"(d[15]),
      "+f"(d[16]), "+f"(d[17]), "+f"(d[18]), "+f"(d[19]), "+f"(d[20]), "+f"(d[21]), "+f"(d[22]), "+f"(d[23]),
      "+f"(d[24]), "+f"(d[25]), "+f"(d[26]), "+f"(d[27]), "+f"(d[28]), "+f"(d[29]), "+f"(d[30]), "+f"(d[31]),
      "+f"(d[32]), "+f"(d[33]), "+f"(d[34]), "+f"(d[35]), "+f"(d[36]), "+f"(d[37]), "+f"(d[38]), "+f"(d[39]),
      "+f"(d[40]), "+f"(d[41]), "+f"(d[42]), "+f"(d[43]), "+f"(d[44]), "+f"(d[45]), "+f"(d[46]), "+f"(d[47]),
      "+f"(d[48]), "+f"(d[49]), "+f"(d[50]), "+f"(d[51]), "+f"(d[52]), "+f"(d[53]), "+f"(d[54]), "+f"(d[55]),
      "+f"(d[56]), "+f"(d[57]), "+f"(d[58]), "+f"(d[59]), "+f"(d[60]), "+f"(d[61]), "+f"(d[62]), "+f"(d[63]),
      "+f"(d[64]), "+f"(d[65]), "+f"(d[66]), "+f"(d[67]), "+f"(d[68]), "+f"(d[69]), "+f"(d[70]), "+f"(d[71]),
      "+f"(d[72]), "+f"(d[73]), "+f"(d[74]), "+f"(d[75]), "+f"(d[76]), "+f"(d[77]), "+f"(d[78]), "+f"(d[79]),
      "+f"(d[80]), "+f"(d[81]), "+f"(d[82]), "+f"(d[83]), "+f"(d[84]), "+f"(d[85]), "+f"(d[86]), "+f"(d[87]),
      "+f"(d[88]), "+f"(d[89]), "+f"(d[90]), "+f"(d[91]), "+f"(d[92]), "+f"(d[93]), "+f"(d[94]), "+f"(d[95])
    : "r"(a[0]), "r"(a[1]), "r"(a[2]), "r"(a[3]), "l"(db), "r"(sd));
}

__device__ __forceinline__ void wgmma_rs_n208(float* d, const uint32_t* a, uint64_t db, int sd) {
  asm volatile("{ .reg .pred p; setp.ne.b32 p, %109, 0;\n"
      "wgmma.mma_async.sync.aligned.m64n208k16.f32.bf16.bf16 {"
      "%0,%1,%2,%3,%4,%5,%6,%7,%8,%9,%10,%11,%12,%13,%14,%15,"
      "%16,%17,%18,%19,%20,%21,%22,%23,%24,%25,%26,%27,%28,%29,%30,%31,"
      "%32,%33,%34,%35,%36,%37,%38,%39,%40,%41,%42,%43,%44,%45,%46,%47,"
      "%48,%49,%50,%51,%52,%53,%54,%55,%56,%57,%58,%59,%60,%61,%62,%63,"
      "%64,%65,%66,%67,%68,%69,%70,%71,%72,%73,%74,%75,%76,%77,%78,%79,"
      "%80,%81,%82,%83,%84,%85,%86,%87,%88,%89,%90,%91,%92,%93,%94,%95,"
      "%96,%97,%98,%99,%100,%101,%102,%103"
      "}, {%104,%105,%106,%107}, %108, p, 1, 1, 0; }"
    : "+f"(d[0]), "+f"(d[1]), "+f"(d[2]), "+f"(d[3]), "+f"(d[4]), "+f"(d[5]), "+f"(d[6]), "+f"(d[7]),
      "+f"(d[8]), "+f"(d[9]), "+f"(d[10]), "+f"(d[11]), "+f"(d[12]), "+f"(d[13]), "+f"(d[14]), "+f"(d[15]),
      "+f"(d[16]), "+f"(d[17]), "+f"(d[18]), "+f"(d[19]), "+f"(d[20]), "+f"(d[21]), "+f"(d[22]), "+f"(d[23]),
      "+f"(d[24]), "+f"(d[25]), "+f"(d[26]), "+f"(d[27]), "+f"(d[28]), "+f"(d[29]), "+f"(d[30]), "+f"(d[31]),
      "+f"(d[32]), "+f"(d[33]), "+f"(d[34]), "+f"(d[35]), "+f"(d[36]), "+f"(d[37]), "+f"(d[38]), "+f"(d[39]),
      "+f"(d[40]), "+f"(d[41]), "+f"(d[42]), "+f"(d[43]), "+f"(d[44]), "+f"(d[45]), "+f"(d[46]), "+f"(d[47]),
      "+f"(d[48]), "+f"(d[49]), "+f"(d[50]), "+f"(d[51]), "+f"(d[52]), "+f"(d[53]), "+f"(d[54]), "+f"(d[55]),
      "+f"(d[56]), "+f"(d[57]), "+f"(d[58]), "+f"(d[59]), "+f"(d[60]), "+f"(d[61]), "+f"(d[62]), "+f"(d[63]),
      "+f"(d[64]), "+f"(d[65]), "+f"(d[66]), "+f"(d[67]), "+f"(d[68]), "+f"(d[69]), "+f"(d[70]), "+f"(d[71]),
      "+f"(d[72]), "+f"(d[73]), "+f"(d[74]), "+f"(d[75]), "+f"(d[76]), "+f"(d[77]), "+f"(d[78]), "+f"(d[79]),
      "+f"(d[80]), "+f"(d[81]), "+f"(d[82]), "+f"(d[83]), "+f"(d[84]), "+f"(d[85]), "+f"(d[86]), "+f"(d[87]),
      "+f"(d[88]), "+f"(d[89]), "+f"(d[90]), "+f"(d[91]), "+f"(d[92]), "+f"(d[93]), "+f"(d[94]), "+f"(d[95]),
      "+f"(d[96]), "+f"(d[97]), "+f"(d[98]), "+f"(d[99]), "+f"(d[100]), "+f"(d[101]), "+f"(d[102]), "+f"(d[103])
    : "r"(a[0]), "r"(a[1]), "r"(a[2]), "r"(a[3]), "l"(db), "r"(sd));
}

__device__ __forceinline__ void wgmma_rs_n224(float* d, const uint32_t* a, uint64_t db, int sd) {
  asm volatile("{ .reg .pred p; setp.ne.b32 p, %117, 0;\n"
      "wgmma.mma_async.sync.aligned.m64n224k16.f32.bf16.bf16 {"
      "%0,%1,%2,%3,%4,%5,%6,%7,%8,%9,%10,%11,%12,%13,%14,%15,"
      "%16,%17,%18,%19,%20,%21,%22,%23,%24,%25,%26,%27,%28,%29,%30,%31,"
      "%32,%33,%34,%35,%36,%37,%38,%39,%40,%41,%42,%43,%44,%45,%46,%47,"
      "%48,%49,%50,%51,%52,%53,%54,%55,%56,%57,%58,%59,%60,%61,%62,%63,"
      "%64,%65,%66,%67,%68,%69,%70,%71,%72,%73,%74,%75,%76,%77,%78,%79,"
      "%80,%81,%82,%83,%84,%85,%86,%87,%88,%89,%90,%91,%92,%93,%94,%95,"
      "%96,%97,%98,%99,%100,%101,%102,%103,%104,%105,%106,%107,%108,%109,%110,%111"
      "}, {%112,%113,%114,%115}, %116, p, 1, 1, 0; }"
    : "+f"(d[0]), "+f"(d[1]), "+f"(d[2]), "+f"(d[3]), "+f"(d[4]), "+f"(d[5]), "+f"(d[6]), "+f"(d[7]),
      "+f"(d[8]), "+f"(d[9]), "+f"(d[10]), "+f"(d[11]), "+f"(d[12]), "+f"(d[13]), "+f"(d[14]), "+f"(d[15]),
      "+f"(d[16]), "+f"(d[17]), "+f"(d[18]), "+f"(d[19]), "+f"(d[20]), "+f"(d[21]), "+f"(d[22]), "+f"(d[23]),
      "+f"(d[24]), "+f"(d[25]), "+f"(d[26]), "+f"(d[27]), "+f"(d[28]), "+f"(d[29]), "+f"(d[30]), "+f"(d[31]),
      "+f"(d[32]), "+f"(d[33]), "+f"(d[34]), "+f"(d[35]), "+f"(d[36]), "+f"(d[37]), "+f"(d[38]), "+f"(d[39]),
      "+f"(d[40]), "+f"(d[41]), "+f"(d[42]), "+f"(d[43]), "+f"(d[44]), "+f"(d[45]), "+f"(d[46]), "+f"(d[47]),
      "+f"(d[48]), "+f"(d[49]), "+f"(d[50]), "+f"(d[51]), "+f"(d[52]), "+f"(d[53]), "+f"(d[54]), "+f"(d[55]),
      "+f"(d[56]), "+f"(d[57]), "+f"(d[58]), "+f"(d[59]), "+f"(d[60]), "+f"(d[61]), "+f"(d[62]), "+f"(d[63]),
      "+f"(d[64]), "+f"(d[65]), "+f"(d[66]), "+f"(d[67]), "+f"(d[68]), "+f"(d[69]), "+f"(d[70]), "+f"(d[71]),
      "+f"(d[72]), "+f"(d[73]), "+f"(d[74]), "+f"(d[75]), "+f"(d[76]), "+f"(d[77]), "+f"(d[78]), "+f"(d[79]),
      "+f"(d[80]), "+f"(d[81]), "+f"(d[82]), "+f"(d[83]), "+f"(d[84]), "+f"(d[85]), "+f"(d[86]), "+f"(d[87]),
      "+f"(d[88]), "+f"(d[89]), "+f"(d[90]), "+f"(d[91]), "+f"(d[92]), "+f"(d[93]), "+f"(d[94]), "+f"(d[95]),
      "+f"(d[96]), "+f"(d[97]), "+f"(d[98]), "+f"(d[99]), "+f"(d[100]), "+f"(d[101]), "+f"(d[102]), "+f"(d[103]),
      "+f"(d[104]), "+f"(d[105]), "+f"(d[106]), "+f"(d[107]), "+f"(d[108]), "+f"(d[109]), "+f"(d[110]), "+f"(d[111])
    : "r"(a[0]), "r"(a[1]), "r"(a[2]), "r"(a[3]), "l"(db), "r"(sd));
}

__device__ __forceinline__ void wgmma_rs_n240(float* d, const uint32_t* a, uint64_t db, int sd) {
  asm volatile("{ .reg .pred p; setp.ne.b32 p, %125, 0;\n"
      "wgmma.mma_async.sync.aligned.m64n240k16.f32.bf16.bf16 {"
      "%0,%1,%2,%3,%4,%5,%6,%7,%8,%9,%10,%11,%12,%13,%14,%15,"
      "%16,%17,%18,%19,%20,%21,%22,%23,%24,%25,%26,%27,%28,%29,%30,%31,"
      "%32,%33,%34,%35,%36,%37,%38,%39,%40,%41,%42,%43,%44,%45,%46,%47,"
      "%48,%49,%50,%51,%52,%53,%54,%55,%56,%57,%58,%59,%60,%61,%62,%63,"
      "%64,%65,%66,%67,%68,%69,%70,%71,%72,%73,%74,%75,%76,%77,%78,%79,"
      "%80,%81,%82,%83,%84,%85,%86,%87,%88,%89,%90,%91,%92,%93,%94,%95,"
      "%96,%97,%98,%99,%100,%101,%102,%103,%104,%105,%106,%107,%108,%109,%110,%111,"
      "%112,%113,%114,%115,%116,%117,%118,%119"
      "}, {%120,%121,%122,%123}, %124, p, 1, 1, 0; }"
    : "+f"(d[0]), "+f"(d[1]), "+f"(d[2]), "+f"(d[3]), "+f"(d[4]), "+f"(d[5]), "+f"(d[6]), "+f"(d[7]),
      "+f"(d[8]), "+f"(d[9]), "+f"(d[10]), "+f"(d[11]), "+f"(d[12]), "+f"(d[13]), "+f"(d[14]), "+f"(d[15]),
      "+f"(d[16]), "+f"(d[17]), "+f"(d[18]), "+f"(d[19]), "+f"(d[20]), "+f"(d[21]), "+f"(d[22]), "+f"(d[23]),
      "+f"(d[24]), "+f"(d[25]), "+f"(d[26]), "+f"(d[27]), "+f"(d[28]), "+f"(d[29]), "+f"(d[30]), "+f"(d[31]),
      "+f"(d[32]), "+f"(d[33]), "+f"(d[34]), "+f"(d[35]), "+f"(d[36]), "+f"(d[37]), "+f"(d[38]), "+f"(d[39]),
      "+f"(d[40]), "+f"(d[41]), "+f"(d[42]), "+f"(d[43]), "+f"(d[44]), "+f"(d[45]), "+f"(d[46]), "+f"(d[47]),
      "+f"(d[48]), "+f"(d[49]), "+f"(d[50]), "+f"(d[51]), "+f"(d[52]), "+f"(d[53]), "+f"(d[54]), "+f"(d[55]),
      "+f"(d[56]), "+f"(d[57]), "+f"(d[58]), "+f"(d[59]), "+f"(d[60]), "+f"(d[61]), "+f"(d[62]), "+f"(d[63]),
      "+f"(d[64]), "+f"(d[65]), "+f"(d[66]), "+f"(d[67]), "+f"(d[68]), "+f"(d[69]), "+f"(d[70]), "+f"(d[71]),
      "+f"(d[72]), "+f"(d[73]), "+f"(d[74]), "+f"(d[75]), "+f"(d[76]), "+f"(d[77]), "+f"(d[78]), "+f"(d[79]),
      "+f"(d[80]), "+f"(d[81]), "+f"(d[82]), "+f"(d[83]), "+f"(d[84]), "+f"(d[85]), "+f"(d[86]), "+f"(d[87]),
      "+f"(d[88]), "+f"(d[89]), "+f"(d[90]), "+f"(d[91]), "+f"(d[92]), "+f"(d[93]), "+f"(d[94]), "+f"(d[95]),
      "+f"(d[96]), "+f"(d[97]), "+f"(d[98]), "+f"(d[99]), "+f"(d[100]), "+f"(d[101]), "+f"(d[102]), "+f"(d[103]),
      "+f"(d[104]), "+f"(d[105]), "+f"(d[106]), "+f"(d[107]), "+f"(d[108]), "+f"(d[109]), "+f"(d[110]), "+f"(d[111]),
      "+f"(d[112]), "+f"(d[113]), "+f"(d[114]), "+f"(d[115]), "+f"(d[116]), "+f"(d[117]), "+f"(d[118]), "+f"(d[119])
    : "r"(a[0]), "r"(a[1]), "r"(a[2]), "r"(a[3]), "l"(db), "r"(sd));
}

__device__ __forceinline__ void wgmma_rs_n256(float* d, const uint32_t* a, uint64_t db, int sd) {
  asm volatile("{ .reg .pred p; setp.ne.b32 p, %133, 0;\n"
      "wgmma.mma_async.sync.aligned.m64n256k16.f32.bf16.bf16 {"
      "%0,%1,%2,%3,%4,%5,%6,%7,%8,%9,%10,%11,%12,%13,%14,%15,"
      "%16,%17,%18,%19,%20,%21,%22,%23,%24,%25,%26,%27,%28,%29,%30,%31,"
      "%32,%33,%34,%35,%36,%37,%38,%39,%40,%41,%42,%43,%44,%45,%46,%47,"
      "%48,%49,%50,%51,%52,%53,%54,%55,%56,%57,%58,%59,%60,%61,%62,%63,"
      "%64,%65,%66,%67,%68,%69,%70,%71,%72,%73,%74,%75,%76,%77,%78,%79,"
      "%80,%81,%82,%83,%84,%85,%86,%87,%88,%89,%90,%91,%92,%93,%94,%95,"
      "%96,%97,%98,%99,%100,%101,%102,%103,%104,%105,%106,%107,%108,%109,%110,%111,"
      "%112,%113,%114,%115,%116,%117,%118,%119,%120,%121,%122,%123,%124,%125,%126,%127"
      "}, {%128,%129,%130,%131}, %132, p, 1, 1, 0; }"
    : "+f"(d[0]), "+f"(d[1]), "+f"(d[2]), "+f"(d[3]), "+f"(d[4]), "+f"(d[5]), "+f"(d[6]), "+f"(d[7]),
      "+f"(d[8]), "+f"(d[9]), "+f"(d[10]), "+f"(d[11]), "+f"(d[12]), "+f"(d[13]), "+f"(d[14]), "+f"(d[15]),
      "+f"(d[16]), "+f"(d[17]), "+f"(d[18]), "+f"(d[19]), "+f"(d[20]), "+f"(d[21]), "+f"(d[22]), "+f"(d[23]),
      "+f"(d[24]), "+f"(d[25]), "+f"(d[26]), "+f"(d[27]), "+f"(d[28]), "+f"(d[29]), "+f"(d[30]), "+f"(d[31]),
      "+f"(d[32]), "+f"(d[33]), "+f"(d[34]), "+f"(d[35]), "+f"(d[36]), "+f"(d[37]), "+f"(d[38]), "+f"(d[39]),
      "+f"(d[40]), "+f"(d[41]), "+f"(d[42]), "+f"(d[43]), "+f"(d[44]), "+f"(d[45]), "+f"(d[46]), "+f"(d[47]),
      "+f"(d[48]), "+f"(d[49]), "+f"(d[50]), "+f"(d[51]), "+f"(d[52]), "+f"(d[53]), "+f"(d[54]), "+f"(d[55]),
      "+f"(d[56]), "+f"(d[57]), "+f"(d[58]), "+f"(d[59]), "+f"(d[60]), "+f"(d[61]), "+f"(d[62]), "+f"(d[63]),
      "+f"(d[64]), "+f"(d[65]), "+f"(d[66]), "+f"(d[67]), "+f"(d[68]), "+f"(d[69]), "+f"(d[70]), "+f"(d[71]),
      "+f"(d[72]), "+f"(d[73]), "+f"(d[74]), "+f"(d[75]), "+f"(d[76]), "+f"(d[77]), "+f"(d[78]), "+f"(d[79]),
      "+f"(d[80]), "+f"(d[81]), "+f"(d[82]), "+f"(d[83]), "+f"(d[84]), "+f"(d[85]), "+f"(d[86]), "+f"(d[87]),
      "+f"(d[88]), "+f"(d[89]), "+f"(d[90]), "+f"(d[91]), "+f"(d[92]), "+f"(d[93]), "+f"(d[94]), "+f"(d[95]),
      "+f"(d[96]), "+f"(d[97]), "+f"(d[98]), "+f"(d[99]), "+f"(d[100]), "+f"(d[101]), "+f"(d[102]), "+f"(d[103]),
      "+f"(d[104]), "+f"(d[105]), "+f"(d[106]), "+f"(d[107]), "+f"(d[108]), "+f"(d[109]), "+f"(d[110]), "+f"(d[111]),
      "+f"(d[112]), "+f"(d[113]), "+f"(d[114]), "+f"(d[115]), "+f"(d[116]), "+f"(d[117]), "+f"(d[118]), "+f"(d[119]),
      "+f"(d[120]), "+f"(d[121]), "+f"(d[122]), "+f"(d[123]), "+f"(d[124]), "+f"(d[125]), "+f"(d[126]), "+f"(d[127])
    : "r"(a[0]), "r"(a[1]), "r"(a[2]), "r"(a[3]), "l"(db), "r"(sd));
}

__device__ __forceinline__ void ln_finish(float mean, float var, float& mb, float& rinv) {
  mb = round_bf16(mean);
  float sd;
  asm("sqrt.approx.ftz.f32 %0, %1;" : "=f"(sd) : "f"(round_bf16(round_bf16(var) + 1e-5f)));
  asm("rcp.approx.ftz.f32 %0, %1;" : "=f"(rinv) : "f"(round_bf16(sd)));
}
__device__ __forceinline__ uint32_t ln_apply(uint32_t x2, uint32_t mb2, float rinv) {
  uint32_t c = bsub2(x2, mb2);
  return pack_bf16(bf_lo(c) * rinv, bf_hi(c) * rinv);
}
__device__ __forceinline__ int conv_channel(int cta, int i) {
  return i < N_SHORT ? i * N_CONV_CTA + cta : N_SHORT * N_CONV_CTA + (i - N_SHORT) * 4 + cta;
}
__device__ __forceinline__ uint32_t sum4(uint32_t a, uint32_t b, uint32_t c, uint32_t d) {
  return pack_bf16((bf_lo(a) + bf_lo(b)) + (bf_lo(c) + bf_lo(d)), (bf_hi(a) + bf_hi(b)) + (bf_hi(c) + bf_hi(d)));
}
struct Ring {
  uint32_t s, ph;
  __device__ __forceinline__ void next() { if (++s == NSTAGE) { s = 0; ph ^= 1; } }
};

struct Cta {
  int rank, g1m, g1n, g2m, g2n;
  __device__ __forceinline__ explicit Cta(const Params& P) {
    const int b = cta_id();
    const Role r = P.roles.r[b >> 1];
    rank = b & 1; g1m = r.g1m; g1n = r.g1n; g2m = r.g2m; g2n = r.g2n;
  }
  __device__ __forceinline__ int cvc() const { return 2 * (-1 - g1m) + rank; }
  __device__ __forceinline__ int n_conv() const { return g2m < 0 ? N_SHORT + N_LONG_EXTRA : N_SHORT; }
  __device__ __forceinline__ int fill() const { return CH_FILL + (g1m * 3 + g1n) * 2 + rank; }
  __device__ __forceinline__ int dk() const { return g2n * 144 + rank * 72; }
  __device__ __forceinline__ void await_u(int wg, uint32_t tag) const {
    const uint32_t* p0 = g_cnt + (C_U + ((g2n * 144) / 192) * 4 + rank * 2 + wg) * 32;
    const uint32_t* p1 = g_cnt + (C_U + ((g2n * 144 + 143) / 192) * 4 + rank * 2 + wg) * 32;
    for (uint32_t n = 0;; n++) {
      const uint32_t v0 = ld_flag(p0) - tag * 18, v1 = ld_flag(p1) - tag * 18;
      if ((int32_t)(v0 | v1) >= 0) break;
      if (n > 4000000u) __trap();
    }
  }
  __device__ __forceinline__ int g2k(int kb) const { return (rank * G2_KB + (kb < 18 ? 2 * kb : 2 * kb - 35)) * 64; }
};

#define CONV_LDA(j, base) { a[2 * (j)] = lds32((base) + ((j) >> 1) * 256 + ((j) & 1) * 16); a[2 * (j) + 1] = lds32((base) + ((j) >> 1) * 256 + ((j) & 1) * 16 + 128); }
__device__ __forceinline__ void conv_mma(float* acc, const uint32_t* a, uint64_t db) {
  wgmma_rs_n256(acc, a, db, 0);
  wgmma_rs_n240(acc, a + 4, db + 16, 1);
  wgmma_rs_n224(acc, a + 8, db + 32, 1);
  wgmma_rs_n208(acc, a + 12, db + 48, 1);
  wgmma_rs_n192(acc, a + 16, db + 64, 1);
  wgmma_rs_n176(acc, a + 20, db + 80, 1);
  wgmma_rs_n160(acc, a + 24, db + 96, 1);
  wgmma_rs_n144(acc, a + 28, db + 112, 1);
  wgmma_rs_n128(acc, a + 32, db + 128, 1);
  wgmma_rs_n112(acc, a + 36, db + 144, 1);
  wgmma_rs_n96(acc, a + 40, db + 160, 1);
  wgmma_rs_n80(acc, a + 44, db + 176, 1);
  wgmma_rs_n64(acc, a + 48, db + 192, 1);
  wgmma_rs_n48(acc, a + 52, db + 208, 1);
  wgmma_rs_n32(acc, a + 56, db + 224, 1);
  wgmma_rs_n16(acc, a + 60, db + 240, 1);
}
__device__ __forceinline__ uint32_t conv_part(const float* acc, int j) {
  const int q = 31 - j;
  return q == 31 ? pack_bf16(acc[124], acc[125]) : pack_bf16(acc[4 * q] + acc[(4 * q + 6) & 127], acc[4 * q + 1] + acc[(4 * q + 7) & 127]);
}
__device__ __forceinline__ void conv_out(const uint4 (*p)[4], int ch, int wtid) {
  uint4* yo = reinterpret_cast<uint4*>(g_y + (size_t)ch * S_) + wtid;
#pragma unroll
  for (int c = 0; c < 2; c++)
    yo[128 * c] = make_uint4(sum4(p[c][0].x, p[c][1].x, p[c][2].x, p[c][3].x), sum4(p[c][0].y, p[c][1].y, p[c][2].y, p[c][3].y),
                             sum4(p[c][0].z, p[c][1].z, p[c][2].z, p[c][3].z), sum4(p[c][0].w, p[c][1].w, p[c][2].w, p[c][3].w));
}

__global__ void __cluster_dims__(2, 1, 1) __launch_bounds__(384, 1) fused_kernel(const __grid_constant__ Params P) {
  extern __shared__ uint8_t smem_raw[];
  const uint32_t t0 = clk();
  const uint32_t sb = (smem_u32(smem_raw) + 1023) & ~1023u;
  const uint32_t bars = sb + SM_BAR;
  const int tid = threadIdx.x, warp = __shfl_sync(0xffffffffu, tid >> 5, 0), lane = tid & 31;
  const bool p0 = blockIdx.x < 128;

  if (warp >= 8) {
    asm volatile("setmaxnreg.dec.sync.aligned.u32 56;");
    if (warp == 8 && lane < 9) asm volatile("prefetch.tensormap [%0];" :: "l"(&P.m_w1 + lane) : "memory");
    const uint32_t tag = ld_flag(&g_epoch) + 1;
    if (lane == 0) {
      const bool g1 = Cta(P).g1m >= 0;
      if (warp == 8) {
        for (int s = 0; s < NSTAGE; s++) mbar_init(bars + 8 * (B_FULL + s), 1);
        for (int s = 0; s < CV_NSLOT; s++) mbar_init(bars + 8 * (B_CFULL + s), 1);
        if (!g1) { mbar_arrive(bars + 8 * B_FULL); mbar_arrive(bars + 8 * (B_FULL + 1)); }
      } else if (warp == 9) {
        for (int s = 0; s < NSTAGE; s++) mbar_init(bars + 8 * (B_EMPTY + s), 2);
        mbar_init(bars + 8 * B_YDONE, g1 ? 4 : 8);
      } else if (warp == 10) {
        for (int s = B_STG; s <= B_FILL; s++) mbar_init(bars + 8 * s, 4);
      } else {
        for (int s = B_XRDY; s <= B_GO; s++) mbar_init(bars + 8 * s, 1);
      }
      asm volatile("fence.mbarrier_init.release.cluster;" ::: "memory");
    }
    __syncwarp();
    asm volatile("barrier.cluster.arrive.relaxed.aligned;" ::: "memory");
    if (warp == 8) {
      asm volatile("barrier.cluster.wait.aligned;" ::: "memory");
      if (lane == 0) {
        const Cta c(P);
        if (c.g1m >= 0) {
          const int fg = (2 * c.g1m + c.rank) * 2, dg = c.g1n * 3;
          for (int s = 0; s < NSTAGE; s++) mbar_expect_tx(bars + 8 * (B_FULL + s), G1_BYTES);
          int nw = 0;
          for (uint32_t n = 0;; n++) {
            if (nw < NSTAGE && clk() - t0 >= W1T0 + nw * W1D + (c.g1m & 7) * STAG) { tma3d_ef(sb + nw * SLOT, &P.m_w1, 0, nw * 64, fg, bars + 8 * (B_FULL + nw)); nw++; }
            if (reached(C_H, tag * 128)) break;
            if (n > 4000000u) __trap();
          }
          TLREC(2);
          fence_async_global();
#pragma unroll 1
          for (int s = 0; s < NSTAGE; s++) {
            if (s >= nw) tma3d_ef(sb + s * SLOT, &P.m_w1, 0, s * 64, fg, bars + 8 * (B_FULL + s));
            if (s == 4) { mbar_arrive(bars + 8 * B_GO); await(C_H + 1, tag * 128); fence_async_global(); }
            tma3d(sb + s * SLOT + 16384, &P.m_h, 0, s * 64, dg, bars + 8 * (B_FULL + s));
          }
          Ring r{0, 0};
#pragma unroll 1
          for (int kb = NSTAGE; kb < G1_KB; kb++, r.next()) {
            if (kb == 8) {
              for (uint32_t n = 0;; n++) {
                uint32_t v[6];
#pragma unroll
                for (int i = 0; i < 6; i++) v[i] = ld_flag(g_cnt + (C_H + 2 + i) * 32) - tag * 128;
                if ((int32_t)(v[0] | v[1] | v[2] | v[3] | v[4] | v[5]) >= 0) break;
                if (n > 4000000u) __trap();
              }
              fence_async_global();
              TLREC(8);
            }
            mbar_wait(bars + 8 * (B_EMPTY + r.s), r.ph);
            mbar_expect_tx(bars + 8 * (B_FULL + r.s), G1_BYTES);
            tma3d_ef(sb + r.s * SLOT, &P.m_w1, 0, kb * 64, fg, bars + 8 * (B_FULL + r.s));
            tma3d(sb + r.s * SLOT + 16384, &P.m_h, 0, kb * 64, dg, bars + 8 * (B_FULL + r.s));
            if (PF1 && kb + PF1 < G1_KB && (kb + PF1) % 3 == c.g1n) pf3d(&P.m_w1, 0, (kb + PF1) * 64, fg);
            if (kb >= 12 && kb < 12 + PF2 && (kb & 3) == c.g2n) pf3d(&P.m_w2, 0, c.g2k(kb - 12), c.g2m * 2);
          }
        } else {
          const int cvc = c.cvc(), n_conv = c.n_conv();
          pace(t0, CKT0);
          for (int i = 0; i < CV_NSLOT; i++) {
            mbar_expect_tx(bars + 8 * (B_CFULL + i), 8192 + 4096);
            bulk_load(sb + i * CV_SLOT + CV_KOFF + 32, P.ssm_k + (size_t)conv_channel(cvc, i) * S_, 4096, bars + 8 * (B_CFULL + i));
          }
          int ready = -1;
#pragma unroll 1
          for (int i = 0; i < n_conv; i++) {
            const int ch = conv_channel(cvc, i), s = i % CV_NSLOT;
            const uint32_t slot = sb + s * CV_SLOT, fb = bars + 8 * (B_CFULL + s);
            if (i >= CV_NSLOT) {
              mbar_wait(bars + 8 * (B_CEMPTY + s), ((i / CV_NSLOT) - 1) & 1);
              mbar_expect_tx(fb, 8192 + 4096);
              bulk_load(slot + CV_KOFF + 32, P.ssm_k + (size_t)ch * S_, 4096, fb);
            }
            const int r = ch / 96;
            if (r > ready) {
              await(C_KV + r, tag * 128);
              fence_async_global();
              if (r == 0) { mbar_arrive(bars + 8 * B_GO); TLREC(18); }
              ready = r;
            }
            bulk_load(slot, g_ub + (size_t)ch * 4096, 8192, fb);
            if (c.g2m >= 0 && i >= 8 && i < 8 + PF2 / 2 && !(i & 1)) pf3d(&P.m_w2, 0, c.g2k((i - 8) * 2 + c.g2n), c.g2m * 2);
          }
        }
        if (c.g2m >= 0) {
          const int sg = c.g2m * 2, dk = c.dk(), ds = c.g2n * 144 + (c.rank ^ 1) * 72;
          constexpr int NPRE = 3;
#pragma unroll 1
          for (int kb = 0; kb < NPRE; kb++) {
            const int s = G1_KB % NSTAGE + kb;
            mbar_wait(bars + 8 * (B_EMPTY + s), ((G1_KB / NSTAGE) - 1) & 1);
            mbar_expect_tx(bars + 8 * (B_FULL + s), G2_BYTES);
            tma3d_ef(sb + s * SLOT, &P.m_w2, 0, c.g2k(kb), sg, bars + 8 * (B_FULL + s));
          }
          Ring r{G1_KB % NSTAGE, ((G1_KB / NSTAGE) - 1) & 1};
#pragma unroll 1
          for (int kb = 0; kb < G2_KB; kb++, r.next()) {
            const int k0 = c.g2k(kb);
            const uint32_t fb = bars + 8 * (B_FULL + r.s), slot = sb + r.s * SLOT;
            if (kb == 0) { c.await_u(0, tag); fence_async_global(); TLREC(6); }
            if (kb == 18) { mbar_wait(bars + 8 * B_ULATE, 0); fence_async_global(); }
            if (kb >= NPRE) {
              mbar_wait(bars + 8 * (B_EMPTY + r.s), r.ph);
              mbar_expect_tx(fb, G2_BYTES);
              tma3d_ef(slot, &P.m_w2, 0, k0, sg, fb);
            }
            tma2d(slot + 16384, &P.m_uld, k0, ds, fb);
            tma2d(slot + 16384 + 9216, &P.m_uld, k0, dk, fb);
            if (PF2 && kb + PF2 < G2_KB && (kb & 3) == c.g2n) pf3d(&P.m_w2, 0, c.g2k(kb + PF2), sg);
          }
          mbar_expect_tx(bars + 8 * B_XFULL, 18432);
          mbar_expect_tx(bars + 8 * (B_XFULL + 1), 18432);
          mbar_wait(bars + 8 * (B_EMPTY + XSLOT), r.ph);
          mbar_arrive_remote(mapa(bars + 8 * B_XRDY, c.rank ^ 1));
        }
      }
    } else {
      const int ht = tid - 288;
      if (p0) {
        const int hf = ht / 48, pr = ht % 48;
        const int s0 = blockIdx.x * 16 + hf * 8;
        const bool first = s0 == 0;
        const __nv_bfloat16* kp = P.k + (ptrdiff_t)(s0 - 4) * D_ + 2 * pr;
        const __nv_bfloat16* vp = P.v + (ptrdiff_t)(s0 - 1) * D_ + 2 * pr;
        const uint4* wp = reinterpret_cast<const uint4*>(P.shift_k) + pr;
        const uint32_t st = sb + SM_KVS + (1 - hf) * 1536 + pr * 32;
        uint32_t kk[12], vv[9];
        uint4 w;
        auto load = [&](int r) {
#pragma unroll
          for (int j = 0; j < 12; j++) kk[j] = (j < 4 && first) ? 0u : ldg32(kp + r * 96 + j * D_);
#pragma unroll
          for (int j = 0; j < 9; j++) vv[j] = (j < 1 && first) ? 0u : ldg32(vp + r * 96 + j * D_);
          w = __ldg(wp + r * 48);
        };
        pace(t0, KVT0 + (blockIdx.x & 7) * STAG);
        load(0);
        asm volatile("barrier.cluster.wait.aligned;" ::: "memory");
#pragma unroll 1
        for (int r = 0; r < KV_ROUNDS; r++) {
          const uint32_t w0 = __byte_perm(w.x, w.z, 0x5410), w1 = __byte_perm(w.x, w.z, 0x7632);
          const uint32_t w2 = __byte_perm(w.y, w.w, 0x5410), w3 = __byte_perm(w.y, w.w, 0x7632);
#pragma unroll
          for (int j = 0; j < 9; j++)
            vv[j] = bmul2(bfma2(kk[j + 3], w0, bfma2(kk[j + 2], w1, bfma2(kk[j + 1], w2, bmul2(kk[j], w3)))), vv[j]);
#pragma unroll
          for (int c = 0; c < 2; c++)
#pragma unroll
            for (int pi = 0; pi < 2; pi++) {
              const uint32_t sel = c ? 0x7632 : 0x5410;
              sts128(st + c * 3072 + pi * 16, __byte_perm(vv[7 + pi], vv[6 + pi], sel), __byte_perm(vv[5 + pi], vv[4 + pi], sel),
                     __byte_perm(vv[3 + pi], vv[2 + pi], sel), __byte_perm(vv[1 + pi], vv[pi], sel));
            }
          bar_sync(1, 96);
          if (ht == 0) { fence_async_smem(); tma3d_store(&P.m_ub, sb + SM_KVS, 16 * (127 - blockIdx.x), r * 48, 0); bulk_commit(); }
          if (r > 0 && r + 1 < KV_ROUNDS) load(r + 1);
          if (ht == 0) { bulk_wait_all(); signal_stored(C_KV + r); if (r == 0 || r == 5) TLREC(22 + r); }
          if (r == 0) { mbar_wait(bars + 8 * B_GO, 0); load(1); }
          __syncwarp();
          bar_sync(1, 96);
        }
        if (ht == 0) mbar_arrive(bars + 8 * B_KVDONE);
      } else {
        asm volatile("barrier.cluster.wait.aligned;" ::: "memory");
      }
      if (lane == 0) {
        const Cta c(P);
        if (warp < 11) {
          if (c.g1m >= 0) {
            const int wg = warp - 9, fb64 = (2 * c.g1m + c.rank) * 2 + wg;
            const uint32_t stg = wg == 0 ? sb + SM_DED : sb + SLOT + 16384;
#pragma unroll 1
            for (int ck = 0; ck < 3; ck++) {
              mbar_wait(bars + 8 * (B_STG + wg * 3 + ck), 0);
              fence_async_smem();
              tma2d_store(&P.m_ust, stg + ck * 8192, fb64 * 64, c.g1n * 192 + ck * 64);
            }
            TLREC(13 + wg);
            bulk_commit();
            bulk_wait_all();
            signal_stored(C_U + c.g1n * 4 + (fb64 / G2_KB) * 2 + wg);
            mbar_arrive(bars + 8 * (wg == 0 ? B_DED : B_EMPTY + 1));
            TLREC(15 + wg);
          }
          if (warp == 10 && c.g2m >= 0) {
            mbar_wait(bars + 8 * B_YDONE, 0);
            c.await_u(1, tag);
            mbar_arrive(bars + 8 * B_ULATE);
            fence_async_smem();
            mbar_expect_tx(bars + 8 * B_XT, 18432);
#pragma unroll 1
            for (int j = 0; j < 8; j++)
              tma2d(sb + ((XSLOT + 1 + (j >> 1)) % NSTAGE) * SLOT + G2_BYTES + (j & 1) * 2304, &P.m_x, c.dk(), c.g2m * 128 + j * 16, bars + 8 * B_XT);
          }
        } else {
          if (c.g1m >= 0) {
            const int ch = c.fill();
            await(C_KV + ch / 96, tag * 128);
            fence_async_global();
            mbar_wait(bars + 8 * B_FILL, 0);
            sts128(sb + SLOT, 0, 0, 0, 0); sts128(sb + SLOT + 16, 0, 0, 0, 0);
            mbar_expect_tx(bars + 8 * B_CFULL, 8192 + 4096);
            bulk_load(sb + SLOT + 32, P.ssm_k + (size_t)ch * S_, 4096, bars + 8 * B_CFULL);
            bulk_load(sb, g_ub + (size_t)ch * 4096, 8192, bars + 8 * B_CFULL);
          }
          mbar_wait(bars + 8 * B_YDONE, 0);
          signal(C_Y);
          if (c.g2m >= 0) {
            await<true>(C_Y, tag * 132);
            fence_async_global(); fence_async_smem();
            if (blockIdx.x == 0) st_flag(&g_epoch, tag);
            TLREC(19);
            mbar_expect_tx(bars + 8 * B_Y2, 18432);
            tma2d(sb + SM_DED, &P.m_y, c.g2m * 128, c.dk(), bars + 8 * B_Y2);
            tma2d(sb + SM_DED + 9216, &P.m_y, c.g2m * 128 + 64, c.dk(), bars + 8 * B_Y2);
          }
        }
      }
    }
    TLEND();
  } else {
    asm volatile("barrier.cluster.arrive.relaxed.aligned;" ::: "memory");
    if (p0) {
      const int row = warp * 256 + blockIdx.x * 2 + (lane >> 4);
      const uint2* src = reinterpret_cast<const uint2*>(P.x + (size_t)row * D_) + (lane & 15);
      if (warp) pace(t0, XD0 + (warp - 1) * XD);
      uint32_t xr[18];
#pragma unroll
      for (int j = 0; j < 9; j++) asm volatile("ld.global.nc.v2.u32 {%0,%1}, [%2];" : "=r"(xr[2 * j]), "=r"(xr[2 * j + 1]) : "l"(src + 16 * j));
      float c[36];
      float s[4] = {0.f, 0.f, 0.f, 0.f};
#pragma unroll
      for (int i = 0; i < 18; i++) { c[2 * i] = bf_lo(xr[i]); c[2 * i + 1] = bf_hi(xr[i]); }
#pragma unroll
      for (int i = 0; i < 36; i++) s[i & 3] += c[i];
      const float ml = ((s[0] + s[1]) + (s[2] + s[3])) * (1.0f / 36.0f);
      if (tid == 0 && ml != 123.456f) TLREC(28);
#pragma unroll
      for (int i = 0; i < 36; i++) { c[i] -= ml; s[i & 3] = i < 4 ? c[i] * c[i] : fmaf(c[i], c[i], s[i & 3]); }
      float m = ml, q = (s[0] + s[1]) + (s[2] + s[3]), n2 = 18.f;
#pragma unroll
      for (int o = 1; o < 16; o <<= 1) {
        const float mo = __shfl_xor_sync(0xffffffffu, m, o), qo = __shfl_xor_sync(0xffffffffu, q, o);
        const float dl = m - mo;
        q = fmaf(dl * dl, n2, q + qo);
        m = 0.5f * (m + mo);
        n2 *= 2.f;
      }
      const float var = q * (1.0f / 576.0f);
      float mb, rinv, mb2, rinv2;
      ln_finish(m, var, mb, rinv);
      ln_finish((m - mb) * rinv, var * rinv * rinv, mb2, rinv2);
      const float ca = rinv * rinv2, cb = fmaf(ml - mb, rinv, -mb2) * rinv2;
      const uint32_t hs = sb + SM_DED + warp * 2304, ss = sb + SM_DED + 18432 + warp * 32;
#pragma unroll
      for (int j = 0; j < 9; j++)
        sts64(hs + (lane >> 4) * 1152 + (lane & 15) * 8 + j * 128, pack_bf16(fmaf(c[4 * j], ca, cb), fmaf(c[4 * j + 1], ca, cb)),
              pack_bf16(fmaf(c[4 * j + 2], ca, cb), fmaf(c[4 * j + 3], ca, cb)));
      if ((lane & 15) == 0) sts128(ss + lane, __float_as_uint(mb), __float_as_uint(rinv), 0, 0);
      __syncwarp();
      if (lane == 0) {
        if (tid == 0) TLREC(29);
        fence_async_smem();
        bulk_store(g_h + (size_t)row * D_, hs, 2304);
        bulk_store(g_stats + row, ss, 32);
        bulk_commit();
        bulk_wait_all();
        signal_stored(C_H + warp);
        if (tid == 0) TLREC(1);
        if (tid == 224) TLREC(31);
      }
      __syncwarp();
    }
    asm volatile("setmaxnreg.inc.sync.aligned.u32 224;");
    asm volatile("barrier.cluster.wait.aligned;" ::: "memory");
    const int wg = warp >> 2, w = warp & 3, g = lane >> 2, t = lane & 3, wtid = tid & 127;
    const bool elect = w == 0 && lane == 0;
    const uint64_t da0 = make_desc(sb + wg * 8192, 8192, 1024, 1);
    const uint32_t dm0 = (w == 0 && g + t == 7) ? 0xffffu : 0u, dm2 = (w == 0 && g + t == 3) ? 0xffffu : 0u;
    if (const Cta c(P); c.g1m >= 0) {
      const int frow = ((2 * c.g1m + c.rank) * 2 + wg) * 64 + w * 16 + g;
      const float hb0 = 0.5f * __bfloat162float(P.b1[frow]), hb1 = 0.5f * __bfloat162float(P.b1[frow + 8]);
      const uint32_t dd = __bfloat16_as_ushort(P.ssm_D[c.fill()]);
      {
        const uint64_t db0 = make_desc(sb + 16384, 8192, 1024, 1);
        float acc[96];
        Ring r{0, 0};
        uint32_t prev = 0;
        auto step = [&](int first, bool release) {
          mbar_wait(bars + 8 * (B_FULL + r.s), r.ph);
          const uint64_t da = da0 + r.s * (SLOT >> 4), db = db0 + r.s * (SLOT >> 4);
          wg_fence();
          wgmma_ss_n192_t11(acc, da, db, !first);
#pragma unroll
          for (int k = 1; k < 4; k++) wgmma_ss_n192_t11(acc, da + k * 128, db + k * 128, 1);
          wg_commit();
          if (release) { wg_wait<1>(); if (elect) mbar_arrive(bars + 8 * (B_EMPTY + prev)); }
          prev = r.s;
          r.next();
        };
        step(1, false);
        if (tid == 0) TLREC(3);
#pragma unroll 1
        for (int kb = 1; kb < G1_KB - G1_TAIL; kb++) step(0, true);
        if (elect) TLREC(20 + wg);
        if (wg == 1) {
          wg_wait<0>();
          if (elect) mbar_arrive(bars + 8 * (B_EMPTY + prev));
          bar_sync(5, 256);
        }
        step(0, wg == 0);
#pragma unroll 1
        for (int kb = G1_KB - G1_TAIL + 1; kb < G1_KB - 1; kb++) step(0, true);
        step(0, wg == 1);
        if (wg == 0) bar_arrive(5, 256);
        wg_wait<0>();
        pin_regs<96>(acc);
        if (elect) TLREC(4 + wg);
        if (wg == 0 && lane == 0) mbar_arrive(bars + 8 * B_FILL);
        mbar_wait(bars + 8 * (wg == 0 ? B_KVDONE : B_FILL), 0);
        const uint32_t stg = wg == 0 ? sb + SM_DED : sb + SLOT + 16384;
        const uint32_t sa = stg + ((lane >> 4) * 8 + (lane & 7)) * 128 + (((2 * w + ((lane >> 3) & 1)) ^ (lane & 7)) << 4);
#pragma unroll
        for (int ck = 0; ck < 3; ck++) {
          const uint32_t zero = blockIdx.y;
          uint32_t pk[16];
#pragma unroll
          for (int i = 0; i < 16; i++) {
            float hb = (i & 1) ? hb1 : hb0;
            if (i >= 6) asm("lop3.b32 %0, %1, %2, %3, 0xea;" : "=f"(hb) : "r"(pk[i - 6]), "r"(zero), "f"((i & 1) ? hb1 : hb0));
            pk[i] = pack_bf16(gelu_half(fmaf(acc[32 * ck + 2 * i], 0.5f, hb)), gelu_half(fmaf(acc[32 * ck + 2 * i + 1], 0.5f, hb)));
            if ((i & 3) == 3) stsm4t(sa + ck * 8192 + (i >> 2) * 2048, pk[i - 3], pk[i - 2], pk[i - 1], pk[i]);
          }
          __syncwarp();
          if (lane == 0) mbar_arrive(bars + 8 * (B_STG + wg * 3 + ck));
          if (ck < 2) mbar_wait(bars + 8 * B_KVDONE, 0);
        }
      }
      if (wg == 0) {
        uint32_t a[64];
        float acc[128];
        mbar_wait(bars + 8 * B_CFULL, 0);
#pragma unroll
        for (int j = 0; j < 32; j++) CONV_LDA(j, sb + SLOT + (8 * w + g + t + 1) * 4)
        a[0] = badd2(a[0], dd & dm0); a[2] = badd2(a[2], dd & dm2);
        wg_fence();
        conv_mma(acc, a, make_desc(sb, 4096, 128, 0));
        wg_commit();
        mbar_wait(bars + 8 * B_DED, 0);
        wg_wait<0>();
        pin_regs<128>(acc);
        if (elect) { TLREC(17); mbar_arrive(bars + 8 * B_EMPTY); mbar_arrive(bars + 8 * (B_EMPTY + 1)); }
        const uint32_t red = sb + SM_DED;
        if (lane < 8 * w) sts32(red + w * CV_REDW + lane * 4, 0);
#pragma unroll
        for (int j = 0; j < 32; j++) sts32(red + w * CV_REDW + (8 * (3 - t + w) + g) * 4 + j * 128, conv_part(acc, j));
        bar_sync(3, 128);
        uint4 p[2][4];
#pragma unroll
        for (int i = 0; i < 8; i++) p[i >> 2][i & 3] = lds128(red + (i & 3) * CV_REDW + (wtid + 128 * (i >> 2)) * 16);
        conv_out(p, Cta(P).fill(), wtid);
        __syncwarp();
        if (lane == 0) mbar_arrive(bars + 8 * B_YDONE);
        if (elect) TLREC(18);
      }
    } else {
      const int cvc = c.cvc(), n_conv = c.n_conv();
      const uint32_t red = wg == 0 ? sb + SM_DED : sb + CV_RED1;
      bar_sync(2, 256);
      if (wtid < 8 * CV_NSLOT / 2) sts32(sb + (2 * (wtid >> 3) + wg) * CV_SLOT + CV_KOFF + (wtid & 7) * 4, 0);
      sts32(red + w * CV_REDW + lane * 4, 0);
      bar_sync(3 + wg, 128);
      const uint32_t ko = sb + CV_KOFF + (8 * w + g + t + 1) * 4;
      const uint32_t wr = red + w * CV_REDW + (8 * (3 - t + w) + g) * 4;
      uint32_t a[64];
      uint32_t dd = __bfloat16_as_ushort(P.ssm_D[conv_channel(cvc, wg)]);
      mbar_wait(bars + 8 * (B_CFULL + wg), 0);
      if (tid == 0) TLREC(17);
#pragma unroll
      for (int j = 0; j < 32; j++) CONV_LDA(j, ko + wg * CV_SLOT)
      if (wg == 1) bar_arrive(5, 256);
#pragma unroll 1
      for (int i = wg; i < n_conv; i += 2) {
        const int s = i % CV_NSLOT;
        const int in = i + 2 < n_conv ? i + 2 : i, sn = in % CV_NSLOT;
        a[0] = badd2(a[0], dd & dm0); a[2] = badd2(a[2], dd & dm2);
        dd = __bfloat16_as_ushort(P.ssm_D[conv_channel(cvc, in)]);
        float acc[128];
        bar_sync(5 + wg, 256);
        wg_fence();
        conv_mma(acc, a, make_desc(sb + s * CV_SLOT, 4096, 128, 0));
        wg_commit();
        if (i + 1 < n_conv) bar_arrive(5 + (wg ^ 1), 256);
        wg_wait<0>();
        pin_regs<128>(acc);
        if (lane == 0) mbar_arrive(bars + 8 * (B_CEMPTY + s));
        mbar_wait(bars + 8 * (B_CFULL + sn), (in / CV_NSLOT) & 1);
        const uint32_t ka = ko + sn * CV_SLOT;
#pragma unroll
        for (int j = 0; j < 32; j++) {
          if (j < 24) CONV_LDA(j, ka)
          sts32(wr + j * 128, conv_part(acc, j));
        }
        bar_sync(3 + wg, 128);
        uint4 p[2][4];
#pragma unroll
        for (int x = 0; x < 8; x++) p[x >> 2][x & 3] = lds128(red + (x & 3) * CV_REDW + (wtid + 128 * (x >> 2)) * 16);
#pragma unroll
        for (int j = 24; j < 32; j++) CONV_LDA(j, ka)
        conv_out(p, conv_channel(cvc, i), wtid);
      }
      fence_async_smem();
      bar_sync(3 + wg, 128);
      if (elect) { mbar_arrive(bars + 8 * B_EMPTY); mbar_arrive(bars + 8 * (B_EMPTY + 1)); TLREC(20 + wg); }
      if (lane == 0) mbar_arrive(bars + 8 * B_YDONE);
      __syncwarp();
    }
    if (const Cta c(P); c.g2m >= 0) {
      const int srow = c.g2m * 128 + wg * 64 + w * 16 + g;
      const uint64_t db0 = make_desc(sb + 16384, 16, 1024, 1);
      float acc[72], acc2[36], acc3[36];
      Ring r{G1_KB % NSTAGE, (G1_KB / NSTAGE) & 1};
      uint32_t prev = 0;
      auto step = [&](int first) {
        mbar_wait(bars + 8 * (B_FULL + r.s), r.ph);
        const uint64_t da = da0 + r.s * (SLOT >> 4), db = db0 + r.s * (SLOT >> 4);
        wg_fence();
        wgmma_ss_n144_t10(acc, da, db, !first);
#pragma unroll
        for (int k = 1; k < 4; k++) wgmma_ss_n144_t10(acc, da + k * 128, db + k * 2, 1);
        wg_commit();
        if (!first) { wg_wait<1>(); if (elect) mbar_arrive(bars + 8 * (B_EMPTY + prev)); }
        prev = r.s;
        r.next();
      };
      step(1);
      if (tid == 128) TLREC(7);
      const float2 st0 = __ldcg(reinterpret_cast<const float2*>(g_stats + srow)), st1 = __ldcg(reinterpret_cast<const float2*>(g_stats + srow + 8));
      const float hb0 = 0.5f * __bfloat162float(P.b2[srow]), hb1 = 0.5f * __bfloat162float(P.b2[srow + 8]);
#pragma unroll 1
      for (int kb = 1; kb < G2_KB - G2_TAIL; kb++) step(0);
      if (tid == 0) TLREC(30);
      const uint32_t xo = sb + ((XSLOT + 1 + (warp >> 1)) % NSTAGE) * SLOT + G2_BYTES + (warp & 1) * 2304;
      const uint32_t xa = xo + (lane & 15) * 144 + (lane >> 4) * 16;
      uint32_t xx[18], ss[18];
      auto prep = [&]() {
        mbar_wait(bars + 8 * B_XT, 0);
        mbar_wait(bars + 8 * B_Y2, 0);
        const uint32_t ya = sb + SM_DED + wg * 9216 + ((lane >> 4) * 8 + (lane & 7)) * 128 + (((2 * w + ((lane >> 3) & 1)) ^ (lane & 7)) << 4);
#pragma unroll
        for (int q = 0; q < 8; q += 2) { ldsm4(xx + 2 * q, xa + q * 16); ldsm4t(ss + 2 * q, ya + q * 1024); }
        ldsm2(xx + 16, xo + (lane & 15) * 144 + 128);
        ldsm2t(ss + 16, ya - (lane >> 4) * 1024 + 8 * 1024);
        const uint32_t m0 = pack_bf16(st0.x, st0.x), m1 = pack_bf16(st1.x, st1.x);
#pragma unroll
        for (int i = 0; i < 18; i++) ss[i] = bmul2(ln_apply(xx[i], (i & 1) ? m1 : m0, (i & 1) ? st1.y : st0.y), ss[i]);
      };
      if (wg == 1) {
        wg_wait<0>();
        if (elect) mbar_arrive(bars + 8 * (B_EMPTY + XSLOT));
        prep();
        bar_sync(5, 256);
      }
#pragma unroll
      for (int kb = G2_KB - G2_TAIL; kb < G2_KB; kb++) {
        const int p = G1_KB + kb, s = p % NSTAGE;
        mbar_wait(bars + 8 * (B_FULL + s), (p / NSTAGE) & 1);
        wg_fence();
#pragma unroll
        for (int k = 0; k < 4; k++)
          wgmma_ss_n72_t10(acc3, da0 + s * (SLOT >> 4) + k * 128, db0 + s * (SLOT >> 4) + k * 2, kb != G2_KB - G2_TAIL || k != 0);
        wg_commit();
        if (kb == G2_KB - G2_TAIL) { wg_wait<1>(); if (tid == 0) mbar_arrive(bars + 8 * (B_EMPTY + XSLOT)); }
      }
      bar_arrive(5 + wg, 256);
      wg_wait<0>();
      pin_regs<72>(acc);
      pin_regs<36>(acc3);
      const uint32_t xz = sb + XSLOT * SLOT + wg * 18432 + wtid * 16;
      mbar_wait(bars + 8 * B_XRDY, 0);
      {
        const uint32_t rz = mapa(xz, c.rank ^ 1), rb = mapa(bars + 8 * (B_XFULL + wg), c.rank ^ 1);
#pragma unroll
        for (int q = 0; q < 9; q++)
          asm volatile("st.async.weak.shared::cluster.mbarrier::complete_tx::bytes.v4.f32 [%0], {%1,%2,%3,%4}, [%5];"
                       :: "r"(rz + q * 2048), "f"(acc[4 * q] + acc3[4 * q]), "f"(acc[4 * q + 1] + acc3[4 * q + 1]), "f"(acc[4 * q + 2] + acc3[4 * q + 2]),
                          "f"(acc[4 * q + 3] + acc3[4 * q + 3]), "r"(rb) : "memory");
      }
      if (wg == 0) prep();
      bar_sync(6 - wg, 256);
      wg_fence();
#pragma unroll
      for (int kb = G2_KB - G2_TAIL; kb < G2_KB; kb++) {
        const int s = (G1_KB + kb) % NSTAGE;
#pragma unroll
        for (int k = 0; k < 4; k++)
          wgmma_ss_n72_t10(acc2, da0 + s * (SLOT >> 4) + k * 128, db0 + s * (SLOT >> 4) + (9216 >> 4) + k * 2, kb != G2_KB - G2_TAIL || k != 0);
      }
      wg_commit();
      if (wg == 0) bar_arrive(5, 256);
      mbar_wait_cluster(bars + 8 * (B_XFULL + wg), 0);
#pragma unroll
      for (int q = 0; q < 9; q++) {
        const float4 pv = lds128f(xz + q * 2048);
        acc[36 + 4 * q] = fmaf(acc[36 + 4 * q] + pv.x, 0.5f, hb0); acc[37 + 4 * q] = fmaf(acc[37 + 4 * q] + pv.y, 0.5f, hb0);
        acc[38 + 4 * q] = fmaf(acc[38 + 4 * q] + pv.z, 0.5f, hb1); acc[39 + 4 * q] = fmaf(acc[39 + 4 * q] + pv.w, 0.5f, hb1);
      }
      wg_wait<0>();
      pin_regs<36>(acc2);
      if (elect) TLREC(9 + wg);
      uint32_t ob[18];
#pragma unroll
      for (int i = 0; i < 18; i++)
        ob[i] = bfma2(ss[i], pack_bf16(silu_half(fmaf(acc2[2 * i], 0.5f, acc[36 + 2 * i])), silu_half(fmaf(acc2[2 * i + 1], 0.5f, acc[37 + 2 * i]))), xx[i]);
#pragma unroll
      for (int q = 0; q < 8; q += 2) stsm4(xa + q * 16, ob[2 * q], ob[2 * q + 1], ob[2 * q + 2], ob[2 * q + 3]);
      stsm2(xo + (lane & 15) * 144 + 128, ob[16], ob[17]);
      __syncwarp();
      if (lane == 0) {
        fence_async_smem();
        tma2d_store(&P.m_out, xo, Cta(P).dk(), srow);
        bulk_commit();
        bulk_wait_read();
      }
      if (elect) TLREC(11 + wg);
    }
    TLEND();
  }
}

typedef CUresult (*EncodeFn)(CUtensorMap*, CUtensorMapDataType, cuuint32_t, void*, const cuuint64_t*, const cuuint64_t*, const cuuint32_t*,
                             const cuuint32_t*, CUtensorMapInterleave, CUtensorMapSwizzle, CUtensorMapL2promotion, CUtensorMapFloatOOBfill);

#define L2PROM CU_TENSOR_MAP_L2_PROMOTION_L2_256B
void make_map(EncodeFn fn, CUtensorMap* m, const void* ptr, int rank, const cuuint64_t* dims, const cuuint64_t* strides, const cuuint32_t* box,
              CUtensorMapSwizzle sw) {
  const cuuint32_t es[3] = {1, 1, 1};
  fn(m, CU_TENSOR_MAP_DATA_TYPE_BFLOAT16, rank, const_cast<void*>(ptr), dims, strides, box, es, CU_TENSOR_MAP_INTERLEAVE_NONE, sw,
     L2PROM, CU_TENSOR_MAP_FLOAT_OOB_FILL_NONE);
}

void make_roles(Roles& R) {
  int c1 = 0, ncv = 2;
  for (int g = 0; g < 8; g++)
    for (int c = 0; c < 66; c++) {
      const int tp = (c + 62) % 66;
      int gg, idx;
      if (tp < 32) { gg = tp % 8; idx = tp / 8; }
      else if (tp < 60) { gg = 1 + (tp - 32) % 7; idx = 4 + (tp - 32) / 7; }
      else if (tp < 62) { gg = 6 + tp - 60; idx = 8; }
      else { gg = 0; idx = 4 + tp - 62; }
      if (gg != g) continue;
      Role& r = R.r[c];
      if (idx < 8) { r.g2m = (int8_t)(2 * g + idx / 4); r.g2n = (int8_t)(idx % 4); }
      else { r.g2m = -1; r.g2n = 0; }
      if (idx < (g < 2 ? 6 : 7)) { r.g1m = (int8_t)(c1 / 3); r.g1n = (int8_t)(c1 % 3); c1++; }
      else { r.g1m = (int8_t)(-1 - (idx == 8 ? tp - 60 : ncv++)); r.g1n = 0; }
    }
}

}

extern "C" void kernel_launch(void* const* d_in, const int* in_sizes, int n_in, void* d_out, int out_size) {
  static Params P;
  static const void* cached[4] = {nullptr, nullptr, nullptr, nullptr};
  if (cached[0] != d_in[7] || cached[1] != d_in[9] || cached[2] != d_out || cached[3] != d_in[0]) {
    void* fp = nullptr;
    cudaDriverEntryPointQueryResult qr;
    cudaGetDriverEntryPoint("cuTensorMapEncodeTiled", &fp, cudaEnableDefault, &qr);
    EncodeFn fn = (EncodeFn)fp;
    void *ph, *pu, *py, *pb;
    cudaGetSymbolAddress(&pb, g_ub);
    cudaGetSymbolAddress(&py, g_y);
    cudaGetSymbolAddress(&ph, g_h);
    cudaGetSymbolAddress(&pu, g_u);
    { cuuint64_t d[3] = {64, S_, F_ / 64}, s[2] = {F_ * 2, 128}; cuuint32_t b[3] = {64, 64, 2}; make_map(fn, &P.m_w1, d_in[7], 3, d, s, b, CU_TENSOR_MAP_SWIZZLE_128B); }
    { cuuint64_t d[3] = {64, S_, D_ / 64}, s[2] = {D_ * 2, 128}; cuuint32_t b[3] = {64, 64, 3}; make_map(fn, &P.m_h, ph, 3, d, s, b, CU_TENSOR_MAP_SWIZZLE_128B); }
    { cuuint64_t d[2] = {F_, D_}, s[1] = {F_ * 2}; cuuint32_t b[2] = {64, 64}; make_map(fn, &P.m_ust, pu, 2, d, s, b, CU_TENSOR_MAP_SWIZZLE_128B); }
    { cuuint64_t d[3] = {64, F_, S_ / 64}, s[2] = {S_ * 2, 128}; cuuint32_t b[3] = {64, 64, 2}; make_map(fn, &P.m_w2, d_in[9], 3, d, s, b, CU_TENSOR_MAP_SWIZZLE_128B); }
    { cuuint64_t d[2] = {F_, D_}, s[1] = {F_ * 2}; cuuint32_t b[2] = {64, 72}; make_map(fn, &P.m_uld, pu, 2, d, s, b, CU_TENSOR_MAP_SWIZZLE_128B); }
    { cuuint64_t d[2] = {D_, S_}, s[1] = {D_ * 2}; cuuint32_t b[2] = {72, 16}; make_map(fn, &P.m_out, d_out, 2, d, s, b, CU_TENSOR_MAP_SWIZZLE_NONE);
      make_map(fn, &P.m_x, d_in[0], 2, d, s, b, CU_TENSOR_MAP_SWIZZLE_NONE); }
    { cuuint64_t d[2] = {S_, D_}, s[1] = {S_ * 2}; cuuint32_t b[2] = {64, 72}; make_map(fn, &P.m_y, py, 2, d, s, b, CU_TENSOR_MAP_SWIZZLE_128B); }
    { cuuint64_t d[3] = {2048, D_ / 2, 4}, s[2] = {16384, 4096}; cuuint32_t b[3] = {16, 48, 4}; make_map(fn, &P.m_ub, pb, 3, d, s, b, CU_TENSOR_MAP_SWIZZLE_NONE); }
    make_roles(P.roles);
    cudaFuncSetAttribute(fused_kernel, cudaFuncAttributeMaxDynamicSharedMemorySize, SM_TOTAL);
    cached[0] = d_in[7]; cached[1] = d_in[9]; cached[2] = d_out; cached[3] = d_in[0];
  }
  P.x = (const __nv_bfloat16*)d_in[0]; P.k = (const __nv_bfloat16*)d_in[1]; P.v = (const __nv_bfloat16*)d_in[2];
  P.shift_k = (const __nv_bfloat16*)d_in[3]; P.ssm_k = (const __nv_bfloat16*)d_in[4]; P.ssm_D = (const __nv_bfloat16*)d_in[5];
  P.b1 = (const __nv_bfloat16*)d_in[8]; P.b2 = (const __nv_bfloat16*)d_in[10];
  fused_kernel<<<132, 384, SM_TOTAL>>>(P);
}
```

```cpp
#include <cuda_runtime.h>
#include <cuda.h>
#include <cuda_bf16.h>
#include <stddef.h>
#include <stdint.h>

namespace {

constexpr int S_ = 2048, D_ = 576, F_ = 4608;
constexpr int NSTAGE = 5, SLOT = 40960;
constexpr int G1_KB = 32, G2_KB = 36;
constexpr int G1_BYTES = 40960, G2_BYTES = 16384 + 18432;
constexpr int N_CONV_CTA = 24, N_SHORT = 18, N_LONG_EXTRA = 9, CH_FILL = N_CONV_CTA * N_SHORT + 4 * N_LONG_EXTRA;
static_assert(CH_FILL + 108 == D_, "conv split");
constexpr int KV_ROUNDS = 6;
#define G1T 5
constexpr int G1_TAIL = G1T, G2_TAIL = 4;
constexpr uint32_t XD0 = 200, XD = 0, W1T0 = 1800, W1D = 900, KVT0 = 2400, STAG = 60, CKT0 = 2400;

constexpr int SM_DED = NSTAGE * SLOT;
constexpr int SM_KVS = SM_DED + 18944;
constexpr int SM_BAR = SM_DED + 18432 + 3 * 2304;
constexpr int SM_TOTAL = SM_BAR + 256 + 1024;
constexpr int CV_NSLOT = 4, CV_KOFF = 8192, CV_SLOT = 8192 + 4224;
constexpr int CV_REDW = 2112 * 2, CV_RED1 = CV_NSLOT * CV_SLOT;
static_assert(CV_RED1 + 4 * CV_REDW <= 2 * SLOT, "conv overlay");
static_assert(G1_KB % NSTAGE == 2, "slots 0 and 1 hold the last two GEMM1 k-blocks");
constexpr int XSLOT = (G1_KB + G2_KB) % NSTAGE;
static_assert(XSLOT == 3, "x tile placement");
__host__ __device__ constexpr int x_off(int j) {
  return j < 2 ? 2 * SLOT + G2_BYTES + j * 2304 : j == 2 ? 3 * SLOT + 36864 : j < 5 ? 4 * SLOT + G2_BYTES + (j - 3) * 2304 : SM_DED + 18432 + (j - 5) * 2304;
}
constexpr int B_FULL = 0, B_EMPTY = NSTAGE, B_CFULL = 2 * NSTAGE, B_STG = B_CFULL + CV_NSLOT  , B_CEMPTY = B_STG,
              B_FILL = B_STG + 6, B_YDONE = B_FILL + 1, B_XRDY = B_YDONE + 1, B_XFULL = B_XRDY + 1  , B_XT = B_XFULL + 2,
              B_Y2 = B_XT + 1, B_KVDONE = B_Y2 + 1, B_DED = B_KVDONE + 1, B_ULATE = B_DED + 1, B_YRDY = B_ULATE + 1, B_GO = B_YRDY + 1;
static_assert(B_GO < 32, "barrier page");
constexpr int C_H = 0  , C_KV = 8, C_U = C_KV + KV_ROUNDS  , C_Y = C_U + 12, C_COUNT = C_Y + 1;

struct Scratch {
  uint32_t cnt[C_COUNT * 32];
  uint32_t epoch[32];
  alignas(1024) float4 stats[S_];
  alignas(1024) __nv_bfloat16 h[S_ * D_];
  alignas(1024) __nv_bfloat16 ub[D_ * 4096];
  alignas(1024) __nv_bfloat16 y[D_ * S_];
  alignas(1024) __nv_bfloat16 u[D_ * F_];
};
__device__ Scratch g_scratch;

struct Hot {
  const __nv_bfloat16 *x, *k, *v, *shift_k, *ssm_k;
  Scratch* S;
};
struct Params {
  const __nv_bfloat16 *ssm_D, *b1, *b2;
  CUtensorMap m_w1, m_h, m_ust, m_w2, m_uld, m_out, m_x, m_y, m_ub;
};

#define TLREC(i) do { } while (0)
#define TLEND() do { } while (0)

__device__ __forceinline__ uint32_t smem_u32(const void* p) { return (uint32_t)__cvta_generic_to_shared(p); }
__device__ __forceinline__ void mbar_init(uint32_t bar, uint32_t cnt) { asm volatile("mbarrier.init.shared::cta.b64 [%0], %1;" :: "r"(bar), "r"(cnt) : "memory"); }
__device__ __forceinline__ void mbar_expect_tx(uint32_t bar, uint32_t bytes) { asm volatile("mbarrier.arrive.expect_tx.shared::cta.b64 _, [%0], %1;" :: "r"(bar), "r"(bytes) : "memory"); }
__device__ __forceinline__ void mbar_arrive(uint32_t bar) { asm volatile("mbarrier.arrive.shared::cta.b64 _, [%0];" :: "r"(bar) : "memory"); }
__device__ __forceinline__ uint32_t mapa(uint32_t addr, uint32_t cta) { uint32_t r; asm volatile("mapa.shared::cluster.u32 %0, %1, %2;" : "=r"(r) : "r"(addr), "r"(cta)); return r; }
__device__ __forceinline__ void mbar_arrive_remote(uint32_t rbar) { asm volatile("mbarrier.arrive.shared::cluster.b64 _, [%0];" :: "r"(rbar) : "memory"); }
__device__ __forceinline__ void mbar_wait(uint32_t bar, uint32_t parity) {
  asm volatile("{\n .reg .pred p;\n .reg .u32 c;\n mov.u32 c, 0;\n"
               "W_%=:\n mbarrier.try_wait.parity.shared::cta.b64 p, [%0], %1;\n @p bra D_%=;\n"
               " add.u32 c, c, 1;\n setp.lt.u32 p, c, 2000000;\n @p bra W_%=;\n trap;\n D_%=:\n }" :: "r"(bar), "r"(parity) : "memory");
}
__device__ __forceinline__ bool mbar_test(uint32_t bar, uint32_t parity) {
  uint32_t ok;
  asm volatile("{ .reg .pred p; mbarrier.test_wait.parity.shared::cta.b64 p, [%1], %2; selp.u32 %0, 1, 0, p; }" : "=r"(ok) : "r"(bar), "r"(parity) : "memory");
  return ok;
}
__device__ __forceinline__ void mbar_wait_cluster(uint32_t bar, uint32_t parity) {
  asm volatile("{\n .reg .pred p;\n .reg .u32 c;\n mov.u32 c, 0;\n"
               "W_%=:\n mbarrier.try_wait.parity.acquire.cluster.shared::cta.b64 p, [%0], %1;\n @p bra D_%=;\n"
               " add.u32 c, c, 1;\n setp.lt.u32 p, c, 2000000;\n @p bra W_%=;\n trap;\n D_%=:\n }" :: "r"(bar), "r"(parity) : "memory");
}
__device__ __forceinline__ void tma2d(uint32_t dst, const CUtensorMap* m, int c0, int c1, uint32_t bar) {
  asm volatile("cp.async.bulk.tensor.2d.shared::cluster.global.mbarrier::complete_tx::bytes [%0], [%1, {%3, %4}], [%2];"
               :: "r"(dst), "l"(m), "r"(bar), "r"(c0), "r"(c1) : "memory");
}
__device__ __forceinline__ void tma3d(uint32_t dst, const CUtensorMap* m, int c0, int c1, int c2, uint32_t bar) {
  asm volatile("cp.async.bulk.tensor.3d.shared::cluster.global.mbarrier::complete_tx::bytes [%0], [%1, {%3, %4, %5}], [%2];"
               :: "r"(dst), "l"(m), "r"(bar), "r"(c0), "r"(c1), "r"(c2) : "memory");
}
__device__ __forceinline__ void tma3d_ef(uint32_t dst, const CUtensorMap* m, int c0, int c1, int c2, uint32_t bar) {
  tma3d(dst, m, c0, c1, c2, bar);
}
__device__ __forceinline__ void tma2d_store(const CUtensorMap* m, uint32_t src, int c0, int c1) {
  asm volatile("cp.async.bulk.tensor.2d.global.shared::cta.bulk_group [%0, {%2, %3}], [%1];" :: "l"(m), "r"(src), "r"(c0), "r"(c1) : "memory");
}
__device__ __forceinline__ void bulk_load(uint32_t dst, const void* src, uint32_t bytes, uint32_t bar) {
  asm volatile("cp.async.bulk.shared::cluster.global.mbarrier::complete_tx::bytes [%0], [%1], %2, [%3];" :: "r"(dst), "l"(src), "r"(bytes), "r"(bar) : "memory");
}
__device__ __forceinline__ void bulk_store(void* dst, uint32_t src, uint32_t bytes) {
  asm volatile("cp.async.bulk.global.shared::cta.bulk_group [%0], [%1], %2;" :: "l"(dst), "r"(src), "r"(bytes) : "memory");
}
__device__ __forceinline__ void tma3d_store(const CUtensorMap* m, uint32_t src, int c0, int c1, int c2) {
  asm volatile("cp.async.bulk.tensor.3d.global.shared::cta.bulk_group [%0, {%2, %3, %4}], [%1];" :: "l"(m), "r"(src), "r"(c0), "r"(c1), "r"(c2) : "memory");
}
__device__ __forceinline__ void bulk_commit() { asm volatile("cp.async.bulk.commit_group;" ::: "memory"); }
__device__ __forceinline__ void bulk_wait_all() { asm volatile("cp.async.bulk.wait_group 0;" ::: "memory"); }
__device__ __forceinline__ void bulk_wait_read() { asm volatile("cp.async.bulk.wait_group.read 0;" ::: "memory"); }
__device__ __forceinline__ void fence_async_smem() { asm volatile("fence.proxy.async.shared::cta;" ::: "memory"); }
__device__ __forceinline__ void fence_async_global() { asm volatile("fence.proxy.async.global;" ::: "memory"); }
__device__ __forceinline__ void st_flag(uint32_t* p, uint32_t v) { asm volatile("st.relaxed.gpu.global.u32 [%0], %1;" :: "l"(p), "r"(v) : "memory"); }
__device__ __forceinline__ uint32_t ld_flag(const uint32_t* p) { uint32_t v; asm volatile("ld.relaxed.gpu.global.u32 %0, [%1];" : "=r"(v) : "l"(p) : "memory"); return v; }
__device__ __forceinline__ void signal(Scratch* S, int c) { asm volatile("red.release.gpu.global.add.u32 [%0], 1;" :: "l"(S->cnt + c * 32) : "memory"); }
__device__ __forceinline__ void signal_stored(Scratch* S, int c) { asm volatile("red.relaxed.gpu.global.add.u32 [%0], 1;" :: "l"(S->cnt + c * 32) : "memory"); }
__device__ __forceinline__ bool reached(Scratch* S, int c, uint32_t target) { return (int32_t)(ld_flag(S->cnt + c * 32) - target) >= 0; }
__device__ __forceinline__ uint32_t clk() { uint32_t c; asm volatile("mov.u32 %0, %%clock;" : "=r"(c)); return c; }
__device__ __forceinline__ void pace(uint32_t t0, uint32_t dt) { while (clk() - t0 < dt) { } }
__device__ __forceinline__ int cta_id() { int c; asm volatile("mov.u32 %0, %%ctaid.x;" : "=r"(c)); return c; }
template <bool SLOW = false> __device__ __forceinline__ void await(Scratch* S, int c, uint32_t target) {
  for (uint32_t n = 0; !reached(S, c, target); n++) {
    if (SLOW) __nanosleep(300);
    if (n > 4000000u) __trap();
  }
}
__device__ __forceinline__ void bar_sync(int id, int n) { asm volatile("bar.sync %0, %1;" :: "r"(id), "r"(n) : "memory"); }
__device__ __forceinline__ void bar_arrive(int id, int n) { asm volatile("bar.arrive %0, %1;" :: "r"(id), "r"(n) : "memory"); }
__device__ __forceinline__ void wg_fence() { asm volatile("wgmma.fence.sync.aligned;" ::: "memory"); }
__device__ __forceinline__ void wg_commit() { asm volatile("wgmma.commit_group.sync.aligned;" ::: "memory"); }
template <int N> __device__ __forceinline__ void wg_wait() { asm volatile("wgmma.wait_group.sync.aligned %0;" :: "n"(N) : "memory"); }
template <int N> __device__ __forceinline__ void pin_regs(float* a) {
#pragma unroll
  for (int i = 0; i < N; i++) asm volatile("" : "+f"(a[i]) :: "memory");
}
__device__ __forceinline__ uint64_t make_desc(uint32_t addr, uint32_t lbo, uint32_t sbo, uint32_t swz) {
  return (uint64_t)((addr & 0x3FFFF) >> 4) | ((uint64_t)(lbo >> 4) << 16) | ((uint64_t)(sbo >> 4) << 32) | ((uint64_t)swz << 62);
}
__device__ __forceinline__ uint32_t pack_bf16(float lo, float hi) { uint32_t r; asm("cvt.rn.bf16x2.f32 %0, %1, %2;" : "=r"(r) : "f"(hi), "f"(lo)); return r; }
__device__ __forceinline__ float bf_lo(uint32_t p) { return __uint_as_float(p << 16); }
__device__ __forceinline__ float bf_hi(uint32_t p) { return __uint_as_float(p & 0xffff0000u); }
__device__ __forceinline__ float round_bf16(float v) { return bf_lo(pack_bf16(v, 0.f)); }
__device__ __forceinline__ uint32_t bmul2(uint32_t a, uint32_t b) { uint32_t r; asm("mul.rn.bf16x2 %0, %1, %2;" : "=r"(r) : "r"(a), "r"(b)); return r; }
__device__ __forceinline__ uint32_t badd2(uint32_t a, uint32_t b) { uint32_t r; asm("add.rn.bf16x2 %0, %1, %2;" : "=r"(r) : "r"(a), "r"(b)); return r; }
__device__ __forceinline__ uint32_t bfma2(uint32_t a, uint32_t b, uint32_t c) { uint32_t r; asm("fma.rn.bf16x2 %0, %1, %2, %3;" : "=r"(r) : "r"(a), "r"(b), "r"(c)); return r; }
__device__ __forceinline__ uint32_t bsub2(uint32_t a, uint32_t b) { uint32_t r; asm("sub.rn.bf16x2 %0, %1, %2;" : "=r"(r) : "r"(a), "r"(b)); return r; }
__device__ __forceinline__ float tanh_fast(float v) { float r; asm("tanh.approx.f32 %0, %1;" : "=f"(r) : "f"(v)); return r; }
__device__ __forceinline__ float gelu_half(float h) {
  return fmaf(h, tanh_fast(h * fmaf(h * h, 8.0f * 0.7978845608028654f * 0.044715f, 2.0f * 0.7978845608028654f)), h);
}
__device__ __forceinline__ float silu_half(float h) { return fmaf(h, tanh_fast(h), h); }
__device__ __forceinline__ uint32_t ldg32(const void* p) { uint32_t v; asm volatile("ld.global.nc.u32 %0, [%1];" : "=r"(v) : "l"(p)); return v; }
__device__ __forceinline__ uint32_t lds32(uint32_t a) { uint32_t v; asm volatile("ld.shared.u32 %0, [%1];" : "=r"(v) : "r"(a) : "memory"); return v; }
__device__ __forceinline__ float4 lds128f(uint32_t a) { float4 v; asm volatile("ld.shared.v4.f32 {%0,%1,%2,%3}, [%4];" : "=f"(v.x), "=f"(v.y), "=f"(v.z), "=f"(v.w) : "r"(a) : "memory"); return v; }
__device__ __forceinline__ uint4 lds128(uint32_t a) { uint4 v; asm volatile("ld.shared.v4.u32 {%0,%1,%2,%3}, [%4];" : "=r"(v.x), "=r"(v.y), "=r"(v.z), "=r"(v.w) : "r"(a) : "memory"); return v; }
__device__ __forceinline__ void sts64(uint32_t a, uint32_t x, uint32_t y) { asm volatile("st.shared.v2.u32 [%0], {%1,%2};" :: "r"(a), "r"(x), "r"(y) : "memory"); }
__device__ __forceinline__ void sts128(uint32_t a, uint32_t x, uint32_t y, uint32_t z, uint32_t w) {
  asm volatile("st.shared.v4.u32 [%0], {%1,%2,%3,%4};" :: "r"(a), "r"(x), "r"(y), "r"(z), "r"(w) : "memory");
}
__device__ __forceinline__ void sts32(uint32_t a, uint32_t v) { asm volatile("st.shared.u32 [%0], %1;" :: "r"(a), "r"(v) : "memory"); }
__device__ __forceinline__ void ldsm4(uint32_t* r, uint32_t a) {
  asm volatile("ldmatrix.sync.aligned.m8n8.x4.shared.b16 {%0,%1,%2,%3}, [%4];" : "=r"(r[0]), "=r"(r[1]), "=r"(r[2]), "=r"(r[3]) : "r"(a) : "memory");
}
__device__ __forceinline__ void ldsm2(uint32_t* r, uint32_t a) {
  asm volatile("ldmatrix.sync.aligned.m8n8.x2.shared.b16 {%0,%1}, [%2];" : "=r"(r[0]), "=r"(r[1]) : "r"(a) : "memory");
}
__device__ __forceinline__ void ldsm4t(uint32_t* r, uint32_t a) {
  asm volatile("ldmatrix.sync.aligned.m8n8.x4.trans.shared.b16 {%0,%1,%2,%3}, [%4];" : "=r"(r[0]), "=r"(r[1]), "=r"(r[2]), "=r"(r[3]) : "r"(a) : "memory");
}
__device__ __forceinline__ void ldsm2t(uint32_t* r, uint32_t a) {
  asm volatile("ldmatrix.sync.aligned.m8n8.x2.trans.shared.b16 {%0,%1}, [%2];" : "=r"(r[0]), "=r"(r[1]) : "r"(a) : "memory");
}
__device__ __forceinline__ void stsm4(uint32_t a, uint32_t r0, uint32_t r1, uint32_t r2, uint32_t r3) {
  asm volatile("stmatrix.sync.aligned.m8n8.x4.shared.b16 [%0], {%1,%2,%3,%4};" :: "r"(a), "r"(r0), "r"(r1), "r"(r2), "r"(r3) : "memory");
}
__device__ __forceinline__ void stsm2(uint32_t a, uint32_t r0, uint32_t r1) {
  asm volatile("stmatrix.sync.aligned.m8n8.x2.shared.b16 [%0], {%1,%2};" :: "r"(a), "r"(r0), "r"(r1) : "memory");
}
__device__ __forceinline__ void stsm4t(uint32_t a, uint32_t r0, uint32_t r1, uint32_t r2, uint32_t r3) {
  asm volatile("stmatrix.sync.aligned.m8n8.x4.trans.shared.b16 [%0], {%1,%2,%3,%4};" :: "r"(a), "r"(r0), "r"(r1), "r"(r2), "r"(r3) : "memory");
}

__device__ __forceinline__ void wgmma_ss_n144_t10(float* d, uint64_t da, uint64_t db, int sd) {
  asm volatile("{ .reg .pred p; setp.ne.b32 p, %74, 0;\n"
      "wgmma.mma_async.sync.aligned.m64n144k16.f32.bf16.bf16 {"
      "%0,%1,%2,%3,%4,%5,%6,%7,%8,%9,%10,%11,%12,%13,%14,%15,"
      "%16,%17,%18,%19,%20,%21,%22,%23,%24,%25,%26,%27,%28,%29,%30,%31,"
      "%32,%33,%34,%35,%36,%37,%38,%39,%40,%41,%42,%43,%44,%45,%46,%47,"
      "%48,%49,%50,%51,%52,%53,%54,%55,%56,%57,%58,%59,%60,%61,%62,%63,"
      "%64,%65,%66,%67,%68,%69,%70,%71"
      "}, %72, %73, p, 1, 1, 1, 0; }"
    : "+f"(d[0]), "+f"(d[1]), "+f"(d[2]), "+f"(d[3]), "+f"(d[4]), "+f"(d[5]), "+f"(d[6]), "+f"(d[7]),
      "+f"(d[8]), "+f"(d[9]), "+f"(d[10]), "+f"(d[11]), "+f"(d[12]), "+f"(d[13]), "+f"(d[14]), "+f"(d[15]),
      "+f"(d[16]), "+f"(d[17]), "+f"(d[18]), "+f"(d[19]), "+f"(d[20]), "+f"(d[21]), "+f"(d[22]), "+f"(d[23]),
      "+f"(d[24]), "+f"(d[25]), "+f"(d[26]), "+f"(d[27]), "+f"(d[28]), "+f"(d[29]), "+f"(d[30]), "+f"(d[31]),
      "+f"(d[32]), "+f"(d[33]), "+f"(d[34]), "+f"(d[35]), "+f"(d[36]), "+f"(d[37]), "+f"(d[38]), "+f"(d[39]),
      "+f"(d[40]), "+f"(d[41]), "+f"(d[42]), "+f"(d[43]), "+f"(d[44]), "+f"(d[45]), "+f"(d[46]), "+f"(d[47]),
      "+f"(d[48]), "+f"(d[49]), "+f"(d[50]), "+f"(d[51]), "+f"(d[52]), "+f"(d[53]), "+f"(d[54]), "+f"(d[55]),
      "+f"(d[56]), "+f"(d[57]), "+f"(d[58]), "+f"(d[59]), "+f"(d[60]), "+f"(d[61]), "+f"(d[62]), "+f"(d[63]),
      "+f"(d[64]), "+f"(d[65]), "+f"(d[66]), "+f"(d[67]), "+f"(d[68]), "+f"(d[69]), "+f"(d[70]), "+f"(d[71])
    : "l"(da), "l"(db), "r"(sd));
}

__device__ __forceinline__ void wgmma_ss_n192_t11(float* d, uint64_t da, uint64_t db, int sd) {
  asm volatile("{ .reg .pred p; setp.ne.b32 p, %98, 0;\n"
      "wgmma.mma_async.sync.aligned.m64n192k16.f32.bf16.bf16 {"
      "%0,%1,%2,%3,%4,%5,%6,%7,%8,%9,%10,%11,%12,%13,%14,%15,"
      "%16,%17,%18,%19,%20,%21,%22,%23,%24,%25,%26,%27,%28,%29,%30,%31,"
      "%32,%33,%34,%35,%36,%37,%38,%39,%40,%41,%42,%43,%44,%45,%46,%47,"
      "%48,%49,%50,%51,%52,%53,%54,%55,%56,%57,%58,%59,%60,%61,%62,%63,"
      "%64,%65,%66,%67,%68,%69,%70,%71,%72,%73,%74,%75,%76,%77,%78,%79,"
      "%80,%81,%82,%83,%84,%85,%86,%87,%88,%89,%90,%91,%92,%93,%94,%95"
      "}, %96, %97, p, 1, 1, 1, 1; }"
    : "+f"(d[0]), "+f"(d[1]), "+f"(d[2]), "+f"(d[3]), "+f"(d[4]), "+f"(d[5]), "+f"(d[6]), "+f"(d[7]),
      "+f"(d[8]), "+f"(d[9]), "+f"(d[10]), "+f"(d[11]), "+f"(d[12]), "+f"(d[13]), "+f"(d[14]), "+f"(d[15]),
      "+f"(d[16]), "+f"(d[17]), "+f"(d[18]), "+f"(d[19]), "+f"(d[20]), "+f"(d[21]), "+f"(d[22]), "+f"(d[23]),
      "+f"(d[24]), "+f"(d[25]), "+f"(d[26]), "+f"(d[27]), "+f"(d[28]), "+f"(d[29]), "+f"(d[30]), "+f"(d[31]),
      "+f"(d[32]), "+f"(d[33]), "+f"(d[34]), "+f"(d[35]), "+f"(d[36]), "+f"(d[37]), "+f"(d[38]), "+f"(d[39]),
      "+f"(d[40]), "+f"(d[41]), "+f"(d[42]), "+f"(d[43]), "+f"(d[44]), "+f"(d[45]), "+f"(d[46]), "+f"(d[47]),
      "+f"(d[48]), "+f"(d[49]), "+f"(d[50]), "+f"(d[51]), "+f"(d[52]), "+f"(d[53]), "+f"(d[54]), "+f"(d[55]),
      "+f"(d[56]), "+f"(d[57]), "+f"(d[58]), "+f"(d[59]), "+f"(d[60]), "+f"(d[61]), "+f"(d[62]), "+f"(d[63]),
      "+f"(d[64]), "+f"(d[65]), "+f"(d[66]), "+f"(d[67]), "+f"(d[68]), "+f"(d[69]), "+f"(d[70]), "+f"(d[71]),
      "+f"(d[72]), "+f"(d[73]), "+f"(d[74]), "+f"(d[75]), "+f"(d[76]), "+f"(d[77]), "+f"(d[78]), "+f"(d[79]),
      "+f"(d[80]), "+f"(d[81]), "+f"(d[82]), "+f"(d[83]), "+f"(d[84]), "+f"(d[85]), "+f"(d[86]), "+f"(d[87]),
      "+f"(d[88]), "+f"(d[89]), "+f"(d[90]), "+f"(d[91]), "+f"(d[92]), "+f"(d[93]), "+f"(d[94]), "+f"(d[95])
    : "l"(da), "l"(db), "r"(sd));
}

__device__ __forceinline__ void wgmma_ss_n72_t10(float* d, uint64_t da, uint64_t db, int sd) {
  asm volatile("{ .reg .pred p; setp.ne.b32 p, %38, 0;\n"
      "wgmma.mma_async.sync.aligned.m64n72k16.f32.bf16.bf16 {"
      "%0,%1,%2,%3,%4,%5,%6,%7,%8,%9,%10,%11,%12,%13,%14,%15,"
      "%16,%17,%18,%19,%20,%21,%22,%23,%24,%25,%26,%27,%28,%29,%30,%31,"
      "%32,%33,%34,%35"
      "}, %36, %37, p, 1, 1, 1, 0; }"
    : "+f"(d[0]), "+f"(d[1]), "+f"(d[2]), "+f"(d[3]), "+f"(d[4]), "+f"(d[5]), "+f"(d[6]), "+f"(d[7]),
      "+f"(d[8]), "+f"(d[9]), "+f"(d[10]), "+f"(d[11]), "+f"(d[12]), "+f"(d[13]), "+f"(d[14]), "+f"(d[15]),
      "+f"(d[16]), "+f"(d[17]), "+f"(d[18]), "+f"(d[19]), "+f"(d[20]), "+f"(d[21]), "+f"(d[22]), "+f"(d[23]),
      "+f"(d[24]), "+f"(d[25]), "+f"(d[26]), "+f"(d[27]), "+f"(d[28]), "+f"(d[29]), "+f"(d[30]), "+f"(d[31]),
      "+f"(d[32]), "+f"(d[33]), "+f"(d[34]), "+f"(d[35])
    : "l"(da), "l"(db), "r"(sd));
}

__device__ __forceinline__ void wgmma_rs_n16(float* d, const uint32_t* a, uint64_t db, int sd) {
  asm volatile("{ .reg .pred p; setp.ne.b32 p, %13, 0;\n"
      "wgmma.mma_async.sync.aligned.m64n16k16.f32.bf16.bf16 {"
      "%0,%1,%2,%3,%4,%5,%6,%7"
      "}, {%8,%9,%10,%11}, %12, p, 1, 1, 0; }"
    : "+f"(d[0]), "+f"(d[1]), "+f"(d[2]), "+f"(d[3]), "+f"(d[4]), "+f"(d[5]), "+f"(d[6]), "+f"(d[7])
    : "r"(a[0]), "r"(a[1]), "r"(a[2]), "r"(a[3]), "l"(db), "r"(sd));
}

__device__ __forceinline__ void wgmma_rs_n32(float* d, const uint32_t* a, uint64_t db, int sd) {
  asm volatile("{ .reg .pred p; setp.ne.b32 p, %21, 0;\n"
      "wgmma.mma_async.sync.aligned.m64n32k16.f32.bf16.bf16 {"
      "%0,%1,%2,%3,%4,%5,%6,%7,%8,%9,%10,%11,%12,%13,%14,%15"
      "}, {%16,%17,%18,%19}, %20, p, 1, 1, 0; }"
    : "+f"(d[0]), "+f"(d[1]), "+f"(d[2]), "+f"(d[3]), "+f"(d[4]), "+f"(d[5]), "+f"(d[6]), "+f"(d[7]),
      "+f"(d[8]), "+f"(d[9]), "+f"(d[10]), "+f"(d[11]), "+f"(d[12]), "+f"(d[13]), "+f"(d[14]), "+f"(d[15])
    : "r"(a[0]), "r"(a[1]), "r"(a[2]), "r"(a[3]), "l"(db), "r"(sd));
}

__device__ __forceinline__ void wgmma_rs_n48(float* d, const uint32_t* a, uint64_t db, int sd) {
  asm volatile("{ .reg .pred p; setp.ne.b32 p, %29, 0;\n"
      "wgmma.mma_async.sync.aligned.m64n48k16.f32.bf16.bf16 {"
      "%0,%1,%2,%3,%4,%5,%6,%7,%8,%9,%10,%11,%12,%13,%14,%15,"
      "%16,%17,%18,%19,%20,%21,%22,%23"
      "}, {%24,%25,%26,%27}, %28, p, 1, 1, 0; }"
    : "+f"(d[0]), "+f"(d[1]), "+f"(d[2]), "+f"(d[3]), "+f"(d[4]), "+f"(d[5]), "+f"(d[6]), "+f"(d[7]),
      "+f"(d[8]), "+f"(d[9]), "+f"(d[10]), "+f"(d[11]), "+f"(d[12]), "+f"(d[13]), "+f"(d[14]), "+f"(d[15]),
      "+f"(d[16]), "+f"(d[17]), "+f"(d[18]), "+f"(d[19]), "+f"(d[20]), "+f"(d[21]), "+f"(d[22]), "+f"(d[23])
    : "r"(a[0]), "r"(a[1]), "r"(a[2]), "r"(a[3]), "l"(db), "r"(sd));
}

__device__ __forceinline__ void wgmma_rs_n64(float* d, const uint32_t* a, uint64_t db, int sd) {
  asm volatile("{ .reg .pred p; setp.ne.b32 p, %37, 0;\n"
      "wgmma.mma_async.sync.aligned.m64n64k16.f32.bf16.bf16 {"
      "%0,%1,%2,%3,%4,%5,%6,%7,%8,%9,%10,%11,%12,%13,%14,%15,"
      "%16,%17,%18,%19,%20,%21,%22,%23,%24,%25,%26,%27,%28,%29,%30,%31"
      "}, {%32,%33,%34,%35}, %36, p, 1, 1, 0; }"
    : "+f"(d[0]), "+f"(d[1]), "+f"(d[2]), "+f"(d[3]), "+f"(d[4]), "+f"(d[5]), "+f"(d[6]), "+f"(d[7]),
      "+f"(d[8]), "+f"(d[9]), "+f"(d[10]), "+f"(d[11]), "+f"(d[12]), "+f"(d[13]), "+f"(d[14]), "+f"(d[15]),
      "+f"(d[16]), "+f"(d[17]), "+f"(d[18]), "+f"(d[19]), "+f"(d[20]), "+f"(d[21]), "+f"(d[22]), "+f"(d[23]),
      "+f"(d[24]), "+f"(d[25]), "+f"(d[26]), "+f"(d[27]), "+f"(d[28]), "+f"(d[29]), "+f"(d[30]), "+f"(d[31])
    : "r"(a[0]), "r"(a[1]), "r"(a[2]), "r"(a[3]), "l"(db), "r"(sd));
}

__device__ __forceinline__ void wgmma_rs_n80(float* d, const uint32_t* a, uint64_t db, int sd) {
  asm volatile("{ .reg .pred p; setp.ne.b32 p, %45, 0;\n"
      "wgmma.mma_async.sync.aligned.m64n80k16.f32.bf16.bf16 {"
      "%0,%1,%2,%3,%4,%5,%6,%7,%8,%9,%10,%11,%12,%13,%14,%15,"
      "%16,%17,%18,%19,%20,%21,%22,%23,%24,%25,%26,%27,%28,%29,%30,%31,"
      "%32,%33,%34,%35,%36,%37,%38,%39"
      "}, {%40,%41,%42,%43}, %44, p, 1, 1, 0; }"
    : "+f"(d[0]), "+f"(d[1]), "+f"(d[2]), "+f"(d[3]), "+f"(d[4]), "+f"(d[5]), "+f"(d[6]), "+f"(d[7]),
      "+f"(d[8]), "+f"(d[9]), "+f"(d[10]), "+f"(d[11]), "+f"(d[12]), "+f"(d[13]), "+f"(d[14]), "+f"(d[15]),
      "+f"(d[16]), "+f"(d[17]), "+f"(d[18]), "+f"(d[19]), "+f"(d[20]), "+f"(d[21]), "+f"(d[22]), "+f"(d[23]),
      "+f"(d[24]), "+f"(d[25]), "+f"(d[26]), "+f"(d[27]), "+f"(d[28]), "+f"(d[29]), "+f"(d[30]), "+f"(d[31]),
      "+f"(d[32]), "+f"(d[33]), "+f"(d[34]), "+f"(d[35]), "+f"(d[36]), "+f"(d[37]), "+f"(d[38]), "+f"(d[39])
    : "r"(a[0]), "r"(a[1]), "r"(a[2]), "r"(a[3]), "l"(db), "r"(sd));
}

__device__ __forceinline__ void wgmma_rs_n96(float* d, const uint32_t* a, uint64_t db, int sd) {
  asm volatile("{ .reg .pred p; setp.ne.b32 p, %53, 0;\n"
      "wgmma.mma_async.sync.aligned.m64n96k16.f32.bf16.bf16 {"
      "%0,%1,%2,%3,%4,%5,%6,%7,%8,%9,%10,%11,%12,%13,%14,%15,"
      "%16,%17,%18,%19,%20,%21,%22,%23,%24,%25,%26,%27,%28,%29,%30,%31,"
      "%32,%33,%34,%35,%36,%37,%38,%39,%40,%41,%42,%43,%44,%45,%46,%47"
      "}, {%48,%49,%50,%51}, %52, p, 1, 1, 0; }"
    : "+f"(d[0]), "+f"(d[1]), "+f"(d[2]), "+f"(d[3]), "+f"(d[4]), "+f"(d[5]), "+f"(d[6]), "+f"(d[7]),
      "+f"(d[8]), "+f"(d[9]), "+f"(d[10]), "+f"(d[11]), "+f"(d[12]), "+f"(d[13]), "+f"(d[14]), "+f"(d[15]),
      "+f"(d[16]), "+f"(d[17]), "+f"(d[18]), "+f"(d[19]), "+f"(d[20]), "+f"(d[21]), "+f"(d[22]), "+f"(d[23]),
      "+f"(d[24]), "+f"(d[25]), "+f"(d[26]), "+f"(d[27]), "+f"(d[28]), "+f"(d[29]), "+f"(d[30]), "+f"(d[31]),
      "+f"(d[32]), "+f"(d[33]), "+f"(d[34]), "+f"(d[35]), "+f"(d[36]), "+f"(d[37]), "+f"(d[38]), "+f"(d[39]),
      "+f"(d[40]), "+f"(d[41]), "+f"(d[42]), "+f"(d[43]), "+f"(d[44]), "+f"(d[45]), "+f"(d[46]), "+f"(d[47])
    : "r"(a[0]), "r"(a[1]), "r"(a[2]), "r"(a[3]), "l"(db), "r"(sd));
}

__device__ __forceinline__ void wgmma_rs_n112(float* d, const uint32_t* a, uint64_t db, int sd) {
  asm volatile("{ .reg .pred p; setp.ne.b32 p, %61, 0;\n"
      "wgmma.mma_async.sync.aligned.m64n112k16.f32.bf16.bf16 {"
      "%0,%1,%2,%3,%4,%5,%6,%7,%8,%9,%10,%11,%12,%13,%14,%15,"
      "%16,%17,%18,%19,%20,%21,%22,%23,%24,%25,%26,%27,%28,%29,%30,%31,"
      "%32,%33,%34,%35,%36,%37,%38,%39,%40,%41,%42,%43,%44,%45,%46,%47,"
      "%48,%49,%50,%51,%52,%53,%54,%55"
      "}, {%56,%57,%58,%59}, %60, p, 1, 1, 0; }"
    : "+f"(d[0]), "+f"(d[1]), "+f"(d[2]), "+f"(d[3]), "+f"(d[4]), "+f"(d[5]), "+f"(d[6]), "+f"(d[7]),
      "+f"(d[8]), "+f"(d[9]), "+f"(d[10]), "+f"(d[11]), "+f"(d[12]), "+f"(d[13]), "+f"(d[14]), "+f"(d[15]),
      "+f"(d[16]), "+f"(d[17]), "+f"(d[18]), "+f"(d[19]), "+f"(d[20]), "+f"(d[21]), "+f"(d[22]), "+f"(d[23]),
      "+f"(d[24]), "+f"(d[25]), "+f"(d[26]), "+f"(d[27]), "+f"(d[28]), "+f"(d[29]), "+f"(d[30]), "+f"(d[31]),
      "+f"(d[32]), "+f"(d[33]), "+f"(d[34]), "+f"(d[35]), "+f"(d[36]), "+f"(d[37]), "+f"(d[38]), "+f"(d[39]),
      "+f"(d[40]), "+f"(d[41]), "+f"(d[42]), "+f"(d[43]), "+f"(d[44]), "+f"(d[45]), "+f"(d[46]), "+f"(d[47]),
      "+f"(d[48]), "+f"(d[49]), "+f"(d[50]), "+f"(d[51]), "+f"(d[52]), "+f"(d[53]), "+f"(d[54]), "+f"(d[55])
    : "r"(a[0]), "r"(a[1]), "r"(a[2]), "r"(a[3]), "l"(db), "r"(sd));
}

__device__ __forceinline__ void wgmma_rs_n128(float* d, const uint32_t* a, uint64_t db, int sd) {
  asm volatile("{ .reg .pred p; setp.ne.b32 p, %69, 0;\n"
      "wgmma.mma_async.sync.aligned.m64n128k16.f32.bf16.bf16 {"
      "%0,%1,%2,%3,%4,%5,%6,%7,%8,%9,%10,%11,%12,%13,%14,%15,"
      "%16,%17,%18,%19,%20,%21,%22,%23,%24,%25,%26,%27,%28,%29,%30,%31,"
      "%32,%33,%34,%35,%36,%37,%38,%39,%40,%41,%42,%43,%44,%45,%46,%47,"
      "%48,%49,%50,%51,%52,%53,%54,%55,%56,%57,%58,%59,%60,%61,%62,%63"
      "}, {%64,%65,%66,%67}, %68, p, 1, 1, 0; }"
    : "+f"(d[0]), "+f"(d[1]), "+f"(d[2]), "+f"(d[3]), "+f"(d[4]), "+f"(d[5]), "+f"(d[6]), "+f"(d[7]),
      "+f"(d[8]), "+f"(d[9]), "+f"(d[10]), "+f"(d[11]), "+f"(d[12]), "+f"(d[13]), "+f"(d[14]), "+f"(d[15]),
      "+f"(d[16]), "+f"(d[17]), "+f"(d[18]), "+f"(d[19]), "+f"(d[20]), "+f"(d[21]), "+f"(d[22]), "+f"(d[23]),
      "+f"(d[24]), "+f"(d[25]), "+f"(d[26]), "+f"(d[27]), "+f"(d[28]), "+f"(d[29]), "+f"(d[30]), "+f"(d[31]),
      "+f"(d[32]), "+f"(d[33]), "+f"(d[34]), "+f"(d[35]), "+f"(d[36]), "+f"(d[37]), "+f"(d[38]), "+f"(d[39]),
      "+f"(d[40]), "+f"(d[41]), "+f"(d[42]), "+f"(d[43]), "+f"(d[44]), "+f"(d[45]), "+f"(d[46]), "+f"(d[47]),
      "+f"(d[48]), "+f"(d[49]), "+f"(d[50]), "+f"(d[51]), "+f"(d[52]), "+f"(d[53]), "+f"(d[54]), "+f"(d[55]),
      "+f"(d[56]), "+f"(d[57]), "+f"(d[58]), "+f"(d[59]), "+f"(d[60]), "+f"(d[61]), "+f"(d[62]), "+f"(d[63])
    : "r"(a[0]), "r"(a[1]), "r"(a[2]), "r"(a[3]), "l"(db), "r"(sd));
}

__device__ __forceinline__ void wgmma_rs_n144(float* d, const uint32_t* a, uint64_t db, int sd) {
  asm volatile("{ .reg .pred p; setp.ne.b32 p, %77, 0;\n"
      "wgmma.mma_async.sync.aligned.m64n144k16.f32.bf16.bf16 {"
      "%0,%1,%2,%3,%4,%5,%6,%7,%8,%9,%10,%11,%12,%13,%14,%15,"
      "%16,%17,%18,%19,%20,%21,%22,%23,%24,%25,%26,%27,%28,%29,%30,%31,"
      "%32,%33,%34,%35,%36,%37,%38,%39,%40,%41,%42,%43,%44,%45,%46,%47,"
      "%48,%49,%50,%51,%52,%53,%54,%55,%56,%57,%58,%59,%60,%61,%62,%63,"
      "%64,%65,%66,%67,%68,%69,%70,%71"
      "}, {%72,%73,%74,%75}, %76, p, 1, 1, 0; }"
    : "+f"(d[0]), "+f"(d[1]), "+f"(d[2]), "+f"(d[3]), "+f"(d[4]), "+f"(d[5]), "+f"(d[6]), "+f"(d[7]),
      "+f"(d[8]), "+f"(d[9]), "+f"(d[10]), "+f"(d[11]), "+f"(d[12]), "+f"(d[13]), "+f"(d[14]), "+f"(d[15]),
      "+f"(d[16]), "+f"(d[17]), "+f"(d[18]), "+f"(d[19]), "+f"(d[20]), "+f"(d[21]), "+f"(d[22]), "+f"(d[23]),
      "+f"(d[24]), "+f"(d[25]), "+f"(d[26]), "+f"(d[27]), "+f"(d[28]), "+f"(d[29]), "+f"(d[30]), "+f"(d[31]),
      "+f"(d[32]), "+f"(d[33]), "+f"(d[34]), "+f"(d[35]), "+f"(d[36]), "+f"(d[37]), "+f"(d[38]), "+f"(d[39]),
      "+f"(d[40]), "+f"(d[41]), "+f"(d[42]), "+f"(d[43]), "+f"(d[44]), "+f"(d[45]), "+f"(d[46]), "+f"(d[47]),
      "+f"(d[48]), "+f"(d[49]), "+f"(d[50]), "+f"(d[51]), "+f"(d[52]), "+f"(d[53]), "+f"(d[54]), "+f"(d[55]),
      "+f"(d[56]), "+f"(d[57]), "+f"(d[58]), "+f"(d[59]), "+f"(d[60]), "+f"(d[61]), "+f"(d[62]), "+f"(d[63]),
      "+f"(d[64]), "+f"(d[65]), "+f"(d[66]), "+f"(d[67]), "+f"(d[68]), "+f"(d[69]), "+f"(d[70]), "+f"(d[71])
    : "r"(a[0]), "r"(a[1]), "r"(a[2]), "r"(a[3]), "l"(db), "r"(sd));
}

__device__ __forceinline__ void wgmma_rs_n160(float* d, const uint32_t* a, uint64_t db, int sd) {
  asm volatile("{ .reg .pred p; setp.ne.b32 p, %85, 0;\n"
      "wgmma.mma_async.sync.aligned.m64n160k16.f32.bf16.bf16 {"
      "%0,%1,%2,%3,%4,%5,%6,%7,%8,%9,%10,%11,%12,%13,%14,%15,"
      "%16,%17,%18,%19,%20,%21,%22,%23,%24,%25,%26,%27,%28,%29,%30,%31,"
      "%32,%33,%34,%35,%36,%37,%38,%39,%40,%41,%42,%43,%44,%45,%46,%47,"
      "%48,%49,%50,%51,%52,%53,%54,%55,%56,%57,%58,%59,%60,%61,%62,%63,"
      "%64,%65,%66,%67,%68,%69,%70,%71,%72,%73,%74,%75,%76,%77,%78,%79"
      "}, {%80,%81,%82,%83}, %84, p, 1, 1, 0; }"
    : "+f"(d[0]), "+f"(d[1]), "+f"(d[2]), "+f"(d[3]), "+f"(d[4]), "+f"(d[5]), "+f"(d[6]), "+f"(d[7]),
      "+f"(d[8]), "+f"(d[9]), "+f"(d[10]), "+f"(d[11]), "+f"(d[12]), "+f"(d[13]), "+f"(d[14]), "+f"(d[15]),
      "+f"(d[16]), "+f"(d[17]), "+f"(d[18]), "+f"(d[19]), "+f"(d[20]), "+f"(d[21]), "+f"(d[22]), "+f"(d[23]),
      "+f"(d[24]), "+f"(d[25]), "+f"(d[26]), "+f"(d[27]), "+f"(d[28]), "+f"(d[29]), "+f"(d[30]), "+f"(d[31]),
      "+f"(d[32]), "+f"(d[33]), "+f"(d[34]), "+f"(d[35]), "+f"(d[36]), "+f"(d[37]), "+f"(d[38]), "+f"(d[39]),
      "+f"(d[40]), "+f"(d[41]), "+f"(d[42]), "+f"(d[43]), "+f"(d[44]), "+f"(d[45]), "+f"(d[46]), "+f"(d[47]),
      "+f"(d[48]), "+f"(d[49]), "+f"(d[50]), "+f"(d[51]), "+f"(d[52]), "+f"(d[53]), "+f"(d[54]), "+f"(d[55]),
      "+f"(d[56]), "+f"(d[57]), "+f"(d[58]), "+f"(d[59]), "+f"(d[60]), "+f"(d[61]), "+f"(d[62]), "+f"(d[63]),
      "+f"(d[64]), "+f"(d[65]), "+f"(d[66]), "+f"(d[67]), "+f"(d[68]), "+f"(d[69]), "+f"(d[70]), "+f"(d[71]),
      "+f"(d[72]), "+f"(d[73]), "+f"(d[74]), "+f"(d[75]), "+f"(d[76]), "+f"(d[77]), "+f"(d[78]), "+f"(d[79])
    : "r"(a[0]), "r"(a[1]), "r"(a[2]), "r"(a[3]), "l"(db), "r"(sd));
}

__device__ __forceinline__ void wgmma_rs_n176(float* d, const uint32_t* a, uint64_t db, int sd) {
  asm volatile("{ .reg .pred p; setp.ne.b32 p, %93, 0;\n"
      "wgmma.mma_async.sync.aligned.m64n176k16.f32.bf16.bf16 {"
      "%0,%1,%2,%3,%4,%5,%6,%7,%8,%9,%10,%11,%12,%13,%14,%15,"
      "%16,%17,%18,%19,%20,%21,%22,%23,%24,%25,%26,%27,%28,%29,%30,%31,"
      "%32,%33,%34,%35,%36,%37,%38,%39,%40,%41,%42,%43,%44,%45,%46,%47,"
      "%48,%49,%50,%51,%52,%53,%54,%55,%56,%57,%58,%59,%60,%61,%62,%63,"
      "%64,%65,%66,%67,%68,%69,%70,%71,%72,%73,%74,%75,%76,%77,%78,%79,"
      "%80,%81,%82,%83,%84,%85,%86,%87"
      "}, {%88,%89,%90,%91}, %92, p, 1, 1, 0; }"
    : "+f"(d[0]), "+f"(d[1]), "+f"(d[2]), "+f"(d[3]), "+f"(d[4]), "+f"(d[5]), "+f"(d[6]), "+f"(d[7]),
      "+f"(d[8]), "+f"(d[9]), "+f"(d[10]), "+f"(d[11]), "+f"(d[12]), "+f"(d[13]), "+f"(d[14]), "+f"(d[15]),
      "+f"(d[16]), "+f"(d[17]), "+f"(d[18]), "+f"(d[19]), "+f"(d[20]), "+f"(d[21]), "+f"(d[22]), "+f"(d[23]),
      "+f"(d[24]), "+f"(d[25]), "+f"(d[26]), "+f"(d[27]), "+f"(d[28]), "+f"(d[29]), "+f"(d[30]), "+f"(d[31]),
      "+f"(d[32]), "+f"(d[33]), "+f"(d[34]), "+f"(d[35]), "+f"(d[36]), "+f"(d[37]), "+f"(d[38]), "+f"(d[39]),
      "+f"(d[40]), "+f"(d[41]), "+f"(d[42]), "+f"(d[43]), "+f"(d[44]), "+f"(d[45]), "+f"(d[46]), "+f"(d[47]),
      "+f"(d[48]), "+f"(d[49]), "+f"(d[50]), "+f"(d[51]), "+f"(d[52]), "+f"(d[53]), "+f"(d[54]), "+f"(d[55]),
      "+f"(d[56]), "+f"(d[57]), "+f"(d[58]), "+f"(d[59]), "+f"(d[60]), "+f"(d[61]), "+f"(d[62]), "+f"(d[63]),
      "+f"(d[64]), "+f"(d[65]), "+f"(d[66]), "+f"(d[67]), "+f"(d[68]), "+f"(d[69]), "+f"(d[70]), "+f"(d[71]),
      "+f"(d[72]), "+f"(d[73]), "+f"(d[74]), "+f"(d[75]), "+f"(d[76]), "+f"(d[77]), "+f"(d[78]), "+f"(d[79]),
      "+f"(d[80]), "+f"(d[81]), "+f"(d[82]), "+f"(d[83]), "+f"(d[84]), "+f"(d[85]), "+f"(d[86]), "+f"(d[87])
    : "r"(a[0]), "r"(a[1]), "r"(a[2]), "r"(a[3]), "l"(db), "r"(sd));
}

__device__ __forceinline__ void wgmma_rs_n192(float* d, const uint32_t* a, uint64_t db, int sd) {
  asm volatile("{ .reg .pred p; setp.ne.b32 p, %101, 0;\n"
      "wgmma.mma_async.sync.aligned.m64n192k16.f32.bf16.bf16 {"
      "%0,%1,%2,%3,%4,%5,%6,%7,%8,%9,%10,%11,%12,%13,%14,%15,"
      "%16,%17,%18,%19,%20,%21,%22,%23,%24,%25,%26,%27,%28,%29,%30,%31,"
      "%32,%33,%34,%35,%36,%37,%38,%39,%40,%41,%42,%43,%44,%45,%46,%47,"
      "%48,%49,%50,%51,%52,%53,%54,%55,%56,%57,%58,%59,%60,%61,%62,%63,"
      "%64,%65,%66,%67,%68,%69,%70,%71,%72,%73,%74,%75,%76,%77,%78,%79,"
      "%80,%81,%82,%83,%84,%85,%86,%87,%88,%89,%90,%91,%92,%93,%94,%95"
      "}, {%96,%97,%98,%99}, %100, p, 1, 1, 0; }"
    : "+f"(d[0]), "+f"(d[1]), "+f"(d[2]), "+f"(d[3]), "+f"(d[4]), "+f"(d[5]), "+f"(d[6]), "+f"(d[7]),
      "+f"(d[8]), "+f"(d[9]), "+f"(d[10]), "+f"(d[11]), "+f"(d[12]), "+f"(d[13]), "+f"(d[14]), "+f"(d[15]),
      "+f"(d[16]), "+f"(d[17]), "+f"(d[18]), "+f"(d[19]), "+f"(d[20]), "+f"(d[21]), "+f"(d[22]), "+f"(d[23]),
      "+f"(d[24]), "+f"(d[25]), "+f"(d[26]), "+f"(d[27]), "+f"(d[28]), "+f"(d[29]), "+f"(d[30]), "+f"(d[31]),
      "+f"(d[32]), "+f"(d[33]), "+f"(d[34]), "+f"(d[35]), "+f"(d[36]), "+f"(d[37]), "+f"(d[38]), "+f"(d[39]),
      "+f"(d[40]), "+f"(d[41]), "+f"(d[42]), "+f"(d[43]), "+f"(d[44]), "+f"(d[45]), "+f"(d[46]), "+f"(d[47]),
      "+f"(d[48]), "+f"(d[49]), "+f"(d[50]), "+f"(d[51]), "+f"(d[52]), "+f"(d[53]), "+f"(d[54]), "+f"(d[55]),
      "+f"(d[56]), "+f"(d[57]), "+f"(d[58]), "+f"(d[59]), "+f"(d[60]), "+f"(d[61]), "+f"(d[62]), "+f"(d[63]),
      "+f"(d[64]), "+f"(d[65]), "+f"(d[66]), "+f"(d[67]), "+f"(d[68]), "+f"(d[69]), "+f"(d[70]), "+f"(d[71]),
      "+f"(d[72]), "+f"(d[73]), "+f"(d[74]), "+f"(d[75]), "+f"(d[76]), "+f"(d[77]), "+f"(d[78]), "+f"(d[79]),
      "+f"(d[80]), "+f"(d[81]), "+f"(d[82]), "+f"(d[83]), "+f"(d[84]), "+f"(d[85]), "+f"(d[86]), "+f"(d[87]),
      "+f"(d[88]), "+f"(d[89]), "+f"(d[90]), "+f"(d[91]), "+f"(d[92]), "+f"(d[93]), "+f"(d[94]), "+f"(d[95])
    : "r"(a[0]), "r"(a[1]), "r"(a[2]), "r"(a[3]), "l"(db), "r"(sd));
}

__device__ __forceinline__ void wgmma_rs_n208(float* d, const uint32_t* a, uint64_t db, int sd) {
  asm volatile("{ .reg .pred p; setp.ne.b32 p, %109, 0;\n"
      "wgmma.mma_async.sync.aligned.m64n208k16.f32.bf16.bf16 {"
      "%0,%1,%2,%3,%4,%5,%6,%7,%8,%9,%10,%11,%12,%13,%14,%15,"
      "%16,%17,%18,%19,%20,%21,%22,%23,%24,%25,%26,%27,%28,%29,%30,%31,"
      "%32,%33,%34,%35,%36,%37,%38,%39,%40,%41,%42,%43,%44,%45,%46,%47,"
      "%48,%49,%50,%51,%52,%53,%54,%55,%56,%57,%58,%59,%60,%61,%62,%63,"
      "%64,%65,%66,%67,%68,%69,%70,%71,%72,%73,%74,%75,%76,%77,%78,%79,"
      "%80,%81,%82,%83,%84,%85,%86,%87,%88,%89,%90,%91,%92,%93,%94,%95,"
      "%96,%97,%98,%99,%100,%101,%102,%103"
      "}, {%104,%105,%106,%107}, %108, p, 1, 1, 0; }"
    : "+f"(d[0]), "+f"(d[1]), "+f"(d[2]), "+f"(d[3]), "+f"(d[4]), "+f"(d[5]), "+f"(d[6]), "+f"(d[7]),
      "+f"(d[8]), "+f"(d[9]), "+f"(d[10]), "+f"(d[11]), "+f"(d[12]), "+f"(d[13]), "+f"(d[14]), "+f"(d[15]),
      "+f"(d[16]), "+f"(d[17]), "+f"(d[18]), "+f"(d[19]), "+f"(d[20]), "+f"(d[21]), "+f"(d[22]), "+f"(d[23]),
      "+f"(d[24]), "+f"(d[25]), "+f"(d[26]), "+f"(d[27]), "+f"(d[28]), "+f"(d[29]), "+f"(d[30]), "+f"(d[31]),
      "+f"(d[32]), "+f"(d[33]), "+f"(d[34]), "+f"(d[35]), "+f"(d[36]), "+f"(d[37]), "+f"(d[38]), "+f"(d[39]),
      "+f"(d[40]), "+f"(d[41]), "+f"(d[42]), "+f"(d[43]), "+f"(d[44]), "+f"(d[45]), "+f"(d[46]), "+f"(d[47]),
      "+f"(d[48]), "+f"(d[49]), "+f"(d[50]), "+f"(d[51]), "+f"(d[52]), "+f"(d[53]), "+f"(d[54]), "+f"(d[55]),
      "+f"(d[56]), "+f"(d[57]), "+f"(d[58]), "+f"(d[59]), "+f"(d[60]), "+f"(d[61]), "+f"(d[62]), "+f"(d[63]),
      "+f"(d[64]), "+f"(d[65]), "+f"(d[66]), "+f"(d[67]), "+f"(d[68]), "+f"(d[69]), "+f"(d[70]), "+f"(d[71]),
      "+f"(d[72]), "+f"(d[73]), "+f"(d[74]), "+f"(d[75]), "+f"(d[76]), "+f"(d[77]), "+f"(d[78]), "+f"(d[79]),
      "+f"(d[80]), "+f"(d[81]), "+f"(d[82]), "+f"(d[83]), "+f"(d[84]), "+f"(d[85]), "+f"(d[86]), "+f"(d[87]),
      "+f"(d[88]), "+f"(d[89]), "+f"(d[90]), "+f"(d[91]), "+f"(d[92]), "+f"(d[93]), "+f"(d[94]), "+f"(d[95]),
      "+f"(d[96]), "+f"(d[97]), "+f"(d[98]), "+f"(d[99]), "+f"(d[100]), "+f"(d[101]), "+f"(d[102]), "+f"(d[103])
    : "r"(a[0]), "r"(a[1]), "r"(a[2]), "r"(a[3]), "l"(db), "r"(sd));
}

__device__ __forceinline__ void wgmma_rs_n224(float* d, const uint32_t* a, uint64_t db, int sd) {
  asm volatile("{ .reg .pred p; setp.ne.b32 p, %117, 0;\n"
      "wgmma.mma_async.sync.aligned.m64n224k16.f32.bf16.bf16 {"
      "%0,%1,%2,%3,%4,%5,%6,%7,%8,%9,%10,%11,%12,%13,%14,%15,"
      "%16,%17,%18,%19,%20,%21,%22,%23,%24,%25,%26,%27,%28,%29,%30,%31,"
      "%32,%33,%34,%35,%36,%37,%38,%39,%40,%41,%42,%43,%44,%45,%46,%47,"
      "%48,%49,%50,%51,%52,%53,%54,%55,%56,%57,%58,%59,%60,%61,%62,%63,"
      "%64,%65,%66,%67,%68,%69,%70,%71,%72,%73,%74,%75,%76,%77,%78,%79,"
      "%80,%81,%82,%83,%84,%85,%86,%87,%88,%89,%90,%91,%92,%93,%94,%95,"
      "%96,%97,%98,%99,%100,%101,%102,%103,%104,%105,%106,%107,%108,%109,%110,%111"
      "}, {%112,%113,%114,%115}, %116, p, 1, 1, 0; }"
    : "+f"(d[0]), "+f"(d[1]), "+f"(d[2]), "+f"(d[3]), "+f"(d[4]), "+f"(d[5]), "+f"(d[6]), "+f"(d[7]),
      "+f"(d[8]), "+f"(d[9]), "+f"(d[10]), "+f"(d[11]), "+f"(d[12]), "+f"(d[13]), "+f"(d[14]), "+f"(d[15]),
      "+f"(d[16]), "+f"(d[17]), "+f"(d[18]), "+f"(d[19]), "+f"(d[20]), "+f"(d[21]), "+f"(d[22]), "+f"(d[23]),
      "+f"(d[24]), "+f"(d[25]), "+f"(d[26]), "+f"(d[27]), "+f"(d[28]), "+f"(d[29]), "+f"(d[30]), "+f"(d[31]),
      "+f"(d[32]), "+f"(d[33]), "+f"(d[34]), "+f"(d[35]), "+f"(d[36]), "+f"(d[37]), "+f"(d[38]), "+f"(d[39]),
      "+f"(d[40]), "+f"(d[41]), "+f"(d[42]), "+f"(d[43]), "+f"(d[44]), "+f"(d[45]), "+f"(d[46]), "+f"(d[47]),
      "+f"(d[48]), "+f"(d[49]), "+f"(d[50]), "+f"(d[51]), "+f"(d[52]), "+f"(d[53]), "+f"(d[54]), "+f"(d[55]),
      "+f"(d[56]), "+f"(d[57]), "+f"(d[58]), "+f"(d[59]), "+f"(d[60]), "+f"(d[61]), "+f"(d[62]), "+f"(d[63]),
      "+f"(d[64]), "+f"(d[65]), "+f"(d[66]), "+f"(d[67]), "+f"(d[68]), "+f"(d[69]), "+f"(d[70]), "+f"(d[71]),
      "+f"(d[72]), "+f"(d[73]), "+f"(d[74]), "+f"(d[75]), "+f"(d[76]), "+f"(d[77]), "+f"(d[78]), "+f"(d[79]),
      "+f"(d[80]), "+f"(d[81]), "+f"(d[82]), "+f"(d[83]), "+f"(d[84]), "+f"(d[85]), "+f"(d[86]), "+f"(d[87]),
      "+f"(d[88]), "+f"(d[89]), "+f"(d[90]), "+f"(d[91]), "+f"(d[92]), "+f"(d[93]), "+f"(d[94]), "+f"(d[95]),
      "+f"(d[96]), "+f"(d[97]), "+f"(d[98]), "+f"(d[99]), "+f"(d[100]), "+f"(d[101]), "+f"(d[102]), "+f"(d[103]),
      "+f"(d[104]), "+f"(d[105]), "+f"(d[106]), "+f"(d[107]), "+f"(d[108]), "+f"(d[109]), "+f"(d[110]), "+f"(d[111])
    : "r"(a[0]), "r"(a[1]), "r"(a[2]), "r"(a[3]), "l"(db), "r"(sd));
}

__device__ __forceinline__ void wgmma_rs_n240(float* d, const uint32_t* a, uint64_t db, int sd) {
  asm volatile("{ .reg .pred p; setp.ne.b32 p, %125, 0;\n"
      "wgmma.mma_async.sync.aligned.m64n240k16.f32.bf16.bf16 {"
      "%0,%1,%2,%3,%4,%5,%6,%7,%8,%9,%10,%11,%12,%13,%14,%15,"
      "%16,%17,%18,%19,%20,%21,%22,%23,%24,%25,%26,%27,%28,%29,%30,%31,"
      "%32,%33,%34,%35,%36,%37,%38,%39,%40,%41,%42,%43,%44,%45,%46,%47,"
      "%48,%49,%50,%51,%52,%53,%54,%55,%56,%57,%58,%59,%60,%61,%62,%63,"
      "%64,%65,%66,%67,%68,%69,%70,%71,%72,%73,%74,%75,%76,%77,%78,%79,"
      "%80,%81,%82,%83,%84,%85,%86,%87,%88,%89,%90,%91,%92,%93,%94,%95,"
      "%96,%97,%98,%99,%100,%101,%102,%103,%104,%105,%106,%107,%108,%109,%110,%111,"
      "%112,%113,%114,%115,%116,%117,%118,%119"
      "}, {%120,%121,%122,%123}, %124, p, 1, 1, 0; }"
    : "+f"(d[0]), "+f"(d[1]), "+f"(d[2]), "+f"(d[3]), "+f"(d[4]), "+f"(d[5]), "+f"(d[6]), "+f"(d[7]),
      "+f"(d[8]), "+f"(d[9]), "+f"(d[10]), "+f"(d[11]), "+f"(d[12]), "+f"(d[13]), "+f"(d[14]), "+f"(d[15]),
      "+f"(d[16]), "+f"(d[17]), "+f"(d[18]), "+f"(d[19]), "+f"(d[20]), "+f"(d[21]), "+f"(d[22]), "+f"(d[23]),
      "+f"(d[24]), "+f"(d[25]), "+f"(d[26]), "+f"(d[27]), "+f"(d[28]), "+f"(d[29]), "+f"(d[30]), "+f"(d[31]),
      "+f"(d[32]), "+f"(d[33]), "+f"(d[34]), "+f"(d[35]), "+f"(d[36]), "+f"(d[37]), "+f"(d[38]), "+f"(d[39]),
      "+f"(d[40]), "+f"(d[41]), "+f"(d[42]), "+f"(d[43]), "+f"(d[44]), "+f"(d[45]), "+f"(d[46]), "+f"(d[47]),
      "+f"(d[48]), "+f"(d[49]), "+f"(d[50]), "+f"(d[51]), "+f"(d[52]), "+f"(d[53]), "+f"(d[54]), "+f"(d[55]),
      "+f"(d[56]), "+f"(d[57]), "+f"(d[58]), "+f"(d[59]), "+f"(d[60]), "+f"(d[61]), "+f"(d[62]), "+f"(d[63]),
      "+f"(d[64]), "+f"(d[65]), "+f"(d[66]), "+f"(d[67]), "+f"(d[68]), "+f"(d[69]), "+f"(d[70]), "+f"(d[71]),
      "+f"(d[72]), "+f"(d[73]), "+f"(d[74]), "+f"(d[75]), "+f"(d[76]), "+f"(d[77]), "+f"(d[78]), "+f"(d[79]),
      "+f"(d[80]), "+f"(d[81]), "+f"(d[82]), "+f"(d[83]), "+f"(d[84]), "+f"(d[85]), "+f"(d[86]), "+f"(d[87]),
      "+f"(d[88]), "+f"(d[89]), "+f"(d[90]), "+f"(d[91]), "+f"(d[92]), "+f"(d[93]), "+f"(d[94]), "+f"(d[95]),
      "+f"(d[96]), "+f"(d[97]), "+f"(d[98]), "+f"(d[99]), "+f"(d[100]), "+f"(d[101]), "+f"(d[102]), "+f"(d[103]),
      "+f"(d[104]), "+f"(d[105]), "+f"(d[106]), "+f"(d[107]), "+f"(d[108]), "+f"(d[109]), "+f"(d[110]), "+f"(d[111]),
      "+f"(d[112]), "+f"(d[113]), "+f"(d[114]), "+f"(d[115]), "+f"(d[116]), "+f"(d[117]), "+f"(d[118]), "+f"(d[119])
    : "r"(a[0]), "r"(a[1]), "r"(a[2]), "r"(a[3]), "l"(db), "r"(sd));
}

__device__ __forceinline__ void wgmma_rs_n256(float* d, const uint32_t* a, uint64_t db, int sd) {
  asm volatile("{ .reg .pred p; setp.ne.b32 p, %133, 0;\n"
      "wgmma.mma_async.sync.aligned.m64n256k16.f32.bf16.bf16 {"
      "%0,%1,%2,%3,%4,%5,%6,%7,%8,%9,%10,%11,%12,%13,%14,%15,"
      "%16,%17,%18,%19,%20,%21,%22,%23,%24,%25,%26,%27,%28,%29,%30,%31,"
      "%32,%33,%34,%35,%36,%37,%38,%39,%40,%41,%42,%43,%44,%45,%46,%47,"
      "%48,%49,%50,%51,%52,%53,%54,%55,%56,%57,%58,%59,%60,%61,%62,%63,"
      "%64,%65,%66,%67,%68,%69,%70,%71,%72,%73,%74,%75,%76,%77,%78,%79,"
      "%80,%81,%82,%83,%84,%85,%86,%87,%88,%89,%90,%91,%92,%93,%94,%95,"
      "%96,%97,%98,%99,%100,%101,%102,%103,%104,%105,%106,%107,%108,%109,%110,%111,"
      "%112,%113,%114,%115,%116,%117,%118,%119,%120,%121,%122,%123,%124,%125,%126,%127"
      "}, {%128,%129,%130,%131}, %132, p, 1, 1, 0; }"
    : "+f"(d[0]), "+f"(d[1]), "+f"(d[2]), "+f"(d[3]), "+f"(d[4]), "+f"(d[5]), "+f"(d[6]), "+f"(d[7]),
      "+f"(d[8]), "+f"(d[9]), "+f"(d[10]), "+f"(d[11]), "+f"(d[12]), "+f"(d[13]), "+f"(d[14]), "+f"(d[15]),
      "+f"(d[16]), "+f"(d[17]), "+f"(d[18]), "+f"(d[19]), "+f"(d[20]), "+f"(d[21]), "+f"(d[22]), "+f"(d[23]),
      "+f"(d[24]), "+f"(d[25]), "+f"(d[26]), "+f"(d[27]), "+f"(d[28]), "+f"(d[29]), "+f"(d[30]), "+f"(d[31]),
      "+f"(d[32]), "+f"(d[33]), "+f"(d[34]), "+f"(d[35]), "+f"(d[36]), "+f"(d[37]), "+f"(d[38]), "+f"(d[39]),
      "+f"(d[40]), "+f"(d[41]), "+f"(d[42]), "+f"(d[43]), "+f"(d[44]), "+f"(d[45]), "+f"(d[46]), "+f"(d[47]),
      "+f"(d[48]), "+f"(d[49]), "+f"(d[50]), "+f"(d[51]), "+f"(d[52]), "+f"(d[53]), "+f"(d[54]), "+f"(d[55]),
      "+f"(d[56]), "+f"(d[57]), "+f"(d[58]), "+f"(d[59]), "+f"(d[60]), "+f"(d[61]), "+f"(d[62]), "+f"(d[63]),
      "+f"(d[64]), "+f"(d[65]), "+f"(d[66]), "+f"(d[67]), "+f"(d[68]), "+f"(d[69]), "+f"(d[70]), "+f"(d[71]),
      "+f"(d[72]), "+f"(d[73]), "+f"(d[74]), "+f"(d[75]), "+f"(d[76]), "+f"(d[77]), "+f"(d[78]), "+f"(d[79]),
      "+f"(d[80]), "+f"(d[81]), "+f"(d[82]), "+f"(d[83]), "+f"(d[84]), "+f"(d[85]), "+f"(d[86]), "+f"(d[87]),
      "+f"(d[88]), "+f"(d[89]), "+f"(d[90]), "+f"(d[91]), "+f"(d[92]), "+f"(d[93]), "+f"(d[94]), "+f"(d[95]),
      "+f"(d[96]), "+f"(d[97]), "+f"(d[98]), "+f"(d[99]), "+f"(d[100]), "+f"(d[101]), "+f"(d[102]), "+f"(d[103]),
      "+f"(d[104]), "+f"(d[105]), "+f"(d[106]), "+f"(d[107]), "+f"(d[108]), "+f"(d[109]), "+f"(d[110]), "+f"(d[111]),
      "+f"(d[112]), "+f"(d[113]), "+f"(d[114]), "+f"(d[115]), "+f"(d[116]), "+f"(d[117]), "+f"(d[118]), "+f"(d[119]),
      "+f"(d[120]), "+f"(d[121]), "+f"(d[122]), "+f"(d[123]), "+f"(d[124]), "+f"(d[125]), "+f"(d[126]), "+f"(d[127])
    : "r"(a[0]), "r"(a[1]), "r"(a[2]), "r"(a[3]), "l"(db), "r"(sd));
}

__device__ __forceinline__ void ln_finish(float mean, float var, float& mb, float& rinv) {
  mb = round_bf16(mean);
  float sd;
  asm("sqrt.approx.ftz.f32 %0, %1;" : "=f"(sd) : "f"(round_bf16(round_bf16(var) + 1e-5f)));
  asm("rcp.approx.ftz.f32 %0, %1;" : "=f"(rinv) : "f"(round_bf16(sd)));
}
__device__ __forceinline__ uint32_t ln_apply(uint32_t x2, uint32_t mb2, float rinv) {
  uint32_t c = bsub2(x2, mb2);
  return pack_bf16(bf_lo(c) * rinv, bf_hi(c) * rinv);
}
__device__ __forceinline__ int conv_channel(int cta, int i) {
  return i < N_SHORT ? i * N_CONV_CTA + cta : N_SHORT * N_CONV_CTA + (i - N_SHORT) * 4 + cta;
}
__device__ __forceinline__ uint32_t sum4(uint32_t a, uint32_t b, uint32_t c, uint32_t d) {
  return pack_bf16((bf_lo(a) + bf_lo(b)) + (bf_lo(c) + bf_lo(d)), (bf_hi(a) + bf_hi(b)) + (bf_hi(c) + bf_hi(d)));
}
struct Ring {
  uint32_t s, ph;
  __device__ __forceinline__ void next() { if (++s == NSTAGE) { s = 0; ph ^= 1; } }
};

struct Cta {
  int rank, g1m  , g1n, g2m  , g2n;
  __device__ __forceinline__ Cta() {
    const int b = cta_id(), c = b >> 1;
    int g, idx;
    if (c < 4) { g = 0; idx = 4 + c; }
    else if (c < 36) { g = (c - 4) & 7; idx = (c - 4) >> 3; }
    else if (c < 64) { g = 1 + (c - 36) % 7; idx = 4 + (c - 36) / 7; }
    else { g = c - 58; idx = 8; }
    rank = b & 1;
    g2m = idx < 8 ? 2 * g + (idx >> 2) : -1;
    g2n = idx & 3;
    if (idx < (g < 2 ? 6 : 7)) { const int c1 = (g < 2 ? 6 * g : 7 * g - 2) + idx; g1m = c1 / 3; g1n = c1 % 3; }
    else { g1m = -1 - (idx == 8 ? g - 6 : (g < 2 ? 2 * g + idx - 4 : g + 4)); g1n = 0; }
  }
  __device__ __forceinline__ int cvc() const { return 2 * (-1 - g1m) + rank; }
  __device__ __forceinline__ int n_conv() const { return g2m < 0 ? N_SHORT + N_LONG_EXTRA : N_SHORT; }
  __device__ __forceinline__ int fill() const { return CH_FILL + (g1m * 3 + g1n) * 2 + rank; }
  __device__ __forceinline__ int dk() const { return g2n * 144 + rank * 72; }
  __device__ __forceinline__ void await_u(Scratch* S, int wg, uint32_t tag) const {
    const uint32_t* p0 = S->cnt + (C_U + ((g2n * 144) / 192) * 4 + rank * 2 + wg) * 32;
    const uint32_t* p1 = S->cnt + (C_U + ((g2n * 144 + 143) / 192) * 4 + rank * 2 + wg) * 32;
    for (uint32_t n = 0;; n++) {
      const uint32_t v0 = ld_flag(p0) - tag * 18, v1 = ld_flag(p1) - tag * 18;
      if ((int32_t)(v0 | v1) >= 0) break;
      if (n > 4000000u) __trap();
    }
  }
  __device__ __forceinline__ int g2k(int kb) const { return (rank * G2_KB + (kb < 18 ? 2 * kb : 2 * kb - 35)) * 64; }
};

#define CONV_LDA(j, base) { a[2 * (j)] = lds32((base) + ((j) >> 1) * 256 + ((j) & 1) * 16); a[2 * (j) + 1] = lds32((base) + ((j) >> 1) * 256 + ((j) & 1) * 16 + 128); }
__device__ __forceinline__ void conv_mma(float* acc, const uint32_t* a, uint64_t db) {
  wgmma_rs_n256(acc, a, db, 0);
  wgmma_rs_n240(acc, a + 4, db + 16, 1);
  wgmma_rs_n224(acc, a + 8, db + 32, 1);
  wgmma_rs_n208(acc, a + 12, db + 48, 1);
  wgmma_rs_n192(acc, a + 16, db + 64, 1);
  wgmma_rs_n176(acc, a + 20, db + 80, 1);
  wgmma_rs_n160(acc, a + 24, db + 96, 1);
  wgmma_rs_n144(acc, a + 28, db + 112, 1);
  wgmma_rs_n128(acc, a + 32, db + 128, 1);
  wgmma_rs_n112(acc, a + 36, db + 144, 1);
  wgmma_rs_n96(acc, a + 40, db + 160, 1);
  wgmma_rs_n80(acc, a + 44, db + 176, 1);
  wgmma_rs_n64(acc, a + 48, db + 192, 1);
  wgmma_rs_n48(acc, a + 52, db + 208, 1);
  wgmma_rs_n32(acc, a + 56, db + 224, 1);
  wgmma_rs_n16(acc, a + 60, db + 240, 1);
}
__device__ __forceinline__ uint32_t conv_part(const float* acc, int j) {
  const int q = 31 - j;
  return q == 31 ? pack_bf16(acc[124], acc[125]) : pack_bf16(acc[4 * q] + acc[(4 * q + 6) & 127], acc[4 * q + 1] + acc[(4 * q + 7) & 127]);
}
__device__ __forceinline__ void conv_out(Scratch* S, const uint4 (*p)[4], int ch, int wtid) {
  uint4* yo = reinterpret_cast<uint4*>(S->y + (size_t)ch * S_) + wtid;
#pragma unroll
  for (int c = 0; c < 2; c++)
    yo[128 * c] = make_uint4(sum4(p[c][0].x, p[c][1].x, p[c][2].x, p[c][3].x), sum4(p[c][0].y, p[c][1].y, p[c][2].y, p[c][3].y),
                             sum4(p[c][0].z, p[c][1].z, p[c][2].z, p[c][3].z), sum4(p[c][0].w, p[c][1].w, p[c][2].w, p[c][3].w));
}

__global__ void __cluster_dims__(2, 1, 1) __launch_bounds__(384, 1) fused_kernel(const __grid_constant__ Hot H, const __grid_constant__ Params P) {
  extern __shared__ uint8_t smem_raw[];
  const uint32_t t0 = clk();
  Scratch* const S = H.S;
  const uint32_t sb = (smem_u32(smem_raw) + 1023) & ~1023u;
  const uint32_t bars = sb + SM_BAR;
  const int tid = threadIdx.x, warp = __shfl_sync(0xffffffffu, tid >> 5, 0), lane = tid & 31;
  const bool p0 = blockIdx.x < 128;

  if (warp >= 8) {
    asm volatile("setmaxnreg.dec.sync.aligned.u32 56;");
    const uint32_t tag = ld_flag(S->epoch) + 1;
    if (lane == 0) {
      const bool g1 = Cta().g1m >= 0;
      if (warp == 8) {
        for (int s = 0; s < NSTAGE; s++) mbar_init(bars + 8 * (B_FULL + s), 1);
        for (int s = 0; s < CV_NSLOT; s++) mbar_init(bars + 8 * (B_CFULL + s), 1);
        if (!g1) { mbar_arrive(bars + 8 * B_FULL); mbar_arrive(bars + 8 * (B_FULL + 1)); }
      } else if (warp == 9) {
        for (int s = 0; s < NSTAGE; s++) mbar_init(bars + 8 * (B_EMPTY + s), 2);
        mbar_init(bars + 8 * B_YDONE, g1 ? 4 : 8);
      } else if (warp == 10) {
        for (int s = B_STG; s <= B_FILL; s++) mbar_init(bars + 8 * s, 4);
      } else {
        for (int s = B_XRDY; s <= B_GO; s++) mbar_init(bars + 8 * s, s == B_XT ? 2 : 1);
      }
      asm volatile("fence.mbarrier_init.release.cluster;" ::: "memory");
    }
    __syncwarp();
    asm volatile("barrier.cluster.arrive.relaxed.aligned;" ::: "memory");
    if (warp == 8) {
      if (lane < 9) asm volatile("prefetch.tensormap [%0];" :: "l"(&P.m_w1 + lane) : "memory");
      const Cta c;
      const int fg = (2 * c.g1m + c.rank) * 2, dg = c.g1n * 3;
      if (lane == 0) {
        if (c.g1m >= 0) {
          for (int s = 0; s < NSTAGE; s++) mbar_expect_tx(bars + 8 * (B_FULL + s), G1_BYTES);
          int nw = 0;
          TLREC(25);
          if (tag != 0) TLREC(26);
          for (uint32_t n = 0;; n++) {
            if (nw < NSTAGE && clk() - t0 >= W1T0 + nw * W1D + (c.g1m & 7) * STAG) { tma3d_ef(sb + nw * SLOT, &P.m_w1, 0, nw * 64, fg, bars + 8 * (B_FULL + nw)); nw++; }
            if (reached(S, C_H, tag * 128)) {
              break; }
            if (n > 4000000u) __trap();
          }
          TLREC(2);
          fence_async_global();
#pragma unroll 1
          for (int s = 0; s < NSTAGE; s++) {
            if (s >= nw) tma3d_ef(sb + s * SLOT, &P.m_w1, 0, s * 64, fg, bars + 8 * (B_FULL + s));
            if (s < 4) tma3d(sb + s * SLOT + 16384, &P.m_h, 0, s * 64, dg, bars + 8 * (B_FULL + s));
          }
        } else {
          pace(t0, CKT0);
#pragma unroll 1
          for (int i = 0; i < CV_NSLOT; i++) {
            mbar_expect_tx(bars + 8 * (B_CFULL + i), 8192 + 4096);
            bulk_load(sb + i * CV_SLOT + CV_KOFF + 32, H.ssm_k + (size_t)conv_channel(c.cvc(), i) * S_, 4096, bars + 8 * (B_CFULL + i));
          }
        }
      }
      __syncwarp();
      asm volatile("barrier.cluster.wait.aligned;" ::: "memory");
      if (lane == 0) {
        if (c.g1m >= 0) {
          mbar_arrive(bars + 8 * B_GO);
          await(S, C_H + 1, tag * 128);
          fence_async_global();
          tma3d(sb + 4 * SLOT + 16384, &P.m_h, 0, 4 * 64, dg, bars + 8 * (B_FULL + 4));
          Ring r{0, 0};
#pragma unroll 1
          for (int kb = NSTAGE; kb < G1_KB; kb++, r.next()) {
            if (kb == 8) {
              for (uint32_t n = 0;; n++) {
                uint32_t v[6];
#pragma unroll
                for (int i = 0; i < 6; i++) v[i] = ld_flag(S->cnt + (C_H + 2 + i) * 32) - tag * 128;
                if ((int32_t)(v[0] | v[1] | v[2] | v[3] | v[4] | v[5]) >= 0) break;
                if (n > 4000000u) __trap();
              }
              fence_async_global();
            }
            mbar_wait(bars + 8 * (B_EMPTY + r.s), r.ph);
            mbar_expect_tx(bars + 8 * (B_FULL + r.s), G1_BYTES);
            tma3d_ef(sb + r.s * SLOT, &P.m_w1, 0, kb * 64, fg, bars + 8 * (B_FULL + r.s));
            tma3d(sb + r.s * SLOT + 16384, &P.m_h, 0, kb * 64, dg, bars + 8 * (B_FULL + r.s));
          }
        } else {
          const int cvc = c.cvc(), n_conv = c.n_conv();
          int ready = -1;
#pragma unroll 1
          for (int i = 0; i < n_conv; i++) {
            const int ch = conv_channel(cvc, i), s = i % CV_NSLOT;
            const uint32_t slot = sb + s * CV_SLOT, fb = bars + 8 * (B_CFULL + s);
            if (i >= CV_NSLOT) {
              mbar_wait(bars + 8 * (B_CEMPTY + s), ((i / CV_NSLOT) - 1) & 1);
              mbar_expect_tx(fb, 8192 + 4096);
              bulk_load(slot + CV_KOFF + 32, H.ssm_k + (size_t)ch * S_, 4096, fb);
            }
            const int r = ch / 96;
            if (r > ready) {
              await(S, C_KV + r, tag * 128);
              fence_async_global();
              if (r == 0) { mbar_arrive(bars + 8 * B_GO); TLREC(18); }
              ready = r;
            }
            bulk_load(slot, S->ub + (size_t)ch * 4096, 8192, fb);
          }
        }
        if (c.g2m >= 0) {
          const int sg = c.g2m * 2, dk = c.dk(), ds = c.g2n * 144 + (c.rank ^ 1) * 72;
          constexpr int NPRE = 3;
#pragma unroll 1
          for (int kb = 0; kb < NPRE; kb++) {
            const int s = G1_KB % NSTAGE + kb;
            mbar_wait(bars + 8 * (B_EMPTY + s), ((G1_KB / NSTAGE) - 1) & 1);
            mbar_expect_tx(bars + 8 * (B_FULL + s), G2_BYTES);
            tma3d_ef(sb + s * SLOT, &P.m_w2, 0, c.g2k(kb), sg, bars + 8 * (B_FULL + s));
          }
          mbar_expect_tx(bars + 8 * B_XT, 5 * 2304);
#pragma unroll 1
          for (int j = 0; j < 5; j++) tma2d(sb + x_off(j), &P.m_x, dk, c.g2m * 128 + j * 16, bars + 8 * B_XT);
          mbar_expect_tx(bars + 8 * B_Y2, 18432);
          int ny = 0;
          auto load_y = [&]() { tma2d(sb + SM_DED + ny * 3072, &P.m_y, c.g2m * 128 + (ny / 3) * 64, dk + (ny % 3) * 24, bars + 8 * B_Y2); ny++; };
          Ring r{G1_KB % NSTAGE, ((G1_KB / NSTAGE) - 1) & 1};
#pragma unroll 1
          for (int kb = 0; kb < G2_KB; kb++, r.next()) {
            const int k0 = c.g2k(kb);
            const uint32_t fb = bars + 8 * (B_FULL + r.s), slot = sb + r.s * SLOT;
            if (kb == 0) { c.await_u(S, 0, tag); fence_async_global(); TLREC(6); }
            if (kb == 18) { mbar_wait(bars + 8 * B_ULATE, 0); fence_async_global(); }
            if (kb >= NPRE) {
              mbar_wait(bars + 8 * (B_EMPTY + r.s), r.ph);
              mbar_expect_tx(fb, G2_BYTES);
              tma3d_ef(slot, &P.m_w2, 0, k0, sg, fb);
            }
            tma2d(slot + 16384, &P.m_uld, k0, ds, fb);
            tma2d(slot + 16384 + 9216, &P.m_uld, k0, dk, fb);
            if (kb >= 20 && ny < 6 && (ny > 0 || mbar_test(bars + 8 * B_YRDY, 0))) {
              if (ny == 0) { fence_async_global(); fence_async_smem(); }
              load_y();
            }
          }
          mbar_expect_tx(bars + 8 * B_XFULL, 18432);
          mbar_expect_tx(bars + 8 * (B_XFULL + 1), 18432);
          mbar_wait(bars + 8 * (B_EMPTY + XSLOT), r.ph);
          mbar_arrive_remote(mapa(bars + 8 * B_XRDY, c.rank ^ 1));
          if (ny == 0) { mbar_wait(bars + 8 * B_YRDY, 0); fence_async_global(); fence_async_smem(); }
          while (ny < 6) load_y();
        }
      }
    } else {
      const int ht = tid - 288;
      if (p0) {
        const int hf = ht / 48, pr = ht % 48;
        const int s0 = blockIdx.x * 16 + hf * 8;
        const bool first = s0 == 0;
        const __nv_bfloat16* kp = H.k + (ptrdiff_t)(s0 - 4) * D_ + 2 * pr;
        const __nv_bfloat16* vp = H.v + (ptrdiff_t)(s0 - 1) * D_ + 2 * pr;
        const uint4* wp = reinterpret_cast<const uint4*>(H.shift_k) + pr;
        const uint32_t st = sb + SM_KVS + (1 - hf) * 1536 + pr * 32;
        uint32_t kk[12], vv[9];
        uint4 w;
        auto load = [&](int r) {
#pragma unroll
          for (int j = 0; j < 12; j++) kk[j] = (j < 4 && first) ? 0u : ldg32(kp + r * 96 + j * D_);
#pragma unroll
          for (int j = 0; j < 9; j++) vv[j] = (j < 1 && first) ? 0u : ldg32(vp + r * 96 + j * D_);
          w = __ldg(wp + r * 48);
        };
        pace(t0, KVT0 + (blockIdx.x & 7) * STAG);
        load(0);
        asm volatile("barrier.cluster.wait.aligned;" ::: "memory");
#pragma unroll 1
        for (int r = 0; r < KV_ROUNDS; r++) {
          const uint32_t w0 = __byte_perm(w.x, w.z, 0x5410), w1 = __byte_perm(w.x, w.z, 0x7632);
          const uint32_t w2 = __byte_perm(w.y, w.w, 0x5410), w3 = __byte_perm(w.y, w.w, 0x7632);
#pragma unroll
          for (int j = 0; j < 9; j++)
            vv[j] = bmul2(bfma2(kk[j + 3], w0, bfma2(kk[j + 2], w1, bfma2(kk[j + 1], w2, bmul2(kk[j], w3)))), vv[j]);
#pragma unroll
          for (int c = 0; c < 2; c++)
#pragma unroll
            for (int pi = 0; pi < 2; pi++) {
              const uint32_t sel = c ? 0x7632 : 0x5410;
              sts128(st + c * 3072 + pi * 16, __byte_perm(vv[7 + pi], vv[6 + pi], sel), __byte_perm(vv[5 + pi], vv[4 + pi], sel),
                     __byte_perm(vv[3 + pi], vv[2 + pi], sel), __byte_perm(vv[1 + pi], vv[pi], sel));
            }
          bar_sync(1, 96);
          if (ht == 0) { fence_async_smem(); tma3d_store(&P.m_ub, sb + SM_KVS, 16 * (127 - blockIdx.x), r * 48, 0); bulk_commit(); }
          if (r > 0 && r + 1 < KV_ROUNDS) load(r + 1);
          if (ht == 0) { bulk_wait_all(); signal_stored(S, C_KV + r); if (r == 0) TLREC(22); }
          if (r == 0) { mbar_wait(bars + 8 * B_GO, 0); load(1); }
          __syncwarp();
          bar_sync(1, 96);
        }
        if (ht == 0) mbar_arrive(bars + 8 * B_KVDONE);
      } else {
        asm volatile("barrier.cluster.wait.aligned;" ::: "memory");
      }
      if (lane == 0) {
        const Cta c;
        if (warp < 11) {
          if (c.g1m >= 0) {
            const int wg = warp - 9, fb64 = (2 * c.g1m + c.rank) * 2 + wg;
            const uint32_t stg = wg == 0 ? sb + SM_DED : sb + SLOT + 16384;
#pragma unroll 1
            for (int ck = 0; ck < 3; ck++) {
              mbar_wait(bars + 8 * (B_STG + wg * 3 + ck), 0);
              fence_async_smem();
              tma2d_store(&P.m_ust, stg + ck * 8192, fb64 * 64, c.g1n * 192 + ck * 64);
            }
            TLREC(13 + wg);
            bulk_commit();
            bulk_wait_all();
            signal_stored(S, C_U + c.g1n * 4 + (fb64 / G2_KB) * 2 + wg);
            mbar_arrive(bars + 8 * (wg == 0 ? B_DED : B_EMPTY + 1));
            TLREC(15 + wg);
          }
          if (c.g2m >= 0) {
            if (warp == 9) {
              fence_async_smem();
              mbar_expect_tx(bars + 8 * B_XT, 3 * 2304);
#pragma unroll 1
              for (int j = 5; j < 8; j++) tma2d(sb + x_off(j), &P.m_x, c.dk(), c.g2m * 128 + j * 16, bars + 8 * B_XT);
            } else {
              mbar_wait(bars + 8 * B_YDONE, 0);
              c.await_u(S, 1, tag);
              mbar_arrive(bars + 8 * B_ULATE);
            }
          }
        } else {
          if (c.g1m >= 0) {
            const int ch = c.fill();
            await(S, C_KV + ch / 96, tag * 128);
            fence_async_global();
            mbar_wait(bars + 8 * B_FILL, 0);
            sts128(sb + SLOT, 0, 0, 0, 0); sts128(sb + SLOT + 16, 0, 0, 0, 0);
            mbar_expect_tx(bars + 8 * B_CFULL, 8192 + 4096);
            bulk_load(sb + SLOT + 32, H.ssm_k + (size_t)ch * S_, 4096, bars + 8 * B_CFULL);
            bulk_load(sb, S->ub + (size_t)ch * 4096, 8192, bars + 8 * B_CFULL);
          }
          mbar_wait(bars + 8 * B_YDONE, 0);
          signal(S, C_Y);
          if (c.g2m >= 0) {
            await<true>(S, C_Y, tag * 132);
            mbar_arrive(bars + 8 * B_YRDY);
            if (blockIdx.x == 0) st_flag(S->epoch, tag);
            TLREC(19);
          }
        }
      }
    }
    TLEND();
  } else {
    asm volatile("barrier.cluster.arrive.relaxed.aligned;" ::: "memory");
    if (p0) {
      const int row = warp * 256 + blockIdx.x * 2 + (lane >> 4);
      const uint2* src = reinterpret_cast<const uint2*>(H.x + (size_t)row * D_) + (lane & 15);
      if (tid == 0 && (size_t)src != 1) TLREC(27);
      if (warp) pace(t0, XD0 + (warp - 1) * XD);
      uint32_t xr[18];
#pragma unroll
      for (int j = 0; j < 9; j++) asm volatile("ld.global.nc.v2.u32 {%0,%1}, [%2];" : "=r"(xr[2 * j]), "=r"(xr[2 * j + 1]) : "l"(src + 16 * j));
      float c[36];
      float s[4] = {0.f, 0.f, 0.f, 0.f};
#pragma unroll
      for (int i = 0; i < 18; i++) { c[2 * i] = bf_lo(xr[i]); c[2 * i + 1] = bf_hi(xr[i]); }
#pragma unroll
      for (int i = 0; i < 36; i++) s[i & 3] += c[i];
      const float ml = ((s[0] + s[1]) + (s[2] + s[3])) * (1.0f / 36.0f);
      if (tid == 0 && ml != 123.456f) TLREC(28);
#pragma unroll
      for (int i = 0; i < 36; i++) { c[i] -= ml; s[i & 3] = i < 4 ? c[i] * c[i] : fmaf(c[i], c[i], s[i & 3]); }
      float m = ml, q = (s[0] + s[1]) + (s[2] + s[3]), n2 = 18.f;
#pragma unroll
      for (int o = 1; o < 16; o <<= 1) {
        const float mo = __shfl_xor_sync(0xffffffffu, m, o), qo = __shfl_xor_sync(0xffffffffu, q, o);
        const float dl = m - mo;
        q = fmaf(dl * dl, n2, q + qo);
        m = 0.5f * (m + mo);
        n2 *= 2.f;
      }
      const float var = q * (1.0f / 576.0f);
      float mb, rinv, mb2, rinv2;
      ln_finish(m, var, mb, rinv);
      ln_finish((m - mb) * rinv, var * rinv * rinv, mb2, rinv2);
      const float ca = rinv * rinv2, cb = fmaf(ml - mb, rinv, -mb2) * rinv2;
      const uint32_t hs = sb + SM_DED + warp * 2304, ss = sb + SM_DED + 18432 + warp * 32;
#pragma unroll
      for (int j = 0; j < 9; j++)
        sts64(hs + (lane >> 4) * 1152 + (lane & 15) * 8 + j * 128, pack_bf16(fmaf(c[4 * j], ca, cb), fmaf(c[4 * j + 1], ca, cb)),
              pack_bf16(fmaf(c[4 * j + 2], ca, cb), fmaf(c[4 * j + 3], ca, cb)));
      if ((lane & 15) == 0) sts128(ss + lane, __float_as_uint(mb), __float_as_uint(rinv), 0, 0);
      __syncwarp();
      if (lane == 0) {
        if (tid == 0) TLREC(29);
        fence_async_smem();
        bulk_store(S->h + (size_t)row * D_, hs, 2304);
        bulk_store(S->stats + row, ss, 32);
        bulk_commit();
        bulk_wait_all();
        signal_stored(S, C_H + warp);
        if (tid == 0) TLREC(1);
        if (tid == 224) TLREC(31);
      }
      __syncwarp();
    }
    asm volatile("setmaxnreg.inc.sync.aligned.u32 224;");
    asm volatile("barrier.cluster.wait.aligned;" ::: "memory");
    const int wg = warp >> 2, w = warp & 3, g = lane >> 2, t = lane & 3, wtid = tid & 127;
    const bool elect = w == 0 && lane == 0;
    const uint64_t da0 = make_desc(sb + wg * 8192, 8192, 1024, 1);
    const uint32_t dm0 = (w == 0 && g + t == 7) ? 0xffffu : 0u, dm2 = (w == 0 && g + t == 3) ? 0xffffu : 0u;
    if (const Cta c; c.g1m >= 0) {
      const int frow = ((2 * c.g1m + c.rank) * 2 + wg) * 64 + w * 16 + g;
      const float hb0 = 0.5f * __bfloat162float(P.b1[frow]), hb1 = 0.5f * __bfloat162float(P.b1[frow + 8]);
      const uint32_t dd = __bfloat16_as_ushort(P.ssm_D[c.fill()]);
      {
        const uint64_t db0 = make_desc(sb + 16384, 8192, 1024, 1);
        float acc[96];
        Ring r{0, 0};
        uint32_t prev = 0;
        auto step = [&](int first, bool release) {
          mbar_wait(bars + 8 * (B_FULL + r.s), r.ph);
          const uint64_t da = da0 + r.s * (SLOT >> 4), db = db0 + r.s * (SLOT >> 4);
          wg_fence();
          wgmma_ss_n192_t11(acc, da, db, !first);
#pragma unroll
          for (int k = 1; k < 4; k++) wgmma_ss_n192_t11(acc, da + k * 128, db + k * 128, 1);
          wg_commit();
          if (release) { wg_wait<1>(); if (elect) mbar_arrive(bars + 8 * (B_EMPTY + prev)); }
          prev = r.s;
          r.next();
        };
        step(1, false);
        if (tid == 0) TLREC(3);
#pragma unroll 1
        for (int kb = 1; kb < G1_KB - G1_TAIL; kb++) step(0, true);
        if (elect) TLREC(20 + wg);
        if (wg == 1) {
          wg_wait<0>();
          if (elect) mbar_arrive(bars + 8 * (B_EMPTY + prev));
          bar_sync(5, 256);
        }
        step(0, wg == 0);
#pragma unroll 1
        for (int kb = G1_KB - G1_TAIL + 1; kb < G1_KB - 1; kb++) step(0, true);
        step(0, wg == 1);
        if (wg == 0) bar_arrive(5, 256);
        wg_wait<0>();
        pin_regs<96>(acc);
        if (elect) TLREC(4 + wg);
        if (wg == 0 && lane == 0) mbar_arrive(bars + 8 * B_FILL);
        mbar_wait(bars + 8 * (wg == 0 ? B_KVDONE : B_FILL), 0);
        const uint32_t stg = wg == 0 ? sb + SM_DED : sb + SLOT + 16384;
        const uint32_t sa = stg + ((lane >> 4) * 8 + (lane & 7)) * 128 + (((2 * w + ((lane >> 3) & 1)) ^ (lane & 7)) << 4);
#pragma unroll
        for (int ck = 0; ck < 3; ck++) {
          const uint32_t zero = blockIdx.y;
          uint32_t pk[16];
#pragma unroll
          for (int i = 0; i < 16; i++) {
            float hb = (i & 1) ? hb1 : hb0;
            if (i >= 6) asm("lop3.b32 %0, %1, %2, %3, 0xea;" : "=f"(hb) : "r"(pk[i - 6]), "r"(zero), "f"((i & 1) ? hb1 : hb0));
            pk[i] = pack_bf16(gelu_half(fmaf(acc[32 * ck + 2 * i], 0.5f, hb)), gelu_half(fmaf(acc[32 * ck + 2 * i + 1], 0.5f, hb)));
            if ((i & 3) == 3) stsm4t(sa + ck * 8192 + (i >> 2) * 2048, pk[i - 3], pk[i - 2], pk[i - 1], pk[i]);
          }
          __syncwarp();
          if (lane == 0) mbar_arrive(bars + 8 * (B_STG + wg * 3 + ck));
          if (ck < 2) mbar_wait(bars + 8 * B_KVDONE, 0);
        }
      }
      if (wg == 0) {
        uint32_t a[64];
        float acc[128];
        mbar_wait(bars + 8 * B_CFULL, 0);
#pragma unroll
        for (int j = 0; j < 32; j++) CONV_LDA(j, sb + SLOT + (8 * w + g + t + 1) * 4)
        a[0] = badd2(a[0], dd & dm0); a[2] = badd2(a[2], dd & dm2);
        wg_fence();
        conv_mma(acc, a, make_desc(sb, 4096, 128, 0));
        wg_commit();
        mbar_wait(bars + 8 * B_DED, 0);
        wg_wait<0>();
        pin_regs<128>(acc);
        if (elect) { TLREC(17); mbar_arrive(bars + 8 * B_EMPTY); mbar_arrive(bars + 8 * (B_EMPTY + 1)); }
        const uint32_t red = sb + SM_DED;
        if (lane < 8 * w) sts32(red + w * CV_REDW + lane * 4, 0);
#pragma unroll
        for (int j = 0; j < 32; j++) sts32(red + w * CV_REDW + (8 * (3 - t + w) + g) * 4 + j * 128, conv_part(acc, j));
        bar_sync(3, 128);
        uint4 p[2][4];
#pragma unroll
        for (int i = 0; i < 8; i++) p[i >> 2][i & 3] = lds128(red + (i & 3) * CV_REDW + (wtid + 128 * (i >> 2)) * 16);
        conv_out(H.S, p, Cta().fill(), wtid);
        __syncwarp();
        if (lane == 0) mbar_arrive(bars + 8 * B_YDONE);
        if (elect) TLREC(18);
      }
    } else {
      const int cvc = c.cvc(), n_conv = c.n_conv();
      const uint32_t red = wg == 0 ? sb + SM_DED : sb + CV_RED1;
      bar_sync(2, 256);
      if (wtid < 8 * CV_NSLOT / 2) sts32(sb + (2 * (wtid >> 3) + wg) * CV_SLOT + CV_KOFF + (wtid & 7) * 4, 0);
      sts32(red + w * CV_REDW + lane * 4, 0);
      bar_sync(3 + wg, 128);
      const uint32_t ko = sb + CV_KOFF + (8 * w + g + t + 1) * 4;
      const uint32_t wr = red + w * CV_REDW + (8 * (3 - t + w) + g) * 4;
      uint32_t a[64];
      uint32_t dd = __bfloat16_as_ushort(P.ssm_D[conv_channel(cvc, wg)]);
      mbar_wait(bars + 8 * (B_CFULL + wg), 0);
      if (tid == 0) TLREC(17);
#pragma unroll
      for (int j = 0; j < 32; j++) CONV_LDA(j, ko + wg * CV_SLOT)
      if (wg == 1) bar_arrive(5, 256);
#pragma unroll 1
      for (int i = wg; i < n_conv; i += 2) {
        const int s = i % CV_NSLOT;
        const int in = i + 2 < n_conv ? i + 2 : i, sn = in % CV_NSLOT;
        a[0] = badd2(a[0], dd & dm0); a[2] = badd2(a[2], dd & dm2);
        dd = __bfloat16_as_ushort(P.ssm_D[conv_channel(cvc, in)]);
        float acc[128];
        bar_sync(5 + wg, 256);
        wg_fence();
        conv_mma(acc, a, make_desc(sb + s * CV_SLOT, 4096, 128, 0));
        wg_commit();
        if (i + 1 < n_conv) bar_arrive(5 + (wg ^ 1), 256);
        wg_wait<0>();
        pin_regs<128>(acc);
        if (lane == 0) mbar_arrive(bars + 8 * (B_CEMPTY + s));
        mbar_wait(bars + 8 * (B_CFULL + sn), (in / CV_NSLOT) & 1);
        const uint32_t ka = ko + sn * CV_SLOT;
#pragma unroll
        for (int j = 0; j < 32; j++) {
          if (j < 24) CONV_LDA(j, ka)
          sts32(wr + j * 128, conv_part(acc, j));
        }
        bar_sync(3 + wg, 128);
        uint4 p[2][4];
#pragma unroll
        for (int x = 0; x < 8; x++) p[x >> 2][x & 3] = lds128(red + (x & 3) * CV_REDW + (wtid + 128 * (x >> 2)) * 16);
#pragma unroll
        for (int j = 24; j < 32; j++) CONV_LDA(j, ka)
        conv_out(H.S, p, conv_channel(cvc, i), wtid);
      }
      fence_async_smem();
      bar_sync(3 + wg, 128);
      if (elect) { mbar_arrive(bars + 8 * B_EMPTY); mbar_arrive(bars + 8 * (B_EMPTY + 1)); TLREC(20 + wg); }
      if (lane == 0) mbar_arrive(bars + 8 * B_YDONE);
      __syncwarp();
    }
    if (const Cta c; c.g2m >= 0) {
      const int srow = c.g2m * 128 + wg * 64 + w * 16 + g;
      const uint64_t db0 = make_desc(sb + 16384, 16, 1024, 1);
      float acc[72], acc2[36], acc3[36];
      Ring r{G1_KB % NSTAGE, (G1_KB / NSTAGE) & 1};
      uint32_t prev = 0;
      auto step = [&](int first) {
        mbar_wait(bars + 8 * (B_FULL + r.s), r.ph);
        const uint64_t da = da0 + r.s * (SLOT >> 4), db = db0 + r.s * (SLOT >> 4);
        wg_fence();
        wgmma_ss_n144_t10(acc, da, db, !first);
#pragma unroll
        for (int k = 1; k < 4; k++) wgmma_ss_n144_t10(acc, da + k * 128, db + k * 2, 1);
        wg_commit();
        if (!first) { wg_wait<1>(); if (elect) mbar_arrive(bars + 8 * (B_EMPTY + prev)); }
        prev = r.s;
        r.next();
      };
      step(1);
      if (tid == 128) TLREC(7);
      const float2 st0 = __ldcg(reinterpret_cast<const float2*>(S->stats + srow)), st1 = __ldcg(reinterpret_cast<const float2*>(S->stats + srow + 8));
      const float hb0 = 0.5f * __bfloat162float(P.b2[srow]), hb1 = 0.5f * __bfloat162float(P.b2[srow + 8]);
#pragma unroll 1
      for (int kb = 1; kb < G2_KB - G2_TAIL; kb++) step(0);
      if (tid == 0) TLREC(30);
      const uint32_t xo = sb + x_off(warp);
      const uint32_t xa = xo + (lane & 15) * 144 + (lane >> 4) * 16;
      uint32_t xx[18], ss[18];
      auto prep = [&]() {
        mbar_wait(bars + 8 * B_XT, 0);
        mbar_wait(bars + 8 * B_Y2, 0);
        const uint32_t ya = sb + SM_DED + wg * 9216 + ((lane >> 4) * 8 + (lane & 7)) * 128 + (((2 * w + ((lane >> 3) & 1)) ^ (lane & 7)) << 4);
#pragma unroll
        for (int q = 0; q < 8; q += 2) { ldsm4(xx + 2 * q, xa + q * 16); ldsm4t(ss + 2 * q, ya + q * 1024); }
        ldsm2(xx + 16, xo + (lane & 15) * 144 + 128);
        ldsm2t(ss + 16, ya - (lane >> 4) * 1024 + 8 * 1024);
        const uint32_t m0 = pack_bf16(st0.x, st0.x), m1 = pack_bf16(st1.x, st1.x);
#pragma unroll
        for (int i = 0; i < 18; i++) ss[i] = bmul2(ln_apply(xx[i], (i & 1) ? m1 : m0, (i & 1) ? st1.y : st0.y), ss[i]);
      };
      if (wg == 1) {
        wg_wait<0>();
        if (elect) mbar_arrive(bars + 8 * (B_EMPTY + XSLOT));
        prep();
        bar_sync(5, 256);
      }
#pragma unroll
      for (int kb = G2_KB - G2_TAIL; kb < G2_KB; kb++) {
        const int p = G1_KB + kb, s = p % NSTAGE;
        mbar_wait(bars + 8 * (B_FULL + s), (p / NSTAGE) & 1);
        wg_fence();
#pragma unroll
        for (int k = 0; k < 4; k++)
          wgmma_ss_n72_t10(acc3, da0 + s * (SLOT >> 4) + k * 128, db0 + s * (SLOT >> 4) + k * 2, kb != G2_KB - G2_TAIL || k != 0);
        wg_commit();
        if (kb == G2_KB - G2_TAIL) { wg_wait<1>(); if (tid == 0) mbar_arrive(bars + 8 * (B_EMPTY + XSLOT)); }
      }
      bar_arrive(5 + wg, 256);
      wg_wait<0>();
      pin_regs<72>(acc);
      pin_regs<36>(acc3);
      const uint32_t xz = sb + XSLOT * SLOT + wg * 18432 + wtid * 16;
      mbar_wait(bars + 8 * B_XRDY, 0);
      {
        const uint32_t rz = mapa(xz, c.rank ^ 1), rb = mapa(bars + 8 * (B_XFULL + wg), c.rank ^ 1);
#pragma unroll
        for (int q = 0; q < 9; q++)
          asm volatile("st.async.weak.shared::cluster.mbarrier::complete_tx::bytes.v4.f32 [%0], {%1,%2,%3,%4}, [%5];"
                       :: "r"(rz + q * 2048), "f"(acc[4 * q] + acc3[4 * q]), "f"(acc[4 * q + 1] + acc3[4 * q + 1]), "f"(acc[4 * q + 2] + acc3[4 * q + 2]),
                          "f"(acc[4 * q + 3] + acc3[4 * q + 3]), "r"(rb) : "memory");
      }
      if (wg == 0) prep();
      bar_sync(6 - wg, 256);
      wg_fence();
#pragma unroll
      for (int kb = G2_KB - G2_TAIL; kb < G2_KB; kb++) {
        const int s = (G1_KB + kb) % NSTAGE;
#pragma unroll
        for (int k = 0; k < 4; k++)
          wgmma_ss_n72_t10(acc2, da0 + s * (SLOT >> 4) + k * 128, db0 + s * (SLOT >> 4) + (9216 >> 4) + k * 2, kb != G2_KB - G2_TAIL || k != 0);
      }
      wg_commit();
      if (wg == 0) bar_arrive(5, 256);
      mbar_wait_cluster(bars + 8 * (B_XFULL + wg), 0);
#pragma unroll
      for (int q = 0; q < 9; q++) {
        const float4 pv = lds128f(xz + q * 2048);
        acc[36 + 4 * q] = fmaf(acc[36 + 4 * q] + pv.x, 0.5f, hb0); acc[37 + 4 * q] = fmaf(acc[37 + 4 * q] + pv.y, 0.5f, hb0);
        acc[38 + 4 * q] = fmaf(acc[38 + 4 * q] + pv.z, 0.5f, hb1); acc[39 + 4 * q] = fmaf(acc[39 + 4 * q] + pv.w, 0.5f, hb1);
      }
      wg_wait<0>();
      pin_regs<36>(acc2);
      if (elect) TLREC(9 + wg);
      uint32_t ob[18];
#pragma unroll
      for (int i = 0; i < 18; i++)
        ob[i] = bfma2(ss[i], pack_bf16(silu_half(fmaf(acc2[2 * i], 0.5f, acc[36 + 2 * i])), silu_half(fmaf(acc2[2 * i + 1], 0.5f, acc[37 + 2 * i]))), xx[i]);
#pragma unroll
      for (int q = 0; q < 8; q += 2) stsm4(xa + q * 16, ob[2 * q], ob[2 * q + 1], ob[2 * q + 2], ob[2 * q + 3]);
      stsm2(xo + (lane & 15) * 144 + 128, ob[16], ob[17]);
      __syncwarp();
      if (lane == 0) {
        fence_async_smem();
        tma2d_store(&P.m_out, xo, Cta().dk(), srow);
        bulk_commit();
        bulk_wait_read();
      }
      if (elect) TLREC(11 + wg);
    }
    TLEND();
  }
}

typedef CUresult (*EncodeFn)(CUtensorMap*, CUtensorMapDataType, cuuint32_t, void*, const cuuint64_t*, const cuuint64_t*, const cuuint32_t*,
                             const cuuint32_t*, CUtensorMapInterleave, CUtensorMapSwizzle, CUtensorMapL2promotion, CUtensorMapFloatOOBfill);

#define L2PROM CU_TENSOR_MAP_L2_PROMOTION_L2_256B
void make_map(EncodeFn fn, CUtensorMap* m, const void* ptr, int rank, const cuuint64_t* dims, const cuuint64_t* strides, const cuuint32_t* box,
              CUtensorMapSwizzle sw) {
  const cuuint32_t es[3] = {1, 1, 1};
  fn(m, CU_TENSOR_MAP_DATA_TYPE_BFLOAT16, rank, const_cast<void*>(ptr), dims, strides, box, es, CU_TENSOR_MAP_INTERLEAVE_NONE, sw,
     L2PROM, CU_TENSOR_MAP_FLOAT_OOB_FILL_NONE);
}

}

extern "C" void kernel_launch(void* const* d_in, const int* in_sizes, int n_in, void* d_out, int out_size) {
  static Params P;
  static Hot H;
  static const void* cached[4] = {nullptr, nullptr, nullptr, nullptr};
  if (cached[0] != d_in[7] || cached[1] != d_in[9] || cached[2] != d_out || cached[3] != d_in[0]) {
    void* fp = nullptr;
    cudaDriverEntryPointQueryResult qr;
    cudaGetDriverEntryPoint("cuTensorMapEncodeTiled", &fp, cudaEnableDefault, &qr);
    EncodeFn fn = (EncodeFn)fp;
    void* ps;
    cudaGetSymbolAddress(&ps, g_scratch);
    H.S = (Scratch*)ps;
    const void *ph = (char*)ps + offsetof(Scratch, h), *pu = (char*)ps + offsetof(Scratch, u), *py = (char*)ps + offsetof(Scratch, y),
               *pb = (char*)ps + offsetof(Scratch, ub);
    { cuuint64_t d[3] = {64, S_, F_ / 64}, s[2] = {F_ * 2, 128}; cuuint32_t b[3] = {64, 64, 2}; make_map(fn, &P.m_w1, d_in[7], 3, d, s, b, CU_TENSOR_MAP_SWIZZLE_128B); }
    { cuuint64_t d[3] = {64, S_, D_ / 64}, s[2] = {D_ * 2, 128}; cuuint32_t b[3] = {64, 64, 3}; make_map(fn, &P.m_h, ph, 3, d, s, b, CU_TENSOR_MAP_SWIZZLE_128B); }
    { cuuint64_t d[2] = {F_, D_}, s[1] = {F_ * 2}; cuuint32_t b[2] = {64, 64}; make_map(fn, &P.m_ust, pu, 2, d, s, b, CU_TENSOR_MAP_SWIZZLE_128B); }
    { cuuint64_t d[3] = {64, F_, S_ / 64}, s[2] = {S_ * 2, 128}; cuuint32_t b[3] = {64, 64, 2}; make_map(fn, &P.m_w2, d_in[9], 3, d, s, b, CU_TENSOR_MAP_SWIZZLE_128B); }
    { cuuint64_t d[2] = {F_, D_}, s[1] = {F_ * 2}; cuuint32_t b[2] = {64, 72}; make_map(fn, &P.m_uld, pu, 2, d, s, b, CU_TENSOR_MAP_SWIZZLE_128B); }
    { cuuint64_t d[2] = {D_, S_}, s[1] = {D_ * 2}; cuuint32_t b[2] = {72, 16}; make_map(fn, &P.m_out, d_out, 2, d, s, b, CU_TENSOR_MAP_SWIZZLE_NONE);
      make_map(fn, &P.m_x, d_in[0], 2, d, s, b, CU_TENSOR_MAP_SWIZZLE_NONE); }
    { cuuint64_t d[2] = {S_, D_}, s[1] = {S_ * 2}; cuuint32_t b[2] = {64, 24}; make_map(fn, &P.m_y, py, 2, d, s, b, CU_TENSOR_MAP_SWIZZLE_128B); }
    { cuuint64_t d[3] = {2048, D_ / 2, 4}, s[2] = {16384, 4096}; cuuint32_t b[3] = {16, 48, 4}; make_map(fn, &P.m_ub, pb, 3, d, s, b, CU_TENSOR_MAP_SWIZZLE_NONE); }
    cudaFuncSetAttribute(fused_kernel, cudaFuncAttributeMaxDynamicSharedMemorySize, SM_TOTAL);
    cached[0] = d_in[7]; cached[1] = d_in[9]; cached[2] = d_out; cached[3] = d_in[0];
  }
  H.x = (const __nv_bfloat16*)d_in[0]; H.k = (const __nv_bfloat16*)d_in[1]; H.v = (const __nv_bfloat16*)d_in[2];
  H.shift_k = (const __nv_bfloat16*)d_in[3]; H.ssm_k = (const __nv_bfloat16*)d_in[4]; P.ssm_D = (const __nv_bfloat16*)d_in[5];
  P.b1 = (const __nv_bfloat16*)d_in[8]; P.b2 = (const __nv_bfloat16*)d_in[10];
  fused_kernel<<<132, 384, SM_TOTAL>>>(H, P);
}
```

```cpp
#include <cuda_runtime.h>
#include <cuda.h>
#include <cuda_bf16.h>
#include <stddef.h>
#include <stdint.h>

namespace {

constexpr int S_ = 2048, D_ = 576, F_ = 4608;
constexpr int NSTAGE = 5, SLOT = 36864;
constexpr int G1_KB = 32, G2_KB = 36;
constexpr int G1_BYTES = 36864, G2_BYTES = 16384 + 18432;
#define NCV_LEFT 5
constexpr int NCV_REG = 4, NCV_LONG = (D_ - 108 * NCV_REG - 20 * NCV_LEFT) / 4;
static_assert(108 * NCV_REG + 20 * NCV_LEFT + 4 * NCV_LONG == D_, "conv split");
constexpr int KV_ROUNDS = 6;
constexpr int NW0 = 1;
constexpr int G1_TAIL = 4, G2_TAIL = 3;
constexpr int SYNCKB = 5;
constexpr int G2_PREP = 28;

constexpr int CV_KOFF = 8192, CV_SLOT = 8192 + 4224, CV_REDW = 2112 * 2;
constexpr int SM_DED = NSTAGE * SLOT;
constexpr int SM_CV = SM_DED + 20480;
constexpr int SM_ST1 = SLOT;
constexpr int SM_BAR = SM_CV + 2 * CV_SLOT;
constexpr int SM_TOTAL = SM_BAR + 1024;
static_assert(G1_KB % NSTAGE == 2, "slots 0 and 1 hold the last two GEMM1 k-blocks");
constexpr int XSLOT = (G1_KB + G2_KB) % NSTAGE;
__device__ __forceinline__ uint32_t cv_slot(int i) { return (i & 2 ? 0 : SM_CV) + (i & 1) * CV_SLOT; }
constexpr int bar_at(int i) { return SM_BAR + 8 * i; }
constexpr int B_FULL = bar_at(0)  , B_KFULL = bar_at(5)  , B_UFULL = bar_at(9)  , B_KVDONE = bar_at(13), B_SFREE = bar_at(14)  ,
              B_XRDY = bar_at(16), B_XFULL = bar_at(17)  , B_XY = bar_at(19), B_YRDY = bar_at(20), B_GO = bar_at(21),
              B_EMPTY = bar_at(22)  ,
              B_CEMPTY = bar_at(27)  , B_STG = bar_at(31)  ,
              B_G1DONE = bar_at(33), B_YDONE = bar_at(34), B_DONE = bar_at(35);
constexpr int C_H = 0, C_KV = 1, C_U = 2, C_Y = 3, C_SYNC = 4, C_EPOCH = 5, C_COUNT = 6;
constexpr uint32_t EPOCH = 128 * 33;

struct Scratch {
  uint32_t cnt[C_COUNT * 32];
  alignas(1024) uint4 stats[S_];
  alignas(1024) __nv_bfloat16 h[S_ * D_];
  alignas(1024) __nv_bfloat16 ub[D_ * 4096];
  alignas(1024) __nv_bfloat16 y[D_ * S_];
  alignas(1024) __nv_bfloat16 u[D_ * F_];
};
__device__ Scratch g_scratch;

struct Hot {
  const __nv_bfloat16 *x, *k, *v, *shift_k, *ssm_k;
  Scratch* S;
};
struct Role {
  int8_t fg;
  int8_t at;
  int8_t sg;
  int8_t dk, ds;
  int8_t ncv;
  int16_t ch;
};
struct Params {
  const __nv_bfloat16 *ssm_D, *b1, *b2;
  Role role[132];
  CUtensorMap m_w1, m_w1l, m_ust, m_w2, m_uld, m_out, m_x, m_y, m_ub;
};

#define TLREC(i) do { } while (0)
#define TLEND() do { } while (0)

__device__ __forceinline__ uint32_t smem_u32(const void* p) { return (uint32_t)__cvta_generic_to_shared(p); }
__device__ __forceinline__ void mbar_init(uint32_t bar, uint32_t cnt) { asm volatile("mbarrier.init.shared::cta.b64 [%0], %1;" :: "r"(bar), "r"(cnt) : "memory"); }
__device__ __forceinline__ void mbar_expect_tx(uint32_t bar, uint32_t bytes) { asm volatile("mbarrier.arrive.expect_tx.shared::cta.b64 _, [%0], %1;" :: "r"(bar), "r"(bytes) : "memory"); }
__device__ __forceinline__ void mbar_arrive(uint32_t bar) { asm volatile("mbarrier.arrive.shared::cta.b64 _, [%0];" :: "r"(bar) : "memory"); }
__device__ __forceinline__ uint32_t mapa(uint32_t addr, uint32_t cta) { uint32_t r; asm volatile("mapa.shared::cluster.u32 %0, %1, %2;" : "=r"(r) : "r"(addr), "r"(cta)); return r; }
__device__ __forceinline__ void mbar_arrive_remote(uint32_t rbar) { asm volatile("mbarrier.arrive.shared::cluster.b64 _, [%0];" :: "r"(rbar) : "memory"); }
__device__ __forceinline__ uint32_t clk() { uint32_t c; asm volatile("mov.u32 %0, %%clock;" : "=r"(c)); return c; }
__device__ __forceinline__ bool elect_one() {
  uint32_t p; asm volatile("{ .reg .pred p; elect.sync _|p, 0xffffffff; selp.u32 %0, 1, 0, p; }" : "=r"(p)); return p;
}
__device__ __forceinline__ void guard(uint32_t t0) { if ((int32_t)(clk() - t0) < 0) __trap(); }
__device__ __forceinline__ void mbar_wait(uint32_t bar, uint32_t parity) {
  asm volatile("{\n .reg .pred p;\n W_%=:\n mbarrier.try_wait.parity.shared::cta.b64 p, [%0], %1;\n @!p bra W_%=;\n }" :: "r"(bar), "r"(parity) : "memory");
}
__device__ __forceinline__ void mbar_wait_cluster(uint32_t bar, uint32_t parity) {
  asm volatile("{\n .reg .pred p;\n W_%=:\n mbarrier.try_wait.parity.acquire.cluster.shared::cta.b64 p, [%0], %1;\n @!p bra W_%=;\n }" :: "r"(bar), "r"(parity) : "memory");
}
__device__ __forceinline__ bool mbar_try(uint32_t bar, uint32_t parity) {
  uint32_t ok;
  asm volatile("{ .reg .pred p; mbarrier.try_wait.parity.shared::cta.b64 p, [%1], %2; selp.u32 %0, 1, 0, p; }" : "=r"(ok) : "r"(bar), "r"(parity) : "memory");
  return ok;
}
__device__ __forceinline__ void mbar_wait_guarded(uint32_t bar, uint32_t t0, uint32_t parity = 0) { while (!mbar_try(bar, parity)) guard(t0); }
__device__ __forceinline__ void tma2d(uint32_t dst, const CUtensorMap* m, int c0, int c1, uint32_t bar) {
  asm volatile("cp.async.bulk.tensor.2d.shared::cluster.global.mbarrier::complete_tx::bytes [%0], [%1, {%3, %4}], [%2];"
               :: "r"(dst), "l"(m), "r"(bar), "r"(c0), "r"(c1) : "memory");
}
__device__ __forceinline__ void tma3d(uint32_t dst, const CUtensorMap* m, int c0, int c1, int c2, uint32_t bar) {
  asm volatile("cp.async.bulk.tensor.3d.shared::cluster.global.mbarrier::complete_tx::bytes [%0], [%1, {%3, %4, %5}], [%2];"
               :: "r"(dst), "l"(m), "r"(bar), "r"(c0), "r"(c1), "r"(c2) : "memory");
}
__device__ __forceinline__ void tma2d_store(const CUtensorMap* m, uint32_t src, int c0, int c1) {
  asm volatile("cp.async.bulk.tensor.2d.global.shared::cta.bulk_group [%0, {%2, %3}], [%1];" :: "l"(m), "r"(src), "r"(c0), "r"(c1) : "memory");
}
__device__ __forceinline__ void bulk_load(uint32_t dst, const void* src, uint32_t bytes, uint32_t bar) {
  asm volatile("cp.async.bulk.shared::cluster.global.mbarrier::complete_tx::bytes [%0], [%1], %2, [%3];" :: "r"(dst), "l"(src), "r"(bytes), "r"(bar) : "memory");
}
__device__ __forceinline__ void tma3d_store(const CUtensorMap* m, uint32_t src, int c0, int c1, int c2) {
  asm volatile("cp.async.bulk.tensor.3d.global.shared::cta.bulk_group [%0, {%2, %3, %4}], [%1];" :: "l"(m), "r"(src), "r"(c0), "r"(c1), "r"(c2) : "memory");
}
__device__ __forceinline__ void bulk_commit() { asm volatile("cp.async.bulk.commit_group;" ::: "memory"); }
__device__ __forceinline__ void bulk_wait_all() { asm volatile("cp.async.bulk.wait_group 0;" ::: "memory"); }
__device__ __forceinline__ void bulk_wait_read() { asm volatile("cp.async.bulk.wait_group.read 0;" ::: "memory"); }
__device__ __forceinline__ void fence_async_smem() { asm volatile("fence.proxy.async.shared::cta;" ::: "memory"); }
__device__ __forceinline__ void fence_async_global() { asm volatile("fence.proxy.async.global;" ::: "memory"); }
__device__ __forceinline__ uint32_t ld_cnt(Scratch* S, int c) { uint32_t v; asm volatile("ld.relaxed.gpu.global.u32 %0, [%1];" : "=r"(v) : "l"(S->cnt + c * 32) : "memory"); return v; }
__device__ __forceinline__ void signal(Scratch* S, int c, uint32_t inc) { asm volatile("red.release.gpu.global.add.u32 [%0], %1;" :: "l"(S->cnt + c * 32), "r"(inc) : "memory"); }
__device__ __forceinline__ bool reached(Scratch* S, int c, uint32_t ep) { return ld_cnt(S, c) - ep >= EPOCH; }
__device__ __forceinline__ void await(Scratch* S, int c, uint32_t ep) { while (!reached(S, c, ep)) { } }
__device__ __forceinline__ void await_guarded(Scratch* S, int c, uint32_t ep, uint32_t t0) { while (!reached(S, c, ep)) { __nanosleep(200); guard(t0); } }
__device__ __forceinline__ void bar_sync(int id, int n) { asm volatile("bar.sync %0, %1;" :: "r"(id), "r"(n) : "memory"); }
__device__ __forceinline__ void bar_arrive(int id, int n) { asm volatile("bar.arrive %0, %1;" :: "r"(id), "r"(n) : "memory"); }
__device__ __forceinline__ void wg_fence() { asm volatile("wgmma.fence.sync.aligned;" ::: "memory"); }
__device__ __forceinline__ void wg_commit() { asm volatile("wgmma.commit_group.sync.aligned;" ::: "memory"); }
template <int N> __device__ __forceinline__ void wg_wait() { asm volatile("wgmma.wait_group.sync.aligned %0;" :: "n"(N) : "memory"); }
template <int N> __device__ __forceinline__ void pin_regs(float* a) {
#pragma unroll
  for (int i = 0; i < N; i++) asm volatile("" : "+f"(a[i]) :: "memory");
}
__device__ __forceinline__ uint64_t make_desc(uint32_t addr, uint32_t lbo, uint32_t sbo, uint32_t swz) {
  return (uint64_t)((addr & 0x3FFFF) >> 4) | ((uint64_t)(lbo >> 4) << 16) | ((uint64_t)(sbo >> 4) << 32) | ((uint64_t)swz << 62);
}
__device__ __forceinline__ uint32_t pack_bf16(float lo, float hi) { uint32_t r; asm("cvt.rn.bf16x2.f32 %0, %1, %2;" : "=r"(r) : "f"(hi), "f"(lo)); return r; }
__device__ __forceinline__ float bf_lo(uint32_t p) { return __uint_as_float(p << 16); }
__device__ __forceinline__ float bf_hi(uint32_t p) { return __uint_as_float(p & 0xffff0000u); }
__device__ __forceinline__ float round_bf16(float v) { return bf_lo(pack_bf16(v, 0.f)); }
__device__ __forceinline__ uint32_t bmul2(uint32_t a, uint32_t b) { uint32_t r; asm("mul.rn.bf16x2 %0, %1, %2;" : "=r"(r) : "r"(a), "r"(b)); return r; }
__device__ __forceinline__ uint32_t badd2(uint32_t a, uint32_t b) { uint32_t r; asm("add.rn.bf16x2 %0, %1, %2;" : "=r"(r) : "r"(a), "r"(b)); return r; }
__device__ __forceinline__ uint32_t bfma2(uint32_t a, uint32_t b, uint32_t c) { uint32_t r; asm("fma.rn.bf16x2 %0, %1, %2, %3;" : "=r"(r) : "r"(a), "r"(b), "r"(c)); return r; }
__device__ __forceinline__ uint32_t bsub2(uint32_t a, uint32_t b) { uint32_t r; asm("sub.rn.bf16x2 %0, %1, %2;" : "=r"(r) : "r"(a), "r"(b)); return r; }
__device__ __forceinline__ float tanh_fast(float v) { float r; asm("tanh.approx.f32 %0, %1;" : "=f"(r) : "f"(v)); return r; }
__device__ __forceinline__ float gelu_half(float h) {
  return fmaf(h, tanh_fast(h * fmaf(h * h, 8.0f * 0.7978845608028654f * 0.044715f, 2.0f * 0.7978845608028654f)), h);
}
__device__ __forceinline__ float silu_half(float h) { return fmaf(h, tanh_fast(h), h); }
__device__ __forceinline__ uint32_t ldg32(const void* p) { uint32_t v; asm volatile("ld.global.u32 %0, [%1];" : "=r"(v) : "l"(p) : "memory"); return v; }
__device__ __forceinline__ uint4 lds128(uint32_t a) { uint4 v; asm volatile("ld.shared.v4.u32 {%0,%1,%2,%3}, [%4];" : "=r"(v.x), "=r"(v.y), "=r"(v.z), "=r"(v.w) : "r"(a) : "memory"); return v; }
__device__ __forceinline__ void sts128(uint32_t a, uint32_t x, uint32_t y, uint32_t z, uint32_t w) {
  asm volatile("st.shared.v4.u32 [%0], {%1,%2,%3,%4};" :: "r"(a), "r"(x), "r"(y), "r"(z), "r"(w) : "memory");
}
__device__ __forceinline__ void sts32(uint32_t a, uint32_t v) { asm volatile("st.shared.u32 [%0], %1;" :: "r"(a), "r"(v) : "memory"); }
__device__ __forceinline__ void ldsm4(uint32_t* r, uint32_t a) {
  asm volatile("ldmatrix.sync.aligned.m8n8.x4.shared.b16 {%0,%1,%2,%3}, [%4];" : "=r"(r[0]), "=r"(r[1]), "=r"(r[2]), "=r"(r[3]) : "r"(a) : "memory");
}
__device__ __forceinline__ void ldsm2(uint32_t* r, uint32_t a) {
  asm volatile("ldmatrix.sync.aligned.m8n8.x2.shared.b16 {%0,%1}, [%2];" : "=r"(r[0]), "=r"(r[1]) : "r"(a) : "memory");
}
__device__ __forceinline__ void ldsm4t(uint32_t* r, uint32_t a) {
  asm volatile("ldmatrix.sync.aligned.m8n8.x4.trans.shared.b16 {%0,%1,%2,%3}, [%4];" : "=r"(r[0]), "=r"(r[1]), "=r"(r[2]), "=r"(r[3]) : "r"(a) : "memory");
}
__device__ __forceinline__ void ldsm2t(uint32_t* r, uint32_t a) {
  asm volatile("ldmatrix.sync.aligned.m8n8.x2.trans.shared.b16 {%0,%1}, [%2];" : "=r"(r[0]), "=r"(r[1]) : "r"(a) : "memory");
}
__device__ __forceinline__ void stsm4(uint32_t a, uint32_t r0, uint32_t r1, uint32_t r2, uint32_t r3) {
  asm volatile("stmatrix.sync.aligned.m8n8.x4.shared.b16 [%0], {%1,%2,%3,%4};" :: "r"(a), "r"(r0), "r"(r1), "r"(r2), "r"(r3) : "memory");
}
__device__ __forceinline__ void stsm2(uint32_t a, uint32_t r0, uint32_t r1) {
  asm volatile("stmatrix.sync.aligned.m8n8.x2.shared.b16 [%0], {%1,%2};" :: "r"(a), "r"(r0), "r"(r1) : "memory");
}
__device__ __forceinline__ void stsm4t(uint32_t a, uint32_t r0, uint32_t r1, uint32_t r2, uint32_t r3) {
  asm volatile("stmatrix.sync.aligned.m8n8.x4.trans.shared.b16 [%0], {%1,%2,%3,%4};" :: "r"(a), "r"(r0), "r"(r1), "r"(r2), "r"(r3) : "memory");
}

__device__ __forceinline__ void wgmma_ss_n144_t10(float* d, uint64_t da, uint64_t db, int sd) {
  asm volatile("{ .reg .pred p; setp.ne.b32 p, %74, 0;\n"
      "wgmma.mma_async.sync.aligned.m64n144k16.f32.bf16.bf16 {"
      "%0,%1,%2,%3,%4,%5,%6,%7,%8,%9,%10,%11,%12,%13,%14,%15,"
      "%16,%17,%18,%19,%20,%21,%22,%23,%24,%25,%26,%27,%28,%29,%30,%31,"
      "%32,%33,%34,%35,%36,%37,%38,%39,%40,%41,%42,%43,%44,%45,%46,%47,"
      "%48,%49,%50,%51,%52,%53,%54,%55,%56,%57,%58,%59,%60,%61,%62,%63,"
      "%64,%65,%66,%67,%68,%69,%70,%71"
      "}, %72, %73, p, 1, 1, 1, 0; }"
    : "+f"(d[0]), "+f"(d[1]), "+f"(d[2]), "+f"(d[3]), "+f"(d[4]), "+f"(d[5]), "+f"(d[6]), "+f"(d[7]),
      "+f"(d[8]), "+f"(d[9]), "+f"(d[10]), "+f"(d[11]), "+f"(d[12]), "+f"(d[13]), "+f"(d[14]), "+f"(d[15]),
      "+f"(d[16]), "+f"(d[17]), "+f"(d[18]), "+f"(d[19]), "+f"(d[20]), "+f"(d[21]), "+f"(d[22]), "+f"(d[23]),
      "+f"(d[24]), "+f"(d[25]), "+f"(d[26]), "+f"(d[27]), "+f"(d[28]), "+f"(d[29]), "+f"(d[30]), "+f"(d[31]),
      "+f"(d[32]), "+f"(d[33]), "+f"(d[34]), "+f"(d[35]), "+f"(d[36]), "+f"(d[37]), "+f"(d[38]), "+f"(d[39]),
      "+f"(d[40]), "+f"(d[41]), "+f"(d[42]), "+f"(d[43]), "+f"(d[44]), "+f"(d[45]), "+f"(d[46]), "+f"(d[47]),
      "+f"(d[48]), "+f"(d[49]), "+f"(d[50]), "+f"(d[51]), "+f"(d[52]), "+f"(d[53]), "+f"(d[54]), "+f"(d[55]),
      "+f"(d[56]), "+f"(d[57]), "+f"(d[58]), "+f"(d[59]), "+f"(d[60]), "+f"(d[61]), "+f"(d[62]), "+f"(d[63]),
      "+f"(d[64]), "+f"(d[65]), "+f"(d[66]), "+f"(d[67]), "+f"(d[68]), "+f"(d[69]), "+f"(d[70]), "+f"(d[71])
    : "l"(da), "l"(db), "r"(sd));
}

__device__ __forceinline__ void wgmma_ss_n160_t11(float* d, uint64_t da, uint64_t db, int sd) {
  asm volatile("{ .reg .pred p; setp.ne.b32 p, %82, 0;\n"
      "wgmma.mma_async.sync.aligned.m64n160k16.f32.bf16.bf16 {"
      "%0,%1,%2,%3,%4,%5,%6,%7,%8,%9,%10,%11,%12,%13,%14,%15,"
      "%16,%17,%18,%19,%20,%21,%22,%23,%24,%25,%26,%27,%28,%29,%30,%31,"
      "%32,%33,%34,%35,%36,%37,%38,%39,%40,%41,%42,%43,%44,%45,%46,%47,"
      "%48,%49,%50,%51,%52,%53,%54,%55,%56,%57,%58,%59,%60,%61,%62,%63,"
      "%64,%65,%66,%67,%68,%69,%70,%71,%72,%73,%74,%75,%76,%77,%78,%79"
      "}, %80, %81, p, 1, 1, 1, 1; }"
    : "+f"(d[0]), "+f"(d[1]), "+f"(d[2]), "+f"(d[3]), "+f"(d[4]), "+f"(d[5]), "+f"(d[6]), "+f"(d[7]),
      "+f"(d[8]), "+f"(d[9]), "+f"(d[10]), "+f"(d[11]), "+f"(d[12]), "+f"(d[13]), "+f"(d[14]), "+f"(d[15]),
      "+f"(d[16]), "+f"(d[17]), "+f"(d[18]), "+f"(d[19]), "+f"(d[20]), "+f"(d[21]), "+f"(d[22]), "+f"(d[23]),
      "+f"(d[24]), "+f"(d[25]), "+f"(d[26]), "+f"(d[27]), "+f"(d[28]), "+f"(d[29]), "+f"(d[30]), "+f"(d[31]),
      "+f"(d[32]), "+f"(d[33]), "+f"(d[34]), "+f"(d[35]), "+f"(d[36]), "+f"(d[37]), "+f"(d[38]), "+f"(d[39]),
      "+f"(d[40]), "+f"(d[41]), "+f"(d[42]), "+f"(d[43]), "+f"(d[44]), "+f"(d[45]), "+f"(d[46]), "+f"(d[47]),
      "+f"(d[48]), "+f"(d[49]), "+f"(d[50]), "+f"(d[51]), "+f"(d[52]), "+f"(d[53]), "+f"(d[54]), "+f"(d[55]),
      "+f"(d[56]), "+f"(d[57]), "+f"(d[58]), "+f"(d[59]), "+f"(d[60]), "+f"(d[61]), "+f"(d[62]), "+f"(d[63]),
      "+f"(d[64]), "+f"(d[65]), "+f"(d[66]), "+f"(d[67]), "+f"(d[68]), "+f"(d[69]), "+f"(d[70]), "+f"(d[71]),
      "+f"(d[72]), "+f"(d[73]), "+f"(d[74]), "+f"(d[75]), "+f"(d[76]), "+f"(d[77]), "+f"(d[78]), "+f"(d[79])
    : "l"(da), "l"(db), "r"(sd));
}

__device__ __forceinline__ void wgmma_ss_n96_t11(float* d, uint64_t da, uint64_t db, int sd) {
  asm volatile("{ .reg .pred p; setp.ne.b32 p, %50, 0;\n"
      "wgmma.mma_async.sync.aligned.m64n96k16.f32.bf16.bf16 {"
      "%0,%1,%2,%3,%4,%5,%6,%7,%8,%9,%10,%11,%12,%13,%14,%15,"
      "%16,%17,%18,%19,%20,%21,%22,%23,%24,%25,%26,%27,%28,%29,%30,%31,"
      "%32,%33,%34,%35,%36,%37,%38,%39,%40,%41,%42,%43,%44,%45,%46,%47"
      "}, %48, %49, p, 1, 1, 1, 1; }"
    : "+f"(d[0]), "+f"(d[1]), "+f"(d[2]), "+f"(d[3]), "+f"(d[4]), "+f"(d[5]), "+f"(d[6]), "+f"(d[7]),
      "+f"(d[8]), "+f"(d[9]), "+f"(d[10]), "+f"(d[11]), "+f"(d[12]), "+f"(d[13]), "+f"(d[14]), "+f"(d[15]),
      "+f"(d[16]), "+f"(d[17]), "+f"(d[18]), "+f"(d[19]), "+f"(d[20]), "+f"(d[21]), "+f"(d[22]), "+f"(d[23]),
      "+f"(d[24]), "+f"(d[25]), "+f"(d[26]), "+f"(d[27]), "+f"(d[28]), "+f"(d[29]), "+f"(d[30]), "+f"(d[31]),
      "+f"(d[32]), "+f"(d[33]), "+f"(d[34]), "+f"(d[35]), "+f"(d[36]), "+f"(d[37]), "+f"(d[38]), "+f"(d[39]),
      "+f"(d[40]), "+f"(d[41]), "+f"(d[42]), "+f"(d[43]), "+f"(d[44]), "+f"(d[45]), "+f"(d[46]), "+f"(d[47])
    : "l"(da), "l"(db), "r"(sd));
}

__device__ __forceinline__ void wgmma_rs_n16(float* d, const uint32_t* a, uint64_t db, int sd) {
  asm volatile("{ .reg .pred p; setp.ne.b32 p, %13, 0;\n"
      "wgmma.mma_async.sync.aligned.m64n16k16.f32.bf16.bf16 {"
      "%0,%1,%2,%3,%4,%5,%6,%7"
      "}, {%8,%9,%10,%11}, %12, p, 1, 1, 0; }"
    : "+f"(d[0]), "+f"(d[1]), "+f"(d[2]), "+f"(d[3]), "+f"(d[4]), "+f"(d[5]), "+f"(d[6]), "+f"(d[7])
    : "r"(a[0]), "r"(a[1]), "r"(a[2]), "r"(a[3]), "l"(db), "r"(sd));
}

__device__ __forceinline__ void wgmma_rs_n32(float* d, const uint32_t* a, uint64_t db, int sd) {
  asm volatile("{ .reg .pred p; setp.ne.b32 p, %21, 0;\n"
      "wgmma.mma_async.sync.aligned.m64n32k16.f32.bf16.bf16 {"
      "%0,%1,%2,%3,%4,%5,%6,%7,%8,%9,%10,%11,%12,%13,%14,%15"
      "}, {%16,%17,%18,%19}, %20, p, 1, 1, 0; }"
    : "+f"(d[0]), "+f"(d[1]), "+f"(d[2]), "+f"(d[3]), "+f"(d[4]), "+f"(d[5]), "+f"(d[6]), "+f"(d[7]),
      "+f"(d[8]), "+f"(d[9]), "+f"(d[10]), "+f"(d[11]), "+f"(d[12]), "+f"(d[13]), "+f"(d[14]), "+f"(d[15])
    : "r"(a[0]), "r"(a[1]), "r"(a[2]), "r"(a[3]), "l"(db), "r"(sd));
}

__device__ __forceinline__ void wgmma_rs_n48(float* d, const uint32_t* a, uint64_t db, int sd) {
  asm volatile("{ .reg .pred p; setp.ne.b32 p, %29, 0;\n"
      "wgmma.mma_async.sync.aligned.m64n48k16.f32.bf16.bf16 {"
      "%0,%1,%2,%3,%4,%5,%6,%7,%8,%9,%10,%11,%12,%13,%14,%15,"
      "%16,%17,%18,%19,%20,%21,%22,%23"
      "}, {%24,%25,%26,%27}, %28, p, 1, 1, 0; }"
    : "+f"(d[0]), "+f"(d[1]), "+f"(d[2]), "+f"(d[3]), "+f"(d[4]), "+f"(d[5]), "+f"(d[6]), "+f"(d[7]),
      "+f"(d[8]), "+f"(d[9]), "+f"(d[10]), "+f"(d[11]), "+f"(d[12]), "+f"(d[13]), "+f"(d[14]), "+f"(d[15]),
      "+f"(d[16]), "+f"(d[17]), "+f"(d[18]), "+f"(d[19]), "+f"(d[20]), "+f"(d[21]), "+f"(d[22]), "+f"(d[23])
    : "r"(a[0]), "r"(a[1]), "r"(a[2]), "r"(a[3]), "l"(db), "r"(sd));
}

__device__ __forceinline__ void wgmma_rs_n64(float* d, const uint32_t* a, uint64_t db, int sd) {
  asm volatile("{ .reg .pred p; setp.ne.b32 p, %37, 0;\n"
      "wgmma.mma_async.sync.aligned.m64n64k16.f32.bf16.bf16 {"
      "%0,%1,%2,%3,%4,%5,%6,%7,%8,%9,%10,%11,%12,%13,%14,%15,"
      "%16,%17,%18,%19,%20,%21,%22,%23,%24,%25,%26,%27,%28,%29,%30,%31"
      "}, {%32,%33,%34,%35}, %36, p, 1, 1, 0; }"
    : "+f"(d[0]), "+f"(d[1]), "+f"(d[2]), "+f"(d[3]), "+f"(d[4]), "+f"(d[5]), "+f"(d[6]), "+f"(d[7]),
      "+f"(d[8]), "+f"(d[9]), "+f"(d[10]), "+f"(d[11]), "+f"(d[12]), "+f"(d[13]), "+f"(d[14]), "+f"(d[15]),
      "+f"(d[16]), "+f"(d[17]), "+f"(d[18]), "+f"(d[19]), "+f"(d[20]), "+f"(d[21]), "+f"(d[22]), "+f"(d[23]),
      "+f"(d[24]), "+f"(d[25]), "+f"(d[26]), "+f"(d[27]), "+f"(d[28]), "+f"(d[29]), "+f"(d[30]), "+f"(d[31])
    : "r"(a[0]), "r"(a[1]), "r"(a[2]), "r"(a[3]), "l"(db), "r"(sd));
}

__device__ __forceinline__ void wgmma_rs_n80(float* d, const uint32_t* a, uint64_t db, int sd) {
  asm volatile("{ .reg .pred p; setp.ne.b32 p, %45, 0;\n"
      "wgmma.mma_async.sync.aligned.m64n80k16.f32.bf16.bf16 {"
      "%0,%1,%2,%3,%4,%5,%6,%7,%8,%9,%10,%11,%12,%13,%14,%15,"
      "%16,%17,%18,%19,%20,%21,%22,%23,%24,%25,%26,%27,%28,%29,%30,%31,"
      "%32,%33,%34,%35,%36,%37,%38,%39"
      "}, {%40,%41,%42,%43}, %44, p, 1, 1, 0; }"
    : "+f"(d[0]), "+f"(d[1]), "+f"(d[2]), "+f"(d[3]), "+f"(d[4]), "+f"(d[5]), "+f"(d[6]), "+f"(d[7]),
      "+f"(d[8]), "+f"(d[9]), "+f"(d[10]), "+f"(d[11]), "+f"(d[12]), "+f"(d[13]), "+f"(d[14]), "+f"(d[15]),
      "+f"(d[16]), "+f"(d[17]), "+f"(d[18]), "+f"(d[19]), "+f"(d[20]), "+f"(d[21]), "+f"(d[22]), "+f"(d[23]),
      "+f"(d[24]), "+f"(d[25]), "+f"(d[26]), "+f"(d[27]), "+f"(d[28]), "+f"(d[29]), "+f"(d[30]), "+f"(d[31]),
      "+f"(d[32]), "+f"(d[33]), "+f"(d[34]), "+f"(d[35]), "+f"(d[36]), "+f"(d[37]), "+f"(d[38]), "+f"(d[39])
    : "r"(a[0]), "r"(a[1]), "r"(a[2]), "r"(a[3]), "l"(db), "r"(sd));
}

__device__ __forceinline__ void wgmma_rs_n96(float* d, const uint32_t* a, uint64_t db, int sd) {
  asm volatile("{ .reg .pred p; setp.ne.b32 p, %53, 0;\n"
      "wgmma.mma_async.sync.aligned.m64n96k16.f32.bf16.bf16 {"
      "%0,%1,%2,%3,%4,%5,%6,%7,%8,%9,%10,%11,%12,%13,%14,%15,"
      "%16,%17,%18,%19,%20,%21,%22,%23,%24,%25,%26,%27,%28,%29,%30,%31,"
      "%32,%33,%34,%35,%36,%37,%38,%39,%40,%41,%42,%43,%44,%45,%46,%47"
      "}, {%48,%49,%50,%51}, %52, p, 1, 1, 0; }"
    : "+f"(d[0]), "+f"(d[1]), "+f"(d[2]), "+f"(d[3]), "+f"(d[4]), "+f"(d[5]), "+f"(d[6]), "+f"(d[7]),
      "+f"(d[8]), "+f"(d[9]), "+f"(d[10]), "+f"(d[11]), "+f"(d[12]), "+f"(d[13]), "+f"(d[14]), "+f"(d[15]),
      "+f"(d[16]), "+f"(d[17]), "+f"(d[18]), "+f"(d[19]), "+f"(d[20]), "+f"(d[21]), "+f"(d[22]), "+f"(d[23]),
      "+f"(d[24]), "+f"(d[25]), "+f"(d[26]), "+f"(d[27]), "+f"(d[28]), "+f"(d[29]), "+f"(d[30]), "+f"(d[31]),
      "+f"(d[32]), "+f"(d[33]), "+f"(d[34]), "+f"(d[35]), "+f"(d[36]), "+f"(d[37]), "+f"(d[38]), "+f"(d[39]),
      "+f"(d[40]), "+f"(d[41]), "+f"(d[42]), "+f"(d[43]), "+f"(d[44]), "+f"(d[45]), "+f"(d[46]), "+f"(d[47])
    : "r"(a[0]), "r"(a[1]), "r"(a[2]), "r"(a[3]), "l"(db), "r"(sd));
}

__device__ __forceinline__ void wgmma_rs_n112(float* d, const uint32_t* a, uint64_t db, int sd) {
  asm volatile("{ .reg .pred p; setp.ne.b32 p, %61, 0;\n"
      "wgmma.mma_async.sync.aligned.m64n112k16.f32.bf16.bf16 {"
      "%0,%1,%2,%3,%4,%5,%6,%7,%8,%9,%10,%11,%12,%13,%14,%15,"
      "%16,%17,%18,%19,%20,%21,%22,%23,%24,%25,%26,%27,%28,%29,%30,%31,"
      "%32,%33,%34,%35,%36,%37,%38,%39,%40,%41,%42,%43,%44,%45,%46,%47,"
      "%48,%49,%50,%51,%52,%53,%54,%55"
      "}, {%56,%57,%58,%59}, %60, p, 1, 1, 0; }"
    : "+f"(d[0]), "+f"(d[1]), "+f"(d[2]), "+f"(d[3]), "+f"(d[4]), "+f"(d[5]), "+f"(d[6]), "+f"(d[7]),
      "+f"(d[8]), "+f"(d[9]), "+f"(d[10]), "+f"(d[11]), "+f"(d[12]), "+f"(d[13]), "+f"(d[14]), "+f"(d[15]),
      "+f"(d[16]), "+f"(d[17]), "+f"(d[18]), "+f"(d[19]), "+f"(d[20]), "+f"(d[21]), "+f"(d[22]), "+f"(d[23]),
      "+f"(d[24]), "+f"(d[25]), "+f"(d[26]), "+f"(d[27]), "+f"(d[28]), "+f"(d[29]), "+f"(d[30]), "+f"(d[31]),
      "+f"(d[32]), "+f"(d[33]), "+f"(d[34]), "+f"(d[35]), "+f"(d[36]), "+f"(d[37]), "+f"(d[38]), "+f"(d[39]),
      "+f"(d[40]), "+f"(d[41]), "+f"(d[42]), "+f"(d[43]), "+f"(d[44]), "+f"(d[45]), "+f"(d[46]), "+f"(d[47]),
      "+f"(d[48]), "+f"(d[49]), "+f"(d[50]), "+f"(d[51]), "+f"(d[52]), "+f"(d[53]), "+f"(d[54]), "+f"(d[55])
    : "r"(a[0]), "r"(a[1]), "r"(a[2]), "r"(a[3]), "l"(db), "r"(sd));
}

__device__ __forceinline__ void wgmma_rs_n128(float* d, const uint32_t* a, uint64_t db, int sd) {
  asm volatile("{ .reg .pred p; setp.ne.b32 p, %69, 0;\n"
      "wgmma.mma_async.sync.aligned.m64n128k16.f32.bf16.bf16 {"
      "%0,%1,%2,%3,%4,%5,%6,%7,%8,%9,%10,%11,%12,%13,%14,%15,"
      "%16,%17,%18,%19,%20,%21,%22,%23,%24,%25,%26,%27,%28,%29,%30,%31,"
      "%32,%33,%34,%35,%36,%37,%38,%39,%40,%41,%42,%43,%44,%45,%46,%47,"
      "%48,%49,%50,%51,%52,%53,%54,%55,%56,%57,%58,%59,%60,%61,%62,%63"
      "}, {%64,%65,%66,%67}, %68, p, 1, 1, 0; }"
    : "+f"(d[0]), "+f"(d[1]), "+f"(d[2]), "+f"(d[3]), "+f"(d[4]), "+f"(d[5]), "+f"(d[6]), "+f"(d[7]),
      "+f"(d[8]), "+f"(d[9]), "+f"(d[10]), "+f"(d[11]), "+f"(d[12]), "+f"(d[13]), "+f"(d[14]), "+f"(d[15]),
      "+f"(d[16]), "+f"(d[17]), "+f"(d[18]), "+f"(d[19]), "+f"(d[20]), "+f"(d[21]), "+f"(d[22]), "+f"(d[23]),
      "+f"(d[24]), "+f"(d[25]), "+f"(d[26]), "+f"(d[27]), "+f"(d[28]), "+f"(d[29]), "+f"(d[30]), "+f"(d[31]),
      "+f"(d[32]), "+f"(d[33]), "+f"(d[34]), "+f"(d[35]), "+f"(d[36]), "+f"(d[37]), "+f"(d[38]), "+f"(d[39]),
      "+f"(d[40]), "+f"(d[41]), "+f"(d[42]), "+f"(d[43]), "+f"(d[44]), "+f"(d[45]), "+f"(d[46]), "+f"(d[47]),
      "+f"(d[48]), "+f"(d[49]), "+f"(d[50]), "+f"(d[51]), "+f"(d[52]), "+f"(d[53]), "+f"(d[54]), "+f"(d[55]),
      "+f"(d[56]), "+f"(d[57]), "+f"(d[58]), "+f"(d[59]), "+f"(d[60]), "+f"(d[61]), "+f"(d[62]), "+f"(d[63])
    : "r"(a[0]), "r"(a[1]), "r"(a[2]), "r"(a[3]), "l"(db), "r"(sd));
}

__device__ __forceinline__ void wgmma_rs_n144(float* d, const uint32_t* a, uint64_t db, int sd) {
  asm volatile("{ .reg .pred p; setp.ne.b32 p, %77, 0;\n"
      "wgmma.mma_async.sync.aligned.m64n144k16.f32.bf16.bf16 {"
      "%0,%1,%2,%3,%4,%5,%6,%7,%8,%9,%10,%11,%12,%13,%14,%15,"
      "%16,%17,%18,%19,%20,%21,%22,%23,%24,%25,%26,%27,%28,%29,%30,%31,"
      "%32,%33,%34,%35,%36,%37,%38,%39,%40,%41,%42,%43,%44,%45,%46,%47,"
      "%48,%49,%50,%51,%52,%53,%54,%55,%56,%57,%58,%59,%60,%61,%62,%63,"
      "%64,%65,%66,%67,%68,%69,%70,%71"
      "}, {%72,%73,%74,%75}, %76, p, 1, 1, 0; }"
    : "+f"(d[0]), "+f"(d[1]), "+f"(d[2]), "+f"(d[3]), "+f"(d[4]), "+f"(d[5]), "+f"(d[6]), "+f"(d[7]),
      "+f"(d[8]), "+f"(d[9]), "+f"(d[10]), "+f"(d[11]), "+f"(d[12]), "+f"(d[13]), "+f"(d[14]), "+f"(d[15]),
      "+f"(d[16]), "+f"(d[17]), "+f"(d[18]), "+f"(d[19]), "+f"(d[20]), "+f"(d[21]), "+f"(d[22]), "+f"(d[23]),
      "+f"(d[24]), "+f"(d[25]), "+f"(d[26]), "+f"(d[27]), "+f"(d[28]), "+f"(d[29]), "+f"(d[30]), "+f"(d[31]),
      "+f"(d[32]), "+f"(d[33]), "+f"(d[34]), "+f"(d[35]), "+f"(d[36]), "+f"(d[37]), "+f"(d[38]), "+f"(d[39]),
      "+f"(d[40]), "+f"(d[41]), "+f"(d[42]), "+f"(d[43]), "+f"(d[44]), "+f"(d[45]), "+f"(d[46]), "+f"(d[47]),
      "+f"(d[48]), "+f"(d[49]), "+f"(d[50]), "+f"(d[51]), "+f"(d[52]), "+f"(d[53]), "+f"(d[54]), "+f"(d[55]),
      "+f"(d[56]), "+f"(d[57]), "+f"(d[58]), "+f"(d[59]), "+f"(d[60]), "+f"(d[61]), "+f"(d[62]), "+f"(d[63]),
      "+f"(d[64]), "+f"(d[65]), "+f"(d[66]), "+f"(d[67]), "+f"(d[68]), "+f"(d[69]), "+f"(d[70]), "+f"(d[71])
    : "r"(a[0]), "r"(a[1]), "r"(a[2]), "r"(a[3]), "l"(db), "r"(sd));
}

__device__ __forceinline__ void wgmma_rs_n160(float* d, const uint32_t* a, uint64_t db, int sd) {
  asm volatile("{ .reg .pred p; setp.ne.b32 p, %85, 0;\n"
      "wgmma.mma_async.sync.aligned.m64n160k16.f32.bf16.bf16 {"
      "%0,%1,%2,%3,%4,%5,%6,%7,%8,%9,%10,%11,%12,%13,%14,%15,"
      "%16,%17,%18,%19,%20,%21,%22,%23,%24,%25,%26,%27,%28,%29,%30,%31,"
      "%32,%33,%34,%35,%36,%37,%38,%39,%40,%41,%42,%43,%44,%45,%46,%47,"
      "%48,%49,%50,%51,%52,%53,%54,%55,%56,%57,%58,%59,%60,%61,%62,%63,"
      "%64,%65,%66,%67,%68,%69,%70,%71,%72,%73,%74,%75,%76,%77,%78,%79"
      "}, {%80,%81,%82,%83}, %84, p, 1, 1, 0; }"
    : "+f"(d[0]), "+f"(d[1]), "+f"(d[2]), "+f"(d[3]), "+f"(d[4]), "+f"(d[5]), "+f"(d[6]), "+f"(d[7]),
      "+f"(d[8]), "+f"(d[9]), "+f"(d[10]), "+f"(d[11]), "+f"(d[12]), "+f"(d[13]), "+f"(d[14]), "+f"(d[15]),
      "+f"(d[16]), "+f"(d[17]), "+f"(d[18]), "+f"(d[19]), "+f"(d[20]), "+f"(d[21]), "+f"(d[22]), "+f"(d[23]),
      "+f"(d[24]), "+f"(d[25]), "+f"(d[26]), "+f"(d[27]), "+f"(d[28]), "+f"(d[29]), "+f"(d[30]), "+f"(d[31]),
      "+f"(d[32]), "+f"(d[33]), "+f"(d[34]), "+f"(d[35]), "+f"(d[36]), "+f"(d[37]), "+f"(d[38]), "+f"(d[39]),
      "+f"(d[40]), "+f"(d[41]), "+f"(d[42]), "+f"(d[43]), "+f"(d[44]), "+f"(d[45]), "+f"(d[46]), "+f"(d[47]),
      "+f"(d[48]), "+f"(d[49]), "+f"(d[50]), "+f"(d[51]), "+f"(d[52]), "+f"(d[53]), "+f"(d[54]), "+f"(d[55]),
      "+f"(d[56]), "+f"(d[57]), "+f"(d[58]), "+f"(d[59]), "+f"(d[60]), "+f"(d[61]), "+f"(d[62]), "+f"(d[63]),
      "+f"(d[64]), "+f"(d[65]), "+f"(d[66]), "+f"(d[67]), "+f"(d[68]), "+f"(d[69]), "+f"(d[70]), "+f"(d[71]),
      "+f"(d[72]), "+f"(d[73]), "+f"(d[74]), "+f"(d[75]), "+f"(d[76]), "+f"(d[77]), "+f"(d[78]), "+f"(d[79])
    : "r"(a[0]), "r"(a[1]), "r"(a[2]), "r"(a[3]), "l"(db), "r"(sd));
}

__device__ __forceinline__ void wgmma_rs_n176(float* d, const uint32_t* a, uint64_t db, int sd) {
  asm volatile("{ .reg .pred p; setp.ne.b32 p, %93, 0;\n"
      "wgmma.mma_async.sync.aligned.m64n176k16.f32.bf16.bf16 {"
      "%0,%1,%2,%3,%4,%5,%6,%7,%8,%9,%10,%11,%12,%13,%14,%15,"
      "%16,%17,%18,%19,%20,%21,%22,%23,%24,%25,%26,%27,%28,%29,%30,%31,"
      "%32,%33,%34,%35,%36,%37,%38,%39,%40,%41,%42,%43,%44,%45,%46,%47,"
      "%48,%49,%50,%51,%52,%53,%54,%55,%56,%57,%58,%59,%60,%61,%62,%63,"
      "%64,%65,%66,%67,%68,%69,%70,%71,%72,%73,%74,%75,%76,%77,%78,%79,"
      "%80,%81,%82,%83,%84,%85,%86,%87"
      "}, {%88,%89,%90,%91}, %92, p, 1, 1, 0; }"
    : "+f"(d[0]), "+f"(d[1]), "+f"(d[2]), "+f"(d[3]), "+f"(d[4]), "+f"(d[5]), "+f"(d[6]), "+f"(d[7]),
      "+f"(d[8]), "+f"(d[9]), "+f"(d[10]), "+f"(d[11]), "+f"(d[12]), "+f"(d[13]), "+f"(d[14]), "+f"(d[15]),
      "+f"(d[16]), "+f"(d[17]), "+f"(d[18]), "+f"(d[19]), "+f"(d[20]), "+f"(d[21]), "+f"(d[22]), "+f"(d[23]),
      "+f"(d[24]), "+f"(d[25]), "+f"(d[26]), "+f"(d[27]), "+f"(d[28]), "+f"(d[29]), "+f"(d[30]), "+f"(d[31]),
      "+f"(d[32]), "+f"(d[33]), "+f"(d[34]), "+f"(d[35]), "+f"(d[36]), "+f"(d[37]), "+f"(d[38]), "+f"(d[39]),
      "+f"(d[40]), "+f"(d[41]), "+f"(d[42]), "+f"(d[43]), "+f"(d[44]), "+f"(d[45]), "+f"(d[46]), "+f"(d[47]),
      "+f"(d[48]), "+f"(d[49]), "+f"(d[50]), "+f"(d[51]), "+f"(d[52]), "+f"(d[53]), "+f"(d[54]), "+f"(d[55]),
      "+f"(d[56]), "+f"(d[57]), "+f"(d[58]), "+f"(d[59]), "+f"(d[60]), "+f"(d[61]), "+f"(d[62]), "+f"(d[63]),
      "+f"(d[64]), "+f"(d[65]), "+f"(d[66]), "+f"(d[67]), "+f"(d[68]), "+f"(d[69]), "+f"(d[70]), "+f"(d[71]),
      "+f"(d[72]), "+f"(d[73]), "+f"(d[74]), "+f"(d[75]), "+f"(d[76]), "+f"(d[77]), "+f"(d[78]), "+f"(d[79]),
      "+f"(d[80]), "+f"(d[81]), "+f"(d[82]), "+f"(d[83]), "+f"(d[84]), "+f"(d[85]), "+f"(d[86]), "+f"(d[87])
    : "r"(a[0]), "r"(a[1]), "r"(a[2]), "r"(a[3]), "l"(db), "r"(sd));
}

__device__ __forceinline__ void wgmma_rs_n192(float* d, const uint32_t* a, uint64_t db, int sd) {
  asm volatile("{ .reg .pred p; setp.ne.b32 p, %101, 0;\n"
      "wgmma.mma_async.sync.aligned.m64n192k16.f32.bf16.bf16 {"
      "%0,%1,%2,%3,%4,%5,%6,%7,%8,%9,%10,%11,%12,%13,%14,%15,"
      "%16,%17,%18,%19,%20,%21,%22,%23,%24,%25,%26,%27,%28,%29,%30,%31,"
      "%32,%33,%34,%35,%36,%37,%38,%39,%40,%41,%42,%43,%44,%45,%46,%47,"
      "%48,%49,%50,%51,%52,%53,%54,%55,%56,%57,%58,%59,%60,%61,%62,%63,"
      "%64,%65,%66,%67,%68,%69,%70,%71,%72,%73,%74,%75,%76,%77,%78,%79,"
      "%80,%81,%82,%83,%84,%85,%86,%87,%88,%89,%90,%91,%92,%93,%94,%95"
      "}, {%96,%97,%98,%99}, %100, p, 1, 1, 0; }"
    : "+f"(d[0]), "+f"(d[1]), "+f"(d[2]), "+f"(d[3]), "+f"(d[4]), "+f"(d[5]), "+f"(d[6]), "+f"(d[7]),
      "+f"(d[8]), "+f"(d[9]), "+f"(d[10]), "+f"(d[11]), "+f"(d[12]), "+f"(d[13]), "+f"(d[14]), "+f"(d[15]),
      "+f"(d[16]), "+f"(d[17]), "+f"(d[18]), "+f"(d[19]), "+f"(d[20]), "+f"(d[21]), "+f"(d[22]), "+f"(d[23]),
      "+f"(d[24]), "+f"(d[25]), "+f"(d[26]), "+f"(d[27]), "+f"(d[28]), "+f"(d[29]), "+f"(d[30]), "+f"(d[31]),
      "+f"(d[32]), "+f"(d[33]), "+f"(d[34]), "+f"(d[35]), "+f"(d[36]), "+f"(d[37]), "+f"(d[38]), "+f"(d[39]),
      "+f"(d[40]), "+f"(d[41]), "+f"(d[42]), "+f"(d[43]), "+f"(d[44]), "+f"(d[45]), "+f"(d[46]), "+f"(d[47]),
      "+f"(d[48]), "+f"(d[49]), "+f"(d[50]), "+f"(d[51]), "+f"(d[52]), "+f"(d[53]), "+f"(d[54]), "+f"(d[55]),
      "+f"(d[56]), "+f"(d[57]), "+f"(d[58]), "+f"(d[59]), "+f"(d[60]), "+f"(d[61]), "+f"(d[62]), "+f"(d[63]),
      "+f"(d[64]), "+f"(d[65]), "+f"(d[66]), "+f"(d[67]), "+f"(d[68]), "+f"(d[69]), "+f"(d[70]), "+f"(d[71]),
      "+f"(d[72]), "+f"(d[73]), "+f"(d[74]), "+f"(d[75]), "+f"(d[76]), "+f"(d[77]), "+f"(d[78]), "+f"(d[79]),
      "+f"(d[80]), "+f"(d[81]), "+f"(d[82]), "+f"(d[83]), "+f"(d[84]), "+f"(d[85]), "+f"(d[86]), "+f"(d[87]),
      "+f"(d[88]), "+f"(d[89]), "+f"(d[90]), "+f"(d[91]), "+f"(d[92]), "+f"(d[93]), "+f"(d[94]), "+f"(d[95])
    : "r"(a[0]), "r"(a[1]), "r"(a[2]), "r"(a[3]), "l"(db), "r"(sd));
}

__device__ __forceinline__ void wgmma_rs_n208(float* d, const uint32_t* a, uint64_t db, int sd) {
  asm volatile("{ .reg .pred p; setp.ne.b32 p, %109, 0;\n"
      "wgmma.mma_async.sync.aligned.m64n208k16.f32.bf16.bf16 {"
      "%0,%1,%2,%3,%4,%5,%6,%7,%8,%9,%10,%11,%12,%13,%14,%15,"
      "%16,%17,%18,%19,%20,%21,%22,%23,%24,%25,%26,%27,%28,%29,%30,%31,"
      "%32,%33,%34,%35,%36,%37,%38,%39,%40,%41,%42,%43,%44,%45,%46,%47,"
      "%48,%49,%50,%51,%52,%53,%54,%55,%56,%57,%58,%59,%60,%61,%62,%63,"
      "%64,%65,%66,%67,%68,%69,%70,%71,%72,%73,%74,%75,%76,%77,%78,%79,"
      "%80,%81,%82,%83,%84,%85,%86,%87,%88,%89,%90,%91,%92,%93,%94,%95,"
      "%96,%97,%98,%99,%100,%101,%102,%103"
      "}, {%104,%105,%106,%107}, %108, p, 1, 1, 0; }"
    : "+f"(d[0]), "+f"(d[1]), "+f"(d[2]), "+f"(d[3]), "+f"(d[4]), "+f"(d[5]), "+f"(d[6]), "+f"(d[7]),
      "+f"(d[8]), "+f"(d[9]), "+f"(d[10]), "+f"(d[11]), "+f"(d[12]), "+f"(d[13]), "+f"(d[14]), "+f"(d[15]),
      "+f"(d[16]), "+f"(d[17]), "+f"(d[18]), "+f"(d[19]), "+f"(d[20]), "+f"(d[21]), "+f"(d[22]), "+f"(d[23]),
      "+f"(d[24]), "+f"(d[25]), "+f"(d[26]), "+f"(d[27]), "+f"(d[28]), "+f"(d[29]), "+f"(d[30]), "+f"(d[31]),
      "+f"(d[32]), "+f"(d[33]), "+f"(d[34]), "+f"(d[35]), "+f"(d[36]), "+f"(d[37]), "+f"(d[38]), "+f"(d[39]),
      "+f"(d[40]), "+f"(d[41]), "+f"(d[42]), "+f"(d[43]), "+f"(d[44]), "+f"(d[45]), "+f"(d[46]), "+f"(d[47]),
      "+f"(d[48]), "+f"(d[49]), "+f"(d[50]), "+f"(d[51]), "+f"(d[52]), "+f"(d[53]), "+f"(d[54]), "+f"(d[55]),
      "+f"(d[56]), "+f"(d[57]), "+f"(d[58]), "+f"(d[59]), "+f"(d[60]), "+f"(d[61]), "+f"(d[62]), "+f"(d[63]),
      "+f"(d[64]), "+f"(d[65]), "+f"(d[66]), "+f"(d[67]), "+f"(d[68]), "+f"(d[69]), "+f"(d[70]), "+f"(d[71]),
      "+f"(d[72]), "+f"(d[73]), "+f"(d[74]), "+f"(d[75]), "+f"(d[76]), "+f"(d[77]), "+f"(d[78]), "+f"(d[79]),
      "+f"(d[80]), "+f"(d[81]), "+f"(d[82]), "+f"(d[83]), "+f"(d[84]), "+f"(d[85]), "+f"(d[86]), "+f"(d[87]),
      "+f"(d[88]), "+f"(d[89]), "+f"(d[90]), "+f"(d[91]), "+f"(d[92]), "+f"(d[93]), "+f"(d[94]), "+f"(d[95]),
      "+f"(d[96]), "+f"(d[97]), "+f"(d[98]), "+f"(d[99]), "+f"(d[100]), "+f"(d[101]), "+f"(d[102]), "+f"(d[103])
    : "r"(a[0]), "r"(a[1]), "r"(a[2]), "r"(a[3]), "l"(db), "r"(sd));
}

__device__ __forceinline__ void wgmma_rs_n224(float* d, const uint32_t* a, uint64_t db, int sd) {
  asm volatile("{ .reg .pred p; setp.ne.b32 p, %117, 0;\n"
      "wgmma.mma_async.sync.aligned.m64n224k16.f32.bf16.bf16 {"
      "%0,%1,%2,%3,%4,%5,%6,%7,%8,%9,%10,%11,%12,%13,%14,%15,"
      "%16,%17,%18,%19,%20,%21,%22,%23,%24,%25,%26,%27,%28,%29,%30,%31,"
      "%32,%33,%34,%35,%36,%37,%38,%39,%40,%41,%42,%43,%44,%45,%46,%47,"
      "%48,%49,%50,%51,%52,%53,%54,%55,%56,%57,%58,%59,%60,%61,%62,%63,"
      "%64,%65,%66,%67,%68,%69,%70,%71,%72,%73,%74,%75,%76,%77,%78,%79,"
      "%80,%81,%82,%83,%84,%85,%86,%87,%88,%89,%90,%91,%92,%93,%94,%95,"
      "%96,%97,%98,%99,%100,%101,%102,%103,%104,%105,%106,%107,%108,%109,%110,%111"
      "}, {%112,%113,%114,%115}, %116, p, 1, 1, 0; }"
    : "+f"(d[0]), "+f"(d[1]), "+f"(d[2]), "+f"(d[3]), "+f"(d[4]), "+f"(d[5]), "+f"(d[6]), "+f"(d[7]),
      "+f"(d[8]), "+f"(d[9]), "+f"(d[10]), "+f"(d[11]), "+f"(d[12]), "+f"(d[13]), "+f"(d[14]), "+f"(d[15]),
      "+f"(d[16]), "+f"(d[17]), "+f"(d[18]), "+f"(d[19]), "+f"(d[20]), "+f"(d[21]), "+f"(d[22]), "+f"(d[23]),
      "+f"(d[24]), "+f"(d[25]), "+f"(d[26]), "+f"(d[27]), "+f"(d[28]), "+f"(d[29]), "+f"(d[30]), "+f"(d[31]),
      "+f"(d[32]), "+f"(d[33]), "+f"(d[34]), "+f"(d[35]), "+f"(d[36]), "+f"(d[37]), "+f"(d[38]), "+f"(d[39]),
      "+f"(d[40]), "+f"(d[41]), "+f"(d[42]), "+f"(d[43]), "+f"(d[44]), "+f"(d[45]), "+f"(d[46]), "+f"(d[47]),
      "+f"(d[48]), "+f"(d[49]), "+f"(d[50]), "+f"(d[51]), "+f"(d[52]), "+f"(d[53]), "+f"(d[54]), "+f"(d[55]),
      "+f"(d[56]), "+f"(d[57]), "+f"(d[58]), "+f"(d[59]), "+f"(d[60]), "+f"(d[61]), "+f"(d[62]), "+f"(d[63]),
      "+f"(d[64]), "+f"(d[65]), "+f"(d[66]), "+f"(d[67]), "+f"(d[68]), "+f"(d[69]), "+f"(d[70]), "+f"(d[71]),
      "+f"(d[72]), "+f"(d[73]), "+f"(d[74]), "+f"(d[75]), "+f"(d[76]), "+f"(d[77]), "+f"(d[78]), "+f"(d[79]),
      "+f"(d[80]), "+f"(d[81]), "+f"(d[82]), "+f"(d[83]), "+f"(d[84]), "+f"(d[85]), "+f"(d[86]), "+f"(d[87]),
      "+f"(d[88]), "+f"(d[89]), "+f"(d[90]), "+f"(d[91]), "+f"(d[92]), "+f"(d[93]), "+f"(d[94]), "+f"(d[95]),
      "+f"(d[96]), "+f"(d[97]), "+f"(d[98]), "+f"(d[99]), "+f"(d[100]), "+f"(d[101]), "+f"(d[102]), "+f"(d[103]),
      "+f"(d[104]), "+f"(d[105]), "+f"(d[106]), "+f"(d[107]), "+f"(d[108]), "+f"(d[109]), "+f"(d[110]), "+f"(d[111])
    : "r"(a[0]), "r"(a[1]), "r"(a[2]), "r"(a[3]), "l"(db), "r"(sd));
}

__device__ __forceinline__ void wgmma_rs_n240(float* d, const uint32_t* a, uint64_t db, int sd) {
  asm volatile("{ .reg .pred p; setp.ne.b32 p, %125, 0;\n"
      "wgmma.mma_async.sync.aligned.m64n240k16.f32.bf16.bf16 {"
      "%0,%1,%2,%3,%4,%5,%6,%7,%8,%9,%10,%11,%12,%13,%14,%15,"
      "%16,%17,%18,%19,%20,%21,%22,%23,%24,%25,%26,%27,%28,%29,%30,%31,"
      "%32,%33,%34,%35,%36,%37,%38,%39,%40,%41,%42,%43,%44,%45,%46,%47,"
      "%48,%49,%50,%51,%52,%53,%54,%55,%56,%57,%58,%59,%60,%61,%62,%63,"
      "%64,%65,%66,%67,%68,%69,%70,%71,%72,%73,%74,%75,%76,%77,%78,%79,"
      "%80,%81,%82,%83,%84,%85,%86,%87,%88,%89,%90,%91,%92,%93,%94,%95,"
      "%96,%97,%98,%99,%100,%101,%102,%103,%104,%105,%106,%107,%108,%109,%110,%111,"
      "%112,%113,%114,%115,%116,%117,%118,%119"
      "}, {%120,%121,%122,%123}, %124, p, 1, 1, 0; }"
    : "+f"(d[0]), "+f"(d[1]), "+f"(d[2]), "+f"(d[3]), "+f"(d[4]), "+f"(d[5]), "+f"(d[6]), "+f"(d[7]),
      "+f"(d[8]), "+f"(d[9]), "+f"(d[10]), "+f"(d[11]), "+f"(d[12]), "+f"(d[13]), "+f"(d[14]), "+f"(d[15]),
      "+f"(d[16]), "+f"(d[17]), "+f"(d[18]), "+f"(d[19]), "+f"(d[20]), "+f"(d[21]), "+f"(d[22]), "+f"(d[23]),
      "+f"(d[24]), "+f"(d[25]), "+f"(d[26]), "+f"(d[27]), "+f"(d[28]), "+f"(d[29]), "+f"(d[30]), "+f"(d[31]),
      "+f"(d[32]), "+f"(d[33]), "+f"(d[34]), "+f"(d[35]), "+f"(d[36]), "+f"(d[37]), "+f"(d[38]), "+f"(d[39]),
      "+f"(d[40]), "+f"(d[41]), "+f"(d[42]), "+f"(d[43]), "+f"(d[44]), "+f"(d[45]), "+f"(d[46]), "+f"(d[47]),
      "+f"(d[48]), "+f"(d[49]), "+f"(d[50]), "+f"(d[51]), "+f"(d[52]), "+f"(d[53]), "+f"(d[54]), "+f"(d[55]),
      "+f"(d[56]), "+f"(d[57]), "+f"(d[58]), "+f"(d[59]), "+f"(d[60]), "+f"(d[61]), "+f"(d[62]), "+f"(d[63]),
      "+f"(d[64]), "+f"(d[65]), "+f"(d[66]), "+f"(d[67]), "+f"(d[68]), "+f"(d[69]), "+f"(d[70]), "+f"(d[71]),
      "+f"(d[72]), "+f"(d[73]), "+f"(d[74]), "+f"(d[75]), "+f"(d[76]), "+f"(d[77]), "+f"(d[78]), "+f"(d[79]),
      "+f"(d[80]), "+f"(d[81]), "+f"(d[82]), "+f"(d[83]), "+f"(d[84]), "+f"(d[85]), "+f"(d[86]), "+f"(d[87]),
      "+f"(d[88]), "+f"(d[89]), "+f"(d[90]), "+f"(d[91]), "+f"(d[92]), "+f"(d[93]), "+f"(d[94]), "+f"(d[95]),
      "+f"(d[96]), "+f"(d[97]), "+f"(d[98]), "+f"(d[99]), "+f"(d[100]), "+f"(d[101]), "+f"(d[102]), "+f"(d[103]),
      "+f"(d[104]), "+f"(d[105]), "+f"(d[106]), "+f"(d[107]), "+f"(d[108]), "+f"(d[109]), "+f"(d[110]), "+f"(d[111]),
      "+f"(d[112]), "+f"(d[113]), "+f"(d[114]), "+f"(d[115]), "+f"(d[116]), "+f"(d[117]), "+f"(d[118]), "+f"(d[119])
    : "r"(a[0]), "r"(a[1]), "r"(a[2]), "r"(a[3]), "l"(db), "r"(sd));
}

__device__ __forceinline__ void wgmma_rs_n256(float* d, const uint32_t* a, uint64_t db, int sd) {
  asm volatile("{ .reg .pred p; setp.ne.b32 p, %133, 0;\n"
      "wgmma.mma_async.sync.aligned.m64n256k16.f32.bf16.bf16 {"
      "%0,%1,%2,%3,%4,%5,%6,%7,%8,%9,%10,%11,%12,%13,%14,%15,"
      "%16,%17,%18,%19,%20,%21,%22,%23,%24,%25,%26,%27,%28,%29,%30,%31,"
      "%32,%33,%34,%35,%36,%37,%38,%39,%40,%41,%42,%43,%44,%45,%46,%47,"
      "%48,%49,%50,%51,%52,%53,%54,%55,%56,%57,%58,%59,%60,%61,%62,%63,"
      "%64,%65,%66,%67,%68,%69,%70,%71,%72,%73,%74,%75,%76,%77,%78,%79,"
      "%80,%81,%82,%83,%84,%85,%86,%87,%88,%89,%90,%91,%92,%93,%94,%95,"
      "%96,%97,%98,%99,%100,%101,%102,%103,%104,%105,%106,%107,%108,%109,%110,%111,"
      "%112,%113,%114,%115,%116,%117,%118,%119,%120,%121,%122,%123,%124,%125,%126,%127"
      "}, {%128,%129,%130,%131}, %132, p, 1, 1, 0; }"
    : "+f"(d[0]), "+f"(d[1]), "+f"(d[2]), "+f"(d[3]), "+f"(d[4]), "+f"(d[5]), "+f"(d[6]), "+f"(d[7]),
      "+f"(d[8]), "+f"(d[9]), "+f"(d[10]), "+f"(d[11]), "+f"(d[12]), "+f"(d[13]), "+f"(d[14]), "+f"(d[15]),
      "+f"(d[16]), "+f"(d[17]), "+f"(d[18]), "+f"(d[19]), "+f"(d[20]), "+f"(d[21]), "+f"(d[22]), "+f"(d[23]),
      "+f"(d[24]), "+f"(d[25]), "+f"(d[26]), "+f"(d[27]), "+f"(d[28]), "+f"(d[29]), "+f"(d[30]), "+f"(d[31]),
      "+f"(d[32]), "+f"(d[33]), "+f"(d[34]), "+f"(d[35]), "+f"(d[36]), "+f"(d[37]), "+f"(d[38]), "+f"(d[39]),
      "+f"(d[40]), "+f"(d[41]), "+f"(d[42]), "+f"(d[43]), "+f"(d[44]), "+f"(d[45]), "+f"(d[46]), "+f"(d[47]),
      "+f"(d[48]), "+f"(d[49]), "+f"(d[50]), "+f"(d[51]), "+f"(d[52]), "+f"(d[53]), "+f"(d[54]), "+f"(d[55]),
      "+f"(d[56]), "+f"(d[57]), "+f"(d[58]), "+f"(d[59]), "+f"(d[60]), "+f"(d[61]), "+f"(d[62]), "+f"(d[63]),
      "+f"(d[64]), "+f"(d[65]), "+f"(d[66]), "+f"(d[67]), "+f"(d[68]), "+f"(d[69]), "+f"(d[70]), "+f"(d[71]),
      "+f"(d[72]), "+f"(d[73]), "+f"(d[74]), "+f"(d[75]), "+f"(d[76]), "+f"(d[77]), "+f"(d[78]), "+f"(d[79]),
      "+f"(d[80]), "+f"(d[81]), "+f"(d[82]), "+f"(d[83]), "+f"(d[84]), "+f"(d[85]), "+f"(d[86]), "+f"(d[87]),
      "+f"(d[88]), "+f"(d[89]), "+f"(d[90]), "+f"(d[91]), "+f"(d[92]), "+f"(d[93]), "+f"(d[94]), "+f"(d[95]),
      "+f"(d[96]), "+f"(d[97]), "+f"(d[98]), "+f"(d[99]), "+f"(d[100]), "+f"(d[101]), "+f"(d[102]), "+f"(d[103]),
      "+f"(d[104]), "+f"(d[105]), "+f"(d[106]), "+f"(d[107]), "+f"(d[108]), "+f"(d[109]), "+f"(d[110]), "+f"(d[111]),
      "+f"(d[112]), "+f"(d[113]), "+f"(d[114]), "+f"(d[115]), "+f"(d[116]), "+f"(d[117]), "+f"(d[118]), "+f"(d[119]),
      "+f"(d[120]), "+f"(d[121]), "+f"(d[122]), "+f"(d[123]), "+f"(d[124]), "+f"(d[125]), "+f"(d[126]), "+f"(d[127])
    : "r"(a[0]), "r"(a[1]), "r"(a[2]), "r"(a[3]), "l"(db), "r"(sd));
}

__device__ __forceinline__ void ln_finish(float mean, float var, float& mb, float& rinv) {
  mb = round_bf16(mean);
  float sd;
  asm("sqrt.approx.ftz.f32 %0, %1;" : "=f"(sd) : "f"(round_bf16(round_bf16(var) + 1e-5f)));
  asm("rcp.approx.ftz.f32 %0, %1;" : "=f"(rinv) : "f"(round_bf16(sd)));
}
__device__ __forceinline__ uint32_t sum4(uint32_t a, uint32_t b, uint32_t c, uint32_t d) {
  return pack_bf16((bf_lo(a) + bf_lo(b)) + (bf_lo(c) + bf_lo(d)), (bf_hi(a) + bf_hi(b)) + (bf_hi(c) + bf_hi(d)));
}
struct Ring {
  uint32_t s, ph;
  __device__ __forceinline__ void next() { if (++s == NSTAGE) { s = 0; ph ^= 1; } }
};

__device__ __forceinline__ void conv_lda(uint32_t* a, int j, uint32_t base, bool on) {
  asm volatile("{ .reg .pred p; setp.ne.u32 p, %3, 0;\n @p ld.shared.u32 %0, [%2];\n @p ld.shared.u32 %1, [%2 + 128]; }"
               : "+r"(a[2 * j]), "+r"(a[2 * j + 1]) : "r"(base + (j >> 1) * 256 + (j & 1) * 16), "r"((uint32_t)on) : "memory");
}
__device__ __forceinline__ void conv_mma(float* acc, const uint32_t* a, uint64_t db) {
  wgmma_rs_n256(acc, a, db, 0);
  wgmma_rs_n240(acc, a + 4, db + 16, 1);
  wgmma_rs_n224(acc, a + 8, db + 32, 1);
  wgmma_rs_n208(acc, a + 12, db + 48, 1);
  wgmma_rs_n192(acc, a + 16, db + 64, 1);
  wgmma_rs_n176(acc, a + 20, db + 80, 1);
  wgmma_rs_n160(acc, a + 24, db + 96, 1);
  wgmma_rs_n144(acc, a + 28, db + 112, 1);
  wgmma_rs_n128(acc, a + 32, db + 128, 1);
  wgmma_rs_n112(acc, a + 36, db + 144, 1);
  wgmma_rs_n96(acc, a + 40, db + 160, 1);
  wgmma_rs_n80(acc, a + 44, db + 176, 1);
  wgmma_rs_n64(acc, a + 48, db + 192, 1);
  wgmma_rs_n48(acc, a + 52, db + 208, 1);
  wgmma_rs_n32(acc, a + 56, db + 224, 1);
  wgmma_rs_n16(acc, a + 60, db + 240, 1);
}
__device__ __forceinline__ uint32_t conv_part(const float* acc, int j) {
  const int q = 31 - j;
  return q == 31 ? pack_bf16(acc[124], acc[125]) : pack_bf16(acc[4 * q] + acc[(4 * q + 6) & 127], acc[4 * q + 1] + acc[(4 * q + 7) & 127]);
}
__device__ __forceinline__ uint4 conv_sum(const uint4* p) {
  return make_uint4(sum4(p[0].x, p[1].x, p[2].x, p[3].x), sum4(p[0].y, p[1].y, p[2].y, p[3].y), sum4(p[0].z, p[1].z, p[2].z, p[3].z),
                    sum4(p[0].w, p[1].w, p[2].w, p[3].w));
}
template <int NV> __device__ __forceinline__ void gelu_stage(float* acc, const float* hb, uint32_t sa, int passes) {
#pragma unroll
  for (int i = 0; i < NV; i++) acc[i] = fmaf(acc[i], 0.5f, hb[(i >> 1) & 1]);
#pragma unroll 1
  for (; passes > 0; passes--, sa += NV * 256) {
#pragma unroll
    for (int i = 0; i < NV; i += 8)
      stsm4t(sa + i * 256, pack_bf16(gelu_half(acc[i]), gelu_half(acc[i + 1])), pack_bf16(gelu_half(acc[i + 2]), gelu_half(acc[i + 3])),
             pack_bf16(gelu_half(acc[i + 4]), gelu_half(acc[i + 5])), pack_bf16(gelu_half(acc[i + 6]), gelu_half(acc[i + 7])));
#pragma unroll
    for (int i = 0; i < NV; i++) acc[i] = fmaf(acc[NV + i], 0.5f, hb[2 + ((i >> 1) & 1)]);
  }
}

__global__ void __cluster_dims__(2, 1, 1) __launch_bounds__(384, 1) fused_kernel(const __grid_constant__ Hot H, const __grid_constant__ Params P) {
  extern __shared__ __align__(1024) uint8_t smem_raw[];
  const uint32_t t0 = clk();
  const uint32_t sb = smem_u32(smem_raw);
  const int tid = threadIdx.x, lane = tid & 31;
  const int bid = blockIdx.x, rank = bid & 1;
  const Role& R = P.role[bid];
  Scratch* const S = H.S;
  uint32_t xr[18];
  const int row = bid * 16 + (tid >> 4);
  if (tid < 256 && bid < 128) {
    const char* src = reinterpret_cast<const char*>(H.x) + row * (D_ * 2) + (lane & 15) * 8;
#pragma unroll
    for (int j = 0; j < 9; j++) asm volatile("ld.global.nc.v2.u32 {%0,%1}, [%2];" : "=r"(xr[2 * j]), "=r"(xr[2 * j + 1]) : "l"(src + 128 * j));
  }
  const int warp = __shfl_sync(0xffffffffu, tid >> 5, 0);

  if (warp >= 8) {
    const bool one = elect_one();
    if (warp == 8 && one) {
#pragma unroll
      for (int b = B_FULL; b <= B_DONE; b += 8) mbar_init(sb + b, b < B_EMPTY ? 1 : b < B_CEMPTY ? 2 : b < B_G1DONE ? 4 : 8);
      asm volatile("fence.mbarrier_init.release.cluster;" ::: "memory");
    }
    __syncwarp();
    asm volatile("barrier.cluster.arrive.relaxed.aligned;" ::: "memory");
    asm volatile("setmaxnreg.dec.sync.aligned.u32 56;");
    const uint32_t ep = ldg32(S->cnt + C_EPOCH * 32);
    asm volatile("barrier.cluster.wait.aligned;" ::: "memory");
    const bool left = R.at == 15;
    if (warp == 8) {
      if (one) {
#pragma unroll 1
        for (int i = 0; i < 9; i++) asm volatile("prefetch.tensormap [%0];" :: "l"(&P.m_w1 + i) : "memory");
      }
      __syncwarp();
      if (bid < 128) bar_sync(2, 288);
      if (one) {
        TLREC(31);
        signal(S, C_H, EPOCH / 132);
        TLREC(1);
        const uint32_t boff = left ? 24576 : 16384;
        Ring r{0, 1};
#pragma unroll 1
        for (int kb = -NW0; kb < G1_KB; kb++) {
          const int kw = kb < 0 ? kb + NW0 : kb, s = kb < 0 ? kw : r.s;
          const uint32_t fb = sb + B_FULL + 8 * s;
          if (kb < 0 || kb >= NW0) {
            mbar_wait(sb + B_EMPTY + 8 * s, r.ph);
            mbar_expect_tx(fb, G1_BYTES);
            tma3d(sb + s * SLOT, &P.m_w1 + left, 0, kw * 64, R.fg, fb);
            if (kb < 0) continue;
          }
          if (kb == 0) { await(S, C_H, ep); fence_async_global(); TLREC(2); }
          bulk_load(sb + s * SLOT + boff, S->h + (kb * 18 + R.at) * 2048, G1_BYTES - boff, fb);
          if (kb == NSTAGE - 1) mbar_arrive(sb + B_GO);
          r.next();
        }
        await(S, C_KV, ep);
        fence_async_global();
#pragma unroll 1
        for (int i = 0; i < R.ncv; i++) {
          if (i == 2) {
            if (R.sg >= 0) {
#pragma unroll 1
              for (int s = 2; s < NSTAGE; s++) {
                mbar_wait(sb + B_EMPTY + 8 * s, ((G1_KB / NSTAGE) - 1) & 1);
                mbar_expect_tx(sb + B_FULL + 8 * s, G2_BYTES);
                tma3d(sb + s * SLOT, &P.m_w2, 0, (rank * G2_KB + s - 2) * 64, R.sg, sb + B_FULL + 8 * s);
              }
            }
            mbar_wait(sb + B_G1DONE, 0);
          }
          const uint32_t slot = sb + cv_slot(i), b8 = sb + 8 * (i & 3);
          mbar_wait(b8 + B_CEMPTY, ((i >> 2) & 1) ^ 1);
          sts128(slot + CV_KOFF, 0, 0, 0, 0); sts128(slot + CV_KOFF + 16, 0, 0, 0, 0);
          mbar_expect_tx(b8 + B_KFULL, 4096);
          bulk_load(slot + CV_KOFF + 32, H.ssm_k + (R.ch + i) * S_, 4096, b8 + B_KFULL);
          mbar_expect_tx(b8 + B_UFULL, 8192);
          bulk_load(slot, S->ub + (R.ch + i) * 4096, 8192, b8 + B_UFULL);
        }
        if (R.sg >= 0) {
          mbar_expect_tx(sb + B_XY, 2 * 18432);
          mbar_expect_tx(sb + B_XFULL, 9216);
          mbar_expect_tx(sb + B_XFULL + 8, 9216);
          await(S, C_U, ep);
          fence_async_global();
          TLREC(6);
#pragma unroll 1
          for (int kb = 0; kb < G2_KB; kb++, r.next()) {
            const int k0 = (rank * G2_KB + kb) * 64;
            const uint32_t fb = sb + B_FULL + 8 * r.s, slot = sb + r.s * SLOT;
            if (kb >= NSTAGE - 2) {
              mbar_wait(sb + B_EMPTY + 8 * r.s, r.ph);
              if (kb == NSTAGE) asm volatile("red.relaxed.gpu.global.add.u32 [%0], %1;" :: "l"(S->cnt + C_SYNC * 32), "r"(EPOCH / 128) : "memory");
              if (kb == SYNCKB) await(S, C_SYNC, ep);
              mbar_expect_tx(fb, G2_BYTES);
              tma3d(slot, &P.m_w2, 0, k0, R.sg, fb);
            }
            tma2d(slot + 16384, &P.m_uld, k0, R.ds * 8, fb);
            tma2d(slot + 16384 + 9216, &P.m_uld, k0, R.dk * 8, fb);
            const uint32_t nx = kb - 8, ny = kb - (G2_PREP - 4);
            if (nx < 8) tma2d(sb + SM_CV + nx * 2304, &P.m_x, R.dk * 8, R.sg * 64 + nx * 16, sb + B_XY);
            if (ny == 0) { mbar_wait(sb + B_YRDY, 0); fence_async_global(); }
            if (ny < 6) tma2d(sb + SM_DED + ny * 3072, &P.m_y, (R.sg + (ny >= 3)) * 64, R.dk * 8 + (ny % 3) * 24, sb + B_XY);
          }
          mbar_wait(sb + B_EMPTY + 8 * XSLOT, r.ph);
          mbar_arrive_remote(mapa(sb + B_XRDY, rank ^ 1));
        }
      }
    } else {
      if (bid < 128) {
        const int ht = tid - 288, hf = ht >= 48, pr = ht - 48 * hf;
        const int s0 = bid * 16 + hf * 8;
        const uint32_t keep = s0 ? 0xffffffffu : 0u;
        const int off = s0 * D_ + 2 * pr, back = s0 ? 5 * D_ : 0;
        const uint32_t st = sb + SM_DED + (1 - hf) * 1536 + pr * 32;
        mbar_wait_guarded(sb + B_GO, t0);
#pragma unroll 1
        for (int r = 0; r < KV_ROUNDS; r++) {
          const __nv_bfloat16 *kp = H.k + off + r * 96, *vp = H.v + off + r * 96;
          uint32_t kk[12], vv[9];
#pragma unroll
          for (int j = 0; j < 12; j++) kk[j] = ldg32(j < 4 ? kp - back + (j + 1) * D_ : kp + (j - 4) * D_);
#pragma unroll
          for (int j = 0; j < 9; j++) vv[j] = ldg32(j < 1 ? vp - back + 4 * D_ : vp + (j - 1) * D_);
          const uint4 w = __ldg(reinterpret_cast<const uint4*>(H.shift_k) + pr + r * 48);
          const uint32_t w0 = __byte_perm(w.x, w.z, 0x5410), w1 = __byte_perm(w.x, w.z, 0x7632);
          const uint32_t w2 = __byte_perm(w.y, w.w, 0x5410), w3 = __byte_perm(w.y, w.w, 0x7632);
#pragma unroll
          for (int j = 1; j < 4; j++) kk[j] &= keep;
#pragma unroll
          for (int j = 0; j < 9; j++)
            vv[j] = bmul2(badd2(badd2(badd2(bmul2(kk[j], w3), bmul2(kk[j + 1], w2)), bmul2(kk[j + 2], w1)), bmul2(kk[j + 3], w0)), vv[j]);
          vv[0] &= keep;
          const uint32_t buf = (r % 3) * 6144;
#pragma unroll
          for (int c = 0; c < 2; c++)
#pragma unroll
            for (int pi = 0; pi < 2; pi++) {
              const uint32_t sel = c ? 0x7632 : 0x5410;
              sts128(st + buf + c * 3072 + pi * 16, __byte_perm(vv[7 + pi], vv[6 + pi], sel), __byte_perm(vv[5 + pi], vv[4 + pi], sel),
                     __byte_perm(vv[3 + pi], vv[2 + pi], sel), __byte_perm(vv[1 + pi], vv[pi], sel));
            }
          bar_sync(1, 96);
          if (warp == 9 && one) {
            bulk_wait_all();
            fence_async_smem();
            tma3d_store(&P.m_ub, sb + SM_DED + buf, 16 * (127 - bid), r * 48, 0);
            bulk_commit();
          }
          __syncwarp();
        }
      }
      if (one) {
        if (warp < 11) {
          const int wg = warp - 9;
          if (!wg) {
            bulk_wait_all();
            mbar_arrive(sb + B_KVDONE);
            signal(S, C_KV, EPOCH / 132);
            TLREC(27);
          }
          mbar_wait_guarded(sb + B_STG + 8 * wg, t0);
          fence_async_smem();
          TLREC(13 + wg);
#pragma unroll 1
          for (int j = 0; j < (left ? 3 + 3 * wg : 5); j++) {
            const int hi = left && j >= 3;
            tma2d_store(&P.m_ust, sb + (wg ? SM_ST1 : SM_DED) + j * 4096, (R.fg + wg + hi) * 64, (R.at + j - 3 * hi) * 32);
          }
          bulk_commit();
          bulk_wait_all();
          mbar_arrive(sb + B_SFREE + 8 * wg);
          signal(S, C_U, EPOCH / 264);
          TLREC(15 + wg);
        } else {
          mbar_wait_guarded(sb + B_YDONE, t0);
          signal(S, C_Y, EPOCH / 132);
          await_guarded(S, C_Y, ep, t0);
          mbar_arrive(sb + B_YRDY);
          TLREC(19);
          if (bid == 0) signal(S, C_EPOCH, EPOCH);
          if (R.sg >= 0) mbar_wait_guarded(sb + B_DONE, t0);
        }
      }
    }
    TLEND();
  } else {
    asm volatile("barrier.cluster.arrive.relaxed.aligned;" ::: "memory");
    if (bid < 128) {
      float c[36], s[4];
#pragma unroll
      for (int i = 0; i < 18; i++) { c[2 * i] = bf_lo(xr[i]); c[2 * i + 1] = bf_hi(xr[i]); }
#pragma unroll
      for (int i = 0; i < 36; i++) s[i & 3] = i < 4 ? c[i] : s[i & 3] + c[i];
      const float ml = ((s[0] + s[1]) + (s[2] + s[3])) * (1.0f / 36.0f);
#pragma unroll
      for (int i = 0; i < 36; i++) { c[i] -= ml; s[i & 3] = i < 4 ? c[i] * c[i] : fmaf(c[i], c[i], s[i & 3]); }
      float m = ml, q = (s[0] + s[1]) + (s[2] + s[3]), n2 = 18.f;
#pragma unroll
      for (int o = 1; o < 16; o <<= 1) {
        const float mo = __shfl_xor_sync(0xffffffffu, m, o), qo = __shfl_xor_sync(0xffffffffu, q, o);
        const float dl = m - mo;
        q = fmaf(dl * dl, n2, q + qo);
        m = fmaf(dl, -0.5f, m);
        n2 *= 2.f;
      }
      const float var = q * (1.0f / 576.0f);
      float mb, rinv, mb2, rinv2;
      ln_finish(m, var, mb, rinv);
      ln_finish((m - mb) * rinv, var * rinv * rinv, mb2, rinv2);
      const float ca = rinv * rinv2, cb = fmaf(ml - mb, rinv, -mb2) * rinv2;
      uint2* dst = reinterpret_cast<uint2*>(S->h) + ((row >> 6) * 18 + ((lane >> 3) & 1)) * 512 + (row & 63) * 8 + ((lane & 7) ^ (row & 6));
#pragma unroll
      for (int j = 0; j < 9; j++)
        dst[1024 * j] = make_uint2(pack_bf16(fmaf(c[4 * j], ca, cb), fmaf(c[4 * j + 1], ca, cb)), pack_bf16(fmaf(c[4 * j + 2], ca, cb), fmaf(c[4 * j + 3], ca, cb)));
      const uint32_t rh = pack_bf16(rinv, rinv);
      if (!(lane & 15)) S->stats[row] = make_uint4(pack_bf16(mb, mb), rh, pack_bf16(rinv - bf_lo(rh), rinv - bf_lo(rh)), 0);
      __syncwarp();
      bar_arrive(2, 288);
    }
    asm volatile("setmaxnreg.inc.sync.aligned.u32 224;");
    asm volatile("barrier.cluster.wait.aligned;" ::: "memory");
    const int wg = warp >> 2, w = warp & 3, g = lane >> 2, t = lane & 3, wtid = tid & 127;
    const bool elect = wtid == 0;
    const uint64_t da0 = make_desc(sb + wg * 8192, 8192, 1024, 1);
    const uint32_t swz = ((lane >> 4) * 8 + (lane & 7)) * 128 + (((2 * w + ((lane >> 3) & 1)) ^ (lane & 7)) << 4);
    const uint32_t stg = sb + (wg ? SM_ST1 : SM_DED);
    {
      auto mainloop = [&](auto&& mma) {
        Ring r{0, 0};
        uint32_t rel = 0;
#pragma unroll 1
        for (int kb = 0; kb < G1_KB; kb++, r.next()) {
          if (kb == G1_KB - G1_TAIL && wg) {
            wg_wait<0>();
            if (elect) mbar_arrive(rel);
            rel = 0;
            bar_sync(5, 256);
          }
          mbar_wait(sb + B_FULL + 8 * r.s, r.ph);
          if (kb == 0 && warp == 0) TLREC(3);
          wg_fence();
          mma(r.s * (SLOT >> 4), kb);
          wg_commit();
          if (kb == G1_KB - 1) break;
          wg_wait<1>();
          if (elect && rel) mbar_arrive(rel);
          rel = sb + B_EMPTY + 8 * r.s;
        }
        bar_arrive(5, 256);
        wg_wait<0>();
      };
      auto staged = [&]() {
        if (!w) TLREC(4 + wg);
        if (lane == 0) mbar_arrive(sb + B_G1DONE);
        mbar_wait(sb + (wg ? B_G1DONE : B_KVDONE), 0);
      };
      mbar_wait(sb + B_GO, 0);
      const __nv_bfloat16* bp = P.b1 + R.fg * 64 + warp * 16 + g;
      float hb[4];
      hb[0] = 0.5f * __bfloat162float(bp[0]); hb[1] = 0.5f * __bfloat162float(bp[8]);
      if (R.at != 15) {
        const uint64_t db0 = make_desc(sb + 16384, 4096, 512, 2);
        hb[2] = hb[0]; hb[3] = hb[1];
        float acc[80];
        mainloop([&](uint32_t o, int kb) {
          wgmma_ss_n160_t11(acc, da0 + o, db0 + o, kb);
#pragma unroll
          for (int k = 1; k < 4; k++) wgmma_ss_n160_t11(acc, da0 + o + k * 128, db0 + o + k * 64, 1);
        });
        pin_regs<80>(acc);
        staged();
        gelu_stage<40>(acc, hb, stg + swz, 2);
      } else {
        const uint64_t db0 = make_desc(sb + 24576, 4096, 512, 2);
        hb[2] = 0.5f * __bfloat162float(bp[64]); hb[3] = 0.5f * __bfloat162float(bp[72]);
        float acc[96];
        auto block = [&](float* d, uint64_t da, uint64_t db, int kb) {
          wgmma_ss_n96_t11(d, da, db, kb);
#pragma unroll
          for (int k = 1; k < 4; k++) wgmma_ss_n96_t11(d, da + k * 128, db + k * 64, 1);
        };
        if (wg) mainloop([&](uint32_t o, int kb) { block(acc, da0 + o, db0 + o, kb); block(acc + 48, da0 + o + 512, db0 + o, kb); });
        else mainloop([&](uint32_t o, int kb) { block(acc, da0 + o, db0 + o, kb); });
        pin_regs<96>(acc);
        staged();
        gelu_stage<48>(acc, hb, stg + swz, 1 + wg);
      }
      __syncwarp();
      if (lane == 0) mbar_arrive(sb + B_STG + 8 * wg);
    }
    {
      const uint32_t ka0 = CV_KOFF + (8 * w + g + t + 1) * 4, wr = stg + w * CV_REDW + (8 * (3 - t + w) + g) * 4;
      uint32_t a[64];
      uint32_t dd = __bfloat16_as_ushort(P.ssm_D[R.ch + wg]);
      mbar_wait(sb + B_KFULL + 8 * wg, 0);
#pragma unroll
      for (int j = 0; j < 32; j++) conv_lda(a, j, sb + SM_CV + wg * CV_SLOT + ka0, true);
#pragma unroll 1
      for (int i = wg; i < R.ncv; i += 2) {
        const bool more = i + 2 < R.ncv;
        a[0] = badd2(a[0], ka0 == CV_KOFF + 32 ? dd : 0); a[2] = badd2(a[2], ka0 == CV_KOFF + 16 ? dd : 0);
        if (more) dd = __bfloat16_as_ushort(P.ssm_D[R.ch + i + 2]);
        float acc[128];
        mbar_wait(sb + B_UFULL + 8 * (i & 3), (i >> 2) & 1);
        bar_sync(5 + wg, 256);
        if (!w && i < 4) TLREC(22 + i);
        wg_fence();
        conv_mma(acc, a, make_desc(sb + cv_slot(i), 4096, 128, 0));
        wg_commit();
        if (i + 1 < R.ncv) bar_arrive(5 + (wg ^ 1), 256);
        mbar_wait(sb + B_SFREE + 8 * wg, 0);
        if (lane < 8 * w) sts32(stg + w * CV_REDW + lane * 4, 0);
        if (more) mbar_wait(sb + B_KFULL + 8 * ((i + 2) & 3), ((i + 2) >> 2) & 1);
        wg_wait<0>();
        pin_regs<128>(acc);
        if (lane == 0) mbar_arrive(sb + B_CEMPTY + 8 * (i & 3));
        const uint32_t ka = sb + cv_slot(i + 2) + ka0;
#pragma unroll
        for (int j = 0; j < 32; j++) {
          if (j < 24) conv_lda(a, j, ka, more);
          sts32(wr + j * 128, conv_part(acc, j));
        }
        bar_sync(3 + wg, 128);
        uint4 p[2][4];
#pragma unroll
        for (int x = 0; x < 8; x++) p[x >> 2][x & 3] = lds128(stg + (x & 3) * CV_REDW + (wtid + 128 * (x >> 2)) * 16);
#pragma unroll
        for (int j = 24; j < 32; j++) conv_lda(a, j, ka, more);
        uint4* yo = reinterpret_cast<uint4*>(S->y + (R.ch + i) * S_) + wtid;
        yo[0] = conv_sum(p[0]); yo[128] = conv_sum(p[1]);
      }
      fence_async_smem();
      bar_sync(3 + wg, 128);
      if (elect) { mbar_arrive(sb + B_EMPTY); mbar_arrive(sb + B_EMPTY + 8); }
      if (lane == 0) mbar_arrive(sb + B_YDONE);
      if (!w) TLREC(20 + wg);
    }
    if (R.sg >= 0) {
      const int srow = R.sg * 64 + warp * 16;
      const uint64_t db0 = make_desc(sb + 16384, 16, 1024, 1);
      const uint32_t xo = sb + SM_CV + warp * 2304, xa = xo + (lane & 15) * 144;
      float acc[72];
      uint32_t xx[18], ss[18];
      const uint4 st0 = __ldcg(S->stats + srow + g), st1 = __ldcg(S->stats + srow + g + 8);
      const float hb0 = 0.5f * __bfloat162float(P.b2[srow + g]), hb1 = 0.5f * __bfloat162float(P.b2[srow + g + 8]);
      Ring r{G1_KB % NSTAGE, (G1_KB / NSTAGE) & 1};
      uint32_t rel = 0;
#pragma unroll 1
      for (int kb = 0; kb < G2_KB; kb++, r.next()) {
        if (kb == (wg ? G2_KB - G2_TAIL : G2_PREP)) {
          wg_wait<0>();
          if (elect) mbar_arrive(rel);
          rel = 0;
          mbar_wait(sb + B_XY, 0);
          const uint32_t ya = sb + SM_DED + wg * 9216 + swz;
#pragma unroll
          for (int q = 0; q < 8; q += 2) { ldsm4(xx + 2 * q, xa + (lane >> 4) * 16 + q * 16); ldsm4t(ss + 2 * q, ya + q * 1024); }
          ldsm2(xx + 16, xa + 128);
          ldsm2t(ss + 16, ya + 8 * 1024);
#pragma unroll
          for (int i = 0; i < 18; i++) {
            const uint4& st = (i & 1) ? st1 : st0;
            const uint32_t c = bsub2(xx[i], st.x);
            ss[i] = bmul2(bfma2(c, st.y, bmul2(c, st.z)), ss[i]);
          }
          if (wg) bar_sync(7, 256);
        }
        mbar_wait(sb + B_FULL + 8 * r.s, r.ph);
        if (kb == 0 && !w) TLREC(17 + wg);
        if (kb == 8 && warp == 0) TLREC(26);
        if (kb == 20 && warp == 0) TLREC(8);
        if (kb == 27 && warp == 0) TLREC(30);
        const uint64_t da = da0 + r.s * (SLOT >> 4), db = db0 + r.s * (SLOT >> 4);
        wg_fence();
        wgmma_ss_n144_t10(acc, da, db, kb);
#pragma unroll
        for (int k = 1; k < 4; k++) wgmma_ss_n144_t10(acc, da + k * 128, db + k * 2, 1);
        wg_commit();
        if (kb == G2_KB - 1) break;
        wg_wait<1>();
        if (elect && rel) mbar_arrive(rel);
        rel = sb + B_EMPTY + 8 * r.s;
      }
      if (!wg) bar_arrive(7, 256);
      const uint32_t xz = sb + XSLOT * SLOT + wg * 10240 + wtid * 16;
      const uint32_t rz = mapa(xz, rank ^ 1), rb = mapa(sb + B_XFULL + 8 * wg, rank ^ 1);
      mbar_wait(sb + B_XRDY, 0);
      wg_wait<0>();
      pin_regs<72>(acc);
      if (!w) TLREC(28 + wg);
#pragma unroll
      for (int i = 0; i < 32; i += 8)
        asm volatile("st.async.weak.shared::cluster.mbarrier::complete_tx::bytes.v4.b32 [%0], {%1,%2,%3,%4}, [%5];"
                     :: "r"(rz + i * 256), "r"(pack_bf16(acc[i], acc[i + 1])), "r"(pack_bf16(acc[i + 2], acc[i + 3])),
                        "r"(pack_bf16(acc[i + 4], acc[i + 5])), "r"(pack_bf16(acc[i + 6], acc[i + 7])), "r"(rb) : "memory");
      asm volatile("st.async.weak.shared::cluster.mbarrier::complete_tx::bytes.v2.b32 [%0], {%1,%2}, [%3];"
                   :: "r"(rz + 8192), "r"(pack_bf16(acc[32], acc[33])), "r"(pack_bf16(acc[34], acc[35])), "r"(rb) : "memory");
#pragma unroll
      for (int i = 36; i < 72; i++) acc[i] = fmaf(acc[i], 0.5f, (i & 2) ? hb1 : hb0);
      mbar_wait_cluster(sb + B_XFULL + 8 * wg, 0);
      if (!w) TLREC(9 + wg);
#pragma unroll
      for (int q = 0; q < 5; q++) {
        const uint4 v = lds128(xz + q * 2048);
        const uint32_t pv[4] = {v.x, v.y, v.z, v.w};
#pragma unroll
        for (int i = 4 * q; i < 4 * q + 4 && i < 18; i++)
          xx[i] = bfma2(ss[i], pack_bf16(silu_half(fmaf(bf_lo(pv[i & 3]), 0.5f, acc[36 + 2 * i])), silu_half(fmaf(bf_hi(pv[i & 3]), 0.5f, acc[37 + 2 * i]))), xx[i]);
        if (q < 4) stsm4(xa + (lane >> 4) * 16 + q * 32, xx[4 * q], xx[4 * q + 1], xx[4 * q + 2], xx[4 * q + 3]);
        else stsm2(xa + 128, xx[16], xx[17]);
      }
      __syncwarp();
      if (elect_one()) {
        fence_async_smem();
        tma2d_store(&P.m_out, xo, R.dk * 8, srow);
        bulk_commit();
        mbar_arrive(sb + B_DONE);
        bulk_wait_read();
      }
      if (!w) TLREC(11 + wg);
    }
    TLEND();
  }
}

typedef CUresult (*EncodeFn)(CUtensorMap*, CUtensorMapDataType, cuuint32_t, void*, const cuuint64_t*, const cuuint64_t*, const cuuint32_t*,
                             const cuuint32_t*, CUtensorMapInterleave, CUtensorMapSwizzle, CUtensorMapL2promotion, CUtensorMapFloatOOBfill);

void make_map(EncodeFn fn, CUtensorMap* m, const void* ptr, int rank, const cuuint64_t* dims, const cuuint64_t* strides, const cuuint32_t* box,
              CUtensorMapSwizzle sw) {
  const cuuint32_t es[3] = {1, 1, 1};
  fn(m, CU_TENSOR_MAP_DATA_TYPE_BFLOAT16, rank, const_cast<void*>(ptr), dims, strides, box, es, CU_TENSOR_MAP_INTERLEAVE_NONE, sw,
     CU_TENSOR_MAP_L2_PROMOTION_L2_256B, CU_TENSOR_MAP_FLOAT_OOB_FILL_NONE);
}

void make_roles(Role* R) {
  int nl = 0, ch = 0;
  for (int gi = 0; gi < 8; gi++)
    for (int b = 0; b < 132; b++) {
      const int c = b >> 1, rank = b & 1;
      int g, idx;
      if (c < 4) { g = 0; idx = 4 + c; }
      else if (c < 36) { g = (c - 4) & 7; idx = (c - 4) >> 3; }
      else if (c < 64) { g = 1 + (c - 36) % 7; idx = 4 + (c - 36) / 7; }
      else { g = c - 58; idx = 8; }
      if (g != gi) continue;
      Role& r = R[b];
      r.sg = (int8_t)(idx < 8 ? 2 * (2 * g + (idx >> 2)) : -1);
      r.dk = (int8_t)((idx & 3) * 18 + rank * 9);
      r.ds = (int8_t)((idx & 3) * 18 + (rank ^ 1) * 9);
      if (idx < (g < 2 ? 6 : 7)) {
        const int c1 = (g < 2 ? 6 * g : 7 * g - 2) + idx;
        r.fg = (int8_t)((2 * (c1 / 3) + rank) * 2); r.at = (int8_t)(c1 % 3 * 5); r.ncv = NCV_REG;
      } else {
        r.fg = (int8_t)(3 * nl++); r.at = 15; r.ncv = idx < 8 ? NCV_LEFT : NCV_LONG;
      }
      r.ch = (int16_t)ch;
      ch += r.ncv;
    }
}

}

extern "C" void kernel_launch(void* const* d_in, const int* in_sizes, int n_in, void* d_out, int out_size) {
  static Params P;
  static Hot H;
  static const void* cached[4] = {nullptr, nullptr, nullptr, nullptr};
  if (cached[0] != d_in[7] || cached[1] != d_in[9] || cached[2] != d_out || cached[3] != d_in[0]) {
    void* fp = nullptr;
    cudaDriverEntryPointQueryResult qr;
    cudaGetDriverEntryPoint("cuTensorMapEncodeTiled", &fp, cudaEnableDefault, &qr);
    EncodeFn fn = (EncodeFn)fp;
    void* ps;
    cudaGetSymbolAddress(&ps, g_scratch);
    H.S = (Scratch*)ps;
    const void *pu = (char*)ps + offsetof(Scratch, u), *py = (char*)ps + offsetof(Scratch, y),
               *pb = (char*)ps + offsetof(Scratch, ub);
    { cuuint64_t d[3] = {64, S_, F_ / 64}, s[2] = {F_ * 2, 128}; cuuint32_t b[3] = {64, 64, 2}; make_map(fn, &P.m_w1, d_in[7], 3, d, s, b, CU_TENSOR_MAP_SWIZZLE_128B);
      b[2] = 3; make_map(fn, &P.m_w1l, d_in[7], 3, d, s, b, CU_TENSOR_MAP_SWIZZLE_128B); }
    { cuuint64_t d[2] = {F_, D_}, s[1] = {F_ * 2}; cuuint32_t b[2] = {64, 32}; make_map(fn, &P.m_ust, pu, 2, d, s, b, CU_TENSOR_MAP_SWIZZLE_128B); }
    { cuuint64_t d[3] = {64, F_, S_ / 64}, s[2] = {S_ * 2, 128}; cuuint32_t b[3] = {64, 64, 2}; make_map(fn, &P.m_w2, d_in[9], 3, d, s, b, CU_TENSOR_MAP_SWIZZLE_128B); }
    { cuuint64_t d[2] = {F_, D_}, s[1] = {F_ * 2}; cuuint32_t b[2] = {64, 72}; make_map(fn, &P.m_uld, pu, 2, d, s, b, CU_TENSOR_MAP_SWIZZLE_128B); }
    { cuuint64_t d[2] = {D_, S_}, s[1] = {D_ * 2}; cuuint32_t b[2] = {72, 16}; make_map(fn, &P.m_out, d_out, 2, d, s, b, CU_TENSOR_MAP_SWIZZLE_NONE);
      make_map(fn, &P.m_x, d_in[0], 2, d, s, b, CU_TENSOR_MAP_SWIZZLE_NONE); }
    { cuuint64_t d[2] = {S_, D_}, s[1] = {S_ * 2}; cuuint32_t b[2] = {64, 24}; make_map(fn, &P.m_y, py, 2, d, s, b, CU_TENSOR_MAP_SWIZZLE_128B); }
    { cuuint64_t d[3] = {2048, D_ / 2, 4}, s[2] = {16384, 4096}; cuuint32_t b[3] = {16, 48, 4}; make_map(fn, &P.m_ub, pb, 3, d, s, b, CU_TENSOR_MAP_SWIZZLE_NONE); }
    make_roles(P.role);
    cudaFuncSetAttribute(fused_kernel, cudaFuncAttributeMaxDynamicSharedMemorySize, SM_TOTAL);
    cached[0] = d_in[7]; cached[1] = d_in[9]; cached[2] = d_out; cached[3] = d_in[0];
  }
  H.x = (const __nv_bfloat16*)d_in[0]; H.k = (const __nv_bfloat16*)d_in[1]; H.v = (const __nv_bfloat16*)d_in[2];
  H.shift_k = (const __nv_bfloat16*)d_in[3]; H.ssm_k = (const __nv_bfloat16*)d_in[4]; P.ssm_D = (const __nv_bfloat16*)d_in[5];
  P.b1 = (const __nv_bfloat16*)d_in[8]; P.b2 = (const __nv_bfloat16*)d_in[10];
  fused_kernel<<<132, 384, SM_TOTAL>>>(H, P);
}
```

```cpp
#include <cuda_runtime.h>
#include <cuda.h>
#include <cuda_bf16.h>
#include <stddef.h>
#include <stdint.h>

namespace {

constexpr int S_ = 2048, D_ = 576, F_ = 4608;
constexpr int NSTAGE = 5, SLOT = 36864;
constexpr int G1_KB = 32, G2_KB = 36;
constexpr int G1_BYTES = 36864, G2_BYTES = 16384 + 18432;
#define NCV_LEFT 4
constexpr int NCV_REG = 4, NCV_LONG = (D_ - 108 * NCV_REG - 20 * NCV_LEFT) / 4;
static_assert(108 * NCV_REG + 20 * NCV_LEFT + 4 * NCV_LONG == D_, "conv split");
constexpr int KV_ROUNDS = 6;
constexpr int NW0 = 1;
constexpr int G1_TAIL = 4, G2_TAIL = 3;
constexpr int SYNCKB = 5;
constexpr int PFK = 1;

constexpr int CV_KOFF = 8192, CV_SLOT = 8192 + 4224, CV_REDW = 2112 * 2;
constexpr int SM_DED = NSTAGE * SLOT;
constexpr int SM_CV = SM_DED + 20480;
constexpr int SM_ST1 = SLOT;
constexpr int SM_ST = SM_CV + 18432, SM_B2 = SM_ST + 2048;
constexpr int SM_B1 = SM_CV + 2 * CV_SLOT, SM_D = SM_B1 + 384;
constexpr int SM_BAR = SM_D + 1152;
constexpr int SM_TOTAL = SM_BAR + 768;
static_assert(G1_KB % NSTAGE == 2, "slots 0 and 1 hold the last two GEMM1 k-blocks");
constexpr int XSLOT = (G1_KB + G2_KB) % NSTAGE;
__device__ __forceinline__ uint32_t cv_slot(int i) { return (i & 2 ? 0 : SM_CV) + (i & 1) * CV_SLOT; }
constexpr int bar_at(int i) { return SM_BAR + 8 * i; }
constexpr int B_FULL = bar_at(0)  , B_KFULL = bar_at(5)  , B_UFULL = bar_at(9)  , B_KVDONE = bar_at(13), B_SFREE = bar_at(14)  ,
              B_XFULL = bar_at(16)  , B_XY = bar_at(18), B_MISC = bar_at(19), B_GO = bar_at(20),
              B_EMPTY = bar_at(21)  , B_XRDY = bar_at(26),
              B_CEMPTY = bar_at(27)  , B_STG = bar_at(31)  ,
              B_G1DONE = bar_at(33), B_YDONE = bar_at(34), B_DONE = bar_at(35);
constexpr int C_H = 0, C_KV = 1, C_U = 2, C_Y = 3, C_SYNC = 4, C_EPOCH = 5, C_COUNT = 6;
constexpr uint32_t EPOCH = 128 * 33;

struct Scratch {
  uint32_t cnt[C_COUNT * 32];
  alignas(1024) uint4 stats[S_];
  alignas(1024) __nv_bfloat16 h[S_ * D_];
  alignas(1024) __nv_bfloat16 ub[D_ * 4096];
  alignas(1024) __nv_bfloat16 y[D_ * S_];
  alignas(1024) __nv_bfloat16 u[D_ * F_];
};
__device__ Scratch g_scratch;

struct Hot {
  const __nv_bfloat16 *x, *k, *v, *shift_k, *ssm_k;
  Scratch* S;
};
struct Role {
  int8_t fg;
  int8_t at;
  int8_t sg;
  int8_t dk, ds;
  int8_t ncv;
  int16_t ch;
};
struct Params {
  const __nv_bfloat16 *ssm_D, *b1, *b2;
  Role role[132];
  CUtensorMap m_w1, m_w1l, m_ust, m_w2, m_uld, m_out, m_x, m_y, m_ub;
};

#define TLREC(i) do { } while (0)
#define TLEND() do { } while (0)

__device__ __forceinline__ uint32_t smem_u32(const void* p) { return (uint32_t)__cvta_generic_to_shared(p); }
__device__ __forceinline__ void mbar_init(uint32_t bar, uint32_t cnt) { asm volatile("mbarrier.init.shared::cta.b64 [%0], %1;" :: "r"(bar), "r"(cnt) : "memory"); }
__device__ __forceinline__ void mbar_expect_tx(uint32_t bar, uint32_t bytes) { asm volatile("mbarrier.arrive.expect_tx.shared::cta.b64 _, [%0], %1;" :: "r"(bar), "r"(bytes) : "memory"); }
__device__ __forceinline__ void mbar_arrive(uint32_t bar) { asm volatile("mbarrier.arrive.shared::cta.b64 _, [%0];" :: "r"(bar) : "memory"); }
__device__ __forceinline__ uint32_t mapa(uint32_t addr, uint32_t cta) { uint32_t r; asm volatile("mapa.shared::cluster.u32 %0, %1, %2;" : "=r"(r) : "r"(addr), "r"(cta)); return r; }
__device__ __forceinline__ void mbar_arrive_remote(uint32_t rbar) { asm volatile("mbarrier.arrive.shared::cluster.b64 _, [%0];" :: "r"(rbar) : "memory"); }
__device__ __forceinline__ uint32_t clk() { uint32_t c; asm volatile("mov.u32 %0, %%clock;" : "=r"(c)); return c; }
__device__ __forceinline__ bool elect_one() {
  uint32_t p; asm volatile("{ .reg .pred p; elect.sync _|p, 0xffffffff; selp.u32 %0, 1, 0, p; }" : "=r"(p)); return p;
}
__device__ __forceinline__ void guard(uint32_t t0) { if ((int32_t)(clk() - t0) < 0) __trap(); }
__device__ __forceinline__ void mbar_wait(uint32_t bar, uint32_t parity) {
  asm volatile("{\n .reg .pred p;\n W_%=:\n mbarrier.try_wait.parity.shared::cta.b64 p, [%0], %1;\n @!p bra W_%=;\n }" :: "r"(bar), "r"(parity) : "memory");
}
__device__ __forceinline__ void mbar_wait_cluster(uint32_t bar, uint32_t parity) {
  asm volatile("{\n .reg .pred p;\n W_%=:\n mbarrier.try_wait.parity.acquire.cluster.shared::cta.b64 p, [%0], %1;\n @!p bra W_%=;\n }" :: "r"(bar), "r"(parity) : "memory");
}
__device__ __forceinline__ bool mbar_try(uint32_t bar, uint32_t parity) {
  uint32_t ok;
  asm volatile("{ .reg .pred p; mbarrier.try_wait.parity.shared::cta.b64 p, [%1], %2; selp.u32 %0, 1, 0, p; }" : "=r"(ok) : "r"(bar), "r"(parity) : "memory");
  return ok;
}
__device__ __forceinline__ void mbar_wait_guarded(uint32_t bar, uint32_t t0, uint32_t parity = 0) { while (!mbar_try(bar, parity)) guard(t0); }
__device__ __forceinline__ void tma2d(uint32_t dst, const CUtensorMap* m, int c0, int c1, uint32_t bar) {
  asm volatile("cp.async.bulk.tensor.2d.shared::cluster.global.mbarrier::complete_tx::bytes [%0], [%1, {%3, %4}], [%2];"
               :: "r"(dst), "l"(m), "r"(bar), "r"(c0), "r"(c1) : "memory");
}
__device__ __forceinline__ void tma3d(uint32_t dst, const CUtensorMap* m, int c0, int c1, int c2, uint32_t bar) {
  asm volatile("cp.async.bulk.tensor.3d.shared::cluster.global.mbarrier::complete_tx::bytes [%0], [%1, {%3, %4, %5}], [%2];"
               :: "r"(dst), "l"(m), "r"(bar), "r"(c0), "r"(c1), "r"(c2) : "memory");
}
__device__ __forceinline__ void tma2d_store(const CUtensorMap* m, uint32_t src, int c0, int c1) {
  asm volatile("cp.async.bulk.tensor.2d.global.shared::cta.bulk_group [%0, {%2, %3}], [%1];" :: "l"(m), "r"(src), "r"(c0), "r"(c1) : "memory");
}
__device__ __forceinline__ void bulk_load(uint32_t dst, const void* src, uint32_t bytes, uint32_t bar) {
  asm volatile("cp.async.bulk.shared::cluster.global.mbarrier::complete_tx::bytes [%0], [%1], %2, [%3];" :: "r"(dst), "l"(src), "r"(bytes), "r"(bar) : "memory");
}
__device__ __forceinline__ void tma3d_store(const CUtensorMap* m, uint32_t src, int c0, int c1, int c2) {
  asm volatile("cp.async.bulk.tensor.3d.global.shared::cta.bulk_group [%0, {%2, %3, %4}], [%1];" :: "l"(m), "r"(src), "r"(c0), "r"(c1), "r"(c2) : "memory");
}
__device__ __forceinline__ void bulk_commit() { asm volatile("cp.async.bulk.commit_group;" ::: "memory"); }
__device__ __forceinline__ void bulk_wait_all() { asm volatile("cp.async.bulk.wait_group 0;" ::: "memory"); }
__device__ __forceinline__ void bulk_wait_read() { asm volatile("cp.async.bulk.wait_group.read 0;" ::: "memory"); }
__device__ __forceinline__ void fence_async_smem() { asm volatile("fence.proxy.async.shared::cta;" ::: "memory"); }
__device__ __forceinline__ void fence_async_global() { asm volatile("fence.proxy.async.global;" ::: "memory"); }
__device__ __forceinline__ uint32_t ld_cnt(Scratch* S, int c) { uint32_t v; asm volatile("ld.relaxed.gpu.global.u32 %0, [%1];" : "=r"(v) : "l"(S->cnt + c * 32) : "memory"); return v; }
__device__ __forceinline__ void signal(Scratch* S, int c, uint32_t inc) { asm volatile("red.release.gpu.global.add.u32 [%0], %1;" :: "l"(S->cnt + c * 32), "r"(inc) : "memory"); }
__device__ __forceinline__ bool reached(Scratch* S, int c, uint32_t ep) { return ld_cnt(S, c) - ep >= EPOCH; }
__device__ __forceinline__ void await(Scratch* S, int c, uint32_t ep) { while (!reached(S, c, ep)) { } }
__device__ __forceinline__ void bar_sync(int id, int n) { asm volatile("bar.sync %0, %1;" :: "r"(id), "r"(n) : "memory"); }
__device__ __forceinline__ void bar_arrive(int id, int n) { asm volatile("bar.arrive %0, %1;" :: "r"(id), "r"(n) : "memory"); }
__device__ __forceinline__ void wg_fence() { asm volatile("wgmma.fence.sync.aligned;" ::: "memory"); }
__device__ __forceinline__ void wg_commit() { asm volatile("wgmma.commit_group.sync.aligned;" ::: "memory"); }
template <int N> __device__ __forceinline__ void wg_wait() { asm volatile("wgmma.wait_group.sync.aligned %0;" :: "n"(N) : "memory"); }
template <int N> __device__ __forceinline__ void pin_regs(float* a) {
#pragma unroll
  for (int i = 0; i < N; i++) asm volatile("" : "+f"(a[i]) :: "memory");
}
__device__ __forceinline__ uint64_t make_desc(uint32_t addr, uint32_t lbo, uint32_t sbo, uint32_t swz) {
  return (uint64_t)((addr & 0x3FFFF) >> 4) | ((uint64_t)(lbo >> 4) << 16) | ((uint64_t)(sbo >> 4) << 32) | ((uint64_t)swz << 62);
}
__device__ __forceinline__ uint32_t pack_bf16(float lo, float hi) { uint32_t r; asm("cvt.rn.bf16x2.f32 %0, %1, %2;" : "=r"(r) : "f"(hi), "f"(lo)); return r; }
__device__ __forceinline__ float bf_lo(uint32_t p) { return __uint_as_float(p << 16); }
__device__ __forceinline__ float bf_hi(uint32_t p) { return __uint_as_float(p & 0xffff0000u); }
__device__ __forceinline__ float round_bf16(float v) { return bf_lo(pack_bf16(v, 0.f)); }
__device__ __forceinline__ uint32_t bmul2(uint32_t a, uint32_t b) { uint32_t r; asm("mul.rn.bf16x2 %0, %1, %2;" : "=r"(r) : "r"(a), "r"(b)); return r; }
__device__ __forceinline__ uint32_t badd2(uint32_t a, uint32_t b) { uint32_t r; asm("add.rn.bf16x2 %0, %1, %2;" : "=r"(r) : "r"(a), "r"(b)); return r; }
__device__ __forceinline__ uint32_t bfma2(uint32_t a, uint32_t b, uint32_t c) { uint32_t r; asm("fma.rn.bf16x2 %0, %1, %2, %3;" : "=r"(r) : "r"(a), "r"(b), "r"(c)); return r; }
__device__ __forceinline__ uint32_t bsub2(uint32_t a, uint32_t b) { uint32_t r; asm("sub.rn.bf16x2 %0, %1, %2;" : "=r"(r) : "r"(a), "r"(b)); return r; }
__device__ __forceinline__ float tanh_fast(float v) { float r; asm("tanh.approx.f32 %0, %1;" : "=f"(r) : "f"(v)); return r; }
__device__ __forceinline__ float gelu_half(float h) {
  return fmaf(h, tanh_fast(h * fmaf(h * h, 8.0f * 0.7978845608028654f * 0.044715f, 2.0f * 0.7978845608028654f)), h);
}
__device__ __forceinline__ float silu_half(float h) { return fmaf(h, tanh_fast(h), h); }
__device__ __forceinline__ uint32_t ldg32(const void* p) { uint32_t v; asm volatile("ld.global.u32 %0, [%1];" : "=r"(v) : "l"(p) : "memory"); return v; }
__device__ __forceinline__ uint32_t lds16(uint32_t a) { uint32_t v; asm volatile("ld.shared.u16 %0, [%1];" : "=r"(v) : "r"(a) : "memory"); return v; }
__device__ __forceinline__ uint4 lds128(uint32_t a) { uint4 v; asm volatile("ld.shared.v4.u32 {%0,%1,%2,%3}, [%4];" : "=r"(v.x), "=r"(v.y), "=r"(v.z), "=r"(v.w) : "r"(a) : "memory"); return v; }
__device__ __forceinline__ void sts128(uint32_t a, uint32_t x, uint32_t y, uint32_t z, uint32_t w) {
  asm volatile("st.shared.v4.u32 [%0], {%1,%2,%3,%4};" :: "r"(a), "r"(x), "r"(y), "r"(z), "r"(w) : "memory");
}
__device__ __forceinline__ void sts32(uint32_t a, uint32_t v) { asm volatile("st.shared.u32 [%0], %1;" :: "r"(a), "r"(v) : "memory"); }
__device__ __forceinline__ void ldsm4(uint32_t* r, uint32_t a) {
  asm volatile("ldmatrix.sync.aligned.m8n8.x4.shared.b16 {%0,%1,%2,%3}, [%4];" : "=r"(r[0]), "=r"(r[1]), "=r"(r[2]), "=r"(r[3]) : "r"(a) : "memory");
}
__device__ __forceinline__ void ldsm2(uint32_t* r, uint32_t a) {
  asm volatile("ldmatrix.sync.aligned.m8n8.x2.shared.b16 {%0,%1}, [%2];" : "=r"(r[0]), "=r"(r[1]) : "r"(a) : "memory");
}
__device__ __forceinline__ void ldsm4t(uint32_t* r, uint32_t a) {
  asm volatile("ldmatrix.sync.aligned.m8n8.x4.trans.shared.b16 {%0,%1,%2,%3}, [%4];" : "=r"(r[0]), "=r"(r[1]), "=r"(r[2]), "=r"(r[3]) : "r"(a) : "memory");
}
__device__ __forceinline__ void ldsm2t(uint32_t* r, uint32_t a) {
  asm volatile("ldmatrix.sync.aligned.m8n8.x2.trans.shared.b16 {%0,%1}, [%2];" : "=r"(r[0]), "=r"(r[1]) : "r"(a) : "memory");
}
__device__ __forceinline__ void stsm4(uint32_t a, uint32_t r0, uint32_t r1, uint32_t r2, uint32_t r3) {
  asm volatile("stmatrix.sync.aligned.m8n8.x4.shared.b16 [%0], {%1,%2,%3,%4};" :: "r"(a), "r"(r0), "r"(r1), "r"(r2), "r"(r3) : "memory");
}
__device__ __forceinline__ void stsm2(uint32_t a, uint32_t r0, uint32_t r1) {
  asm volatile("stmatrix.sync.aligned.m8n8.x2.shared.b16 [%0], {%1,%2};" :: "r"(a), "r"(r0), "r"(r1) : "memory");
}
__device__ __forceinline__ void stsm4t(uint32_t a, uint32_t r0, uint32_t r1, uint32_t r2, uint32_t r3) {
  asm volatile("stmatrix.sync.aligned.m8n8.x4.trans.shared.b16 [%0], {%1,%2,%3,%4};" :: "r"(a), "r"(r0), "r"(r1), "r"(r2), "r"(r3) : "memory");
}

__device__ __forceinline__ void wgmma_ss_n144_t10(float* d, uint64_t da, uint64_t db, int sd) {
  asm volatile("{ .reg .pred p; setp.ne.b32 p, %74, 0;\n"
      "wgmma.mma_async.sync.aligned.m64n144k16.f32.bf16.bf16 {"
      "%0,%1,%2,%3,%4,%5,%6,%7,%8,%9,%10,%11,%12,%13,%14,%15,"
      "%16,%17,%18,%19,%20,%21,%22,%23,%24,%25,%26,%27,%28,%29,%30,%31,"
      "%32,%33,%34,%35,%36,%37,%38,%39,%40,%41,%42,%43,%44,%45,%46,%47,"
      "%48,%49,%50,%51,%52,%53,%54,%55,%56,%57,%58,%59,%60,%61,%62,%63,"
      "%64,%65,%66,%67,%68,%69,%70,%71"
      "}, %72, %73, p, 1, 1, 1, 0; }"
    : "+f"(d[0]), "+f"(d[1]), "+f"(d[2]), "+f"(d[3]), "+f"(d[4]), "+f"(d[5]), "+f"(d[6]), "+f"(d[7]),
      "+f"(d[8]), "+f"(d[9]), "+f"(d[10]), "+f"(d[11]), "+f"(d[12]), "+f"(d[13]), "+f"(d[14]), "+f"(d[15]),
      "+f"(d[16]), "+f"(d[17]), "+f"(d[18]), "+f"(d[19]), "+f"(d[20]), "+f"(d[21]), "+f"(d[22]), "+f"(d[23]),
      "+f"(d[24]), "+f"(d[25]), "+f"(d[26]), "+f"(d[27]), "+f"(d[28]), "+f"(d[29]), "+f"(d[30]), "+f"(d[31]),
      "+f"(d[32]), "+f"(d[33]), "+f"(d[34]), "+f"(d[35]), "+f"(d[36]), "+f"(d[37]), "+f"(d[38]), "+f"(d[39]),
      "+f"(d[40]), "+f"(d[41]), "+f"(d[42]), "+f"(d[43]), "+f"(d[44]), "+f"(d[45]), "+f"(d[46]), "+f"(d[47]),
      "+f"(d[48]), "+f"(d[49]), "+f"(d[50]), "+f"(d[51]), "+f"(d[52]), "+f"(d[53]), "+f"(d[54]), "+f"(d[55]),
      "+f"(d[56]), "+f"(d[57]), "+f"(d[58]), "+f"(d[59]), "+f"(d[60]), "+f"(d[61]), "+f"(d[62]), "+f"(d[63]),
      "+f"(d[64]), "+f"(d[65]), "+f"(d[66]), "+f"(d[67]), "+f"(d[68]), "+f"(d[69]), "+f"(d[70]), "+f"(d[71])
    : "l"(da), "l"(db), "r"(sd));
}

__device__ __forceinline__ void wgmma_ss_n160_t11(float* d, uint64_t da, uint64_t db, int sd) {
  asm volatile("{ .reg .pred p; setp.ne.b32 p, %82, 0;\n"
      "wgmma.mma_async.sync.aligned.m64n160k16.f32.bf16.bf16 {"
      "%0,%1,%2,%3,%4,%5,%6,%7,%8,%9,%10,%11,%12,%13,%14,%15,"
      "%16,%17,%18,%19,%20,%21,%22,%23,%24,%25,%26,%27,%28,%29,%30,%31,"
      "%32,%33,%34,%35,%36,%37,%38,%39,%40,%41,%42,%43,%44,%45,%46,%47,"
      "%48,%49,%50,%51,%52,%53,%54,%55,%56,%57,%58,%59,%60,%61,%62,%63,"
      "%64,%65,%66,%67,%68,%69,%70,%71,%72,%73,%74,%75,%76,%77,%78,%79"
      "}, %80, %81, p, 1, 1, 1, 1; }"
    : "+f"(d[0]), "+f"(d[1]), "+f"(d[2]), "+f"(d[3]), "+f"(d[4]), "+f"(d[5]), "+f"(d[6]), "+f"(d[7]),
      "+f"(d[8]), "+f"(d[9]), "+f"(d[10]), "+f"(d[11]), "+f"(d[12]), "+f"(d[13]), "+f"(d[14]), "+f"(d[15]),
      "+f"(d[16]), "+f"(d[17]), "+f"(d[18]), "+f"(d[19]), "+f"(d[20]), "+f"(d[21]), "+f"(d[22]), "+f"(d[23]),
      "+f"(d[24]), "+f"(d[25]), "+f"(d[26]), "+f"(d[27]), "+f"(d[28]), "+f"(d[29]), "+f"(d[30]), "+f"(d[31]),
      "+f"(d[32]), "+f"(d[33]), "+f"(d[34]), "+f"(d[35]), "+f"(d[36]), "+f"(d[37]), "+f"(d[38]), "+f"(d[39]),
      "+f"(d[40]), "+f"(d[41]), "+f"(d[42]), "+f"(d[43]), "+f"(d[44]), "+f"(d[45]), "+f"(d[46]), "+f"(d[47]),
      "+f"(d[48]), "+f"(d[49]), "+f"(d[50]), "+f"(d[51]), "+f"(d[52]), "+f"(d[53]), "+f"(d[54]), "+f"(d[55]),
      "+f"(d[56]), "+f"(d[57]), "+f"(d[58]), "+f"(d[59]), "+f"(d[60]), "+f"(d[61]), "+f"(d[62]), "+f"(d[63]),
      "+f"(d[64]), "+f"(d[65]), "+f"(d[66]), "+f"(d[67]), "+f"(d[68]), "+f"(d[69]), "+f"(d[70]), "+f"(d[71]),
      "+f"(d[72]), "+f"(d[73]), "+f"(d[74]), "+f"(d[75]), "+f"(d[76]), "+f"(d[77]), "+f"(d[78]), "+f"(d[79])
    : "l"(da), "l"(db), "r"(sd));
}

__device__ __forceinline__ void wgmma_ss_n96_t11(float* d, uint64_t da, uint64_t db, int sd) {
  asm volatile("{ .reg .pred p; setp.ne.b32 p, %50, 0;\n"
      "wgmma.mma_async.sync.aligned.m64n96k16.f32.bf16.bf16 {"
      "%0,%1,%2,%3,%4,%5,%6,%7,%8,%9,%10,%11,%12,%13,%14,%15,"
      "%16,%17,%18,%19,%20,%21,%22,%23,%24,%25,%26,%27,%28,%29,%30,%31,"
      "%32,%33,%34,%35,%36,%37,%38,%39,%40,%41,%42,%43,%44,%45,%46,%47"
      "}, %48, %49, p, 1, 1, 1, 1; }"
    : "+f"(d[0]), "+f"(d[1]), "+f"(d[2]), "+f"(d[3]), "+f"(d[4]), "+f"(d[5]), "+f"(d[6]), "+f"(d[7]),
      "+f"(d[8]), "+f"(d[9]), "+f"(d[10]), "+f"(d[11]), "+f"(d[12]), "+f"(d[13]), "+f"(d[14]), "+f"(d[15]),
      "+f"(d[16]), "+f"(d[17]), "+f"(d[18]), "+f"(d[19]), "+f"(d[20]), "+f"(d[21]), "+f"(d[22]), "+f"(d[23]),
      "+f"(d[24]), "+f"(d[25]), "+f"(d[26]), "+f"(d[27]), "+f"(d[28]), "+f"(d[29]), "+f"(d[30]), "+f"(d[31]),
      "+f"(d[32]), "+f"(d[33]), "+f"(d[34]), "+f"(d[35]), "+f"(d[36]), "+f"(d[37]), "+f"(d[38]), "+f"(d[39]),
      "+f"(d[40]), "+f"(d[41]), "+f"(d[42]), "+f"(d[43]), "+f"(d[44]), "+f"(d[45]), "+f"(d[46]), "+f"(d[47])
    : "l"(da), "l"(db), "r"(sd));
}

__device__ __forceinline__ void wgmma_rs_n16(float* d, const uint32_t* a, uint64_t db, int sd) {
  asm volatile("{ .reg .pred p; setp.ne.b32 p, %13, 0;\n"
      "wgmma.mma_async.sync.aligned.m64n16k16.f32.bf16.bf16 {"
      "%0,%1,%2,%3,%4,%5,%6,%7"
      "}, {%8,%9,%10,%11}, %12, p, 1, 1, 0; }"
    : "+f"(d[0]), "+f"(d[1]), "+f"(d[2]), "+f"(d[3]), "+f"(d[4]), "+f"(d[5]), "+f"(d[6]), "+f"(d[7])
    : "r"(a[0]), "r"(a[1]), "r"(a[2]), "r"(a[3]), "l"(db), "r"(sd));
}

__device__ __forceinline__ void wgmma_rs_n32(float* d, const uint32_t* a, uint64_t db, int sd) {
  asm volatile("{ .reg .pred p; setp.ne.b32 p, %21, 0;\n"
      "wgmma.mma_async.sync.aligned.m64n32k16.f32.bf16.bf16 {"
      "%0,%1,%2,%3,%4,%5,%6,%7,%8,%9,%10,%11,%12,%13,%14,%15"
      "}, {%16,%17,%18,%19}, %20, p, 1, 1, 0; }"
    : "+f"(d[0]), "+f"(d[1]), "+f"(d[2]), "+f"(d[3]), "+f"(d[4]), "+f"(d[5]), "+f"(d[6]), "+f"(d[7]),
      "+f"(d[8]), "+f"(d[9]), "+f"(d[10]), "+f"(d[11]), "+f"(d[12]), "+f"(d[13]), "+f"(d[14]), "+f"(d[15])
    : "r"(a[0]), "r"(a[1]), "r"(a[2]), "r"(a[3]), "l"(db), "r"(sd));
}

__device__ __forceinline__ void wgmma_rs_n48(float* d, const uint32_t* a, uint64_t db, int sd) {
  asm volatile("{ .reg .pred p; setp.ne.b32 p, %29, 0;\n"
      "wgmma.mma_async.sync.aligned.m64n48k16.f32.bf16.bf16 {"
      "%0,%1,%2,%3,%4,%5,%6,%7,%8,%9,%10,%11,%12,%13,%14,%15,"
      "%16,%17,%18,%19,%20,%21,%22,%23"
      "}, {%24,%25,%26,%27}, %28, p, 1, 1, 0; }"
    : "+f"(d[0]), "+f"(d[1]), "+f"(d[2]), "+f"(d[3]), "+f"(d[4]), "+f"(d[5]), "+f"(d[6]), "+f"(d[7]),
      "+f"(d[8]), "+f"(d[9]), "+f"(d[10]), "+f"(d[11]), "+f"(d[12]), "+f"(d[13]), "+f"(d[14]), "+f"(d[15]),
      "+f"(d[16]), "+f"(d[17]), "+f"(d[18]), "+f"(d[19]), "+f"(d[20]), "+f"(d[21]), "+f"(d[22]), "+f"(d[23])
    : "r"(a[0]), "r"(a[1]), "r"(a[2]), "r"(a[3]), "l"(db), "r"(sd));
}

__device__ __forceinline__ void wgmma_rs_n64(float* d, const uint32_t* a, uint64_t db, int sd) {
  asm volatile("{ .reg .pred p; setp.ne.b32 p, %37, 0;\n"
      "wgmma.mma_async.sync.aligned.m64n64k16.f32.bf16.bf16 {"
      "%0,%1,%2,%3,%4,%5,%6,%7,%8,%9,%10,%11,%12,%13,%14,%15,"
      "%16,%17,%18,%19,%20,%21,%22,%23,%24,%25,%26,%27,%28,%29,%30,%31"
      "}, {%32,%33,%34,%35}, %36, p, 1, 1, 0; }"
    : "+f"(d[0]), "+f"(d[1]), "+f"(d[2]), "+f"(d[3]), "+f"(d[4]), "+f"(d[5]), "+f"(d[6]), "+f"(d[7]),
      "+f"(d[8]), "+f"(d[9]), "+f"(d[10]), "+f"(d[11]), "+f"(d[12]), "+f"(d[13]), "+f"(d[14]), "+f"(d[15]),
      "+f"(d[16]), "+f"(d[17]), "+f"(d[18]), "+f"(d[19]), "+f"(d[20]), "+f"(d[21]), "+f"(d[22]), "+f"(d[23]),
      "+f"(d[24]), "+f"(d[25]), "+f"(d[26]), "+f"(d[27]), "+f"(d[28]), "+f"(d[29]), "+f"(d[30]), "+f"(d[31])
    : "r"(a[0]), "r"(a[1]), "r"(a[2]), "r"(a[3]), "l"(db), "r"(sd));
}

__device__ __forceinline__ void wgmma_rs_n80(float* d, const uint32_t* a, uint64_t db, int sd) {
  asm volatile("{ .reg .pred p; setp.ne.b32 p, %45, 0;\n"
      "wgmma.mma_async.sync.aligned.m64n80k16.f32.bf16.bf16 {"
      "%0,%1,%2,%3,%4,%5,%6,%7,%8,%9,%10,%11,%12,%13,%14,%15,"
      "%16,%17,%18,%19,%20,%21,%22,%23,%24,%25,%26,%27,%28,%29,%30,%31,"
      "%32,%33,%34,%35,%36,%37,%38,%39"
      "}, {%40,%41,%42,%43}, %44, p, 1, 1, 0; }"
    : "+f"(d[0]), "+f"(d[1]), "+f"(d[2]), "+f"(d[3]), "+f"(d[4]), "+f"(d[5]), "+f"(d[6]), "+f"(d[7]),
      "+f"(d[8]), "+f"(d[9]), "+f"(d[10]), "+f"(d[11]), "+f"(d[12]), "+f"(d[13]), "+f"(d[14]), "+f"(d[15]),
      "+f"(d[16]), "+f"(d[17]), "+f"(d[18]), "+f"(d[19]), "+f"(d[20]), "+f"(d[21]), "+f"(d[22]), "+f"(d[23]),
      "+f"(d[24]), "+f"(d[25]), "+f"(d[26]), "+f"(d[27]), "+f"(d[28]), "+f"(d[29]), "+f"(d[30]), "+f"(d[31]),
      "+f"(d[32]), "+f"(d[33]), "+f"(d[34]), "+f"(d[35]), "+f"(d[36]), "+f"(d[37]), "+f"(d[38]), "+f"(d[39])
    : "r"(a[0]), "r"(a[1]), "r"(a[2]), "r"(a[3]), "l"(db), "r"(sd));
}

__device__ __forceinline__ void wgmma_rs_n96(float* d, const uint32_t* a, uint64_t db, int sd) {
  asm volatile("{ .reg .pred p; setp.ne.b32 p, %53, 0;\n"
      "wgmma.mma_async.sync.aligned.m64n96k16.f32.bf16.bf16 {"
      "%0,%1,%2,%3,%4,%5,%6,%7,%8,%9,%10,%11,%12,%13,%14,%15,"
      "%16,%17,%18,%19,%20,%21,%22,%23,%24,%25,%26,%27,%28,%29,%30,%31,"
      "%32,%33,%34,%35,%36,%37,%38,%39,%40,%41,%42,%43,%44,%45,%46,%47"
      "}, {%48,%49,%50,%51}, %52, p, 1, 1, 0; }"
    : "+f"(d[0]), "+f"(d[1]), "+f"(d[2]), "+f"(d[3]), "+f"(d[4]), "+f"(d[5]), "+f"(d[6]), "+f"(d[7]),
      "+f"(d[8]), "+f"(d[9]), "+f"(d[10]), "+f"(d[11]), "+f"(d[12]), "+f"(d[13]), "+f"(d[14]), "+f"(d[15]),
      "+f"(d[16]), "+f"(d[17]), "+f"(d[18]), "+f"(d[19]), "+f"(d[20]), "+f"(d[21]), "+f"(d[22]), "+f"(d[23]),
      "+f"(d[24]), "+f"(d[25]), "+f"(d[26]), "+f"(d[27]), "+f"(d[28]), "+f"(d[29]), "+f"(d[30]), "+f"(d[31]),
      "+f"(d[32]), "+f"(d[33]), "+f"(d[34]), "+f"(d[35]), "+f"(d[36]), "+f"(d[37]), "+f"(d[38]), "+f"(d[39]),
      "+f"(d[40]), "+f"(d[41]), "+f"(d[42]), "+f"(d[43]), "+f"(d[44]), "+f"(d[45]), "+f"(d[46]), "+f"(d[47])
    : "r"(a[0]), "r"(a[1]), "r"(a[2]), "r"(a[3]), "l"(db), "r"(sd));
}

__device__ __forceinline__ void wgmma_rs_n112(float* d, const uint32_t* a, uint64_t db, int sd) {
  asm volatile("{ .reg .pred p; setp.ne.b32 p, %61, 0;\n"
      "wgmma.mma_async.sync.aligned.m64n112k16.f32.bf16.bf16 {"
      "%0,%1,%2,%3,%4,%5,%6,%7,%8,%9,%10,%11,%12,%13,%14,%15,"
      "%16,%17,%18,%19,%20,%21,%22,%23,%24,%25,%26,%27,%28,%29,%30,%31,"
      "%32,%33,%34,%35,%36,%37,%38,%39,%40,%41,%42,%43,%44,%45,%46,%47,"
      "%48,%49,%50,%51,%52,%53,%54,%55"
      "}, {%56,%57,%58,%59}, %60, p, 1, 1, 0; }"
    : "+f"(d[0]), "+f"(d[1]), "+f"(d[2]), "+f"(d[3]), "+f"(d[4]), "+f"(d[5]), "+f"(d[6]), "+f"(d[7]),
      "+f"(d[8]), "+f"(d[9]), "+f"(d[10]), "+f"(d[11]), "+f"(d[12]), "+f"(d[13]), "+f"(d[14]), "+f"(d[15]),
      "+f"(d[16]), "+f"(d[17]), "+f"(d[18]), "+f"(d[19]), "+f"(d[20]), "+f"(d[21]), "+f"(d[22]), "+f"(d[23]),
      "+f"(d[24]), "+f"(d[25]), "+f"(d[26]), "+f"(d[27]), "+f"(d[28]), "+f"(d[29]), "+f"(d[30]), "+f"(d[31]),
      "+f"(d[32]), "+f"(d[33]), "+f"(d[34]), "+f"(d[35]), "+f"(d[36]), "+f"(d[37]), "+f"(d[38]), "+f"(d[39]),
      "+f"(d[40]), "+f"(d[41]), "+f"(d[42]), "+f"(d[43]), "+f"(d[44]), "+f"(d[45]), "+f"(d[46]), "+f"(d[47]),
      "+f"(d[48]), "+f"(d[49]), "+f"(d[50]), "+f"(d[51]), "+f"(d[52]), "+f"(d[53]), "+f"(d[54]), "+f"(d[55])
    : "r"(a[0]), "r"(a[1]), "r"(a[2]), "r"(a[3]), "l"(db), "r"(sd));
}

__device__ __forceinline__ void wgmma_rs_n128(float* d, const uint32_t* a, uint64_t db, int sd) {
  asm volatile("{ .reg .pred p; setp.ne.b32 p, %69, 0;\n"
      "wgmma.mma_async.sync.aligned.m64n128k16.f32.bf16.bf16 {"
      "%0,%1,%2,%3,%4,%5,%6,%7,%8,%9,%10,%11,%12,%13,%14,%15,"
      "%16,%17,%18,%19,%20,%21,%22,%23,%24,%25,%26,%27,%28,%29,%30,%31,"
      "%32,%33,%34,%35,%36,%37,%38,%39,%40,%41,%42,%43,%44,%45,%46,%47,"
      "%48,%49,%50,%51,%52,%53,%54,%55,%56,%57,%58,%59,%60,%61,%62,%63"
      "}, {%64,%65,%66,%67}, %68, p, 1, 1, 0; }"
    : "+f"(d[0]), "+f"(d[1]), "+f"(d[2]), "+f"(d[3]), "+f"(d[4]), "+f"(d[5]), "+f"(d[6]), "+f"(d[7]),
      "+f"(d[8]), "+f"(d[9]), "+f"(d[10]), "+f"(d[11]), "+f"(d[12]), "+f"(d[13]), "+f"(d[14]), "+f"(d[15]),
      "+f"(d[16]), "+f"(d[17]), "+f"(d[18]), "+f"(d[19]), "+f"(d[20]), "+f"(d[21]), "+f"(d[22]), "+f"(d[23]),
      "+f"(d[24]), "+f"(d[25]), "+f"(d[26]), "+f"(d[27]), "+f"(d[28]), "+f"(d[29]), "+f"(d[30]), "+f"(d[31]),
      "+f"(d[32]), "+f"(d[33]), "+f"(d[34]), "+f"(d[35]), "+f"(d[36]), "+f"(d[37]), "+f"(d[38]), "+f"(d[39]),
      "+f"(d[40]), "+f"(d[41]), "+f"(d[42]), "+f"(d[43]), "+f"(d[44]), "+f"(d[45]), "+f"(d[46]), "+f"(d[47]),
      "+f"(d[48]), "+f"(d[49]), "+f"(d[50]), "+f"(d[51]), "+f"(d[52]), "+f"(d[53]), "+f"(d[54]), "+f"(d[55]),
      "+f"(d[56]), "+f"(d[57]), "+f"(d[58]), "+f"(d[59]), "+f"(d[60]), "+f"(d[61]), "+f"(d[62]), "+f"(d[63])
    : "r"(a[0]), "r"(a[1]), "r"(a[2]), "r"(a[3]), "l"(db), "r"(sd));
}

__device__ __forceinline__ void wgmma_rs_n144(float* d, const uint32_t* a, uint64_t db, int sd) {
  asm volatile("{ .reg .pred p; setp.ne.b32 p, %77, 0;\n"
      "wgmma.mma_async.sync.aligned.m64n144k16.f32.bf16.bf16 {"
      "%0,%1,%2,%3,%4,%5,%6,%7,%8,%9,%10,%11,%12,%13,%14,%15,"
      "%16,%17,%18,%19,%20,%21,%22,%23,%24,%25,%26,%27,%28,%29,%30,%31,"
      "%32,%33,%34,%35,%36,%37,%38,%39,%40,%41,%42,%43,%44,%45,%46,%47,"
      "%48,%49,%50,%51,%52,%53,%54,%55,%56,%57,%58,%59,%60,%61,%62,%63,"
      "%64,%65,%66,%67,%68,%69,%70,%71"
      "}, {%72,%73,%74,%75}, %76, p, 1, 1, 0; }"
    : "+f"(d[0]), "+f"(d[1]), "+f"(d[2]), "+f"(d[3]), "+f"(d[4]), "+f"(d[5]), "+f"(d[6]), "+f"(d[7]),
      "+f"(d[8]), "+f"(d[9]), "+f"(d[10]), "+f"(d[11]), "+f"(d[12]), "+f"(d[13]), "+f"(d[14]), "+f"(d[15]),
      "+f"(d[16]), "+f"(d[17]), "+f"(d[18]), "+f"(d[19]), "+f"(d[20]), "+f"(d[21]), "+f"(d[22]), "+f"(d[23]),
      "+f"(d[24]), "+f"(d[25]), "+f"(d[26]), "+f"(d[27]), "+f"(d[28]), "+f"(d[29]), "+f"(d[30]), "+f"(d[31]),
      "+f"(d[32]), "+f"(d[33]), "+f"(d[34]), "+f"(d[35]), "+f"(d[36]), "+f"(d[37]), "+f"(d[38]), "+f"(d[39]),
      "+f"(d[40]), "+f"(d[41]), "+f"(d[42]), "+f"(d[43]), "+f"(d[44]), "+f"(d[45]), "+f"(d[46]), "+f"(d[47]),
      "+f"(d[48]), "+f"(d[49]), "+f"(d[50]), "+f"(d[51]), "+f"(d[52]), "+f"(d[53]), "+f"(d[54]), "+f"(d[55]),
      "+f"(d[56]), "+f"(d[57]), "+f"(d[58]), "+f"(d[59]), "+f"(d[60]), "+f"(d[61]), "+f"(d[62]), "+f"(d[63]),
      "+f"(d[64]), "+f"(d[65]), "+f"(d[66]), "+f"(d[67]), "+f"(d[68]), "+f"(d[69]), "+f"(d[70]), "+f"(d[71])
    : "r"(a[0]), "r"(a[1]), "r"(a[2]), "r"(a[3]), "l"(db), "r"(sd));
}

__device__ __forceinline__ void wgmma_rs_n160(float* d, const uint32_t* a, uint64_t db, int sd) {
  asm volatile("{ .reg .pred p; setp.ne.b32 p, %85, 0;\n"
      "wgmma.mma_async.sync.aligned.m64n160k16.f32.bf16.bf16 {"
      "%0,%1,%2,%3,%4,%5,%6,%7,%8,%9,%10,%11,%12,%13,%14,%15,"
      "%16,%17,%18,%19,%20,%21,%22,%23,%24,%25,%26,%27,%28,%29,%30,%31,"
      "%32,%33,%34,%35,%36,%37,%38,%39,%40,%41,%42,%43,%44,%45,%46,%47,"
      "%48,%49,%50,%51,%52,%53,%54,%55,%56,%57,%58,%59,%60,%61,%62,%63,"
      "%64,%65,%66,%67,%68,%69,%70,%71,%72,%73,%74,%75,%76,%77,%78,%79"
      "}, {%80,%81,%82,%83}, %84, p, 1, 1, 0; }"
    : "+f"(d[0]), "+f"(d[1]), "+f"(d[2]), "+f"(d[3]), "+f"(d[4]), "+f"(d[5]), "+f"(d[6]), "+f"(d[7]),
      "+f"(d[8]), "+f"(d[9]), "+f"(d[10]), "+f"(d[11]), "+f"(d[12]), "+f"(d[13]), "+f"(d[14]), "+f"(d[15]),
      "+f"(d[16]), "+f"(d[17]), "+f"(d[18]), "+f"(d[19]), "+f"(d[20]), "+f"(d[21]), "+f"(d[22]), "+f"(d[23]),
      "+f"(d[24]), "+f"(d[25]), "+f"(d[26]), "+f"(d[27]), "+f"(d[28]), "+f"(d[29]), "+f"(d[30]), "+f"(d[31]),
      "+f"(d[32]), "+f"(d[33]), "+f"(d[34]), "+f"(d[35]), "+f"(d[36]), "+f"(d[37]), "+f"(d[38]), "+f"(d[39]),
      "+f"(d[40]), "+f"(d[41]), "+f"(d[42]), "+f"(d[43]), "+f"(d[44]), "+f"(d[45]), "+f"(d[46]), "+f"(d[47]),
      "+f"(d[48]), "+f"(d[49]), "+f"(d[50]), "+f"(d[51]), "+f"(d[52]), "+f"(d[53]), "+f"(d[54]), "+f"(d[55]),
      "+f"(d[56]), "+f"(d[57]), "+f"(d[58]), "+f"(d[59]), "+f"(d[60]), "+f"(d[61]), "+f"(d[62]), "+f"(d[63]),
      "+f"(d[64]), "+f"(d[65]), "+f"(d[66]), "+f"(d[67]), "+f"(d[68]), "+f"(d[69]), "+f"(d[70]), "+f"(d[71]),
      "+f"(d[72]), "+f"(d[73]), "+f"(d[74]), "+f"(d[75]), "+f"(d[76]), "+f"(d[77]), "+f"(d[78]), "+f"(d[79])
    : "r"(a[0]), "r"(a[1]), "r"(a[2]), "r"(a[3]), "l"(db), "r"(sd));
}

__device__ __forceinline__ void wgmma_rs_n176(float* d, const uint32_t* a, uint64_t db, int sd) {
  asm volatile("{ .reg .pred p; setp.ne.b32 p, %93, 0;\n"
      "wgmma.mma_async.sync.aligned.m64n176k16.f32.bf16.bf16 {"
      "%0,%1,%2,%3,%4,%5,%6,%7,%8,%9,%10,%11,%12,%13,%14,%15,"
      "%16,%17,%18,%19,%20,%21,%22,%23,%24,%25,%26,%27,%28,%29,%30,%31,"
      "%32,%33,%34,%35,%36,%37,%38,%39,%40,%41,%42,%43,%44,%45,%46,%47,"
      "%48,%49,%50,%51,%52,%53,%54,%55,%56,%57,%58,%59,%60,%61,%62,%63,"
      "%64,%65,%66,%67,%68,%69,%70,%71,%72,%73,%74,%75,%76,%77,%78,%79,"
      "%80,%81,%82,%83,%84,%85,%86,%87"
      "}, {%88,%89,%90,%91}, %92, p, 1, 1, 0; }"
    : "+f"(d[0]), "+f"(d[1]), "+f"(d[2]), "+f"(d[3]), "+f"(d[4]), "+f"(d[5]), "+f"(d[6]), "+f"(d[7]),
      "+f"(d[8]), "+f"(d[9]), "+f"(d[10]), "+f"(d[11]), "+f"(d[12]), "+f"(d[13]), "+f"(d[14]), "+f"(d[15]),
      "+f"(d[16]), "+f"(d[17]), "+f"(d[18]), "+f"(d[19]), "+f"(d[20]), "+f"(d[21]), "+f"(d[22]), "+f"(d[23]),
      "+f"(d[24]), "+f"(d[25]), "+f"(d[26]), "+f"(d[27]), "+f"(d[28]), "+f"(d[29]), "+f"(d[30]), "+f"(d[31]),
      "+f"(d[32]), "+f"(d[33]), "+f"(d[34]), "+f"(d[35]), "+f"(d[36]), "+f"(d[37]), "+f"(d[38]), "+f"(d[39]),
      "+f"(d[40]), "+f"(d[41]), "+f"(d[42]), "+f"(d[43]), "+f"(d[44]), "+f"(d[45]), "+f"(d[46]), "+f"(d[47]),
      "+f"(d[48]), "+f"(d[49]), "+f"(d[50]), "+f"(d[51]), "+f"(d[52]), "+f"(d[53]), "+f"(d[54]), "+f"(d[55]),
      "+f"(d[56]), "+f"(d[57]), "+f"(d[58]), "+f"(d[59]), "+f"(d[60]), "+f"(d[61]), "+f"(d[62]), "+f"(d[63]),
      "+f"(d[64]), "+f"(d[65]), "+f"(d[66]), "+f"(d[67]), "+f"(d[68]), "+f"(d[69]), "+f"(d[70]), "+f"(d[71]),
      "+f"(d[72]), "+f"(d[73]), "+f"(d[74]), "+f"(d[75]), "+f"(d[76]), "+f"(d[77]), "+f"(d[78]), "+f"(d[79]),
      "+f"(d[80]), "+f"(d[81]), "+f"(d[82]), "+f"(d[83]), "+f"(d[84]), "+f"(d[85]), "+f"(d[86]), "+f"(d[87])
    : "r"(a[0]), "r"(a[1]), "r"(a[2]), "r"(a[3]), "l"(db), "r"(sd));
}

__device__ __forceinline__ void wgmma_rs_n192(float* d, const uint32_t* a, uint64_t db, int sd) {
  asm volatile("{ .reg .pred p; setp.ne.b32 p, %101, 0;\n"
      "wgmma.mma_async.sync.aligned.m64n192k16.f32.bf16.bf16 {"
      "%0,%1,%2,%3,%4,%5,%6,%7,%8,%9,%10,%11,%12,%13,%14,%15,"
      "%16,%17,%18,%19,%20,%21,%22,%23,%24,%25,%26,%27,%28,%29,%30,%31,"
      "%32,%33,%34,%35,%36,%37,%38,%39,%40,%41,%42,%43,%44,%45,%46,%47,"
      "%48,%49,%50,%51,%52,%53,%54,%55,%56,%57,%58,%59,%60,%61,%62,%63,"
      "%64,%65,%66,%67,%68,%69,%70,%71,%72,%73,%74,%75,%76,%77,%78,%79,"
      "%80,%81,%82,%83,%84,%85,%86,%87,%88,%89,%90,%91,%92,%93,%94,%95"
      "}, {%96,%97,%98,%99}, %100, p, 1, 1, 0; }"
    : "+f"(d[0]), "+f"(d[1]), "+f"(d[2]), "+f"(d[3]), "+f"(d[4]), "+f"(d[5]), "+f"(d[6]), "+f"(d[7]),
      "+f"(d[8]), "+f"(d[9]), "+f"(d[10]), "+f"(d[11]), "+f"(d[12]), "+f"(d[13]), "+f"(d[14]), "+f"(d[15]),
      "+f"(d[16]), "+f"(d[17]), "+f"(d[18]), "+f"(d[19]), "+f"(d[20]), "+f"(d[21]), "+f"(d[22]), "+f"(d[23]),
      "+f"(d[24]), "+f"(d[25]), "+f"(d[26]), "+f"(d[27]), "+f"(d[28]), "+f"(d[29]), "+f"(d[30]), "+f"(d[31]),
      "+f"(d[32]), "+f"(d[33]), "+f"(d[34]), "+f"(d[35]), "+f"(d[36]), "+f"(d[37]), "+f"(d[38]), "+f"(d[39]),
      "+f"(d[40]), "+f"(d[41]), "+f"(d[42]), "+f"(d[43]), "+f"(d[44]), "+f"(d[45]), "+f"(d[46]), "+f"(d[47]),
      "+f"(d[48]), "+f"(d[49]), "+f"(d[50]), "+f"(d[51]), "+f"(d[52]), "+f"(d[53]), "+f"(d[54]), "+f"(d[55]),
      "+f"(d[56]), "+f"(d[57]), "+f"(d[58]), "+f"(d[59]), "+f"(d[60]), "+f"(d[61]), "+f"(d[62]), "+f"(d[63]),
      "+f"(d[64]), "+f"(d[65]), "+f"(d[66]), "+f"(d[67]), "+f"(d[68]), "+f"(d[69]), "+f"(d[70]), "+f"(d[71]),
      "+f"(d[72]), "+f"(d[73]), "+f"(d[74]), "+f"(d[75]), "+f"(d[76]), "+f"(d[77]), "+f"(d[78]), "+f"(d[79]),
      "+f"(d[80]), "+f"(d[81]), "+f"(d[82]), "+f"(d[83]), "+f"(d[84]), "+f"(d[85]), "+f"(d[86]), "+f"(d[87]),
      "+f"(d[88]), "+f"(d[89]), "+f"(d[90]), "+f"(d[91]), "+f"(d[92]), "+f"(d[93]), "+f"(d[94]), "+f"(d[95])
    : "r"(a[0]), "r"(a[1]), "r"(a[2]), "r"(a[3]), "l"(db), "r"(sd));
}

__device__ __forceinline__ void wgmma_rs_n208(float* d, const uint32_t* a, uint64_t db, int sd) {
  asm volatile("{ .reg .pred p; setp.ne.b32 p, %109, 0;\n"
      "wgmma.mma_async.sync.aligned.m64n208k16.f32.bf16.bf16 {"
      "%0,%1,%2,%3,%4,%5,%6,%7,%8,%9,%10,%11,%12,%13,%14,%15,"
      "%16,%17,%18,%19,%20,%21,%22,%23,%24,%25,%26,%27,%28,%29,%30,%31,"
      "%32,%33,%34,%35,%36,%37,%38,%39,%40,%41,%42,%43,%44,%45,%46,%47,"
      "%48,%49,%50,%51,%52,%53,%54,%55,%56,%57,%58,%59,%60,%61,%62,%63,"
      "%64,%65,%66,%67,%68,%69,%70,%71,%72,%73,%74,%75,%76,%77,%78,%79,"
      "%80,%81,%82,%83,%84,%85,%86,%87,%88,%89,%90,%91,%92,%93,%94,%95,"
      "%96,%97,%98,%99,%100,%101,%102,%103"
      "}, {%104,%105,%106,%107}, %108, p, 1, 1, 0; }"
    : "+f"(d[0]), "+f"(d[1]), "+f"(d[2]), "+f"(d[3]), "+f"(d[4]), "+f"(d[5]), "+f"(d[6]), "+f"(d[7]),
      "+f"(d[8]), "+f"(d[9]), "+f"(d[10]), "+f"(d[11]), "+f"(d[12]), "+f"(d[13]), "+f"(d[14]), "+f"(d[15]),
      "+f"(d[16]), "+f"(d[17]), "+f"(d[18]), "+f"(d[19]), "+f"(d[20]), "+f"(d[21]), "+f"(d[22]), "+f"(d[23]),
      "+f"(d[24]), "+f"(d[25]), "+f"(d[26]), "+f"(d[27]), "+f"(d[28]), "+f"(d[29]), "+f"(d[30]), "+f"(d[31]),
      "+f"(d[32]), "+f"(d[33]), "+f"(d[34]), "+f"(d[35]), "+f"(d[36]), "+f"(d[37]), "+f"(d[38]), "+f"(d[39]),
      "+f"(d[40]), "+f"(d[41]), "+f"(d[42]), "+f"(d[43]), "+f"(d[44]), "+f"(d[45]), "+f"(d[46]), "+f"(d[47]),
      "+f"(d[48]), "+f"(d[49]), "+f"(d[50]), "+f"(d[51]), "+f"(d[52]), "+f"(d[53]), "+f"(d[54]), "+f"(d[55]),
      "+f"(d[56]), "+f"(d[57]), "+f"(d[58]), "+f"(d[59]), "+f"(d[60]), "+f"(d[61]), "+f"(d[62]), "+f"(d[63]),
      "+f"(d[64]), "+f"(d[65]), "+f"(d[66]), "+f"(d[67]), "+f"(d[68]), "+f"(d[69]), "+f"(d[70]), "+f"(d[71]),
      "+f"(d[72]), "+f"(d[73]), "+f"(d[74]), "+f"(d[75]), "+f"(d[76]), "+f"(d[77]), "+f"(d[78]), "+f"(d[79]),
      "+f"(d[80]), "+f"(d[81]), "+f"(d[82]), "+f"(d[83]), "+f"(d[84]), "+f"(d[85]), "+f"(d[86]), "+f"(d[87]),
      "+f"(d[88]), "+f"(d[89]), "+f"(d[90]), "+f"(d[91]), "+f"(d[92]), "+f"(d[93]), "+f"(d[94]), "+f"(d[95]),
      "+f"(d[96]), "+f"(d[97]), "+f"(d[98]), "+f"(d[99]), "+f"(d[100]), "+f"(d[101]), "+f"(d[102]), "+f"(d[103])
    : "r"(a[0]), "r"(a[1]), "r"(a[2]), "r"(a[3]), "l"(db), "r"(sd));
}

__device__ __forceinline__ void wgmma_rs_n224(float* d, const uint32_t* a, uint64_t db, int sd) {
  asm volatile("{ .reg .pred p; setp.ne.b32 p, %117, 0;\n"
      "wgmma.mma_async.sync.aligned.m64n224k16.f32.bf16.bf16 {"
      "%0,%1,%2,%3,%4,%5,%6,%7,%8,%9,%10,%11,%12,%13,%14,%15,"
      "%16,%17,%18,%19,%20,%21,%22,%23,%24,%25,%26,%27,%28,%29,%30,%31,"
      "%32,%33,%34,%35,%36,%37,%38,%39,%40,%41,%42,%43,%44,%45,%46,%47,"
      "%48,%49,%50,%51,%52,%53,%54,%55,%56,%57,%58,%59,%60,%61,%62,%63,"
      "%64,%65,%66,%67,%68,%69,%70,%71,%72,%73,%74,%75,%76,%77,%78,%79,"
      "%80,%81,%82,%83,%84,%85,%86,%87,%88,%89,%90,%91,%92,%93,%94,%95,"
      "%96,%97,%98,%99,%100,%101,%102,%103,%104,%105,%106,%107,%108,%109,%110,%111"
      "}, {%112,%113,%114,%115}, %116, p, 1, 1, 0; }"
    : "+f"(d[0]), "+f"(d[1]), "+f"(d[2]), "+f"(d[3]), "+f"(d[4]), "+f"(d[5]), "+f"(d[6]), "+f"(d[7]),
      "+f"(d[8]), "+f"(d[9]), "+f"(d[10]), "+f"(d[11]), "+f"(d[12]), "+f"(d[13]), "+f"(d[14]), "+f"(d[15]),
      "+f"(d[16]), "+f"(d[17]), "+f"(d[18]), "+f"(d[19]), "+f"(d[20]), "+f"(d[21]), "+f"(d[22]), "+f"(d[23]),
      "+f"(d[24]), "+f"(d[25]), "+f"(d[26]), "+f"(d[27]), "+f"(d[28]), "+f"(d[29]), "+f"(d[30]), "+f"(d[31]),
      "+f"(d[32]), "+f"(d[33]), "+f"(d[34]), "+f"(d[35]), "+f"(d[36]), "+f"(d[37]), "+f"(d[38]), "+f"(d[39]),
      "+f"(d[40]), "+f"(d[41]), "+f"(d[42]), "+f"(d[43]), "+f"(d[44]), "+f"(d[45]), "+f"(d[46]), "+f"(d[47]),
      "+f"(d[48]), "+f"(d[49]), "+f"(d[50]), "+f"(d[51]), "+f"(d[52]), "+f"(d[53]), "+f"(d[54]), "+f"(d[55]),
      "+f"(d[56]), "+f"(d[57]), "+f"(d[58]), "+f"(d[59]), "+f"(d[60]), "+f"(d[61]), "+f"(d[62]), "+f"(d[63]),
      "+f"(d[64]), "+f"(d[65]), "+f"(d[66]), "+f"(d[67]), "+f"(d[68]), "+f"(d[69]), "+f"(d[70]), "+f"(d[71]),
      "+f"(d[72]), "+f"(d[73]), "+f"(d[74]), "+f"(d[75]), "+f"(d[76]), "+f"(d[77]), "+f"(d[78]), "+f"(d[79]),
      "+f"(d[80]), "+f"(d[81]), "+f"(d[82]), "+f"(d[83]), "+f"(d[84]), "+f"(d[85]), "+f"(d[86]), "+f"(d[87]),
      "+f"(d[88]), "+f"(d[89]), "+f"(d[90]), "+f"(d[91]), "+f"(d[92]), "+f"(d[93]), "+f"(d[94]), "+f"(d[95]),
      "+f"(d[96]), "+f"(d[97]), "+f"(d[98]), "+f"(d[99]), "+f"(d[100]), "+f"(d[101]), "+f"(d[102]), "+f"(d[103]),
      "+f"(d[104]), "+f"(d[105]), "+f"(d[106]), "+f"(d[107]), "+f"(d[108]), "+f"(d[109]), "+f"(d[110]), "+f"(d[111])
    : "r"(a[0]), "r"(a[1]), "r"(a[2]), "r"(a[3]), "l"(db), "r"(sd));
}

__device__ __forceinline__ void wgmma_rs_n240(float* d, const uint32_t* a, uint64_t db, int sd) {
  asm volatile("{ .reg .pred p; setp.ne.b32 p, %125, 0;\n"
      "wgmma.mma_async.sync.aligned.m64n240k16.f32.bf16.bf16 {"
      "%0,%1,%2,%3,%4,%5,%6,%7,%8,%9,%10,%11,%12,%13,%14,%15,"
      "%16,%17,%18,%19,%20,%21,%22,%23,%24,%25,%26,%27,%28,%29,%30,%31,"
      "%32,%33,%34,%35,%36,%37,%38,%39,%40,%41,%42,%43,%44,%45,%46,%47,"
      "%48,%49,%50,%51,%52,%53,%54,%55,%56,%57,%58,%59,%60,%61,%62,%63,"
      "%64,%65,%66,%67,%68,%69,%70,%71,%72,%73,%74,%75,%76,%77,%78,%79,"
      "%80,%81,%82,%83,%84,%85,%86,%87,%88,%89,%90,%91,%92,%93,%94,%95,"
      "%96,%97,%98,%99,%100,%101,%102,%103,%104,%105,%106,%107,%108,%109,%110,%111,"
      "%112,%113,%114,%115,%116,%117,%118,%119"
      "}, {%120,%121,%122,%123}, %124, p, 1, 1, 0; }"
    : "+f"(d[0]), "+f"(d[1]), "+f"(d[2]), "+f"(d[3]), "+f"(d[4]), "+f"(d[5]), "+f"(d[6]), "+f"(d[7]),
      "+f"(d[8]), "+f"(d[9]), "+f"(d[10]), "+f"(d[11]), "+f"(d[12]), "+f"(d[13]), "+f"(d[14]), "+f"(d[15]),
      "+f"(d[16]), "+f"(d[17]), "+f"(d[18]), "+f"(d[19]), "+f"(d[20]), "+f"(d[21]), "+f"(d[22]), "+f"(d[23]),
      "+f"(d[24]), "+f"(d[25]), "+f"(d[26]), "+f"(d[27]), "+f"(d[28]), "+f"(d[29]), "+f"(d[30]), "+f"(d[31]),
      "+f"(d[32]), "+f"(d[33]), "+f"(d[34]), "+f"(d[35]), "+f"(d[36]), "+f"(d[37]), "+f"(d[38]), "+f"(d[39]),
      "+f"(d[40]), "+f"(d[41]), "+f"(d[42]), "+f"(d[43]), "+f"(d[44]), "+f"(d[45]), "+f"(d[46]), "+f"(d[47]),
      "+f"(d[48]), "+f"(d[49]), "+f"(d[50]), "+f"(d[51]), "+f"(d[52]), "+f"(d[53]), "+f"(d[54]), "+f"(d[55]),
      "+f"(d[56]), "+f"(d[57]), "+f"(d[58]), "+f"(d[59]), "+f"(d[60]), "+f"(d[61]), "+f"(d[62]), "+f"(d[63]),
      "+f"(d[64]), "+f"(d[65]), "+f"(d[66]), "+f"(d[67]), "+f"(d[68]), "+f"(d[69]), "+f"(d[70]), "+f"(d[71]),
      "+f"(d[72]), "+f"(d[73]), "+f"(d[74]), "+f"(d[75]), "+f"(d[76]), "+f"(d[77]), "+f"(d[78]), "+f"(d[79]),
      "+f"(d[80]), "+f"(d[81]), "+f"(d[82]), "+f"(d[83]), "+f"(d[84]), "+f"(d[85]), "+f"(d[86]), "+f"(d[87]),
      "+f"(d[88]), "+f"(d[89]), "+f"(d[90]), "+f"(d[91]), "+f"(d[92]), "+f"(d[93]), "+f"(d[94]), "+f"(d[95]),
      "+f"(d[96]), "+f"(d[97]), "+f"(d[98]), "+f"(d[99]), "+f"(d[100]), "+f"(d[101]), "+f"(d[102]), "+f"(d[103]),
      "+f"(d[104]), "+f"(d[105]), "+f"(d[106]), "+f"(d[107]), "+f"(d[108]), "+f"(d[109]), "+f"(d[110]), "+f"(d[111]),
      "+f"(d[112]), "+f"(d[113]), "+f"(d[114]), "+f"(d[115]), "+f"(d[116]), "+f"(d[117]), "+f"(d[118]), "+f"(d[119])
    : "r"(a[0]), "r"(a[1]), "r"(a[2]), "r"(a[3]), "l"(db), "r"(sd));
}

__device__ __forceinline__ void wgmma_rs_n256(float* d, const uint32_t* a, uint64_t db, int sd) {
  asm volatile("{ .reg .pred p; setp.ne.b32 p, %133, 0;\n"
      "wgmma.mma_async.sync.aligned.m64n256k16.f32.bf16.bf16 {"
      "%0,%1,%2,%3,%4,%5,%6,%7,%8,%9,%10,%11,%12,%13,%14,%15,"
      "%16,%17,%18,%19,%20,%21,%22,%23,%24,%25,%26,%27,%28,%29,%30,%31,"
      "%32,%33,%34,%35,%36,%37,%38,%39,%40,%41,%42,%43,%44,%45,%46,%47,"
      "%48,%49,%50,%51,%52,%53,%54,%55,%56,%57,%58,%59,%60,%61,%62,%63,"
      "%64,%65,%66,%67,%68,%69,%70,%71,%72,%73,%74,%75,%76,%77,%78,%79,"
      "%80,%81,%82,%83,%84,%85,%86,%87,%88,%89,%90,%91,%92,%93,%94,%95,"
      "%96,%97,%98,%99,%100,%101,%102,%103,%104,%105,%106,%107,%108,%109,%110,%111,"
      "%112,%113,%114,%115,%116,%117,%118,%119,%120,%121,%122,%123,%124,%125,%126,%127"
      "}, {%128,%129,%130,%131}, %132, p, 1, 1, 0; }"
    : "+f"(d[0]), "+f"(d[1]), "+f"(d[2]), "+f"(d[3]), "+f"(d[4]), "+f"(d[5]), "+f"(d[6]), "+f"(d[7]),
      "+f"(d[8]), "+f"(d[9]), "+f"(d[10]), "+f"(d[11]), "+f"(d[12]), "+f"(d[13]), "+f"(d[14]), "+f"(d[15]),
      "+f"(d[16]), "+f"(d[17]), "+f"(d[18]), "+f"(d[19]), "+f"(d[20]), "+f"(d[21]), "+f"(d[22]), "+f"(d[23]),
      "+f"(d[24]), "+f"(d[25]), "+f"(d[26]), "+f"(d[27]), "+f"(d[28]), "+f"(d[29]), "+f"(d[30]), "+f"(d[31]),
      "+f"(d[32]), "+f"(d[33]), "+f"(d[34]), "+f"(d[35]), "+f"(d[36]), "+f"(d[37]), "+f"(d[38]), "+f"(d[39]),
      "+f"(d[40]), "+f"(d[41]), "+f"(d[42]), "+f"(d[43]), "+f"(d[44]), "+f"(d[45]), "+f"(d[46]), "+f"(d[47]),
      "+f"(d[48]), "+f"(d[49]), "+f"(d[50]), "+f"(d[51]), "+f"(d[52]), "+f"(d[53]), "+f"(d[54]), "+f"(d[55]),
      "+f"(d[56]), "+f"(d[57]), "+f"(d[58]), "+f"(d[59]), "+f"(d[60]), "+f"(d[61]), "+f"(d[62]), "+f"(d[63]),
      "+f"(d[64]), "+f"(d[65]), "+f"(d[66]), "+f"(d[67]), "+f"(d[68]), "+f"(d[69]), "+f"(d[70]), "+f"(d[71]),
      "+f"(d[72]), "+f"(d[73]), "+f"(d[74]), "+f"(d[75]), "+f"(d[76]), "+f"(d[77]), "+f"(d[78]), "+f"(d[79]),
      "+f"(d[80]), "+f"(d[81]), "+f"(d[82]), "+f"(d[83]), "+f"(d[84]), "+f"(d[85]), "+f"(d[86]), "+f"(d[87]),
      "+f"(d[88]), "+f"(d[89]), "+f"(d[90]), "+f"(d[91]), "+f"(d[92]), "+f"(d[93]), "+f"(d[94]), "+f"(d[95]),
      "+f"(d[96]), "+f"(d[97]), "+f"(d[98]), "+f"(d[99]), "+f"(d[100]), "+f"(d[101]), "+f"(d[102]), "+f"(d[103]),
      "+f"(d[104]), "+f"(d[105]), "+f"(d[106]), "+f"(d[107]), "+f"(d[108]), "+f"(d[109]), "+f"(d[110]), "+f"(d[111]),
      "+f"(d[112]), "+f"(d[113]), "+f"(d[114]), "+f"(d[115]), "+f"(d[116]), "+f"(d[117]), "+f"(d[118]), "+f"(d[119]),
      "+f"(d[120]), "+f"(d[121]), "+f"(d[122]), "+f"(d[123]), "+f"(d[124]), "+f"(d[125]), "+f"(d[126]), "+f"(d[127])
    : "r"(a[0]), "r"(a[1]), "r"(a[2]), "r"(a[3]), "l"(db), "r"(sd));
}

__device__ __forceinline__ void ln_finish(float mean, float var, float& mb, float& rinv) {
  mb = round_bf16(mean);
  float sd;
  asm("sqrt.approx.ftz.f32 %0, %1;" : "=f"(sd) : "f"(round_bf16(round_bf16(var) + 1e-5f)));
  asm("rcp.approx.ftz.f32 %0, %1;" : "=f"(rinv) : "f"(round_bf16(sd)));
}
__device__ __forceinline__ uint32_t sum4(uint32_t a, uint32_t b, uint32_t c, uint32_t d) {
  return pack_bf16((bf_lo(a) + bf_lo(b)) + (bf_lo(c) + bf_lo(d)), (bf_hi(a) + bf_hi(b)) + (bf_hi(c) + bf_hi(d)));
}
struct Ring {
  uint32_t s, ph;
  __device__ __forceinline__ void next() { if (++s == NSTAGE) { s = 0; ph ^= 1; } }
};

__device__ __forceinline__ void conv_lda(uint32_t* a, int j, uint32_t base, bool on) {
  asm volatile("{ .reg .pred p; setp.ne.u32 p, %3, 0;\n @p ld.shared.u32 %0, [%2];\n @p ld.shared.u32 %1, [%2 + 128]; }"
               : "+r"(a[2 * j]), "+r"(a[2 * j + 1]) : "r"(base + (j >> 1) * 256 + (j & 1) * 16), "r"((uint32_t)on) : "memory");
}
__device__ __forceinline__ void conv_mma(float* acc, const uint32_t* a, uint64_t db) {
  wgmma_rs_n256(acc, a, db, 0);
  wgmma_rs_n240(acc, a + 4, db + 16, 1);
  wgmma_rs_n224(acc, a + 8, db + 32, 1);
  wgmma_rs_n208(acc, a + 12, db + 48, 1);
  wgmma_rs_n192(acc, a + 16, db + 64, 1);
  wgmma_rs_n176(acc, a + 20, db + 80, 1);
  wgmma_rs_n160(acc, a + 24, db + 96, 1);
  wgmma_rs_n144(acc, a + 28, db + 112, 1);
  wgmma_rs_n128(acc, a + 32, db + 128, 1);
  wgmma_rs_n112(acc, a + 36, db + 144, 1);
  wgmma_rs_n96(acc, a + 40, db + 160, 1);
  wgmma_rs_n80(acc, a + 44, db + 176, 1);
  wgmma_rs_n64(acc, a + 48, db + 192, 1);
  wgmma_rs_n48(acc, a + 52, db + 208, 1);
  wgmma_rs_n32(acc, a + 56, db + 224, 1);
  wgmma_rs_n16(acc, a + 60, db + 240, 1);
}
__device__ __forceinline__ uint32_t conv_part(const float* acc, int j) {
  const int q = 31 - j;
  return q == 31 ? pack_bf16(acc[124], acc[125]) : pack_bf16(acc[4 * q] + acc[(4 * q + 6) & 127], acc[4 * q + 1] + acc[(4 * q + 7) & 127]);
}
__device__ __forceinline__ uint4 conv_sum(const uint4* p) {
  return make_uint4(sum4(p[0].x, p[1].x, p[2].x, p[3].x), sum4(p[0].y, p[1].y, p[2].y, p[3].y), sum4(p[0].z, p[1].z, p[2].z, p[3].z),
                    sum4(p[0].w, p[1].w, p[2].w, p[3].w));
}
template <int NV> __device__ __forceinline__ void gelu_stage(float* acc, const float* hb, uint32_t sa, int passes) {
#pragma unroll
  for (int i = 0; i < NV; i++) acc[i] = fmaf(acc[i], 0.5f, hb[(i >> 1) & 1]);
#pragma unroll 1
  for (; passes > 0; passes--, sa += NV * 256) {
#pragma unroll
    for (int i = 0; i < NV; i += 8)
      stsm4t(sa + i * 256, pack_bf16(gelu_half(acc[i]), gelu_half(acc[i + 1])), pack_bf16(gelu_half(acc[i + 2]), gelu_half(acc[i + 3])),
             pack_bf16(gelu_half(acc[i + 4]), gelu_half(acc[i + 5])), pack_bf16(gelu_half(acc[i + 6]), gelu_half(acc[i + 7])));
#pragma unroll
    for (int i = 0; i < NV; i++) acc[i] = fmaf(acc[NV + i], 0.5f, hb[2 + ((i >> 1) & 1)]);
  }
}

__global__ void __cluster_dims__(2, 1, 1) __launch_bounds__(384, 1) fused_kernel(const __grid_constant__ Hot H, const __grid_constant__ Params P) {
  extern __shared__ __align__(1024) uint8_t smem_raw[];
  const uint32_t t0 = clk();
  const uint32_t sb = smem_u32(smem_raw);
  const int tid = threadIdx.x, lane = tid & 31;
  const int bid = blockIdx.x, rank = bid & 1;
  const Role& R = P.role[bid];
  Scratch* const S = H.S;
  uint32_t xr[18];
  const int row = bid * 16 + (tid >> 4);
  if (tid < 256 && bid < 128) {
    const char* src = reinterpret_cast<const char*>(H.x) + row * (D_ * 2) + (lane & 15) * 8;
#pragma unroll
    for (int j = 0; j < 9; j++) asm volatile("ld.global.nc.v2.u32 {%0,%1}, [%2];" : "=r"(xr[2 * j]), "=r"(xr[2 * j + 1]) : "l"(src + 128 * j));
  }
  const int warp = __shfl_sync(0xffffffffu, tid >> 5, 0);

  if (warp >= 8) {
    const bool one = elect_one();
    if (warp == 8 && one) {
#pragma unroll
      for (int b = B_FULL; b <= B_DONE; b += 8) mbar_init(sb + b, b < B_EMPTY ? 1 : b < B_CEMPTY ? 2 : b < B_G1DONE ? 4 : 8);
      asm volatile("fence.mbarrier_init.release.cluster;" ::: "memory");
    }
    __syncwarp();
    asm volatile("barrier.cluster.arrive.relaxed.aligned;" ::: "memory");
    asm volatile("setmaxnreg.dec.sync.aligned.u32 56;");
    asm volatile("barrier.cluster.wait.aligned;" ::: "memory");
    const bool left = R.at == 15;
    if (warp == 8) {
      const uint32_t ep = ldg32(S->cnt + C_EPOCH * 32);
      if (one) {
#pragma unroll 1
        for (int i = 0; i < 9; i++) asm volatile("prefetch.tensormap [%0];" :: "l"(&P.m_w1 + i) : "memory");
      }
      __syncwarp();
      if (bid < 128) bar_sync(2, 288);
      if (one) {
        TLREC(31);
        signal(S, C_H, EPOCH / 132);
        TLREC(1);
        const uint32_t boff = left ? 24576 : 16384;
        Ring r{0, 1};
#pragma unroll 1
        for (int kb = -NW0; kb < G1_KB; kb++) {
          const int kw = kb < 0 ? kb + NW0 : kb, s = kb < 0 ? kw : r.s;
          const uint32_t fb = sb + B_FULL + 8 * s;
          if (kb < 0 || kb >= NW0) {
            mbar_wait(sb + B_EMPTY + 8 * s, r.ph);
            mbar_expect_tx(fb, G1_BYTES);
            tma3d(sb + s * SLOT, &P.m_w1 + left, 0, kw * 64, R.fg, fb);
            if (kb < 0) continue;
          }
          if (kb == 0) { await(S, C_H, ep); fence_async_global(); TLREC(2); }
          bulk_load(sb + s * SLOT + boff, S->h + (kb * 18 + R.at) * 2048, G1_BYTES - boff, fb);
          if (kb == NSTAGE - 1) {
            mbar_arrive(sb + B_GO);
            mbar_expect_tx(sb + B_MISC, boff / 64 + 1152);
            bulk_load(sb + SM_B1, P.b1 + R.fg * 64, boff / 64, sb + B_MISC);
            bulk_load(sb + SM_D, P.ssm_D, 1152, sb + B_MISC);
          }
          r.next();
        }
        await(S, C_KV, ep);
        fence_async_global();
#pragma unroll 1
        for (int i = 0; i < R.ncv; i++) {
          if (i == 2) {
            if (R.sg >= 0) {
#pragma unroll 1
              for (int s = 2; s < NSTAGE; s++) {
                mbar_wait(sb + B_EMPTY + 8 * s, ((G1_KB / NSTAGE) - 1) & 1);
                mbar_expect_tx(sb + B_FULL + 8 * s, G2_BYTES);
                tma3d(sb + s * SLOT, &P.m_w2, 0, (rank * G2_KB + s - 2) * 64, R.sg, sb + B_FULL + 8 * s);
              }
            }
            mbar_wait(sb + B_G1DONE, 0);
          }
          const uint32_t slot = sb + cv_slot(i), b8 = sb + 8 * (i & 3);
          mbar_wait(b8 + B_CEMPTY, ((i >> 2) & 1) ^ 1);
          sts128(slot + CV_KOFF, 0, 0, 0, 0); sts128(slot + CV_KOFF + 16, 0, 0, 0, 0);
          mbar_expect_tx(b8 + B_KFULL, 4096);
          bulk_load(slot + CV_KOFF + 32, H.ssm_k + (R.ch + i) * S_, 4096, b8 + B_KFULL);
          mbar_expect_tx(b8 + B_UFULL, 8192);
          bulk_load(slot, S->ub + (R.ch + i) * 4096, 8192, b8 + B_UFULL);
        }
        if (R.sg >= 0) {
          mbar_expect_tx(sb + B_XY, 2 * 18432 + 2048 + 256);
          mbar_expect_tx(sb + B_XFULL, 9216);
          mbar_expect_tx(sb + B_XFULL + 8, 9216);
          await(S, C_U, ep);
          fence_async_global();
          TLREC(6);
#pragma unroll 1
          for (int kb = 0; kb < G2_KB; kb++, r.next()) {
            const int k0 = (rank * G2_KB + kb) * 64;
            const uint32_t fb = sb + B_FULL + 8 * r.s, slot = sb + r.s * SLOT;
            if (kb >= NSTAGE - 2) {
              mbar_wait(sb + B_EMPTY + 8 * r.s, r.ph);
              if (kb == NSTAGE) asm volatile("red.relaxed.gpu.global.add.u32 [%0], %1;" :: "l"(S->cnt + C_SYNC * 32), "r"(EPOCH / 128) : "memory");
              if (kb == SYNCKB) await(S, C_SYNC, ep);
              mbar_expect_tx(fb, G2_BYTES);
              tma3d(slot, &P.m_w2, 0, k0, R.sg, fb);
            }
            tma2d(slot + 16384, &P.m_uld, k0, R.ds * 8, fb);
            tma2d(slot + 16384 + 9216, &P.m_uld, k0, R.dk * 8, fb);
            const uint32_t nx = kb - 8;
            if (nx < 8) tma2d(sb + SM_CV + nx * 2304, &P.m_x, R.dk * 8, R.sg * 64 + nx * 16, sb + B_XY);
          }
          bulk_load(sb + SM_ST, S->stats + R.sg * 64, 2048, sb + B_XY);
          bulk_load(sb + SM_B2, P.b2 + R.sg * 64, 256, sb + B_XY);
          await(S, C_Y, ep);
          fence_async_global();
          TLREC(19);
          tma3d(sb + SM_DED, &P.m_y, 0, R.dk * 8, R.sg, sb + B_XY);
          if (bid == 0) signal(S, C_EPOCH, EPOCH);
        }
      }
    } else {
      if (bid < 128) {
        const int ht = tid - 288, hf = ht >= 48, pr = ht - 48 * hf;
        const int s0 = bid * 16 + hf * 8;
        const uint32_t keep = s0 ? 0xffffffffu : 0u;
        const int off = s0 * D_ + 2 * pr, back = s0 ? 5 * D_ : 0;
        const uint32_t st = sb + SM_DED + (1 - hf) * 1536 + pr * 32;
        mbar_wait_guarded(sb + B_GO, t0);
        if (PFK && warp > 9 && one) asm volatile("cp.async.bulk.prefetch.L2.global [%0], 18432;" :: "l"((warp == 10 ? H.k : H.v) + bid * 16 * D_) : "memory");
        uint32_t kk[12], vi[9], vv[9];
        uint4 w;
#pragma unroll 1
        for (int r = -1; r < KV_ROUNDS; r++) {
          if (r >= 0) {
            const uint32_t w0 = __byte_perm(w.x, w.z, 0x5410), w1 = __byte_perm(w.x, w.z, 0x7632);
            const uint32_t w2 = __byte_perm(w.y, w.w, 0x5410), w3 = __byte_perm(w.y, w.w, 0x7632);
#pragma unroll
            for (int j = 1; j < 4; j++) kk[j] &= keep;
#pragma unroll
            for (int j = 0; j < 9; j++)
              vv[j] = bmul2(badd2(badd2(badd2(bmul2(kk[j], w3), bmul2(kk[j + 1], w2)), bmul2(kk[j + 2], w1)), bmul2(kk[j + 3], w0)), vi[j]);
            vv[0] &= keep;
          }
          if (r + 1 < KV_ROUNDS) {
            const __nv_bfloat16 *kp = H.k + off + (r + 1) * 96, *vp = H.v + off + (r + 1) * 96;
#pragma unroll
            for (int j = 0; j < 12; j++) kk[j] = ldg32(j < 4 ? kp - back + (j + 1) * D_ : kp + (j - 4) * D_);
#pragma unroll
            for (int j = 0; j < 9; j++) vi[j] = ldg32(j < 1 ? vp - back + 4 * D_ : vp + (j - 1) * D_);
            w = __ldg(reinterpret_cast<const uint4*>(H.shift_k) + pr + (r + 1) * 48);
            if (r < 0) continue;
          }
          const uint32_t buf = (r % 3) * 6144;
#pragma unroll
          for (int c = 0; c < 2; c++)
#pragma unroll
            for (int pi = 0; pi < 2; pi++) {
              const uint32_t sel = c ? 0x7632 : 0x5410;
              sts128(st + buf + c * 3072 + pi * 16, __byte_perm(vv[7 + pi], vv[6 + pi], sel), __byte_perm(vv[5 + pi], vv[4 + pi], sel),
                     __byte_perm(vv[3 + pi], vv[2 + pi], sel), __byte_perm(vv[1 + pi], vv[pi], sel));
            }
          bar_sync(1, 96);
          if (warp == 9 && one) {
            bulk_wait_all();
            fence_async_smem();
            tma3d_store(&P.m_ub, sb + SM_DED + buf, 16 * (127 - bid), r * 48, 0);
            bulk_commit();
          }
          __syncwarp();
        }
      }
      if (one) {
        if (warp < 11) {
          const int wg = warp - 9;
          if (!wg) {
            bulk_wait_all();
            mbar_arrive(sb + B_KVDONE);
            signal(S, C_KV, EPOCH / 132);
            TLREC(27);
          }
          mbar_wait_guarded(sb + B_STG + 8 * wg, t0);
          fence_async_smem();
          TLREC(13 + wg);
#pragma unroll 1
          for (int j = 0; j < (left ? 3 + 3 * wg : 5); j++) {
            const int hi = left && j >= 3;
            tma2d_store(&P.m_ust, sb + (wg ? SM_ST1 : SM_DED) + j * 4096, (R.fg + wg + hi) * 64, (R.at + j - 3 * hi) * 32);
          }
          bulk_commit();
          bulk_wait_all();
          mbar_arrive(sb + B_SFREE + 8 * wg);
          signal(S, C_U, EPOCH / 264);
          TLREC(15 + wg);
        } else {
          mbar_wait_guarded(sb + B_YDONE, t0);
          signal(S, C_Y, EPOCH / 132);
          if (R.sg >= 0) mbar_wait_guarded(sb + B_DONE, t0);
        }
      }
    }
    TLEND();
  } else {
    asm volatile("barrier.cluster.arrive.relaxed.aligned;" ::: "memory");
    if (bid < 128) {
      float c[36], s[4];
#pragma unroll
      for (int i = 0; i < 18; i++) { c[2 * i] = bf_lo(xr[i]); c[2 * i + 1] = bf_hi(xr[i]); }
#pragma unroll
      for (int i = 0; i < 36; i++) s[i & 3] = i < 4 ? c[i] : s[i & 3] + c[i];
      const float ml = ((s[0] + s[1]) + (s[2] + s[3])) * (1.0f / 36.0f);
#pragma unroll
      for (int i = 0; i < 36; i++) { c[i] -= ml; s[i & 3] = i < 4 ? c[i] * c[i] : fmaf(c[i], c[i], s[i & 3]); }
      float m = ml, q = (s[0] + s[1]) + (s[2] + s[3]), n2 = 18.f;
#pragma unroll
      for (int o = 1; o < 16; o <<= 1) {
        const float mo = __shfl_xor_sync(0xffffffffu, m, o), qo = __shfl_xor_sync(0xffffffffu, q, o);
        const float dl = m - mo;
        q = fmaf(dl * dl, n2, q + qo);
        m = fmaf(dl, -0.5f, m);
        n2 *= 2.f;
      }
      const float var = q * (1.0f / 576.0f);
      float mb, rinv, mb2, rinv2;
      ln_finish(m, var, mb, rinv);
      ln_finish((m - mb) * rinv, var * rinv * rinv, mb2, rinv2);
      const float ca = rinv * rinv2, cb = fmaf(ml - mb, rinv, -mb2) * rinv2;
      uint2* dst = reinterpret_cast<uint2*>(S->h) + ((row >> 6) * 18 + ((lane >> 3) & 1)) * 512 + (row & 63) * 8 + ((lane & 7) ^ (row & 6));
#pragma unroll
      for (int j = 0; j < 9; j++)
        dst[1024 * j] = make_uint2(pack_bf16(fmaf(c[4 * j], ca, cb), fmaf(c[4 * j + 1], ca, cb)), pack_bf16(fmaf(c[4 * j + 2], ca, cb), fmaf(c[4 * j + 3], ca, cb)));
      const uint32_t rh = pack_bf16(rinv, rinv);
      if (!(lane & 15)) S->stats[row] = make_uint4(pack_bf16(mb, mb), rh, pack_bf16(rinv - bf_lo(rh), rinv - bf_lo(rh)), 0);
      __syncwarp();
      bar_arrive(2, 288);
    }
    asm volatile("setmaxnreg.inc.sync.aligned.u32 224;");
    asm volatile("barrier.cluster.wait.aligned;" ::: "memory");
    const int wg = warp >> 2, w = warp & 3, g = lane >> 2, t = lane & 3, wtid = tid & 127;
    const bool elect = wtid == 0;
    const uint64_t da0 = make_desc(sb + wg * 8192, 8192, 1024, 1);
    const uint32_t swz = ((lane >> 4) * 8 + (lane & 7)) * 128 + (((2 * w + ((lane >> 3) & 1)) ^ (lane & 7)) << 4);
    const uint32_t stg = sb + (wg ? SM_ST1 : SM_DED);
    {
      auto mainloop = [&](auto&& mma) {
        Ring r{0, 0};
        uint32_t rel = 0;
#pragma unroll 1
        for (int kb = 0; kb < G1_KB; kb++, r.next()) {
          if (kb == G1_KB - G1_TAIL && wg) {
            wg_wait<0>();
            if (elect) mbar_arrive(rel);
            rel = 0;
            bar_sync(5, 256);
          }
          mbar_wait(sb + B_FULL + 8 * r.s, r.ph);
          if (kb == 0 && warp == 0) TLREC(3);
          wg_fence();
          mma(r.s * (SLOT >> 4), kb);
          wg_commit();
          if (kb == G1_KB - 1) break;
          wg_wait<1>();
          if (elect && rel) mbar_arrive(rel);
          rel = sb + B_EMPTY + 8 * r.s;
        }
        bar_arrive(5, 256);
        wg_wait<0>();
      };
      float hb[4];
      auto staged = [&](int second) {
        if (!w) TLREC(4 + wg);
        if (lane == 0) mbar_arrive(sb + B_G1DONE);
        mbar_wait(sb + B_MISC, 0);
#pragma unroll
        for (int i = 0; i < 4; i++) hb[i] = 0.5f * bf_lo(lds16(sb + SM_B1 + (warp * 16 + g + (i & 1) * 8 + (i >> 1) * second) * 2));
        mbar_wait(sb + (wg ? B_G1DONE : B_KVDONE), 0);
      };
      if (R.at != 15) {
        const uint64_t db0 = make_desc(sb + 16384, 4096, 512, 2);
        float acc[80];
        mainloop([&](uint32_t o, int kb) {
          wgmma_ss_n160_t11(acc, da0 + o, db0 + o, kb);
#pragma unroll
          for (int k = 1; k < 4; k++) wgmma_ss_n160_t11(acc, da0 + o + k * 128, db0 + o + k * 64, 1);
        });
        pin_regs<80>(acc);
        staged(0);
        gelu_stage<40>(acc, hb, stg + swz, 2);
      } else {
        const uint64_t db0 = make_desc(sb + 24576, 4096, 512, 2);
        float acc[96];
        auto block = [&](float* d, uint64_t da, uint64_t db, int kb) {
          wgmma_ss_n96_t11(d, da, db, kb);
#pragma unroll
          for (int k = 1; k < 4; k++) wgmma_ss_n96_t11(d, da + k * 128, db + k * 64, 1);
        };
        if (wg) mainloop([&](uint32_t o, int kb) { block(acc, da0 + o, db0 + o, kb); block(acc + 48, da0 + o + 512, db0 + o, kb); });
        else mainloop([&](uint32_t o, int kb) { block(acc, da0 + o, db0 + o, kb); });
        pin_regs<96>(acc);
        staged(64);
        gelu_stage<48>(acc, hb, stg + swz, 1 + wg);
      }
      __syncwarp();
      if (lane == 0) mbar_arrive(sb + B_STG + 8 * wg);
    }
    {
      const uint32_t ka0 = CV_KOFF + (8 * w + g + t + 1) * 4, wr = stg + w * CV_REDW + (8 * (3 - t + w) + g) * 4;
      uint32_t a[64];
      mbar_wait(sb + B_KFULL + 8 * wg, 0);
#pragma unroll
      for (int j = 0; j < 32; j++) conv_lda(a, j, sb + SM_CV + wg * CV_SLOT + ka0, true);
#pragma unroll 1
      for (int i = wg; i < R.ncv; i += 2) {
        const bool more = i + 2 < R.ncv;
        const uint32_t dd = lds16(sb + SM_D + (R.ch + i) * 2);
        a[0] = badd2(a[0], ka0 == CV_KOFF + 32 ? dd : 0); a[2] = badd2(a[2], ka0 == CV_KOFF + 16 ? dd : 0);
        float acc[128];
        mbar_wait(sb + B_UFULL + 8 * (i & 3), (i >> 2) & 1);
        bar_sync(5 + wg, 256);
        if (!w && i < 4) TLREC(22 + i);
        wg_fence();
        conv_mma(acc, a, make_desc(sb + cv_slot(i), 4096, 128, 0));
        wg_commit();
        if (i + 1 < R.ncv) bar_arrive(5 + (wg ^ 1), 256);
        mbar_wait(sb + B_SFREE + 8 * wg, 0);
        if (lane < 8 * w) sts32(stg + w * CV_REDW + lane * 4, 0);
        if (more) mbar_wait(sb + B_KFULL + 8 * ((i + 2) & 3), ((i + 2) >> 2) & 1);
        if (i == 0 && !w) TLREC(7);
        wg_wait<0>();
        pin_regs<128>(acc);
        if (lane == 0) mbar_arrive(sb + B_CEMPTY + 8 * (i & 3));
        const uint32_t ka = sb + cv_slot(i + 2) + ka0;
#pragma unroll
        for (int j = 0; j < 32; j++) {
          if (j < 24) conv_lda(a, j, ka, more);
          sts32(wr + j * 128, conv_part(acc, j));
        }
        bar_sync(3 + wg, 128);
        uint4 p[2][4];
#pragma unroll
        for (int x = 0; x < 8; x++) p[x >> 2][x & 3] = lds128(stg + (x & 3) * CV_REDW + (wtid + 128 * (x >> 2)) * 16);
#pragma unroll
        for (int j = 24; j < 32; j++) conv_lda(a, j, ka, more);
        uint4* yo = reinterpret_cast<uint4*>(S->y + (R.ch + i) * S_) + wtid;
        yo[0] = conv_sum(p[0]); yo[128] = conv_sum(p[1]);
      }
      fence_async_smem();
      bar_sync(3 + wg, 128);
      if (elect) { mbar_arrive(sb + B_EMPTY); mbar_arrive(sb + B_EMPTY + 8); }
      if (lane == 0) mbar_arrive(sb + B_YDONE);
      if (!w) TLREC(20 + wg);
    }
    if (R.sg >= 0) {
      const int srow = R.sg * 64 + warp * 16;
      const uint64_t db0 = make_desc(sb + 16384, 16, 1024, 1);
      const uint32_t xo = sb + SM_CV + warp * 2304, xa = xo + (lane & 15) * 144;
      float acc[72];
      Ring r{G1_KB % NSTAGE, (G1_KB / NSTAGE) & 1};
      uint32_t rel = 0;
#pragma unroll 1
      for (int kb = 0; kb < G2_KB; kb++, r.next()) {
        if (kb == G2_KB - G2_TAIL && wg) {
          wg_wait<0>();
          if (elect) mbar_arrive_remote(rel);
          rel = 0;
          bar_sync(7, 256);
        }
        mbar_wait(sb + B_FULL + 8 * r.s, r.ph);
        if (kb == 0 && !w) TLREC(17 + wg);
        if (kb == 8 && warp == 0) TLREC(26);
        if (kb == 20 && warp == 0) TLREC(8);
        if (kb == 27 && warp == 0) TLREC(30);
        const uint64_t da = da0 + r.s * (SLOT >> 4), db = db0 + r.s * (SLOT >> 4);
        wg_fence();
        wgmma_ss_n144_t10(acc, da, db, kb);
#pragma unroll
        for (int k = 1; k < 4; k++) wgmma_ss_n144_t10(acc, da + k * 128, db + k * 2, 1);
        wg_commit();
        if (kb == G2_KB - 1) break;
        wg_wait<1>();
        if (elect && rel) mbar_arrive_remote(rel);
        rel = kb == G2_KB - NSTAGE ? mapa(sb + B_XRDY, rank ^ 1) : sb + B_EMPTY + 8 * r.s;
      }
      if (!wg) bar_arrive(7, 256);
      const uint32_t xz = sb + XSLOT * SLOT + wg * 10240 + wtid * 16;
      const uint32_t rz = mapa(xz, rank ^ 1), rb = mapa(sb + B_XFULL + 8 * wg, rank ^ 1);
      mbar_wait(sb + B_XRDY, 0);
      wg_wait<0>();
      pin_regs<72>(acc);
      if (!w) TLREC(28 + wg);
#pragma unroll
      for (int i = 0; i < 32; i += 8)
        asm volatile("st.async.weak.shared::cluster.mbarrier::complete_tx::bytes.v4.b32 [%0], {%1,%2,%3,%4}, [%5];"
                     :: "r"(rz + i * 256), "r"(pack_bf16(acc[i], acc[i + 1])), "r"(pack_bf16(acc[i + 2], acc[i + 3])),
                        "r"(pack_bf16(acc[i + 4], acc[i + 5])), "r"(pack_bf16(acc[i + 6], acc[i + 7])), "r"(rb) : "memory");
      asm volatile("st.async.weak.shared::cluster.mbarrier::complete_tx::bytes.v2.b32 [%0], {%1,%2}, [%3];"
                   :: "r"(rz + 8192), "r"(pack_bf16(acc[32], acc[33])), "r"(pack_bf16(acc[34], acc[35])), "r"(rb) : "memory");
      uint32_t xx[18], ss[18];
      mbar_wait(sb + B_XY, 0);
      {
        const uint32_t ya = sb + SM_DED + wg * 9216 + swz;
        const uint4 st0 = lds128(sb + SM_ST + (warp * 16 + g) * 16), st1 = lds128(sb + SM_ST + (warp * 16 + g + 8) * 16);
        const float hb0 = 0.5f * bf_lo(lds16(sb + SM_B2 + (warp * 16 + g) * 2)), hb1 = 0.5f * bf_lo(lds16(sb + SM_B2 + (warp * 16 + g + 8) * 2));
#pragma unroll
        for (int q = 0; q < 8; q += 2) { ldsm4(xx + 2 * q, xa + (lane >> 4) * 16 + q * 16); ldsm4t(ss + 2 * q, ya + q * 1024); }
        ldsm2(xx + 16, xa + 128);
        ldsm2t(ss + 16, ya + 8 * 1024);
#pragma unroll
        for (int i = 0; i < 18; i++) {
          const uint4& st = (i & 1) ? st1 : st0;
          const uint32_t c = bsub2(xx[i], st.x);
          ss[i] = bmul2(bfma2(c, st.y, bmul2(c, st.z)), ss[i]);
        }
#pragma unroll
        for (int i = 36; i < 72; i++) acc[i] = fmaf(acc[i], 0.5f, (i & 2) ? hb1 : hb0);
      }
      mbar_wait_cluster(sb + B_XFULL + 8 * wg, 0);
      if (!w) TLREC(9 + wg);
#pragma unroll
      for (int q = 0; q < 5; q++) {
        const uint4 v = lds128(xz + q * 2048);
        const uint32_t pv[4] = {v.x, v.y, v.z, v.w};
#pragma unroll
        for (int i = 4 * q; i < 4 * q + 4 && i < 18; i++)
          xx[i] = bfma2(ss[i], pack_bf16(silu_half(fmaf(bf_lo(pv[i & 3]), 0.5f, acc[36 + 2 * i])), silu_half(fmaf(bf_hi(pv[i & 3]), 0.5f, acc[37 + 2 * i]))), xx[i]);
        if (q < 4) stsm4(xa + (lane >> 4) * 16 + q * 32, xx[4 * q], xx[4 * q + 1], xx[4 * q + 2], xx[4 * q + 3]);
        else stsm2(xa + 128, xx[16], xx[17]);
      }
      __syncwarp();
      if (elect_one()) {
        fence_async_smem();
        tma2d_store(&P.m_out, xo, R.dk * 8, srow);
        bulk_commit();
        mbar_arrive(sb + B_DONE);
        bulk_wait_read();
      }
      if (!w) TLREC(11 + wg);
    }
    TLEND();
  }
}

typedef CUresult (*EncodeFn)(CUtensorMap*, CUtensorMapDataType, cuuint32_t, void*, const cuuint64_t*, const cuuint64_t*, const cuuint32_t*,
                             const cuuint32_t*, CUtensorMapInterleave, CUtensorMapSwizzle, CUtensorMapL2promotion, CUtensorMapFloatOOBfill);

void make_map(EncodeFn fn, CUtensorMap* m, const void* ptr, int rank, const cuuint64_t* dims, const cuuint64_t* strides, const cuuint32_t* box,
              CUtensorMapSwizzle sw) {
  const cuuint32_t es[3] = {1, 1, 1};
  fn(m, CU_TENSOR_MAP_DATA_TYPE_BFLOAT16, rank, const_cast<void*>(ptr), dims, strides, box, es, CU_TENSOR_MAP_INTERLEAVE_NONE, sw,
     CU_TENSOR_MAP_L2_PROMOTION_L2_256B, CU_TENSOR_MAP_FLOAT_OOB_FILL_NONE);
}

void make_roles(Role* R) {
  int nl = 0, ch = 0;
  for (int gi = 0; gi < 8; gi++)
    for (int b = 0; b < 132; b++) {
      const int c = b >> 1, rank = b & 1;
      int g, idx;
      if (c < 4) { g = 0; idx = 4 + c; }
      else if (c < 36) { g = (c - 4) & 7; idx = (c - 4) >> 3; }
      else if (c < 64) { g = 1 + (c - 36) % 7; idx = 4 + (c - 36) / 7; }
      else { g = c - 58; idx = 8; }
      if (g != gi) continue;
      Role& r = R[b];
      r.sg = (int8_t)(idx < 8 ? 2 * (2 * g + (idx >> 2)) : -1);
      r.dk = (int8_t)((idx & 3) * 18 + rank * 9);
      r.ds = (int8_t)((idx & 3) * 18 + (rank ^ 1) * 9);
      if (idx < (g < 2 ? 6 : 7)) {
        const int c1 = (g < 2 ? 6 * g : 7 * g - 2) + idx;
        r.fg = (int8_t)((2 * (c1 / 3) + rank) * 2); r.at = (int8_t)(c1 % 3 * 5); r.ncv = NCV_REG;
      } else {
        r.fg = (int8_t)(3 * nl++); r.at = 15; r.ncv = idx < 8 ? NCV_LEFT : NCV_LONG;
      }
      r.ch = (int16_t)ch;
      ch += r.ncv;
    }
}

}

extern "C" void kernel_launch(void* const* d_in, const int* in_sizes, int n_in, void* d_out, int out_size) {
  static Params P;
  static Hot H;
  static const void* cached[4] = {nullptr, nullptr, nullptr, nullptr};
  if (cached[0] != d_in[7] || cached[1] != d_in[9] || cached[2] != d_out || cached[3] != d_in[0]) {
    void* fp = nullptr;
    cudaDriverEntryPointQueryResult qr;
    cudaGetDriverEntryPoint("cuTensorMapEncodeTiled", &fp, cudaEnableDefault, &qr);
    EncodeFn fn = (EncodeFn)fp;
    void* ps;
    cudaGetSymbolAddress(&ps, g_scratch);
    H.S = (Scratch*)ps;
    const void *pu = (char*)ps + offsetof(Scratch, u), *py = (char*)ps + offsetof(Scratch, y),
               *pb = (char*)ps + offsetof(Scratch, ub);
    { cuuint64_t d[3] = {64, S_, F_ / 64}, s[2] = {F_ * 2, 128}; cuuint32_t b[3] = {64, 64, 2}; make_map(fn, &P.m_w1, d_in[7], 3, d, s, b, CU_TENSOR_MAP_SWIZZLE_128B);
      b[2] = 3; make_map(fn, &P.m_w1l, d_in[7], 3, d, s, b, CU_TENSOR_MAP_SWIZZLE_128B); }
    { cuuint64_t d[2] = {F_, D_}, s[1] = {F_ * 2}; cuuint32_t b[2] = {64, 32}; make_map(fn, &P.m_ust, pu, 2, d, s, b, CU_TENSOR_MAP_SWIZZLE_128B); }
    { cuuint64_t d[3] = {64, F_, S_ / 64}, s[2] = {S_ * 2, 128}; cuuint32_t b[3] = {64, 64, 2}; make_map(fn, &P.m_w2, d_in[9], 3, d, s, b, CU_TENSOR_MAP_SWIZZLE_128B); }
    { cuuint64_t d[2] = {F_, D_}, s[1] = {F_ * 2}; cuuint32_t b[2] = {64, 72}; make_map(fn, &P.m_uld, pu, 2, d, s, b, CU_TENSOR_MAP_SWIZZLE_128B); }
    { cuuint64_t d[2] = {D_, S_}, s[1] = {D_ * 2}; cuuint32_t b[2] = {72, 16}; make_map(fn, &P.m_out, d_out, 2, d, s, b, CU_TENSOR_MAP_SWIZZLE_NONE);
      make_map(fn, &P.m_x, d_in[0], 2, d, s, b, CU_TENSOR_MAP_SWIZZLE_NONE); }
    { cuuint64_t d[3] = {64, D_, S_ / 64}, s[2] = {S_ * 2, 128}; cuuint32_t b[3] = {64, 72, 2}; make_map(fn, &P.m_y, py, 3, d, s, b, CU_TENSOR_MAP_SWIZZLE_128B); }
    { cuuint64_t d[3] = {2048, D_ / 2, 4}, s[2] = {16384, 4096}; cuuint32_t b[3] = {16, 48, 4}; make_map(fn, &P.m_ub, pb, 3, d, s, b, CU_TENSOR_MAP_SWIZZLE_NONE); }
    make_roles(P.role);
    cudaFuncSetAttribute(fused_kernel, cudaFuncAttributeMaxDynamicSharedMemorySize, SM_TOTAL);
    cached[0] = d_in[7]; cached[1] = d_in[9]; cached[2] = d_out; cached[3] = d_in[0];
  }
  H.x = (const __nv_bfloat16*)d_in[0]; H.k = (const __nv_bfloat16*)d_in[1]; H.v = (const __nv_bfloat16*)d_in[2];
  H.shift_k = (const __nv_bfloat16*)d_in[3]; H.ssm_k = (const __nv_bfloat16*)d_in[4]; P.ssm_D = (const __nv_bfloat16*)d_in[5];
  P.b1 = (const __nv_bfloat16*)d_in[8]; P.b2 = (const __nv_bfloat16*)d_in[10];
  fused_kernel<<<132, 384, SM_TOTAL>>>(H, P);
}
```

```cpp
#include <cuda_runtime.h>
#include <cuda.h>
#include <cuda_bf16.h>
#include <stddef.h>
#include <stdint.h>

namespace {

constexpr int S_ = 2048, D_ = 576, F_ = 4608;
constexpr int NSTAGE = 5, SLOT = 36864;
constexpr int G1_KB = 32, G2_KB = 36;
constexpr int G1_BYTES = 36864, G2_BYTES = 16384 + 18432;
#define NCV_LEFT 4
constexpr int NCV_REG = 4, NCV_LONG = (D_ - 108 * NCV_REG - 20 * NCV_LEFT) / 4;
static_assert(108 * NCV_REG + 20 * NCV_LEFT + 4 * NCV_LONG == D_, "conv split");
constexpr int KV_ROUNDS = 6;
constexpr int NW0 = 1;
constexpr int G1_TAIL = 4, G2_TAIL = 3;
constexpr int SYNCKB = 5;
constexpr int KVD = 500;

constexpr int CV_KOFF = 8192, CV_SLOT = 8192 + 4224, CV_REDW = 2112 * 2;
constexpr int SM_DED = NSTAGE * SLOT;
constexpr int SM_CV = SM_DED + 20480;
constexpr int SM_ST1 = SLOT;
constexpr int SM_ST = SM_CV + 18432, SM_B2 = SM_ST + 2048;
constexpr int SM_B1 = SM_CV + 2 * CV_SLOT, SM_D = SM_B1 + 384;
constexpr int SM_BAR = SM_D + 1152;
constexpr int SM_TOTAL = SM_BAR + 768;
static_assert(G1_KB % NSTAGE == 2, "slots 0 and 1 hold the last two GEMM1 k-blocks");
constexpr int XSLOT = (G1_KB + G2_KB) % NSTAGE;
__device__ __forceinline__ uint32_t cv_slot(int i) { return (i & 2 ? 0 : SM_CV) + (i & 1) * CV_SLOT; }
constexpr int bar_at(int i) { return SM_BAR + 8 * i; }
constexpr int B_FULL = bar_at(0)  , B_KFULL = bar_at(5)  , B_UFULL = bar_at(9)  , B_KVDONE = bar_at(13), B_SFREE = bar_at(14)  ,
              B_XFULL = bar_at(16)  , B_XY = bar_at(18), B_MISC = bar_at(19), B_GO = bar_at(20),
              B_EMPTY = bar_at(21)  , B_XRDY = bar_at(26),
              B_CEMPTY = bar_at(27)  , B_STG = bar_at(31)  ,
              B_G1DONE = bar_at(33), B_YDONE = bar_at(34), B_DONE = bar_at(35);
constexpr int C_H = 0, C_KV = 1, C_U = 2, C_Y = 3, C_SYNC = 4, C_EPOCH = 5, C_COUNT = 6;
constexpr uint32_t EPOCH = 128 * 33;

struct Scratch {
  uint32_t cnt[C_COUNT * 32];
  alignas(1024) uint4 stats[S_];
  alignas(1024) __nv_bfloat16 h[S_ * D_];
  alignas(1024) __nv_bfloat16 ub[D_ * 4096];
  alignas(1024) __nv_bfloat16 y[D_ * S_];
  alignas(1024) __nv_bfloat16 u[D_ * F_];
};
__device__ Scratch g_scratch;

struct Hot {
  const __nv_bfloat16 *x, *shift_k, *ssm_k, *ssm_D, *b1;
  Scratch* S;
};
struct Role {
  int8_t fg;
  int8_t at;
  int8_t sg;
  int8_t dk, ds;
  int8_t ncv;
  int16_t ch;
};
struct Params {
  const __nv_bfloat16* b2;
  Role role[132];
  CUtensorMap m_w1, m_w1l, m_ust, m_w2, m_uld, m_out, m_x, m_y, m_ub, m_k, m_v;
};

#define TLREC(i) do { } while (0)
#define TLEND() do { } while (0)

__device__ __forceinline__ uint32_t smem_u32(const void* p) { return (uint32_t)__cvta_generic_to_shared(p); }
__device__ __forceinline__ void mbar_init(uint32_t bar, uint32_t cnt) { asm volatile("mbarrier.init.shared::cta.b64 [%0], %1;" :: "r"(bar), "r"(cnt) : "memory"); }
__device__ __forceinline__ void mbar_expect_tx(uint32_t bar, uint32_t bytes) { asm volatile("mbarrier.arrive.expect_tx.shared::cta.b64 _, [%0], %1;" :: "r"(bar), "r"(bytes) : "memory"); }
__device__ __forceinline__ void mbar_arrive(uint32_t bar) { asm volatile("mbarrier.arrive.shared::cta.b64 _, [%0];" :: "r"(bar) : "memory"); }
__device__ __forceinline__ uint32_t mapa(uint32_t addr, uint32_t cta) { uint32_t r; asm volatile("mapa.shared::cluster.u32 %0, %1, %2;" : "=r"(r) : "r"(addr), "r"(cta)); return r; }
__device__ __forceinline__ void mbar_arrive_remote(uint32_t rbar) { asm volatile("mbarrier.arrive.shared::cluster.b64 _, [%0];" :: "r"(rbar) : "memory"); }
__device__ __forceinline__ uint32_t clk() { uint32_t c; asm volatile("mov.u32 %0, %%clock;" : "=r"(c)); return c; }
__device__ __forceinline__ bool elect_one() {
  uint32_t p; asm volatile("{ .reg .pred p; elect.sync _|p, 0xffffffff; selp.u32 %0, 1, 0, p; }" : "=r"(p)); return p;
}
__device__ __forceinline__ void guard(uint32_t t0) { if ((int32_t)(clk() - t0) < 0) __trap(); }
__device__ __forceinline__ void mbar_wait(uint32_t bar, uint32_t parity) {
  asm volatile("{\n .reg .pred p;\n W_%=:\n mbarrier.try_wait.parity.shared::cta.b64 p, [%0], %1;\n @!p bra W_%=;\n }" :: "r"(bar), "r"(parity) : "memory");
}
__device__ __forceinline__ void mbar_wait_cluster(uint32_t bar, uint32_t parity) {
  asm volatile("{\n .reg .pred p;\n W_%=:\n mbarrier.try_wait.parity.acquire.cluster.shared::cta.b64 p, [%0], %1;\n @!p bra W_%=;\n }" :: "r"(bar), "r"(parity) : "memory");
}
__device__ __forceinline__ bool mbar_try(uint32_t bar, uint32_t parity) {
  uint32_t ok;
  asm volatile("{ .reg .pred p; mbarrier.try_wait.parity.shared::cta.b64 p, [%1], %2; selp.u32 %0, 1, 0, p; }" : "=r"(ok) : "r"(bar), "r"(parity) : "memory");
  return ok;
}
__device__ __forceinline__ void mbar_wait_guarded(uint32_t bar, uint32_t t0, uint32_t parity = 0) { while (!mbar_try(bar, parity)) guard(t0); }
__device__ __forceinline__ void tma2d(uint32_t dst, const CUtensorMap* m, int c0, int c1, uint32_t bar) {
  asm volatile("cp.async.bulk.tensor.2d.shared::cluster.global.mbarrier::complete_tx::bytes [%0], [%1, {%3, %4}], [%2];"
               :: "r"(dst), "l"(m), "r"(bar), "r"(c0), "r"(c1) : "memory");
}
__device__ __forceinline__ void tma3d(uint32_t dst, const CUtensorMap* m, int c0, int c1, int c2, uint32_t bar) {
  asm volatile("cp.async.bulk.tensor.3d.shared::cluster.global.mbarrier::complete_tx::bytes [%0], [%1, {%3, %4, %5}], [%2];"
               :: "r"(dst), "l"(m), "r"(bar), "r"(c0), "r"(c1), "r"(c2) : "memory");
}
__device__ __forceinline__ void tma2d_store(const CUtensorMap* m, uint32_t src, int c0, int c1) {
  asm volatile("cp.async.bulk.tensor.2d.global.shared::cta.bulk_group [%0, {%2, %3}], [%1];" :: "l"(m), "r"(src), "r"(c0), "r"(c1) : "memory");
}
__device__ __forceinline__ void bulk_load(uint32_t dst, const void* src, uint32_t bytes, uint32_t bar) {
  asm volatile("cp.async.bulk.shared::cluster.global.mbarrier::complete_tx::bytes [%0], [%1], %2, [%3];" :: "r"(dst), "l"(src), "r"(bytes), "r"(bar) : "memory");
}
__device__ __forceinline__ void tma3d_store(const CUtensorMap* m, uint32_t src, int c0, int c1, int c2) {
  asm volatile("cp.async.bulk.tensor.3d.global.shared::cta.bulk_group [%0, {%2, %3, %4}], [%1];" :: "l"(m), "r"(src), "r"(c0), "r"(c1), "r"(c2) : "memory");
}
__device__ __forceinline__ void bulk_commit() { asm volatile("cp.async.bulk.commit_group;" ::: "memory"); }
__device__ __forceinline__ void bulk_wait_all() { asm volatile("cp.async.bulk.wait_group 0;" ::: "memory"); }
__device__ __forceinline__ void bulk_wait_read() { asm volatile("cp.async.bulk.wait_group.read 0;" ::: "memory"); }
__device__ __forceinline__ void fence_async_smem() { asm volatile("fence.proxy.async.shared::cta;" ::: "memory"); }
__device__ __forceinline__ void fence_async_global() { asm volatile("fence.proxy.async.global;" ::: "memory"); }
__device__ __forceinline__ uint32_t ld_cnt(Scratch* S, int c) { uint32_t v; asm volatile("ld.relaxed.gpu.global.u32 %0, [%1];" : "=r"(v) : "l"(S->cnt + c * 32) : "memory"); return v; }
__device__ __forceinline__ void signal(Scratch* S, int c, uint32_t inc) { asm volatile("red.release.gpu.global.add.u32 [%0], %1;" :: "l"(S->cnt + c * 32), "r"(inc) : "memory"); }
__device__ __forceinline__ bool reached(Scratch* S, int c, uint32_t ep) { return ld_cnt(S, c) - ep >= EPOCH; }
__device__ __forceinline__ void await(Scratch* S, int c, uint32_t ep) { while (!reached(S, c, ep)) { } }
__device__ __forceinline__ void bar_sync(int id, int n) { asm volatile("bar.sync %0, %1;" :: "r"(id), "r"(n) : "memory"); }
__device__ __forceinline__ void bar_arrive(int id, int n) { asm volatile("bar.arrive %0, %1;" :: "r"(id), "r"(n) : "memory"); }
__device__ __forceinline__ void wg_fence() { asm volatile("wgmma.fence.sync.aligned;" ::: "memory"); }
__device__ __forceinline__ void wg_commit() { asm volatile("wgmma.commit_group.sync.aligned;" ::: "memory"); }
template <int N> __device__ __forceinline__ void wg_wait() { asm volatile("wgmma.wait_group.sync.aligned %0;" :: "n"(N) : "memory"); }
template <int N> __device__ __forceinline__ void pin_regs(float* a) {
#pragma unroll
  for (int i = 0; i < N; i++) asm volatile("" : "+f"(a[i]) :: "memory");
}
__device__ __forceinline__ uint64_t make_desc(uint32_t addr, uint32_t lbo, uint32_t sbo, uint32_t swz) {
  return (uint64_t)((addr & 0x3FFFF) >> 4) | ((uint64_t)(lbo >> 4) << 16) | ((uint64_t)(sbo >> 4) << 32) | ((uint64_t)swz << 62);
}
__device__ __forceinline__ uint32_t pack_bf16(float lo, float hi) { uint32_t r; asm("cvt.rn.bf16x2.f32 %0, %1, %2;" : "=r"(r) : "f"(hi), "f"(lo)); return r; }
__device__ __forceinline__ float bf_lo(uint32_t p) { return __uint_as_float(p << 16); }
__device__ __forceinline__ float bf_hi(uint32_t p) { return __uint_as_float(p & 0xffff0000u); }
__device__ __forceinline__ float round_bf16(float v) { return bf_lo(pack_bf16(v, 0.f)); }
__device__ __forceinline__ uint32_t bmul2(uint32_t a, uint32_t b) { uint32_t r; asm("mul.rn.bf16x2 %0, %1, %2;" : "=r"(r) : "r"(a), "r"(b)); return r; }
__device__ __forceinline__ uint32_t badd2(uint32_t a, uint32_t b) { uint32_t r; asm("add.rn.bf16x2 %0, %1, %2;" : "=r"(r) : "r"(a), "r"(b)); return r; }
__device__ __forceinline__ uint32_t bfma2(uint32_t a, uint32_t b, uint32_t c) { uint32_t r; asm("fma.rn.bf16x2 %0, %1, %2, %3;" : "=r"(r) : "r"(a), "r"(b), "r"(c)); return r; }
__device__ __forceinline__ uint32_t bsub2(uint32_t a, uint32_t b) { uint32_t r; asm("sub.rn.bf16x2 %0, %1, %2;" : "=r"(r) : "r"(a), "r"(b)); return r; }
__device__ __forceinline__ float tanh_fast(float v) { float r; asm("tanh.approx.f32 %0, %1;" : "=f"(r) : "f"(v)); return r; }
__device__ __forceinline__ float gelu_half(float h) {
  return fmaf(h, tanh_fast(h * fmaf(h * h, 8.0f * 0.7978845608028654f * 0.044715f, 2.0f * 0.7978845608028654f)), h);
}
__device__ __forceinline__ float silu_half(float h) { return fmaf(h, tanh_fast(h), h); }
__device__ __forceinline__ uint32_t ldg32(const void* p) { uint32_t v; asm volatile("ld.global.u32 %0, [%1];" : "=r"(v) : "l"(p) : "memory"); return v; }
__device__ __forceinline__ uint32_t lds32(uint32_t a) { uint32_t v; asm volatile("ld.shared.u32 %0, [%1];" : "=r"(v) : "r"(a) : "memory"); return v; }
__device__ __forceinline__ uint32_t lds16(uint32_t a) { uint32_t v; asm volatile("ld.shared.u16 %0, [%1];" : "=r"(v) : "r"(a) : "memory"); return v; }
__device__ __forceinline__ uint4 lds128(uint32_t a) { uint4 v; asm volatile("ld.shared.v4.u32 {%0,%1,%2,%3}, [%4];" : "=r"(v.x), "=r"(v.y), "=r"(v.z), "=r"(v.w) : "r"(a) : "memory"); return v; }
__device__ __forceinline__ void sts128(uint32_t a, uint32_t x, uint32_t y, uint32_t z, uint32_t w) {
  asm volatile("st.shared.v4.u32 [%0], {%1,%2,%3,%4};" :: "r"(a), "r"(x), "r"(y), "r"(z), "r"(w) : "memory");
}
__device__ __forceinline__ void sts32(uint32_t a, uint32_t v) { asm volatile("st.shared.u32 [%0], %1;" :: "r"(a), "r"(v) : "memory"); }
__device__ __forceinline__ void ldsm4(uint32_t* r, uint32_t a) {
  asm volatile("ldmatrix.sync.aligned.m8n8.x4.shared.b16 {%0,%1,%2,%3}, [%4];" : "=r"(r[0]), "=r"(r[1]), "=r"(r[2]), "=r"(r[3]) : "r"(a) : "memory");
}
__device__ __forceinline__ void ldsm2(uint32_t* r, uint32_t a) {
  asm volatile("ldmatrix.sync.aligned.m8n8.x2.shared.b16 {%0,%1}, [%2];" : "=r"(r[0]), "=r"(r[1]) : "r"(a) : "memory");
}
__device__ __forceinline__ void ldsm4t(uint32_t* r, uint32_t a) {
  asm volatile("ldmatrix.sync.aligned.m8n8.x4.trans.shared.b16 {%0,%1,%2,%3}, [%4];" : "=r"(r[0]), "=r"(r[1]), "=r"(r[2]), "=r"(r[3]) : "r"(a) : "memory");
}
__device__ __forceinline__ void ldsm2t(uint32_t* r, uint32_t a) {
  asm volatile("ldmatrix.sync.aligned.m8n8.x2.trans.shared.b16 {%0,%1}, [%2];" : "=r"(r[0]), "=r"(r[1]) : "r"(a) : "memory");
}
__device__ __forceinline__ void stsm4(uint32_t a, uint32_t r0, uint32_t r1, uint32_t r2, uint32_t r3) {
  asm volatile("stmatrix.sync.aligned.m8n8.x4.shared.b16 [%0], {%1,%2,%3,%4};" :: "r"(a), "r"(r0), "r"(r1), "r"(r2), "r"(r3) : "memory");
}
__device__ __forceinline__ void stsm2(uint32_t a, uint32_t r0, uint32_t r1) {
  asm volatile("stmatrix.sync.aligned.m8n8.x2.shared.b16 [%0], {%1,%2};" :: "r"(a), "r"(r0), "r"(r1) : "memory");
}
__device__ __forceinline__ void stsm4t(uint32_t a, uint32_t r0, uint32_t r1, uint32_t r2, uint32_t r3) {
  asm volatile("stmatrix.sync.aligned.m8n8.x4.trans.shared.b16 [%0], {%1,%2,%3,%4};" :: "r"(a), "r"(r0), "r"(r1), "r"(r2), "r"(r3) : "memory");
}

__device__ __forceinline__ void wgmma_ss_n144_t10(float* d, uint64_t da, uint64_t db, int sd) {
  asm volatile("{ .reg .pred p; setp.ne.b32 p, %74, 0;\n"
      "wgmma.mma_async.sync.aligned.m64n144k16.f32.bf16.bf16 {"
      "%0,%1,%2,%3,%4,%5,%6,%7,%8,%9,%10,%11,%12,%13,%14,%15,"
      "%16,%17,%18,%19,%20,%21,%22,%23,%24,%25,%26,%27,%28,%29,%30,%31,"
      "%32,%33,%34,%35,%36,%37,%38,%39,%40,%41,%42,%43,%44,%45,%46,%47,"
      "%48,%49,%50,%51,%52,%53,%54,%55,%56,%57,%58,%59,%60,%61,%62,%63,"
      "%64,%65,%66,%67,%68,%69,%70,%71"
      "}, %72, %73, p, 1, 1, 1, 0; }"
    : "+f"(d[0]), "+f"(d[1]), "+f"(d[2]), "+f"(d[3]), "+f"(d[4]), "+f"(d[5]), "+f"(d[6]), "+f"(d[7]),
      "+f"(d[8]), "+f"(d[9]), "+f"(d[10]), "+f"(d[11]), "+f"(d[12]), "+f"(d[13]), "+f"(d[14]), "+f"(d[15]),
      "+f"(d[16]), "+f"(d[17]), "+f"(d[18]), "+f"(d[19]), "+f"(d[20]), "+f"(d[21]), "+f"(d[22]), "+f"(d[23]),
      "+f"(d[24]), "+f"(d[25]), "+f"(d[26]), "+f"(d[27]), "+f"(d[28]), "+f"(d[29]), "+f"(d[30]), "+f"(d[31]),
      "+f"(d[32]), "+f"(d[33]), "+f"(d[34]), "+f"(d[35]), "+f"(d[36]), "+f"(d[37]), "+f"(d[38]), "+f"(d[39]),
      "+f"(d[40]), "+f"(d[41]), "+f"(d[42]), "+f"(d[43]), "+f"(d[44]), "+f"(d[45]), "+f"(d[46]), "+f"(d[47]),
      "+f"(d[48]), "+f"(d[49]), "+f"(d[50]), "+f"(d[51]), "+f"(d[52]), "+f"(d[53]), "+f"(d[54]), "+f"(d[55]),
      "+f"(d[56]), "+f"(d[57]), "+f"(d[58]), "+f"(d[59]), "+f"(d[60]), "+f"(d[61]), "+f"(d[62]), "+f"(d[63]),
      "+f"(d[64]), "+f"(d[65]), "+f"(d[66]), "+f"(d[67]), "+f"(d[68]), "+f"(d[69]), "+f"(d[70]), "+f"(d[71])
    : "l"(da), "l"(db), "r"(sd));
}

__device__ __forceinline__ void wgmma_ss_n160_t11(float* d, uint64_t da, uint64_t db, int sd) {
  asm volatile("{ .reg .pred p; setp.ne.b32 p, %82, 0;\n"
      "wgmma.mma_async.sync.aligned.m64n160k16.f32.bf16.bf16 {"
      "%0,%1,%2,%3,%4,%5,%6,%7,%8,%9,%10,%11,%12,%13,%14,%15,"
      "%16,%17,%18,%19,%20,%21,%22,%23,%24,%25,%26,%27,%28,%29,%30,%31,"
      "%32,%33,%34,%35,%36,%37,%38,%39,%40,%41,%42,%43,%44,%45,%46,%47,"
      "%48,%49,%50,%51,%52,%53,%54,%55,%56,%57,%58,%59,%60,%61,%62,%63,"
      "%64,%65,%66,%67,%68,%69,%70,%71,%72,%73,%74,%75,%76,%77,%78,%79"
      "}, %80, %81, p, 1, 1, 1, 1; }"
    : "+f"(d[0]), "+f"(d[1]), "+f"(d[2]), "+f"(d[3]), "+f"(d[4]), "+f"(d[5]), "+f"(d[6]), "+f"(d[7]),
      "+f"(d[8]), "+f"(d[9]), "+f"(d[10]), "+f"(d[11]), "+f"(d[12]), "+f"(d[13]), "+f"(d[14]), "+f"(d[15]),
      "+f"(d[16]), "+f"(d[17]), "+f"(d[18]), "+f"(d[19]), "+f"(d[20]), "+f"(d[21]), "+f"(d[22]), "+f"(d[23]),
      "+f"(d[24]), "+f"(d[25]), "+f"(d[26]), "+f"(d[27]), "+f"(d[28]), "+f"(d[29]), "+f"(d[30]), "+f"(d[31]),
      "+f"(d[32]), "+f"(d[33]), "+f"(d[34]), "+f"(d[35]), "+f"(d[36]), "+f"(d[37]), "+f"(d[38]), "+f"(d[39]),
      "+f"(d[40]), "+f"(d[41]), "+f"(d[42]), "+f"(d[43]), "+f"(d[44]), "+f"(d[45]), "+f"(d[46]), "+f"(d[47]),
      "+f"(d[48]), "+f"(d[49]), "+f"(d[50]), "+f"(d[51]), "+f"(d[52]), "+f"(d[53]), "+f"(d[54]), "+f"(d[55]),
      "+f"(d[56]), "+f"(d[57]), "+f"(d[58]), "+f"(d[59]), "+f"(d[60]), "+f"(d[61]), "+f"(d[62]), "+f"(d[63]),
      "+f"(d[64]), "+f"(d[65]), "+f"(d[66]), "+f"(d[67]), "+f"(d[68]), "+f"(d[69]), "+f"(d[70]), "+f"(d[71]),
      "+f"(d[72]), "+f"(d[73]), "+f"(d[74]), "+f"(d[75]), "+f"(d[76]), "+f"(d[77]), "+f"(d[78]), "+f"(d[79])
    : "l"(da), "l"(db), "r"(sd));
}

__device__ __forceinline__ void wgmma_ss_n96_t11(float* d, uint64_t da, uint64_t db, int sd) {
  asm volatile("{ .reg .pred p; setp.ne.b32 p, %50, 0;\n"
      "wgmma.mma_async.sync.aligned.m64n96k16.f32.bf16.bf16 {"
      "%0,%1,%2,%3,%4,%5,%6,%7,%8,%9,%10,%11,%12,%13,%14,%15,"
      "%16,%17,%18,%19,%20,%21,%22,%23,%24,%25,%26,%27,%28,%29,%30,%31,"
      "%32,%33,%34,%35,%36,%37,%38,%39,%40,%41,%42,%43,%44,%45,%46,%47"
      "}, %48, %49, p, 1, 1, 1, 1; }"
    : "+f"(d[0]), "+f"(d[1]), "+f"(d[2]), "+f"(d[3]), "+f"(d[4]), "+f"(d[5]), "+f"(d[6]), "+f"(d[7]),
      "+f"(d[8]), "+f"(d[9]), "+f"(d[10]), "+f"(d[11]), "+f"(d[12]), "+f"(d[13]), "+f"(d[14]), "+f"(d[15]),
      "+f"(d[16]), "+f"(d[17]), "+f"(d[18]), "+f"(d[19]), "+f"(d[20]), "+f"(d[21]), "+f"(d[22]), "+f"(d[23]),
      "+f"(d[24]), "+f"(d[25]), "+f"(d[26]), "+f"(d[27]), "+f"(d[28]), "+f"(d[29]), "+f"(d[30]), "+f"(d[31]),
      "+f"(d[32]), "+f"(d[33]), "+f"(d[34]), "+f"(d[35]), "+f"(d[36]), "+f"(d[37]), "+f"(d[38]), "+f"(d[39]),
      "+f"(d[40]), "+f"(d[41]), "+f"(d[42]), "+f"(d[43]), "+f"(d[44]), "+f"(d[45]), "+f"(d[46]), "+f"(d[47])
    : "l"(da), "l"(db), "r"(sd));
}

__device__ __forceinline__ void wgmma_rs_n16(float* d, const uint32_t* a, uint64_t db, int sd) {
  asm volatile("{ .reg .pred p; setp.ne.b32 p, %13, 0;\n"
      "wgmma.mma_async.sync.aligned.m64n16k16.f32.bf16.bf16 {"
      "%0,%1,%2,%3,%4,%5,%6,%7"
      "}, {%8,%9,%10,%11}, %12, p, 1, 1, 0; }"
    : "+f"(d[0]), "+f"(d[1]), "+f"(d[2]), "+f"(d[3]), "+f"(d[4]), "+f"(d[5]), "+f"(d[6]), "+f"(d[7])
    : "r"(a[0]), "r"(a[1]), "r"(a[2]), "r"(a[3]), "l"(db), "r"(sd));
}

__device__ __forceinline__ void wgmma_rs_n32(float* d, const uint32_t* a, uint64_t db, int sd) {
  asm volatile("{ .reg .pred p; setp.ne.b32 p, %21, 0;\n"
      "wgmma.mma_async.sync.aligned.m64n32k16.f32.bf16.bf16 {"
      "%0,%1,%2,%3,%4,%5,%6,%7,%8,%9,%10,%11,%12,%13,%14,%15"
      "}, {%16,%17,%18,%19}, %20, p, 1, 1, 0; }"
    : "+f"(d[0]), "+f"(d[1]), "+f"(d[2]), "+f"(d[3]), "+f"(d[4]), "+f"(d[5]), "+f"(d[6]), "+f"(d[7]),
      "+f"(d[8]), "+f"(d[9]), "+f"(d[10]), "+f"(d[11]), "+f"(d[12]), "+f"(d[13]), "+f"(d[14]), "+f"(d[15])
    : "r"(a[0]), "r"(a[1]), "r"(a[2]), "r"(a[3]), "l"(db), "r"(sd));
}

__device__ __forceinline__ void wgmma_rs_n48(float* d, const uint32_t* a, uint64_t db, int sd) {
  asm volatile("{ .reg .pred p; setp.ne.b32 p, %29, 0;\n"
      "wgmma.mma_async.sync.aligned.m64n48k16.f32.bf16.bf16 {"
      "%0,%1,%2,%3,%4,%5,%6,%7,%8,%9,%10,%11,%12,%13,%14,%15,"
      "%16,%17,%18,%19,%20,%21,%22,%23"
      "}, {%24,%25,%26,%27}, %28, p, 1, 1, 0; }"
    : "+f"(d[0]), "+f"(d[1]), "+f"(d[2]), "+f"(d[3]), "+f"(d[4]), "+f"(d[5]), "+f"(d[6]), "+f"(d[7]),
      "+f"(d[8]), "+f"(d[9]), "+f"(d[10]), "+f"(d[11]), "+f"(d[12]), "+f"(d[13]), "+f"(d[14]), "+f"(d[15]),
      "+f"(d[16]), "+f"(d[17]), "+f"(d[18]), "+f"(d[19]), "+f"(d[20]), "+f"(d[21]), "+f"(d[22]), "+f"(d[23])
    : "r"(a[0]), "r"(a[1]), "r"(a[2]), "r"(a[3]), "l"(db), "r"(sd));
}

__device__ __forceinline__ void wgmma_rs_n64(float* d, const uint32_t* a, uint64_t db, int sd) {
  asm volatile("{ .reg .pred p; setp.ne.b32 p, %37, 0;\n"
      "wgmma.mma_async.sync.aligned.m64n64k16.f32.bf16.bf16 {"
      "%0,%1,%2,%3,%4,%5,%6,%7,%8,%9,%10,%11,%12,%13,%14,%15,"
      "%16,%17,%18,%19,%20,%21,%22,%23,%24,%25,%26,%27,%28,%29,%30,%31"
      "}, {%32,%33,%34,%35}, %36, p, 1, 1, 0; }"
    : "+f"(d[0]), "+f"(d[1]), "+f"(d[2]), "+f"(d[3]), "+f"(d[4]), "+f"(d[5]), "+f"(d[6]), "+f"(d[7]),
      "+f"(d[8]), "+f"(d[9]), "+f"(d[10]), "+f"(d[11]), "+f"(d[12]), "+f"(d[13]), "+f"(d[14]), "+f"(d[15]),
      "+f"(d[16]), "+f"(d[17]), "+f"(d[18]), "+f"(d[19]), "+f"(d[20]), "+f"(d[21]), "+f"(d[22]), "+f"(d[23]),
      "+f"(d[24]), "+f"(d[25]), "+f"(d[26]), "+f"(d[27]), "+f"(d[28]), "+f"(d[29]), "+f"(d[30]), "+f"(d[31])
    : "r"(a[0]), "r"(a[1]), "r"(a[2]), "r"(a[3]), "l"(db), "r"(sd));
}

__device__ __forceinline__ void wgmma_rs_n80(float* d, const uint32_t* a, uint64_t db, int sd) {
  asm volatile("{ .reg .pred p; setp.ne.b32 p, %45, 0;\n"
      "wgmma.mma_async.sync.aligned.m64n80k16.f32.bf16.bf16 {"
      "%0,%1,%2,%3,%4,%5,%6,%7,%8,%9,%10,%11,%12,%13,%14,%15,"
      "%16,%17,%18,%19,%20,%21,%22,%23,%24,%25,%26,%27,%28,%29,%30,%31,"
      "%32,%33,%34,%35,%36,%37,%38,%39"
      "}, {%40,%41,%42,%43}, %44, p, 1, 1, 0; }"
    : "+f"(d[0]), "+f"(d[1]), "+f"(d[2]), "+f"(d[3]), "+f"(d[4]), "+f"(d[5]), "+f"(d[6]), "+f"(d[7]),
      "+f"(d[8]), "+f"(d[9]), "+f"(d[10]), "+f"(d[11]), "+f"(d[12]), "+f"(d[13]), "+f"(d[14]), "+f"(d[15]),
      "+f"(d[16]), "+f"(d[17]), "+f"(d[18]), "+f"(d[19]), "+f"(d[20]), "+f"(d[21]), "+f"(d[22]), "+f"(d[23]),
      "+f"(d[24]), "+f"(d[25]), "+f"(d[26]), "+f"(d[27]), "+f"(d[28]), "+f"(d[29]), "+f"(d[30]), "+f"(d[31]),
      "+f"(d[32]), "+f"(d[33]), "+f"(d[34]), "+f"(d[35]), "+f"(d[36]), "+f"(d[37]), "+f"(d[38]), "+f"(d[39])
    : "r"(a[0]), "r"(a[1]), "r"(a[2]), "r"(a[3]), "l"(db), "r"(sd));
}

__device__ __forceinline__ void wgmma_rs_n96(float* d, const uint32_t* a, uint64_t db, int sd) {
  asm volatile("{ .reg .pred p; setp.ne.b32 p, %53, 0;\n"
      "wgmma.mma_async.sync.aligned.m64n96k16.f32.bf16.bf16 {"
      "%0,%1,%2,%3,%4,%5,%6,%7,%8,%9,%10,%11,%12,%13,%14,%15,"
      "%16,%17,%18,%19,%20,%21,%22,%23,%24,%25,%26,%27,%28,%29,%30,%31,"
      "%32,%33,%34,%35,%36,%37,%38,%39,%40,%41,%42,%43,%44,%45,%46,%47"
      "}, {%48,%49,%50,%51}, %52, p, 1, 1, 0; }"
    : "+f"(d[0]), "+f"(d[1]), "+f"(d[2]), "+f"(d[3]), "+f"(d[4]), "+f"(d[5]), "+f"(d[6]), "+f"(d[7]),
      "+f"(d[8]), "+f"(d[9]), "+f"(d[10]), "+f"(d[11]), "+f"(d[12]), "+f"(d[13]), "+f"(d[14]), "+f"(d[15]),
      "+f"(d[16]), "+f"(d[17]), "+f"(d[18]), "+f"(d[19]), "+f"(d[20]), "+f"(d[21]), "+f"(d[22]), "+f"(d[23]),
      "+f"(d[24]), "+f"(d[25]), "+f"(d[26]), "+f"(d[27]), "+f"(d[28]), "+f"(d[29]), "+f"(d[30]), "+f"(d[31]),
      "+f"(d[32]), "+f"(d[33]), "+f"(d[34]), "+f"(d[35]), "+f"(d[36]), "+f"(d[37]), "+f"(d[38]), "+f"(d[39]),
      "+f"(d[40]), "+f"(d[41]), "+f"(d[42]), "+f"(d[43]), "+f"(d[44]), "+f"(d[45]), "+f"(d[46]), "+f"(d[47])
    : "r"(a[0]), "r"(a[1]), "r"(a[2]), "r"(a[3]), "l"(db), "r"(sd));
}

__device__ __forceinline__ void wgmma_rs_n112(float* d, const uint32_t* a, uint64_t db, int sd) {
  asm volatile("{ .reg .pred p; setp.ne.b32 p, %61, 0;\n"
      "wgmma.mma_async.sync.aligned.m64n112k16.f32.bf16.bf16 {"
      "%0,%1,%2,%3,%4,%5,%6,%7,%8,%9,%10,%11,%12,%13,%14,%15,"
      "%16,%17,%18,%19,%20,%21,%22,%23,%24,%25,%26,%27,%28,%29,%30,%31,"
      "%32,%33,%34,%35,%36,%37,%38,%39,%40,%41,%42,%43,%44,%45,%46,%47,"
      "%48,%49,%50,%51,%52,%53,%54,%55"
      "}, {%56,%57,%58,%59}, %60, p, 1, 1, 0; }"
    : "+f"(d[0]), "+f"(d[1]), "+f"(d[2]), "+f"(d[3]), "+f"(d[4]), "+f"(d[5]), "+f"(d[6]), "+f"(d[7]),
      "+f"(d[8]), "+f"(d[9]), "+f"(d[10]), "+f"(d[11]), "+f"(d[12]), "+f"(d[13]), "+f"(d[14]), "+f"(d[15]),
      "+f"(d[16]), "+f"(d[17]), "+f"(d[18]), "+f"(d[19]), "+f"(d[20]), "+f"(d[21]), "+f"(d[22]), "+f"(d[23]),
      "+f"(d[24]), "+f"(d[25]), "+f"(d[26]), "+f"(d[27]), "+f"(d[28]), "+f"(d[29]), "+f"(d[30]), "+f"(d[31]),
      "+f"(d[32]), "+f"(d[33]), "+f"(d[34]), "+f"(d[35]), "+f"(d[36]), "+f"(d[37]), "+f"(d[38]), "+f"(d[39]),
      "+f"(d[40]), "+f"(d[41]), "+f"(d[42]), "+f"(d[43]), "+f"(d[44]), "+f"(d[45]), "+f"(d[46]), "+f"(d[47]),
      "+f"(d[48]), "+f"(d[49]), "+f"(d[50]), "+f"(d[51]), "+f"(d[52]), "+f"(d[53]), "+f"(d[54]), "+f"(d[55])
    : "r"(a[0]), "r"(a[1]), "r"(a[2]), "r"(a[3]), "l"(db), "r"(sd));
}

__device__ __forceinline__ void wgmma_rs_n128(float* d, const uint32_t* a, uint64_t db, int sd) {
  asm volatile("{ .reg .pred p; setp.ne.b32 p, %69, 0;\n"
      "wgmma.mma_async.sync.aligned.m64n128k16.f32.bf16.bf16 {"
      "%0,%1,%2,%3,%4,%5,%6,%7,%8,%9,%10,%11,%12,%13,%14,%15,"
      "%16,%17,%18,%19,%20,%21,%22,%23,%24,%25,%26,%27,%28,%29,%30,%31,"
      "%32,%33,%34,%35,%36,%37,%38,%39,%40,%41,%42,%43,%44,%45,%46,%47,"
      "%48,%49,%50,%51,%52,%53,%54,%55,%56,%57,%58,%59,%60,%61,%62,%63"
      "}, {%64,%65,%66,%67}, %68, p, 1, 1, 0; }"
    : "+f"(d[0]), "+f"(d[1]), "+f"(d[2]), "+f"(d[3]), "+f"(d[4]), "+f"(d[5]), "+f"(d[6]), "+f"(d[7]),
      "+f"(d[8]), "+f"(d[9]), "+f"(d[10]), "+f"(d[11]), "+f"(d[12]), "+f"(d[13]), "+f"(d[14]), "+f"(d[15]),
      "+f"(d[16]), "+f"(d[17]), "+f"(d[18]), "+f"(d[19]), "+f"(d[20]), "+f"(d[21]), "+f"(d[22]), "+f"(d[23]),
      "+f"(d[24]), "+f"(d[25]), "+f"(d[26]), "+f"(d[27]), "+f"(d[28]), "+f"(d[29]), "+f"(d[30]), "+f"(d[31]),
      "+f"(d[32]), "+f"(d[33]), "+f"(d[34]), "+f"(d[35]), "+f"(d[36]), "+f"(d[37]), "+f"(d[38]), "+f"(d[39]),
      "+f"(d[40]), "+f"(d[41]), "+f"(d[42]), "+f"(d[43]), "+f"(d[44]), "+f"(d[45]), "+f"(d[46]), "+f"(d[47]),
      "+f"(d[48]), "+f"(d[49]), "+f"(d[50]), "+f"(d[51]), "+f"(d[52]), "+f"(d[53]), "+f"(d[54]), "+f"(d[55]),
      "+f"(d[56]), "+f"(d[57]), "+f"(d[58]), "+f"(d[59]), "+f"(d[60]), "+f"(d[61]), "+f"(d[62]), "+f"(d[63])
    : "r"(a[0]), "r"(a[1]), "r"(a[2]), "r"(a[3]), "l"(db), "r"(sd));
}

__device__ __forceinline__ void wgmma_rs_n144(float* d, const uint32_t* a, uint64_t db, int sd) {
  asm volatile("{ .reg .pred p; setp.ne.b32 p, %77, 0;\n"
      "wgmma.mma_async.sync.aligned.m64n144k16.f32.bf16.bf16 {"
      "%0,%1,%2,%3,%4,%5,%6,%7,%8,%9,%10,%11,%12,%13,%14,%15,"
      "%16,%17,%18,%19,%20,%21,%22,%23,%24,%25,%26,%27,%28,%29,%30,%31,"
      "%32,%33,%34,%35,%36,%37,%38,%39,%40,%41,%42,%43,%44,%45,%46,%47,"
      "%48,%49,%50,%51,%52,%53,%54,%55,%56,%57,%58,%59,%60,%61,%62,%63,"
      "%64,%65,%66,%67,%68,%69,%70,%71"
      "}, {%72,%73,%74,%75}, %76, p, 1, 1, 0; }"
    : "+f"(d[0]), "+f"(d[1]), "+f"(d[2]), "+f"(d[3]), "+f"(d[4]), "+f"(d[5]), "+f"(d[6]), "+f"(d[7]),
      "+f"(d[8]), "+f"(d[9]), "+f"(d[10]), "+f"(d[11]), "+f"(d[12]), "+f"(d[13]), "+f"(d[14]), "+f"(d[15]),
      "+f"(d[16]), "+f"(d[17]), "+f"(d[18]), "+f"(d[19]), "+f"(d[20]), "+f"(d[21]), "+f"(d[22]), "+f"(d[23]),
      "+f"(d[24]), "+f"(d[25]), "+f"(d[26]), "+f"(d[27]), "+f"(d[28]), "+f"(d[29]), "+f"(d[30]), "+f"(d[31]),
      "+f"(d[32]), "+f"(d[33]), "+f"(d[34]), "+f"(d[35]), "+f"(d[36]), "+f"(d[37]), "+f"(d[38]), "+f"(d[39]),
      "+f"(d[40]), "+f"(d[41]), "+f"(d[42]), "+f"(d[43]), "+f"(d[44]), "+f"(d[45]), "+f"(d[46]), "+f"(d[47]),
      "+f"(d[48]), "+f"(d[49]), "+f"(d[50]), "+f"(d[51]), "+f"(d[52]), "+f"(d[53]), "+f"(d[54]), "+f"(d[55]),
      "+f"(d[56]), "+f"(d[57]), "+f"(d[58]), "+f"(d[59]), "+f"(d[60]), "+f"(d[61]), "+f"(d[62]), "+f"(d[63]),
      "+f"(d[64]), "+f"(d[65]), "+f"(d[66]), "+f"(d[67]), "+f"(d[68]), "+f"(d[69]), "+f"(d[70]), "+f"(d[71])
    : "r"(a[0]), "r"(a[1]), "r"(a[2]), "r"(a[3]), "l"(db), "r"(sd));
}

__device__ __forceinline__ void wgmma_rs_n160(float* d, const uint32_t* a, uint64_t db, int sd) {
  asm volatile("{ .reg .pred p; setp.ne.b32 p, %85, 0;\n"
      "wgmma.mma_async.sync.aligned.m64n160k16.f32.bf16.bf16 {"
      "%0,%1,%2,%3,%4,%5,%6,%7,%8,%9,%10,%11,%12,%13,%14,%15,"
      "%16,%17,%18,%19,%20,%21,%22,%23,%24,%25,%26,%27,%28,%29,%30,%31,"
      "%32,%33,%34,%35,%36,%37,%38,%39,%40,%41,%42,%43,%44,%45,%46,%47,"
      "%48,%49,%50,%51,%52,%53,%54,%55,%56,%57,%58,%59,%60,%61,%62,%63,"
      "%64,%65,%66,%67,%68,%69,%70,%71,%72,%73,%74,%75,%76,%77,%78,%79"
      "}, {%80,%81,%82,%83}, %84, p, 1, 1, 0; }"
    : "+f"(d[0]), "+f"(d[1]), "+f"(d[2]), "+f"(d[3]), "+f"(d[4]), "+f"(d[5]), "+f"(d[6]), "+f"(d[7]),
      "+f"(d[8]), "+f"(d[9]), "+f"(d[10]), "+f"(d[11]), "+f"(d[12]), "+f"(d[13]), "+f"(d[14]), "+f"(d[15]),
      "+f"(d[16]), "+f"(d[17]), "+f"(d[18]), "+f"(d[19]), "+f"(d[20]), "+f"(d[21]), "+f"(d[22]), "+f"(d[23]),
      "+f"(d[24]), "+f"(d[25]), "+f"(d[26]), "+f"(d[27]), "+f"(d[28]), "+f"(d[29]), "+f"(d[30]), "+f"(d[31]),
      "+f"(d[32]), "+f"(d[33]), "+f"(d[34]), "+f"(d[35]), "+f"(d[36]), "+f"(d[37]), "+f"(d[38]), "+f"(d[39]),
      "+f"(d[40]), "+f"(d[41]), "+f"(d[42]), "+f"(d[43]), "+f"(d[44]), "+f"(d[45]), "+f"(d[46]), "+f"(d[47]),
      "+f"(d[48]), "+f"(d[49]), "+f"(d[50]), "+f"(d[51]), "+f"(d[52]), "+f"(d[53]), "+f"(d[54]), "+f"(d[55]),
      "+f"(d[56]), "+f"(d[57]), "+f"(d[58]), "+f"(d[59]), "+f"(d[60]), "+f"(d[61]), "+f"(d[62]), "+f"(d[63]),
      "+f"(d[64]), "+f"(d[65]), "+f"(d[66]), "+f"(d[67]), "+f"(d[68]), "+f"(d[69]), "+f"(d[70]), "+f"(d[71]),
      "+f"(d[72]), "+f"(d[73]), "+f"(d[74]), "+f"(d[75]), "+f"(d[76]), "+f"(d[77]), "+f"(d[78]), "+f"(d[79])
    : "r"(a[0]), "r"(a[1]), "r"(a[2]), "r"(a[3]), "l"(db), "r"(sd));
}

__device__ __forceinline__ void wgmma_rs_n176(float* d, const uint32_t* a, uint64_t db, int sd) {
  asm volatile("{ .reg .pred p; setp.ne.b32 p, %93, 0;\n"
      "wgmma.mma_async.sync.aligned.m64n176k16.f32.bf16.bf16 {"
      "%0,%1,%2,%3,%4,%5,%6,%7,%8,%9,%10,%11,%12,%13,%14,%15,"
      "%16,%17,%18,%19,%20,%21,%22,%23,%24,%25,%26,%27,%28,%29,%30,%31,"
      "%32,%33,%34,%35,%36,%37,%38,%39,%40,%41,%42,%43,%44,%45,%46,%47,"
      "%48,%49,%50,%51,%52,%53,%54,%55,%56,%57,%58,%59,%60,%61,%62,%63,"
      "%64,%65,%66,%67,%68,%69,%70,%71,%72,%73,%74,%75,%76,%77,%78,%79,"
      "%80,%81,%82,%83,%84,%85,%86,%87"
      "}, {%88,%89,%90,%91}, %92, p, 1, 1, 0; }"
    : "+f"(d[0]), "+f"(d[1]), "+f"(d[2]), "+f"(d[3]), "+f"(d[4]), "+f"(d[5]), "+f"(d[6]), "+f"(d[7]),
      "+f"(d[8]), "+f"(d[9]), "+f"(d[10]), "+f"(d[11]), "+f"(d[12]), "+f"(d[13]), "+f"(d[14]), "+f"(d[15]),
      "+f"(d[16]), "+f"(d[17]), "+f"(d[18]), "+f"(d[19]), "+f"(d[20]), "+f"(d[21]), "+f"(d[22]), "+f"(d[23]),
      "+f"(d[24]), "+f"(d[25]), "+f"(d[26]), "+f"(d[27]), "+f"(d[28]), "+f"(d[29]), "+f"(d[30]), "+f"(d[31]),
      "+f"(d[32]), "+f"(d[33]), "+f"(d[34]), "+f"(d[35]), "+f"(d[36]), "+f"(d[37]), "+f"(d[38]), "+f"(d[39]),
      "+f"(d[40]), "+f"(d[41]), "+f"(d[42]), "+f"(d[43]), "+f"(d[44]), "+f"(d[45]), "+f"(d[46]), "+f"(d[47]),
      "+f"(d[48]), "+f"(d[49]), "+f"(d[50]), "+f"(d[51]), "+f"(d[52]), "+f"(d[53]), "+f"(d[54]), "+f"(d[55]),
      "+f"(d[56]), "+f"(d[57]), "+f"(d[58]), "+f"(d[59]), "+f"(d[60]), "+f"(d[61]), "+f"(d[62]), "+f"(d[63]),
      "+f"(d[64]), "+f"(d[65]), "+f"(d[66]), "+f"(d[67]), "+f"(d[68]), "+f"(d[69]), "+f"(d[70]), "+f"(d[71]),
      "+f"(d[72]), "+f"(d[73]), "+f"(d[74]), "+f"(d[75]), "+f"(d[76]), "+f"(d[77]), "+f"(d[78]), "+f"(d[79]),
      "+f"(d[80]), "+f"(d[81]), "+f"(d[82]), "+f"(d[83]), "+f"(d[84]), "+f"(d[85]), "+f"(d[86]), "+f"(d[87])
    : "r"(a[0]), "r"(a[1]), "r"(a[2]), "r"(a[3]), "l"(db), "r"(sd));
}

__device__ __forceinline__ void wgmma_rs_n192(float* d, const uint32_t* a, uint64_t db, int sd) {
  asm volatile("{ .reg .pred p; setp.ne.b32 p, %101, 0;\n"
      "wgmma.mma_async.sync.aligned.m64n192k16.f32.bf16.bf16 {"
      "%0,%1,%2,%3,%4,%5,%6,%7,%8,%9,%10,%11,%12,%13,%14,%15,"
      "%16,%17,%18,%19,%20,%21,%22,%23,%24,%25,%26,%27,%28,%29,%30,%31,"
      "%32,%33,%34,%35,%36,%37,%38,%39,%40,%41,%42,%43,%44,%45,%46,%47,"
      "%48,%49,%50,%51,%52,%53,%54,%55,%56,%57,%58,%59,%60,%61,%62,%63,"
      "%64,%65,%66,%67,%68,%69,%70,%71,%72,%73,%74,%75,%76,%77,%78,%79,"
      "%80,%81,%82,%83,%84,%85,%86,%87,%88,%89,%90,%91,%92,%93,%94,%95"
      "}, {%96,%97,%98,%99}, %100, p, 1, 1, 0; }"
    : "+f"(d[0]), "+f"(d[1]), "+f"(d[2]), "+f"(d[3]), "+f"(d[4]), "+f"(d[5]), "+f"(d[6]), "+f"(d[7]),
      "+f"(d[8]), "+f"(d[9]), "+f"(d[10]), "+f"(d[11]), "+f"(d[12]), "+f"(d[13]), "+f"(d[14]), "+f"(d[15]),
      "+f"(d[16]), "+f"(d[17]), "+f"(d[18]), "+f"(d[19]), "+f"(d[20]), "+f"(d[21]), "+f"(d[22]), "+f"(d[23]),
      "+f"(d[24]), "+f"(d[25]), "+f"(d[26]), "+f"(d[27]), "+f"(d[28]), "+f"(d[29]), "+f"(d[30]), "+f"(d[31]),
      "+f"(d[32]), "+f"(d[33]), "+f"(d[34]), "+f"(d[35]), "+f"(d[36]), "+f"(d[37]), "+f"(d[38]), "+f"(d[39]),
      "+f"(d[40]), "+f"(d[41]), "+f"(d[42]), "+f"(d[43]), "+f"(d[44]), "+f"(d[45]), "+f"(d[46]), "+f"(d[47]),
      "+f"(d[48]), "+f"(d[49]), "+f"(d[50]), "+f"(d[51]), "+f"(d[52]), "+f"(d[53]), "+f"(d[54]), "+f"(d[55]),
      "+f"(d[56]), "+f"(d[57]), "+f"(d[58]), "+f"(d[59]), "+f"(d[60]), "+f"(d[61]), "+f"(d[62]), "+f"(d[63]),
      "+f"(d[64]), "+f"(d[65]), "+f"(d[66]), "+f"(d[67]), "+f"(d[68]), "+f"(d[69]), "+f"(d[70]), "+f"(d[71]),
      "+f"(d[72]), "+f"(d[73]), "+f"(d[74]), "+f"(d[75]), "+f"(d[76]), "+f"(d[77]), "+f"(d[78]), "+f"(d[79]),
      "+f"(d[80]), "+f"(d[81]), "+f"(d[82]), "+f"(d[83]), "+f"(d[84]), "+f"(d[85]), "+f"(d[86]), "+f"(d[87]),
      "+f"(d[88]), "+f"(d[89]), "+f"(d[90]), "+f"(d[91]), "+f"(d[92]), "+f"(d[93]), "+f"(d[94]), "+f"(d[95])
    : "r"(a[0]), "r"(a[1]), "r"(a[2]), "r"(a[3]), "l"(db), "r"(sd));
}

__device__ __forceinline__ void wgmma_rs_n208(float* d, const uint32_t* a, uint64_t db, int sd) {
  asm volatile("{ .reg .pred p; setp.ne.b32 p, %109, 0;\n"
      "wgmma.mma_async.sync.aligned.m64n208k16.f32.bf16.bf16 {"
      "%0,%1,%2,%3,%4,%5,%6,%7,%8,%9,%10,%11,%12,%13,%14,%15,"
      "%16,%17,%18,%19,%20,%21,%22,%23,%24,%25,%26,%27,%28,%29,%30,%31,"
      "%32,%33,%34,%35,%36,%37,%38,%39,%40,%41,%42,%43,%44,%45,%46,%47,"
      "%48,%49,%50,%51,%52,%53,%54,%55,%56,%57,%58,%59,%60,%61,%62,%63,"
      "%64,%65,%66,%67,%68,%69,%70,%71,%72,%73,%74,%75,%76,%77,%78,%79,"
      "%80,%81,%82,%83,%84,%85,%86,%87,%88,%89,%90,%91,%92,%93,%94,%95,"
      "%96,%97,%98,%99,%100,%101,%102,%103"
      "}, {%104,%105,%106,%107}, %108, p, 1, 1, 0; }"
    : "+f"(d[0]), "+f"(d[1]), "+f"(d[2]), "+f"(d[3]), "+f"(d[4]), "+f"(d[5]), "+f"(d[6]), "+f"(d[7]),
      "+f"(d[8]), "+f"(d[9]), "+f"(d[10]), "+f"(d[11]), "+f"(d[12]), "+f"(d[13]), "+f"(d[14]), "+f"(d[15]),
      "+f"(d[16]), "+f"(d[17]), "+f"(d[18]), "+f"(d[19]), "+f"(d[20]), "+f"(d[21]), "+f"(d[22]), "+f"(d[23]),
      "+f"(d[24]), "+f"(d[25]), "+f"(d[26]), "+f"(d[27]), "+f"(d[28]), "+f"(d[29]), "+f"(d[30]), "+f"(d[31]),
      "+f"(d[32]), "+f"(d[33]), "+f"(d[34]), "+f"(d[35]), "+f"(d[36]), "+f"(d[37]), "+f"(d[38]), "+f"(d[39]),
      "+f"(d[40]), "+f"(d[41]), "+f"(d[42]), "+f"(d[43]), "+f"(d[44]), "+f"(d[45]), "+f"(d[46]), "+f"(d[47]),
      "+f"(d[48]), "+f"(d[49]), "+f"(d[50]), "+f"(d[51]), "+f"(d[52]), "+f"(d[53]), "+f"(d[54]), "+f"(d[55]),
      "+f"(d[56]), "+f"(d[57]), "+f"(d[58]), "+f"(d[59]), "+f"(d[60]), "+f"(d[61]), "+f"(d[62]), "+f"(d[63]),
      "+f"(d[64]), "+f"(d[65]), "+f"(d[66]), "+f"(d[67]), "+f"(d[68]), "+f"(d[69]), "+f"(d[70]), "+f"(d[71]),
      "+f"(d[72]), "+f"(d[73]), "+f"(d[74]), "+f"(d[75]), "+f"(d[76]), "+f"(d[77]), "+f"(d[78]), "+f"(d[79]),
      "+f"(d[80]), "+f"(d[81]), "+f"(d[82]), "+f"(d[83]), "+f"(d[84]), "+f"(d[85]), "+f"(d[86]), "+f"(d[87]),
      "+f"(d[88]), "+f"(d[89]), "+f"(d[90]), "+f"(d[91]), "+f"(d[92]), "+f"(d[93]), "+f"(d[94]), "+f"(d[95]),
      "+f"(d[96]), "+f"(d[97]), "+f"(d[98]), "+f"(d[99]), "+f"(d[100]), "+f"(d[101]), "+f"(d[102]), "+f"(d[103])
    : "r"(a[0]), "r"(a[1]), "r"(a[2]), "r"(a[3]), "l"(db), "r"(sd));
}

__device__ __forceinline__ void wgmma_rs_n224(float* d, const uint32_t* a, uint64_t db, int sd) {
  asm volatile("{ .reg .pred p; setp.ne.b32 p, %117, 0;\n"
      "wgmma.mma_async.sync.aligned.m64n224k16.f32.bf16.bf16 {"
      "%0,%1,%2,%3,%4,%5,%6,%7,%8,%9,%10,%11,%12,%13,%14,%15,"
      "%16,%17,%18,%19,%20,%21,%22,%23,%24,%25,%26,%27,%28,%29,%30,%31,"
      "%32,%33,%34,%35,%36,%37,%38,%39,%40,%41,%42,%43,%44,%45,%46,%47,"
      "%48,%49,%50,%51,%52,%53,%54,%55,%56,%57,%58,%59,%60,%61,%62,%63,"
      "%64,%65,%66,%67,%68,%69,%70,%71,%72,%73,%74,%75,%76,%77,%78,%79,"
      "%80,%81,%82,%83,%84,%85,%86,%87,%88,%89,%90,%91,%92,%93,%94,%95,"
      "%96,%97,%98,%99,%100,%101,%102,%103,%104,%105,%106,%107,%108,%109,%110,%111"
      "}, {%112,%113,%114,%115}, %116, p, 1, 1, 0; }"
    : "+f"(d[0]), "+f"(d[1]), "+f"(d[2]), "+f"(d[3]), "+f"(d[4]), "+f"(d[5]), "+f"(d[6]), "+f"(d[7]),
      "+f"(d[8]), "+f"(d[9]), "+f"(d[10]), "+f"(d[11]), "+f"(d[12]), "+f"(d[13]), "+f"(d[14]), "+f"(d[15]),
      "+f"(d[16]), "+f"(d[17]), "+f"(d[18]), "+f"(d[19]), "+f"(d[20]), "+f"(d[21]), "+f"(d[22]), "+f"(d[23]),
      "+f"(d[24]), "+f"(d[25]), "+f"(d[26]), "+f"(d[27]), "+f"(d[28]), "+f"(d[29]), "+f"(d[30]), "+f"(d[31]),
      "+f"(d[32]), "+f"(d[33]), "+f"(d[34]), "+f"(d[35]), "+f"(d[36]), "+f"(d[37]), "+f"(d[38]), "+f"(d[39]),
      "+f"(d[40]), "+f"(d[41]), "+f"(d[42]), "+f"(d[43]), "+f"(d[44]), "+f"(d[45]), "+f"(d[46]), "+f"(d[47]),
      "+f"(d[48]), "+f"(d[49]), "+f"(d[50]), "+f"(d[51]), "+f"(d[52]), "+f"(d[53]), "+f"(d[54]), "+f"(d[55]),
      "+f"(d[56]), "+f"(d[57]), "+f"(d[58]), "+f"(d[59]), "+f"(d[60]), "+f"(d[61]), "+f"(d[62]), "+f"(d[63]),
      "+f"(d[64]), "+f"(d[65]), "+f"(d[66]), "+f"(d[67]), "+f"(d[68]), "+f"(d[69]), "+f"(d[70]), "+f"(d[71]),
      "+f"(d[72]), "+f"(d[73]), "+f"(d[74]), "+f"(d[75]), "+f"(d[76]), "+f"(d[77]), "+f"(d[78]), "+f"(d[79]),
      "+f"(d[80]), "+f"(d[81]), "+f"(d[82]), "+f"(d[83]), "+f"(d[84]), "+f"(d[85]), "+f"(d[86]), "+f"(d[87]),
      "+f"(d[88]), "+f"(d[89]), "+f"(d[90]), "+f"(d[91]), "+f"(d[92]), "+f"(d[93]), "+f"(d[94]), "+f"(d[95]),
      "+f"(d[96]), "+f"(d[97]), "+f"(d[98]), "+f"(d[99]), "+f"(d[100]), "+f"(d[101]), "+f"(d[102]), "+f"(d[103]),
      "+f"(d[104]), "+f"(d[105]), "+f"(d[106]), "+f"(d[107]), "+f"(d[108]), "+f"(d[109]), "+f"(d[110]), "+f"(d[111])
    : "r"(a[0]), "r"(a[1]), "r"(a[2]), "r"(a[3]), "l"(db), "r"(sd));
}

__device__ __forceinline__ void wgmma_rs_n240(float* d, const uint32_t* a, uint64_t db, int sd) {
  asm volatile("{ .reg .pred p; setp.ne.b32 p, %125, 0;\n"
      "wgmma.mma_async.sync.aligned.m64n240k16.f32.bf16.bf16 {"
      "%0,%1,%2,%3,%4,%5,%6,%7,%8,%9,%10,%11,%12,%13,%14,%15,"
      "%16,%17,%18,%19,%20,%21,%22,%23,%24,%25,%26,%27,%28,%29,%30,%31,"
      "%32,%33,%34,%35,%36,%37,%38,%39,%40,%41,%42,%43,%44,%45,%46,%47,"
      "%48,%49,%50,%51,%52,%53,%54,%55,%56,%57,%58,%59,%60,%61,%62,%63,"
      "%64,%65,%66,%67,%68,%69,%70,%71,%72,%73,%74,%75,%76,%77,%78,%79,"
      "%80,%81,%82,%83,%84,%85,%86,%87,%88,%89,%90,%91,%92,%93,%94,%95,"
      "%96,%97,%98,%99,%100,%101,%102,%103,%104,%105,%106,%107,%108,%109,%110,%111,"
      "%112,%113,%114,%115,%116,%117,%118,%119"
      "}, {%120,%121,%122,%123}, %124, p, 1, 1, 0; }"
    : "+f"(d[0]), "+f"(d[1]), "+f"(d[2]), "+f"(d[3]), "+f"(d[4]), "+f"(d[5]), "+f"(d[6]), "+f"(d[7]),
      "+f"(d[8]), "+f"(d[9]), "+f"(d[10]), "+f"(d[11]), "+f"(d[12]), "+f"(d[13]), "+f"(d[14]), "+f"(d[15]),
      "+f"(d[16]), "+f"(d[17]), "+f"(d[18]), "+f"(d[19]), "+f"(d[20]), "+f"(d[21]), "+f"(d[22]), "+f"(d[23]),
      "+f"(d[24]), "+f"(d[25]), "+f"(d[26]), "+f"(d[27]), "+f"(d[28]), "+f"(d[29]), "+f"(d[30]), "+f"(d[31]),
      "+f"(d[32]), "+f"(d[33]), "+f"(d[34]), "+f"(d[35]), "+f"(d[36]), "+f"(d[37]), "+f"(d[38]), "+f"(d[39]),
      "+f"(d[40]), "+f"(d[41]), "+f"(d[42]), "+f"(d[43]), "+f"(d[44]), "+f"(d[45]), "+f"(d[46]), "+f"(d[47]),
      "+f"(d[48]), "+f"(d[49]), "+f"(d[50]), "+f"(d[51]), "+f"(d[52]), "+f"(d[53]), "+f"(d[54]), "+f"(d[55]),
      "+f"(d[56]), "+f"(d[57]), "+f"(d[58]), "+f"(d[59]), "+f"(d[60]), "+f"(d[61]), "+f"(d[62]), "+f"(d[63]),
      "+f"(d[64]), "+f"(d[65]), "+f"(d[66]), "+f"(d[67]), "+f"(d[68]), "+f"(d[69]), "+f"(d[70]), "+f"(d[71]),
      "+f"(d[72]), "+f"(d[73]), "+f"(d[74]), "+f"(d[75]), "+f"(d[76]), "+f"(d[77]), "+f"(d[78]), "+f"(d[79]),
      "+f"(d[80]), "+f"(d[81]), "+f"(d[82]), "+f"(d[83]), "+f"(d[84]), "+f"(d[85]), "+f"(d[86]), "+f"(d[87]),
      "+f"(d[88]), "+f"(d[89]), "+f"(d[90]), "+f"(d[91]), "+f"(d[92]), "+f"(d[93]), "+f"(d[94]), "+f"(d[95]),
      "+f"(d[96]), "+f"(d[97]), "+f"(d[98]), "+f"(d[99]), "+f"(d[100]), "+f"(d[101]), "+f"(d[102]), "+f"(d[103]),
      "+f"(d[104]), "+f"(d[105]), "+f"(d[106]), "+f"(d[107]), "+f"(d[108]), "+f"(d[109]), "+f"(d[110]), "+f"(d[111]),
      "+f"(d[112]), "+f"(d[113]), "+f"(d[114]), "+f"(d[115]), "+f"(d[116]), "+f"(d[117]), "+f"(d[118]), "+f"(d[119])
    : "r"(a[0]), "r"(a[1]), "r"(a[2]), "r"(a[3]), "l"(db), "r"(sd));
}

__device__ __forceinline__ void wgmma_rs_n256(float* d, const uint32_t* a, uint64_t db, int sd) {
  asm volatile("{ .reg .pred p; setp.ne.b32 p, %133, 0;\n"
      "wgmma.mma_async.sync.aligned.m64n256k16.f32.bf16.bf16 {"
      "%0,%1,%2,%3,%4,%5,%6,%7,%8,%9,%10,%11,%12,%13,%14,%15,"
      "%16,%17,%18,%19,%20,%21,%22,%23,%24,%25,%26,%27,%28,%29,%30,%31,"
      "%32,%33,%34,%35,%36,%37,%38,%39,%40,%41,%42,%43,%44,%45,%46,%47,"
      "%48,%49,%50,%51,%52,%53,%54,%55,%56,%57,%58,%59,%60,%61,%62,%63,"
      "%64,%65,%66,%67,%68,%69,%70,%71,%72,%73,%74,%75,%76,%77,%78,%79,"
      "%80,%81,%82,%83,%84,%85,%86,%87,%88,%89,%90,%91,%92,%93,%94,%95,"
      "%96,%97,%98,%99,%100,%101,%102,%103,%104,%105,%106,%107,%108,%109,%110,%111,"
      "%112,%113,%114,%115,%116,%117,%118,%119,%120,%121,%122,%123,%124,%125,%126,%127"
      "}, {%128,%129,%130,%131}, %132, p, 1, 1, 0; }"
    : "+f"(d[0]), "+f"(d[1]), "+f"(d[2]), "+f"(d[3]), "+f"(d[4]), "+f"(d[5]), "+f"(d[6]), "+f"(d[7]),
      "+f"(d[8]), "+f"(d[9]), "+f"(d[10]), "+f"(d[11]), "+f"(d[12]), "+f"(d[13]), "+f"(d[14]), "+f"(d[15]),
      "+f"(d[16]), "+f"(d[17]), "+f"(d[18]), "+f"(d[19]), "+f"(d[20]), "+f"(d[21]), "+f"(d[22]), "+f"(d[23]),
      "+f"(d[24]), "+f"(d[25]), "+f"(d[26]), "+f"(d[27]), "+f"(d[28]), "+f"(d[29]), "+f"(d[30]), "+f"(d[31]),
      "+f"(d[32]), "+f"(d[33]), "+f"(d[34]), "+f"(d[35]), "+f"(d[36]), "+f"(d[37]), "+f"(d[38]), "+f"(d[39]),
      "+f"(d[40]), "+f"(d[41]), "+f"(d[42]), "+f"(d[43]), "+f"(d[44]), "+f"(d[45]), "+f"(d[46]), "+f"(d[47]),
      "+f"(d[48]), "+f"(d[49]), "+f"(d[50]), "+f"(d[51]), "+f"(d[52]), "+f"(d[53]), "+f"(d[54]), "+f"(d[55]),
      "+f"(d[56]), "+f"(d[57]), "+f"(d[58]), "+f"(d[59]), "+f"(d[60]), "+f"(d[61]), "+f"(d[62]), "+f"(d[63]),
      "+f"(d[64]), "+f"(d[65]), "+f"(d[66]), "+f"(d[67]), "+f"(d[68]), "+f"(d[69]), "+f"(d[70]), "+f"(d[71]),
      "+f"(d[72]), "+f"(d[73]), "+f"(d[74]), "+f"(d[75]), "+f"(d[76]), "+f"(d[77]), "+f"(d[78]), "+f"(d[79]),
      "+f"(d[80]), "+f"(d[81]), "+f"(d[82]), "+f"(d[83]), "+f"(d[84]), "+f"(d[85]), "+f"(d[86]), "+f"(d[87]),
      "+f"(d[88]), "+f"(d[89]), "+f"(d[90]), "+f"(d[91]), "+f"(d[92]), "+f"(d[93]), "+f"(d[94]), "+f"(d[95]),
      "+f"(d[96]), "+f"(d[97]), "+f"(d[98]), "+f"(d[99]), "+f"(d[100]), "+f"(d[101]), "+f"(d[102]), "+f"(d[103]),
      "+f"(d[104]), "+f"(d[105]), "+f"(d[106]), "+f"(d[107]), "+f"(d[108]), "+f"(d[109]), "+f"(d[110]), "+f"(d[111]),
      "+f"(d[112]), "+f"(d[113]), "+f"(d[114]), "+f"(d[115]), "+f"(d[116]), "+f"(d[117]), "+f"(d[118]), "+f"(d[119]),
      "+f"(d[120]), "+f"(d[121]), "+f"(d[122]), "+f"(d[123]), "+f"(d[124]), "+f"(d[125]), "+f"(d[126]), "+f"(d[127])
    : "r"(a[0]), "r"(a[1]), "r"(a[2]), "r"(a[3]), "l"(db), "r"(sd));
}

__device__ __forceinline__ void ln_finish(float mean, float var, float& mb, float& rinv) {
  mb = round_bf16(mean);
  float sd;
  asm("sqrt.approx.ftz.f32 %0, %1;" : "=f"(sd) : "f"(round_bf16(round_bf16(var) + 1e-5f)));
  asm("rcp.approx.ftz.f32 %0, %1;" : "=f"(rinv) : "f"(round_bf16(sd)));
}
__device__ __forceinline__ uint32_t sum4(uint32_t a, uint32_t b, uint32_t c, uint32_t d) {
  return pack_bf16((bf_lo(a) + bf_lo(b)) + (bf_lo(c) + bf_lo(d)), (bf_hi(a) + bf_hi(b)) + (bf_hi(c) + bf_hi(d)));
}
struct Ring {
  uint32_t s, ph;
  __device__ __forceinline__ void next() { if (++s == NSTAGE) { s = 0; ph ^= 1; } }
};

__device__ __forceinline__ void conv_lda(uint32_t* a, int j, uint32_t base, bool on) {
  asm volatile("{ .reg .pred p; setp.ne.u32 p, %3, 0;\n @p ld.shared.u32 %0, [%2];\n @p ld.shared.u32 %1, [%2 + 128]; }"
               : "+r"(a[2 * j]), "+r"(a[2 * j + 1]) : "r"(base + (j >> 1) * 256 + (j & 1) * 16), "r"((uint32_t)on) : "memory");
}
__device__ __forceinline__ void conv_mma(float* acc, const uint32_t* a, uint64_t db) {
  wgmma_rs_n256(acc, a, db, 0);
  wgmma_rs_n240(acc, a + 4, db + 16, 1);
  wgmma_rs_n224(acc, a + 8, db + 32, 1);
  wgmma_rs_n208(acc, a + 12, db + 48, 1);
  wgmma_rs_n192(acc, a + 16, db + 64, 1);
  wgmma_rs_n176(acc, a + 20, db + 80, 1);
  wgmma_rs_n160(acc, a + 24, db + 96, 1);
  wgmma_rs_n144(acc, a + 28, db + 112, 1);
  wgmma_rs_n128(acc, a + 32, db + 128, 1);
  wgmma_rs_n112(acc, a + 36, db + 144, 1);
  wgmma_rs_n96(acc, a + 40, db + 160, 1);
  wgmma_rs_n80(acc, a + 44, db + 176, 1);
  wgmma_rs_n64(acc, a + 48, db + 192, 1);
  wgmma_rs_n48(acc, a + 52, db + 208, 1);
  wgmma_rs_n32(acc, a + 56, db + 224, 1);
  wgmma_rs_n16(acc, a + 60, db + 240, 1);
}
__device__ __forceinline__ uint32_t conv_part(const float* acc, int j) {
  const int q = 31 - j;
  return q == 31 ? pack_bf16(acc[124], acc[125]) : pack_bf16(acc[4 * q] + acc[(4 * q + 6) & 127], acc[4 * q + 1] + acc[(4 * q + 7) & 127]);
}
__device__ __forceinline__ uint4 conv_sum(const uint4* p) {
  return make_uint4(sum4(p[0].x, p[1].x, p[2].x, p[3].x), sum4(p[0].y, p[1].y, p[2].y, p[3].y), sum4(p[0].z, p[1].z, p[2].z, p[3].z),
                    sum4(p[0].w, p[1].w, p[2].w, p[3].w));
}
template <int NV> __device__ __forceinline__ void gelu_stage(float* acc, const float* hb, uint32_t sa, int passes) {
#pragma unroll
  for (int i = 0; i < NV; i++) acc[i] = fmaf(acc[i], 0.5f, hb[(i >> 1) & 1]);
#pragma unroll 1
  for (; passes > 0; passes--, sa += NV * 256) {
#pragma unroll
    for (int i = 0; i < NV; i += 8)
      stsm4t(sa + i * 256, pack_bf16(gelu_half(acc[i]), gelu_half(acc[i + 1])), pack_bf16(gelu_half(acc[i + 2]), gelu_half(acc[i + 3])),
             pack_bf16(gelu_half(acc[i + 4]), gelu_half(acc[i + 5])), pack_bf16(gelu_half(acc[i + 6]), gelu_half(acc[i + 7])));
#pragma unroll
    for (int i = 0; i < NV; i++) acc[i] = fmaf(acc[NV + i], 0.5f, hb[2 + ((i >> 1) & 1)]);
  }
}

__global__ void __cluster_dims__(2, 1, 1) __launch_bounds__(384, 1) fused_kernel(const __grid_constant__ Hot H, const __grid_constant__ Params P) {
  extern __shared__ __align__(1024) uint8_t smem_raw[];
  const uint32_t t0 = clk();
  const uint32_t sb = smem_u32(smem_raw);
  const int tid = threadIdx.x, lane = tid & 31;
  const int bid = blockIdx.x, rank = bid & 1;
  const Role& R = P.role[bid];
  Scratch* const S = H.S;
  uint32_t xr[18];
  const int row = bid * 16 + (tid >> 4);
  if (tid < 256 && bid < 128) {
    const char* src = reinterpret_cast<const char*>(H.x) + row * (D_ * 2) + (lane & 15) * 8;
#pragma unroll
    for (int j = 0; j < 9; j++) asm volatile("ld.global.nc.v2.u32 {%0,%1}, [%2];" : "=r"(xr[2 * j]), "=r"(xr[2 * j + 1]) : "l"(src + 128 * j));
  }
  const int warp = __shfl_sync(0xffffffffu, tid >> 5, 0);

  if (warp >= 8) {
    const bool one = elect_one();
    if (warp == 8 && one) {
#pragma unroll
      for (int b = B_FULL; b <= B_DONE; b += 8) mbar_init(sb + b, b < B_EMPTY ? 1 : b < B_CEMPTY ? 2 : b < B_G1DONE ? 4 : 8);
      asm volatile("fence.mbarrier_init.release.cluster;" ::: "memory");
    }
    __syncwarp();
    asm volatile("barrier.cluster.arrive.relaxed.aligned;" ::: "memory");
    asm volatile("setmaxnreg.dec.sync.aligned.u32 56;");
    asm volatile("barrier.cluster.wait.aligned;" ::: "memory");
    const bool left = R.at == 15;
    if (warp == 8) {
      const uint32_t ep = ldg32(S->cnt + C_EPOCH * 32);
      if (one) {
#pragma unroll 1
        for (int i = 0; i < 11; i++) asm volatile("prefetch.tensormap [%0];" :: "l"(&P.m_w1 + i) : "memory");
      }
      __syncwarp();
      if (bid < 128) bar_sync(2, 288);
      if (one) {
        TLREC(31);
        signal(S, C_H, EPOCH / 132);
        TLREC(1);
        const uint32_t boff = left ? 24576 : 16384;
        Ring r{0, 1};
#pragma unroll 1
        for (int kb = -NW0; kb < G1_KB; kb++) {
          const int kw = kb < 0 ? kb + NW0 : kb, s = kb < 0 ? kw : r.s;
          const uint32_t fb = sb + B_FULL + 8 * s;
          if (kb < 0 || kb >= NW0) {
            mbar_wait(sb + B_EMPTY + 8 * s, r.ph);
            mbar_expect_tx(fb, G1_BYTES);
            tma3d(sb + s * SLOT, &P.m_w1 + left, 0, kw * 64, R.fg, fb);
            if (kb < 0) continue;
          }
          if (kb == 0) { await(S, C_H, ep); fence_async_global(); TLREC(2); }
          bulk_load(sb + s * SLOT + boff, S->h + (kb * 18 + R.at) * 2048, G1_BYTES - boff, fb);
          if (kb == NSTAGE - 1) {
            mbar_arrive(sb + B_GO);
            mbar_expect_tx(sb + B_MISC, boff / 64 + 1152);
            bulk_load(sb + SM_B1, H.b1 + R.fg * 64, boff / 64, sb + B_MISC);
            bulk_load(sb + SM_D, H.ssm_D, 1152, sb + B_MISC);
          }
          r.next();
        }
        await(S, C_KV, ep);
        fence_async_global();
#pragma unroll 1
        for (int i = 0; i < R.ncv; i++) {
          if (i == 2) {
            if (R.sg >= 0) {
#pragma unroll 1
              for (int s = 2; s < NSTAGE; s++) {
                mbar_wait(sb + B_EMPTY + 8 * s, ((G1_KB / NSTAGE) - 1) & 1);
                mbar_expect_tx(sb + B_FULL + 8 * s, G2_BYTES);
                tma3d(sb + s * SLOT, &P.m_w2, 0, (rank * G2_KB + s - 2) * 64, R.sg, sb + B_FULL + 8 * s);
              }
            }
            mbar_wait(sb + B_G1DONE, 0);
          }
          const uint32_t slot = sb + cv_slot(i), b8 = sb + 8 * (i & 3);
          mbar_wait(b8 + B_CEMPTY, ((i >> 2) & 1) ^ 1);
          sts128(slot + CV_KOFF, 0, 0, 0, 0); sts128(slot + CV_KOFF + 16, 0, 0, 0, 0);
          mbar_expect_tx(b8 + B_KFULL, 4096);
          bulk_load(slot + CV_KOFF + 32, H.ssm_k + (R.ch + i) * S_, 4096, b8 + B_KFULL);
          mbar_expect_tx(b8 + B_UFULL, 8192);
          bulk_load(slot, S->ub + (R.ch + i) * 4096, 8192, b8 + B_UFULL);
        }
        if (R.sg >= 0) {
          mbar_expect_tx(sb + B_XY, 2 * 18432 + 2048 + 256);
          mbar_expect_tx(sb + B_XFULL, 9216);
          mbar_expect_tx(sb + B_XFULL + 8, 9216);
          await(S, C_U, ep);
          fence_async_global();
          TLREC(6);
#pragma unroll 1
          for (int kb = 0; kb < G2_KB; kb++, r.next()) {
            const int k0 = (rank * G2_KB + kb) * 64;
            const uint32_t fb = sb + B_FULL + 8 * r.s, slot = sb + r.s * SLOT;
            if (kb >= NSTAGE - 2) {
              mbar_wait(sb + B_EMPTY + 8 * r.s, r.ph);
              if (kb == NSTAGE) asm volatile("red.relaxed.gpu.global.add.u32 [%0], %1;" :: "l"(S->cnt + C_SYNC * 32), "r"(EPOCH / 128) : "memory");
              if (kb == SYNCKB) await(S, C_SYNC, ep);
              mbar_expect_tx(fb, G2_BYTES);
              tma3d(slot, &P.m_w2, 0, k0, R.sg, fb);
            }
            tma2d(slot + 16384, &P.m_uld, k0, R.ds * 8, fb);
            tma2d(slot + 16384 + 9216, &P.m_uld, k0, R.dk * 8, fb);
            const uint32_t nx = kb - 8;
            if (nx < 8) tma2d(sb + SM_CV + nx * 2304, &P.m_x, R.dk * 8, R.sg * 64 + nx * 16, sb + B_XY);
          }
          bulk_load(sb + SM_ST, S->stats + R.sg * 64, 2048, sb + B_XY);
          bulk_load(sb + SM_B2, P.b2 + R.sg * 64, 256, sb + B_XY);
          await(S, C_Y, ep);
          fence_async_global();
          TLREC(19);
          tma3d(sb + SM_DED, &P.m_y, 0, R.dk * 8, R.sg, sb + B_XY);
          if (bid == 0) signal(S, C_EPOCH, EPOCH);
        }
      }
    } else {
      if (bid < 128) {
        const int ht = tid - 288, hf = ht >= 48, pr = ht - 48 * hf;
        const uint32_t st = sb + SM_DED + (1 - hf) * 1536 + pr * 32;
        mbar_wait_guarded(sb + B_GO, t0);
#pragma unroll 1
        for (int r = -3; r < KV_ROUNDS; r++) {
          const int q = (r + 3) % 3;
          const uint32_t in = sb + SM_CV + q * 7936, fb = sb + B_UFULL + 8 * q;
          if (r >= 0) {
            mbar_wait_guarded(fb, t0, r >= 3);
            uint32_t kk[12], vv[9];
#pragma unroll
            for (int j = 0; j < 12; j++) kk[j] = lds32(in + hf * 1536 + pr * 4 + j * 192);
#pragma unroll
            for (int j = 0; j < 9; j++) vv[j] = lds32(in + 3840 + hf * 1536 + pr * 4 + j * 192);
            const uint4 w = lds128(in + 7168 + pr * 16);
            const uint32_t w0 = __byte_perm(w.x, w.z, 0x5410), w1 = __byte_perm(w.x, w.z, 0x7632);
            const uint32_t w2 = __byte_perm(w.y, w.w, 0x5410), w3 = __byte_perm(w.y, w.w, 0x7632);
#pragma unroll
            for (int j = 0; j < 9; j++)
              vv[j] = bmul2(badd2(badd2(badd2(bmul2(kk[j], w3), bmul2(kk[j + 1], w2)), bmul2(kk[j + 2], w1)), bmul2(kk[j + 3], w0)), vv[j]);
#pragma unroll
            for (int c = 0; c < 2; c++)
#pragma unroll
              for (int pi = 0; pi < 2; pi++) {
                const uint32_t sel = c ? 0x7632 : 0x5410;
                sts128(st + q * 6144 + c * 3072 + pi * 16, __byte_perm(vv[7 + pi], vv[6 + pi], sel), __byte_perm(vv[5 + pi], vv[4 + pi], sel),
                       __byte_perm(vv[3 + pi], vv[2 + pi], sel), __byte_perm(vv[1 + pi], vv[pi], sel));
              }
            bar_sync(1, 96);
            if (warp == 9 && one) {
              bulk_wait_all();
              fence_async_smem();
              tma3d_store(&P.m_ub, sb + SM_DED + q * 6144, 16 * (127 - bid), r * 48, 0);
              bulk_commit();
            }
          }
          if (warp == 10 && one && r < KV_ROUNDS - 3) {
            if (r < 0) __nanosleep(KVD);
            mbar_expect_tx(fb, 3840 + 3264 + 768);
            tma2d(in, &P.m_k, (r + 3) * 96, bid * 16 - 4, fb);
            tma2d(in + 3840, &P.m_v, (r + 3) * 96, bid * 16 - 1, fb);
            bulk_load(in + 7168, H.shift_k + (r + 3) * 384, 768, fb);
          }
          __syncwarp();
        }
      }
      if (one) {
        if (warp < 11) {
          const int wg = warp - 9;
          if (!wg) {
            bulk_wait_all();
            mbar_arrive(sb + B_KVDONE);
            signal(S, C_KV, EPOCH / 132);
            TLREC(27);
          }
          mbar_wait_guarded(sb + B_STG + 8 * wg, t0);
          fence_async_smem();
          TLREC(13 + wg);
#pragma unroll 1
          for (int j = 0; j < (left ? 3 + 3 * wg : 5); j++) {
            const int hi = left && j >= 3;
            tma2d_store(&P.m_ust, sb + (wg ? SM_ST1 : SM_DED) + j * 4096, (R.fg + wg + hi) * 64, (R.at + j - 3 * hi) * 32);
          }
          bulk_commit();
          bulk_wait_all();
          mbar_arrive(sb + B_SFREE + 8 * wg);
          signal(S, C_U, EPOCH / 264);
          TLREC(15 + wg);
        } else {
          mbar_wait_guarded(sb + B_YDONE, t0);
          signal(S, C_Y, EPOCH / 132);
          if (R.sg >= 0) mbar_wait_guarded(sb + B_DONE, t0);
        }
      }
    }
    TLEND();
  } else {
    asm volatile("barrier.cluster.arrive.relaxed.aligned;" ::: "memory");
    if (bid < 128) {
      float c[36], s[4];
#pragma unroll
      for (int i = 0; i < 18; i++) { c[2 * i] = bf_lo(xr[i]); c[2 * i + 1] = bf_hi(xr[i]); }
#pragma unroll
      for (int i = 0; i < 36; i++) s[i & 3] = i < 4 ? c[i] : s[i & 3] + c[i];
      const float ml = ((s[0] + s[1]) + (s[2] + s[3])) * (1.0f / 36.0f);
#pragma unroll
      for (int i = 0; i < 36; i++) { c[i] -= ml; s[i & 3] = i < 4 ? c[i] * c[i] : fmaf(c[i], c[i], s[i & 3]); }
      float m = ml, q = (s[0] + s[1]) + (s[2] + s[3]), n2 = 18.f;
#pragma unroll
      for (int o = 1; o < 16; o <<= 1) {
        const float mo = __shfl_xor_sync(0xffffffffu, m, o), qo = __shfl_xor_sync(0xffffffffu, q, o);
        const float dl = m - mo;
        q = fmaf(dl * dl, n2, q + qo);
        m = fmaf(dl, -0.5f, m);
        n2 *= 2.f;
      }
      const float var = q * (1.0f / 576.0f);
      float mb, rinv, mb2, rinv2;
      ln_finish(m, var, mb, rinv);
      ln_finish((m - mb) * rinv, var * rinv * rinv, mb2, rinv2);
      const float ca = rinv * rinv2, cb = fmaf(ml - mb, rinv, -mb2) * rinv2;
      uint2* dst = reinterpret_cast<uint2*>(S->h) + ((row >> 6) * 18 + ((lane >> 3) & 1)) * 512 + (row & 63) * 8 + ((lane & 7) ^ (row & 6));
#pragma unroll
      for (int j = 0; j < 9; j++)
        dst[1024 * j] = make_uint2(pack_bf16(fmaf(c[4 * j], ca, cb), fmaf(c[4 * j + 1], ca, cb)), pack_bf16(fmaf(c[4 * j + 2], ca, cb), fmaf(c[4 * j + 3], ca, cb)));
      const uint32_t rh = pack_bf16(rinv, rinv);
      if (!(lane & 15)) S->stats[row] = make_uint4(pack_bf16(mb, mb), rh, pack_bf16(rinv - bf_lo(rh), rinv - bf_lo(rh)), 0);
      __syncwarp();
      bar_arrive(2, 288);
    }
    asm volatile("setmaxnreg.inc.sync.aligned.u32 224;");
    asm volatile("barrier.cluster.wait.aligned;" ::: "memory");
    const int wg = warp >> 2, w = warp & 3, g = lane >> 2, t = lane & 3, wtid = tid & 127;
    const bool elect = wtid == 0;
    const uint64_t da0 = make_desc(sb + wg * 8192, 8192, 1024, 1);
    const uint32_t swz = ((lane >> 4) * 8 + (lane & 7)) * 128 + (((2 * w + ((lane >> 3) & 1)) ^ (lane & 7)) << 4);
    const uint32_t stg = sb + (wg ? SM_ST1 : SM_DED);
    {
      auto mainloop = [&](auto&& mma) {
        Ring r{0, 0};
        uint32_t rel = 0;
#pragma unroll 1
        for (int kb = 0; kb < G1_KB; kb++, r.next()) {
          if (kb == G1_KB - G1_TAIL && wg) {
            wg_wait<0>();
            if (elect) mbar_arrive(rel);
            rel = 0;
            bar_sync(5, 256);
          }
          mbar_wait(sb + B_FULL + 8 * r.s, r.ph);
          if (kb == 0 && warp == 0) TLREC(3);
          wg_fence();
          mma(r.s * (SLOT >> 4), kb);
          wg_commit();
          if (kb == G1_KB - 1) break;
          wg_wait<1>();
          if (elect && rel) mbar_arrive(rel);
          rel = sb + B_EMPTY + 8 * r.s;
        }
        bar_arrive(5, 256);
        wg_wait<0>();
      };
      float hb[4];
      auto staged = [&](int second) {
        if (!w) TLREC(4 + wg);
        if (lane == 0) mbar_arrive(sb + B_G1DONE);
        mbar_wait(sb + B_MISC, 0);
#pragma unroll
        for (int i = 0; i < 4; i++) hb[i] = 0.5f * bf_lo(lds16(sb + SM_B1 + (warp * 16 + g + (i & 1) * 8 + (i >> 1) * second) * 2));
        mbar_wait(sb + (wg ? B_G1DONE : B_KVDONE), 0);
      };
      if (R.at != 15) {
        const uint64_t db0 = make_desc(sb + 16384, 4096, 512, 2);
        float acc[80];
        mainloop([&](uint32_t o, int kb) {
          wgmma_ss_n160_t11(acc, da0 + o, db0 + o, kb);
#pragma unroll
          for (int k = 1; k < 4; k++) wgmma_ss_n160_t11(acc, da0 + o + k * 128, db0 + o + k * 64, 1);
        });
        pin_regs<80>(acc);
        staged(0);
        gelu_stage<40>(acc, hb, stg + swz, 2);
      } else {
        const uint64_t db0 = make_desc(sb + 24576, 4096, 512, 2);
        float acc[96];
        auto block = [&](float* d, uint64_t da, uint64_t db, int kb) {
          wgmma_ss_n96_t11(d, da, db, kb);
#pragma unroll
          for (int k = 1; k < 4; k++) wgmma_ss_n96_t11(d, da + k * 128, db + k * 64, 1);
        };
        if (wg) mainloop([&](uint32_t o, int kb) { block(acc, da0 + o, db0 + o, kb); block(acc + 48, da0 + o + 512, db0 + o, kb); });
        else mainloop([&](uint32_t o, int kb) { block(acc, da0 + o, db0 + o, kb); });
        pin_regs<96>(acc);
        staged(64);
        gelu_stage<48>(acc, hb, stg + swz, 1 + wg);
      }
      __syncwarp();
      if (lane == 0) mbar_arrive(sb + B_STG + 8 * wg);
    }
    {
      const uint32_t ka0 = CV_KOFF + (8 * w + g + t + 1) * 4, wr = stg + w * CV_REDW + (8 * (3 - t + w) + g) * 4;
      uint32_t a[64];
      mbar_wait(sb + B_KFULL + 8 * wg, 0);
#pragma unroll
      for (int j = 0; j < 32; j++) conv_lda(a, j, sb + SM_CV + wg * CV_SLOT + ka0, true);
#pragma unroll 1
      for (int i = wg; i < R.ncv; i += 2) {
        const bool more = i + 2 < R.ncv;
        const uint32_t dd = lds16(sb + SM_D + (R.ch + i) * 2);
        a[0] = badd2(a[0], ka0 == CV_KOFF + 32 ? dd : 0); a[2] = badd2(a[2], ka0 == CV_KOFF + 16 ? dd : 0);
        float acc[128];
        mbar_wait(sb + B_UFULL + 8 * (i & 3), (i >> 2) & 1);
        bar_sync(5 + wg, 256);
        if (!w && i < 4) TLREC(22 + i);
        wg_fence();
        conv_mma(acc, a, make_desc(sb + cv_slot(i), 4096, 128, 0));
        wg_commit();
        if (i + 1 < R.ncv) bar_arrive(5 + (wg ^ 1), 256);
        mbar_wait(sb + B_SFREE + 8 * wg, 0);
        if (lane < 8 * w) sts32(stg + w * CV_REDW + lane * 4, 0);
        if (more) mbar_wait(sb + B_KFULL + 8 * ((i + 2) & 3), ((i + 2) >> 2) & 1);
        if (i == 0 && !w) TLREC(7);
        wg_wait<0>();
        pin_regs<128>(acc);
        if (lane == 0) mbar_arrive(sb + B_CEMPTY + 8 * (i & 3));
        const uint32_t ka = sb + cv_slot(i + 2) + ka0;
#pragma unroll
        for (int j = 0; j < 32; j++) {
          if (j < 24) conv_lda(a, j, ka, more);
          sts32(wr + j * 128, conv_part(acc, j));
        }
        bar_sync(3 + wg, 128);
        uint4 p[2][4];
#pragma unroll
        for (int x = 0; x < 8; x++) p[x >> 2][x & 3] = lds128(stg + (x & 3) * CV_REDW + (wtid + 128 * (x >> 2)) * 16);
#pragma unroll
        for (int j = 24; j < 32; j++) conv_lda(a, j, ka, more);
        uint4* yo = reinterpret_cast<uint4*>(S->y + (R.ch + i) * S_) + wtid;
        yo[0] = conv_sum(p[0]); yo[128] = conv_sum(p[1]);
      }
      fence_async_smem();
      bar_sync(3 + wg, 128);
      if (elect) { mbar_arrive(sb + B_EMPTY); mbar_arrive(sb + B_EMPTY + 8); }
      if (lane == 0) mbar_arrive(sb + B_YDONE);
      if (!w) TLREC(20 + wg);
    }
    if (R.sg >= 0) {
      const int srow = R.sg * 64 + warp * 16;
      const uint64_t db0 = make_desc(sb + 16384, 16, 1024, 1);
      const uint32_t xo = sb + SM_CV + warp * 2304, xa = xo + (lane & 15) * 144;
      float acc[72];
      Ring r{G1_KB % NSTAGE, (G1_KB / NSTAGE) & 1};
      uint32_t rel = 0;
#pragma unroll 1
      for (int kb = 0; kb < G2_KB; kb++, r.next()) {
        if (kb == G2_KB - G2_TAIL && wg) {
          wg_wait<0>();
          if (elect) mbar_arrive_remote(rel);
          rel = 0;
          bar_sync(7, 256);
        }
        mbar_wait(sb + B_FULL + 8 * r.s, r.ph);
        if (kb == 0 && !w) TLREC(17 + wg);
        if (kb == 8 && warp == 0) TLREC(26);
        if (kb == 20 && warp == 0) TLREC(8);
        if (kb == 27 && warp == 0) TLREC(30);
        const uint64_t da = da0 + r.s * (SLOT >> 4), db = db0 + r.s * (SLOT >> 4);
        wg_fence();
        wgmma_ss_n144_t10(acc, da, db, kb);
#pragma unroll
        for (int k = 1; k < 4; k++) wgmma_ss_n144_t10(acc, da + k * 128, db + k * 2, 1);
        wg_commit();
        if (kb == G2_KB - 1) break;
        wg_wait<1>();
        if (elect && rel) mbar_arrive_remote(rel);
        rel = kb == G2_KB - NSTAGE ? mapa(sb + B_XRDY, rank ^ 1) : sb + B_EMPTY + 8 * r.s;
      }
      if (!wg) bar_arrive(7, 256);
      const uint32_t xz = sb + XSLOT * SLOT + wg * 10240 + wtid * 16;
      const uint32_t rz = mapa(xz, rank ^ 1), rb = mapa(sb + B_XFULL + 8 * wg, rank ^ 1);
      mbar_wait(sb + B_XRDY, 0);
      wg_wait<0>();
      pin_regs<72>(acc);
      if (!w) TLREC(28 + wg);
#pragma unroll
      for (int i = 0; i < 32; i += 8)
        asm volatile("st.async.weak.shared::cluster.mbarrier::complete_tx::bytes.v4.b32 [%0], {%1,%2,%3,%4}, [%5];"
                     :: "r"(rz + i * 256), "r"(pack_bf16(acc[i], acc[i + 1])), "r"(pack_bf16(acc[i + 2], acc[i + 3])),
                        "r"(pack_bf16(acc[i + 4], acc[i + 5])), "r"(pack_bf16(acc[i + 6], acc[i + 7])), "r"(rb) : "memory");
      asm volatile("st.async.weak.shared::cluster.mbarrier::complete_tx::bytes.v2.b32 [%0], {%1,%2}, [%3];"
                   :: "r"(rz + 8192), "r"(pack_bf16(acc[32], acc[33])), "r"(pack_bf16(acc[34], acc[35])), "r"(rb) : "memory");
      uint32_t xx[18], ss[18];
      mbar_wait(sb + B_XY, 0);
      {
        const uint32_t ya = sb + SM_DED + wg * 9216 + swz;
        const uint4 st0 = lds128(sb + SM_ST + (warp * 16 + g) * 16), st1 = lds128(sb + SM_ST + (warp * 16 + g + 8) * 16);
        const float hb0 = 0.5f * bf_lo(lds16(sb + SM_B2 + (warp * 16 + g) * 2)), hb1 = 0.5f * bf_lo(lds16(sb + SM_B2 + (warp * 16 + g + 8) * 2));
#pragma unroll
        for (int q = 0; q < 8; q += 2) { ldsm4(xx + 2 * q, xa + (lane >> 4) * 16 + q * 16); ldsm4t(ss + 2 * q, ya + q * 1024); }
        ldsm2(xx + 16, xa + 128);
        ldsm2t(ss + 16, ya + 8 * 1024);
#pragma unroll
        for (int i = 0; i < 18; i++) {
          const uint4& st = (i & 1) ? st1 : st0;
          const uint32_t c = bsub2(xx[i], st.x);
          ss[i] = bmul2(bfma2(c, st.y, bmul2(c, st.z)), ss[i]);
        }
#pragma unroll
        for (int i = 36; i < 72; i++) acc[i] = fmaf(acc[i], 0.5f, (i & 2) ? hb1 : hb0);
      }
      mbar_wait_cluster(sb + B_XFULL + 8 * wg, 0);
      if (!w) TLREC(9 + wg);
#pragma unroll
      for (int q = 0; q < 5; q++) {
        const uint4 v = lds128(xz + q * 2048);
        const uint32_t pv[4] = {v.x, v.y, v.z, v.w};
#pragma unroll
        for (int i = 4 * q; i < 4 * q + 4 && i < 18; i++)
          xx[i] = bfma2(ss[i], pack_bf16(silu_half(fmaf(bf_lo(pv[i & 3]), 0.5f, acc[36 + 2 * i])), silu_half(fmaf(bf_hi(pv[i & 3]), 0.5f, acc[37 + 2 * i]))), xx[i]);
        if (q < 4) stsm4(xa + (lane >> 4) * 16 + q * 32, xx[4 * q], xx[4 * q + 1], xx[4 * q + 2], xx[4 * q + 3]);
        else stsm2(xa + 128, xx[16], xx[17]);
      }
      __syncwarp();
      if (elect_one()) {
        fence_async_smem();
        tma2d_store(&P.m_out, xo, R.dk * 8, srow);
        bulk_commit();
        mbar_arrive(sb + B_DONE);
        bulk_wait_read();
      }
      if (!w) TLREC(11 + wg);
    }
    TLEND();
  }
}

typedef CUresult (*EncodeFn)(CUtensorMap*, CUtensorMapDataType, cuuint32_t, void*, const cuuint64_t*, const cuuint64_t*, const cuuint32_t*,
                             const cuuint32_t*, CUtensorMapInterleave, CUtensorMapSwizzle, CUtensorMapL2promotion, CUtensorMapFloatOOBfill);

void make_map(EncodeFn fn, CUtensorMap* m, const void* ptr, int rank, const cuuint64_t* dims, const cuuint64_t* strides, const cuuint32_t* box,
              CUtensorMapSwizzle sw) {
  const cuuint32_t es[3] = {1, 1, 1};
  fn(m, CU_TENSOR_MAP_DATA_TYPE_BFLOAT16, rank, const_cast<void*>(ptr), dims, strides, box, es, CU_TENSOR_MAP_INTERLEAVE_NONE, sw,
     CU_TENSOR_MAP_L2_PROMOTION_L2_256B, CU_TENSOR_MAP_FLOAT_OOB_FILL_NONE);
}

void make_roles(Role* R) {
  int nl = 0, ch = 0;
  for (int gi = 0; gi < 8; gi++)
    for (int b = 0; b < 132; b++) {
      const int c = b >> 1, rank = b & 1;
      int g, idx;
      if (c < 4) { g = 0; idx = 4 + c; }
      else if (c < 36) { g = (c - 4) & 7; idx = (c - 4) >> 3; }
      else if (c < 64) { g = 1 + (c - 36) % 7; idx = 4 + (c - 36) / 7; }
      else { g = c - 58; idx = 8; }
      if (g != gi) continue;
      Role& r = R[b];
      r.sg = (int8_t)(idx < 8 ? 2 * (2 * g + (idx >> 2)) : -1);
      r.dk = (int8_t)((idx & 3) * 18 + rank * 9);
      r.ds = (int8_t)((idx & 3) * 18 + (rank ^ 1) * 9);
      if (idx < (g < 2 ? 6 : 7)) {
        const int c1 = (g < 2 ? 6 * g : 7 * g - 2) + idx;
        r.fg = (int8_t)((2 * (c1 / 3) + rank) * 2); r.at = (int8_t)(c1 % 3 * 5); r.ncv = NCV_REG;
      } else {
        r.fg = (int8_t)(3 * nl++); r.at = 15; r.ncv = idx < 8 ? NCV_LEFT : NCV_LONG;
      }
      r.ch = (int16_t)ch;
      ch += r.ncv;
    }
}

}

extern "C" void kernel_launch(void* const* d_in, const int* in_sizes, int n_in, void* d_out, int out_size) {
  static Params P;
  static Hot H;
  static const void* cached[6] = {nullptr, nullptr, nullptr, nullptr, nullptr, nullptr};
  const void* now[6] = {d_in[0], d_in[1], d_in[2], d_in[7], d_in[9], d_out};
  bool same = true;
  for (int i = 0; i < 6; i++) { same = same && cached[i] == now[i]; cached[i] = now[i]; }
  if (!same) {
    void* fp = nullptr;
    cudaDriverEntryPointQueryResult qr;
    cudaGetDriverEntryPoint("cuTensorMapEncodeTiled", &fp, cudaEnableDefault, &qr);
    EncodeFn fn = (EncodeFn)fp;
    void* ps;
    cudaGetSymbolAddress(&ps, g_scratch);
    H.S = (Scratch*)ps;
    const void *pu = (char*)ps + offsetof(Scratch, u), *py = (char*)ps + offsetof(Scratch, y),
               *pb = (char*)ps + offsetof(Scratch, ub);
    { cuuint64_t d[3] = {64, S_, F_ / 64}, s[2] = {F_ * 2, 128}; cuuint32_t b[3] = {64, 64, 2}; make_map(fn, &P.m_w1, d_in[7], 3, d, s, b, CU_TENSOR_MAP_SWIZZLE_128B);
      b[2] = 3; make_map(fn, &P.m_w1l, d_in[7], 3, d, s, b, CU_TENSOR_MAP_SWIZZLE_128B); }
    { cuuint64_t d[2] = {F_, D_}, s[1] = {F_ * 2}; cuuint32_t b[2] = {64, 32}; make_map(fn, &P.m_ust, pu, 2, d, s, b, CU_TENSOR_MAP_SWIZZLE_128B); }
    { cuuint64_t d[3] = {64, F_, S_ / 64}, s[2] = {S_ * 2, 128}; cuuint32_t b[3] = {64, 64, 2}; make_map(fn, &P.m_w2, d_in[9], 3, d, s, b, CU_TENSOR_MAP_SWIZZLE_128B); }
    { cuuint64_t d[2] = {F_, D_}, s[1] = {F_ * 2}; cuuint32_t b[2] = {64, 72}; make_map(fn, &P.m_uld, pu, 2, d, s, b, CU_TENSOR_MAP_SWIZZLE_128B); }
    { cuuint64_t d[2] = {D_, S_}, s[1] = {D_ * 2}; cuuint32_t b[2] = {72, 16}; make_map(fn, &P.m_out, d_out, 2, d, s, b, CU_TENSOR_MAP_SWIZZLE_NONE);
      make_map(fn, &P.m_x, d_in[0], 2, d, s, b, CU_TENSOR_MAP_SWIZZLE_NONE);
      b[0] = 96; b[1] = 20; make_map(fn, &P.m_k, d_in[1], 2, d, s, b, CU_TENSOR_MAP_SWIZZLE_NONE);
      b[1] = 17; make_map(fn, &P.m_v, d_in[2], 2, d, s, b, CU_TENSOR_MAP_SWIZZLE_NONE); }
    { cuuint64_t d[3] = {64, D_, S_ / 64}, s[2] = {S_ * 2, 128}; cuuint32_t b[3] = {64, 72, 2}; make_map(fn, &P.m_y, py, 3, d, s, b, CU_TENSOR_MAP_SWIZZLE_128B); }
    { cuuint64_t d[3] = {2048, D_ / 2, 4}, s[2] = {16384, 4096}; cuuint32_t b[3] = {16, 48, 4}; make_map(fn, &P.m_ub, pb, 3, d, s, b, CU_TENSOR_MAP_SWIZZLE_NONE); }
    make_roles(P.role);
    cudaFuncSetAttribute(fused_kernel, cudaFuncAttributeMaxDynamicSharedMemorySize, SM_TOTAL);
  }
  H.x = (const __nv_bfloat16*)d_in[0];
  H.shift_k = (const __nv_bfloat16*)d_in[3]; H.ssm_k = (const __nv_bfloat16*)d_in[4]; H.ssm_D = (const __nv_bfloat16*)d_in[5];
  H.b1 = (const __nv_bfloat16*)d_in[8]; P.b2 = (const __nv_bfloat16*)d_in[10];
  fused_kernel<<<132, 384, SM_TOTAL>>>(H, P);
}
```

```cpp
#include <cuda_runtime.h>
#include <cuda.h>
#include <cuda_bf16.h>
#include <stddef.h>
#include <stdint.h>

namespace {

constexpr int S_ = 2048, D_ = 576, F_ = 4608;
constexpr int NSTAGE = 5, SLOT = 36864;
constexpr int G1_KB = 32, G2_KB = 36;
constexpr int G1_BYTES = 36864, G2_BYTES = 16384 + 18432;
#define NCV_LEFT 4
constexpr int NCV_REG = 4, NCV_LONG = (D_ - 108 * NCV_REG - 20 * NCV_LEFT) / 4;
static_assert(108 * NCV_REG + 20 * NCV_LEFT + 4 * NCV_LONG == D_, "conv split");
constexpr int KV_ROUNDS = 6;
constexpr int NWE = 0, NW0 = 1;
constexpr int G1_TAIL = 4, G2_TAIL = 3;
constexpr int SYNCKB = 7;
constexpr int KV0 = 5;

constexpr int CV_K = 4224, CV_REDW = 2112 * 2;
constexpr int SM_DED = NSTAGE * SLOT;
constexpr int SM_CV = SM_DED + 20480;
constexpr int SM_ST1 = 0;
constexpr int SM_ST = SM_CV + 18432, SM_B2 = SM_ST + 2048;
constexpr int SM_B1 = SM_CV + 2 * (8192 + CV_K), SM_D = SM_B1 + 384;
constexpr int SM_BAR = SM_D + 1152;
constexpr int SM_TOTAL = SM_BAR + 768;
static_assert(G1_KB % NSTAGE == 2, "slots 0 and 1 hold the last GEMM1 k-blocks and the last two of the first GEMM2 stages");
static_assert(NCV_REG % 4 == 0 && NCV_LEFT % 4 == 0 && NCV_LONG % 4 == 0, "the last two channels use buffers 2 and 3");
constexpr int XSLOT = (G1_KB + G2_KB) % NSTAGE;
__device__ __forceinline__ uint32_t cv_in(int i) { return (i & 2 ? SLOT : SM_CV) + (i & 1) * 8192; }
__device__ __forceinline__ uint32_t cv_taps(int i) { return (i & 2 ? SM_ST1 + 24576 : SM_CV + 16384) + (i & 1) * CV_K; }
constexpr int bar_at(int i) { return SM_BAR + 8 * i; }
constexpr int B_FULL = bar_at(0)  , B_KFULL = bar_at(5)  , B_UFULL = bar_at(9)  , B_KVDONE = bar_at(13), B_SFREE = bar_at(14)  ,
              B_XFULL = bar_at(16)  , B_XY = bar_at(18), B_MISC = bar_at(19),
              B_EMPTY = bar_at(21)  , B_XRDY = bar_at(26),
              B_CEMPTY = bar_at(27)  , B_STG = bar_at(31)  ,
              B_G1DONE = bar_at(33), B_YDONE = bar_at(34), B_DONE = bar_at(35);
constexpr int C_H = 0, C_KV = 1, C_U = 2, C_Y = 3, C_SYNC = 4, C_EPOCH = 5, C_COUNT = 6;
constexpr uint32_t EPOCH = 128 * 33;

struct Scratch {
  uint32_t cnt[C_COUNT * 32];
  alignas(1024) uint4 stats[S_];
  alignas(1024) __nv_bfloat16 h[S_ * D_];
  alignas(1024) __nv_bfloat16 ub[D_ * 4096];
  alignas(1024) __nv_bfloat16 y[D_ * S_];
  alignas(1024) __nv_bfloat16 u[D_ * F_];
};
__device__ Scratch g_scratch;

struct Hot {
  const __nv_bfloat16 *x, *shift_k, *ssm_k, *ssm_D, *b1;
  Scratch* S;
};
struct Role {
  int8_t fg;
  int8_t at;
  int8_t sg;
  int8_t dk, ds;
  int8_t ncv;
  int16_t ch;
};
struct Params {
  const __nv_bfloat16* b2;
  Role role[132];
  CUtensorMap m_w1, m_w1l, m_ust, m_w2, m_uld, m_out, m_x, m_y, m_k, m_v, m_ub;
};

#define TLREC(i) do { } while (0)
#define TLEND() do { } while (0)

__device__ __forceinline__ uint32_t smem_u32(const void* p) { return (uint32_t)__cvta_generic_to_shared(p); }
__device__ __forceinline__ void mbar_init(uint32_t bar, uint32_t cnt) { asm volatile("mbarrier.init.shared::cta.b64 [%0], %1;" :: "r"(bar), "r"(cnt) : "memory"); }
__device__ __forceinline__ void mbar_expect_tx(uint32_t bar, uint32_t bytes) { asm volatile("mbarrier.arrive.expect_tx.shared::cta.b64 _, [%0], %1;" :: "r"(bar), "r"(bytes) : "memory"); }
__device__ __forceinline__ void mbar_arrive(uint32_t bar) { asm volatile("mbarrier.arrive.shared::cta.b64 _, [%0];" :: "r"(bar) : "memory"); }
__device__ __forceinline__ uint32_t mapa(uint32_t addr, uint32_t cta) { uint32_t r; asm volatile("mapa.shared::cluster.u32 %0, %1, %2;" : "=r"(r) : "r"(addr), "r"(cta)); return r; }
__device__ __forceinline__ void mbar_arrive_remote(uint32_t rbar) { asm volatile("mbarrier.arrive.shared::cluster.b64 _, [%0];" :: "r"(rbar) : "memory"); }
__device__ __forceinline__ uint32_t clk() { uint32_t c; asm volatile("mov.u32 %0, %%clock;" : "=r"(c)); return c; }
__device__ __forceinline__ bool elect_one() {
  uint32_t p; asm volatile("{ .reg .pred p; elect.sync _|p, 0xffffffff; selp.u32 %0, 1, 0, p; }" : "=r"(p)); return p;
}
__device__ __forceinline__ void guard(uint32_t t0) { if ((int32_t)(clk() - t0) < 0) __trap(); }
__device__ __forceinline__ void mbar_wait(uint32_t bar, uint32_t parity) {
  asm volatile("{\n .reg .pred p;\n W_%=:\n mbarrier.try_wait.parity.shared::cta.b64 p, [%0], %1;\n @!p bra W_%=;\n }" :: "r"(bar), "r"(parity) : "memory");
}
__device__ __forceinline__ void mbar_wait_cluster(uint32_t bar, uint32_t parity) {
  asm volatile("{\n .reg .pred p;\n W_%=:\n mbarrier.try_wait.parity.acquire.cluster.shared::cta.b64 p, [%0], %1;\n @!p bra W_%=;\n }" :: "r"(bar), "r"(parity) : "memory");
}
__device__ __forceinline__ bool mbar_try(uint32_t bar, uint32_t parity) {
  uint32_t ok;
  asm volatile("{ .reg .pred p; mbarrier.try_wait.parity.shared::cta.b64 p, [%1], %2; selp.u32 %0, 1, 0, p; }" : "=r"(ok) : "r"(bar), "r"(parity) : "memory");
  return ok;
}
__device__ __forceinline__ bool mbar_test(uint32_t bar, uint32_t parity) {
  uint32_t ok;
  asm volatile("{ .reg .pred p; mbarrier.test_wait.parity.shared::cta.b64 p, [%1], %2; selp.u32 %0, 1, 0, p; }" : "=r"(ok) : "r"(bar), "r"(parity) : "memory");
  return ok;
}
__device__ __forceinline__ void mbar_wait_guarded(uint32_t bar, uint32_t t0, uint32_t parity = 0) { while (!mbar_try(bar, parity)) guard(t0); }
__device__ __forceinline__ void tma2d(uint32_t dst, const CUtensorMap* m, int c0, int c1, uint32_t bar) {
  asm volatile("cp.async.bulk.tensor.2d.shared::cluster.global.mbarrier::complete_tx::bytes [%0], [%1, {%3, %4}], [%2];"
               :: "r"(dst), "l"(m), "r"(bar), "r"(c0), "r"(c1) : "memory");
}
__device__ __forceinline__ void tma3d(uint32_t dst, const CUtensorMap* m, int c0, int c1, int c2, uint32_t bar) {
  asm volatile("cp.async.bulk.tensor.3d.shared::cluster.global.mbarrier::complete_tx::bytes [%0], [%1, {%3, %4, %5}], [%2];"
               :: "r"(dst), "l"(m), "r"(bar), "r"(c0), "r"(c1), "r"(c2) : "memory");
}
__device__ __forceinline__ void tma2d_store(const CUtensorMap* m, uint32_t src, int c0, int c1) {
  asm volatile("cp.async.bulk.tensor.2d.global.shared::cta.bulk_group [%0, {%2, %3}], [%1];" :: "l"(m), "r"(src), "r"(c0), "r"(c1) : "memory");
}
__device__ __forceinline__ void bulk_load(uint32_t dst, const void* src, uint32_t bytes, uint32_t bar) {
  asm volatile("cp.async.bulk.shared::cluster.global.mbarrier::complete_tx::bytes [%0], [%1], %2, [%3];" :: "r"(dst), "l"(src), "r"(bytes), "r"(bar) : "memory");
}
__device__ __forceinline__ void tma3d_store(const CUtensorMap* m, uint32_t src, int c0, int c1, int c2) {
  asm volatile("cp.async.bulk.tensor.3d.global.shared::cta.bulk_group [%0, {%2, %3, %4}], [%1];" :: "l"(m), "r"(src), "r"(c0), "r"(c1), "r"(c2) : "memory");
}
__device__ __forceinline__ void bulk_commit() { asm volatile("cp.async.bulk.commit_group;" ::: "memory"); }
__device__ __forceinline__ void bulk_wait_all() { asm volatile("cp.async.bulk.wait_group 0;" ::: "memory"); }
__device__ __forceinline__ void bulk_wait_read() { asm volatile("cp.async.bulk.wait_group.read 0;" ::: "memory"); }
__device__ __forceinline__ void fence_async_smem() { asm volatile("fence.proxy.async.shared::cta;" ::: "memory"); }
__device__ __forceinline__ void fence_async_global() { asm volatile("fence.proxy.async.global;" ::: "memory"); }
__device__ __forceinline__ uint32_t ld_cnt(Scratch* S, int c) { uint32_t v; asm volatile("ld.relaxed.gpu.global.u32 %0, [%1];" : "=r"(v) : "l"(S->cnt + c * 32) : "memory"); return v; }
__device__ __forceinline__ void signal(Scratch* S, int c, uint32_t inc) { asm volatile("red.release.gpu.global.add.u32 [%0], %1;" :: "l"(S->cnt + c * 32), "r"(inc) : "memory"); }
__device__ __forceinline__ bool reached(Scratch* S, int c, uint32_t ep) { return ld_cnt(S, c) - ep >= EPOCH; }
__device__ __forceinline__ void await(Scratch* S, int c, uint32_t ep) { while (!reached(S, c, ep)) { } }
__device__ __forceinline__ void bar_sync(int id, int n) { asm volatile("bar.sync %0, %1;" :: "r"(id), "r"(n) : "memory"); }
__device__ __forceinline__ void bar_arrive(int id, int n) { asm volatile("bar.arrive %0, %1;" :: "r"(id), "r"(n) : "memory"); }
__device__ __forceinline__ void wg_fence() { asm volatile("wgmma.fence.sync.aligned;" ::: "memory"); }
__device__ __forceinline__ void wg_commit() { asm volatile("wgmma.commit_group.sync.aligned;" ::: "memory"); }
template <int N> __device__ __forceinline__ void wg_wait() { asm volatile("wgmma.wait_group.sync.aligned %0;" :: "n"(N) : "memory"); }
template <int N> __device__ __forceinline__ void pin_regs(float* a) {
#pragma unroll
  for (int i = 0; i < N; i++) asm volatile("" : "+f"(a[i]) :: "memory");
}
__device__ __forceinline__ uint64_t make_desc(uint32_t addr, uint32_t lbo, uint32_t sbo, uint32_t swz) {
  return (uint64_t)((addr & 0x3FFFF) >> 4) | ((uint64_t)(lbo >> 4) << 16) | ((uint64_t)(sbo >> 4) << 32) | ((uint64_t)swz << 62);
}
__device__ __forceinline__ uint32_t pack_bf16(float lo, float hi) { uint32_t r; asm("cvt.rn.bf16x2.f32 %0, %1, %2;" : "=r"(r) : "f"(hi), "f"(lo)); return r; }
__device__ __forceinline__ float bf_lo(uint32_t p) { return __uint_as_float(p << 16); }
__device__ __forceinline__ float bf_hi(uint32_t p) { return __uint_as_float(p & 0xffff0000u); }
__device__ __forceinline__ float round_bf16(float v) { return bf_lo(pack_bf16(v, 0.f)); }
__device__ __forceinline__ uint32_t bmul2(uint32_t a, uint32_t b) { uint32_t r; asm("mul.rn.bf16x2 %0, %1, %2;" : "=r"(r) : "r"(a), "r"(b)); return r; }
__device__ __forceinline__ uint32_t badd2(uint32_t a, uint32_t b) { uint32_t r; asm("add.rn.bf16x2 %0, %1, %2;" : "=r"(r) : "r"(a), "r"(b)); return r; }
__device__ __forceinline__ uint32_t bfma2(uint32_t a, uint32_t b, uint32_t c) { uint32_t r; asm("fma.rn.bf16x2 %0, %1, %2, %3;" : "=r"(r) : "r"(a), "r"(b), "r"(c)); return r; }
__device__ __forceinline__ uint32_t bsub2(uint32_t a, uint32_t b) { uint32_t r; asm("sub.rn.bf16x2 %0, %1, %2;" : "=r"(r) : "r"(a), "r"(b)); return r; }
__device__ __forceinline__ float tanh_fast(float v) { float r; asm("tanh.approx.f32 %0, %1;" : "=f"(r) : "f"(v)); return r; }
__device__ __forceinline__ float gelu_half(float h) {
  return fmaf(h, tanh_fast(h * fmaf(h * h, 8.0f * 0.7978845608028654f * 0.044715f, 2.0f * 0.7978845608028654f)), h);
}
__device__ __forceinline__ float silu_half(float h) { return fmaf(h, tanh_fast(h), h); }
__device__ __forceinline__ uint32_t ldg32(const void* p) { uint32_t v; asm volatile("ld.global.u32 %0, [%1];" : "=r"(v) : "l"(p) : "memory"); return v; }
__device__ __forceinline__ uint32_t lds32(uint32_t a) { uint32_t v; asm volatile("ld.shared.u32 %0, [%1];" : "=r"(v) : "r"(a) : "memory"); return v; }
__device__ __forceinline__ uint32_t lds16(uint32_t a) { uint32_t v; asm volatile("ld.shared.u16 %0, [%1];" : "=r"(v) : "r"(a) : "memory"); return v; }
__device__ __forceinline__ uint4 lds128(uint32_t a) { uint4 v; asm volatile("ld.shared.v4.u32 {%0,%1,%2,%3}, [%4];" : "=r"(v.x), "=r"(v.y), "=r"(v.z), "=r"(v.w) : "r"(a) : "memory"); return v; }
__device__ __forceinline__ void sts128(uint32_t a, uint32_t x, uint32_t y, uint32_t z, uint32_t w) {
  asm volatile("st.shared.v4.u32 [%0], {%1,%2,%3,%4};" :: "r"(a), "r"(x), "r"(y), "r"(z), "r"(w) : "memory");
}
__device__ __forceinline__ void sts32(uint32_t a, uint32_t v) { asm volatile("st.shared.u32 [%0], %1;" :: "r"(a), "r"(v) : "memory"); }
__device__ __forceinline__ void ldsm4(uint32_t* r, uint32_t a) {
  asm volatile("ldmatrix.sync.aligned.m8n8.x4.shared.b16 {%0,%1,%2,%3}, [%4];" : "=r"(r[0]), "=r"(r[1]), "=r"(r[2]), "=r"(r[3]) : "r"(a) : "memory");
}
__device__ __forceinline__ void ldsm2(uint32_t* r, uint32_t a) {
  asm volatile("ldmatrix.sync.aligned.m8n8.x2.shared.b16 {%0,%1}, [%2];" : "=r"(r[0]), "=r"(r[1]) : "r"(a) : "memory");
}
__device__ __forceinline__ void ldsm4t(uint32_t* r, uint32_t a) {
  asm volatile("ldmatrix.sync.aligned.m8n8.x4.trans.shared.b16 {%0,%1,%2,%3}, [%4];" : "=r"(r[0]), "=r"(r[1]), "=r"(r[2]), "=r"(r[3]) : "r"(a) : "memory");
}
__device__ __forceinline__ void ldsm2t(uint32_t* r, uint32_t a) {
  asm volatile("ldmatrix.sync.aligned.m8n8.x2.trans.shared.b16 {%0,%1}, [%2];" : "=r"(r[0]), "=r"(r[1]) : "r"(a) : "memory");
}
__device__ __forceinline__ void stsm4(uint32_t a, uint32_t r0, uint32_t r1, uint32_t r2, uint32_t r3) {
  asm volatile("stmatrix.sync.aligned.m8n8.x4.shared.b16 [%0], {%1,%2,%3,%4};" :: "r"(a), "r"(r0), "r"(r1), "r"(r2), "r"(r3) : "memory");
}
__device__ __forceinline__ void stsm2(uint32_t a, uint32_t r0, uint32_t r1) {
  asm volatile("stmatrix.sync.aligned.m8n8.x2.shared.b16 [%0], {%1,%2};" :: "r"(a), "r"(r0), "r"(r1) : "memory");
}
__device__ __forceinline__ void stsm4t(uint32_t a, uint32_t r0, uint32_t r1, uint32_t r2, uint32_t r3) {
  asm volatile("stmatrix.sync.aligned.m8n8.x4.trans.shared.b16 [%0], {%1,%2,%3,%4};" :: "r"(a), "r"(r0), "r"(r1), "r"(r2), "r"(r3) : "memory");
}

__device__ __forceinline__ void wgmma_ss_n144_t10(float* d, uint64_t da, uint64_t db, int sd) {
  asm volatile("{ .reg .pred p; setp.ne.b32 p, %74, 0;\n"
      "wgmma.mma_async.sync.aligned.m64n144k16.f32.bf16.bf16 {"
      "%0,%1,%2,%3,%4,%5,%6,%7,%8,%9,%10,%11,%12,%13,%14,%15,"
      "%16,%17,%18,%19,%20,%21,%22,%23,%24,%25,%26,%27,%28,%29,%30,%31,"
      "%32,%33,%34,%35,%36,%37,%38,%39,%40,%41,%42,%43,%44,%45,%46,%47,"
      "%48,%49,%50,%51,%52,%53,%54,%55,%56,%57,%58,%59,%60,%61,%62,%63,"
      "%64,%65,%66,%67,%68,%69,%70,%71"
      "}, %72, %73, p, 1, 1, 1, 0; }"
    : "+f"(d[0]), "+f"(d[1]), "+f"(d[2]), "+f"(d[3]), "+f"(d[4]), "+f"(d[5]), "+f"(d[6]), "+f"(d[7]),
      "+f"(d[8]), "+f"(d[9]), "+f"(d[10]), "+f"(d[11]), "+f"(d[12]), "+f"(d[13]), "+f"(d[14]), "+f"(d[15]),
      "+f"(d[16]), "+f"(d[17]), "+f"(d[18]), "+f"(d[19]), "+f"(d[20]), "+f"(d[21]), "+f"(d[22]), "+f"(d[23]),
      "+f"(d[24]), "+f"(d[25]), "+f"(d[26]), "+f"(d[27]), "+f"(d[28]), "+f"(d[29]), "+f"(d[30]), "+f"(d[31]),
      "+f"(d[32]), "+f"(d[33]), "+f"(d[34]), "+f"(d[35]), "+f"(d[36]), "+f"(d[37]), "+f"(d[38]), "+f"(d[39]),
      "+f"(d[40]), "+f"(d[41]), "+f"(d[42]), "+f"(d[43]), "+f"(d[44]), "+f"(d[45]), "+f"(d[46]), "+f"(d[47]),
      "+f"(d[48]), "+f"(d[49]), "+f"(d[50]), "+f"(d[51]), "+f"(d[52]), "+f"(d[53]), "+f"(d[54]), "+f"(d[55]),
      "+f"(d[56]), "+f"(d[57]), "+f"(d[58]), "+f"(d[59]), "+f"(d[60]), "+f"(d[61]), "+f"(d[62]), "+f"(d[63]),
      "+f"(d[64]), "+f"(d[65]), "+f"(d[66]), "+f"(d[67]), "+f"(d[68]), "+f"(d[69]), "+f"(d[70]), "+f"(d[71])
    : "l"(da), "l"(db), "r"(sd));
}

__device__ __forceinline__ void wgmma_ss_n160_t11(float* d, uint64_t da, uint64_t db, int sd) {
  asm volatile("{ .reg .pred p; setp.ne.b32 p, %82, 0;\n"
      "wgmma.mma_async.sync.aligned.m64n160k16.f32.bf16.bf16 {"
      "%0,%1,%2,%3,%4,%5,%6,%7,%8,%9,%10,%11,%12,%13,%14,%15,"
      "%16,%17,%18,%19,%20,%21,%22,%23,%24,%25,%26,%27,%28,%29,%30,%31,"
      "%32,%33,%34,%35,%36,%37,%38,%39,%40,%41,%42,%43,%44,%45,%46,%47,"
      "%48,%49,%50,%51,%52,%53,%54,%55,%56,%57,%58,%59,%60,%61,%62,%63,"
      "%64,%65,%66,%67,%68,%69,%70,%71,%72,%73,%74,%75,%76,%77,%78,%79"
      "}, %80, %81, p, 1, 1, 1, 1; }"
    : "+f"(d[0]), "+f"(d[1]), "+f"(d[2]), "+f"(d[3]), "+f"(d[4]), "+f"(d[5]), "+f"(d[6]), "+f"(d[7]),
      "+f"(d[8]), "+f"(d[9]), "+f"(d[10]), "+f"(d[11]), "+f"(d[12]), "+f"(d[13]), "+f"(d[14]), "+f"(d[15]),
      "+f"(d[16]), "+f"(d[17]), "+f"(d[18]), "+f"(d[19]), "+f"(d[20]), "+f"(d[21]), "+f"(d[22]), "+f"(d[23]),
      "+f"(d[24]), "+f"(d[25]), "+f"(d[26]), "+f"(d[27]), "+f"(d[28]), "+f"(d[29]), "+f"(d[30]), "+f"(d[31]),
      "+f"(d[32]), "+f"(d[33]), "+f"(d[34]), "+f"(d[35]), "+f"(d[36]), "+f"(d[37]), "+f"(d[38]), "+f"(d[39]),
      "+f"(d[40]), "+f"(d[41]), "+f"(d[42]), "+f"(d[43]), "+f"(d[44]), "+f"(d[45]), "+f"(d[46]), "+f"(d[47]),
      "+f"(d[48]), "+f"(d[49]), "+f"(d[50]), "+f"(d[51]), "+f"(d[52]), "+f"(d[53]), "+f"(d[54]), "+f"(d[55]),
      "+f"(d[56]), "+f"(d[57]), "+f"(d[58]), "+f"(d[59]), "+f"(d[60]), "+f"(d[61]), "+f"(d[62]), "+f"(d[63]),
      "+f"(d[64]), "+f"(d[65]), "+f"(d[66]), "+f"(d[67]), "+f"(d[68]), "+f"(d[69]), "+f"(d[70]), "+f"(d[71]),
      "+f"(d[72]), "+f"(d[73]), "+f"(d[74]), "+f"(d[75]), "+f"(d[76]), "+f"(d[77]), "+f"(d[78]), "+f"(d[79])
    : "l"(da), "l"(db), "r"(sd));
}

__device__ __forceinline__ void wgmma_ss_n96_t11(float* d, uint64_t da, uint64_t db, int sd) {
  asm volatile("{ .reg .pred p; setp.ne.b32 p, %50, 0;\n"
      "wgmma.mma_async.sync.aligned.m64n96k16.f32.bf16.bf16 {"
      "%0,%1,%2,%3,%4,%5,%6,%7,%8,%9,%10,%11,%12,%13,%14,%15,"
      "%16,%17,%18,%19,%20,%21,%22,%23,%24,%25,%26,%27,%28,%29,%30,%31,"
      "%32,%33,%34,%35,%36,%37,%38,%39,%40,%41,%42,%43,%44,%45,%46,%47"
      "}, %48, %49, p, 1, 1, 1, 1; }"
    : "+f"(d[0]), "+f"(d[1]), "+f"(d[2]), "+f"(d[3]), "+f"(d[4]), "+f"(d[5]), "+f"(d[6]), "+f"(d[7]),
      "+f"(d[8]), "+f"(d[9]), "+f"(d[10]), "+f"(d[11]), "+f"(d[12]), "+f"(d[13]), "+f"(d[14]), "+f"(d[15]),
      "+f"(d[16]), "+f"(d[17]), "+f"(d[18]), "+f"(d[19]), "+f"(d[20]), "+f"(d[21]), "+f"(d[22]), "+f"(d[23]),
      "+f"(d[24]), "+f"(d[25]), "+f"(d[26]), "+f"(d[27]), "+f"(d[28]), "+f"(d[29]), "+f"(d[30]), "+f"(d[31]),
      "+f"(d[32]), "+f"(d[33]), "+f"(d[34]), "+f"(d[35]), "+f"(d[36]), "+f"(d[37]), "+f"(d[38]), "+f"(d[39]),
      "+f"(d[40]), "+f"(d[41]), "+f"(d[42]), "+f"(d[43]), "+f"(d[44]), "+f"(d[45]), "+f"(d[46]), "+f"(d[47])
    : "l"(da), "l"(db), "r"(sd));
}

__device__ __forceinline__ void wgmma_rs_n16(float* d, const uint32_t* a, uint64_t db, int sd) {
  asm volatile("{ .reg .pred p; setp.ne.b32 p, %13, 0;\n"
      "wgmma.mma_async.sync.aligned.m64n16k16.f32.bf16.bf16 {"
      "%0,%1,%2,%3,%4,%5,%6,%7"
      "}, {%8,%9,%10,%11}, %12, p, 1, 1, 0; }"
    : "+f"(d[0]), "+f"(d[1]), "+f"(d[2]), "+f"(d[3]), "+f"(d[4]), "+f"(d[5]), "+f"(d[6]), "+f"(d[7])
    : "r"(a[0]), "r"(a[1]), "r"(a[2]), "r"(a[3]), "l"(db), "r"(sd));
}

__device__ __forceinline__ void wgmma_rs_n32(float* d, const uint32_t* a, uint64_t db, int sd) {
  asm volatile("{ .reg .pred p; setp.ne.b32 p, %21, 0;\n"
      "wgmma.mma_async.sync.aligned.m64n32k16.f32.bf16.bf16 {"
      "%0,%1,%2,%3,%4,%5,%6,%7,%8,%9,%10,%11,%12,%13,%14,%15"
      "}, {%16,%17,%18,%19}, %20, p, 1, 1, 0; }"
    : "+f"(d[0]), "+f"(d[1]), "+f"(d[2]), "+f"(d[3]), "+f"(d[4]), "+f"(d[5]), "+f"(d[6]), "+f"(d[7]),
      "+f"(d[8]), "+f"(d[9]), "+f"(d[10]), "+f"(d[11]), "+f"(d[12]), "+f"(d[13]), "+f"(d[14]), "+f"(d[15])
    : "r"(a[0]), "r"(a[1]), "r"(a[2]), "r"(a[3]), "l"(db), "r"(sd));
}

__device__ __forceinline__ void wgmma_rs_n48(float* d, const uint32_t* a, uint64_t db, int sd) {
  asm volatile("{ .reg .pred p; setp.ne.b32 p, %29, 0;\n"
      "wgmma.mma_async.sync.aligned.m64n48k16.f32.bf16.bf16 {"
      "%0,%1,%2,%3,%4,%5,%6,%7,%8,%9,%10,%11,%12,%13,%14,%15,"
      "%16,%17,%18,%19,%20,%21,%22,%23"
      "}, {%24,%25,%26,%27}, %28, p, 1, 1, 0; }"
    : "+f"(d[0]), "+f"(d[1]), "+f"(d[2]), "+f"(d[3]), "+f"(d[4]), "+f"(d[5]), "+f"(d[6]), "+f"(d[7]),
      "+f"(d[8]), "+f"(d[9]), "+f"(d[10]), "+f"(d[11]), "+f"(d[12]), "+f"(d[13]), "+f"(d[14]), "+f"(d[15]),
      "+f"(d[16]), "+f"(d[17]), "+f"(d[18]), "+f"(d[19]), "+f"(d[20]), "+f"(d[21]), "+f"(d[22]), "+f"(d[23])
    : "r"(a[0]), "r"(a[1]), "r"(a[2]), "r"(a[3]), "l"(db), "r"(sd));
}

__device__ __forceinline__ void wgmma_rs_n64(float* d, const uint32_t* a, uint64_t db, int sd) {
  asm volatile("{ .reg .pred p; setp.ne.b32 p, %37, 0;\n"
      "wgmma.mma_async.sync.aligned.m64n64k16.f32.bf16.bf16 {"
      "%0,%1,%2,%3,%4,%5,%6,%7,%8,%9,%10,%11,%12,%13,%14,%15,"
      "%16,%17,%18,%19,%20,%21,%22,%23,%24,%25,%26,%27,%28,%29,%30,%31"
      "}, {%32,%33,%34,%35}, %36, p, 1, 1, 0; }"
    : "+f"(d[0]), "+f"(d[1]), "+f"(d[2]), "+f"(d[3]), "+f"(d[4]), "+f"(d[5]), "+f"(d[6]), "+f"(d[7]),
      "+f"(d[8]), "+f"(d[9]), "+f"(d[10]), "+f"(d[11]), "+f"(d[12]), "+f"(d[13]), "+f"(d[14]), "+f"(d[15]),
      "+f"(d[16]), "+f"(d[17]), "+f"(d[18]), "+f"(d[19]), "+f"(d[20]), "+f"(d[21]), "+f"(d[22]), "+f"(d[23]),
      "+f"(d[24]), "+f"(d[25]), "+f"(d[26]), "+f"(d[27]), "+f"(d[28]), "+f"(d[29]), "+f"(d[30]), "+f"(d[31])
    : "r"(a[0]), "r"(a[1]), "r"(a[2]), "r"(a[3]), "l"(db), "r"(sd));
}

__device__ __forceinline__ void wgmma_rs_n80(float* d, const uint32_t* a, uint64_t db, int sd) {
  asm volatile("{ .reg .pred p; setp.ne.b32 p, %45, 0;\n"
      "wgmma.mma_async.sync.aligned.m64n80k16.f32.bf16.bf16 {"
      "%0,%1,%2,%3,%4,%5,%6,%7,%8,%9,%10,%11,%12,%13,%14,%15,"
      "%16,%17,%18,%19,%20,%21,%22,%23,%24,%25,%26,%27,%28,%29,%30,%31,"
      "%32,%33,%34,%35,%36,%37,%38,%39"
      "}, {%40,%41,%42,%43}, %44, p, 1, 1, 0; }"
    : "+f"(d[0]), "+f"(d[1]), "+f"(d[2]), "+f"(d[3]), "+f"(d[4]), "+f"(d[5]), "+f"(d[6]), "+f"(d[7]),
      "+f"(d[8]), "+f"(d[9]), "+f"(d[10]), "+f"(d[11]), "+f"(d[12]), "+f"(d[13]), "+f"(d[14]), "+f"(d[15]),
      "+f"(d[16]), "+f"(d[17]), "+f"(d[18]), "+f"(d[19]), "+f"(d[20]), "+f"(d[21]), "+f"(d[22]), "+f"(d[23]),
      "+f"(d[24]), "+f"(d[25]), "+f"(d[26]), "+f"(d[27]), "+f"(d[28]), "+f"(d[29]), "+f"(d[30]), "+f"(d[31]),
      "+f"(d[32]), "+f"(d[33]), "+f"(d[34]), "+f"(d[35]), "+f"(d[36]), "+f"(d[37]), "+f"(d[38]), "+f"(d[39])
    : "r"(a[0]), "r"(a[1]), "r"(a[2]), "r"(a[3]), "l"(db), "r"(sd));
}

__device__ __forceinline__ void wgmma_rs_n96(float* d, const uint32_t* a, uint64_t db, int sd) {
  asm volatile("{ .reg .pred p; setp.ne.b32 p, %53, 0;\n"
      "wgmma.mma_async.sync.aligned.m64n96k16.f32.bf16.bf16 {"
      "%0,%1,%2,%3,%4,%5,%6,%7,%8,%9,%10,%11,%12,%13,%14,%15,"
      "%16,%17,%18,%19,%20,%21,%22,%23,%24,%25,%26,%27,%28,%29,%30,%31,"
      "%32,%33,%34,%35,%36,%37,%38,%39,%40,%41,%42,%43,%44,%45,%46,%47"
      "}, {%48,%49,%50,%51}, %52, p, 1, 1, 0; }"
    : "+f"(d[0]), "+f"(d[1]), "+f"(d[2]), "+f"(d[3]), "+f"(d[4]), "+f"(d[5]), "+f"(d[6]), "+f"(d[7]),
      "+f"(d[8]), "+f"(d[9]), "+f"(d[10]), "+f"(d[11]), "+f"(d[12]), "+f"(d[13]), "+f"(d[14]), "+f"(d[15]),
      "+f"(d[16]), "+f"(d[17]), "+f"(d[18]), "+f"(d[19]), "+f"(d[20]), "+f"(d[21]), "+f"(d[22]), "+f"(d[23]),
      "+f"(d[24]), "+f"(d[25]), "+f"(d[26]), "+f"(d[27]), "+f"(d[28]), "+f"(d[29]), "+f"(d[30]), "+f"(d[31]),
      "+f"(d[32]), "+f"(d[33]), "+f"(d[34]), "+f"(d[35]), "+f"(d[36]), "+f"(d[37]), "+f"(d[38]), "+f"(d[39]),
      "+f"(d[40]), "+f"(d[41]), "+f"(d[42]), "+f"(d[43]), "+f"(d[44]), "+f"(d[45]), "+f"(d[46]), "+f"(d[47])
    : "r"(a[0]), "r"(a[1]), "r"(a[2]), "r"(a[3]), "l"(db), "r"(sd));
}

__device__ __forceinline__ void wgmma_rs_n112(float* d, const uint32_t* a, uint64_t db, int sd) {
  asm volatile("{ .reg .pred p; setp.ne.b32 p, %61, 0;\n"
      "wgmma.mma_async.sync.aligned.m64n112k16.f32.bf16.bf16 {"
      "%0,%1,%2,%3,%4,%5,%6,%7,%8,%9,%10,%11,%12,%13,%14,%15,"
      "%16,%17,%18,%19,%20,%21,%22,%23,%24,%25,%26,%27,%28,%29,%30,%31,"
      "%32,%33,%34,%35,%36,%37,%38,%39,%40,%41,%42,%43,%44,%45,%46,%47,"
      "%48,%49,%50,%51,%52,%53,%54,%55"
      "}, {%56,%57,%58,%59}, %60, p, 1, 1, 0; }"
    : "+f"(d[0]), "+f"(d[1]), "+f"(d[2]), "+f"(d[3]), "+f"(d[4]), "+f"(d[5]), "+f"(d[6]), "+f"(d[7]),
      "+f"(d[8]), "+f"(d[9]), "+f"(d[10]), "+f"(d[11]), "+f"(d[12]), "+f"(d[13]), "+f"(d[14]), "+f"(d[15]),
      "+f"(d[16]), "+f"(d[17]), "+f"(d[18]), "+f"(d[19]), "+f"(d[20]), "+f"(d[21]), "+f"(d[22]), "+f"(d[23]),
      "+f"(d[24]), "+f"(d[25]), "+f"(d[26]), "+f"(d[27]), "+f"(d[28]), "+f"(d[29]), "+f"(d[30]), "+f"(d[31]),
      "+f"(d[32]), "+f"(d[33]), "+f"(d[34]), "+f"(d[35]), "+f"(d[36]), "+f"(d[37]), "+f"(d[38]), "+f"(d[39]),
      "+f"(d[40]), "+f"(d[41]), "+f"(d[42]), "+f"(d[43]), "+f"(d[44]), "+f"(d[45]), "+f"(d[46]), "+f"(d[47]),
      "+f"(d[48]), "+f"(d[49]), "+f"(d[50]), "+f"(d[51]), "+f"(d[52]), "+f"(d[53]), "+f"(d[54]), "+f"(d[55])
    : "r"(a[0]), "r"(a[1]), "r"(a[2]), "r"(a[3]), "l"(db), "r"(sd));
}

__device__ __forceinline__ void wgmma_rs_n128(float* d, const uint32_t* a, uint64_t db, int sd) {
  asm volatile("{ .reg .pred p; setp.ne.b32 p, %69, 0;\n"
      "wgmma.mma_async.sync.aligned.m64n128k16.f32.bf16.bf16 {"
      "%0,%1,%2,%3,%4,%5,%6,%7,%8,%9,%10,%11,%12,%13,%14,%15,"
      "%16,%17,%18,%19,%20,%21,%22,%23,%24,%25,%26,%27,%28,%29,%30,%31,"
      "%32,%33,%34,%35,%36,%37,%38,%39,%40,%41,%42,%43,%44,%45,%46,%47,"
      "%48,%49,%50,%51,%52,%53,%54,%55,%56,%57,%58,%59,%60,%61,%62,%63"
      "}, {%64,%65,%66,%67}, %68, p, 1, 1, 0; }"
    : "+f"(d[0]), "+f"(d[1]), "+f"(d[2]), "+f"(d[3]), "+f"(d[4]), "+f"(d[5]), "+f"(d[6]), "+f"(d[7]),
      "+f"(d[8]), "+f"(d[9]), "+f"(d[10]), "+f"(d[11]), "+f"(d[12]), "+f"(d[13]), "+f"(d[14]), "+f"(d[15]),
      "+f"(d[16]), "+f"(d[17]), "+f"(d[18]), "+f"(d[19]), "+f"(d[20]), "+f"(d[21]), "+f"(d[22]), "+f"(d[23]),
      "+f"(d[24]), "+f"(d[25]), "+f"(d[26]), "+f"(d[27]), "+f"(d[28]), "+f"(d[29]), "+f"(d[30]), "+f"(d[31]),
      "+f"(d[32]), "+f"(d[33]), "+f"(d[34]), "+f"(d[35]), "+f"(d[36]), "+f"(d[37]), "+f"(d[38]), "+f"(d[39]),
      "+f"(d[40]), "+f"(d[41]), "+f"(d[42]), "+f"(d[43]), "+f"(d[44]), "+f"(d[45]), "+f"(d[46]), "+f"(d[47]),
      "+f"(d[48]), "+f"(d[49]), "+f"(d[50]), "+f"(d[51]), "+f"(d[52]), "+f"(d[53]), "+f"(d[54]), "+f"(d[55]),
      "+f"(d[56]), "+f"(d[57]), "+f"(d[58]), "+f"(d[59]), "+f"(d[60]), "+f"(d[61]), "+f"(d[62]), "+f"(d[63])
    : "r"(a[0]), "r"(a[1]), "r"(a[2]), "r"(a[3]), "l"(db), "r"(sd));
}

__device__ __forceinline__ void wgmma_rs_n144(float* d, const uint32_t* a, uint64_t db, int sd) {
  asm volatile("{ .reg .pred p; setp.ne.b32 p, %77, 0;\n"
      "wgmma.mma_async.sync.aligned.m64n144k16.f32.bf16.bf16 {"
      "%0,%1,%2,%3,%4,%5,%6,%7,%8,%9,%10,%11,%12,%13,%14,%15,"
      "%16,%17,%18,%19,%20,%21,%22,%23,%24,%25,%26,%27,%28,%29,%30,%31,"
      "%32,%33,%34,%35,%36,%37,%38,%39,%40,%41,%42,%43,%44,%45,%46,%47,"
      "%48,%49,%50,%51,%52,%53,%54,%55,%56,%57,%58,%59,%60,%61,%62,%63,"
      "%64,%65,%66,%67,%68,%69,%70,%71"
      "}, {%72,%73,%74,%75}, %76, p, 1, 1, 0; }"
    : "+f"(d[0]), "+f"(d[1]), "+f"(d[2]), "+f"(d[3]), "+f"(d[4]), "+f"(d[5]), "+f"(d[6]), "+f"(d[7]),
      "+f"(d[8]), "+f"(d[9]), "+f"(d[10]), "+f"(d[11]), "+f"(d[12]), "+f"(d[13]), "+f"(d[14]), "+f"(d[15]),
      "+f"(d[16]), "+f"(d[17]), "+f"(d[18]), "+f"(d[19]), "+f"(d[20]), "+f"(d[21]), "+f"(d[22]), "+f"(d[23]),
      "+f"(d[24]), "+f"(d[25]), "+f"(d[26]), "+f"(d[27]), "+f"(d[28]), "+f"(d[29]), "+f"(d[30]), "+f"(d[31]),
      "+f"(d[32]), "+f"(d[33]), "+f"(d[34]), "+f"(d[35]), "+f"(d[36]), "+f"(d[37]), "+f"(d[38]), "+f"(d[39]),
      "+f"(d[40]), "+f"(d[41]), "+f"(d[42]), "+f"(d[43]), "+f"(d[44]), "+f"(d[45]), "+f"(d[46]), "+f"(d[47]),
      "+f"(d[48]), "+f"(d[49]), "+f"(d[50]), "+f"(d[51]), "+f"(d[52]), "+f"(d[53]), "+f"(d[54]), "+f"(d[55]),
      "+f"(d[56]), "+f"(d[57]), "+f"(d[58]), "+f"(d[59]), "+f"(d[60]), "+f"(d[61]), "+f"(d[62]), "+f"(d[63]),
      "+f"(d[64]), "+f"(d[65]), "+f"(d[66]), "+f"(d[67]), "+f"(d[68]), "+f"(d[69]), "+f"(d[70]), "+f"(d[71])
    : "r"(a[0]), "r"(a[1]), "r"(a[2]), "r"(a[3]), "l"(db), "r"(sd));
}

__device__ __forceinline__ void wgmma_rs_n160(float* d, const uint32_t* a, uint64_t db, int sd) {
  asm volatile("{ .reg .pred p; setp.ne.b32 p, %85, 0;\n"
      "wgmma.mma_async.sync.aligned.m64n160k16.f32.bf16.bf16 {"
      "%0,%1,%2,%3,%4,%5,%6,%7,%8,%9,%10,%11,%12,%13,%14,%15,"
      "%16,%17,%18,%19,%20,%21,%22,%23,%24,%25,%26,%27,%28,%29,%30,%31,"
      "%32,%33,%34,%35,%36,%37,%38,%39,%40,%41,%42,%43,%44,%45,%46,%47,"
      "%48,%49,%50,%51,%52,%53,%54,%55,%56,%57,%58,%59,%60,%61,%62,%63,"
      "%64,%65,%66,%67,%68,%69,%70,%71,%72,%73,%74,%75,%76,%77,%78,%79"
      "}, {%80,%81,%82,%83}, %84, p, 1, 1, 0; }"
    : "+f"(d[0]), "+f"(d[1]), "+f"(d[2]), "+f"(d[3]), "+f"(d[4]), "+f"(d[5]), "+f"(d[6]), "+f"(d[7]),
      "+f"(d[8]), "+f"(d[9]), "+f"(d[10]), "+f"(d[11]), "+f"(d[12]), "+f"(d[13]), "+f"(d[14]), "+f"(d[15]),
      "+f"(d[16]), "+f"(d[17]), "+f"(d[18]), "+f"(d[19]), "+f"(d[20]), "+f"(d[21]), "+f"(d[22]), "+f"(d[23]),
      "+f"(d[24]), "+f"(d[25]), "+f"(d[26]), "+f"(d[27]), "+f"(d[28]), "+f"(d[29]), "+f"(d[30]), "+f"(d[31]),
      "+f"(d[32]), "+f"(d[33]), "+f"(d[34]), "+f"(d[35]), "+f"(d[36]), "+f"(d[37]), "+f"(d[38]), "+f"(d[39]),
      "+f"(d[40]), "+f"(d[41]), "+f"(d[42]), "+f"(d[43]), "+f"(d[44]), "+f"(d[45]), "+f"(d[46]), "+f"(d[47]),
      "+f"(d[48]), "+f"(d[49]), "+f"(d[50]), "+f"(d[51]), "+f"(d[52]), "+f"(d[53]), "+f"(d[54]), "+f"(d[55]),
      "+f"(d[56]), "+f"(d[57]), "+f"(d[58]), "+f"(d[59]), "+f"(d[60]), "+f"(d[61]), "+f"(d[62]), "+f"(d[63]),
      "+f"(d[64]), "+f"(d[65]), "+f"(d[66]), "+f"(d[67]), "+f"(d[68]), "+f"(d[69]), "+f"(d[70]), "+f"(d[71]),
      "+f"(d[72]), "+f"(d[73]), "+f"(d[74]), "+f"(d[75]), "+f"(d[76]), "+f"(d[77]), "+f"(d[78]), "+f"(d[79])
    : "r"(a[0]), "r"(a[1]), "r"(a[2]), "r"(a[3]), "l"(db), "r"(sd));
}

__device__ __forceinline__ void wgmma_rs_n176(float* d, const uint32_t* a, uint64_t db, int sd) {
  asm volatile("{ .reg .pred p; setp.ne.b32 p, %93, 0;\n"
      "wgmma.mma_async.sync.aligned.m64n176k16.f32.bf16.bf16 {"
      "%0,%1,%2,%3,%4,%5,%6,%7,%8,%9,%10,%11,%12,%13,%14,%15,"
      "%16,%17,%18,%19,%20,%21,%22,%23,%24,%25,%26,%27,%28,%29,%30,%31,"
      "%32,%33,%34,%35,%36,%37,%38,%39,%40,%41,%42,%43,%44,%45,%46,%47,"
      "%48,%49,%50,%51,%52,%53,%54,%55,%56,%57,%58,%59,%60,%61,%62,%63,"
      "%64,%65,%66,%67,%68,%69,%70,%71,%72,%73,%74,%75,%76,%77,%78,%79,"
      "%80,%81,%82,%83,%84,%85,%86,%87"
      "}, {%88,%89,%90,%91}, %92, p, 1, 1, 0; }"
    : "+f"(d[0]), "+f"(d[1]), "+f"(d[2]), "+f"(d[3]), "+f"(d[4]), "+f"(d[5]), "+f"(d[6]), "+f"(d[7]),
      "+f"(d[8]), "+f"(d[9]), "+f"(d[10]), "+f"(d[11]), "+f"(d[12]), "+f"(d[13]), "+f"(d[14]), "+f"(d[15]),
      "+f"(d[16]), "+f"(d[17]), "+f"(d[18]), "+f"(d[19]), "+f"(d[20]), "+f"(d[21]), "+f"(d[22]), "+f"(d[23]),
      "+f"(d[24]), "+f"(d[25]), "+f"(d[26]), "+f"(d[27]), "+f"(d[28]), "+f"(d[29]), "+f"(d[30]), "+f"(d[31]),
      "+f"(d[32]), "+f"(d[33]), "+f"(d[34]), "+f"(d[35]), "+f"(d[36]), "+f"(d[37]), "+f"(d[38]), "+f"(d[39]),
      "+f"(d[40]), "+f"(d[41]), "+f"(d[42]), "+f"(d[43]), "+f"(d[44]), "+f"(d[45]), "+f"(d[46]), "+f"(d[47]),
      "+f"(d[48]), "+f"(d[49]), "+f"(d[50]), "+f"(d[51]), "+f"(d[52]), "+f"(d[53]), "+f"(d[54]), "+f"(d[55]),
      "+f"(d[56]), "+f"(d[57]), "+f"(d[58]), "+f"(d[59]), "+f"(d[60]), "+f"(d[61]), "+f"(d[62]), "+f"(d[63]),
      "+f"(d[64]), "+f"(d[65]), "+f"(d[66]), "+f"(d[67]), "+f"(d[68]), "+f"(d[69]), "+f"(d[70]), "+f"(d[71]),
      "+f"(d[72]), "+f"(d[73]), "+f"(d[74]), "+f"(d[75]), "+f"(d[76]), "+f"(d[77]), "+f"(d[78]), "+f"(d[79]),
      "+f"(d[80]), "+f"(d[81]), "+f"(d[82]), "+f"(d[83]), "+f"(d[84]), "+f"(d[85]), "+f"(d[86]), "+f"(d[87])
    : "r"(a[0]), "r"(a[1]), "r"(a[2]), "r"(a[3]), "l"(db), "r"(sd));
}

__device__ __forceinline__ void wgmma_rs_n192(float* d, const uint32_t* a, uint64_t db, int sd) {
  asm volatile("{ .reg .pred p; setp.ne.b32 p, %101, 0;\n"
      "wgmma.mma_async.sync.aligned.m64n192k16.f32.bf16.bf16 {"
      "%0,%1,%2,%3,%4,%5,%6,%7,%8,%9,%10,%11,%12,%13,%14,%15,"
      "%16,%17,%18,%19,%20,%21,%22,%23,%24,%25,%26,%27,%28,%29,%30,%31,"
      "%32,%33,%34,%35,%36,%37,%38,%39,%40,%41,%42,%43,%44,%45,%46,%47,"
      "%48,%49,%50,%51,%52,%53,%54,%55,%56,%57,%58,%59,%60,%61,%62,%63,"
      "%64,%65,%66,%67,%68,%69,%70,%71,%72,%73,%74,%75,%76,%77,%78,%79,"
      "%80,%81,%82,%83,%84,%85,%86,%87,%88,%89,%90,%91,%92,%93,%94,%95"
      "}, {%96,%97,%98,%99}, %100, p, 1, 1, 0; }"
    : "+f"(d[0]), "+f"(d[1]), "+f"(d[2]), "+f"(d[3]), "+f"(d[4]), "+f"(d[5]), "+f"(d[6]), "+f"(d[7]),
      "+f"(d[8]), "+f"(d[9]), "+f"(d[10]), "+f"(d[11]), "+f"(d[12]), "+f"(d[13]), "+f"(d[14]), "+f"(d[15]),
      "+f"(d[16]), "+f"(d[17]), "+f"(d[18]), "+f"(d[19]), "+f"(d[20]), "+f"(d[21]), "+f"(d[22]), "+f"(d[23]),
      "+f"(d[24]), "+f"(d[25]), "+f"(d[26]), "+f"(d[27]), "+f"(d[28]), "+f"(d[29]), "+f"(d[30]), "+f"(d[31]),
      "+f"(d[32]), "+f"(d[33]), "+f"(d[34]), "+f"(d[35]), "+f"(d[36]), "+f"(d[37]), "+f"(d[38]), "+f"(d[39]),
      "+f"(d[40]), "+f"(d[41]), "+f"(d[42]), "+f"(d[43]), "+f"(d[44]), "+f"(d[45]), "+f"(d[46]), "+f"(d[47]),
      "+f"(d[48]), "+f"(d[49]), "+f"(d[50]), "+f"(d[51]), "+f"(d[52]), "+f"(d[53]), "+f"(d[54]), "+f"(d[55]),
      "+f"(d[56]), "+f"(d[57]), "+f"(d[58]), "+f"(d[59]), "+f"(d[60]), "+f"(d[61]), "+f"(d[62]), "+f"(d[63]),
      "+f"(d[64]), "+f"(d[65]), "+f"(d[66]), "+f"(d[67]), "+f"(d[68]), "+f"(d[69]), "+f"(d[70]), "+f"(d[71]),
      "+f"(d[72]), "+f"(d[73]), "+f"(d[74]), "+f"(d[75]), "+f"(d[76]), "+f"(d[77]), "+f"(d[78]), "+f"(d[79]),
      "+f"(d[80]), "+f"(d[81]), "+f"(d[82]), "+f"(d[83]), "+f"(d[84]), "+f"(d[85]), "+f"(d[86]), "+f"(d[87]),
      "+f"(d[88]), "+f"(d[89]), "+f"(d[90]), "+f"(d[91]), "+f"(d[92]), "+f"(d[93]), "+f"(d[94]), "+f"(d[95])
    : "r"(a[0]), "r"(a[1]), "r"(a[2]), "r"(a[3]), "l"(db), "r"(sd));
}

__device__ __forceinline__ void wgmma_rs_n208(float* d, const uint32_t* a, uint64_t db, int sd) {
  asm volatile("{ .reg .pred p; setp.ne.b32 p, %109, 0;\n"
      "wgmma.mma_async.sync.aligned.m64n208k16.f32.bf16.bf16 {"
      "%0,%1,%2,%3,%4,%5,%6,%7,%8,%9,%10,%11,%12,%13,%14,%15,"
      "%16,%17,%18,%19,%20,%21,%22,%23,%24,%25,%26,%27,%28,%29,%30,%31,"
      "%32,%33,%34,%35,%36,%37,%38,%39,%40,%41,%42,%43,%44,%45,%46,%47,"
      "%48,%49,%50,%51,%52,%53,%54,%55,%56,%57,%58,%59,%60,%61,%62,%63,"
      "%64,%65,%66,%67,%68,%69,%70,%71,%72,%73,%74,%75,%76,%77,%78,%79,"
      "%80,%81,%82,%83,%84,%85,%86,%87,%88,%89,%90,%91,%92,%93,%94,%95,"
      "%96,%97,%98,%99,%100,%101,%102,%103"
      "}, {%104,%105,%106,%107}, %108, p, 1, 1, 0; }"
    : "+f"(d[0]), "+f"(d[1]), "+f"(d[2]), "+f"(d[3]), "+f"(d[4]), "+f"(d[5]), "+f"(d[6]), "+f"(d[7]),
      "+f"(d[8]), "+f"(d[9]), "+f"(d[10]), "+f"(d[11]), "+f"(d[12]), "+f"(d[13]), "+f"(d[14]), "+f"(d[15]),
      "+f"(d[16]), "+f"(d[17]), "+f"(d[18]), "+f"(d[19]), "+f"(d[20]), "+f"(d[21]), "+f"(d[22]), "+f"(d[23]),
      "+f"(d[24]), "+f"(d[25]), "+f"(d[26]), "+f"(d[27]), "+f"(d[28]), "+f"(d[29]), "+f"(d[30]), "+f"(d[31]),
      "+f"(d[32]), "+f"(d[33]), "+f"(d[34]), "+f"(d[35]), "+f"(d[36]), "+f"(d[37]), "+f"(d[38]), "+f"(d[39]),
      "+f"(d[40]), "+f"(d[41]), "+f"(d[42]), "+f"(d[43]), "+f"(d[44]), "+f"(d[45]), "+f"(d[46]), "+f"(d[47]),
      "+f"(d[48]), "+f"(d[49]), "+f"(d[50]), "+f"(d[51]), "+f"(d[52]), "+f"(d[53]), "+f"(d[54]), "+f"(d[55]),
      "+f"(d[56]), "+f"(d[57]), "+f"(d[58]), "+f"(d[59]), "+f"(d[60]), "+f"(d[61]), "+f"(d[62]), "+f"(d[63]),
      "+f"(d[64]), "+f"(d[65]), "+f"(d[66]), "+f"(d[67]), "+f"(d[68]), "+f"(d[69]), "+f"(d[70]), "+f"(d[71]),
      "+f"(d[72]), "+f"(d[73]), "+f"(d[74]), "+f"(d[75]), "+f"(d[76]), "+f"(d[77]), "+f"(d[78]), "+f"(d[79]),
      "+f"(d[80]), "+f"(d[81]), "+f"(d[82]), "+f"(d[83]), "+f"(d[84]), "+f"(d[85]), "+f"(d[86]), "+f"(d[87]),
      "+f"(d[88]), "+f"(d[89]), "+f"(d[90]), "+f"(d[91]), "+f"(d[92]), "+f"(d[93]), "+f"(d[94]), "+f"(d[95]),
      "+f"(d[96]), "+f"(d[97]), "+f"(d[98]), "+f"(d[99]), "+f"(d[100]), "+f"(d[101]), "+f"(d[102]), "+f"(d[103])
    : "r"(a[0]), "r"(a[1]), "r"(a[2]), "r"(a[3]), "l"(db), "r"(sd));
}

__device__ __forceinline__ void wgmma_rs_n224(float* d, const uint32_t* a, uint64_t db, int sd) {
  asm volatile("{ .reg .pred p; setp.ne.b32 p, %117, 0;\n"
      "wgmma.mma_async.sync.aligned.m64n224k16.f32.bf16.bf16 {"
      "%0,%1,%2,%3,%4,%5,%6,%7,%8,%9,%10,%11,%12,%13,%14,%15,"
      "%16,%17,%18,%19,%20,%21,%22,%23,%24,%25,%26,%27,%28,%29,%30,%31,"
      "%32,%33,%34,%35,%36,%37,%38,%39,%40,%41,%42,%43,%44,%45,%46,%47,"
      "%48,%49,%50,%51,%52,%53,%54,%55,%56,%57,%58,%59,%60,%61,%62,%63,"
      "%64,%65,%66,%67,%68,%69,%70,%71,%72,%73,%74,%75,%76,%77,%78,%79,"
      "%80,%81,%82,%83,%84,%85,%86,%87,%88,%89,%90,%91,%92,%93,%94,%95,"
      "%96,%97,%98,%99,%100,%101,%102,%103,%104,%105,%106,%107,%108,%109,%110,%111"
      "}, {%112,%113,%114,%115}, %116, p, 1, 1, 0; }"
    : "+f"(d[0]), "+f"(d[1]), "+f"(d[2]), "+f"(d[3]), "+f"(d[4]), "+f"(d[5]), "+f"(d[6]), "+f"(d[7]),
      "+f"(d[8]), "+f"(d[9]), "+f"(d[10]), "+f"(d[11]), "+f"(d[12]), "+f"(d[13]), "+f"(d[14]), "+f"(d[15]),
      "+f"(d[16]), "+f"(d[17]), "+f"(d[18]), "+f"(d[19]), "+f"(d[20]), "+f"(d[21]), "+f"(d[22]), "+f"(d[23]),
      "+f"(d[24]), "+f"(d[25]), "+f"(d[26]), "+f"(d[27]), "+f"(d[28]), "+f"(d[29]), "+f"(d[30]), "+f"(d[31]),
      "+f"(d[32]), "+f"(d[33]), "+f"(d[34]), "+f"(d[35]), "+f"(d[36]), "+f"(d[37]), "+f"(d[38]), "+f"(d[39]),
      "+f"(d[40]), "+f"(d[41]), "+f"(d[42]), "+f"(d[43]), "+f"(d[44]), "+f"(d[45]), "+f"(d[46]), "+f"(d[47]),
      "+f"(d[48]), "+f"(d[49]), "+f"(d[50]), "+f"(d[51]), "+f"(d[52]), "+f"(d[53]), "+f"(d[54]), "+f"(d[55]),
      "+f"(d[56]), "+f"(d[57]), "+f"(d[58]), "+f"(d[59]), "+f"(d[60]), "+f"(d[61]), "+f"(d[62]), "+f"(d[63]),
      "+f"(d[64]), "+f"(d[65]), "+f"(d[66]), "+f"(d[67]), "+f"(d[68]), "+f"(d[69]), "+f"(d[70]), "+f"(d[71]),
      "+f"(d[72]), "+f"(d[73]), "+f"(d[74]), "+f"(d[75]), "+f"(d[76]), "+f"(d[77]), "+f"(d[78]), "+f"(d[79]),
      "+f"(d[80]), "+f"(d[81]), "+f"(d[82]), "+f"(d[83]), "+f"(d[84]), "+f"(d[85]), "+f"(d[86]), "+f"(d[87]),
      "+f"(d[88]), "+f"(d[89]), "+f"(d[90]), "+f"(d[91]), "+f"(d[92]), "+f"(d[93]), "+f"(d[94]), "+f"(d[95]),
      "+f"(d[96]), "+f"(d[97]), "+f"(d[98]), "+f"(d[99]), "+f"(d[100]), "+f"(d[101]), "+f"(d[102]), "+f"(d[103]),
      "+f"(d[104]), "+f"(d[105]), "+f"(d[106]), "+f"(d[107]), "+f"(d[108]), "+f"(d[109]), "+f"(d[110]), "+f"(d[111])
    : "r"(a[0]), "r"(a[1]), "r"(a[2]), "r"(a[3]), "l"(db), "r"(sd));
}

__device__ __forceinline__ void wgmma_rs_n240(float* d, const uint32_t* a, uint64_t db, int sd) {
  asm volatile("{ .reg .pred p; setp.ne.b32 p, %125, 0;\n"
      "wgmma.mma_async.sync.aligned.m64n240k16.f32.bf16.bf16 {"
      "%0,%1,%2,%3,%4,%5,%6,%7,%8,%9,%10,%11,%12,%13,%14,%15,"
      "%16,%17,%18,%19,%20,%21,%22,%23,%24,%25,%26,%27,%28,%29,%30,%31,"
      "%32,%33,%34,%35,%36,%37,%38,%39,%40,%41,%42,%43,%44,%45,%46,%47,"
      "%48,%49,%50,%51,%52,%53,%54,%55,%56,%57,%58,%59,%60,%61,%62,%63,"
      "%64,%65,%66,%67,%68,%69,%70,%71,%72,%73,%74,%75,%76,%77,%78,%79,"
      "%80,%81,%82,%83,%84,%85,%86,%87,%88,%89,%90,%91,%92,%93,%94,%95,"
      "%96,%97,%98,%99,%100,%101,%102,%103,%104,%105,%106,%107,%108,%109,%110,%111,"
      "%112,%113,%114,%115,%116,%117,%118,%119"
      "}, {%120,%121,%122,%123}, %124, p, 1, 1, 0; }"
    : "+f"(d[0]), "+f"(d[1]), "+f"(d[2]), "+f"(d[3]), "+f"(d[4]), "+f"(d[5]), "+f"(d[6]), "+f"(d[7]),
      "+f"(d[8]), "+f"(d[9]), "+f"(d[10]), "+f"(d[11]), "+f"(d[12]), "+f"(d[13]), "+f"(d[14]), "+f"(d[15]),
      "+f"(d[16]), "+f"(d[17]), "+f"(d[18]), "+f"(d[19]), "+f"(d[20]), "+f"(d[21]), "+f"(d[22]), "+f"(d[23]),
      "+f"(d[24]), "+f"(d[25]), "+f"(d[26]), "+f"(d[27]), "+f"(d[28]), "+f"(d[29]), "+f"(d[30]), "+f"(d[31]),
      "+f"(d[32]), "+f"(d[33]), "+f"(d[34]), "+f"(d[35]), "+f"(d[36]), "+f"(d[37]), "+f"(d[38]), "+f"(d[39]),
      "+f"(d[40]), "+f"(d[41]), "+f"(d[42]), "+f"(d[43]), "+f"(d[44]), "+f"(d[45]), "+f"(d[46]), "+f"(d[47]),
      "+f"(d[48]), "+f"(d[49]), "+f"(d[50]), "+f"(d[51]), "+f"(d[52]), "+f"(d[53]), "+f"(d[54]), "+f"(d[55]),
      "+f"(d[56]), "+f"(d[57]), "+f"(d[58]), "+f"(d[59]), "+f"(d[60]), "+f"(d[61]), "+f"(d[62]), "+f"(d[63]),
      "+f"(d[64]), "+f"(d[65]), "+f"(d[66]), "+f"(d[67]), "+f"(d[68]), "+f"(d[69]), "+f"(d[70]), "+f"(d[71]),
      "+f"(d[72]), "+f"(d[73]), "+f"(d[74]), "+f"(d[75]), "+f"(d[76]), "+f"(d[77]), "+f"(d[78]), "+f"(d[79]),
      "+f"(d[80]), "+f"(d[81]), "+f"(d[82]), "+f"(d[83]), "+f"(d[84]), "+f"(d[85]), "+f"(d[86]), "+f"(d[87]),
      "+f"(d[88]), "+f"(d[89]), "+f"(d[90]), "+f"(d[91]), "+f"(d[92]), "+f"(d[93]), "+f"(d[94]), "+f"(d[95]),
      "+f"(d[96]), "+f"(d[97]), "+f"(d[98]), "+f"(d[99]), "+f"(d[100]), "+f"(d[101]), "+f"(d[102]), "+f"(d[103]),
      "+f"(d[104]), "+f"(d[105]), "+f"(d[106]), "+f"(d[107]), "+f"(d[108]), "+f"(d[109]), "+f"(d[110]), "+f"(d[111]),
      "+f"(d[112]), "+f"(d[113]), "+f"(d[114]), "+f"(d[115]), "+f"(d[116]), "+f"(d[117]), "+f"(d[118]), "+f"(d[119])
    : "r"(a[0]), "r"(a[1]), "r"(a[2]), "r"(a[3]), "l"(db), "r"(sd));
}

__device__ __forceinline__ void wgmma_rs_n256(float* d, const uint32_t* a, uint64_t db, int sd) {
  asm volatile("{ .reg .pred p; setp.ne.b32 p, %133, 0;\n"
      "wgmma.mma_async.sync.aligned.m64n256k16.f32.bf16.bf16 {"
      "%0,%1,%2,%3,%4,%5,%6,%7,%8,%9,%10,%11,%12,%13,%14,%15,"
      "%16,%17,%18,%19,%20,%21,%22,%23,%24,%25,%26,%27,%28,%29,%30,%31,"
      "%32,%33,%34,%35,%36,%37,%38,%39,%40,%41,%42,%43,%44,%45,%46,%47,"
      "%48,%49,%50,%51,%52,%53,%54,%55,%56,%57,%58,%59,%60,%61,%62,%63,"
      "%64,%65,%66,%67,%68,%69,%70,%71,%72,%73,%74,%75,%76,%77,%78,%79,"
      "%80,%81,%82,%83,%84,%85,%86,%87,%88,%89,%90,%91,%92,%93,%94,%95,"
      "%96,%97,%98,%99,%100,%101,%102,%103,%104,%105,%106,%107,%108,%109,%110,%111,"
      "%112,%113,%114,%115,%116,%117,%118,%119,%120,%121,%122,%123,%124,%125,%126,%127"
      "}, {%128,%129,%130,%131}, %132, p, 1, 1, 0; }"
    : "+f"(d[0]), "+f"(d[1]), "+f"(d[2]), "+f"(d[3]), "+f"(d[4]), "+f"(d[5]), "+f"(d[6]), "+f"(d[7]),
      "+f"(d[8]), "+f"(d[9]), "+f"(d[10]), "+f"(d[11]), "+f"(d[12]), "+f"(d[13]), "+f"(d[14]), "+f"(d[15]),
      "+f"(d[16]), "+f"(d[17]), "+f"(d[18]), "+f"(d[19]), "+f"(d[20]), "+f"(d[21]), "+f"(d[22]), "+f"(d[23]),
      "+f"(d[24]), "+f"(d[25]), "+f"(d[26]), "+f"(d[27]), "+f"(d[28]), "+f"(d[29]), "+f"(d[30]), "+f"(d[31]),
      "+f"(d[32]), "+f"(d[33]), "+f"(d[34]), "+f"(d[35]), "+f"(d[36]), "+f"(d[37]), "+f"(d[38]), "+f"(d[39]),
      "+f"(d[40]), "+f"(d[41]), "+f"(d[42]), "+f"(d[43]), "+f"(d[44]), "+f"(d[45]), "+f"(d[46]), "+f"(d[47]),
      "+f"(d[48]), "+f"(d[49]), "+f"(d[50]), "+f"(d[51]), "+f"(d[52]), "+f"(d[53]), "+f"(d[54]), "+f"(d[55]),
      "+f"(d[56]), "+f"(d[57]), "+f"(d[58]), "+f"(d[59]), "+f"(d[60]), "+f"(d[61]), "+f"(d[62]), "+f"(d[63]),
      "+f"(d[64]), "+f"(d[65]), "+f"(d[66]), "+f"(d[67]), "+f"(d[68]), "+f"(d[69]), "+f"(d[70]), "+f"(d[71]),
      "+f"(d[72]), "+f"(d[73]), "+f"(d[74]), "+f"(d[75]), "+f"(d[76]), "+f"(d[77]), "+f"(d[78]), "+f"(d[79]),
      "+f"(d[80]), "+f"(d[81]), "+f"(d[82]), "+f"(d[83]), "+f"(d[84]), "+f"(d[85]), "+f"(d[86]), "+f"(d[87]),
      "+f"(d[88]), "+f"(d[89]), "+f"(d[90]), "+f"(d[91]), "+f"(d[92]), "+f"(d[93]), "+f"(d[94]), "+f"(d[95]),
      "+f"(d[96]), "+f"(d[97]), "+f"(d[98]), "+f"(d[99]), "+f"(d[100]), "+f"(d[101]), "+f"(d[102]), "+f"(d[103]),
      "+f"(d[104]), "+f"(d[105]), "+f"(d[106]), "+f"(d[107]), "+f"(d[108]), "+f"(d[109]), "+f"(d[110]), "+f"(d[111]),
      "+f"(d[112]), "+f"(d[113]), "+f"(d[114]), "+f"(d[115]), "+f"(d[116]), "+f"(d[117]), "+f"(d[118]), "+f"(d[119]),
      "+f"(d[120]), "+f"(d[121]), "+f"(d[122]), "+f"(d[123]), "+f"(d[124]), "+f"(d[125]), "+f"(d[126]), "+f"(d[127])
    : "r"(a[0]), "r"(a[1]), "r"(a[2]), "r"(a[3]), "l"(db), "r"(sd));
}

__device__ __forceinline__ void ln_finish(float mean, float var, float& mb, float& rinv) {
  mb = round_bf16(mean);
  float sd;
  asm("sqrt.approx.ftz.f32 %0, %1;" : "=f"(sd) : "f"(round_bf16(round_bf16(var) + 1e-5f)));
  asm("rcp.approx.ftz.f32 %0, %1;" : "=f"(rinv) : "f"(round_bf16(sd)));
}
__device__ __forceinline__ uint32_t sum4(uint32_t a, uint32_t b, uint32_t c, uint32_t d) {
  return pack_bf16((bf_lo(a) + bf_lo(b)) + (bf_lo(c) + bf_lo(d)), (bf_hi(a) + bf_hi(b)) + (bf_hi(c) + bf_hi(d)));
}
struct Ring {
  uint32_t s, ph;
  __device__ __forceinline__ void next() { if (++s == NSTAGE) { s = 0; ph ^= 1; } }
};

__device__ __forceinline__ void conv_lda(uint32_t* a, int j, uint32_t base, bool on) {
  asm volatile("{ .reg .pred p; setp.ne.u32 p, %3, 0;\n @p ld.shared.u32 %0, [%2];\n @p ld.shared.u32 %1, [%2 + 128]; }"
               : "+r"(a[2 * j]), "+r"(a[2 * j + 1]) : "r"(base + (j >> 1) * 256 + (j & 1) * 16), "r"((uint32_t)on) : "memory");
}
__device__ __forceinline__ void conv_mma(float* acc, const uint32_t* a, uint64_t db) {
  wgmma_rs_n256(acc, a, db, 0);
  wgmma_rs_n240(acc, a + 4, db + 16, 1);
  wgmma_rs_n224(acc, a + 8, db + 32, 1);
  wgmma_rs_n208(acc, a + 12, db + 48, 1);
  wgmma_rs_n192(acc, a + 16, db + 64, 1);
  wgmma_rs_n176(acc, a + 20, db + 80, 1);
  wgmma_rs_n160(acc, a + 24, db + 96, 1);
  wgmma_rs_n144(acc, a + 28, db + 112, 1);
  wgmma_rs_n128(acc, a + 32, db + 128, 1);
  wgmma_rs_n112(acc, a + 36, db + 144, 1);
  wgmma_rs_n96(acc, a + 40, db + 160, 1);
  wgmma_rs_n80(acc, a + 44, db + 176, 1);
  wgmma_rs_n64(acc, a + 48, db + 192, 1);
  wgmma_rs_n48(acc, a + 52, db + 208, 1);
  wgmma_rs_n32(acc, a + 56, db + 224, 1);
  wgmma_rs_n16(acc, a + 60, db + 240, 1);
}
__device__ __forceinline__ uint32_t conv_part(const float* acc, int j) {
  const int q = 31 - j;
  return q == 31 ? pack_bf16(acc[124], acc[125]) : pack_bf16(acc[4 * q] + acc[(4 * q + 6) & 127], acc[4 * q + 1] + acc[(4 * q + 7) & 127]);
}
__device__ __forceinline__ uint4 conv_sum(const uint4* p) {
  return make_uint4(sum4(p[0].x, p[1].x, p[2].x, p[3].x), sum4(p[0].y, p[1].y, p[2].y, p[3].y), sum4(p[0].z, p[1].z, p[2].z, p[3].z),
                    sum4(p[0].w, p[1].w, p[2].w, p[3].w));
}
template <int NV> __device__ __forceinline__ void gelu_stage(float* acc, const float* hb, uint32_t sa, int passes) {
#pragma unroll
  for (int i = 0; i < NV; i++) acc[i] = fmaf(acc[i], 0.5f, hb[(i >> 1) & 1]);
#pragma unroll 1
  for (; passes > 0; passes--, sa += NV * 256) {
#pragma unroll
    for (int i = 0; i < NV; i += 8)
      stsm4t(sa + i * 256, pack_bf16(gelu_half(acc[i]), gelu_half(acc[i + 1])), pack_bf16(gelu_half(acc[i + 2]), gelu_half(acc[i + 3])),
             pack_bf16(gelu_half(acc[i + 4]), gelu_half(acc[i + 5])), pack_bf16(gelu_half(acc[i + 6]), gelu_half(acc[i + 7])));
#pragma unroll
    for (int i = 0; i < NV; i++) acc[i] = fmaf(acc[NV + i], 0.5f, hb[2 + ((i >> 1) & 1)]);
  }
}

__global__ void __cluster_dims__(2, 1, 1) __launch_bounds__(384, 1) fused_kernel(const __grid_constant__ Hot H, const __grid_constant__ Params P) {
  extern __shared__ __align__(1024) uint8_t smem_raw[];
  const uint32_t t0 = clk();
  const uint32_t sb = smem_u32(smem_raw);
  const int tid = threadIdx.x, lane = tid & 31;
  const int bid = blockIdx.x, rank = bid & 1;
  const Role& R = P.role[bid];
  Scratch* const S = H.S;
  uint32_t xr[18];
  const int row = bid * 16 + (tid >> 4);
  if (tid < 256 && bid < 128) {
    const char* src = reinterpret_cast<const char*>(H.x) + row * (D_ * 2) + (lane & 15) * 8;
#pragma unroll
    for (int j = 0; j < 9; j++) asm volatile("ld.global.nc.v2.u32 {%0,%1}, [%2];" : "=r"(xr[2 * j]), "=r"(xr[2 * j + 1]) : "l"(src + 128 * j));
  }
  const int warp = __shfl_sync(0xffffffffu, tid >> 5, 0);

  if (warp >= 8) {
    const bool one = elect_one();
    if (warp == 8 && one) {
#pragma unroll
      for (int b = B_FULL; b <= B_DONE; b += 8) mbar_init(sb + b, b < B_EMPTY ? 1 : b < B_CEMPTY ? 2 : b < B_G1DONE ? 4 : 8);
      asm volatile("fence.mbarrier_init.release.cluster;" ::: "memory");
    }
    __syncwarp();
    asm volatile("barrier.cluster.arrive.relaxed.aligned;" ::: "memory");
    asm volatile("setmaxnreg.dec.sync.aligned.u32 56;");
    asm volatile("barrier.cluster.wait.aligned;" ::: "memory");
    const bool left = R.at == 15;
    if (warp == 8) {
      const uint32_t ep = ldg32(S->cnt + C_EPOCH * 32);
      if (one) {
#pragma unroll 1
        for (int i = 0; i < 11; i++) asm volatile("prefetch.tensormap [%0];" :: "l"(&P.m_w1 + i) : "memory");
#pragma unroll 1
        for (int s = 0; s < NWE; s++) {
          mbar_expect_tx(sb + B_FULL + 8 * s, G1_BYTES);
          tma3d(sb + s * SLOT, &P.m_w1 + left, 0, s * 64, R.fg, sb + B_FULL + 8 * s);
        }
      }
      __syncwarp();
      if (bid < 128) bar_sync(2, 288);
      if (one) {
        TLREC(31);
        signal(S, C_H, EPOCH / 132);
        TLREC(1);
        const uint32_t boff = left ? 24576 : 16384;
        int kr = bid < 128 ? -3 : KV_ROUNDS, ks = 2;
        auto kv_step = [&]() {
          const int q = (kr + 3) % 3;
          if (ks < 2) {
            if (!mbar_test(sb + B_KFULL + 8 * q, kr >= 3)) return;
            fence_async_smem();
            tma3d_store(&P.m_ub, sb + SM_DED + q * 6144 + ks * 3072, 16 * (127 - bid), kr * 48, 2 * ks);
            bulk_commit();
            ks++;
          } else {
            bulk_wait_all();
            if (kr < KV_ROUNDS - 3) {
              const uint32_t in = sb + SM_CV + q * 7936, fb = sb + B_UFULL + 8 * q;
              mbar_expect_tx(fb, 3840 + 3264 + 768);
              tma2d(in, &P.m_k, (kr + 3) * 96, bid * 16 - 4, fb);
              tma2d(in + 3840, &P.m_v, (kr + 3) * 96, bid * 16 - 1, fb);
              bulk_load(in + 7168, H.shift_k + (kr + 3) * 384, 768, fb);
            }
            if (++kr >= 0) ks = 0;
            if (kr == KV_ROUNDS) mbar_arrive(sb + B_KVDONE);
          }
        };
        if (bid >= 128) mbar_arrive(sb + B_KVDONE);
        Ring r{0, 1};
#pragma unroll 1
        for (int kb = NWE - NW0; kb < G1_KB || kr < KV_ROUNDS; kb++) {
          if (kb < G1_KB) {
          const int kw = kb < 0 ? kb + NW0 : kb, s = kb < 0 ? kw : r.s;
          const uint32_t fb = sb + B_FULL + 8 * s;
          if (kb < 0 || kb >= NW0) {
            mbar_wait(sb + B_EMPTY + 8 * s, r.ph);
            mbar_expect_tx(fb, G1_BYTES);
            tma3d(sb + s * SLOT, &P.m_w1 + left, 0, kw * 64, R.fg, fb);
            if (kb < 0) continue;
          }
          if (kb == 0) { await(S, C_H, ep); fence_async_global(); TLREC(2); }
          bulk_load(sb + s * SLOT + boff, S->h + (kb * 18 + R.at) * 2048, G1_BYTES - boff, fb);
          if (kb == NSTAGE - 1) {
            mbar_expect_tx(sb + B_MISC, boff / 64 + 1152);
            bulk_load(sb + SM_B1, H.b1 + R.fg * 64, boff / 64, sb + B_MISC);
            bulk_load(sb + SM_D, H.ssm_D, 1152, sb + B_MISC);
          }
          r.next();
          }
          if (kb >= KV0 && kr < KV_ROUNDS) kv_step();
        }
        await(S, C_KV, ep);
        fence_async_global();
#pragma unroll 1
        for (int i = 0; i < R.ncv; i++) {
          if (i == 2) {
            if (R.sg >= 0) {
#pragma unroll 1
              for (int s = 2; s < NSTAGE; s++) {
                mbar_wait(sb + B_EMPTY + 8 * s, ((G1_KB / NSTAGE) - 1) & 1);
                mbar_expect_tx(sb + B_FULL + 8 * s, G2_BYTES);
                tma3d(sb + s * SLOT, &P.m_w2, 0, (rank * G2_KB + s - 2) * 64, R.sg, sb + B_FULL + 8 * s);
              }
            }
            mbar_wait(sb + B_G1DONE, 0);
          }
          const uint32_t kt = sb + cv_taps(i), b8 = sb + 8 * (i & 3);
          mbar_wait(b8 + B_CEMPTY, ((i >> 2) & 1) ^ 1);
          sts128(kt, 0, 0, 0, 0); sts128(kt + 16, 0, 0, 0, 0);
          mbar_expect_tx(b8 + B_KFULL, 4096);
          bulk_load(kt + 32, H.ssm_k + (R.ch + i) * S_, 4096, b8 + B_KFULL);
          mbar_expect_tx(b8 + B_UFULL, 8192);
          bulk_load(sb + cv_in(i), S->ub + (R.ch + i) * 4096, 8192, b8 + B_UFULL);
        }
        if (R.sg >= 0) {
          mbar_expect_tx(sb + B_XY, 2 * 18432 + 2048 + 256);
          mbar_expect_tx(sb + B_XFULL, 9216);
          mbar_expect_tx(sb + B_XFULL + 8, 9216);
          await(S, C_U, ep);
          fence_async_global();
          TLREC(6);
#pragma unroll 1
          for (int kb = 0; kb < G2_KB; kb++, r.next()) {
            const int k0 = (rank * G2_KB + kb) * 64;
            const uint32_t fb = sb + B_FULL + 8 * r.s, slot = sb + r.s * SLOT;
            if (kb >= NSTAGE - 2) {
              mbar_wait(sb + B_EMPTY + 8 * r.s, r.ph);
              if (kb == NSTAGE) asm volatile("red.relaxed.gpu.global.add.u32 [%0], %1;" :: "l"(S->cnt + C_SYNC * 32), "r"(EPOCH / 128) : "memory");
              if (kb == SYNCKB) await(S, C_SYNC, ep);
              mbar_expect_tx(fb, G2_BYTES);
              tma3d(slot, &P.m_w2, 0, k0, R.sg, fb);
            }
            tma2d(slot + 16384, &P.m_uld, k0, R.ds * 8, fb);
            tma2d(slot + 16384 + 9216, &P.m_uld, k0, R.dk * 8, fb);
            const uint32_t nx = kb - 8;
            if (nx < 8) tma2d(sb + SM_CV + nx * 2304, &P.m_x, R.dk * 8, R.sg * 64 + nx * 16, sb + B_XY);
          }
          bulk_load(sb + SM_ST, S->stats + R.sg * 64, 2048, sb + B_XY);
          bulk_load(sb + SM_B2, P.b2 + R.sg * 64, 256, sb + B_XY);
          await(S, C_Y, ep);
          fence_async_global();
          TLREC(19);
          tma3d(sb + SM_DED, &P.m_y, 0, R.dk * 8, R.sg, sb + B_XY);
          if (bid == 0) signal(S, C_EPOCH, EPOCH);
        }
      }
    } else {
      if (bid < 128) {
        const int ht = tid - 288, hf = ht >= 48, pr = ht - 48 * hf;
        const uint32_t st = sb + SM_DED + (1 - hf) * 1536 + pr * 32, sw = (pr & 4) * 4;
#pragma unroll 1
        for (int r = 0; r < KV_ROUNDS; r++) {
          const int q = r % 3;
          const uint32_t in = sb + SM_CV + q * 7936;
          {
            mbar_wait_guarded(sb + B_UFULL + 8 * q, t0, r >= 3);
            uint32_t kk[12], vv[9];
#pragma unroll
            for (int j = 0; j < 12; j++) kk[j] = lds32(in + hf * 1536 + pr * 4 + j * 192);
#pragma unroll
            for (int j = 0; j < 9; j++) vv[j] = lds32(in + 3840 + hf * 1536 + pr * 4 + j * 192);
            const uint4 w = lds128(in + 7168 + pr * 16);
            const uint32_t w0 = __byte_perm(w.x, w.z, 0x5410), w1 = __byte_perm(w.x, w.z, 0x7632);
            const uint32_t w2 = __byte_perm(w.y, w.w, 0x5410), w3 = __byte_perm(w.y, w.w, 0x7632);
#pragma unroll
            for (int j = 0; j < 9; j++)
              vv[j] = bmul2(badd2(badd2(badd2(bmul2(kk[j], w3), bmul2(kk[j + 1], w2)), bmul2(kk[j + 2], w1)), bmul2(kk[j + 3], w0)), vv[j]);
#pragma unroll
            for (int c = 0; c < 2; c++)
#pragma unroll
              for (int pi = 0; pi < 2; pi++) {
                const uint32_t sel = c ? 0x7632 : 0x5410;
                sts128(st + q * 6144 + c * 3072 + (pi * 16 ^ sw), __byte_perm(vv[7 + pi], vv[6 + pi], sel), __byte_perm(vv[5 + pi], vv[4 + pi], sel),
                       __byte_perm(vv[3 + pi], vv[2 + pi], sel), __byte_perm(vv[1 + pi], vv[pi], sel));
              }
            bar_sync(1, 96);
            if (ht == 0) mbar_arrive(sb + B_KFULL + 8 * q);
          }
          __syncwarp();
        }
      }
      if (one) {
        if (warp < 11) {
          const int wg = warp - 9;
          mbar_wait_guarded(sb + B_STG + 8 * wg, t0);
          fence_async_smem();
          TLREC(13 + wg);
#pragma unroll 1
          for (int j = 0; j < (left ? 3 + 3 * wg : 5); j++) {
            const int hi = left && j >= 3;
            tma2d_store(&P.m_ust, sb + (wg ? SM_ST1 : SM_DED) + j * 4096, (R.fg + wg + hi) * 64, (R.at + j - 3 * hi) * 32);
          }
          bulk_commit();
          bulk_wait_all();
          mbar_arrive(sb + B_SFREE + 8 * wg);
          signal(S, C_U, EPOCH / 264);
          TLREC(15 + wg);
        } else {
          mbar_wait_guarded(sb + B_KVDONE, t0);
          signal(S, C_KV, EPOCH / 132);
          TLREC(27);
          mbar_wait_guarded(sb + B_YDONE, t0);
          signal(S, C_Y, EPOCH / 132);
          if (R.sg >= 0) mbar_wait_guarded(sb + B_DONE, t0);
        }
      }
    }
    TLEND();
  } else {
    asm volatile("barrier.cluster.arrive.relaxed.aligned;" ::: "memory");
    if (bid < 128) {
      float c[36], s[4];
#pragma unroll
      for (int i = 0; i < 18; i++) { c[2 * i] = bf_lo(xr[i]); c[2 * i + 1] = bf_hi(xr[i]); }
#pragma unroll
      for (int i = 0; i < 36; i++) s[i & 3] = i < 4 ? c[i] : s[i & 3] + c[i];
      const float ml = ((s[0] + s[1]) + (s[2] + s[3])) * (1.0f / 36.0f);
#pragma unroll
      for (int i = 0; i < 36; i++) { c[i] -= ml; s[i & 3] = i < 4 ? c[i] * c[i] : fmaf(c[i], c[i], s[i & 3]); }
      float m = ml, q = (s[0] + s[1]) + (s[2] + s[3]), n2 = 18.f;
#pragma unroll
      for (int o = 1; o < 16; o <<= 1) {
        const float mo = __shfl_xor_sync(0xffffffffu, m, o), qo = __shfl_xor_sync(0xffffffffu, q, o);
        const float dl = m - mo;
        q = fmaf(dl * dl, n2, q + qo);
        m = fmaf(dl, -0.5f, m);
        n2 *= 2.f;
      }
      const float var = q * (1.0f / 576.0f);
      float mb, rinv, mb2, rinv2;
      ln_finish(m, var, mb, rinv);
      ln_finish((m - mb) * rinv, var * rinv * rinv, mb2, rinv2);
      const float ca = rinv * rinv2, cb = fmaf(ml - mb, rinv, -mb2) * rinv2;
      uint2* dst = reinterpret_cast<uint2*>(S->h) + ((row >> 6) * 18 + ((lane >> 3) & 1)) * 512 + (row & 63) * 8 + ((lane & 7) ^ (row & 6));
#pragma unroll
      for (int j = 0; j < 9; j++)
        dst[1024 * j] = make_uint2(pack_bf16(fmaf(c[4 * j], ca, cb), fmaf(c[4 * j + 1], ca, cb)), pack_bf16(fmaf(c[4 * j + 2], ca, cb), fmaf(c[4 * j + 3], ca, cb)));
      const uint32_t rh = pack_bf16(rinv, rinv);
      if (!(lane & 15)) S->stats[row] = make_uint4(pack_bf16(mb, mb), rh, pack_bf16(rinv - bf_lo(rh), rinv - bf_lo(rh)), 0);
      __syncwarp();
      bar_arrive(2, 288);
    }
    asm volatile("setmaxnreg.inc.sync.aligned.u32 224;");
    asm volatile("barrier.cluster.wait.aligned;" ::: "memory");
    const int wg = warp >> 2, w = warp & 3, g = lane >> 2, t = lane & 3, wtid = tid & 127;
    const bool elect = wtid == 0;
    const uint64_t da0 = make_desc(sb + wg * 8192, 8192, 1024, 1);
    const uint32_t swz = ((lane >> 4) * 8 + (lane & 7)) * 128 + (((2 * w + ((lane >> 3) & 1)) ^ (lane & 7)) << 4);
    const uint32_t stg = sb + (wg ? SM_ST1 : SM_DED);
    {
      auto mainloop = [&](auto&& mma) {
        Ring r{0, 0};
        uint32_t rel = 0;
#pragma unroll 1
        for (int kb = 0; kb < G1_KB; kb++, r.next()) {
          if (kb == G1_KB - G1_TAIL && wg) {
            wg_wait<0>();
            if (elect) mbar_arrive(rel);
            rel = 0;
            bar_sync(5, 256);
          }
          mbar_wait(sb + B_FULL + 8 * r.s, r.ph);
          if (kb == 0 && warp == 0) TLREC(3);
          wg_fence();
          mma(r.s * (SLOT >> 4), kb);
          wg_commit();
          if (kb == G1_KB - 1) break;
          wg_wait<1>();
          if (elect && rel) mbar_arrive(rel);
          rel = sb + B_EMPTY + 8 * r.s;
        }
        bar_arrive(5, 256);
        wg_wait<0>();
      };
      float hb[4];
      auto staged = [&](int second) {
        if (!w) TLREC(4 + wg);
        if (lane == 0) mbar_arrive(sb + B_G1DONE);
        mbar_wait(sb + B_MISC, 0);
#pragma unroll
        for (int i = 0; i < 4; i++) hb[i] = 0.5f * bf_lo(lds16(sb + SM_B1 + (warp * 16 + g + (i & 1) * 8 + (i >> 1) * second) * 2));
        mbar_wait(sb + B_KVDONE, 0);
        if (wg) mbar_wait(sb + B_G1DONE, 0);
      };
      if (R.at != 15) {
        const uint64_t db0 = make_desc(sb + 16384, 4096, 512, 2);
        float acc[80];
        mainloop([&](uint32_t o, int kb) {
          wgmma_ss_n160_t11(acc, da0 + o, db0 + o, kb);
#pragma unroll
          for (int k = 1; k < 4; k++) wgmma_ss_n160_t11(acc, da0 + o + k * 128, db0 + o + k * 64, 1);
        });
        pin_regs<80>(acc);
        staged(0);
        gelu_stage<40>(acc, hb, stg + swz, 2);
      } else {
        const uint64_t db0 = make_desc(sb + 24576, 4096, 512, 2);
        float acc[96];
        auto block = [&](float* d, uint64_t da, uint64_t db, int kb) {
          wgmma_ss_n96_t11(d, da, db, kb);
#pragma unroll
          for (int k = 1; k < 4; k++) wgmma_ss_n96_t11(d, da + k * 128, db + k * 64, 1);
        };
        if (wg) mainloop([&](uint32_t o, int kb) { block(acc, da0 + o, db0 + o, kb); block(acc + 48, da0 + o + 512, db0 + o, kb); });
        else mainloop([&](uint32_t o, int kb) { block(acc, da0 + o, db0 + o, kb); });
        pin_regs<96>(acc);
        staged(64);
        gelu_stage<48>(acc, hb, stg + swz, 1 + wg);
      }
      __syncwarp();
      if (lane == 0) mbar_arrive(sb + B_STG + 8 * wg);
    }
    {
      const uint32_t ka0 = (8 * w + g + t + 1) * 4;
      uint32_t a[64];
      mbar_wait(sb + B_KFULL + 8 * wg, 0);
#pragma unroll
      for (int j = 0; j < 32; j++) conv_lda(a, j, sb + SM_CV + 16384 + wg * CV_K + ka0, true);
#pragma unroll 1
      for (int i = wg; i < R.ncv; i += 2) {
        const bool more = i + 2 < R.ncv;
        const uint32_t dd = lds16(sb + SM_D + (R.ch + i) * 2);
        a[0] = badd2(a[0], ka0 == 32 ? dd : 0); a[2] = badd2(a[2], ka0 == 16 ? dd : 0);
        float acc[128];
        mbar_wait(sb + B_UFULL + 8 * (i & 3), (i >> 2) & 1);
        if (!more) fence_async_smem();
        bar_sync(5 + wg, 256);
        if (!more && elect) mbar_arrive(sb + B_EMPTY);
        if (!w && i < 4) TLREC(22 + i);
        wg_fence();
        conv_mma(acc, a, make_desc(sb + cv_in(i), 4096, 128, 0));
        wg_commit();
        const bool last = i + 1 == R.ncv;
        if (!last) bar_arrive(5 + (wg ^ 1), 256);
        mbar_wait(sb + B_SFREE + 8 * wg, 0);
        if (more) mbar_wait(sb + B_KFULL + 8 * ((i + 2) & 3), ((i + 2) >> 2) & 1);
        if (i == 0 && !w) TLREC(7);
        wg_wait<0>();
        pin_regs<128>(acc);
        if (lane == 0) mbar_arrive(sb + B_CEMPTY + 8 * (i & 3));
        if (!more && elect) mbar_arrive(sb + B_EMPTY + 8);
        const uint32_t red = last ? sb + SM_CV : stg, ka = sb + cv_taps(i + 2) + ka0;
        if (lane < 8 * w) sts32(red + w * CV_REDW + lane * 4, 0);
        const uint32_t wr = red + w * CV_REDW + (8 * (3 - t + w) + g) * 4;
#pragma unroll
        for (int j = 0; j < 32; j++) {
          if (j < 24) conv_lda(a, j, ka, more);
          sts32(wr + j * 128, conv_part(acc, j));
        }
        bar_sync(3 + wg, 128);
        uint4 p[2][4];
#pragma unroll
        for (int x = 0; x < 8; x++) p[x >> 2][x & 3] = lds128(red + (x & 3) * CV_REDW + (wtid + 128 * (x >> 2)) * 16);
#pragma unroll
        for (int j = 24; j < 32; j++) conv_lda(a, j, ka, more);
        uint4* yo = reinterpret_cast<uint4*>(S->y + (R.ch + i) * S_) + wtid;
        yo[0] = conv_sum(p[0]); yo[128] = conv_sum(p[1]);
      }
      fence_async_smem();
      __syncwarp();
      if (lane == 0) mbar_arrive(sb + B_YDONE);
      if (!w) TLREC(20 + wg);
    }
    if (R.sg >= 0) {
      const int srow = R.sg * 64 + warp * 16;
      const uint64_t db0 = make_desc(sb + 16384, 16, 1024, 1);
      const uint32_t xo = sb + SM_CV + warp * 2304, xa = xo + (lane & 15) * 144;
      float acc[72];
      Ring r{G1_KB % NSTAGE, (G1_KB / NSTAGE) & 1};
      uint32_t rel = 0;
#pragma unroll 1
      for (int kb = 0; kb < G2_KB; kb++, r.next()) {
        if (kb == G2_KB - G2_TAIL && wg) {
          wg_wait<0>();
          if (elect) mbar_arrive_remote(rel);
          rel = 0;
          bar_sync(7, 256);
        }
        mbar_wait(sb + B_FULL + 8 * r.s, r.ph);
        if (kb == 0 && !w) TLREC(17 + wg);
        if (kb == 8 && warp == 0) TLREC(26);
        if (kb == 20 && warp == 0) TLREC(8);
        if (kb == 27 && warp == 0) TLREC(30);
        const uint64_t da = da0 + r.s * (SLOT >> 4), db = db0 + r.s * (SLOT >> 4);
        wg_fence();
        wgmma_ss_n144_t10(acc, da, db, kb);
#pragma unroll
        for (int k = 1; k < 4; k++) wgmma_ss_n144_t10(acc, da + k * 128, db + k * 2, 1);
        wg_commit();
        if (kb == G2_KB - 1) break;
        wg_wait<1>();
        if (elect && rel) mbar_arrive_remote(rel);
        rel = kb == G2_KB - NSTAGE ? mapa(sb + B_XRDY, rank ^ 1) : sb + B_EMPTY + 8 * r.s;
      }
      if (!wg) bar_arrive(7, 256);
      const uint32_t xz = sb + XSLOT * SLOT + wg * 10240 + wtid * 16;
      const uint32_t rz = mapa(xz, rank ^ 1), rb = mapa(sb + B_XFULL + 8 * wg, rank ^ 1);
      mbar_wait(sb + B_XRDY, 0);
      wg_wait<0>();
      pin_regs<72>(acc);
      if (!w) TLREC(28 + wg);
#pragma unroll
      for (int i = 0; i < 32; i += 8)
        asm volatile("st.async.weak.shared::cluster.mbarrier::complete_tx::bytes.v4.b32 [%0], {%1,%2,%3,%4}, [%5];"
                     :: "r"(rz + i * 256), "r"(pack_bf16(acc[i], acc[i + 1])), "r"(pack_bf16(acc[i + 2], acc[i + 3])),
                        "r"(pack_bf16(acc[i + 4], acc[i + 5])), "r"(pack_bf16(acc[i + 6], acc[i + 7])), "r"(rb) : "memory");
      asm volatile("st.async.weak.shared::cluster.mbarrier::complete_tx::bytes.v2.b32 [%0], {%1,%2}, [%3];"
                   :: "r"(rz + 8192), "r"(pack_bf16(acc[32], acc[33])), "r"(pack_bf16(acc[34], acc[35])), "r"(rb) : "memory");
      uint32_t xx[18], ss[18];
      mbar_wait(sb + B_XY, 0);
      {
        const uint32_t ya = sb + SM_DED + wg * 9216 + swz;
        const uint4 st0 = lds128(sb + SM_ST + (warp * 16 + g) * 16), st1 = lds128(sb + SM_ST + (warp * 16 + g + 8) * 16);
        const float hb0 = 0.5f * bf_lo(lds16(sb + SM_B2 + (warp * 16 + g) * 2)), hb1 = 0.5f * bf_lo(lds16(sb + SM_B2 + (warp * 16 + g + 8) * 2));
#pragma unroll
        for (int q = 0; q < 8; q += 2) { ldsm4(xx + 2 * q, xa + (lane >> 4) * 16 + q * 16); ldsm4t(ss + 2 * q, ya + q * 1024); }
        ldsm2(xx + 16, xa + 128);
        ldsm2t(ss + 16, ya + 8 * 1024);
#pragma unroll
        for (int i = 0; i < 18; i++) {
          const uint4& st = (i & 1) ? st1 : st0;
          const uint32_t c = bsub2(xx[i], st.x);
          ss[i] = bmul2(bfma2(c, st.y, bmul2(c, st.z)), ss[i]);
        }
#pragma unroll
        for (int i = 36; i < 72; i++) acc[i] = fmaf(acc[i], 0.5f, (i & 2) ? hb1 : hb0);
      }
      mbar_wait_cluster(sb + B_XFULL + 8 * wg, 0);
      if (!w) TLREC(9 + wg);
#pragma unroll
      for (int q = 0; q < 5; q++) {
        const uint4 v = lds128(xz + q * 2048);
        const uint32_t pv[4] = {v.x, v.y, v.z, v.w};
#pragma unroll
        for (int i = 4 * q; i < 4 * q + 4 && i < 18; i++)
          xx[i] = bfma2(ss[i], pack_bf16(silu_half(fmaf(bf_lo(pv[i & 3]), 0.5f, acc[36 + 2 * i])), silu_half(fmaf(bf_hi(pv[i & 3]), 0.5f, acc[37 + 2 * i]))), xx[i]);
        if (q < 4) stsm4(xa + (lane >> 4) * 16 + q * 32, xx[4 * q], xx[4 * q + 1], xx[4 * q + 2], xx[4 * q + 3]);
        else stsm2(xa + 128, xx[16], xx[17]);
      }
      __syncwarp();
      if (elect_one()) {
        fence_async_smem();
        tma2d_store(&P.m_out, xo, R.dk * 8, srow);
        bulk_commit();
        mbar_arrive(sb + B_DONE);
        bulk_wait_read();
      }
      if (!w) TLREC(11 + wg);
    }
    TLEND();
  }
}

typedef CUresult (*EncodeFn)(CUtensorMap*, CUtensorMapDataType, cuuint32_t, void*, const cuuint64_t*, const cuuint64_t*, const cuuint32_t*,
                             const cuuint32_t*, CUtensorMapInterleave, CUtensorMapSwizzle, CUtensorMapL2promotion, CUtensorMapFloatOOBfill);

void make_map(EncodeFn fn, CUtensorMap* m, const void* ptr, int rank, const cuuint64_t* dims, const cuuint64_t* strides, const cuuint32_t* box,
              CUtensorMapSwizzle sw) {
  const cuuint32_t es[3] = {1, 1, 1};
  fn(m, CU_TENSOR_MAP_DATA_TYPE_BFLOAT16, rank, const_cast<void*>(ptr), dims, strides, box, es, CU_TENSOR_MAP_INTERLEAVE_NONE, sw,
     CU_TENSOR_MAP_L2_PROMOTION_L2_256B, CU_TENSOR_MAP_FLOAT_OOB_FILL_NONE);
}

void make_roles(Role* R) {
  int nl = 0, ch = 0;
  for (int gi = 0; gi < 8; gi++)
    for (int b = 0; b < 132; b++) {
      const int c = b >> 1, rank = b & 1;
      int g, idx;
      if (c < 4) { g = 0; idx = 4 + c; }
      else if (c < 36) { g = (c - 4) & 7; idx = (c - 4) >> 3; }
      else if (c < 64) { g = 1 + (c - 36) % 7; idx = 4 + (c - 36) / 7; }
      else { g = c - 58; idx = 8; }
      if (g != gi) continue;
      Role& r = R[b];
      r.sg = (int8_t)(idx < 8 ? 2 * (2 * g + (idx >> 2)) : -1);
      r.dk = (int8_t)((idx & 3) * 18 + rank * 9);
      r.ds = (int8_t)((idx & 3) * 18 + (rank ^ 1) * 9);
      if (idx < (g < 2 ? 6 : 7)) {
        const int c1 = (g < 2 ? 6 * g : 7 * g - 2) + idx;
        r.fg = (int8_t)((2 * (c1 / 3) + rank) * 2); r.at = (int8_t)(c1 % 3 * 5); r.ncv = NCV_REG;
      } else {
        r.fg = (int8_t)(3 * nl++); r.at = 15; r.ncv = idx < 8 ? NCV_LEFT : NCV_LONG;
      }
      r.ch = (int16_t)ch;
      ch += r.ncv;
    }
}

}

extern "C" void kernel_launch(void* const* d_in, const int* in_sizes, int n_in, void* d_out, int out_size) {
  static Params P;
  static Hot H;
  static const void* cached[6] = {nullptr, nullptr, nullptr, nullptr, nullptr, nullptr};
  const void* now[6] = {d_in[0], d_in[1], d_in[2], d_in[7], d_in[9], d_out};
  bool same = true;
  for (int i = 0; i < 6; i++) { same = same && cached[i] == now[i]; cached[i] = now[i]; }
  if (!same) {
    void* fp = nullptr;
    cudaDriverEntryPointQueryResult qr;
    cudaGetDriverEntryPoint("cuTensorMapEncodeTiled", &fp, cudaEnableDefault, &qr);
    EncodeFn fn = (EncodeFn)fp;
    void* ps;
    cudaGetSymbolAddress(&ps, g_scratch);
    H.S = (Scratch*)ps;
    const void *pu = (char*)ps + offsetof(Scratch, u), *py = (char*)ps + offsetof(Scratch, y), *pb = (char*)ps + offsetof(Scratch, ub);
    { cuuint64_t d[3] = {64, S_, F_ / 64}, s[2] = {F_ * 2, 128}; cuuint32_t b[3] = {64, 64, 2}; make_map(fn, &P.m_w1, d_in[7], 3, d, s, b, CU_TENSOR_MAP_SWIZZLE_128B);
      b[2] = 3; make_map(fn, &P.m_w1l, d_in[7], 3, d, s, b, CU_TENSOR_MAP_SWIZZLE_128B); }
    { cuuint64_t d[2] = {F_, D_}, s[1] = {F_ * 2}; cuuint32_t b[2] = {64, 32}; make_map(fn, &P.m_ust, pu, 2, d, s, b, CU_TENSOR_MAP_SWIZZLE_128B); }
    { cuuint64_t d[3] = {64, F_, S_ / 64}, s[2] = {S_ * 2, 128}; cuuint32_t b[3] = {64, 64, 2}; make_map(fn, &P.m_w2, d_in[9], 3, d, s, b, CU_TENSOR_MAP_SWIZZLE_128B); }
    { cuuint64_t d[2] = {F_, D_}, s[1] = {F_ * 2}; cuuint32_t b[2] = {64, 72}; make_map(fn, &P.m_uld, pu, 2, d, s, b, CU_TENSOR_MAP_SWIZZLE_128B); }
    { cuuint64_t d[2] = {D_, S_}, s[1] = {D_ * 2}; cuuint32_t b[2] = {72, 16}; make_map(fn, &P.m_out, d_out, 2, d, s, b, CU_TENSOR_MAP_SWIZZLE_NONE);
      make_map(fn, &P.m_x, d_in[0], 2, d, s, b, CU_TENSOR_MAP_SWIZZLE_NONE);
      b[0] = 96; b[1] = 20; make_map(fn, &P.m_k, d_in[1], 2, d, s, b, CU_TENSOR_MAP_SWIZZLE_NONE);
      b[1] = 17; make_map(fn, &P.m_v, d_in[2], 2, d, s, b, CU_TENSOR_MAP_SWIZZLE_NONE); }
    { cuuint64_t d[3] = {64, D_, S_ / 64}, s[2] = {S_ * 2, 128}; cuuint32_t b[3] = {64, 72, 2}; make_map(fn, &P.m_y, py, 3, d, s, b, CU_TENSOR_MAP_SWIZZLE_128B); }
    { cuuint64_t d[3] = {2048, D_ / 2, 4}, s[2] = {16384, 4096}; cuuint32_t b[3] = {16, 48, 2}; make_map(fn, &P.m_ub, pb, 3, d, s, b, CU_TENSOR_MAP_SWIZZLE_32B); }
    make_roles(P.role);
    cudaFuncSetAttribute(fused_kernel, cudaFuncAttributeMaxDynamicSharedMemorySize, SM_TOTAL);
  }
  H.x = (const __nv_bfloat16*)d_in[0];
  H.shift_k = (const __nv_bfloat16*)d_in[3]; H.ssm_k = (const __nv_bfloat16*)d_in[4]; H.ssm_D = (const __nv_bfloat16*)d_in[5];
  H.b1 = (const __nv_bfloat16*)d_in[8]; P.b2 = (const __nv_bfloat16*)d_in[10];
  fused_kernel<<<132, 384, SM_TOTAL>>>(H, P);
}
```

```cpp
#include <cuda_runtime.h>
#include <cuda.h>
#include <cuda_bf16.h>
#include <stddef.h>
#include <stdint.h>

namespace {

constexpr int S_ = 2048, D_ = 576, F_ = 4608;
constexpr int NSTAGE = 5, SLOT = 36864;
constexpr int G1_KB = 32, G2_KB = 36;
constexpr int G1_BYTES = 36864, G2_BYTES = 16384 + 18432;
#define NCV_LEFT 4
constexpr int NCV_REG = 4, NCV_LONG = (D_ - 108 * NCV_REG - 20 * NCV_LEFT) / 4;
static_assert(108 * NCV_REG + 20 * NCV_LEFT + 4 * NCV_LONG == D_, "conv split");
constexpr int KV_ROUNDS = 6;
constexpr int NWE = 0, NW0 = 1;
constexpr int G1_TAIL = 4, G2_TAIL = 3;
constexpr int SYNCKB = 5;
constexpr int PRE1 = 1;
constexpr int KV0 = 5;

constexpr int CV_K = 4224, CV_REDW = 2112 * 2;
constexpr int SM_DED = NSTAGE * SLOT;
constexpr int SM_CV = SM_DED + 20480;
constexpr int SM_ST1 = 0;
constexpr int SM_ST = SM_CV + 18432, SM_B2 = SM_ST + 2048;
constexpr int SM_B1 = SM_CV + 2 * (8192 + CV_K), SM_D = SM_B1 + 384;
constexpr int SM_BAR = SM_D + 1152;
constexpr int SM_TOTAL = SM_BAR + 768;
static_assert(G1_KB % NSTAGE == 2, "slots 0 and 1 hold the last GEMM1 k-blocks and the last two of the first GEMM2 stages");
static_assert(NCV_REG == 4 && NCV_LEFT == 4 && NCV_LONG % 4 == 0, "the last two channels use buffers 2 and 3");
constexpr int XSLOT = (G1_KB + G2_KB) % NSTAGE;
__device__ __forceinline__ uint32_t kv_buf(int q) { return q == 2 ? SM_DED : SM_CV + q * 8192; }
__device__ __forceinline__ uint32_t cv_red(int i, int n) { return i + 2 == n ? SM_CV : (i & 1) && i + 1 < n ? SM_ST1 : SM_DED; }
__device__ __forceinline__ uint32_t cv_in(int i) { return (i & 2 ? SLOT : SM_CV) + (i & 1) * 8192; }
__device__ __forceinline__ uint32_t cv_taps(int i) { return (i & 2 ? SM_ST1 + 24576 : SM_CV + 16384) + (i & 1) * CV_K; }
constexpr int bar_at(int i) { return SM_BAR + 8 * i; }
constexpr int B_FULL = bar_at(0)  , B_KFULL = bar_at(5)  , B_UFULL = bar_at(9)  , B_KVDONE = bar_at(13), B_STORED = bar_at(14)  ,
              B_XFULL = bar_at(16)  , B_XY = bar_at(18), B_MISC = bar_at(19),
              B_EMPTY = bar_at(20)  , B_XRDY = bar_at(25),
              B_SFREE = bar_at(26)  , B_PDONE = bar_at(28),
              B_CEMPTY = bar_at(29)  , B_STG = bar_at(33)  ,
              B_G1DONE = bar_at(37), B_DONE = bar_at(38);
constexpr int C_H = 0, C_KV = 1, C_U = 2, C_Y = 3, C_SYNC = 4, C_EPOCH = 5, C_COUNT = 6;
constexpr uint32_t EPOCH = 256 * 33;

struct Scratch {
  uint32_t cnt[C_COUNT * 32];
  alignas(1024) uint4 stats[S_];
  alignas(1024) __nv_bfloat16 h[S_ * D_];
  alignas(1024) __nv_bfloat16 ub[D_ * 4096];
  alignas(1024) __nv_bfloat16 y[D_ * S_];
  alignas(1024) __nv_bfloat16 u[D_ * F_];
};
__device__ Scratch g_scratch;

struct Hot {
  const __nv_bfloat16 *x, *shift_k, *ssm_k, *ssm_D, *b1;
  Scratch* S;
};
struct Role {
  int8_t fg;
  int8_t at;
  int8_t sg;
  int8_t dk, ds;
  int8_t ncv;
  int16_t ch;
};
struct Params {
  const __nv_bfloat16* b2;
  Role role[132];
  CUtensorMap m_w1, m_w1l, m_ust, m_w2, m_uld, m_out, m_x, m_y, m_k, m_v, m_ub;
};

#define TLREC(i) do { } while (0)
#define TLEND() do { } while (0)

__device__ __forceinline__ uint32_t smem_u32(const void* p) { return (uint32_t)__cvta_generic_to_shared(p); }
__device__ __forceinline__ void mbar_init(uint32_t bar, uint32_t cnt) { asm volatile("mbarrier.init.shared::cta.b64 [%0], %1;" :: "r"(bar), "r"(cnt) : "memory"); }
__device__ __forceinline__ void mbar_expect_tx(uint32_t bar, uint32_t bytes) { asm volatile("mbarrier.arrive.expect_tx.shared::cta.b64 _, [%0], %1;" :: "r"(bar), "r"(bytes) : "memory"); }
__device__ __forceinline__ void mbar_arrive(uint32_t bar) { asm volatile("mbarrier.arrive.shared::cta.b64 _, [%0];" :: "r"(bar) : "memory"); }
__device__ __forceinline__ uint32_t mapa(uint32_t addr, uint32_t cta) { uint32_t r; asm volatile("mapa.shared::cluster.u32 %0, %1, %2;" : "=r"(r) : "r"(addr), "r"(cta)); return r; }
__device__ __forceinline__ void mbar_arrive_remote(uint32_t rbar) { asm volatile("mbarrier.arrive.shared::cluster.b64 _, [%0];" :: "r"(rbar) : "memory"); }
__device__ __forceinline__ uint32_t clk() { uint32_t c; asm volatile("mov.u32 %0, %%clock;" : "=r"(c)); return c; }
__device__ __forceinline__ bool elect_one() {
  uint32_t p; asm volatile("{ .reg .pred p; elect.sync _|p, 0xffffffff; selp.u32 %0, 1, 0, p; }" : "=r"(p)); return p;
}
__device__ __forceinline__ void guard(uint32_t t0) { if ((int32_t)(clk() - t0) < 0) __trap(); }
__device__ __forceinline__ void mbar_wait(uint32_t bar, uint32_t parity) {
  asm volatile("{\n .reg .pred p;\n W_%=:\n mbarrier.try_wait.parity.shared::cta.b64 p, [%0], %1;\n @!p bra W_%=;\n }" :: "r"(bar), "r"(parity) : "memory");
}
__device__ __forceinline__ void mbar_wait_cluster(uint32_t bar, uint32_t parity) {
  asm volatile("{\n .reg .pred p;\n W_%=:\n mbarrier.try_wait.parity.acquire.cluster.shared::cta.b64 p, [%0], %1;\n @!p bra W_%=;\n }" :: "r"(bar), "r"(parity) : "memory");
}
__device__ __forceinline__ bool mbar_try(uint32_t bar, uint32_t parity) {
  uint32_t ok;
  asm volatile("{ .reg .pred p; mbarrier.try_wait.parity.shared::cta.b64 p, [%1], %2, 100000; selp.u32 %0, 1, 0, p; }" : "=r"(ok) : "r"(bar), "r"(parity) : "memory");
  return ok;
}
__device__ __forceinline__ bool mbar_test(uint32_t bar, uint32_t parity) {
  uint32_t ok;
  asm volatile("{ .reg .pred p; mbarrier.test_wait.parity.shared::cta.b64 p, [%1], %2; selp.u32 %0, 1, 0, p; }" : "=r"(ok) : "r"(bar), "r"(parity) : "memory");
  return ok;
}
__device__ __forceinline__ void mbar_wait_guarded(uint32_t bar, uint32_t t0, uint32_t parity = 0) { while (!mbar_try(bar, parity)) guard(t0); }
__device__ __forceinline__ void tma2d(uint32_t dst, const CUtensorMap* m, int c0, int c1, uint32_t bar) {
  asm volatile("cp.async.bulk.tensor.2d.shared::cluster.global.mbarrier::complete_tx::bytes [%0], [%1, {%3, %4}], [%2];"
               :: "r"(dst), "l"(m), "r"(bar), "r"(c0), "r"(c1) : "memory");
}
__device__ __forceinline__ void tma3d(uint32_t dst, const CUtensorMap* m, int c0, int c1, int c2, uint32_t bar) {
  asm volatile("cp.async.bulk.tensor.3d.shared::cluster.global.mbarrier::complete_tx::bytes [%0], [%1, {%3, %4, %5}], [%2];"
               :: "r"(dst), "l"(m), "r"(bar), "r"(c0), "r"(c1), "r"(c2) : "memory");
}
__device__ __forceinline__ void tma2d_store(const CUtensorMap* m, uint32_t src, int c0, int c1) {
  asm volatile("cp.async.bulk.tensor.2d.global.shared::cta.bulk_group [%0, {%2, %3}], [%1];" :: "l"(m), "r"(src), "r"(c0), "r"(c1) : "memory");
}
__device__ __forceinline__ void bulk_load(uint32_t dst, const void* src, uint32_t bytes, uint32_t bar) {
  asm volatile("cp.async.bulk.shared::cluster.global.mbarrier::complete_tx::bytes [%0], [%1], %2, [%3];" :: "r"(dst), "l"(src), "r"(bytes), "r"(bar) : "memory");
}
__device__ __forceinline__ void tma3d_store(const CUtensorMap* m, uint32_t src, int c0, int c1, int c2) {
  asm volatile("cp.async.bulk.tensor.3d.global.shared::cta.bulk_group [%0, {%2, %3, %4}], [%1];" :: "l"(m), "r"(src), "r"(c0), "r"(c1), "r"(c2) : "memory");
}
__device__ __forceinline__ void bulk_commit() { asm volatile("cp.async.bulk.commit_group;" ::: "memory"); }
__device__ __forceinline__ void bulk_wait_all() { asm volatile("cp.async.bulk.wait_group 0;" ::: "memory"); }
__device__ __forceinline__ void bulk_wait_read() { asm volatile("cp.async.bulk.wait_group.read 0;" ::: "memory"); }
__device__ __forceinline__ void fence_async_smem() { asm volatile("fence.proxy.async.shared::cta;" ::: "memory"); }
__device__ __forceinline__ void fence_async_global() { asm volatile("fence.proxy.async.global;" ::: "memory"); }
__device__ __forceinline__ uint32_t ld_cnt(Scratch* S, int c) { uint32_t v; asm volatile("ld.relaxed.gpu.global.u32 %0, [%1];" : "=r"(v) : "l"(S->cnt + c * 32) : "memory"); return v; }
__device__ __forceinline__ void signal(Scratch* S, int c, uint32_t inc) { asm volatile("red.release.gpu.global.add.u32 [%0], %1;" :: "l"(S->cnt + c * 32), "r"(inc) : "memory"); }
__device__ __forceinline__ bool reached(Scratch* S, int c, uint32_t ep) { return ld_cnt(S, c) - ep >= EPOCH; }
__device__ __forceinline__ void await(Scratch* S, int c, uint32_t ep) { while (!reached(S, c, ep)) { } }
__device__ __forceinline__ void bar_sync(int id, int n) { asm volatile("bar.sync %0, %1;" :: "r"(id), "r"(n) : "memory"); }
__device__ __forceinline__ void bar_arrive(int id, int n) { asm volatile("bar.arrive %0, %1;" :: "r"(id), "r"(n) : "memory"); }
__device__ __forceinline__ void wg_fence() { asm volatile("wgmma.fence.sync.aligned;" ::: "memory"); }
__device__ __forceinline__ void wg_commit() { asm volatile("wgmma.commit_group.sync.aligned;" ::: "memory"); }
template <int N> __device__ __forceinline__ void wg_wait() { asm volatile("wgmma.wait_group.sync.aligned %0;" :: "n"(N) : "memory"); }
template <int N> __device__ __forceinline__ void pin_regs(float* a) {
#pragma unroll
  for (int i = 0; i < N; i++) asm volatile("" : "+f"(a[i]) :: "memory");
}
__device__ __forceinline__ uint64_t make_desc(uint32_t addr, uint32_t lbo, uint32_t sbo, uint32_t swz) {
  return (uint64_t)((addr & 0x3FFFF) >> 4) | ((uint64_t)(lbo >> 4) << 16) | ((uint64_t)(sbo >> 4) << 32) | ((uint64_t)swz << 62);
}
__device__ __forceinline__ uint32_t pack_bf16(float lo, float hi) { uint32_t r; asm("cvt.rn.bf16x2.f32 %0, %1, %2;" : "=r"(r) : "f"(hi), "f"(lo)); return r; }
__device__ __forceinline__ float bf_lo(uint32_t p) { return __uint_as_float(p << 16); }
__device__ __forceinline__ float bf_hi(uint32_t p) { return __uint_as_float(p & 0xffff0000u); }
__device__ __forceinline__ float round_bf16(float v) { return bf_lo(pack_bf16(v, 0.f)); }
__device__ __forceinline__ uint32_t bmul2(uint32_t a, uint32_t b) { uint32_t r; asm("mul.rn.bf16x2 %0, %1, %2;" : "=r"(r) : "r"(a), "r"(b)); return r; }
__device__ __forceinline__ uint32_t badd2(uint32_t a, uint32_t b) { uint32_t r; asm("add.rn.bf16x2 %0, %1, %2;" : "=r"(r) : "r"(a), "r"(b)); return r; }
__device__ __forceinline__ uint32_t bfma2(uint32_t a, uint32_t b, uint32_t c) { uint32_t r; asm("fma.rn.bf16x2 %0, %1, %2, %3;" : "=r"(r) : "r"(a), "r"(b), "r"(c)); return r; }
__device__ __forceinline__ uint32_t bsub2(uint32_t a, uint32_t b) { uint32_t r; asm("sub.rn.bf16x2 %0, %1, %2;" : "=r"(r) : "r"(a), "r"(b)); return r; }
__device__ __forceinline__ float tanh_fast(float v) { float r; asm("tanh.approx.f32 %0, %1;" : "=f"(r) : "f"(v)); return r; }
__device__ __forceinline__ float gelu_half(float h) {
  return fmaf(h, tanh_fast(h * fmaf(h * h, 8.0f * 0.7978845608028654f * 0.044715f, 2.0f * 0.7978845608028654f)), h);
}
__device__ __forceinline__ float silu_half(float h) { return fmaf(h, tanh_fast(h), h); }
__device__ __forceinline__ uint32_t ldg32(const void* p) { uint32_t v; asm volatile("ld.global.u32 %0, [%1];" : "=r"(v) : "l"(p) : "memory"); return v; }
__device__ __forceinline__ uint32_t lds32(uint32_t a) { uint32_t v; asm volatile("ld.shared.u32 %0, [%1];" : "=r"(v) : "r"(a) : "memory"); return v; }
__device__ __forceinline__ uint32_t lds16(uint32_t a) { uint32_t v; asm volatile("ld.shared.u16 %0, [%1];" : "=r"(v) : "r"(a) : "memory"); return v; }
__device__ __forceinline__ uint4 lds128(uint32_t a) { uint4 v; asm volatile("ld.shared.v4.u32 {%0,%1,%2,%3}, [%4];" : "=r"(v.x), "=r"(v.y), "=r"(v.z), "=r"(v.w) : "r"(a) : "memory"); return v; }
__device__ __forceinline__ void sts128(uint32_t a, uint32_t x, uint32_t y, uint32_t z, uint32_t w) {
  asm volatile("st.shared.v4.u32 [%0], {%1,%2,%3,%4};" :: "r"(a), "r"(x), "r"(y), "r"(z), "r"(w) : "memory");
}
__device__ __forceinline__ void sts32(uint32_t a, uint32_t v) { asm volatile("st.shared.u32 [%0], %1;" :: "r"(a), "r"(v) : "memory"); }
__device__ __forceinline__ void ldsm4(uint32_t* r, uint32_t a) {
  asm volatile("ldmatrix.sync.aligned.m8n8.x4.shared.b16 {%0,%1,%2,%3}, [%4];" : "=r"(r[0]), "=r"(r[1]), "=r"(r[2]), "=r"(r[3]) : "r"(a) : "memory");
}
__device__ __forceinline__ void ldsm2(uint32_t* r, uint32_t a) {
  asm volatile("ldmatrix.sync.aligned.m8n8.x2.shared.b16 {%0,%1}, [%2];" : "=r"(r[0]), "=r"(r[1]) : "r"(a) : "memory");
}
__device__ __forceinline__ void ldsm4t(uint32_t* r, uint32_t a) {
  asm volatile("ldmatrix.sync.aligned.m8n8.x4.trans.shared.b16 {%0,%1,%2,%3}, [%4];" : "=r"(r[0]), "=r"(r[1]), "=r"(r[2]), "=r"(r[3]) : "r"(a) : "memory");
}
__device__ __forceinline__ void ldsm2t(uint32_t* r, uint32_t a) {
  asm volatile("ldmatrix.sync.aligned.m8n8.x2.trans.shared.b16 {%0,%1}, [%2];" : "=r"(r[0]), "=r"(r[1]) : "r"(a) : "memory");
}
__device__ __forceinline__ void stsm4(uint32_t a, uint32_t r0, uint32_t r1, uint32_t r2, uint32_t r3) {
  asm volatile("stmatrix.sync.aligned.m8n8.x4.shared.b16 [%0], {%1,%2,%3,%4};" :: "r"(a), "r"(r0), "r"(r1), "r"(r2), "r"(r3) : "memory");
}
__device__ __forceinline__ void stsm2(uint32_t a, uint32_t r0, uint32_t r1) {
  asm volatile("stmatrix.sync.aligned.m8n8.x2.shared.b16 [%0], {%1,%2};" :: "r"(a), "r"(r0), "r"(r1) : "memory");
}
__device__ __forceinline__ void stsm4t(uint32_t a, uint32_t r0, uint32_t r1, uint32_t r2, uint32_t r3) {
  asm volatile("stmatrix.sync.aligned.m8n8.x4.trans.shared.b16 [%0], {%1,%2,%3,%4};" :: "r"(a), "r"(r0), "r"(r1), "r"(r2), "r"(r3) : "memory");
}

__device__ __forceinline__ void wgmma_ss_n144_t10(float* d, uint64_t da, uint64_t db, int sd) {
  asm volatile("{ .reg .pred p; setp.ne.b32 p, %74, 0;\n"
      "wgmma.mma_async.sync.aligned.m64n144k16.f32.bf16.bf16 {"
      "%0,%1,%2,%3,%4,%5,%6,%7,%8,%9,%10,%11,%12,%13,%14,%15,"
      "%16,%17,%18,%19,%20,%21,%22,%23,%24,%25,%26,%27,%28,%29,%30,%31,"
      "%32,%33,%34,%35,%36,%37,%38,%39,%40,%41,%42,%43,%44,%45,%46,%47,"
      "%48,%49,%50,%51,%52,%53,%54,%55,%56,%57,%58,%59,%60,%61,%62,%63,"
      "%64,%65,%66,%67,%68,%69,%70,%71"
      "}, %72, %73, p, 1, 1, 1, 0; }"
    : "+f"(d[0]), "+f"(d[1]), "+f"(d[2]), "+f"(d[3]), "+f"(d[4]), "+f"(d[5]), "+f"(d[6]), "+f"(d[7]),
      "+f"(d[8]), "+f"(d[9]), "+f"(d[10]), "+f"(d[11]), "+f"(d[12]), "+f"(d[13]), "+f"(d[14]), "+f"(d[15]),
      "+f"(d[16]), "+f"(d[17]), "+f"(d[18]), "+f"(d[19]), "+f"(d[20]), "+f"(d[21]), "+f"(d[22]), "+f"(d[23]),
      "+f"(d[24]), "+f"(d[25]), "+f"(d[26]), "+f"(d[27]), "+f"(d[28]), "+f"(d[29]), "+f"(d[30]), "+f"(d[31]),
      "+f"(d[32]), "+f"(d[33]), "+f"(d[34]), "+f"(d[35]), "+f"(d[36]), "+f"(d[37]), "+f"(d[38]), "+f"(d[39]),
      "+f"(d[40]), "+f"(d[41]), "+f"(d[42]), "+f"(d[43]), "+f"(d[44]), "+f"(d[45]), "+f"(d[46]), "+f"(d[47]),
      "+f"(d[48]), "+f"(d[49]), "+f"(d[50]), "+f"(d[51]), "+f"(d[52]), "+f"(d[53]), "+f"(d[54]), "+f"(d[55]),
      "+f"(d[56]), "+f"(d[57]), "+f"(d[58]), "+f"(d[59]), "+f"(d[60]), "+f"(d[61]), "+f"(d[62]), "+f"(d[63]),
      "+f"(d[64]), "+f"(d[65]), "+f"(d[66]), "+f"(d[67]), "+f"(d[68]), "+f"(d[69]), "+f"(d[70]), "+f"(d[71])
    : "l"(da), "l"(db), "r"(sd));
}

__device__ __forceinline__ void wgmma_ss_n160_t11(float* d, uint64_t da, uint64_t db, int sd) {
  asm volatile("{ .reg .pred p; setp.ne.b32 p, %82, 0;\n"
      "wgmma.mma_async.sync.aligned.m64n160k16.f32.bf16.bf16 {"
      "%0,%1,%2,%3,%4,%5,%6,%7,%8,%9,%10,%11,%12,%13,%14,%15,"
      "%16,%17,%18,%19,%20,%21,%22,%23,%24,%25,%26,%27,%28,%29,%30,%31,"
      "%32,%33,%34,%35,%36,%37,%38,%39,%40,%41,%42,%43,%44,%45,%46,%47,"
      "%48,%49,%50,%51,%52,%53,%54,%55,%56,%57,%58,%59,%60,%61,%62,%63,"
      "%64,%65,%66,%67,%68,%69,%70,%71,%72,%73,%74,%75,%76,%77,%78,%79"
      "}, %80, %81, p, 1, 1, 1, 1; }"
    : "+f"(d[0]), "+f"(d[1]), "+f"(d[2]), "+f"(d[3]), "+f"(d[4]), "+f"(d[5]), "+f"(d[6]), "+f"(d[7]),
      "+f"(d[8]), "+f"(d[9]), "+f"(d[10]), "+f"(d[11]), "+f"(d[12]), "+f"(d[13]), "+f"(d[14]), "+f"(d[15]),
      "+f"(d[16]), "+f"(d[17]), "+f"(d[18]), "+f"(d[19]), "+f"(d[20]), "+f"(d[21]), "+f"(d[22]), "+f"(d[23]),
      "+f"(d[24]), "+f"(d[25]), "+f"(d[26]), "+f"(d[27]), "+f"(d[28]), "+f"(d[29]), "+f"(d[30]), "+f"(d[31]),
      "+f"(d[32]), "+f"(d[33]), "+f"(d[34]), "+f"(d[35]), "+f"(d[36]), "+f"(d[37]), "+f"(d[38]), "+f"(d[39]),
      "+f"(d[40]), "+f"(d[41]), "+f"(d[42]), "+f"(d[43]), "+f"(d[44]), "+f"(d[45]), "+f"(d[46]), "+f"(d[47]),
      "+f"(d[48]), "+f"(d[49]), "+f"(d[50]), "+f"(d[51]), "+f"(d[52]), "+f"(d[53]), "+f"(d[54]), "+f"(d[55]),
      "+f"(d[56]), "+f"(d[57]), "+f"(d[58]), "+f"(d[59]), "+f"(d[60]), "+f"(d[61]), "+f"(d[62]), "+f"(d[63]),
      "+f"(d[64]), "+f"(d[65]), "+f"(d[66]), "+f"(d[67]), "+f"(d[68]), "+f"(d[69]), "+f"(d[70]), "+f"(d[71]),
      "+f"(d[72]), "+f"(d[73]), "+f"(d[74]), "+f"(d[75]), "+f"(d[76]), "+f"(d[77]), "+f"(d[78]), "+f"(d[79])
    : "l"(da), "l"(db), "r"(sd));
}

__device__ __forceinline__ void wgmma_ss_n96_t11(float* d, uint64_t da, uint64_t db, int sd) {
  asm volatile("{ .reg .pred p; setp.ne.b32 p, %50, 0;\n"
      "wgmma.mma_async.sync.aligned.m64n96k16.f32.bf16.bf16 {"
      "%0,%1,%2,%3,%4,%5,%6,%7,%8,%9,%10,%11,%12,%13,%14,%15,"
      "%16,%17,%18,%19,%20,%21,%22,%23,%24,%25,%26,%27,%28,%29,%30,%31,"
      "%32,%33,%34,%35,%36,%37,%38,%39,%40,%41,%42,%43,%44,%45,%46,%47"
      "}, %48, %49, p, 1, 1, 1, 1; }"
    : "+f"(d[0]), "+f"(d[1]), "+f"(d[2]), "+f"(d[3]), "+f"(d[4]), "+f"(d[5]), "+f"(d[6]), "+f"(d[7]),
      "+f"(d[8]), "+f"(d[9]), "+f"(d[10]), "+f"(d[11]), "+f"(d[12]), "+f"(d[13]), "+f"(d[14]), "+f"(d[15]),
      "+f"(d[16]), "+f"(d[17]), "+f"(d[18]), "+f"(d[19]), "+f"(d[20]), "+f"(d[21]), "+f"(d[22]), "+f"(d[23]),
      "+f"(d[24]), "+f"(d[25]), "+f"(d[26]), "+f"(d[27]), "+f"(d[28]), "+f"(d[29]), "+f"(d[30]), "+f"(d[31]),
      "+f"(d[32]), "+f"(d[33]), "+f"(d[34]), "+f"(d[35]), "+f"(d[36]), "+f"(d[37]), "+f"(d[38]), "+f"(d[39]),
      "+f"(d[40]), "+f"(d[41]), "+f"(d[42]), "+f"(d[43]), "+f"(d[44]), "+f"(d[45]), "+f"(d[46]), "+f"(d[47])
    : "l"(da), "l"(db), "r"(sd));
}

__device__ __forceinline__ void wgmma_rs_n16(float* d, const uint32_t* a, uint64_t db, int sd) {
  asm volatile("{ .reg .pred p; setp.ne.b32 p, %13, 0;\n"
      "wgmma.mma_async.sync.aligned.m64n16k16.f32.bf16.bf16 {"
      "%0,%1,%2,%3,%4,%5,%6,%7"
      "}, {%8,%9,%10,%11}, %12, p, 1, 1, 0; }"
    : "+f"(d[0]), "+f"(d[1]), "+f"(d[2]), "+f"(d[3]), "+f"(d[4]), "+f"(d[5]), "+f"(d[6]), "+f"(d[7])
    : "r"(a[0]), "r"(a[1]), "r"(a[2]), "r"(a[3]), "l"(db), "r"(sd));
}

__device__ __forceinline__ void wgmma_rs_n32(float* d, const uint32_t* a, uint64_t db, int sd) {
  asm volatile("{ .reg .pred p; setp.ne.b32 p, %21, 0;\n"
      "wgmma.mma_async.sync.aligned.m64n32k16.f32.bf16.bf16 {"
      "%0,%1,%2,%3,%4,%5,%6,%7,%8,%9,%10,%11,%12,%13,%14,%15"
      "}, {%16,%17,%18,%19}, %20, p, 1, 1, 0; }"
    : "+f"(d[0]), "+f"(d[1]), "+f"(d[2]), "+f"(d[3]), "+f"(d[4]), "+f"(d[5]), "+f"(d[6]), "+f"(d[7]),
      "+f"(d[8]), "+f"(d[9]), "+f"(d[10]), "+f"(d[11]), "+f"(d[12]), "+f"(d[13]), "+f"(d[14]), "+f"(d[15])
    : "r"(a[0]), "r"(a[1]), "r"(a[2]), "r"(a[3]), "l"(db), "r"(sd));
}

__device__ __forceinline__ void wgmma_rs_n48(float* d, const uint32_t* a, uint64_t db, int sd) {
  asm volatile("{ .reg .pred p; setp.ne.b32 p, %29, 0;\n"
      "wgmma.mma_async.sync.aligned.m64n48k16.f32.bf16.bf16 {"
      "%0,%1,%2,%3,%4,%5,%6,%7,%8,%9,%10,%11,%12,%13,%14,%15,"
      "%16,%17,%18,%19,%20,%21,%22,%23"
      "}, {%24,%25,%26,%27}, %28, p, 1, 1, 0; }"
    : "+f"(d[0]), "+f"(d[1]), "+f"(d[2]), "+f"(d[3]), "+f"(d[4]), "+f"(d[5]), "+f"(d[6]), "+f"(d[7]),
      "+f"(d[8]), "+f"(d[9]), "+f"(d[10]), "+f"(d[11]), "+f"(d[12]), "+f"(d[13]), "+f"(d[14]), "+f"(d[15]),
      "+f"(d[16]), "+f"(d[17]), "+f"(d[18]), "+f"(d[19]), "+f"(d[20]), "+f"(d[21]), "+f"(d[22]), "+f"(d[23])
    : "r"(a[0]), "r"(a[1]), "r"(a[2]), "r"(a[3]), "l"(db), "r"(sd));
}

__device__ __forceinline__ void wgmma_rs_n64(float* d, const uint32_t* a, uint64_t db, int sd) {
  asm volatile("{ .reg .pred p; setp.ne.b32 p, %37, 0;\n"
      "wgmma.mma_async.sync.aligned.m64n64k16.f32.bf16.bf16 {"
      "%0,%1,%2,%3,%4,%5,%6,%7,%8,%9,%10,%11,%12,%13,%14,%15,"
      "%16,%17,%18,%19,%20,%21,%22,%23,%24,%25,%26,%27,%28,%29,%30,%31"
      "}, {%32,%33,%34,%35}, %36, p, 1, 1, 0; }"
    : "+f"(d[0]), "+f"(d[1]), "+f"(d[2]), "+f"(d[3]), "+f"(d[4]), "+f"(d[5]), "+f"(d[6]), "+f"(d[7]),
      "+f"(d[8]), "+f"(d[9]), "+f"(d[10]), "+f"(d[11]), "+f"(d[12]), "+f"(d[13]), "+f"(d[14]), "+f"(d[15]),
      "+f"(d[16]), "+f"(d[17]), "+f"(d[18]), "+f"(d[19]), "+f"(d[20]), "+f"(d[21]), "+f"(d[22]), "+f"(d[23]),
      "+f"(d[24]), "+f"(d[25]), "+f"(d[26]), "+f"(d[27]), "+f"(d[28]), "+f"(d[29]), "+f"(d[30]), "+f"(d[31])
    : "r"(a[0]), "r"(a[1]), "r"(a[2]), "r"(a[3]), "l"(db), "r"(sd));
}

__device__ __forceinline__ void wgmma_rs_n80(float* d, const uint32_t* a, uint64_t db, int sd) {
  asm volatile("{ .reg .pred p; setp.ne.b32 p, %45, 0;\n"
      "wgmma.mma_async.sync.aligned.m64n80k16.f32.bf16.bf16 {"
      "%0,%1,%2,%3,%4,%5,%6,%7,%8,%9,%10,%11,%12,%13,%14,%15,"
      "%16,%17,%18,%19,%20,%21,%22,%23,%24,%25,%26,%27,%28,%29,%30,%31,"
      "%32,%33,%34,%35,%36,%37,%38,%39"
      "}, {%40,%41,%42,%43}, %44, p, 1, 1, 0; }"
    : "+f"(d[0]), "+f"(d[1]), "+f"(d[2]), "+f"(d[3]), "+f"(d[4]), "+f"(d[5]), "+f"(d[6]), "+f"(d[7]),
      "+f"(d[8]), "+f"(d[9]), "+f"(d[10]), "+f"(d[11]), "+f"(d[12]), "+f"(d[13]), "+f"(d[14]), "+f"(d[15]),
      "+f"(d[16]), "+f"(d[17]), "+f"(d[18]), "+f"(d[19]), "+f"(d[20]), "+f"(d[21]), "+f"(d[22]), "+f"(d[23]),
      "+f"(d[24]), "+f"(d[25]), "+f"(d[26]), "+f"(d[27]), "+f"(d[28]), "+f"(d[29]), "+f"(d[30]), "+f"(d[31]),
      "+f"(d[32]), "+f"(d[33]), "+f"(d[34]), "+f"(d[35]), "+f"(d[36]), "+f"(d[37]), "+f"(d[38]), "+f"(d[39])
    : "r"(a[0]), "r"(a[1]), "r"(a[2]), "r"(a[3]), "l"(db), "r"(sd));
}

__device__ __forceinline__ void wgmma_rs_n96(float* d, const uint32_t* a, uint64_t db, int sd) {
  asm volatile("{ .reg .pred p; setp.ne.b32 p, %53, 0;\n"
      "wgmma.mma_async.sync.aligned.m64n96k16.f32.bf16.bf16 {"
      "%0,%1,%2,%3,%4,%5,%6,%7,%8,%9,%10,%11,%12,%13,%14,%15,"
      "%16,%17,%18,%19,%20,%21,%22,%23,%24,%25,%26,%27,%28,%29,%30,%31,"
      "%32,%33,%34,%35,%36,%37,%38,%39,%40,%41,%42,%43,%44,%45,%46,%47"
      "}, {%48,%49,%50,%51}, %52, p, 1, 1, 0; }"
    : "+f"(d[0]), "+f"(d[1]), "+f"(d[2]), "+f"(d[3]), "+f"(d[4]), "+f"(d[5]), "+f"(d[6]), "+f"(d[7]),
      "+f"(d[8]), "+f"(d[9]), "+f"(d[10]), "+f"(d[11]), "+f"(d[12]), "+f"(d[13]), "+f"(d[14]), "+f"(d[15]),
      "+f"(d[16]), "+f"(d[17]), "+f"(d[18]), "+f"(d[19]), "+f"(d[20]), "+f"(d[21]), "+f"(d[22]), "+f"(d[23]),
      "+f"(d[24]), "+f"(d[25]), "+f"(d[26]), "+f"(d[27]), "+f"(d[28]), "+f"(d[29]), "+f"(d[30]), "+f"(d[31]),
      "+f"(d[32]), "+f"(d[33]), "+f"(d[34]), "+f"(d[35]), "+f"(d[36]), "+f"(d[37]), "+f"(d[38]), "+f"(d[39]),
      "+f"(d[40]), "+f"(d[41]), "+f"(d[42]), "+f"(d[43]), "+f"(d[44]), "+f"(d[45]), "+f"(d[46]), "+f"(d[47])
    : "r"(a[0]), "r"(a[1]), "r"(a[2]), "r"(a[3]), "l"(db), "r"(sd));
}

__device__ __forceinline__ void wgmma_rs_n112(float* d, const uint32_t* a, uint64_t db, int sd) {
  asm volatile("{ .reg .pred p; setp.ne.b32 p, %61, 0;\n"
      "wgmma.mma_async.sync.aligned.m64n112k16.f32.bf16.bf16 {"
      "%0,%1,%2,%3,%4,%5,%6,%7,%8,%9,%10,%11,%12,%13,%14,%15,"
      "%16,%17,%18,%19,%20,%21,%22,%23,%24,%25,%26,%27,%28,%29,%30,%31,"
      "%32,%33,%34,%35,%36,%37,%38,%39,%40,%41,%42,%43,%44,%45,%46,%47,"
      "%48,%49,%50,%51,%52,%53,%54,%55"
      "}, {%56,%57,%58,%59}, %60, p, 1, 1, 0; }"
    : "+f"(d[0]), "+f"(d[1]), "+f"(d[2]), "+f"(d[3]), "+f"(d[4]), "+f"(d[5]), "+f"(d[6]), "+f"(d[7]),
      "+f"(d[8]), "+f"(d[9]), "+f"(d[10]), "+f"(d[11]), "+f"(d[12]), "+f"(d[13]), "+f"(d[14]), "+f"(d[15]),
      "+f"(d[16]), "+f"(d[17]), "+f"(d[18]), "+f"(d[19]), "+f"(d[20]), "+f"(d[21]), "+f"(d[22]), "+f"(d[23]),
      "+f"(d[24]), "+f"(d[25]), "+f"(d[26]), "+f"(d[27]), "+f"(d[28]), "+f"(d[29]), "+f"(d[30]), "+f"(d[31]),
      "+f"(d[32]), "+f"(d[33]), "+f"(d[34]), "+f"(d[35]), "+f"(d[36]), "+f"(d[37]), "+f"(d[38]), "+f"(d[39]),
      "+f"(d[40]), "+f"(d[41]), "+f"(d[42]), "+f"(d[43]), "+f"(d[44]), "+f"(d[45]), "+f"(d[46]), "+f"(d[47]),
      "+f"(d[48]), "+f"(d[49]), "+f"(d[50]), "+f"(d[51]), "+f"(d[52]), "+f"(d[53]), "+f"(d[54]), "+f"(d[55])
    : "r"(a[0]), "r"(a[1]), "r"(a[2]), "r"(a[3]), "l"(db), "r"(sd));
}

__device__ __forceinline__ void wgmma_rs_n128(float* d, const uint32_t* a, uint64_t db, int sd) {
  asm volatile("{ .reg .pred p; setp.ne.b32 p, %69, 0;\n"
      "wgmma.mma_async.sync.aligned.m64n128k16.f32.bf16.bf16 {"
      "%0,%1,%2,%3,%4,%5,%6,%7,%8,%9,%10,%11,%12,%13,%14,%15,"
      "%16,%17,%18,%19,%20,%21,%22,%23,%24,%25,%26,%27,%28,%29,%30,%31,"
      "%32,%33,%34,%35,%36,%37,%38,%39,%40,%41,%42,%43,%44,%45,%46,%47,"
      "%48,%49,%50,%51,%52,%53,%54,%55,%56,%57,%58,%59,%60,%61,%62,%63"
      "}, {%64,%65,%66,%67}, %68, p, 1, 1, 0; }"
    : "+f"(d[0]), "+f"(d[1]), "+f"(d[2]), "+f"(d[3]), "+f"(d[4]), "+f"(d[5]), "+f"(d[6]), "+f"(d[7]),
      "+f"(d[8]), "+f"(d[9]), "+f"(d[10]), "+f"(d[11]), "+f"(d[12]), "+f"(d[13]), "+f"(d[14]), "+f"(d[15]),
      "+f"(d[16]), "+f"(d[17]), "+f"(d[18]), "+f"(d[19]), "+f"(d[20]), "+f"(d[21]), "+f"(d[22]), "+f"(d[23]),
      "+f"(d[24]), "+f"(d[25]), "+f"(d[26]), "+f"(d[27]), "+f"(d[28]), "+f"(d[29]), "+f"(d[30]), "+f"(d[31]),
      "+f"(d[32]), "+f"(d[33]), "+f"(d[34]), "+f"(d[35]), "+f"(d[36]), "+f"(d[37]), "+f"(d[38]), "+f"(d[39]),
      "+f"(d[40]), "+f"(d[41]), "+f"(d[42]), "+f"(d[43]), "+f"(d[44]), "+f"(d[45]), "+f"(d[46]), "+f"(d[47]),
      "+f"(d[48]), "+f"(d[49]), "+f"(d[50]), "+f"(d[51]), "+f"(d[52]), "+f"(d[53]), "+f"(d[54]), "+f"(d[55]),
      "+f"(d[56]), "+f"(d[57]), "+f"(d[58]), "+f"(d[59]), "+f"(d[60]), "+f"(d[61]), "+f"(d[62]), "+f"(d[63])
    : "r"(a[0]), "r"(a[1]), "r"(a[2]), "r"(a[3]), "l"(db), "r"(sd));
}

__device__ __forceinline__ void wgmma_rs_n144(float* d, const uint32_t* a, uint64_t db, int sd) {
  asm volatile("{ .reg .pred p; setp.ne.b32 p, %77, 0;\n"
      "wgmma.mma_async.sync.aligned.m64n144k16.f32.bf16.bf16 {"
      "%0,%1,%2,%3,%4,%5,%6,%7,%8,%9,%10,%11,%12,%13,%14,%15,"
      "%16,%17,%18,%19,%20,%21,%22,%23,%24,%25,%26,%27,%28,%29,%30,%31,"
      "%32,%33,%34,%35,%36,%37,%38,%39,%40,%41,%42,%43,%44,%45,%46,%47,"
      "%48,%49,%50,%51,%52,%53,%54,%55,%56,%57,%58,%59,%60,%61,%62,%63,"
      "%64,%65,%66,%67,%68,%69,%70,%71"
      "}, {%72,%73,%74,%75}, %76, p, 1, 1, 0; }"
    : "+f"(d[0]), "+f"(d[1]), "+f"(d[2]), "+f"(d[3]), "+f"(d[4]), "+f"(d[5]), "+f"(d[6]), "+f"(d[7]),
      "+f"(d[8]), "+f"(d[9]), "+f"(d[10]), "+f"(d[11]), "+f"(d[12]), "+f"(d[13]), "+f"(d[14]), "+f"(d[15]),
      "+f"(d[16]), "+f"(d[17]), "+f"(d[18]), "+f"(d[19]), "+f"(d[20]), "+f"(d[21]), "+f"(d[22]), "+f"(d[23]),
      "+f"(d[24]), "+f"(d[25]), "+f"(d[26]), "+f"(d[27]), "+f"(d[28]), "+f"(d[29]), "+f"(d[30]), "+f"(d[31]),
      "+f"(d[32]), "+f"(d[33]), "+f"(d[34]), "+f"(d[35]), "+f"(d[36]), "+f"(d[37]), "+f"(d[38]), "+f"(d[39]),
      "+f"(d[40]), "+f"(d[41]), "+f"(d[42]), "+f"(d[43]), "+f"(d[44]), "+f"(d[45]), "+f"(d[46]), "+f"(d[47]),
      "+f"(d[48]), "+f"(d[49]), "+f"(d[50]), "+f"(d[51]), "+f"(d[52]), "+f"(d[53]), "+f"(d[54]), "+f"(d[55]),
      "+f"(d[56]), "+f"(d[57]), "+f"(d[58]), "+f"(d[59]), "+f"(d[60]), "+f"(d[61]), "+f"(d[62]), "+f"(d[63]),
      "+f"(d[64]), "+f"(d[65]), "+f"(d[66]), "+f"(d[67]), "+f"(d[68]), "+f"(d[69]), "+f"(d[70]), "+f"(d[71])
    : "r"(a[0]), "r"(a[1]), "r"(a[2]), "r"(a[3]), "l"(db), "r"(sd));
}

__device__ __forceinline__ void wgmma_rs_n160(float* d, const uint32_t* a, uint64_t db, int sd) {
  asm volatile("{ .reg .pred p; setp.ne.b32 p, %85, 0;\n"
      "wgmma.mma_async.sync.aligned.m64n160k16.f32.bf16.bf16 {"
      "%0,%1,%2,%3,%4,%5,%6,%7,%8,%9,%10,%11,%12,%13,%14,%15,"
      "%16,%17,%18,%19,%20,%21,%22,%23,%24,%25,%26,%27,%28,%29,%30,%31,"
      "%32,%33,%34,%35,%36,%37,%38,%39,%40,%41,%42,%43,%44,%45,%46,%47,"
      "%48,%49,%50,%51,%52,%53,%54,%55,%56,%57,%58,%59,%60,%61,%62,%63,"
      "%64,%65,%66,%67,%68,%69,%70,%71,%72,%73,%74,%75,%76,%77,%78,%79"
      "}, {%80,%81,%82,%83}, %84, p, 1, 1, 0; }"
    : "+f"(d[0]), "+f"(d[1]), "+f"(d[2]), "+f"(d[3]), "+f"(d[4]), "+f"(d[5]), "+f"(d[6]), "+f"(d[7]),
      "+f"(d[8]), "+f"(d[9]), "+f"(d[10]), "+f"(d[11]), "+f"(d[12]), "+f"(d[13]), "+f"(d[14]), "+f"(d[15]),
      "+f"(d[16]), "+f"(d[17]), "+f"(d[18]), "+f"(d[19]), "+f"(d[20]), "+f"(d[21]), "+f"(d[22]), "+f"(d[23]),
      "+f"(d[24]), "+f"(d[25]), "+f"(d[26]), "+f"(d[27]), "+f"(d[28]), "+f"(d[29]), "+f"(d[30]), "+f"(d[31]),
      "+f"(d[32]), "+f"(d[33]), "+f"(d[34]), "+f"(d[35]), "+f"(d[36]), "+f"(d[37]), "+f"(d[38]), "+f"(d[39]),
      "+f"(d[40]), "+f"(d[41]), "+f"(d[42]), "+f"(d[43]), "+f"(d[44]), "+f"(d[45]), "+f"(d[46]), "+f"(d[47]),
      "+f"(d[48]), "+f"(d[49]), "+f"(d[50]), "+f"(d[51]), "+f"(d[52]), "+f"(d[53]), "+f"(d[54]), "+f"(d[55]),
      "+f"(d[56]), "+f"(d[57]), "+f"(d[58]), "+f"(d[59]), "+f"(d[60]), "+f"(d[61]), "+f"(d[62]), "+f"(d[63]),
      "+f"(d[64]), "+f"(d[65]), "+f"(d[66]), "+f"(d[67]), "+f"(d[68]), "+f"(d[69]), "+f"(d[70]), "+f"(d[71]),
      "+f"(d[72]), "+f"(d[73]), "+f"(d[74]), "+f"(d[75]), "+f"(d[76]), "+f"(d[77]), "+f"(d[78]), "+f"(d[79])
    : "r"(a[0]), "r"(a[1]), "r"(a[2]), "r"(a[3]), "l"(db), "r"(sd));
}

__device__ __forceinline__ void wgmma_rs_n176(float* d, const uint32_t* a, uint64_t db, int sd) {
  asm volatile("{ .reg .pred p; setp.ne.b32 p, %93, 0;\n"
      "wgmma.mma_async.sync.aligned.m64n176k16.f32.bf16.bf16 {"
      "%0,%1,%2,%3,%4,%5,%6,%7,%8,%9,%10,%11,%12,%13,%14,%15,"
      "%16,%17,%18,%19,%20,%21,%22,%23,%24,%25,%26,%27,%28,%29,%30,%31,"
      "%32,%33,%34,%35,%36,%37,%38,%39,%40,%41,%42,%43,%44,%45,%46,%47,"
      "%48,%49,%50,%51,%52,%53,%54,%55,%56,%57,%58,%59,%60,%61,%62,%63,"
      "%64,%65,%66,%67,%68,%69,%70,%71,%72,%73,%74,%75,%76,%77,%78,%79,"
      "%80,%81,%82,%83,%84,%85,%86,%87"
      "}, {%88,%89,%90,%91}, %92, p, 1, 1, 0; }"
    : "+f"(d[0]), "+f"(d[1]), "+f"(d[2]), "+f"(d[3]), "+f"(d[4]), "+f"(d[5]), "+f"(d[6]), "+f"(d[7]),
      "+f"(d[8]), "+f"(d[9]), "+f"(d[10]), "+f"(d[11]), "+f"(d[12]), "+f"(d[13]), "+f"(d[14]), "+f"(d[15]),
      "+f"(d[16]), "+f"(d[17]), "+f"(d[18]), "+f"(d[19]), "+f"(d[20]), "+f"(d[21]), "+f"(d[22]), "+f"(d[23]),
      "+f"(d[24]), "+f"(d[25]), "+f"(d[26]), "+f"(d[27]), "+f"(d[28]), "+f"(d[29]), "+f"(d[30]), "+f"(d[31]),
      "+f"(d[32]), "+f"(d[33]), "+f"(d[34]), "+f"(d[35]), "+f"(d[36]), "+f"(d[37]), "+f"(d[38]), "+f"(d[39]),
      "+f"(d[40]), "+f"(d[41]), "+f"(d[42]), "+f"(d[43]), "+f"(d[44]), "+f"(d[45]), "+f"(d[46]), "+f"(d[47]),
      "+f"(d[48]), "+f"(d[49]), "+f"(d[50]), "+f"(d[51]), "+f"(d[52]), "+f"(d[53]), "+f"(d[54]), "+f"(d[55]),
      "+f"(d[56]), "+f"(d[57]), "+f"(d[58]), "+f"(d[59]), "+f"(d[60]), "+f"(d[61]), "+f"(d[62]), "+f"(d[63]),
      "+f"(d[64]), "+f"(d[65]), "+f"(d[66]), "+f"(d[67]), "+f"(d[68]), "+f"(d[69]), "+f"(d[70]), "+f"(d[71]),
      "+f"(d[72]), "+f"(d[73]), "+f"(d[74]), "+f"(d[75]), "+f"(d[76]), "+f"(d[77]), "+f"(d[78]), "+f"(d[79]),
      "+f"(d[80]), "+f"(d[81]), "+f"(d[82]), "+f"(d[83]), "+f"(d[84]), "+f"(d[85]), "+f"(d[86]), "+f"(d[87])
    : "r"(a[0]), "r"(a[1]), "r"(a[2]), "r"(a[3]), "l"(db), "r"(sd));
}

__device__ __forceinline__ void wgmma_rs_n192(float* d, const uint32_t* a, uint64_t db, int sd) {
  asm volatile("{ .reg .pred p; setp.ne.b32 p, %101, 0;\n"
      "wgmma.mma_async.sync.aligned.m64n192k16.f32.bf16.bf16 {"
      "%0,%1,%2,%3,%4,%5,%6,%7,%8,%9,%10,%11,%12,%13,%14,%15,"
      "%16,%17,%18,%19,%20,%21,%22,%23,%24,%25,%26,%27,%28,%29,%30,%31,"
      "%32,%33,%34,%35,%36,%37,%38,%39,%40,%41,%42,%43,%44,%45,%46,%47,"
      "%48,%49,%50,%51,%52,%53,%54,%55,%56,%57,%58,%59,%60,%61,%62,%63,"
      "%64,%65,%66,%67,%68,%69,%70,%71,%72,%73,%74,%75,%76,%77,%78,%79,"
      "%80,%81,%82,%83,%84,%85,%86,%87,%88,%89,%90,%91,%92,%93,%94,%95"
      "}, {%96,%97,%98,%99}, %100, p, 1, 1, 0; }"
    : "+f"(d[0]), "+f"(d[1]), "+f"(d[2]), "+f"(d[3]), "+f"(d[4]), "+f"(d[5]), "+f"(d[6]), "+f"(d[7]),
      "+f"(d[8]), "+f"(d[9]), "+f"(d[10]), "+f"(d[11]), "+f"(d[12]), "+f"(d[13]), "+f"(d[14]), "+f"(d[15]),
      "+f"(d[16]), "+f"(d[17]), "+f"(d[18]), "+f"(d[19]), "+f"(d[20]), "+f"(d[21]), "+f"(d[22]), "+f"(d[23]),
      "+f"(d[24]), "+f"(d[25]), "+f"(d[26]), "+f"(d[27]), "+f"(d[28]), "+f"(d[29]), "+f"(d[30]), "+f"(d[31]),
      "+f"(d[32]), "+f"(d[33]), "+f"(d[34]), "+f"(d[35]), "+f"(d[36]), "+f"(d[37]), "+f"(d[38]), "+f"(d[39]),
      "+f"(d[40]), "+f"(d[41]), "+f"(d[42]), "+f"(d[43]), "+f"(d[44]), "+f"(d[45]), "+f"(d[46]), "+f"(d[47]),
      "+f"(d[48]), "+f"(d[49]), "+f"(d[50]), "+f"(d[51]), "+f"(d[52]), "+f"(d[53]), "+f"(d[54]), "+f"(d[55]),
      "+f"(d[56]), "+f"(d[57]), "+f"(d[58]), "+f"(d[59]), "+f"(d[60]), "+f"(d[61]), "+f"(d[62]), "+f"(d[63]),
      "+f"(d[64]), "+f"(d[65]), "+f"(d[66]), "+f"(d[67]), "+f"(d[68]), "+f"(d[69]), "+f"(d[70]), "+f"(d[71]),
      "+f"(d[72]), "+f"(d[73]), "+f"(d[74]), "+f"(d[75]), "+f"(d[76]), "+f"(d[77]), "+f"(d[78]), "+f"(d[79]),
      "+f"(d[80]), "+f"(d[81]), "+f"(d[82]), "+f"(d[83]), "+f"(d[84]), "+f"(d[85]), "+f"(d[86]), "+f"(d[87]),
      "+f"(d[88]), "+f"(d[89]), "+f"(d[90]), "+f"(d[91]), "+f"(d[92]), "+f"(d[93]), "+f"(d[94]), "+f"(d[95])
    : "r"(a[0]), "r"(a[1]), "r"(a[2]), "r"(a[3]), "l"(db), "r"(sd));
}

__device__ __forceinline__ void wgmma_rs_n208(float* d, const uint32_t* a, uint64_t db, int sd) {
  asm volatile("{ .reg .pred p; setp.ne.b32 p, %109, 0;\n"
      "wgmma.mma_async.sync.aligned.m64n208k16.f32.bf16.bf16 {"
      "%0,%1,%2,%3,%4,%5,%6,%7,%8,%9,%10,%11,%12,%13,%14,%15,"
      "%16,%17,%18,%19,%20,%21,%22,%23,%24,%25,%26,%27,%28,%29,%30,%31,"
      "%32,%33,%34,%35,%36,%37,%38,%39,%40,%41,%42,%43,%44,%45,%46,%47,"
      "%48,%49,%50,%51,%52,%53,%54,%55,%56,%57,%58,%59,%60,%61,%62,%63,"
      "%64,%65,%66,%67,%68,%69,%70,%71,%72,%73,%74,%75,%76,%77,%78,%79,"
      "%80,%81,%82,%83,%84,%85,%86,%87,%88,%89,%90,%91,%92,%93,%94,%95,"
      "%96,%97,%98,%99,%100,%101,%102,%103"
      "}, {%104,%105,%106,%107}, %108, p, 1, 1, 0; }"
    : "+f"(d[0]), "+f"(d[1]), "+f"(d[2]), "+f"(d[3]), "+f"(d[4]), "+f"(d[5]), "+f"(d[6]), "+f"(d[7]),
      "+f"(d[8]), "+f"(d[9]), "+f"(d[10]), "+f"(d[11]), "+f"(d[12]), "+f"(d[13]), "+f"(d[14]), "+f"(d[15]),
      "+f"(d[16]), "+f"(d[17]), "+f"(d[18]), "+f"(d[19]), "+f"(d[20]), "+f"(d[21]), "+f"(d[22]), "+f"(d[23]),
      "+f"(d[24]), "+f"(d[25]), "+f"(d[26]), "+f"(d[27]), "+f"(d[28]), "+f"(d[29]), "+f"(d[30]), "+f"(d[31]),
      "+f"(d[32]), "+f"(d[33]), "+f"(d[34]), "+f"(d[35]), "+f"(d[36]), "+f"(d[37]), "+f"(d[38]), "+f"(d[39]),
      "+f"(d[40]), "+f"(d[41]), "+f"(d[42]), "+f"(d[43]), "+f"(d[44]), "+f"(d[45]), "+f"(d[46]), "+f"(d[47]),
      "+f"(d[48]), "+f"(d[49]), "+f"(d[50]), "+f"(d[51]), "+f"(d[52]), "+f"(d[53]), "+f"(d[54]), "+f"(d[55]),
      "+f"(d[56]), "+f"(d[57]), "+f"(d[58]), "+f"(d[59]), "+f"(d[60]), "+f"(d[61]), "+f"(d[62]), "+f"(d[63]),
      "+f"(d[64]), "+f"(d[65]), "+f"(d[66]), "+f"(d[67]), "+f"(d[68]), "+f"(d[69]), "+f"(d[70]), "+f"(d[71]),
      "+f"(d[72]), "+f"(d[73]), "+f"(d[74]), "+f"(d[75]), "+f"(d[76]), "+f"(d[77]), "+f"(d[78]), "+f"(d[79]),
      "+f"(d[80]), "+f"(d[81]), "+f"(d[82]), "+f"(d[83]), "+f"(d[84]), "+f"(d[85]), "+f"(d[86]), "+f"(d[87]),
      "+f"(d[88]), "+f"(d[89]), "+f"(d[90]), "+f"(d[91]), "+f"(d[92]), "+f"(d[93]), "+f"(d[94]), "+f"(d[95]),
      "+f"(d[96]), "+f"(d[97]), "+f"(d[98]), "+f"(d[99]), "+f"(d[100]), "+f"(d[101]), "+f"(d[102]), "+f"(d[103])
    : "r"(a[0]), "r"(a[1]), "r"(a[2]), "r"(a[3]), "l"(db), "r"(sd));
}

__device__ __forceinline__ void wgmma_rs_n224(float* d, const uint32_t* a, uint64_t db, int sd) {
  asm volatile("{ .reg .pred p; setp.ne.b32 p, %117, 0;\n"
      "wgmma.mma_async.sync.aligned.m64n224k16.f32.bf16.bf16 {"
      "%0,%1,%2,%3,%4,%5,%6,%7,%8,%9,%10,%11,%12,%13,%14,%15,"
      "%16,%17,%18,%19,%20,%21,%22,%23,%24,%25,%26,%27,%28,%29,%30,%31,"
      "%32,%33,%34,%35,%36,%37,%38,%39,%40,%41,%42,%43,%44,%45,%46,%47,"
      "%48,%49,%50,%51,%52,%53,%54,%55,%56,%57,%58,%59,%60,%61,%62,%63,"
      "%64,%65,%66,%67,%68,%69,%70,%71,%72,%73,%74,%75,%76,%77,%78,%79,"
      "%80,%81,%82,%83,%84,%85,%86,%87,%88,%89,%90,%91,%92,%93,%94,%95,"
      "%96,%97,%98,%99,%100,%101,%102,%103,%104,%105,%106,%107,%108,%109,%110,%111"
      "}, {%112,%113,%114,%115}, %116, p, 1, 1, 0; }"
    : "+f"(d[0]), "+f"(d[1]), "+f"(d[2]), "+f"(d[3]), "+f"(d[4]), "+f"(d[5]), "+f"(d[6]), "+f"(d[7]),
      "+f"(d[8]), "+f"(d[9]), "+f"(d[10]), "+f"(d[11]), "+f"(d[12]), "+f"(d[13]), "+f"(d[14]), "+f"(d[15]),
      "+f"(d[16]), "+f"(d[17]), "+f"(d[18]), "+f"(d[19]), "+f"(d[20]), "+f"(d[21]), "+f"(d[22]), "+f"(d[23]),
      "+f"(d[24]), "+f"(d[25]), "+f"(d[26]), "+f"(d[27]), "+f"(d[28]), "+f"(d[29]), "+f"(d[30]), "+f"(d[31]),
      "+f"(d[32]), "+f"(d[33]), "+f"(d[34]), "+f"(d[35]), "+f"(d[36]), "+f"(d[37]), "+f"(d[38]), "+f"(d[39]),
      "+f"(d[40]), "+f"(d[41]), "+f"(d[42]), "+f"(d[43]), "+f"(d[44]), "+f"(d[45]), "+f"(d[46]), "+f"(d[47]),
      "+f"(d[48]), "+f"(d[49]), "+f"(d[50]), "+f"(d[51]), "+f"(d[52]), "+f"(d[53]), "+f"(d[54]), "+f"(d[55]),
      "+f"(d[56]), "+f"(d[57]), "+f"(d[58]), "+f"(d[59]), "+f"(d[60]), "+f"(d[61]), "+f"(d[62]), "+f"(d[63]),
      "+f"(d[64]), "+f"(d[65]), "+f"(d[66]), "+f"(d[67]), "+f"(d[68]), "+f"(d[69]), "+f"(d[70]), "+f"(d[71]),
      "+f"(d[72]), "+f"(d[73]), "+f"(d[74]), "+f"(d[75]), "+f"(d[76]), "+f"(d[77]), "+f"(d[78]), "+f"(d[79]),
      "+f"(d[80]), "+f"(d[81]), "+f"(d[82]), "+f"(d[83]), "+f"(d[84]), "+f"(d[85]), "+f"(d[86]), "+f"(d[87]),
      "+f"(d[88]), "+f"(d[89]), "+f"(d[90]), "+f"(d[91]), "+f"(d[92]), "+f"(d[93]), "+f"(d[94]), "+f"(d[95]),
      "+f"(d[96]), "+f"(d[97]), "+f"(d[98]), "+f"(d[99]), "+f"(d[100]), "+f"(d[101]), "+f"(d[102]), "+f"(d[103]),
      "+f"(d[104]), "+f"(d[105]), "+f"(d[106]), "+f"(d[107]), "+f"(d[108]), "+f"(d[109]), "+f"(d[110]), "+f"(d[111])
    : "r"(a[0]), "r"(a[1]), "r"(a[2]), "r"(a[3]), "l"(db), "r"(sd));
}

__device__ __forceinline__ void wgmma_rs_n240(float* d, const uint32_t* a, uint64_t db, int sd) {
  asm volatile("{ .reg .pred p; setp.ne.b32 p, %125, 0;\n"
      "wgmma.mma_async.sync.aligned.m64n240k16.f32.bf16.bf16 {"
      "%0,%1,%2,%3,%4,%5,%6,%7,%8,%9,%10,%11,%12,%13,%14,%15,"
      "%16,%17,%18,%19,%20,%21,%22,%23,%24,%25,%26,%27,%28,%29,%30,%31,"
      "%32,%33,%34,%35,%36,%37,%38,%39,%40,%41,%42,%43,%44,%45,%46,%47,"
      "%48,%49,%50,%51,%52,%53,%54,%55,%56,%57,%58,%59,%60,%61,%62,%63,"
      "%64,%65,%66,%67,%68,%69,%70,%71,%72,%73,%74,%75,%76,%77,%78,%79,"
      "%80,%81,%82,%83,%84,%85,%86,%87,%88,%89,%90,%91,%92,%93,%94,%95,"
      "%96,%97,%98,%99,%100,%101,%102,%103,%104,%105,%106,%107,%108,%109,%110,%111,"
      "%112,%113,%114,%115,%116,%117,%118,%119"
      "}, {%120,%121,%122,%123}, %124, p, 1, 1, 0; }"
    : "+f"(d[0]), "+f"(d[1]), "+f"(d[2]), "+f"(d[3]), "+f"(d[4]), "+f"(d[5]), "+f"(d[6]), "+f"(d[7]),
      "+f"(d[8]), "+f"(d[9]), "+f"(d[10]), "+f"(d[11]), "+f"(d[12]), "+f"(d[13]), "+f"(d[14]), "+f"(d[15]),
      "+f"(d[16]), "+f"(d[17]), "+f"(d[18]), "+f"(d[19]), "+f"(d[20]), "+f"(d[21]), "+f"(d[22]), "+f"(d[23]),
      "+f"(d[24]), "+f"(d[25]), "+f"(d[26]), "+f"(d[27]), "+f"(d[28]), "+f"(d[29]), "+f"(d[30]), "+f"(d[31]),
      "+f"(d[32]), "+f"(d[33]), "+f"(d[34]), "+f"(d[35]), "+f"(d[36]), "+f"(d[37]), "+f"(d[38]), "+f"(d[39]),
      "+f"(d[40]), "+f"(d[41]), "+f"(d[42]), "+f"(d[43]), "+f"(d[44]), "+f"(d[45]), "+f"(d[46]), "+f"(d[47]),
      "+f"(d[48]), "+f"(d[49]), "+f"(d[50]), "+f"(d[51]), "+f"(d[52]), "+f"(d[53]), "+f"(d[54]), "+f"(d[55]),
      "+f"(d[56]), "+f"(d[57]), "+f"(d[58]), "+f"(d[59]), "+f"(d[60]), "+f"(d[61]), "+f"(d[62]), "+f"(d[63]),
      "+f"(d[64]), "+f"(d[65]), "+f"(d[66]), "+f"(d[67]), "+f"(d[68]), "+f"(d[69]), "+f"(d[70]), "+f"(d[71]),
      "+f"(d[72]), "+f"(d[73]), "+f"(d[74]), "+f"(d[75]), "+f"(d[76]), "+f"(d[77]), "+f"(d[78]), "+f"(d[79]),
      "+f"(d[80]), "+f"(d[81]), "+f"(d[82]), "+f"(d[83]), "+f"(d[84]), "+f"(d[85]), "+f"(d[86]), "+f"(d[87]),
      "+f"(d[88]), "+f"(d[89]), "+f"(d[90]), "+f"(d[91]), "+f"(d[92]), "+f"(d[93]), "+f"(d[94]), "+f"(d[95]),
      "+f"(d[96]), "+f"(d[97]), "+f"(d[98]), "+f"(d[99]), "+f"(d[100]), "+f"(d[101]), "+f"(d[102]), "+f"(d[103]),
      "+f"(d[104]), "+f"(d[105]), "+f"(d[106]), "+f"(d[107]), "+f"(d[108]), "+f"(d[109]), "+f"(d[110]), "+f"(d[111]),
      "+f"(d[112]), "+f"(d[113]), "+f"(d[114]), "+f"(d[115]), "+f"(d[116]), "+f"(d[117]), "+f"(d[118]), "+f"(d[119])
    : "r"(a[0]), "r"(a[1]), "r"(a[2]), "r"(a[3]), "l"(db), "r"(sd));
}

__device__ __forceinline__ void wgmma_rs_n256(float* d, const uint32_t* a, uint64_t db, int sd) {
  asm volatile("{ .reg .pred p; setp.ne.b32 p, %133, 0;\n"
      "wgmma.mma_async.sync.aligned.m64n256k16.f32.bf16.bf16 {"
      "%0,%1,%2,%3,%4,%5,%6,%7,%8,%9,%10,%11,%12,%13,%14,%15,"
      "%16,%17,%18,%19,%20,%21,%22,%23,%24,%25,%26,%27,%28,%29,%30,%31,"
      "%32,%33,%34,%35,%36,%37,%38,%39,%40,%41,%42,%43,%44,%45,%46,%47,"
      "%48,%49,%50,%51,%52,%53,%54,%55,%56,%57,%58,%59,%60,%61,%62,%63,"
      "%64,%65,%66,%67,%68,%69,%70,%71,%72,%73,%74,%75,%76,%77,%78,%79,"
      "%80,%81,%82,%83,%84,%85,%86,%87,%88,%89,%90,%91,%92,%93,%94,%95,"
      "%96,%97,%98,%99,%100,%101,%102,%103,%104,%105,%106,%107,%108,%109,%110,%111,"
      "%112,%113,%114,%115,%116,%117,%118,%119,%120,%121,%122,%123,%124,%125,%126,%127"
      "}, {%128,%129,%130,%131}, %132, p, 1, 1, 0; }"
    : "+f"(d[0]), "+f"(d[1]), "+f"(d[2]), "+f"(d[3]), "+f"(d[4]), "+f"(d[5]), "+f"(d[6]), "+f"(d[7]),
      "+f"(d[8]), "+f"(d[9]), "+f"(d[10]), "+f"(d[11]), "+f"(d[12]), "+f"(d[13]), "+f"(d[14]), "+f"(d[15]),
      "+f"(d[16]), "+f"(d[17]), "+f"(d[18]), "+f"(d[19]), "+f"(d[20]), "+f"(d[21]), "+f"(d[22]), "+f"(d[23]),
      "+f"(d[24]), "+f"(d[25]), "+f"(d[26]), "+f"(d[27]), "+f"(d[28]), "+f"(d[29]), "+f"(d[30]), "+f"(d[31]),
      "+f"(d[32]), "+f"(d[33]), "+f"(d[34]), "+f"(d[35]), "+f"(d[36]), "+f"(d[37]), "+f"(d[38]), "+f"(d[39]),
      "+f"(d[40]), "+f"(d[41]), "+f"(d[42]), "+f"(d[43]), "+f"(d[44]), "+f"(d[45]), "+f"(d[46]), "+f"(d[47]),
      "+f"(d[48]), "+f"(d[49]), "+f"(d[50]), "+f"(d[51]), "+f"(d[52]), "+f"(d[53]), "+f"(d[54]), "+f"(d[55]),
      "+f"(d[56]), "+f"(d[57]), "+f"(d[58]), "+f"(d[59]), "+f"(d[60]), "+f"(d[61]), "+f"(d[62]), "+f"(d[63]),
      "+f"(d[64]), "+f"(d[65]), "+f"(d[66]), "+f"(d[67]), "+f"(d[68]), "+f"(d[69]), "+f"(d[70]), "+f"(d[71]),
      "+f"(d[72]), "+f"(d[73]), "+f"(d[74]), "+f"(d[75]), "+f"(d[76]), "+f"(d[77]), "+f"(d[78]), "+f"(d[79]),
      "+f"(d[80]), "+f"(d[81]), "+f"(d[82]), "+f"(d[83]), "+f"(d[84]), "+f"(d[85]), "+f"(d[86]), "+f"(d[87]),
      "+f"(d[88]), "+f"(d[89]), "+f"(d[90]), "+f"(d[91]), "+f"(d[92]), "+f"(d[93]), "+f"(d[94]), "+f"(d[95]),
      "+f"(d[96]), "+f"(d[97]), "+f"(d[98]), "+f"(d[99]), "+f"(d[100]), "+f"(d[101]), "+f"(d[102]), "+f"(d[103]),
      "+f"(d[104]), "+f"(d[105]), "+f"(d[106]), "+f"(d[107]), "+f"(d[108]), "+f"(d[109]), "+f"(d[110]), "+f"(d[111]),
      "+f"(d[112]), "+f"(d[113]), "+f"(d[114]), "+f"(d[115]), "+f"(d[116]), "+f"(d[117]), "+f"(d[118]), "+f"(d[119]),
      "+f"(d[120]), "+f"(d[121]), "+f"(d[122]), "+f"(d[123]), "+f"(d[124]), "+f"(d[125]), "+f"(d[126]), "+f"(d[127])
    : "r"(a[0]), "r"(a[1]), "r"(a[2]), "r"(a[3]), "l"(db), "r"(sd));
}

__device__ __forceinline__ void ln_finish(float mean, float var, float& mb, float& rinv) {
  mb = round_bf16(mean);
  float sd;
  asm("sqrt.approx.ftz.f32 %0, %1;" : "=f"(sd) : "f"(round_bf16(round_bf16(var) + 1e-5f)));
  asm("rcp.approx.ftz.f32 %0, %1;" : "=f"(rinv) : "f"(round_bf16(sd)));
}
__device__ __forceinline__ uint32_t sum4(uint32_t a, uint32_t b, uint32_t c, uint32_t d) { return badd2(badd2(badd2(d, c), b), a); }
struct Ring {
  uint32_t s, ph;
  __device__ __forceinline__ void next() { if (++s == NSTAGE) { s = 0; ph ^= 1; } }
};

__device__ __forceinline__ void conv_lda(uint32_t* a, int j, uint32_t base, bool on) {
  asm volatile("{ .reg .pred p; setp.ne.u32 p, %3, 0;\n @p ld.shared.u32 %0, [%2];\n @p ld.shared.u32 %1, [%2 + 128]; }"
               : "+r"(a[2 * j]), "+r"(a[2 * j + 1]) : "r"(base + (j >> 1) * 256 + (j & 1) * 16), "r"((uint32_t)on) : "memory");
}
__device__ __forceinline__ void conv_mma(float* acc, const uint32_t* a, uint64_t db) {
  wgmma_rs_n256(acc, a, db, 0);
  wgmma_rs_n240(acc, a + 4, db + 16, 1);
  wgmma_rs_n224(acc, a + 8, db + 32, 1);
  wgmma_rs_n208(acc, a + 12, db + 48, 1);
  wgmma_rs_n192(acc, a + 16, db + 64, 1);
  wgmma_rs_n176(acc, a + 20, db + 80, 1);
  wgmma_rs_n160(acc, a + 24, db + 96, 1);
  wgmma_rs_n144(acc, a + 28, db + 112, 1);
  wgmma_rs_n128(acc, a + 32, db + 128, 1);
  wgmma_rs_n112(acc, a + 36, db + 144, 1);
  wgmma_rs_n96(acc, a + 40, db + 160, 1);
  wgmma_rs_n80(acc, a + 44, db + 176, 1);
  wgmma_rs_n64(acc, a + 48, db + 192, 1);
  wgmma_rs_n48(acc, a + 52, db + 208, 1);
  wgmma_rs_n32(acc, a + 56, db + 224, 1);
  wgmma_rs_n16(acc, a + 60, db + 240, 1);
}
__device__ __forceinline__ uint32_t conv_part(const float* acc, int j) {
  const int q = 31 - j;
  return q == 31 ? pack_bf16(acc[124], acc[125]) : pack_bf16(acc[4 * q] + acc[(4 * q + 6) & 127], acc[4 * q + 1] + acc[(4 * q + 7) & 127]);
}
__device__ __forceinline__ uint4 conv_sum(const uint4* p) {
  return make_uint4(sum4(p[0].x, p[1].x, p[2].x, p[3].x), sum4(p[0].y, p[1].y, p[2].y, p[3].y), sum4(p[0].z, p[1].z, p[2].z, p[3].z),
                    sum4(p[0].w, p[1].w, p[2].w, p[3].w));
}
__device__ __forceinline__ int g2k(int rank, int kb) { return (rank * G2_KB + (kb < 6 ? 6 * kb : kb - 5 + (kb - 6) / 5)) * 64; }

template <int NV> __device__ __forceinline__ void gelu_stage(float* acc, const float* hb, uint32_t sa, int passes, uint32_t bar) {
#pragma unroll
  for (int i = 0; i < NV; i++) acc[i] = fmaf(acc[i], 0.5f, hb[(i >> 1) & 1]);
#pragma unroll 1
  for (; passes > 0; passes--, sa += NV * 256) {
#pragma unroll
    for (int i = 0; i < NV; i += 8)
      stsm4t(sa + i * 256, pack_bf16(gelu_half(acc[i]), gelu_half(acc[i + 1])), pack_bf16(gelu_half(acc[i + 2]), gelu_half(acc[i + 3])),
             pack_bf16(gelu_half(acc[i + 4]), gelu_half(acc[i + 5])), pack_bf16(gelu_half(acc[i + 6]), gelu_half(acc[i + 7])));
    __syncwarp();
    if (bar) mbar_arrive(bar);
    bar = 0;
#pragma unroll
    for (int i = 0; i < NV; i++) acc[i] = fmaf(acc[NV + i], 0.5f, hb[2 + ((i >> 1) & 1)]);
  }
}

__global__ void __cluster_dims__(2, 1, 1) __launch_bounds__(384, 1) fused_kernel(const __grid_constant__ Hot H, const __grid_constant__ Params P) {
  extern __shared__ __align__(1024) uint8_t smem_raw[];
  const uint32_t t0 = clk();
  const uint32_t sb = smem_u32(smem_raw);
  const int tid = threadIdx.x, lane = tid & 31;
  const int bid = blockIdx.x, rank = bid & 1;
  const Role& R = P.role[bid];
  Scratch* const S = H.S;
  uint32_t xr[18];
  const int row = bid * 16 + (tid >> 4);
  if (tid < 256 && bid < 128) {
    const char* src = reinterpret_cast<const char*>(H.x) + row * (D_ * 2) + (lane & 15) * 8;
#pragma unroll
    for (int j = 0; j < 9; j++) asm volatile("ld.global.nc.v2.u32 {%0,%1}, [%2];" : "=r"(xr[2 * j]), "=r"(xr[2 * j + 1]) : "l"(src + 128 * j));
  }
  const int warp = __shfl_sync(0xffffffffu, tid >> 5, 0);

  if (warp >= 8) {
    const bool one = elect_one();
    if (warp == 8 && one) {
#pragma unroll
      for (int b = B_FULL; b <= B_DONE; b += 8) mbar_init(sb + b, b < B_EMPTY ? 1 : b < B_SFREE ? 2 : b < B_CEMPTY ? 3 : b < B_G1DONE ? 4 : 8);
      asm volatile("fence.mbarrier_init.release.cluster;" ::: "memory");
    }
    __syncwarp();
    asm volatile("barrier.cluster.arrive.relaxed.aligned;" ::: "memory");
    asm volatile("setmaxnreg.dec.sync.aligned.u32 56;");
    asm volatile("barrier.cluster.wait.aligned;" ::: "memory");
    const bool left = R.at == 15;
    if (warp == 8) {
      const uint32_t ep = ldg32(S->cnt + C_EPOCH * 32);
      if (one) {
#pragma unroll 1
        for (int i = 0; i < 11; i++) asm volatile("prefetch.tensormap [%0];" :: "l"(&P.m_w1 + i) : "memory");
#pragma unroll 1
        for (int s = 0; s < NWE; s++) {
          mbar_expect_tx(sb + B_FULL + 8 * s, G1_BYTES);
          tma3d(sb + s * SLOT, &P.m_w1 + left, 0, s * 64, R.fg, sb + B_FULL + 8 * s);
        }
      }
      __syncwarp();
      if (bid < 128) bar_sync(2, 288);
      if (one) {
        TLREC(31);
        signal(S, C_H, EPOCH / 132);
        TLREC(1);
        const uint32_t boff = left ? 24576 : 16384;
        int kr = bid < 128 ? -2 : KV_ROUNDS + 1, ks = 0;
        auto kv_step = [&]() {
          if (ks == 0) {
            bulk_wait_all();
            if (kr < KV_ROUNDS - 2) {
              const int q = (kr + 2) % 3;
              const uint32_t in = sb + kv_buf(q), fb = sb + B_UFULL + 8 * q;
              mbar_expect_tx(fb, 3840 + 3264 + 768);
              tma2d(in, &P.m_k, (kr + 2) * 96, bid * 16 - 4, fb);
              tma2d(in + 3840, &P.m_v, (kr + 2) * 96, bid * 16 - 1, fb);
              bulk_load(in + 7168, H.shift_k + (kr + 2) * 384, 768, fb);
            }
            if (kr == KV_ROUNDS) { mbar_arrive(sb + B_KVDONE); kr++; }
          } else if (kr >= 0) {
            if (!mbar_test(sb + B_KFULL + 8 * (kr % 3), kr >= 3)) return;
            fence_async_smem();
            tma3d_store(&P.m_ub, sb + kv_buf(kr % 3) + (ks - 1) * 3072, 16 * (127 - bid), kr * 48, 2 * ks - 2);
            bulk_commit();
          }
          if (++ks == 3) { kr++; ks = kr == KV_ROUNDS - 2 || kr == KV_ROUNDS - 1; }
        };
        if (bid >= 128) mbar_arrive(sb + B_KVDONE);
        Ring r{0, 1};
#pragma unroll 1
        for (int kb = NWE - NW0; kb < G1_KB || kr <= KV_ROUNDS; kb++) {
          if (kb < G1_KB) {
          const int kw = kb < 0 ? kb + NW0 : kb, s = kb < 0 ? kw : r.s;
          const uint32_t fb = sb + B_FULL + 8 * s;
          if (kb < 0 || kb >= NW0) {
            mbar_wait(sb + B_EMPTY + 8 * s, r.ph);
            mbar_expect_tx(fb, G1_BYTES);
            tma3d(sb + s * SLOT, &P.m_w1 + left, 0, kw * 64, R.fg, fb);
            if (kb < 0) continue;
          }
          if (kb == 0) { await(S, C_H, ep); fence_async_global(); TLREC(2); }
          bulk_load(sb + s * SLOT + boff, S->h + (kb * 18 + R.at) * 2048, G1_BYTES - boff, fb);
          if (kb == 23) {
#pragma unroll 1
            for (int i = 0; i < 2; i++) {
              sts128(sb + cv_taps(i), 0, 0, 0, 0); sts128(sb + cv_taps(i) + 16, 0, 0, 0, 0);
              bulk_load(sb + cv_taps(i) + 32, H.ssm_k + (R.ch + i) * S_, 4096, sb + B_MISC);
            }
            mbar_expect_tx(sb + B_MISC, boff / 64 + 1152 + 8192);
            bulk_load(sb + SM_B1, H.b1 + R.fg * 64, boff / 64, sb + B_MISC);
            bulk_load(sb + SM_D, H.ssm_D, 1152, sb + B_MISC);
          }
          r.next();
          }
          if (kb >= KV0 && kr <= KV_ROUNDS) kv_step();
        }
        await(S, C_KV, ep);
        fence_async_global();
#pragma unroll 1
        for (int i = 0; i < R.ncv; i++) {
          if (i == 2) {
            if (R.sg >= 0) {
#pragma unroll 1
              for (int s = 2; s < NSTAGE; s++) {
                mbar_wait(sb + B_EMPTY + 8 * s, ((G1_KB / NSTAGE) - 1) & 1);
                mbar_expect_tx(sb + B_FULL + 8 * s, G2_BYTES);
                tma3d(sb + s * SLOT, &P.m_w2, 0, (rank * G2_KB + 6 * (s - 2)) * 64, R.sg, sb + B_FULL + 8 * s);
              }
            }
            mbar_wait(sb + B_G1DONE, 0);
          }
          const uint32_t kt = sb + cv_taps(i), b8 = sb + 8 * (i & 3);
          mbar_wait(b8 + B_CEMPTY, ((i >> 2) & 1) ^ 1);
          if (i < 2) mbar_arrive(b8 + B_KFULL);
          else {
            sts128(kt, 0, 0, 0, 0); sts128(kt + 16, 0, 0, 0, 0);
            mbar_expect_tx(b8 + B_KFULL, 4096);
            bulk_load(kt + 32, H.ssm_k + (R.ch + i) * S_, 4096, b8 + B_KFULL);
          }
          mbar_expect_tx(b8 + B_UFULL, 8192);
          bulk_load(sb + cv_in(i), S->ub + (R.ch + i) * 4096, 8192, b8 + B_UFULL);
        }
        if (R.sg >= 0) {
          mbar_expect_tx(sb + B_XY, 2 * 18432 + 2048 + 256);
          mbar_expect_tx(sb + B_XFULL, 9216);
          mbar_expect_tx(sb + B_XFULL + 8, 9216);
          await(S, C_U, ep);
          fence_async_global();
          TLREC(6);
#pragma unroll 1
          for (int kb = 0; kb < G2_KB; kb++, r.next()) {
            const int k0 = g2k(rank, kb);
            const uint32_t fb = sb + B_FULL + 8 * r.s, slot = sb + r.s * SLOT;
            if (kb >= NSTAGE - 2) {
              mbar_wait(sb + B_EMPTY + 8 * r.s, r.ph);
              if (kb == SYNCKB) asm volatile("red.relaxed.gpu.global.add.u32 [%0], %1;" :: "l"(S->cnt + C_SYNC * 32), "r"(EPOCH / 256) : "memory");
              if (kb == 6) { await(S, C_SYNC, ep); fence_async_global(); }
              mbar_expect_tx(fb, G2_BYTES);
              tma3d(slot, &P.m_w2, 0, k0, R.sg, fb);
            }
            tma2d(slot + 16384, &P.m_uld, k0, R.ds * 8, fb);
            tma2d(slot + 16384 + 9216, &P.m_uld, k0, R.dk * 8, fb);
            const uint32_t nx = kb - 8;
            if (nx == 0) { mbar_wait(sb + B_KVDONE, 1); fence_async_smem(); }
            if (nx < 8) tma2d(sb + SM_CV + nx * 2304, &P.m_x, R.dk * 8, R.sg * 64 + nx * 16, sb + B_XY);
          }
          bulk_load(sb + SM_ST, S->stats + R.sg * 64, 2048, sb + B_XY);
          bulk_load(sb + SM_B2, P.b2 + R.sg * 64, 256, sb + B_XY);
          await(S, C_Y, ep);
          fence_async_global();
          TLREC(19);
          tma3d(sb + SM_DED, &P.m_y, 0, R.dk * 8, R.sg, sb + B_XY);
          if (bid == 0) signal(S, C_EPOCH, EPOCH);
        }
      }
    } else {
      if (bid < 128) {
        const int ht = tid - 288, hf = ht >= 48, pr = ht - 48 * hf;
        const uint32_t st = (1 - hf) * 1536 + pr * 32, sw = (pr & 4) * 4;
#pragma unroll 1
        for (int r = 0; r < KV_ROUNDS; r++) {
          const int q = r % 3;
          const uint32_t in = sb + kv_buf(q);
          {
            mbar_wait_guarded(sb + B_UFULL + 8 * q, t0, r >= 3);
            uint32_t kk[12], vv[9];
#pragma unroll
            for (int j = 0; j < 12; j++) kk[j] = lds32(in + hf * 1536 + pr * 4 + j * 192);
#pragma unroll
            for (int j = 0; j < 9; j++) vv[j] = lds32(in + 3840 + hf * 1536 + pr * 4 + j * 192);
            const uint4 w = lds128(in + 7168 + pr * 16);
            const uint32_t w0 = __byte_perm(w.x, w.z, 0x5410), w1 = __byte_perm(w.x, w.z, 0x7632);
            const uint32_t w2 = __byte_perm(w.y, w.w, 0x5410), w3 = __byte_perm(w.y, w.w, 0x7632);
#pragma unroll
            for (int j = 0; j < 9; j++)
              vv[j] = bmul2(badd2(badd2(badd2(bmul2(kk[j], w3), bmul2(kk[j + 1], w2)), bmul2(kk[j + 2], w1)), bmul2(kk[j + 3], w0)), vv[j]);
            bar_sync(1, 96);
#pragma unroll
            for (int c = 0; c < 2; c++)
#pragma unroll
              for (int pi = 0; pi < 2; pi++) {
                const uint32_t sel = c ? 0x7632 : 0x5410;
                sts128(in + st + c * 3072 + (pi * 16 ^ sw), __byte_perm(vv[7 + pi], vv[6 + pi], sel), __byte_perm(vv[5 + pi], vv[4 + pi], sel),
                       __byte_perm(vv[3 + pi], vv[2 + pi], sel), __byte_perm(vv[1 + pi], vv[pi], sel));
              }
            bar_sync(1, 96);
            if (ht == 0) mbar_arrive(sb + B_KFULL + 8 * q);
          }
          __syncwarp();
        }
      }
      if (one) {
        if (warp < 11) {
          const int wg = warp - 9;
#pragma unroll 1
          for (int j = 0; j <= (left ? 3 + 3 * wg : 5); j++) {
            if (j == 0 || j == 2 + left) {
              mbar_wait_guarded(sb + B_STG + 8 * wg + (j ? 0 : 16), t0);
              fence_async_smem();
              TLREC(13 + wg);
            }
            const int hi = left && j >= 3;
            if (j < (left ? 3 + 3 * wg : 5))
              tma2d_store(&P.m_ust, sb + (wg ? SM_ST1 : SM_DED) + j * 4096, (R.fg + wg + hi) * 64, (R.at + j - 3 * hi) * 32);
          }
          bulk_commit();
          bulk_wait_all();
          mbar_arrive(sb + B_STORED + 8 * wg);
          asm volatile("mbarrier.arrive.shared::cta.b64 _, [%0], 3;" :: "r"(sb + B_SFREE + 8 * wg) : "memory");
          signal(S, wg ? C_SYNC : C_U, wg ? EPOCH / 264 : EPOCH / 132);
          TLREC(15 + wg);
        } else {
          mbar_wait_guarded(sb + B_KVDONE, t0);
          signal(S, C_KV, EPOCH / 132);
          TLREC(27);
        }
      }
      __syncwarp();
#pragma unroll 1
      for (int i = 0; i < R.ncv; i++) {
        const uint32_t red = sb + cv_red(i, R.ncv) + (tid - 288) * 16;
        uint4* yo = reinterpret_cast<uint4*>(S->y + (R.ch + i) * S_) + (tid - 288);
        mbar_wait_guarded(sb + B_STORED + 8 * (i & 1), t0);
        mbar_wait_guarded(sb + B_STG + 8 * (i & 1) + (i + 2 < R.ncv ? 0 : 16), t0, i + 2 >= R.ncv || !(i & 2));
        uint4 p[2][4];
#pragma unroll
        for (int x = 0; x < 8; x++) p[x >> 2][x & 3] = lds128(red + (x & 3) * CV_REDW + (x >> 2) * 1536);
        yo[0] = conv_sum(p[0]);
        if (warp < 11) {
#pragma unroll
          for (int x = 0; x < 4; x++) p[0][x] = lds128(red + x * CV_REDW + 3072);
          yo[192] = conv_sum(p[0]);
        }
        yo[96] = conv_sum(p[1]);
        __syncwarp();
        if (one) mbar_arrive(sb + (i + 4 == R.ncv ? B_PDONE : B_SFREE + 8 * (i & 1)));
        if (i + 3 == R.ncv) {
          bar_sync(1, 96);
          if (warp == 11 && one) { fence_async_smem(); mbar_arrive(sb + B_EMPTY); }
          __syncwarp();
        }
      }
      bar_sync(1, 96);
      if (warp == 11 && one) {
        TLREC(7);
        mbar_arrive(sb + B_KVDONE);
        signal(S, C_Y, EPOCH / 132);
        if (R.sg >= 0) mbar_wait_guarded(sb + B_DONE, t0);
      }
    }
    TLEND();
  } else {
    asm volatile("barrier.cluster.arrive.relaxed.aligned;" ::: "memory");
    if (bid < 128) {
      float c[36], s[4];
#pragma unroll
      for (int i = 0; i < 18; i++) { c[2 * i] = bf_lo(xr[i]); c[2 * i + 1] = bf_hi(xr[i]); }
#pragma unroll
      for (int i = 0; i < 36; i++) s[i & 3] = i < 4 ? c[i] : s[i & 3] + c[i];
      const float ml = ((s[0] + s[1]) + (s[2] + s[3])) * (1.0f / 36.0f);
#pragma unroll
      for (int i = 0; i < 36; i++) { c[i] -= ml; s[i & 3] = i < 4 ? c[i] * c[i] : fmaf(c[i], c[i], s[i & 3]); }
      float m = ml, q = (s[0] + s[1]) + (s[2] + s[3]), n2 = 18.f;
#pragma unroll
      for (int o = 1; o < 16; o <<= 1) {
        const float mo = __shfl_xor_sync(0xffffffffu, m, o), qo = __shfl_xor_sync(0xffffffffu, q, o);
        const float dl = m - mo;
        q = fmaf(dl * dl, n2, q + qo);
        m = fmaf(dl, -0.5f, m);
        n2 *= 2.f;
      }
      const float var = q * (1.0f / 576.0f);
      float mb, rinv, mb2, rinv2;
      ln_finish(m, var, mb, rinv);
      ln_finish((m - mb) * rinv, var * rinv * rinv, mb2, rinv2);
      const float ca = rinv * rinv2, cb = fmaf(ml - mb, rinv, -mb2) * rinv2;
      uint2* dst = reinterpret_cast<uint2*>(S->h) + ((row >> 6) * 18 + ((lane >> 3) & 1)) * 512 + (row & 63) * 8 + ((lane & 7) ^ (row & 6));
#pragma unroll
      for (int j = 0; j < 9; j++)
        dst[1024 * j] = make_uint2(pack_bf16(fmaf(c[4 * j], ca, cb), fmaf(c[4 * j + 1], ca, cb)), pack_bf16(fmaf(c[4 * j + 2], ca, cb), fmaf(c[4 * j + 3], ca, cb)));
      const uint32_t rh = pack_bf16(rinv, rinv);
      if (!(lane & 15)) S->stats[row] = make_uint4(pack_bf16(mb, mb), rh, pack_bf16(rinv - bf_lo(rh), rinv - bf_lo(rh)), 0);
      __syncwarp();
      bar_arrive(2, 288);
    }
    asm volatile("setmaxnreg.inc.sync.aligned.u32 224;");
    asm volatile("barrier.cluster.wait.aligned;" ::: "memory");
    const int wg = warp >> 2, w = warp & 3, g = lane >> 2, t = lane & 3, wtid = tid & 127;
    const bool elect = wtid == 0;
    const uint64_t da0 = make_desc(sb + wg * 8192, 8192, 1024, 1);
    const uint32_t swz = ((lane >> 4) * 8 + (lane & 7)) * 128 + (((2 * w + ((lane >> 3) & 1)) ^ (lane & 7)) << 4);
    const uint32_t stg = sb + (wg ? SM_ST1 : SM_DED), ka0 = (8 * w + g + t + 1) * 4;
    uint32_t a[64];
    {
      auto mainloop = [&](auto&& mma) {
        Ring r{0, 0};
        uint32_t rel = 0;
#pragma unroll 1
        for (int kb = 0; kb < G1_KB; kb++, r.next()) {
          if (kb == G1_KB - G1_TAIL && wg) {
            wg_wait<0>();
            if (elect) mbar_arrive(rel);
            rel = 0;
            if (PRE1) {
              mbar_wait(sb + B_MISC, 0);
#pragma unroll
              for (int j = 0; j < 32; j++) conv_lda(a, j, sb + SM_CV + 16384 + CV_K + ka0, true);
            }
            bar_sync(5, 256);
          }
          mbar_wait(sb + B_FULL + 8 * r.s, r.ph);
          if (kb == 0 && warp == 0) TLREC(3);
          wg_fence();
          mma(r.s * (SLOT >> 4), kb);
          wg_commit();
          if (kb == G1_KB - 1) break;
          wg_wait<1>();
          if (elect && rel) mbar_arrive(rel);
          rel = sb + B_EMPTY + 8 * r.s;
        }
        bar_arrive(5, 256);
        wg_wait<0>();
      };
      float hb[4];
      auto staged = [&](int second) {
        if (!w) TLREC(4 + wg);
        if (lane == 0) mbar_arrive(sb + B_G1DONE);
        mbar_wait(sb + B_MISC, 0);
#pragma unroll
        for (int i = 0; i < 4; i++) hb[i] = 0.5f * bf_lo(lds16(sb + SM_B1 + (warp * 16 + g + (i & 1) * 8 + (i >> 1) * second) * 2));
        mbar_wait(sb + B_KVDONE, 0);
        if (wg) mbar_wait(sb + B_G1DONE, 0);
      };
      if (R.at != 15) {
        const uint64_t db0 = make_desc(sb + 16384, 4096, 512, 2);
        float acc[80];
        mainloop([&](uint32_t o, int kb) {
          wgmma_ss_n160_t11(acc, da0 + o, db0 + o, kb);
#pragma unroll
          for (int k = 1; k < 4; k++) wgmma_ss_n160_t11(acc, da0 + o + k * 128, db0 + o + k * 64, 1);
        });
        pin_regs<80>(acc);
        staged(0);
        gelu_stage<40>(acc, hb, stg + swz, 2, lane ? 0 : sb + B_STG + 8 * wg + 16);
      } else {
        const uint64_t db0 = make_desc(sb + 24576, 4096, 512, 2);
        float acc[96];
        auto block = [&](float* d, uint64_t da, uint64_t db, int kb) {
          wgmma_ss_n96_t11(d, da, db, kb);
#pragma unroll
          for (int k = 1; k < 4; k++) wgmma_ss_n96_t11(d, da + k * 128, db + k * 64, 1);
        };
        if (wg) mainloop([&](uint32_t o, int kb) { block(acc, da0 + o, db0 + o, kb); block(acc + 48, da0 + o + 512, db0 + o, kb); });
        else mainloop([&](uint32_t o, int kb) { block(acc, da0 + o, db0 + o, kb); });
        pin_regs<96>(acc);
        staged(64);
        gelu_stage<48>(acc, hb, stg + swz, 1 + wg, lane ? 0 : sb + B_STG + 8 * wg + 16);
      }
      __syncwarp();
      if (lane == 0) mbar_arrive(sb + B_STG + 8 * wg);
    }
    {
      if (!wg || !PRE1) {
#pragma unroll
        for (int j = 0; j < 32; j++) conv_lda(a, j, sb + SM_CV + 16384 + wg * CV_K + ka0, true);
      }
#pragma unroll 1
      for (int i = wg; i < R.ncv; i += 2) {
        const bool more = i + 2 < R.ncv;
        const uint32_t dd = lds16(sb + SM_D + (R.ch + i) * 2);
        a[0] = badd2(a[0], ka0 == 32 ? dd : 0); a[2] = badd2(a[2], ka0 == 16 ? dd : 0);
        float acc[128];
        mbar_wait(sb + B_UFULL + 8 * (i & 3), (i >> 2) & 1);
        bar_sync(5 + wg, 256);
        if (!w && i < 4) TLREC(22 + i);
        wg_fence();
        conv_mma(acc, a, make_desc(sb + cv_in(i), 4096, 128, 0));
        wg_commit();
        const bool last = i + 1 == R.ncv;
        if (!last) bar_arrive(5 + (wg ^ 1), 256);
        if (more) {
          mbar_wait(sb + B_SFREE + 8 * wg, (i >> 1) & 1);
          mbar_wait(sb + B_KFULL + 8 * ((i + 2) & 3), ((i + 2) >> 2) & 1);
        } else if (last) {
          if (elect) mbar_arrive(sb + B_EMPTY);
          mbar_wait(sb + B_PDONE, 0);
        }
        wg_wait<0>();
        pin_regs<128>(acc);
        if (lane == 0) mbar_arrive(sb + B_CEMPTY + 8 * (i & 3));
        if (!more && elect) mbar_arrive(sb + B_EMPTY + 8);
        const uint32_t red = sb + cv_red(i, R.ncv), ka = sb + cv_taps(i + 2) + ka0;
        if (lane < 8 * w) sts32(red + w * CV_REDW + lane * 4, 0);
        const uint32_t wr = red + w * CV_REDW + (8 * (3 - t + w) + g) * 4;
#pragma unroll
        for (int j = 0; j < 32; j++) {
          conv_lda(a, j, ka, more);
          sts32(wr + j * 128, conv_part(acc, j));
        }
        __syncwarp();
        if (lane == 0) mbar_arrive(sb + B_STG + 8 * wg + (more ? 0 : 16));
      }
      if (!w) TLREC(20 + wg);
    }
    if (R.sg >= 0) {
      const int srow = R.sg * 64 + warp * 16;
      const uint64_t db0 = make_desc(sb + 16384, 16, 1024, 1);
      const uint32_t xo = sb + SM_CV + warp * 2304, xa = xo + (lane & 15) * 144;
      float acc[72];
      Ring r{G1_KB % NSTAGE, (G1_KB / NSTAGE) & 1};
      uint32_t rel = 0;
#pragma unroll 1
      for (int kb = 0; kb < G2_KB; kb++, r.next()) {
        if (kb == G2_KB - G2_TAIL && wg) {
          wg_wait<0>();
          if (elect) mbar_arrive_remote(rel);
          rel = 0;
          bar_sync(7, 256);
        }
        mbar_wait(sb + B_FULL + 8 * r.s, r.ph);
        if (kb == 0 && !w) TLREC(17 + wg);
        if (kb == 8 && warp == 0) TLREC(26);
        if (kb == 20 && warp == 0) TLREC(8);
        if (kb == 27 && warp == 0) TLREC(30);
        const uint64_t da = da0 + r.s * (SLOT >> 4), db = db0 + r.s * (SLOT >> 4);
        wg_fence();
        wgmma_ss_n144_t10(acc, da, db, kb);
#pragma unroll
        for (int k = 1; k < 4; k++) wgmma_ss_n144_t10(acc, da + k * 128, db + k * 2, 1);
        wg_commit();
        if (kb == G2_KB - 1) break;
        wg_wait<1>();
        if (elect && rel) mbar_arrive_remote(rel);
        rel = kb == G2_KB - NSTAGE ? mapa(sb + B_XRDY, rank ^ 1) : sb + B_EMPTY + 8 * r.s;
      }
      if (!wg) bar_arrive(7, 256);
      const uint32_t xz = sb + XSLOT * SLOT + wg * 10240 + wtid * 16;
      const uint32_t rz = mapa(xz, rank ^ 1), rb = mapa(sb + B_XFULL + 8 * wg, rank ^ 1);
      mbar_wait(sb + B_XRDY, 0);
      wg_wait<0>();
      pin_regs<72>(acc);
      if (!w) TLREC(28 + wg);
#pragma unroll
      for (int i = 0; i < 32; i += 8)
        asm volatile("st.async.weak.shared::cluster.mbarrier::complete_tx::bytes.v4.b32 [%0], {%1,%2,%3,%4}, [%5];"
                     :: "r"(rz + i * 256), "r"(pack_bf16(acc[i], acc[i + 1])), "r"(pack_bf16(acc[i + 2], acc[i + 3])),
                        "r"(pack_bf16(acc[i + 4], acc[i + 5])), "r"(pack_bf16(acc[i + 6], acc[i + 7])), "r"(rb) : "memory");
      asm volatile("st.async.weak.shared::cluster.mbarrier::complete_tx::bytes.v2.b32 [%0], {%1,%2}, [%3];"
                   :: "r"(rz + 8192), "r"(pack_bf16(acc[32], acc[33])), "r"(pack_bf16(acc[34], acc[35])), "r"(rb) : "memory");
      uint32_t xx[18], ss[18];
      mbar_wait(sb + B_XY, 0);
      {
        const uint32_t ya = sb + SM_DED + wg * 9216 + swz;
        const uint4 st0 = lds128(sb + SM_ST + (warp * 16 + g) * 16), st1 = lds128(sb + SM_ST + (warp * 16 + g + 8) * 16);
        const float hb0 = 0.5f * bf_lo(lds16(sb + SM_B2 + (warp * 16 + g) * 2)), hb1 = 0.5f * bf_lo(lds16(sb + SM_B2 + (warp * 16 + g + 8) * 2));
#pragma unroll
        for (int q = 0; q < 8; q += 2) { ldsm4(xx + 2 * q, xa + (lane >> 4) * 16 + q * 16); ldsm4t(ss + 2 * q, ya + q * 1024); }
        ldsm2(xx + 16, xa + 128);
        ldsm2t(ss + 16, ya + 8 * 1024);
#pragma unroll
        for (int i = 0; i < 18; i++) {
          const uint4& st = (i & 1) ? st1 : st0;
          const uint32_t c = bsub2(xx[i], st.x);
          ss[i] = bmul2(bfma2(c, st.y, bmul2(c, st.z)), ss[i]);
        }
#pragma unroll
        for (int i = 36; i < 72; i++) acc[i] = fmaf(acc[i], 0.5f, (i & 2) ? hb1 : hb0);
      }
      mbar_wait_cluster(sb + B_XFULL + 8 * wg, 0);
      if (!w) TLREC(9 + wg);
#pragma unroll
      for (int q = 0; q < 5; q++) {
        const uint4 v = lds128(xz + q * 2048);
        const uint32_t pv[4] = {v.x, v.y, v.z, v.w};
#pragma unroll
        for (int i = 4 * q; i < 4 * q + 4 && i < 18; i++)
          xx[i] = bfma2(ss[i], pack_bf16(silu_half(fmaf(bf_lo(pv[i & 3]), 0.5f, acc[36 + 2 * i])), silu_half(fmaf(bf_hi(pv[i & 3]), 0.5f, acc[37 + 2 * i]))), xx[i]);
        if (q < 4) stsm4(xa + (lane >> 4) * 16 + q * 32, xx[4 * q], xx[4 * q + 1], xx[4 * q + 2], xx[4 * q + 3]);
        else stsm2(xa + 128, xx[16], xx[17]);
      }
      __syncwarp();
      if (elect_one()) {
        fence_async_smem();
        tma2d_store(&P.m_out, xo, R.dk * 8, srow);
        bulk_commit();
        mbar_arrive(sb + B_DONE);
        bulk_wait_read();
      }
      if (!w) TLREC(11 + wg);
    }
    TLEND();
  }
}

typedef CUresult (*EncodeFn)(CUtensorMap*, CUtensorMapDataType, cuuint32_t, void*, const cuuint64_t*, const cuuint64_t*, const cuuint32_t*,
                             const cuuint32_t*, CUtensorMapInterleave, CUtensorMapSwizzle, CUtensorMapL2promotion, CUtensorMapFloatOOBfill);

void make_map(EncodeFn fn, CUtensorMap* m, const void* ptr, int rank, const cuuint64_t* dims, const cuuint64_t* strides, const cuuint32_t* box,
              CUtensorMapSwizzle sw) {
  const cuuint32_t es[3] = {1, 1, 1};
  fn(m, CU_TENSOR_MAP_DATA_TYPE_BFLOAT16, rank, const_cast<void*>(ptr), dims, strides, box, es, CU_TENSOR_MAP_INTERLEAVE_NONE, sw,
     CU_TENSOR_MAP_L2_PROMOTION_L2_256B, CU_TENSOR_MAP_FLOAT_OOB_FILL_NONE);
}

void make_roles(Role* R) {
  int nl = 0, ch = 0;
  for (int gi = 0; gi < 8; gi++)
    for (int b = 0; b < 132; b++) {
      const int c = b >> 1, rank = b & 1;
      int g, idx;
      if (c < 4) { g = 0; idx = 4 + c; }
      else if (c < 36) { g = (c - 4) & 7; idx = (c - 4) >> 3; }
      else if (c < 64) { g = 1 + (c - 36) % 7; idx = 4 + (c - 36) / 7; }
      else { g = c - 58; idx = 8; }
      if (g != gi) continue;
      Role& r = R[b];
      r.sg = (int8_t)(idx < 8 ? 2 * (2 * g + (idx >> 2)) : -1);
      r.dk = (int8_t)((idx & 3) * 18 + rank * 9);
      r.ds = (int8_t)((idx & 3) * 18 + (rank ^ 1) * 9);
      if (idx < (g < 2 ? 6 : 7)) {
        const int c1 = (g < 2 ? 6 * g : 7 * g - 2) + idx;
        r.fg = (int8_t)((2 * (c1 / 3) + rank) * 2); r.at = (int8_t)(c1 % 3 * 5); r.ncv = NCV_REG;
      } else {
        r.fg = (int8_t)(3 * nl++); r.at = 15; r.ncv = idx < 8 ? NCV_LEFT : NCV_LONG;
      }
      r.ch = (int16_t)ch;
      ch += r.ncv;
    }
}

}

extern "C" void kernel_launch(void* const* d_in, const int* in_sizes, int n_in, void* d_out, int out_size) {
  static Params P;
  static Hot H;
  static const void* cached[6] = {nullptr, nullptr, nullptr, nullptr, nullptr, nullptr};
  const void* now[6] = {d_in[0], d_in[1], d_in[2], d_in[7], d_in[9], d_out};
  bool same = true;
  for (int i = 0; i < 6; i++) { same = same && cached[i] == now[i]; cached[i] = now[i]; }
  if (!same) {
    void* fp = nullptr;
    cudaDriverEntryPointQueryResult qr;
    cudaGetDriverEntryPoint("cuTensorMapEncodeTiled", &fp, cudaEnableDefault, &qr);
    EncodeFn fn = (EncodeFn)fp;
    void* ps;
    cudaGetSymbolAddress(&ps, g_scratch);
    H.S = (Scratch*)ps;
    const void *pu = (char*)ps + offsetof(Scratch, u), *py = (char*)ps + offsetof(Scratch, y), *pb = (char*)ps + offsetof(Scratch, ub);
    { cuuint64_t d[3] = {64, S_, F_ / 64}, s[2] = {F_ * 2, 128}; cuuint32_t b[3] = {64, 64, 2}; make_map(fn, &P.m_w1, d_in[7], 3, d, s, b, CU_TENSOR_MAP_SWIZZLE_128B);
      b[2] = 3; make_map(fn, &P.m_w1l, d_in[7], 3, d, s, b, CU_TENSOR_MAP_SWIZZLE_128B); }
    { cuuint64_t d[2] = {F_, D_}, s[1] = {F_ * 2}; cuuint32_t b[2] = {64, 32}; make_map(fn, &P.m_ust, pu, 2, d, s, b, CU_TENSOR_MAP_SWIZZLE_128B); }
    { cuuint64_t d[3] = {64, F_, S_ / 64}, s[2] = {S_ * 2, 128}; cuuint32_t b[3] = {64, 64, 2}; make_map(fn, &P.m_w2, d_in[9], 3, d, s, b, CU_TENSOR_MAP_SWIZZLE_128B); }
    { cuuint64_t d[2] = {F_, D_}, s[1] = {F_ * 2}; cuuint32_t b[2] = {64, 72}; make_map(fn, &P.m_uld, pu, 2, d, s, b, CU_TENSOR_MAP_SWIZZLE_128B); }
    { cuuint64_t d[2] = {D_, S_}, s[1] = {D_ * 2}; cuuint32_t b[2] = {72, 16}; make_map(fn, &P.m_out, d_out, 2, d, s, b, CU_TENSOR_MAP_SWIZZLE_NONE);
      make_map(fn, &P.m_x, d_in[0], 2, d, s, b, CU_TENSOR_MAP_SWIZZLE_NONE);
      b[0] = 96; b[1] = 20; make_map(fn, &P.m_k, d_in[1], 2, d, s, b, CU_TENSOR_MAP_SWIZZLE_NONE);
      b[1] = 17; make_map(fn, &P.m_v, d_in[2], 2, d, s, b, CU_TENSOR_MAP_SWIZZLE_NONE); }
    { cuuint64_t d[3] = {64, D_, S_ / 64}, s[2] = {S_ * 2, 128}; cuuint32_t b[3] = {64, 72, 2}; make_map(fn, &P.m_y, py, 3, d, s, b, CU_TENSOR_MAP_SWIZZLE_128B); }
    { cuuint64_t d[3] = {2048, D_ / 2, 4}, s[2] = {16384, 4096}; cuuint32_t b[3] = {16, 48, 2}; make_map(fn, &P.m_ub, pb, 3, d, s, b, CU_TENSOR_MAP_SWIZZLE_32B); }
    make_roles(P.role);
    cudaFuncSetAttribute(fused_kernel, cudaFuncAttributeMaxDynamicSharedMemorySize, SM_TOTAL);
  }
  H.x = (const __nv_bfloat16*)d_in[0];
  H.shift_k = (const __nv_bfloat16*)d_in[3]; H.ssm_k = (const __nv_bfloat16*)d_in[4]; H.ssm_D = (const __nv_bfloat16*)d_in[5];
  H.b1 = (const __nv_bfloat16*)d_in[8]; P.b2 = (const __nv_bfloat16*)d_in[10];
  fused_kernel<<<132, 384, SM_TOTAL>>>(H, P);
}
```

```cpp
#include <cuda_runtime.h>
#include <cuda.h>
#include <cuda_bf16.h>
#include <stddef.h>
#include <stdint.h>

namespace {

constexpr int S_ = 2048, D_ = 576, F_ = 4608;
constexpr int NSTAGE = 5, SLOT = 36864;
constexpr int G1_KB = 32, G2_KB = 36;
constexpr int G1_BYTES = 36864, G2_BYTES = 16384 + 18432;
#define NCV_LEFT 4
constexpr int NCV_REG = 4, NCV_LONG = (D_ - 108 * NCV_REG - 20 * NCV_LEFT) / 4;
static_assert(108 * NCV_REG + 20 * NCV_LEFT + 4 * NCV_LONG == D_, "conv split");
constexpr int KV_ROUNDS = 6;
constexpr int NWE = 1, NW0 = 2;
constexpr int G1_TAIL = 4, G2_TAIL = 3;
constexpr int SYNCA = 5, SYNCKB = 8;
constexpr int PRE1 = 1;
constexpr int KV0 = 5;

constexpr int CV_K = 4224, CV_REDW = 2112 * 2;
constexpr int SM_DED = NSTAGE * SLOT;
constexpr int SM_CV = SM_DED + 20480;
constexpr int SM_ST1 = 0;
constexpr int SM_ST = SM_CV + 18432, SM_B2 = SM_ST + 2048;
constexpr int SM_B1 = SM_CV + 2 * (8192 + CV_K), SM_D = SM_B1 + 384;
constexpr int SM_BAR = SM_D + 1152;
constexpr int SM_TOTAL = SM_BAR + 768;
static_assert(G1_KB % NSTAGE == 2, "slots 0 and 1 hold the last GEMM1 k-blocks and the last two of the first GEMM2 stages");
static_assert(NCV_REG == 4 && NCV_LEFT == 4 && NCV_LONG % 4 == 0, "the last two channels use buffers 2 and 3");
constexpr int XSLOT = (G1_KB + G2_KB) % NSTAGE;
__device__ __forceinline__ uint32_t kv_buf(int q) { return q == 2 ? SM_DED : SM_CV + q * 8192; }
__device__ __forceinline__ uint32_t cv_red(int i, int n) { return i + 2 == n ? SM_CV : (i & 1) && i + 1 < n ? SLOT + 16384 : SM_DED; }
__device__ __forceinline__ uint32_t cv_in(int i) { return (i & 2 ? SLOT : SM_CV) + (i & 1) * 8192; }
__device__ __forceinline__ uint32_t cv_taps(int i) { return (i & 2 ? SM_ST1 + 24576 : SM_CV + 16384) + (i & 1) * CV_K; }
constexpr int bar_at(int i) { return SM_BAR + 8 * i; }
constexpr int B_FULL = bar_at(0)  , B_KFULL = bar_at(5)  , B_UFULL = bar_at(9)  , B_KVDONE = bar_at(13), B_STORED = bar_at(14)  ,
              B_XFULL = bar_at(16)  , B_XY = bar_at(18), B_MISC = bar_at(19),
              B_EMPTY = bar_at(20)  , B_XRDY = bar_at(25),
              B_SFREE = bar_at(26)  , B_PDONE = bar_at(28),
              B_CEMPTY = bar_at(29)  , B_STG = bar_at(33)  ,
              B_G1DONE = bar_at(37), B_DONE = bar_at(38);
constexpr int C_H = 0, C_KV = 1, C_U = 2  , C_Y = 4, C_SYNC = 5, C_EPOCH = 6, C_COUNT = 7;
constexpr uint32_t EPOCH = 128 * 33;

struct Scratch {
  uint32_t cnt[C_COUNT * 32];
  alignas(1024) uint4 stats[S_];
  alignas(1024) __nv_bfloat16 h[S_ * D_];
  alignas(1024) __nv_bfloat16 ub[D_ * 4096];
  alignas(1024) __nv_bfloat16 y[D_ * S_];
  alignas(1024) __nv_bfloat16 u[D_ * F_];
};
__device__ Scratch g_scratch;

struct Hot {
  const __nv_bfloat16 *x, *shift_k, *ssm_k, *ssm_D, *b1;
  Scratch* S;
};
struct Role {
  int8_t fg;
  int8_t at;
  int8_t sg;
  int8_t dk, ds;
  int8_t ncv;
  int16_t ch;
};
struct Params {
  const __nv_bfloat16* b2;
  Role role[132];
  CUtensorMap m_w1, m_w1l, m_ust, m_w2, m_uld, m_out, m_x, m_y, m_k, m_v, m_ub;
};

#define TLREC(i) do { } while (0)
#define TLEND() do { } while (0)

__device__ __forceinline__ uint32_t smem_u32(const void* p) { return (uint32_t)__cvta_generic_to_shared(p); }
__device__ __forceinline__ void mbar_init(uint32_t bar, uint32_t cnt) { asm volatile("mbarrier.init.shared::cta.b64 [%0], %1;" :: "r"(bar), "r"(cnt) : "memory"); }
__device__ __forceinline__ void mbar_expect_tx(uint32_t bar, uint32_t bytes) { asm volatile("mbarrier.arrive.expect_tx.shared::cta.b64 _, [%0], %1;" :: "r"(bar), "r"(bytes) : "memory"); }
__device__ __forceinline__ void mbar_arrive(uint32_t bar) { asm volatile("mbarrier.arrive.shared::cta.b64 _, [%0];" :: "r"(bar) : "memory"); }
__device__ __forceinline__ uint32_t mapa(uint32_t addr, uint32_t cta) { uint32_t r; asm volatile("mapa.shared::cluster.u32 %0, %1, %2;" : "=r"(r) : "r"(addr), "r"(cta)); return r; }
__device__ __forceinline__ void mbar_arrive_remote(uint32_t rbar) { asm volatile("mbarrier.arrive.shared::cluster.b64 _, [%0];" :: "r"(rbar) : "memory"); }
__device__ __forceinline__ uint32_t clk() { uint32_t c; asm volatile("mov.u32 %0, %%clock;" : "=r"(c)); return c; }
__device__ __forceinline__ bool elect_one() {
  uint32_t p; asm volatile("{ .reg .pred p; elect.sync _|p, 0xffffffff; selp.u32 %0, 1, 0, p; }" : "=r"(p)); return p;
}
__device__ __forceinline__ void guard(uint32_t t0) { if ((int32_t)(clk() - t0) < 0) __trap(); }
__device__ __forceinline__ void mbar_wait(uint32_t bar, uint32_t parity) {
  asm volatile("{\n .reg .pred p;\n W_%=:\n mbarrier.try_wait.parity.shared::cta.b64 p, [%0], %1;\n @!p bra W_%=;\n }" :: "r"(bar), "r"(parity) : "memory");
}
__device__ __forceinline__ void mbar_wait_cluster(uint32_t bar, uint32_t parity) {
  asm volatile("{\n .reg .pred p;\n W_%=:\n mbarrier.try_wait.parity.acquire.cluster.shared::cta.b64 p, [%0], %1;\n @!p bra W_%=;\n }" :: "r"(bar), "r"(parity) : "memory");
}
__device__ __forceinline__ bool mbar_try(uint32_t bar, uint32_t parity) {
  uint32_t ok;
  asm volatile("{ .reg .pred p; mbarrier.try_wait.parity.shared::cta.b64 p, [%1], %2, 100000; selp.u32 %0, 1, 0, p; }" : "=r"(ok) : "r"(bar), "r"(parity) : "memory");
  return ok;
}
__device__ __forceinline__ bool mbar_test(uint32_t bar, uint32_t parity) {
  uint32_t ok;
  asm volatile("{ .reg .pred p; mbarrier.test_wait.parity.shared::cta.b64 p, [%1], %2; selp.u32 %0, 1, 0, p; }" : "=r"(ok) : "r"(bar), "r"(parity) : "memory");
  return ok;
}
__device__ __forceinline__ void mbar_wait_guarded(uint32_t bar, uint32_t t0, uint32_t parity = 0) { while (!mbar_try(bar, parity)) guard(t0); }
__device__ __forceinline__ void tma2d(uint32_t dst, const CUtensorMap* m, int c0, int c1, uint32_t bar) {
  asm volatile("cp.async.bulk.tensor.2d.shared::cluster.global.mbarrier::complete_tx::bytes [%0], [%1, {%3, %4}], [%2];"
               :: "r"(dst), "l"(m), "r"(bar), "r"(c0), "r"(c1) : "memory");
}
__device__ __forceinline__ void tma3d(uint32_t dst, const CUtensorMap* m, int c0, int c1, int c2, uint32_t bar) {
  asm volatile("cp.async.bulk.tensor.3d.shared::cluster.global.mbarrier::complete_tx::bytes [%0], [%1, {%3, %4, %5}], [%2];"
               :: "r"(dst), "l"(m), "r"(bar), "r"(c0), "r"(c1), "r"(c2) : "memory");
}
__device__ __forceinline__ void tma2d_store(const CUtensorMap* m, uint32_t src, int c0, int c1) {
  asm volatile("cp.async.bulk.tensor.2d.global.shared::cta.bulk_group [%0, {%2, %3}], [%1];" :: "l"(m), "r"(src), "r"(c0), "r"(c1) : "memory");
}
__device__ __forceinline__ void bulk_load(uint32_t dst, const void* src, uint32_t bytes, uint32_t bar) {
  asm volatile("cp.async.bulk.shared::cluster.global.mbarrier::complete_tx::bytes [%0], [%1], %2, [%3];" :: "r"(dst), "l"(src), "r"(bytes), "r"(bar) : "memory");
}
__device__ __forceinline__ void tma3d_store(const CUtensorMap* m, uint32_t src, int c0, int c1, int c2) {
  asm volatile("cp.async.bulk.tensor.3d.global.shared::cta.bulk_group [%0, {%2, %3, %4}], [%1];" :: "l"(m), "r"(src), "r"(c0), "r"(c1), "r"(c2) : "memory");
}
__device__ __forceinline__ void bulk_commit() { asm volatile("cp.async.bulk.commit_group;" ::: "memory"); }
__device__ __forceinline__ void bulk_wait_all() { asm volatile("cp.async.bulk.wait_group 0;" ::: "memory"); }
__device__ __forceinline__ void bulk_wait_read() { asm volatile("cp.async.bulk.wait_group.read 0;" ::: "memory"); }
__device__ __forceinline__ void fence_async_smem() { asm volatile("fence.proxy.async.shared::cta;" ::: "memory"); }
__device__ __forceinline__ void fence_async_global() { asm volatile("fence.proxy.async.global;" ::: "memory"); }
__device__ __forceinline__ uint32_t ld_cnt(Scratch* S, int c) { uint32_t v; asm volatile("ld.relaxed.gpu.global.u32 %0, [%1];" : "=r"(v) : "l"(S->cnt + c * 32) : "memory"); return v; }
__device__ __forceinline__ void signal(Scratch* S, int c, uint32_t inc) { asm volatile("red.release.gpu.global.add.u32 [%0], %1;" :: "l"(S->cnt + c * 32), "r"(inc) : "memory"); }
__device__ __forceinline__ bool reached(Scratch* S, int c, uint32_t ep) { return ld_cnt(S, c) - ep >= EPOCH; }
__device__ __forceinline__ void await(Scratch* S, int c, uint32_t ep) { while (!reached(S, c, ep)) { } }
__device__ __forceinline__ void bar_sync(int id, int n) { asm volatile("bar.sync %0, %1;" :: "r"(id), "r"(n) : "memory"); }
__device__ __forceinline__ void bar_arrive(int id, int n) { asm volatile("bar.arrive %0, %1;" :: "r"(id), "r"(n) : "memory"); }
__device__ __forceinline__ void wg_fence() { asm volatile("wgmma.fence.sync.aligned;" ::: "memory"); }
__device__ __forceinline__ void wg_commit() { asm volatile("wgmma.commit_group.sync.aligned;" ::: "memory"); }
template <int N> __device__ __forceinline__ void wg_wait() { asm volatile("wgmma.wait_group.sync.aligned %0;" :: "n"(N) : "memory"); }
template <int N> __device__ __forceinline__ void pin_regs(float* a) {
#pragma unroll
  for (int i = 0; i < N; i++) asm volatile("" : "+f"(a[i]) :: "memory");
}
__device__ __forceinline__ uint64_t make_desc(uint32_t addr, uint32_t lbo, uint32_t sbo, uint32_t swz) {
  return (uint64_t)((addr & 0x3FFFF) >> 4) | ((uint64_t)(lbo >> 4) << 16) | ((uint64_t)(sbo >> 4) << 32) | ((uint64_t)swz << 62);
}
__device__ __forceinline__ uint32_t pack_bf16(float lo, float hi) { uint32_t r; asm("cvt.rn.bf16x2.f32 %0, %1, %2;" : "=r"(r) : "f"(hi), "f"(lo)); return r; }
__device__ __forceinline__ float bf_lo(uint32_t p) { return __uint_as_float(p << 16); }
__device__ __forceinline__ float bf_hi(uint32_t p) { return __uint_as_float(p & 0xffff0000u); }
__device__ __forceinline__ float round_bf16(float v) { return bf_lo(pack_bf16(v, 0.f)); }
__device__ __forceinline__ uint32_t bmul2(uint32_t a, uint32_t b) { uint32_t r; asm("mul.rn.bf16x2 %0, %1, %2;" : "=r"(r) : "r"(a), "r"(b)); return r; }
__device__ __forceinline__ uint32_t badd2(uint32_t a, uint32_t b) { uint32_t r; asm("add.rn.bf16x2 %0, %1, %2;" : "=r"(r) : "r"(a), "r"(b)); return r; }
__device__ __forceinline__ uint32_t bfma2(uint32_t a, uint32_t b, uint32_t c) { uint32_t r; asm("fma.rn.bf16x2 %0, %1, %2, %3;" : "=r"(r) : "r"(a), "r"(b), "r"(c)); return r; }
__device__ __forceinline__ uint32_t bsub2(uint32_t a, uint32_t b) { uint32_t r; asm("sub.rn.bf16x2 %0, %1, %2;" : "=r"(r) : "r"(a), "r"(b)); return r; }
__device__ __forceinline__ float tanh_fast(float v) { float r; asm("tanh.approx.f32 %0, %1;" : "=f"(r) : "f"(v)); return r; }
__device__ __forceinline__ float gelu_half(float h) {
  return fmaf(h, tanh_fast(h * fmaf(h * h, 8.0f * 0.7978845608028654f * 0.044715f, 2.0f * 0.7978845608028654f)), h);
}
__device__ __forceinline__ float silu_half(float h) { return fmaf(h, tanh_fast(h), h); }
__device__ __forceinline__ uint32_t ldg32(const void* p) { uint32_t v; asm volatile("ld.global.u32 %0, [%1];" : "=r"(v) : "l"(p) : "memory"); return v; }
__device__ __forceinline__ uint32_t lds32(uint32_t a) { uint32_t v; asm volatile("ld.shared.u32 %0, [%1];" : "=r"(v) : "r"(a) : "memory"); return v; }
__device__ __forceinline__ uint32_t lds16(uint32_t a) { uint32_t v; asm volatile("ld.shared.u16 %0, [%1];" : "=r"(v) : "r"(a) : "memory"); return v; }
__device__ __forceinline__ uint4 lds128(uint32_t a) { uint4 v; asm volatile("ld.shared.v4.u32 {%0,%1,%2,%3}, [%4];" : "=r"(v.x), "=r"(v.y), "=r"(v.z), "=r"(v.w) : "r"(a) : "memory"); return v; }
__device__ __forceinline__ void sts128(uint32_t a, uint32_t x, uint32_t y, uint32_t z, uint32_t w) {
  asm volatile("st.shared.v4.u32 [%0], {%1,%2,%3,%4};" :: "r"(a), "r"(x), "r"(y), "r"(z), "r"(w) : "memory");
}
__device__ __forceinline__ void sts32(uint32_t a, uint32_t v) { asm volatile("st.shared.u32 [%0], %1;" :: "r"(a), "r"(v) : "memory"); }
__device__ __forceinline__ void ldsm4(uint32_t* r, uint32_t a) {
  asm volatile("ldmatrix.sync.aligned.m8n8.x4.shared.b16 {%0,%1,%2,%3}, [%4];" : "=r"(r[0]), "=r"(r[1]), "=r"(r[2]), "=r"(r[3]) : "r"(a) : "memory");
}
__device__ __forceinline__ void ldsm2(uint32_t* r, uint32_t a) {
  asm volatile("ldmatrix.sync.aligned.m8n8.x2.shared.b16 {%0,%1}, [%2];" : "=r"(r[0]), "=r"(r[1]) : "r"(a) : "memory");
}
__device__ __forceinline__ void ldsm4t(uint32_t* r, uint32_t a) {
  asm volatile("ldmatrix.sync.aligned.m8n8.x4.trans.shared.b16 {%0,%1,%2,%3}, [%4];" : "=r"(r[0]), "=r"(r[1]), "=r"(r[2]), "=r"(r[3]) : "r"(a) : "memory");
}
__device__ __forceinline__ void ldsm2t(uint32_t* r, uint32_t a) {
  asm volatile("ldmatrix.sync.aligned.m8n8.x2.trans.shared.b16 {%0,%1}, [%2];" : "=r"(r[0]), "=r"(r[1]) : "r"(a) : "memory");
}
__device__ __forceinline__ void stsm4(uint32_t a, uint32_t r0, uint32_t r1, uint32_t r2, uint32_t r3) {
  asm volatile("stmatrix.sync.aligned.m8n8.x4.shared.b16 [%0], {%1,%2,%3,%4};" :: "r"(a), "r"(r0), "r"(r1), "r"(r2), "r"(r3) : "memory");
}
__device__ __forceinline__ void stsm2(uint32_t a, uint32_t r0, uint32_t r1) {
  asm volatile("stmatrix.sync.aligned.m8n8.x2.shared.b16 [%0], {%1,%2};" :: "r"(a), "r"(r0), "r"(r1) : "memory");
}
__device__ __forceinline__ void stsm4t(uint32_t a, uint32_t r0, uint32_t r1, uint32_t r2, uint32_t r3) {
  asm volatile("stmatrix.sync.aligned.m8n8.x4.trans.shared.b16 [%0], {%1,%2,%3,%4};" :: "r"(a), "r"(r0), "r"(r1), "r"(r2), "r"(r3) : "memory");
}

__device__ __forceinline__ void wgmma_ss_n144_t10(float* d, uint64_t da, uint64_t db, int sd) {
  asm volatile("{ .reg .pred p; setp.ne.b32 p, %74, 0;\n"
      "wgmma.mma_async.sync.aligned.m64n144k16.f32.bf16.bf16 {"
      "%0,%1,%2,%3,%4,%5,%6,%7,%8,%9,%10,%11,%12,%13,%14,%15,"
      "%16,%17,%18,%19,%20,%21,%22,%23,%24,%25,%26,%27,%28,%29,%30,%31,"
      "%32,%33,%34,%35,%36,%37,%38,%39,%40,%41,%42,%43,%44,%45,%46,%47,"
      "%48,%49,%50,%51,%52,%53,%54,%55,%56,%57,%58,%59,%60,%61,%62,%63,"
      "%64,%65,%66,%67,%68,%69,%70,%71"
      "}, %72, %73, p, 1, 1, 1, 0; }"
    : "+f"(d[0]), "+f"(d[1]), "+f"(d[2]), "+f"(d[3]), "+f"(d[4]), "+f"(d[5]), "+f"(d[6]), "+f"(d[7]),
      "+f"(d[8]), "+f"(d[9]), "+f"(d[10]), "+f"(d[11]), "+f"(d[12]), "+f"(d[13]), "+f"(d[14]), "+f"(d[15]),
      "+f"(d[16]), "+f"(d[17]), "+f"(d[18]), "+f"(d[19]), "+f"(d[20]), "+f"(d[21]), "+f"(d[22]), "+f"(d[23]),
      "+f"(d[24]), "+f"(d[25]), "+f"(d[26]), "+f"(d[27]), "+f"(d[28]), "+f"(d[29]), "+f"(d[30]), "+f"(d[31]),
      "+f"(d[32]), "+f"(d[33]), "+f"(d[34]), "+f"(d[35]), "+f"(d[36]), "+f"(d[37]), "+f"(d[38]), "+f"(d[39]),
      "+f"(d[40]), "+f"(d[41]), "+f"(d[42]), "+f"(d[43]), "+f"(d[44]), "+f"(d[45]), "+f"(d[46]), "+f"(d[47]),
      "+f"(d[48]), "+f"(d[49]), "+f"(d[50]), "+f"(d[51]), "+f"(d[52]), "+f"(d[53]), "+f"(d[54]), "+f"(d[55]),
      "+f"(d[56]), "+f"(d[57]), "+f"(d[58]), "+f"(d[59]), "+f"(d[60]), "+f"(d[61]), "+f"(d[62]), "+f"(d[63]),
      "+f"(d[64]), "+f"(d[65]), "+f"(d[66]), "+f"(d[67]), "+f"(d[68]), "+f"(d[69]), "+f"(d[70]), "+f"(d[71])
    : "l"(da), "l"(db), "r"(sd));
}

__device__ __forceinline__ void wgmma_ss_n160_t11(float* d, uint64_t da, uint64_t db, int sd) {
  asm volatile("{ .reg .pred p; setp.ne.b32 p, %82, 0;\n"
      "wgmma.mma_async.sync.aligned.m64n160k16.f32.bf16.bf16 {"
      "%0,%1,%2,%3,%4,%5,%6,%7,%8,%9,%10,%11,%12,%13,%14,%15,"
      "%16,%17,%18,%19,%20,%21,%22,%23,%24,%25,%26,%27,%28,%29,%30,%31,"
      "%32,%33,%34,%35,%36,%37,%38,%39,%40,%41,%42,%43,%44,%45,%46,%47,"
      "%48,%49,%50,%51,%52,%53,%54,%55,%56,%57,%58,%59,%60,%61,%62,%63,"
      "%64,%65,%66,%67,%68,%69,%70,%71,%72,%73,%74,%75,%76,%77,%78,%79"
      "}, %80, %81, p, 1, 1, 1, 1; }"
    : "+f"(d[0]), "+f"(d[1]), "+f"(d[2]), "+f"(d[3]), "+f"(d[4]), "+f"(d[5]), "+f"(d[6]), "+f"(d[7]),
      "+f"(d[8]), "+f"(d[9]), "+f"(d[10]), "+f"(d[11]), "+f"(d[12]), "+f"(d[13]), "+f"(d[14]), "+f"(d[15]),
      "+f"(d[16]), "+f"(d[17]), "+f"(d[18]), "+f"(d[19]), "+f"(d[20]), "+f"(d[21]), "+f"(d[22]), "+f"(d[23]),
      "+f"(d[24]), "+f"(d[25]), "+f"(d[26]), "+f"(d[27]), "+f"(d[28]), "+f"(d[29]), "+f"(d[30]), "+f"(d[31]),
      "+f"(d[32]), "+f"(d[33]), "+f"(d[34]), "+f"(d[35]), "+f"(d[36]), "+f"(d[37]), "+f"(d[38]), "+f"(d[39]),
      "+f"(d[40]), "+f"(d[41]), "+f"(d[42]), "+f"(d[43]), "+f"(d[44]), "+f"(d[45]), "+f"(d[46]), "+f"(d[47]),
      "+f"(d[48]), "+f"(d[49]), "+f"(d[50]), "+f"(d[51]), "+f"(d[52]), "+f"(d[53]), "+f"(d[54]), "+f"(d[55]),
      "+f"(d[56]), "+f"(d[57]), "+f"(d[58]), "+f"(d[59]), "+f"(d[60]), "+f"(d[61]), "+f"(d[62]), "+f"(d[63]),
      "+f"(d[64]), "+f"(d[65]), "+f"(d[66]), "+f"(d[67]), "+f"(d[68]), "+f"(d[69]), "+f"(d[70]), "+f"(d[71]),
      "+f"(d[72]), "+f"(d[73]), "+f"(d[74]), "+f"(d[75]), "+f"(d[76]), "+f"(d[77]), "+f"(d[78]), "+f"(d[79])
    : "l"(da), "l"(db), "r"(sd));
}

__device__ __forceinline__ void wgmma_ss_n96_t11(float* d, uint64_t da, uint64_t db, int sd) {
  asm volatile("{ .reg .pred p; setp.ne.b32 p, %50, 0;\n"
      "wgmma.mma_async.sync.aligned.m64n96k16.f32.bf16.bf16 {"
      "%0,%1,%2,%3,%4,%5,%6,%7,%8,%9,%10,%11,%12,%13,%14,%15,"
      "%16,%17,%18,%19,%20,%21,%22,%23,%24,%25,%26,%27,%28,%29,%30,%31,"
      "%32,%33,%34,%35,%36,%37,%38,%39,%40,%41,%42,%43,%44,%45,%46,%47"
      "}, %48, %49, p, 1, 1, 1, 1; }"
    : "+f"(d[0]), "+f"(d[1]), "+f"(d[2]), "+f"(d[3]), "+f"(d[4]), "+f"(d[5]), "+f"(d[6]), "+f"(d[7]),
      "+f"(d[8]), "+f"(d[9]), "+f"(d[10]), "+f"(d[11]), "+f"(d[12]), "+f"(d[13]), "+f"(d[14]), "+f"(d[15]),
      "+f"(d[16]), "+f"(d[17]), "+f"(d[18]), "+f"(d[19]), "+f"(d[20]), "+f"(d[21]), "+f"(d[22]), "+f"(d[23]),
      "+f"(d[24]), "+f"(d[25]), "+f"(d[26]), "+f"(d[27]), "+f"(d[28]), "+f"(d[29]), "+f"(d[30]), "+f"(d[31]),
      "+f"(d[32]), "+f"(d[33]), "+f"(d[34]), "+f"(d[35]), "+f"(d[36]), "+f"(d[37]), "+f"(d[38]), "+f"(d[39]),
      "+f"(d[40]), "+f"(d[41]), "+f"(d[42]), "+f"(d[43]), "+f"(d[44]), "+f"(d[45]), "+f"(d[46]), "+f"(d[47])
    : "l"(da), "l"(db), "r"(sd));
}

__device__ __forceinline__ void wgmma_rs_n16(float* d, const uint32_t* a, uint64_t db, int sd) {
  asm volatile("{ .reg .pred p; setp.ne.b32 p, %13, 0;\n"
      "wgmma.mma_async.sync.aligned.m64n16k16.f32.bf16.bf16 {"
      "%0,%1,%2,%3,%4,%5,%6,%7"
      "}, {%8,%9,%10,%11}, %12, p, 1, 1, 0; }"
    : "+f"(d[0]), "+f"(d[1]), "+f"(d[2]), "+f"(d[3]), "+f"(d[4]), "+f"(d[5]), "+f"(d[6]), "+f"(d[7])
    : "r"(a[0]), "r"(a[1]), "r"(a[2]), "r"(a[3]), "l"(db), "r"(sd));
}

__device__ __forceinline__ void wgmma_rs_n32(float* d, const uint32_t* a, uint64_t db, int sd) {
  asm volatile("{ .reg .pred p; setp.ne.b32 p, %21, 0;\n"
      "wgmma.mma_async.sync.aligned.m64n32k16.f32.bf16.bf16 {"
      "%0,%1,%2,%3,%4,%5,%6,%7,%8,%9,%10,%11,%12,%13,%14,%15"
      "}, {%16,%17,%18,%19}, %20, p, 1, 1, 0; }"
    : "+f"(d[0]), "+f"(d[1]), "+f"(d[2]), "+f"(d[3]), "+f"(d[4]), "+f"(d[5]), "+f"(d[6]), "+f"(d[7]),
      "+f"(d[8]), "+f"(d[9]), "+f"(d[10]), "+f"(d[11]), "+f"(d[12]), "+f"(d[13]), "+f"(d[14]), "+f"(d[15])
    : "r"(a[0]), "r"(a[1]), "r"(a[2]), "r"(a[3]), "l"(db), "r"(sd));
}

__device__ __forceinline__ void wgmma_rs_n48(float* d, const uint32_t* a, uint64_t db, int sd) {
  asm volatile("{ .reg .pred p; setp.ne.b32 p, %29, 0;\n"
      "wgmma.mma_async.sync.aligned.m64n48k16.f32.bf16.bf16 {"
      "%0,%1,%2,%3,%4,%5,%6,%7,%8,%9,%10,%11,%12,%13,%14,%15,"
      "%16,%17,%18,%19,%20,%21,%22,%23"
      "}, {%24,%25,%26,%27}, %28, p, 1, 1, 0; }"
    : "+f"(d[0]), "+f"(d[1]), "+f"(d[2]), "+f"(d[3]), "+f"(d[4]), "+f"(d[5]), "+f"(d[6]), "+f"(d[7]),
      "+f"(d[8]), "+f"(d[9]), "+f"(d[10]), "+f"(d[11]), "+f"(d[12]), "+f"(d[13]), "+f"(d[14]), "+f"(d[15]),
      "+f"(d[16]), "+f"(d[17]), "+f"(d[18]), "+f"(d[19]), "+f"(d[20]), "+f"(d[21]), "+f"(d[22]), "+f"(d[23])
    : "r"(a[0]), "r"(a[1]), "r"(a[2]), "r"(a[3]), "l"(db), "r"(sd));
}

__device__ __forceinline__ void wgmma_rs_n64(float* d, const uint32_t* a, uint64_t db, int sd) {
  asm volatile("{ .reg .pred p; setp.ne.b32 p, %37, 0;\n"
      "wgmma.mma_async.sync.aligned.m64n64k16.f32.bf16.bf16 {"
      "%0,%1,%2,%3,%4,%5,%6,%7,%8,%9,%10,%11,%12,%13,%14,%15,"
      "%16,%17,%18,%19,%20,%21,%22,%23,%24,%25,%26,%27,%28,%29,%30,%31"
      "}, {%32,%33,%34,%35}, %36, p, 1, 1, 0; }"
    : "+f"(d[0]), "+f"(d[1]), "+f"(d[2]), "+f"(d[3]), "+f"(d[4]), "+f"(d[5]), "+f"(d[6]), "+f"(d[7]),
      "+f"(d[8]), "+f"(d[9]), "+f"(d[10]), "+f"(d[11]), "+f"(d[12]), "+f"(d[13]), "+f"(d[14]), "+f"(d[15]),
      "+f"(d[16]), "+f"(d[17]), "+f"(d[18]), "+f"(d[19]), "+f"(d[20]), "+f"(d[21]), "+f"(d[22]), "+f"(d[23]),
      "+f"(d[24]), "+f"(d[25]), "+f"(d[26]), "+f"(d[27]), "+f"(d[28]), "+f"(d[29]), "+f"(d[30]), "+f"(d[31])
    : "r"(a[0]), "r"(a[1]), "r"(a[2]), "r"(a[3]), "l"(db), "r"(sd));
}

__device__ __forceinline__ void wgmma_rs_n80(float* d, const uint32_t* a, uint64_t db, int sd) {
  asm volatile("{ .reg .pred p; setp.ne.b32 p, %45, 0;\n"
      "wgmma.mma_async.sync.aligned.m64n80k16.f32.bf16.bf16 {"
      "%0,%1,%2,%3,%4,%5,%6,%7,%8,%9,%10,%11,%12,%13,%14,%15,"
      "%16,%17,%18,%19,%20,%21,%22,%23,%24,%25,%26,%27,%28,%29,%30,%31,"
      "%32,%33,%34,%35,%36,%37,%38,%39"
      "}, {%40,%41,%42,%43}, %44, p, 1, 1, 0; }"
    : "+f"(d[0]), "+f"(d[1]), "+f"(d[2]), "+f"(d[3]), "+f"(d[4]), "+f"(d[5]), "+f"(d[6]), "+f"(d[7]),
      "+f"(d[8]), "+f"(d[9]), "+f"(d[10]), "+f"(d[11]), "+f"(d[12]), "+f"(d[13]), "+f"(d[14]), "+f"(d[15]),
      "+f"(d[16]), "+f"(d[17]), "+f"(d[18]), "+f"(d[19]), "+f"(d[20]), "+f"(d[21]), "+f"(d[22]), "+f"(d[23]),
      "+f"(d[24]), "+f"(d[25]), "+f"(d[26]), "+f"(d[27]), "+f"(d[28]), "+f"(d[29]), "+f"(d[30]), "+f"(d[31]),
      "+f"(d[32]), "+f"(d[33]), "+f"(d[34]), "+f"(d[35]), "+f"(d[36]), "+f"(d[37]), "+f"(d[38]), "+f"(d[39])
    : "r"(a[0]), "r"(a[1]), "r"(a[2]), "r"(a[3]), "l"(db), "r"(sd));
}

__device__ __forceinline__ void wgmma_rs_n96(float* d, const uint32_t* a, uint64_t db, int sd) {
  asm volatile("{ .reg .pred p; setp.ne.b32 p, %53, 0;\n"
      "wgmma.mma_async.sync.aligned.m64n96k16.f32.bf16.bf16 {"
      "%0,%1,%2,%3,%4,%5,%6,%7,%8,%9,%10,%11,%12,%13,%14,%15,"
      "%16,%17,%18,%19,%20,%21,%22,%23,%24,%25,%26,%27,%28,%29,%30,%31,"
      "%32,%33,%34,%35,%36,%37,%38,%39,%40,%41,%42,%43,%44,%45,%46,%47"
      "}, {%48,%49,%50,%51}, %52, p, 1, 1, 0; }"
    : "+f"(d[0]), "+f"(d[1]), "+f"(d[2]), "+f"(d[3]), "+f"(d[4]), "+f"(d[5]), "+f"(d[6]), "+f"(d[7]),
      "+f"(d[8]), "+f"(d[9]), "+f"(d[10]), "+f"(d[11]), "+f"(d[12]), "+f"(d[13]), "+f"(d[14]), "+f"(d[15]),
      "+f"(d[16]), "+f"(d[17]), "+f"(d[18]), "+f"(d[19]), "+f"(d[20]), "+f"(d[21]), "+f"(d[22]), "+f"(d[23]),
      "+f"(d[24]), "+f"(d[25]), "+f"(d[26]), "+f"(d[27]), "+f"(d[28]), "+f"(d[29]), "+f"(d[30]), "+f"(d[31]),
      "+f"(d[32]), "+f"(d[33]), "+f"(d[34]), "+f"(d[35]), "+f"(d[36]), "+f"(d[37]), "+f"(d[38]), "+f"(d[39]),
      "+f"(d[40]), "+f"(d[41]), "+f"(d[42]), "+f"(d[43]), "+f"(d[44]), "+f"(d[45]), "+f"(d[46]), "+f"(d[47])
    : "r"(a[0]), "r"(a[1]), "r"(a[2]), "r"(a[3]), "l"(db), "r"(sd));
}

__device__ __forceinline__ void wgmma_rs_n112(float* d, const uint32_t* a, uint64_t db, int sd) {
  asm volatile("{ .reg .pred p; setp.ne.b32 p, %61, 0;\n"
      "wgmma.mma_async.sync.aligned.m64n112k16.f32.bf16.bf16 {"
      "%0,%1,%2,%3,%4,%5,%6,%7,%8,%9,%10,%11,%12,%13,%14,%15,"
      "%16,%17,%18,%19,%20,%21,%22,%23,%24,%25,%26,%27,%28,%29,%30,%31,"
      "%32,%33,%34,%35,%36,%37,%38,%39,%40,%41,%42,%43,%44,%45,%46,%47,"
      "%48,%49,%50,%51,%52,%53,%54,%55"
      "}, {%56,%57,%58,%59}, %60, p, 1, 1, 0; }"
    : "+f"(d[0]), "+f"(d[1]), "+f"(d[2]), "+f"(d[3]), "+f"(d[4]), "+f"(d[5]), "+f"(d[6]), "+f"(d[7]),
      "+f"(d[8]), "+f"(d[9]), "+f"(d[10]), "+f"(d[11]), "+f"(d[12]), "+f"(d[13]), "+f"(d[14]), "+f"(d[15]),
      "+f"(d[16]), "+f"(d[17]), "+f"(d[18]), "+f"(d[19]), "+f"(d[20]), "+f"(d[21]), "+f"(d[22]), "+f"(d[23]),
      "+f"(d[24]), "+f"(d[25]), "+f"(d[26]), "+f"(d[27]), "+f"(d[28]), "+f"(d[29]), "+f"(d[30]), "+f"(d[31]),
      "+f"(d[32]), "+f"(d[33]), "+f"(d[34]), "+f"(d[35]), "+f"(d[36]), "+f"(d[37]), "+f"(d[38]), "+f"(d[39]),
      "+f"(d[40]), "+f"(d[41]), "+f"(d[42]), "+f"(d[43]), "+f"(d[44]), "+f"(d[45]), "+f"(d[46]), "+f"(d[47]),
      "+f"(d[48]), "+f"(d[49]), "+f"(d[50]), "+f"(d[51]), "+f"(d[52]), "+f"(d[53]), "+f"(d[54]), "+f"(d[55])
    : "r"(a[0]), "r"(a[1]), "r"(a[2]), "r"(a[3]), "l"(db), "r"(sd));
}

__device__ __forceinline__ void wgmma_rs_n128(float* d, const uint32_t* a, uint64_t db, int sd) {
  asm volatile("{ .reg .pred p; setp.ne.b32 p, %69, 0;\n"
      "wgmma.mma_async.sync.aligned.m64n128k16.f32.bf16.bf16 {"
      "%0,%1,%2,%3,%4,%5,%6,%7,%8,%9,%10,%11,%12,%13,%14,%15,"
      "%16,%17,%18,%19,%20,%21,%22,%23,%24,%25,%26,%27,%28,%29,%30,%31,"
      "%32,%33,%34,%35,%36,%37,%38,%39,%40,%41,%42,%43,%44,%45,%46,%47,"
      "%48,%49,%50,%51,%52,%53,%54,%55,%56,%57,%58,%59,%60,%61,%62,%63"
      "}, {%64,%65,%66,%67}, %68, p, 1, 1, 0; }"
    : "+f"(d[0]), "+f"(d[1]), "+f"(d[2]), "+f"(d[3]), "+f"(d[4]), "+f"(d[5]), "+f"(d[6]), "+f"(d[7]),
      "+f"(d[8]), "+f"(d[9]), "+f"(d[10]), "+f"(d[11]), "+f"(d[12]), "+f"(d[13]), "+f"(d[14]), "+f"(d[15]),
      "+f"(d[16]), "+f"(d[17]), "+f"(d[18]), "+f"(d[19]), "+f"(d[20]), "+f"(d[21]), "+f"(d[22]), "+f"(d[23]),
      "+f"(d[24]), "+f"(d[25]), "+f"(d[26]), "+f"(d[27]), "+f"(d[28]), "+f"(d[29]), "+f"(d[30]), "+f"(d[31]),
      "+f"(d[32]), "+f"(d[33]), "+f"(d[34]), "+f"(d[35]), "+f"(d[36]), "+f"(d[37]), "+f"(d[38]), "+f"(d[39]),
      "+f"(d[40]), "+f"(d[41]), "+f"(d[42]), "+f"(d[43]), "+f"(d[44]), "+f"(d[45]), "+f"(d[46]), "+f"(d[47]),
      "+f"(d[48]), "+f"(d[49]), "+f"(d[50]), "+f"(d[51]), "+f"(d[52]), "+f"(d[53]), "+f"(d[54]), "+f"(d[55]),
      "+f"(d[56]), "+f"(d[57]), "+f"(d[58]), "+f"(d[59]), "+f"(d[60]), "+f"(d[61]), "+f"(d[62]), "+f"(d[63])
    : "r"(a[0]), "r"(a[1]), "r"(a[2]), "r"(a[3]), "l"(db), "r"(sd));
}

__device__ __forceinline__ void wgmma_rs_n144(float* d, const uint32_t* a, uint64_t db, int sd) {
  asm volatile("{ .reg .pred p; setp.ne.b32 p, %77, 0;\n"
      "wgmma.mma_async.sync.aligned.m64n144k16.f32.bf16.bf16 {"
      "%0,%1,%2,%3,%4,%5,%6,%7,%8,%9,%10,%11,%12,%13,%14,%15,"
      "%16,%17,%18,%19,%20,%21,%22,%23,%24,%25,%26,%27,%28,%29,%30,%31,"
      "%32,%33,%34,%35,%36,%37,%38,%39,%40,%41,%42,%43,%44,%45,%46,%47,"
      "%48,%49,%50,%51,%52,%53,%54,%55,%56,%57,%58,%59,%60,%61,%62,%63,"
      "%64,%65,%66,%67,%68,%69,%70,%71"
      "}, {%72,%73,%74,%75}, %76, p, 1, 1, 0; }"
    : "+f"(d[0]), "+f"(d[1]), "+f"(d[2]), "+f"(d[3]), "+f"(d[4]), "+f"(d[5]), "+f"(d[6]), "+f"(d[7]),
      "+f"(d[8]), "+f"(d[9]), "+f"(d[10]), "+f"(d[11]), "+f"(d[12]), "+f"(d[13]), "+f"(d[14]), "+f"(d[15]),
      "+f"(d[16]), "+f"(d[17]), "+f"(d[18]), "+f"(d[19]), "+f"(d[20]), "+f"(d[21]), "+f"(d[22]), "+f"(d[23]),
      "+f"(d[24]), "+f"(d[25]), "+f"(d[26]), "+f"(d[27]), "+f"(d[28]), "+f"(d[29]), "+f"(d[30]), "+f"(d[31]),
      "+f"(d[32]), "+f"(d[33]), "+f"(d[34]), "+f"(d[35]), "+f"(d[36]), "+f"(d[37]), "+f"(d[38]), "+f"(d[39]),
      "+f"(d[40]), "+f"(d[41]), "+f"(d[42]), "+f"(d[43]), "+f"(d[44]), "+f"(d[45]), "+f"(d[46]), "+f"(d[47]),
      "+f"(d[48]), "+f"(d[49]), "+f"(d[50]), "+f"(d[51]), "+f"(d[52]), "+f"(d[53]), "+f"(d[54]), "+f"(d[55]),
      "+f"(d[56]), "+f"(d[57]), "+f"(d[58]), "+f"(d[59]), "+f"(d[60]), "+f"(d[61]), "+f"(d[62]), "+f"(d[63]),
      "+f"(d[64]), "+f"(d[65]), "+f"(d[66]), "+f"(d[67]), "+f"(d[68]), "+f"(d[69]), "+f"(d[70]), "+f"(d[71])
    : "r"(a[0]), "r"(a[1]), "r"(a[2]), "r"(a[3]), "l"(db), "r"(sd));
}

__device__ __forceinline__ void wgmma_rs_n160(float* d, const uint32_t* a, uint64_t db, int sd) {
  asm volatile("{ .reg .pred p; setp.ne.b32 p, %85, 0;\n"
      "wgmma.mma_async.sync.aligned.m64n160k16.f32.bf16.bf16 {"
      "%0,%1,%2,%3,%4,%5,%6,%7,%8,%9,%10,%11,%12,%13,%14,%15,"
      "%16,%17,%18,%19,%20,%21,%22,%23,%24,%25,%26,%27,%28,%29,%30,%31,"
      "%32,%33,%34,%35,%36,%37,%38,%39,%40,%41,%42,%43,%44,%45,%46,%47,"
      "%48,%49,%50,%51,%52,%53,%54,%55,%56,%57,%58,%59,%60,%61,%62,%63,"
      "%64,%65,%66,%67,%68,%69,%70,%71,%72,%73,%74,%75,%76,%77,%78,%79"
      "}, {%80,%81,%82,%83}, %84, p, 1, 1, 0; }"
    : "+f"(d[0]), "+f"(d[1]), "+f"(d[2]), "+f"(d[3]), "+f"(d[4]), "+f"(d[5]), "+f"(d[6]), "+f"(d[7]),
      "+f"(d[8]), "+f"(d[9]), "+f"(d[10]), "+f"(d[11]), "+f"(d[12]), "+f"(d[13]), "+f"(d[14]), "+f"(d[15]),
      "+f"(d[16]), "+f"(d[17]), "+f"(d[18]), "+f"(d[19]), "+f"(d[20]), "+f"(d[21]), "+f"(d[22]), "+f"(d[23]),
      "+f"(d[24]), "+f"(d[25]), "+f"(d[26]), "+f"(d[27]), "+f"(d[28]), "+f"(d[29]), "+f"(d[30]), "+f"(d[31]),
      "+f"(d[32]), "+f"(d[33]), "+f"(d[34]), "+f"(d[35]), "+f"(d[36]), "+f"(d[37]), "+f"(d[38]), "+f"(d[39]),
      "+f"(d[40]), "+f"(d[41]), "+f"(d[42]), "+f"(d[43]), "+f"(d[44]), "+f"(d[45]), "+f"(d[46]), "+f"(d[47]),
      "+f"(d[48]), "+f"(d[49]), "+f"(d[50]), "+f"(d[51]), "+f"(d[52]), "+f"(d[53]), "+f"(d[54]), "+f"(d[55]),
      "+f"(d[56]), "+f"(d[57]), "+f"(d[58]), "+f"(d[59]), "+f"(d[60]), "+f"(d[61]), "+f"(d[62]), "+f"(d[63]),
      "+f"(d[64]), "+f"(d[65]), "+f"(d[66]), "+f"(d[67]), "+f"(d[68]), "+f"(d[69]), "+f"(d[70]), "+f"(d[71]),
      "+f"(d[72]), "+f"(d[73]), "+f"(d[74]), "+f"(d[75]), "+f"(d[76]), "+f"(d[77]), "+f"(d[78]), "+f"(d[79])
    : "r"(a[0]), "r"(a[1]), "r"(a[2]), "r"(a[3]), "l"(db), "r"(sd));
}

__device__ __forceinline__ void wgmma_rs_n176(float* d, const uint32_t* a, uint64_t db, int sd) {
  asm volatile("{ .reg .pred p; setp.ne.b32 p, %93, 0;\n"
      "wgmma.mma_async.sync.aligned.m64n176k16.f32.bf16.bf16 {"
      "%0,%1,%2,%3,%4,%5,%6,%7,%8,%9,%10,%11,%12,%13,%14,%15,"
      "%16,%17,%18,%19,%20,%21,%22,%23,%24,%25,%26,%27,%28,%29,%30,%31,"
      "%32,%33,%34,%35,%36,%37,%38,%39,%40,%41,%42,%43,%44,%45,%46,%47,"
      "%48,%49,%50,%51,%52,%53,%54,%55,%56,%57,%58,%59,%60,%61,%62,%63,"
      "%64,%65,%66,%67,%68,%69,%70,%71,%72,%73,%74,%75,%76,%77,%78,%79,"
      "%80,%81,%82,%83,%84,%85,%86,%87"
      "}, {%88,%89,%90,%91}, %92, p, 1, 1, 0; }"
    : "+f"(d[0]), "+f"(d[1]), "+f"(d[2]), "+f"(d[3]), "+f"(d[4]), "+f"(d[5]), "+f"(d[6]), "+f"(d[7]),
      "+f"(d[8]), "+f"(d[9]), "+f"(d[10]), "+f"(d[11]), "+f"(d[12]), "+f"(d[13]), "+f"(d[14]), "+f"(d[15]),
      "+f"(d[16]), "+f"(d[17]), "+f"(d[18]), "+f"(d[19]), "+f"(d[20]), "+f"(d[21]), "+f"(d[22]), "+f"(d[23]),
      "+f"(d[24]), "+f"(d[25]), "+f"(d[26]), "+f"(d[27]), "+f"(d[28]), "+f"(d[29]), "+f"(d[30]), "+f"(d[31]),
      "+f"(d[32]), "+f"(d[33]), "+f"(d[34]), "+f"(d[35]), "+f"(d[36]), "+f"(d[37]), "+f"(d[38]), "+f"(d[39]),
      "+f"(d[40]), "+f"(d[41]), "+f"(d[42]), "+f"(d[43]), "+f"(d[44]), "+f"(d[45]), "+f"(d[46]), "+f"(d[47]),
      "+f"(d[48]), "+f"(d[49]), "+f"(d[50]), "+f"(d[51]), "+f"(d[52]), "+f"(d[53]), "+f"(d[54]), "+f"(d[55]),
      "+f"(d[56]), "+f"(d[57]), "+f"(d[58]), "+f"(d[59]), "+f"(d[60]), "+f"(d[61]), "+f"(d[62]), "+f"(d[63]),
      "+f"(d[64]), "+f"(d[65]), "+f"(d[66]), "+f"(d[67]), "+f"(d[68]), "+f"(d[69]), "+f"(d[70]), "+f"(d[71]),
      "+f"(d[72]), "+f"(d[73]), "+f"(d[74]), "+f"(d[75]), "+f"(d[76]), "+f"(d[77]), "+f"(d[78]), "+f"(d[79]),
      "+f"(d[80]), "+f"(d[81]), "+f"(d[82]), "+f"(d[83]), "+f"(d[84]), "+f"(d[85]), "+f"(d[86]), "+f"(d[87])
    : "r"(a[0]), "r"(a[1]), "r"(a[2]), "r"(a[3]), "l"(db), "r"(sd));
}

__device__ __forceinline__ void wgmma_rs_n192(float* d, const uint32_t* a, uint64_t db, int sd) {
  asm volatile("{ .reg .pred p; setp.ne.b32 p, %101, 0;\n"
      "wgmma.mma_async.sync.aligned.m64n192k16.f32.bf16.bf16 {"
      "%0,%1,%2,%3,%4,%5,%6,%7,%8,%9,%10,%11,%12,%13,%14,%15,"
      "%16,%17,%18,%19,%20,%21,%22,%23,%24,%25,%26,%27,%28,%29,%30,%31,"
      "%32,%33,%34,%35,%36,%37,%38,%39,%40,%41,%42,%43,%44,%45,%46,%47,"
      "%48,%49,%50,%51,%52,%53,%54,%55,%56,%57,%58,%59,%60,%61,%62,%63,"
      "%64,%65,%66,%67,%68,%69,%70,%71,%72,%73,%74,%75,%76,%77,%78,%79,"
      "%80,%81,%82,%83,%84,%85,%86,%87,%88,%89,%90,%91,%92,%93,%94,%95"
      "}, {%96,%97,%98,%99}, %100, p, 1, 1, 0; }"
    : "+f"(d[0]), "+f"(d[1]), "+f"(d[2]), "+f"(d[3]), "+f"(d[4]), "+f"(d[5]), "+f"(d[6]), "+f"(d[7]),
      "+f"(d[8]), "+f"(d[9]), "+f"(d[10]), "+f"(d[11]), "+f"(d[12]), "+f"(d[13]), "+f"(d[14]), "+f"(d[15]),
      "+f"(d[16]), "+f"(d[17]), "+f"(d[18]), "+f"(d[19]), "+f"(d[20]), "+f"(d[21]), "+f"(d[22]), "+f"(d[23]),
      "+f"(d[24]), "+f"(d[25]), "+f"(d[26]), "+f"(d[27]), "+f"(d[28]), "+f"(d[29]), "+f"(d[30]), "+f"(d[31]),
      "+f"(d[32]), "+f"(d[33]), "+f"(d[34]), "+f"(d[35]), "+f"(d[36]), "+f"(d[37]), "+f"(d[38]), "+f"(d[39]),
      "+f"(d[40]), "+f"(d[41]), "+f"(d[42]), "+f"(d[43]), "+f"(d[44]), "+f"(d[45]), "+f"(d[46]), "+f"(d[47]),
      "+f"(d[48]), "+f"(d[49]), "+f"(d[50]), "+f"(d[51]), "+f"(d[52]), "+f"(d[53]), "+f"(d[54]), "+f"(d[55]),
      "+f"(d[56]), "+f"(d[57]), "+f"(d[58]), "+f"(d[59]), "+f"(d[60]), "+f"(d[61]), "+f"(d[62]), "+f"(d[63]),
      "+f"(d[64]), "+f"(d[65]), "+f"(d[66]), "+f"(d[67]), "+f"(d[68]), "+f"(d[69]), "+f"(d[70]), "+f"(d[71]),
      "+f"(d[72]), "+f"(d[73]), "+f"(d[74]), "+f"(d[75]), "+f"(d[76]), "+f"(d[77]), "+f"(d[78]), "+f"(d[79]),
      "+f"(d[80]), "+f"(d[81]), "+f"(d[82]), "+f"(d[83]), "+f"(d[84]), "+f"(d[85]), "+f"(d[86]), "+f"(d[87]),
      "+f"(d[88]), "+f"(d[89]), "+f"(d[90]), "+f"(d[91]), "+f"(d[92]), "+f"(d[93]), "+f"(d[94]), "+f"(d[95])
    : "r"(a[0]), "r"(a[1]), "r"(a[2]), "r"(a[3]), "l"(db), "r"(sd));
}

__device__ __forceinline__ void wgmma_rs_n208(float* d, const uint32_t* a, uint64_t db, int sd) {
  asm volatile("{ .reg .pred p; setp.ne.b32 p, %109, 0;\n"
      "wgmma.mma_async.sync.aligned.m64n208k16.f32.bf16.bf16 {"
      "%0,%1,%2,%3,%4,%5,%6,%7,%8,%9,%10,%11,%12,%13,%14,%15,"
      "%16,%17,%18,%19,%20,%21,%22,%23,%24,%25,%26,%27,%28,%29,%30,%31,"
      "%32,%33,%34,%35,%36,%37,%38,%39,%40,%41,%42,%43,%44,%45,%46,%47,"
      "%48,%49,%50,%51,%52,%53,%54,%55,%56,%57,%58,%59,%60,%61,%62,%63,"
      "%64,%65,%66,%67,%68,%69,%70,%71,%72,%73,%74,%75,%76,%77,%78,%79,"
      "%80,%81,%82,%83,%84,%85,%86,%87,%88,%89,%90,%91,%92,%93,%94,%95,"
      "%96,%97,%98,%99,%100,%101,%102,%103"
      "}, {%104,%105,%106,%107}, %108, p, 1, 1, 0; }"
    : "+f"(d[0]), "+f"(d[1]), "+f"(d[2]), "+f"(d[3]), "+f"(d[4]), "+f"(d[5]), "+f"(d[6]), "+f"(d[7]),
      "+f"(d[8]), "+f"(d[9]), "+f"(d[10]), "+f"(d[11]), "+f"(d[12]), "+f"(d[13]), "+f"(d[14]), "+f"(d[15]),
      "+f"(d[16]), "+f"(d[17]), "+f"(d[18]), "+f"(d[19]), "+f"(d[20]), "+f"(d[21]), "+f"(d[22]), "+f"(d[23]),
      "+f"(d[24]), "+f"(d[25]), "+f"(d[26]), "+f"(d[27]), "+f"(d[28]), "+f"(d[29]), "+f"(d[30]), "+f"(d[31]),
      "+f"(d[32]), "+f"(d[33]), "+f"(d[34]), "+f"(d[35]), "+f"(d[36]), "+f"(d[37]), "+f"(d[38]), "+f"(d[39]),
      "+f"(d[40]), "+f"(d[41]), "+f"(d[42]), "+f"(d[43]), "+f"(d[44]), "+f"(d[45]), "+f"(d[46]), "+f"(d[47]),
      "+f"(d[48]), "+f"(d[49]), "+f"(d[50]), "+f"(d[51]), "+f"(d[52]), "+f"(d[53]), "+f"(d[54]), "+f"(d[55]),
      "+f"(d[56]), "+f"(d[57]), "+f"(d[58]), "+f"(d[59]), "+f"(d[60]), "+f"(d[61]), "+f"(d[62]), "+f"(d[63]),
      "+f"(d[64]), "+f"(d[65]), "+f"(d[66]), "+f"(d[67]), "+f"(d[68]), "+f"(d[69]), "+f"(d[70]), "+f"(d[71]),
      "+f"(d[72]), "+f"(d[73]), "+f"(d[74]), "+f"(d[75]), "+f"(d[76]), "+f"(d[77]), "+f"(d[78]), "+f"(d[79]),
      "+f"(d[80]), "+f"(d[81]), "+f"(d[82]), "+f"(d[83]), "+f"(d[84]), "+f"(d[85]), "+f"(d[86]), "+f"(d[87]),
      "+f"(d[88]), "+f"(d[89]), "+f"(d[90]), "+f"(d[91]), "+f"(d[92]), "+f"(d[93]), "+f"(d[94]), "+f"(d[95]),
      "+f"(d[96]), "+f"(d[97]), "+f"(d[98]), "+f"(d[99]), "+f"(d[100]), "+f"(d[101]), "+f"(d[102]), "+f"(d[103])
    : "r"(a[0]), "r"(a[1]), "r"(a[2]), "r"(a[3]), "l"(db), "r"(sd));
}

__device__ __forceinline__ void wgmma_rs_n224(float* d, const uint32_t* a, uint64_t db, int sd) {
  asm volatile("{ .reg .pred p; setp.ne.b32 p, %117, 0;\n"
      "wgmma.mma_async.sync.aligned.m64n224k16.f32.bf16.bf16 {"
      "%0,%1,%2,%3,%4,%5,%6,%7,%8,%9,%10,%11,%12,%13,%14,%15,"
      "%16,%17,%18,%19,%20,%21,%22,%23,%24,%25,%26,%27,%28,%29,%30,%31,"
      "%32,%33,%34,%35,%36,%37,%38,%39,%40,%41,%42,%43,%44,%45,%46,%47,"
      "%48,%49,%50,%51,%52,%53,%54,%55,%56,%57,%58,%59,%60,%61,%62,%63,"
      "%64,%65,%66,%67,%68,%69,%70,%71,%72,%73,%74,%75,%76,%77,%78,%79,"
      "%80,%81,%82,%83,%84,%85,%86,%87,%88,%89,%90,%91,%92,%93,%94,%95,"
      "%96,%97,%98,%99,%100,%101,%102,%103,%104,%105,%106,%107,%108,%109,%110,%111"
      "}, {%112,%113,%114,%115}, %116, p, 1, 1, 0; }"
    : "+f"(d[0]), "+f"(d[1]), "+f"(d[2]), "+f"(d[3]), "+f"(d[4]), "+f"(d[5]), "+f"(d[6]), "+f"(d[7]),
      "+f"(d[8]), "+f"(d[9]), "+f"(d[10]), "+f"(d[11]), "+f"(d[12]), "+f"(d[13]), "+f"(d[14]), "+f"(d[15]),
      "+f"(d[16]), "+f"(d[17]), "+f"(d[18]), "+f"(d[19]), "+f"(d[20]), "+f"(d[21]), "+f"(d[22]), "+f"(d[23]),
      "+f"(d[24]), "+f"(d[25]), "+f"(d[26]), "+f"(d[27]), "+f"(d[28]), "+f"(d[29]), "+f"(d[30]), "+f"(d[31]),
      "+f"(d[32]), "+f"(d[33]), "+f"(d[34]), "+f"(d[35]), "+f"(d[36]), "+f"(d[37]), "+f"(d[38]), "+f"(d[39]),
      "+f"(d[40]), "+f"(d[41]), "+f"(d[42]), "+f"(d[43]), "+f"(d[44]), "+f"(d[45]), "+f"(d[46]), "+f"(d[47]),
      "+f"(d[48]), "+f"(d[49]), "+f"(d[50]), "+f"(d[51]), "+f"(d[52]), "+f"(d[53]), "+f"(d[54]), "+f"(d[55]),
      "+f"(d[56]), "+f"(d[57]), "+f"(d[58]), "+f"(d[59]), "+f"(d[60]), "+f"(d[61]), "+f"(d[62]), "+f"(d[63]),
      "+f"(d[64]), "+f"(d[65]), "+f"(d[66]), "+f"(d[67]), "+f"(d[68]), "+f"(d[69]), "+f"(d[70]), "+f"(d[71]),
      "+f"(d[72]), "+f"(d[73]), "+f"(d[74]), "+f"(d[75]), "+f"(d[76]), "+f"(d[77]), "+f"(d[78]), "+f"(d[79]),
      "+f"(d[80]), "+f"(d[81]), "+f"(d[82]), "+f"(d[83]), "+f"(d[84]), "+f"(d[85]), "+f"(d[86]), "+f"(d[87]),
      "+f"(d[88]), "+f"(d[89]), "+f"(d[90]), "+f"(d[91]), "+f"(d[92]), "+f"(d[93]), "+f"(d[94]), "+f"(d[95]),
      "+f"(d[96]), "+f"(d[97]), "+f"(d[98]), "+f"(d[99]), "+f"(d[100]), "+f"(d[101]), "+f"(d[102]), "+f"(d[103]),
      "+f"(d[104]), "+f"(d[105]), "+f"(d[106]), "+f"(d[107]), "+f"(d[108]), "+f"(d[109]), "+f"(d[110]), "+f"(d[111])
    : "r"(a[0]), "r"(a[1]), "r"(a[2]), "r"(a[3]), "l"(db), "r"(sd));
}

__device__ __forceinline__ void wgmma_rs_n240(float* d, const uint32_t* a, uint64_t db, int sd) {
  asm volatile("{ .reg .pred p; setp.ne.b32 p, %125, 0;\n"
      "wgmma.mma_async.sync.aligned.m64n240k16.f32.bf16.bf16 {"
      "%0,%1,%2,%3,%4,%5,%6,%7,%8,%9,%10,%11,%12,%13,%14,%15,"
      "%16,%17,%18,%19,%20,%21,%22,%23,%24,%25,%26,%27,%28,%29,%30,%31,"
      "%32,%33,%34,%35,%36,%37,%38,%39,%40,%41,%42,%43,%44,%45,%46,%47,"
      "%48,%49,%50,%51,%52,%53,%54,%55,%56,%57,%58,%59,%60,%61,%62,%63,"
      "%64,%65,%66,%67,%68,%69,%70,%71,%72,%73,%74,%75,%76,%77,%78,%79,"
      "%80,%81,%82,%83,%84,%85,%86,%87,%88,%89,%90,%91,%92,%93,%94,%95,"
      "%96,%97,%98,%99,%100,%101,%102,%103,%104,%105,%106,%107,%108,%109,%110,%111,"
      "%112,%113,%114,%115,%116,%117,%118,%119"
      "}, {%120,%121,%122,%123}, %124, p, 1, 1, 0; }"
    : "+f"(d[0]), "+f"(d[1]), "+f"(d[2]), "+f"(d[3]), "+f"(d[4]), "+f"(d[5]), "+f"(d[6]), "+f"(d[7]),
      "+f"(d[8]), "+f"(d[9]), "+f"(d[10]), "+f"(d[11]), "+f"(d[12]), "+f"(d[13]), "+f"(d[14]), "+f"(d[15]),
      "+f"(d[16]), "+f"(d[17]), "+f"(d[18]), "+f"(d[19]), "+f"(d[20]), "+f"(d[21]), "+f"(d[22]), "+f"(d[23]),
      "+f"(d[24]), "+f"(d[25]), "+f"(d[26]), "+f"(d[27]), "+f"(d[28]), "+f"(d[29]), "+f"(d[30]), "+f"(d[31]),
      "+f"(d[32]), "+f"(d[33]), "+f"(d[34]), "+f"(d[35]), "+f"(d[36]), "+f"(d[37]), "+f"(d[38]), "+f"(d[39]),
      "+f"(d[40]), "+f"(d[41]), "+f"(d[42]), "+f"(d[43]), "+f"(d[44]), "+f"(d[45]), "+f"(d[46]), "+f"(d[47]),
      "+f"(d[48]), "+f"(d[49]), "+f"(d[50]), "+f"(d[51]), "+f"(d[52]), "+f"(d[53]), "+f"(d[54]), "+f"(d[55]),
      "+f"(d[56]), "+f"(d[57]), "+f"(d[58]), "+f"(d[59]), "+f"(d[60]), "+f"(d[61]), "+f"(d[62]), "+f"(d[63]),
      "+f"(d[64]), "+f"(d[65]), "+f"(d[66]), "+f"(d[67]), "+f"(d[68]), "+f"(d[69]), "+f"(d[70]), "+f"(d[71]),
      "+f"(d[72]), "+f"(d[73]), "+f"(d[74]), "+f"(d[75]), "+f"(d[76]), "+f"(d[77]), "+f"(d[78]), "+f"(d[79]),
      "+f"(d[80]), "+f"(d[81]), "+f"(d[82]), "+f"(d[83]), "+f"(d[84]), "+f"(d[85]), "+f"(d[86]), "+f"(d[87]),
      "+f"(d[88]), "+f"(d[89]), "+f"(d[90]), "+f"(d[91]), "+f"(d[92]), "+f"(d[93]), "+f"(d[94]), "+f"(d[95]),
      "+f"(d[96]), "+f"(d[97]), "+f"(d[98]), "+f"(d[99]), "+f"(d[100]), "+f"(d[101]), "+f"(d[102]), "+f"(d[103]),
      "+f"(d[104]), "+f"(d[105]), "+f"(d[106]), "+f"(d[107]), "+f"(d[108]), "+f"(d[109]), "+f"(d[110]), "+f"(d[111]),
      "+f"(d[112]), "+f"(d[113]), "+f"(d[114]), "+f"(d[115]), "+f"(d[116]), "+f"(d[117]), "+f"(d[118]), "+f"(d[119])
    : "r"(a[0]), "r"(a[1]), "r"(a[2]), "r"(a[3]), "l"(db), "r"(sd));
}

__device__ __forceinline__ void wgmma_rs_n256(float* d, const uint32_t* a, uint64_t db, int sd) {
  asm volatile("{ .reg .pred p; setp.ne.b32 p, %133, 0;\n"
      "wgmma.mma_async.sync.aligned.m64n256k16.f32.bf16.bf16 {"
      "%0,%1,%2,%3,%4,%5,%6,%7,%8,%9,%10,%11,%12,%13,%14,%15,"
      "%16,%17,%18,%19,%20,%21,%22,%23,%24,%25,%26,%27,%28,%29,%30,%31,"
      "%32,%33,%34,%35,%36,%37,%38,%39,%40,%41,%42,%43,%44,%45,%46,%47,"
      "%48,%49,%50,%51,%52,%53,%54,%55,%56,%57,%58,%59,%60,%61,%62,%63,"
      "%64,%65,%66,%67,%68,%69,%70,%71,%72,%73,%74,%75,%76,%77,%78,%79,"
      "%80,%81,%82,%83,%84,%85,%86,%87,%88,%89,%90,%91,%92,%93,%94,%95,"
      "%96,%97,%98,%99,%100,%101,%102,%103,%104,%105,%106,%107,%108,%109,%110,%111,"
      "%112,%113,%114,%115,%116,%117,%118,%119,%120,%121,%122,%123,%124,%125,%126,%127"
      "}, {%128,%129,%130,%131}, %132, p, 1, 1, 0; }"
    : "+f"(d[0]), "+f"(d[1]), "+f"(d[2]), "+f"(d[3]), "+f"(d[4]), "+f"(d[5]), "+f"(d[6]), "+f"(d[7]),
      "+f"(d[8]), "+f"(d[9]), "+f"(d[10]), "+f"(d[11]), "+f"(d[12]), "+f"(d[13]), "+f"(d[14]), "+f"(d[15]),
      "+f"(d[16]), "+f"(d[17]), "+f"(d[18]), "+f"(d[19]), "+f"(d[20]), "+f"(d[21]), "+f"(d[22]), "+f"(d[23]),
      "+f"(d[24]), "+f"(d[25]), "+f"(d[26]), "+f"(d[27]), "+f"(d[28]), "+f"(d[29]), "+f"(d[30]), "+f"(d[31]),
      "+f"(d[32]), "+f"(d[33]), "+f"(d[34]), "+f"(d[35]), "+f"(d[36]), "+f"(d[37]), "+f"(d[38]), "+f"(d[39]),
      "+f"(d[40]), "+f"(d[41]), "+f"(d[42]), "+f"(d[43]), "+f"(d[44]), "+f"(d[45]), "+f"(d[46]), "+f"(d[47]),
      "+f"(d[48]), "+f"(d[49]), "+f"(d[50]), "+f"(d[51]), "+f"(d[52]), "+f"(d[53]), "+f"(d[54]), "+f"(d[55]),
      "+f"(d[56]), "+f"(d[57]), "+f"(d[58]), "+f"(d[59]), "+f"(d[60]), "+f"(d[61]), "+f"(d[62]), "+f"(d[63]),
      "+f"(d[64]), "+f"(d[65]), "+f"(d[66]), "+f"(d[67]), "+f"(d[68]), "+f"(d[69]), "+f"(d[70]), "+f"(d[71]),
      "+f"(d[72]), "+f"(d[73]), "+f"(d[74]), "+f"(d[75]), "+f"(d[76]), "+f"(d[77]), "+f"(d[78]), "+f"(d[79]),
      "+f"(d[80]), "+f"(d[81]), "+f"(d[82]), "+f"(d[83]), "+f"(d[84]), "+f"(d[85]), "+f"(d[86]), "+f"(d[87]),
      "+f"(d[88]), "+f"(d[89]), "+f"(d[90]), "+f"(d[91]), "+f"(d[92]), "+f"(d[93]), "+f"(d[94]), "+f"(d[95]),
      "+f"(d[96]), "+f"(d[97]), "+f"(d[98]), "+f"(d[99]), "+f"(d[100]), "+f"(d[101]), "+f"(d[102]), "+f"(d[103]),
      "+f"(d[104]), "+f"(d[105]), "+f"(d[106]), "+f"(d[107]), "+f"(d[108]), "+f"(d[109]), "+f"(d[110]), "+f"(d[111]),
      "+f"(d[112]), "+f"(d[113]), "+f"(d[114]), "+f"(d[115]), "+f"(d[116]), "+f"(d[117]), "+f"(d[118]), "+f"(d[119]),
      "+f"(d[120]), "+f"(d[121]), "+f"(d[122]), "+f"(d[123]), "+f"(d[124]), "+f"(d[125]), "+f"(d[126]), "+f"(d[127])
    : "r"(a[0]), "r"(a[1]), "r"(a[2]), "r"(a[3]), "l"(db), "r"(sd));
}

__device__ __forceinline__ void ln_finish(float mean, float var, float& mb, float& rinv) {
  mb = round_bf16(mean);
  float sd;
  asm("sqrt.approx.ftz.f32 %0, %1;" : "=f"(sd) : "f"(round_bf16(round_bf16(var) + 1e-5f)));
  asm("rcp.approx.ftz.f32 %0, %1;" : "=f"(rinv) : "f"(round_bf16(sd)));
}
__device__ __forceinline__ uint32_t sum4(uint32_t a, uint32_t b, uint32_t c, uint32_t d) { return badd2(badd2(badd2(d, c), b), a); }
struct Ring {
  uint32_t s, ph;
  __device__ __forceinline__ void next() { if (++s == NSTAGE) { s = 0; ph ^= 1; } }
};

template <int J> __device__ __forceinline__ void conv_lda(uint32_t* a, uint32_t base, bool on) {
  asm volatile("{ .reg .pred p; setp.ne.u32 p, %3, 0;\n @p ld.shared.u32 %0, [%2 + %4];\n @p ld.shared.u32 %1, [%2 + %5]; }"
               : "+r"(a[2 * J]), "+r"(a[2 * J + 1]) : "r"(base), "r"((uint32_t)on), "n"((J >> 1) * 256 + (J & 1) * 16), "n"((J >> 1) * 256 + (J & 1) * 16 + 128) : "memory");
}
template <int J = 0> __device__ __forceinline__ void conv_lda_all(uint32_t* a, uint32_t base) {
  conv_lda<J>(a, base, true);
  if constexpr (J < 31) conv_lda_all<J + 1>(a, base);
}
__device__ __forceinline__ void conv_mma(float* acc, const uint32_t* a, uint64_t db) {
  wgmma_rs_n256(acc, a, db, 0);
  wgmma_rs_n240(acc, a + 4, db + 16, 1);
  wgmma_rs_n224(acc, a + 8, db + 32, 1);
  wgmma_rs_n208(acc, a + 12, db + 48, 1);
  wgmma_rs_n192(acc, a + 16, db + 64, 1);
  wgmma_rs_n176(acc, a + 20, db + 80, 1);
  wgmma_rs_n160(acc, a + 24, db + 96, 1);
  wgmma_rs_n144(acc, a + 28, db + 112, 1);
  wgmma_rs_n128(acc, a + 32, db + 128, 1);
  wgmma_rs_n112(acc, a + 36, db + 144, 1);
  wgmma_rs_n96(acc, a + 40, db + 160, 1);
  wgmma_rs_n80(acc, a + 44, db + 176, 1);
  wgmma_rs_n64(acc, a + 48, db + 192, 1);
  wgmma_rs_n48(acc, a + 52, db + 208, 1);
  wgmma_rs_n32(acc, a + 56, db + 224, 1);
  wgmma_rs_n16(acc, a + 60, db + 240, 1);
}
__device__ __forceinline__ uint32_t conv_part(const float* acc, int j) {
  const int q = 31 - j;
  return q == 31 ? pack_bf16(acc[124], acc[125]) : pack_bf16(acc[4 * q] + acc[(4 * q + 6) & 127], acc[4 * q + 1] + acc[(4 * q + 7) & 127]);
}
template <int J = 0> __device__ __forceinline__ void conv_drain(const float* acc, uint32_t wr, uint32_t* a, uint32_t ka, bool more) {
  conv_lda<J>(a, ka, more);
  sts32(wr + J * 128, conv_part(acc, J));
  if constexpr (J < 31) conv_drain<J + 1>(acc, wr, a, ka, more);
}
__device__ __forceinline__ uint4 conv_sum(const uint4* p) {
  return make_uint4(sum4(p[0].x, p[1].x, p[2].x, p[3].x), sum4(p[0].y, p[1].y, p[2].y, p[3].y), sum4(p[0].z, p[1].z, p[2].z, p[3].z),
                    sum4(p[0].w, p[1].w, p[2].w, p[3].w));
}
__device__ __forceinline__ int g2k(int rank, int kb) { return (rank * G2_KB + (kb < 6 ? 6 * kb : kb - 5 + (kb - 6) / 5)) * 64; }

template <int NV> __device__ __forceinline__ void gelu_stage(float* acc, const float* hb, uint32_t sa, int passes, uint32_t bar) {
#pragma unroll
  for (int i = 0; i < NV; i++) acc[i] = fmaf(acc[i], 0.5f, hb[(i >> 1) & 1]);
#pragma unroll 1
  for (; passes > 0; passes--, sa += NV * 256) {
#pragma unroll
    for (int i = 0; i < NV; i += 8)
      stsm4t(sa + i * 256, pack_bf16(gelu_half(acc[i]), gelu_half(acc[i + 1])), pack_bf16(gelu_half(acc[i + 2]), gelu_half(acc[i + 3])),
             pack_bf16(gelu_half(acc[i + 4]), gelu_half(acc[i + 5])), pack_bf16(gelu_half(acc[i + 6]), gelu_half(acc[i + 7])));
    __syncwarp();
    if (bar) mbar_arrive(bar);
    bar = 0;
    float half = 0.5f;
    asm volatile("" : "+f"(half));
#pragma unroll
    for (int i = 0; i < NV; i++) acc[i] = fmaf(acc[NV + i], half, hb[2 + ((i >> 1) & 1)]);
  }
}

__global__ void __cluster_dims__(2, 1, 1) __launch_bounds__(384, 1) fused_kernel(const __grid_constant__ Hot H, const __grid_constant__ Params P) {
  extern __shared__ __align__(1024) uint8_t smem_raw[];
  const uint32_t t0 = clk();
  const uint32_t sb = smem_u32(smem_raw);
  const int tid = threadIdx.x, lane = tid & 31;
  const int bid = blockIdx.x, rank = bid & 1;
  const Role& R = P.role[bid];
  Scratch* const S = H.S;
  uint32_t xr[18];
  const int row = bid * 16 + (tid >> 4);
  if (tid < 256 && bid < 128) {
    const char* src = reinterpret_cast<const char*>(H.x) + row * (D_ * 2) + (lane & 15) * 8;
#pragma unroll
    for (int j = 0; j < 9; j++) asm volatile("ld.global.nc.v2.u32 {%0,%1}, [%2];" : "=r"(xr[2 * j]), "=r"(xr[2 * j + 1]) : "l"(src + 128 * j));
  }
  const int warp = __shfl_sync(0xffffffffu, tid >> 5, 0);

  if (warp >= 8) {
    const bool one = elect_one();
    if (warp == 8 && one) {
#pragma unroll
      for (int b = B_FULL; b <= B_DONE; b += 8) mbar_init(sb + b, b < B_EMPTY ? 1 : b < B_SFREE ? 2 : b < B_CEMPTY ? 3 : b < B_G1DONE ? 4 : 8);
      asm volatile("fence.mbarrier_init.release.cluster;" ::: "memory");
    }
    __syncwarp();
    asm volatile("barrier.cluster.arrive.relaxed.aligned;" ::: "memory");
    asm volatile("setmaxnreg.dec.sync.aligned.u32 56;");
    asm volatile("barrier.cluster.wait.aligned;" ::: "memory");
    const bool left = R.at == 15;
    if (warp == 8) {
      const uint32_t ep = ldg32(S->cnt + C_EPOCH * 32);
      if (one) {
#pragma unroll 1
        for (int i = 0; i < 11; i++) asm volatile("prefetch.tensormap [%0];" :: "l"(&P.m_w1 + i) : "memory");
#pragma unroll 1
        for (int s = 0; s < NWE; s++) {
          mbar_expect_tx(sb + B_FULL + 8 * s, G1_BYTES);
          tma3d(sb + s * SLOT, &P.m_w1 + left, 0, s * 64, R.fg, sb + B_FULL + 8 * s);
        }
      }
      __syncwarp();
      if (bid < 128) bar_sync(2, 288);
      if (one) {
        TLREC(31);
        signal(S, C_H, EPOCH / 132);
        TLREC(1);
        const uint32_t boff = left ? 24576 : 16384;
        int kr = bid < 128 ? -2 : KV_ROUNDS + 1, ks = 0;
        auto kv_step = [&]() {
          if (ks == 0) {
            bulk_wait_all();
            if (kr < KV_ROUNDS - 2) {
              const int q = (kr + 2) % 3;
              const uint32_t in = sb + kv_buf(q), fb = sb + B_UFULL + 8 * q;
              mbar_expect_tx(fb, 3840 + 3264 + 768);
              tma2d(in, &P.m_k, (kr + 2) * 96, bid * 16 - 4, fb);
              tma2d(in + 3840, &P.m_v, (kr + 2) * 96, bid * 16 - 1, fb);
              bulk_load(in + 7168, H.shift_k + (kr + 2) * 384, 768, fb);
            }
            if (kr == KV_ROUNDS) { mbar_arrive(sb + B_KVDONE); kr++; }
          } else if (kr >= 0) {
            if (!mbar_test(sb + B_KFULL + 8 * (kr % 3), kr >= 3)) return;
            fence_async_smem();
            tma3d_store(&P.m_ub, sb + kv_buf(kr % 3) + (ks - 1) * 3072, 16 * (127 - bid), kr * 48, 2 * ks - 2);
            bulk_commit();
          }
          if (++ks == 3) { kr++; ks = kr == KV_ROUNDS - 2 || kr == KV_ROUNDS - 1; }
        };
        if (bid >= 128) mbar_arrive(sb + B_KVDONE);
        Ring r{0, 1};
#pragma unroll 1
        for (int kb = NWE - NW0; kb < G1_KB || kr <= KV_ROUNDS; kb++) {
          if (kb < G1_KB) {
          const int kw = kb < 0 ? kb + NW0 : kb, s = kb < 0 ? kw : r.s;
          const uint32_t fb = sb + B_FULL + 8 * s;
          if (kb < 0 || kb >= NW0) {
            mbar_wait(sb + B_EMPTY + 8 * s, r.ph);
            mbar_expect_tx(fb, G1_BYTES);
            tma3d(sb + s * SLOT, &P.m_w1 + left, 0, kw * 64, R.fg, fb);
            if (kb < 0) continue;
          }
          if (kb == 0) { await(S, C_H, ep); fence_async_global(); TLREC(2); }
          bulk_load(sb + s * SLOT + boff, S->h + (kb * 18 + R.at) * 2048, G1_BYTES - boff, fb);
          if (kb == 23) {
#pragma unroll 1
            for (int i = 0; i < 2; i++) {
              sts128(sb + cv_taps(i), 0, 0, 0, 0); sts128(sb + cv_taps(i) + 16, 0, 0, 0, 0);
              bulk_load(sb + cv_taps(i) + 32, H.ssm_k + (R.ch + i) * S_, 4096, sb + B_MISC);
            }
            mbar_expect_tx(sb + B_MISC, boff / 64 + 1152 + 8192);
            bulk_load(sb + SM_B1, H.b1 + R.fg * 64, boff / 64, sb + B_MISC);
            bulk_load(sb + SM_D, H.ssm_D, 1152, sb + B_MISC);
          }
          r.next();
          }
          if (kb >= KV0 && kr <= KV_ROUNDS) kv_step();
        }
        await(S, C_KV, ep);
        fence_async_global();
#pragma unroll 1
        for (int i = 0; i < R.ncv; i++) {
          if (i == 2) {
            if (R.sg >= 0) {
#pragma unroll 1
              for (int s = 2; s < NSTAGE; s++) {
                mbar_wait(sb + B_EMPTY + 8 * s, ((G1_KB / NSTAGE) - 1) & 1);
                mbar_expect_tx(sb + B_FULL + 8 * s, G2_BYTES);
                tma3d(sb + s * SLOT, &P.m_w2, 0, (rank * G2_KB + 6 * (s - 2)) * 64, R.sg, sb + B_FULL + 8 * s);
              }
            }
            mbar_wait(sb + B_G1DONE, 0);
          }
          const uint32_t kt = sb + cv_taps(i), b8 = sb + 8 * (i & 3);
          mbar_wait(b8 + B_CEMPTY, ((i >> 2) & 1) ^ 1);
          if (i < 2) mbar_arrive(b8 + B_KFULL);
          else {
            sts128(kt, 0, 0, 0, 0); sts128(kt + 16, 0, 0, 0, 0);
            mbar_expect_tx(b8 + B_KFULL, 4096);
            bulk_load(kt + 32, H.ssm_k + (R.ch + i) * S_, 4096, b8 + B_KFULL);
          }
          mbar_expect_tx(b8 + B_UFULL, 8192);
          bulk_load(sb + cv_in(i), S->ub + (R.ch + i) * 4096, 8192, b8 + B_UFULL);
        }
        if (R.sg >= 0) {
          mbar_expect_tx(sb + B_XY, 2 * 18432 + 2048 + 256);
          mbar_expect_tx(sb + B_XFULL, 9216);
          mbar_expect_tx(sb + B_XFULL + 8, 9216);
#pragma unroll 1
          for (int kb = 0; kb < G2_KB; kb++, r.next()) {
            const int k0 = g2k(rank, kb);
            const uint32_t fb = sb + B_FULL + 8 * r.s, slot = sb + r.s * SLOT;
            if (!(kb & ~4)) { await(S, C_U + (kb >> 2), ep); fence_async_global(); if (!kb) TLREC(6); }
            if (kb >= NSTAGE - 2) {
              mbar_wait(sb + B_EMPTY + 8 * r.s, r.ph);
              if (kb == SYNCA) asm volatile("red.relaxed.gpu.global.add.u32 [%0], %1;" :: "l"(S->cnt + C_SYNC * 32), "r"(EPOCH / 128) : "memory");
              if (kb == SYNCKB) await(S, C_SYNC, ep);
              mbar_expect_tx(fb, G2_BYTES);
              tma3d(slot, &P.m_w2, 0, k0, R.sg, fb);
            }
            tma2d(slot + 16384, &P.m_uld, k0, R.ds * 8, fb);
            tma2d(slot + 16384 + 9216, &P.m_uld, k0, R.dk * 8, fb);
            const uint32_t nx = kb - 8;
            if (nx == 0) { mbar_wait(sb + B_KVDONE, 1); fence_async_smem(); }
            if (nx < 8) tma2d(sb + SM_CV + nx * 2304, &P.m_x, R.dk * 8, R.sg * 64 + nx * 16, sb + B_XY);
          }
          bulk_load(sb + SM_ST, S->stats + R.sg * 64, 2048, sb + B_XY);
          bulk_load(sb + SM_B2, P.b2 + R.sg * 64, 256, sb + B_XY);
          await(S, C_Y, ep);
          fence_async_global();
          TLREC(19);
          tma3d(sb + SM_DED, &P.m_y, 0, R.dk * 8, R.sg, sb + B_XY);
          if (bid == 0) asm volatile("red.relaxed.gpu.global.add.u32 [%0], %1;" :: "l"(S->cnt + C_EPOCH * 32), "r"(EPOCH) : "memory");
        }
      }
    } else {
      if (bid < 128) {
        const int ht = tid - 288, hf = ht >= 48, pr = ht - 48 * hf;
        const uint32_t st = (1 - hf) * 1536 + pr * 32, sw = (pr & 4) * 4;
#pragma unroll 1
        for (int r = 0; r < KV_ROUNDS; r++) {
          const int q = r % 3;
          const uint32_t in = sb + kv_buf(q);
          {
            mbar_wait_guarded(sb + B_UFULL + 8 * q, t0, r >= 3);
            uint32_t kk[12], vv[9];
#pragma unroll
            for (int j = 0; j < 12; j++) kk[j] = lds32(in + hf * 1536 + pr * 4 + j * 192);
#pragma unroll
            for (int j = 0; j < 9; j++) vv[j] = lds32(in + 3840 + hf * 1536 + pr * 4 + j * 192);
            const uint4 w = lds128(in + 7168 + pr * 16);
            const uint32_t w0 = __byte_perm(w.x, w.z, 0x5410), w1 = __byte_perm(w.x, w.z, 0x7632);
            const uint32_t w2 = __byte_perm(w.y, w.w, 0x5410), w3 = __byte_perm(w.y, w.w, 0x7632);
#pragma unroll
            for (int j = 0; j < 9; j++)
              vv[j] = bmul2(badd2(badd2(badd2(bmul2(kk[j], w3), bmul2(kk[j + 1], w2)), bmul2(kk[j + 2], w1)), bmul2(kk[j + 3], w0)), vv[j]);
            bar_sync(1, 96);
#pragma unroll
            for (int c = 0; c < 2; c++)
#pragma unroll
              for (int pi = 0; pi < 2; pi++) {
                const uint32_t sel = c ? 0x7632 : 0x5410;
                sts128(in + st + c * 3072 + (pi * 16 ^ sw), __byte_perm(vv[7 + pi], vv[6 + pi], sel), __byte_perm(vv[5 + pi], vv[4 + pi], sel),
                       __byte_perm(vv[3 + pi], vv[2 + pi], sel), __byte_perm(vv[1 + pi], vv[pi], sel));
              }
            bar_sync(1, 96);
            if (ht == 0) mbar_arrive(sb + B_KFULL + 8 * q);
          }
          __syncwarp();
        }
      }
      if (one) {
        if (warp < 11) {
          const int wg = warp - 9;
#pragma unroll 1
          for (int j = 0; j <= (left ? 3 + 3 * wg : 5); j++) {
            if (j == 0 || j == 2 + left) {
              mbar_wait_guarded(sb + B_STG + 8 * wg + (j ? 0 : 16), t0);
              fence_async_smem();
              TLREC(13 + wg);
            }
            const int hi = left && j >= 3;
            if (j < (left ? 3 + 3 * wg : 5))
              tma2d_store(&P.m_ust, sb + (wg ? SM_ST1 : SM_DED) + j * 4096, (R.fg + wg + hi) * 64, (R.at + j - 3 * hi) * 32);
          }
          bulk_commit();
          bulk_wait_all();
          mbar_arrive(sb + B_STORED + 8 * wg);
          if (wg) mbar_arrive(sb + B_EMPTY);
          asm volatile("mbarrier.arrive.shared::cta.b64 _, [%0], 3;" :: "r"(sb + B_SFREE + 8 * wg) : "memory");
          signal(S, C_U + wg, EPOCH / 132);
          TLREC(15 + wg);
        } else {
          mbar_wait_guarded(sb + B_KVDONE, t0);
          signal(S, C_KV, EPOCH / 132);
          TLREC(27);
        }
      }
      __syncwarp();
#pragma unroll 1
      for (int i = 0; i < R.ncv; i++) {
        const uint32_t red = sb + cv_red(i, R.ncv) + (tid - 288) * 16;
        uint4* yo = reinterpret_cast<uint4*>(S->y + (R.ch + i) * S_) + (tid - 288);
        mbar_wait_guarded(sb + B_STORED + 8 * (i & 1), t0);
        mbar_wait_guarded(sb + B_STG + 8 * (i & 1) + (i + 2 < R.ncv ? 0 : 16), t0, i + 2 >= R.ncv || !(i & 2));
        uint4 p[2][4];
#pragma unroll
        for (int x = 0; x < 8; x++) p[x >> 2][x & 3] = lds128(red + (x & 3) * CV_REDW + (x >> 2) * 1536);
        yo[0] = conv_sum(p[0]);
        if (warp < 11) {
#pragma unroll
          for (int x = 0; x < 4; x++) p[0][x] = lds128(red + x * CV_REDW + 3072);
          yo[192] = conv_sum(p[0]);
        }
        yo[96] = conv_sum(p[1]);
        __syncwarp();
        if (one) mbar_arrive(sb + (i + 4 == R.ncv ? B_PDONE : B_SFREE + 8 * (i & 1)));
        if (i + 3 == R.ncv) {
          bar_sync(1, 96);
          if (warp == 11 && one) { fence_async_smem(); mbar_arrive(sb + B_EMPTY + 8); }
          __syncwarp();
        }
      }
      bar_sync(1, 96);
      if (warp == 11 && one) {
        TLREC(7);
        mbar_arrive(sb + B_KVDONE);
        signal(S, C_Y, EPOCH / 132);
        if (R.sg >= 0) mbar_wait_guarded(sb + B_DONE, t0);
      }
    }
    TLEND();
  } else {
    asm volatile("barrier.cluster.arrive.relaxed.aligned;" ::: "memory");
    if (bid < 128) {
      float c[36], s[4];
#pragma unroll
      for (int i = 0; i < 18; i++) { c[2 * i] = bf_lo(xr[i]); c[2 * i + 1] = bf_hi(xr[i]); }
#pragma unroll
      for (int i = 0; i < 36; i++) s[i & 3] = i < 4 ? c[i] : s[i & 3] + c[i];
      const float ml = ((s[0] + s[1]) + (s[2] + s[3])) * (1.0f / 36.0f);
#pragma unroll
      for (int i = 0; i < 36; i++) { c[i] -= ml; s[i & 3] = i < 4 ? c[i] * c[i] : fmaf(c[i], c[i], s[i & 3]); }
      float m = ml, q = (s[0] + s[1]) + (s[2] + s[3]), n2 = 18.f;
#pragma unroll
      for (int o = 1; o < 16; o <<= 1) {
        const float mo = __shfl_xor_sync(0xffffffffu, m, o), qo = __shfl_xor_sync(0xffffffffu, q, o);
        const float dl = m - mo;
        q = fmaf(dl * dl, n2, q + qo);
        m = fmaf(dl, -0.5f, m);
        n2 *= 2.f;
      }
      const float var = q * (1.0f / 576.0f);
      float mb, rinv, mb2, rinv2;
      ln_finish(m, var, mb, rinv);
      ln_finish((m - mb) * rinv, var * rinv * rinv, mb2, rinv2);
      const float ca = rinv * rinv2, cb = fmaf(ml - mb, rinv, -mb2) * rinv2;
      uint2* dst = reinterpret_cast<uint2*>(S->h) + ((row >> 6) * 18 + ((lane >> 3) & 1)) * 512 + (row & 63) * 8 + ((lane & 7) ^ (row & 6));
#pragma unroll
      for (int j = 0; j < 9; j++)
        dst[1024 * j] = make_uint2(pack_bf16(fmaf(c[4 * j], ca, cb), fmaf(c[4 * j + 1], ca, cb)), pack_bf16(fmaf(c[4 * j + 2], ca, cb), fmaf(c[4 * j + 3], ca, cb)));
      const uint32_t rh = pack_bf16(rinv, rinv);
      if (!(lane & 15)) S->stats[row] = make_uint4(pack_bf16(mb, mb), rh, pack_bf16(rinv - bf_lo(rh), rinv - bf_lo(rh)), 0);
      __syncwarp();
      bar_arrive(2, 288);
    }
    asm volatile("setmaxnreg.inc.sync.aligned.u32 224;");
    asm volatile("barrier.cluster.wait.aligned;" ::: "memory");
    const int wg = warp >> 2, w = warp & 3, g = lane >> 2, t = lane & 3, wtid = tid & 127;
    const bool elect = wtid == 0;
    const uint64_t da0 = make_desc(sb + wg * 8192, 8192, 1024, 1);
    const uint32_t swz = ((lane >> 4) * 8 + (lane & 7)) * 128 + (((2 * w + ((lane >> 3) & 1)) ^ (lane & 7)) << 4);
    const uint32_t stg = sb + (wg ? SM_ST1 : SM_DED), ka0 = (8 * w + g + t + 1) * 4;
    uint32_t a[64];
    {
      auto mainloop = [&](auto&& mma) {
        Ring r{0, 0};
        uint32_t rel = 0;
#pragma unroll 1
        for (int kb = 0; kb < G1_KB; kb++, r.next()) {
          if (kb == G1_KB - G1_TAIL && wg) {
            wg_wait<0>();
            if (elect) mbar_arrive(rel);
            rel = 0;
            if (PRE1) {
              mbar_wait(sb + B_MISC, 0);
              conv_lda_all(a, sb + SM_CV + 16384 + CV_K + ka0);
            }
            bar_sync(5, 256);
          }
          mbar_wait(sb + B_FULL + 8 * r.s, r.ph);
          if (kb == 0 && warp == 0) TLREC(3);
          wg_fence();
          mma(r.s * (SLOT >> 4), kb);
          wg_commit();
          if (kb == G1_KB - 1) break;
          wg_wait<1>();
          if (elect && rel) mbar_arrive(rel);
          rel = sb + B_EMPTY + 8 * r.s;
        }
        bar_arrive(5, 256);
        wg_wait<0>();
      };
      float hb[4];
      auto staged = [&](int second) {
        if (!w) TLREC(4 + wg);
        if (lane == 0) mbar_arrive(sb + B_G1DONE);
        mbar_wait(sb + B_MISC, 0);
#pragma unroll
        for (int i = 0; i < 4; i++) hb[i] = 0.5f * bf_lo(lds16(sb + SM_B1 + (warp * 16 + g + (i & 1) * 8 + (i >> 1) * second) * 2));
        mbar_wait(sb + B_KVDONE, 0);
        if (wg) mbar_wait(sb + B_G1DONE, 0);
      };
      if (R.at != 15) {
        const uint64_t db0 = make_desc(sb + 16384, 4096, 512, 2);
        float acc[80];
        mainloop([&](uint32_t o, int kb) {
          wgmma_ss_n160_t11(acc, da0 + o, db0 + o, kb);
#pragma unroll
          for (int k = 1; k < 4; k++) wgmma_ss_n160_t11(acc, da0 + o + k * 128, db0 + o + k * 64, 1);
        });
        pin_regs<80>(acc);
        staged(0);
        gelu_stage<40>(acc, hb, stg + swz, 2, lane ? 0 : sb + B_STG + 8 * wg + 16);
      } else {
        const uint64_t db0 = make_desc(sb + 24576, 4096, 512, 2);
        float acc[96];
        auto block = [&](float* d, uint64_t da, uint64_t db, int kb) {
          wgmma_ss_n96_t11(d, da, db, kb);
#pragma unroll
          for (int k = 1; k < 4; k++) wgmma_ss_n96_t11(d, da + k * 128, db + k * 64, 1);
        };
        if (wg) mainloop([&](uint32_t o, int kb) { block(acc, da0 + o, db0 + o, kb); block(acc + 48, da0 + o + 512, db0 + o, kb); });
        else mainloop([&](uint32_t o, int kb) { block(acc, da0 + o, db0 + o, kb); });
        pin_regs<96>(acc);
        staged(64);
        gelu_stage<48>(acc, hb, stg + swz, 1 + wg, lane ? 0 : sb + B_STG + 8 * wg + 16);
      }
      __syncwarp();
      if (lane == 0) mbar_arrive(sb + B_STG + 8 * wg);
    }
    {
      if (!wg || !PRE1) conv_lda_all(a, sb + SM_CV + 16384 + wg * CV_K + ka0);
#pragma unroll 1
      for (int i = wg; i < R.ncv; i += 2) {
        const bool more = i + 2 < R.ncv;
        const uint32_t dd = lds16(sb + SM_D + (R.ch + i) * 2);
        a[0] = badd2(a[0], ka0 == 32 ? dd : 0); a[2] = badd2(a[2], ka0 == 16 ? dd : 0);
        float acc[128];
        mbar_wait(sb + B_UFULL + 8 * (i & 3), (i >> 2) & 1);
        bar_sync(5 + wg, 256);
        const bool last = i + 1 == R.ncv;
        if (last && elect) mbar_arrive(sb + B_EMPTY);
        if (!w && i < 4) TLREC(22 + i);
        wg_fence();
        conv_mma(acc, a, make_desc(sb + cv_in(i), 4096, 128, 0));
        wg_commit();
        if (!last) bar_arrive(5 + (wg ^ 1), 256);
        if (more) {
          mbar_wait(sb + B_SFREE + 8 * wg, (i >> 1) & 1);
          mbar_wait(sb + B_KFULL + 8 * ((i + 2) & 3), ((i + 2) >> 2) & 1);
        } else if (last) mbar_wait(sb + B_PDONE, 0);
        wg_wait<0>();
        pin_regs<128>(acc);
        if (lane == 0) mbar_arrive(sb + B_CEMPTY + 8 * (i & 3));
        if (last && elect) mbar_arrive(sb + B_EMPTY + 8);
        const uint32_t red = sb + cv_red(i, R.ncv), ka = sb + cv_taps(i + 2) + ka0;
        if (lane < 8 * w) sts32(red + w * CV_REDW + lane * 4, 0);
        const uint32_t wr = red + w * CV_REDW + (8 * (3 - t + w) + g) * 4;
        conv_drain(acc, wr, a, ka, more);
        __syncwarp();
        if (lane == 0) mbar_arrive(sb + B_STG + 8 * wg + (more ? 0 : 16));
      }
      if (!w) TLREC(20 + wg);
    }
    if (R.sg >= 0) {
      const int srow = R.sg * 64 + warp * 16;
      const uint64_t db0 = make_desc(sb + 16384, 16, 1024, 1);
      const uint32_t xo = sb + SM_CV + warp * 2304, xa = xo + (lane & 15) * 144;
      float acc[72];
      Ring r{G1_KB % NSTAGE, (G1_KB / NSTAGE) & 1};
      uint32_t rel = 0;
#pragma unroll 1
      for (int kb = 0; kb < G2_KB; kb++, r.next()) {
        if (kb == G2_KB - G2_TAIL && wg) {
          wg_wait<0>();
          if (elect) mbar_arrive_remote(rel);
          rel = 0;
          bar_sync(7, 256);
        }
        mbar_wait(sb + B_FULL + 8 * r.s, r.ph);
        if (kb == 0 && !w) TLREC(17 + wg);
        if (kb == 8 && warp == 0) TLREC(26);
        if (kb == 20 && warp == 0) TLREC(8);
        if (kb == 27 && warp == 0) TLREC(30);
        const uint64_t da = da0 + r.s * (SLOT >> 4), db = db0 + r.s * (SLOT >> 4);
        wg_fence();
        wgmma_ss_n144_t10(acc, da, db, kb);
#pragma unroll
        for (int k = 1; k < 4; k++) wgmma_ss_n144_t10(acc, da + k * 128, db + k * 2, 1);
        wg_commit();
        if (kb == G2_KB - 1) break;
        wg_wait<1>();
        if (elect && rel) mbar_arrive_remote(rel);
        rel = kb == G2_KB - NSTAGE ? mapa(sb + B_XRDY, rank ^ 1) : sb + B_EMPTY + 8 * r.s;
      }
      if (!wg) bar_arrive(7, 256);
      const uint32_t xz = sb + XSLOT * SLOT + wg * 10240 + wtid * 16;
      const uint32_t rz = mapa(xz, rank ^ 1), rb = mapa(sb + B_XFULL + 8 * wg, rank ^ 1);
      mbar_wait(sb + B_XRDY, 0);
      wg_wait<0>();
      pin_regs<72>(acc);
      if (!w) TLREC(28 + wg);
#pragma unroll
      for (int i = 0; i < 32; i += 8)
        asm volatile("st.async.weak.shared::cluster.mbarrier::complete_tx::bytes.v4.b32 [%0], {%1,%2,%3,%4}, [%5];"
                     :: "r"(rz + i * 256), "r"(pack_bf16(acc[i], acc[i + 1])), "r"(pack_bf16(acc[i + 2], acc[i + 3])),
                        "r"(pack_bf16(acc[i + 4], acc[i + 5])), "r"(pack_bf16(acc[i + 6], acc[i + 7])), "r"(rb) : "memory");
      asm volatile("st.async.weak.shared::cluster.mbarrier::complete_tx::bytes.v2.b32 [%0], {%1,%2}, [%3];"
                   :: "r"(rz + 8192), "r"(pack_bf16(acc[32], acc[33])), "r"(pack_bf16(acc[34], acc[35])), "r"(rb) : "memory");
      uint32_t xx[18], ss[18];
      mbar_wait(sb + B_XY, 0);
      {
        const uint32_t ya = sb + SM_DED + wg * 9216 + swz;
        const uint4 st0 = lds128(sb + SM_ST + (warp * 16 + g) * 16), st1 = lds128(sb + SM_ST + (warp * 16 + g + 8) * 16);
        const float hb0 = 0.5f * bf_lo(lds16(sb + SM_B2 + (warp * 16 + g) * 2)), hb1 = 0.5f * bf_lo(lds16(sb + SM_B2 + (warp * 16 + g + 8) * 2));
#pragma unroll
        for (int q = 0; q < 8; q += 2) { ldsm4(xx + 2 * q, xa + (lane >> 4) * 16 + q * 16); ldsm4t(ss + 2 * q, ya + q * 1024); }
        ldsm2(xx + 16, xa + 128);
        ldsm2t(ss + 16, ya + 8 * 1024);
#pragma unroll
        for (int i = 0; i < 18; i++) {
          const uint4& st = (i & 1) ? st1 : st0;
          const uint32_t c = bsub2(xx[i], st.x);
          ss[i] = bmul2(bfma2(c, st.y, bmul2(c, st.z)), ss[i]);
        }
#pragma unroll
        for (int i = 36; i < 72; i++) acc[i] = fmaf(acc[i], 0.5f, (i & 2) ? hb1 : hb0);
      }
      mbar_wait_cluster(sb + B_XFULL + 8 * wg, 0);
      if (!w) TLREC(9 + wg);
#pragma unroll
      for (int q = 0; q < 5; q++) {
        const uint4 v = lds128(xz + q * 2048);
        const uint32_t pv[4] = {v.x, v.y, v.z, v.w};
#pragma unroll
        for (int i = 4 * q; i < 4 * q + 4 && i < 18; i++)
          xx[i] = bfma2(ss[i], pack_bf16(silu_half(fmaf(bf_lo(pv[i & 3]), 0.5f, acc[36 + 2 * i])), silu_half(fmaf(bf_hi(pv[i & 3]), 0.5f, acc[37 + 2 * i]))), xx[i]);
        if (q < 4) stsm4(xa + (lane >> 4) * 16 + q * 32, xx[4 * q], xx[4 * q + 1], xx[4 * q + 2], xx[4 * q + 3]);
        else stsm2(xa + 128, xx[16], xx[17]);
      }
      __syncwarp();
      if (elect_one()) {
        fence_async_smem();
        tma2d_store(&P.m_out, xo, R.dk * 8, srow);
        bulk_commit();
        mbar_arrive(sb + B_DONE);
        bulk_wait_read();
      }
      if (!w) TLREC(11 + wg);
    }
    TLEND();
  }
}

typedef CUresult (*EncodeFn)(CUtensorMap*, CUtensorMapDataType, cuuint32_t, void*, const cuuint64_t*, const cuuint64_t*, const cuuint32_t*,
                             const cuuint32_t*, CUtensorMapInterleave, CUtensorMapSwizzle, CUtensorMapL2promotion, CUtensorMapFloatOOBfill);

void make_map(EncodeFn fn, CUtensorMap* m, const void* ptr, int rank, const cuuint64_t* dims, const cuuint64_t* strides, const cuuint32_t* box,
              CUtensorMapSwizzle sw) {
  const cuuint32_t es[3] = {1, 1, 1};
  fn(m, CU_TENSOR_MAP_DATA_TYPE_BFLOAT16, rank, const_cast<void*>(ptr), dims, strides, box, es, CU_TENSOR_MAP_INTERLEAVE_NONE, sw,
     CU_TENSOR_MAP_L2_PROMOTION_L2_256B, CU_TENSOR_MAP_FLOAT_OOB_FILL_NONE);
}

void make_roles(Role* R) {
  int nl = 0, ch = 0;
  for (int gi = 0; gi < 8; gi++)
    for (int b = 0; b < 132; b++) {
      const int c = b >> 1, rank = b & 1;
      int g, idx;
      if (c < 4) { g = 0; idx = 4 + c; }
      else if (c < 36) { g = (c - 4) & 7; idx = (c - 4) >> 3; }
      else if (c < 64) { g = 1 + (c - 36) % 7; idx = 4 + (c - 36) / 7; }
      else { g = c - 58; idx = 8; }
      if (g != gi) continue;
      Role& r = R[b];
      r.sg = (int8_t)(idx < 8 ? 2 * (2 * g + (idx >> 2)) : -1);
      r.dk = (int8_t)((idx & 3) * 18 + rank * 9);
      r.ds = (int8_t)((idx & 3) * 18 + (rank ^ 1) * 9);
      if (idx < (g < 2 ? 6 : 7)) {
        const int c1 = (g < 2 ? 6 * g : 7 * g - 2) + idx;
        r.fg = (int8_t)((2 * (c1 / 3) + rank) * 2); r.at = (int8_t)(c1 % 3 * 5); r.ncv = NCV_REG;
      } else {
        r.fg = (int8_t)(3 * nl++); r.at = 15; r.ncv = idx < 8 ? NCV_LEFT : NCV_LONG;
      }
      r.ch = (int16_t)ch;
      ch += r.ncv;
    }
}

}

extern "C" void kernel_launch(void* const* d_in, const int* in_sizes, int n_in, void* d_out, int out_size) {
  static Params P;
  static Hot H;
  static const void* cached[6] = {nullptr, nullptr, nullptr, nullptr, nullptr, nullptr};
  const void* now[6] = {d_in[0], d_in[1], d_in[2], d_in[7], d_in[9], d_out};
  bool same = true;
  for (int i = 0; i < 6; i++) { same = same && cached[i] == now[i]; cached[i] = now[i]; }
  if (!same) {
    void* fp = nullptr;
    cudaDriverEntryPointQueryResult qr;
    cudaGetDriverEntryPoint("cuTensorMapEncodeTiled", &fp, cudaEnableDefault, &qr);
    EncodeFn fn = (EncodeFn)fp;
    void* ps;
    cudaGetSymbolAddress(&ps, g_scratch);
    H.S = (Scratch*)ps;
    const void *pu = (char*)ps + offsetof(Scratch, u), *py = (char*)ps + offsetof(Scratch, y), *pb = (char*)ps + offsetof(Scratch, ub);
    { cuuint64_t d[3] = {64, S_, F_ / 64}, s[2] = {F_ * 2, 128}; cuuint32_t b[3] = {64, 64, 2}; make_map(fn, &P.m_w1, d_in[7], 3, d, s, b, CU_TENSOR_MAP_SWIZZLE_128B);
      b[2] = 3; make_map(fn, &P.m_w1l, d_in[7], 3, d, s, b, CU_TENSOR_MAP_SWIZZLE_128B); }
    { cuuint64_t d[2] = {F_, D_}, s[1] = {F_ * 2}; cuuint32_t b[2] = {64, 32}; make_map(fn, &P.m_ust, pu, 2, d, s, b, CU_TENSOR_MAP_SWIZZLE_128B); }
    { cuuint64_t d[3] = {64, F_, S_ / 64}, s[2] = {S_ * 2, 128}; cuuint32_t b[3] = {64, 64, 2}; make_map(fn, &P.m_w2, d_in[9], 3, d, s, b, CU_TENSOR_MAP_SWIZZLE_128B); }
    { cuuint64_t d[2] = {F_, D_}, s[1] = {F_ * 2}; cuuint32_t b[2] = {64, 72}; make_map(fn, &P.m_uld, pu, 2, d, s, b, CU_TENSOR_MAP_SWIZZLE_128B); }
    { cuuint64_t d[2] = {D_, S_}, s[1] = {D_ * 2}; cuuint32_t b[2] = {72, 16}; make_map(fn, &P.m_out, d_out, 2, d, s, b, CU_TENSOR_MAP_SWIZZLE_NONE);
      make_map(fn, &P.m_x, d_in[0], 2, d, s, b, CU_TENSOR_MAP_SWIZZLE_NONE);
      b[0] = 96; b[1] = 20; make_map(fn, &P.m_k, d_in[1], 2, d, s, b, CU_TENSOR_MAP_SWIZZLE_NONE);
      b[1] = 17; make_map(fn, &P.m_v, d_in[2], 2, d, s, b, CU_TENSOR_MAP_SWIZZLE_NONE); }
    { cuuint64_t d[3] = {64, D_, S_ / 64}, s[2] = {S_ * 2, 128}; cuuint32_t b[3] = {64, 72, 2}; make_map(fn, &P.m_y, py, 3, d, s, b, CU_TENSOR_MAP_SWIZZLE_128B); }
    { cuuint64_t d[3] = {2048, D_ / 2, 4}, s[2] = {16384, 4096}; cuuint32_t b[3] = {16, 48, 2}; make_map(fn, &P.m_ub, pb, 3, d, s, b, CU_TENSOR_MAP_SWIZZLE_32B); }
    make_roles(P.role);
    cudaFuncSetAttribute(fused_kernel, cudaFuncAttributeMaxDynamicSharedMemorySize, SM_TOTAL);
  }
  H.x = (const __nv_bfloat16*)d_in[0];
  H.shift_k = (const __nv_bfloat16*)d_in[3]; H.ssm_k = (const __nv_bfloat16*)d_in[4]; H.ssm_D = (const __nv_bfloat16*)d_in[5];
  H.b1 = (const __nv_bfloat16*)d_in[8]; P.b2 = (const __nv_bfloat16*)d_in[10];
  fused_kernel<<<132, 384, SM_TOTAL>>>(H, P);
}
```

```cpp
#include <cuda_runtime.h>
#include <cuda.h>
#include <cuda_bf16.h>
#include <stddef.h>
#include <stdint.h>

namespace {

constexpr int S_ = 2048, D_ = 576, F_ = 4608;
constexpr int NSTAGE = 5, SLOT = 36864;
constexpr int G1_KB = 32, G2_KB = 36;
constexpr int G1_BYTES = 36864, G2_BYTES = 16384 + 18432;
#define NCV_LEFT 4
constexpr int NCV_REG = 4, NCV_LONG = (D_ - 108 * NCV_REG - 20 * NCV_LEFT) / 4;
static_assert(108 * NCV_REG + 20 * NCV_LEFT + 4 * NCV_LONG == D_, "conv split");
constexpr int KV_ROUNDS = 6;
constexpr int NWE = 1, NW0 = 2;
constexpr int G1_TAIL = 4, G2_TAIL = 3;
constexpr int SYNCA = 5, SYNCKB = 8;
constexpr int PRE1 = 1;
constexpr int KV0 = 5;

constexpr int CV_K = 4224, CV_REDW = 2112 * 2;
constexpr int SM_DED = NSTAGE * SLOT;
constexpr int SM_CV = SM_DED + 20480;
constexpr int SM_ST1 = 0;
constexpr int SM_ST = SM_CV + 18432, SM_B2 = SM_ST + 2048;
constexpr int SM_B1 = SM_CV + 2 * (8192 + CV_K), SM_D = SM_B1 + 384;
constexpr int SM_BAR = SM_D + 1152;
constexpr int SM_TOTAL = SM_BAR + 768;
static_assert(G1_KB % NSTAGE == 2, "slots 0 and 1 hold the last GEMM1 k-blocks and the last two of the first GEMM2 stages");
static_assert(NCV_REG == 4 && NCV_LEFT == 4 && NCV_LONG % 4 == 0, "the last two channels use buffers 2 and 3");
constexpr int XSLOT = (G1_KB + G2_KB) % NSTAGE;
__device__ __forceinline__ uint32_t kv_buf(int q) { return q == 2 ? SM_DED : SM_CV + q * 8192; }
__device__ __forceinline__ uint32_t cv_red(int i, int n) { return i + 2 == n ? SM_CV : (i & 1) && i + 1 < n ? SLOT + 16384 : SM_DED; }
__device__ __forceinline__ uint32_t cv_in(int i) { return (i & 2 ? SLOT : SM_CV) + (i & 1) * 8192; }
__device__ __forceinline__ uint32_t cv_taps(int i) { return (i & 2 ? SM_ST1 + 24576 : SM_CV + 16384) + (i & 1) * CV_K; }
constexpr int bar_at(int i) { return SM_BAR + 8 * i; }
constexpr int B_FULL = bar_at(0)  , B_KFULL = bar_at(5)  , B_UFULL = bar_at(9)  , B_KVDONE = bar_at(13), B_STORED = bar_at(14)  ,
              B_XFULL = bar_at(16)  , B_XY = bar_at(18), B_MISC = bar_at(19),
              B_EMPTY = bar_at(20)  , B_XRDY = bar_at(25),
              B_SFREE = bar_at(26)  , B_PDONE = bar_at(28),
              B_CEMPTY = bar_at(29)  , B_STG = bar_at(33)  ,
              B_G1DONE = bar_at(37), B_DONE = bar_at(38);
constexpr int C_H = 0, C_KV = 1, C_U = 2  , C_Y = 4, C_SYNC = 5, C_EPOCH = 6, C_COUNT = 7;
constexpr uint32_t EPOCH = 128 * 33;

struct Scratch {
  uint32_t cnt[C_COUNT * 32];
  alignas(1024) uint4 stats[S_];
  alignas(1024) __nv_bfloat16 h[S_ * D_];
  alignas(1024) __nv_bfloat16 ub[D_ * 4096];
  alignas(1024) __nv_bfloat16 y[D_ * S_];
  alignas(1024) __nv_bfloat16 u[D_ * F_];
};
__device__ Scratch g_scratch;

struct Hot {
  const __nv_bfloat16 *x, *shift_k, *ssm_k, *ssm_D, *b1;
  Scratch* S;
};
struct Role {
  int8_t fg;
  int8_t at;
  int8_t sg;
  int8_t dk, ds;
  int8_t ncv;
  int16_t ch;
};
struct Params {
  const __nv_bfloat16* b2;
  __nv_bfloat16* out;
  Role role[132];
  CUtensorMap m_w1, m_w1l, m_ust, m_w2, m_uld, m_x, m_y, m_k, m_v, m_ub;
};

#define TLREC(i) do { } while (0)
#define TLEND() do { } while (0)

__device__ __forceinline__ uint32_t smem_u32(const void* p) { return (uint32_t)__cvta_generic_to_shared(p); }
__device__ __forceinline__ void mbar_init(uint32_t bar, uint32_t cnt) { asm volatile("mbarrier.init.shared::cta.b64 [%0], %1;" :: "r"(bar), "r"(cnt) : "memory"); }
__device__ __forceinline__ void mbar_expect_tx(uint32_t bar, uint32_t bytes) { asm volatile("mbarrier.arrive.expect_tx.shared::cta.b64 _, [%0], %1;" :: "r"(bar), "r"(bytes) : "memory"); }
__device__ __forceinline__ void mbar_arrive(uint32_t bar) { asm volatile("mbarrier.arrive.shared::cta.b64 _, [%0];" :: "r"(bar) : "memory"); }
__device__ __forceinline__ uint32_t mapa(uint32_t addr, uint32_t cta) { uint32_t r; asm volatile("mapa.shared::cluster.u32 %0, %1, %2;" : "=r"(r) : "r"(addr), "r"(cta)); return r; }
__device__ __forceinline__ void mbar_arrive_remote(uint32_t rbar) { asm volatile("mbarrier.arrive.shared::cluster.b64 _, [%0];" :: "r"(rbar) : "memory"); }
__device__ __forceinline__ uint32_t clk() { uint32_t c; asm volatile("mov.u32 %0, %%clock;" : "=r"(c)); return c; }
__device__ __forceinline__ bool elect_one() {
  uint32_t p; asm volatile("{ .reg .pred p; elect.sync _|p, 0xffffffff; selp.u32 %0, 1, 0, p; }" : "=r"(p)); return p;
}
__device__ __forceinline__ void guard(uint32_t t0) { if ((int32_t)(clk() - t0) < 0) __trap(); }
__device__ __forceinline__ void mbar_wait(uint32_t bar, uint32_t parity) {
  asm volatile("{\n .reg .pred p;\n W_%=:\n mbarrier.try_wait.parity.shared::cta.b64 p, [%0], %1;\n @!p bra W_%=;\n }" :: "r"(bar), "r"(parity) : "memory");
}
__device__ __forceinline__ void mbar_wait_cluster(uint32_t bar, uint32_t parity) {
  asm volatile("{\n .reg .pred p;\n W_%=:\n mbarrier.try_wait.parity.acquire.cluster.shared::cta.b64 p, [%0], %1;\n @!p bra W_%=;\n }" :: "r"(bar), "r"(parity) : "memory");
}
__device__ __forceinline__ bool mbar_try(uint32_t bar, uint32_t parity) {
  uint32_t ok;
  asm volatile("{ .reg .pred p; mbarrier.try_wait.parity.shared::cta.b64 p, [%1], %2, 100000; selp.u32 %0, 1, 0, p; }" : "=r"(ok) : "r"(bar), "r"(parity) : "memory");
  return ok;
}
__device__ __forceinline__ bool mbar_test(uint32_t bar, uint32_t parity) {
  uint32_t ok;
  asm volatile("{ .reg .pred p; mbarrier.test_wait.parity.shared::cta.b64 p, [%1], %2; selp.u32 %0, 1, 0, p; }" : "=r"(ok) : "r"(bar), "r"(parity) : "memory");
  return ok;
}
__device__ __forceinline__ void mbar_wait_guarded(uint32_t bar, uint32_t t0, uint32_t parity = 0) { while (!mbar_try(bar, parity)) guard(t0); }
__device__ __forceinline__ void tma2d(uint32_t dst, const CUtensorMap* m, int c0, int c1, uint32_t bar) {
  asm volatile("cp.async.bulk.tensor.2d.shared::cluster.global.mbarrier::complete_tx::bytes [%0], [%1, {%3, %4}], [%2];"
               :: "r"(dst), "l"(m), "r"(bar), "r"(c0), "r"(c1) : "memory");
}
__device__ __forceinline__ void tma3d(uint32_t dst, const CUtensorMap* m, int c0, int c1, int c2, uint32_t bar) {
  asm volatile("cp.async.bulk.tensor.3d.shared::cluster.global.mbarrier::complete_tx::bytes [%0], [%1, {%3, %4, %5}], [%2];"
               :: "r"(dst), "l"(m), "r"(bar), "r"(c0), "r"(c1), "r"(c2) : "memory");
}
__device__ __forceinline__ void tma2d_store(const CUtensorMap* m, uint32_t src, int c0, int c1) {
  asm volatile("cp.async.bulk.tensor.2d.global.shared::cta.bulk_group [%0, {%2, %3}], [%1];" :: "l"(m), "r"(src), "r"(c0), "r"(c1) : "memory");
}
__device__ __forceinline__ void bulk_load(uint32_t dst, const void* src, uint32_t bytes, uint32_t bar) {
  asm volatile("cp.async.bulk.shared::cluster.global.mbarrier::complete_tx::bytes [%0], [%1], %2, [%3];" :: "r"(dst), "l"(src), "r"(bytes), "r"(bar) : "memory");
}
__device__ __forceinline__ void tma3d_store(const CUtensorMap* m, uint32_t src, int c0, int c1, int c2) {
  asm volatile("cp.async.bulk.tensor.3d.global.shared::cta.bulk_group [%0, {%2, %3, %4}], [%1];" :: "l"(m), "r"(src), "r"(c0), "r"(c1), "r"(c2) : "memory");
}
__device__ __forceinline__ void bulk_commit() { asm volatile("cp.async.bulk.commit_group;" ::: "memory"); }
__device__ __forceinline__ void bulk_wait_all() { asm volatile("cp.async.bulk.wait_group 0;" ::: "memory"); }
__device__ __forceinline__ void fence_async_smem() { asm volatile("fence.proxy.async.shared::cta;" ::: "memory"); }
__device__ __forceinline__ void fence_async_global() { asm volatile("fence.proxy.async.global;" ::: "memory"); }
__device__ __forceinline__ uint32_t ld_cnt(Scratch* S, int c) { uint32_t v; asm volatile("ld.relaxed.gpu.global.u32 %0, [%1];" : "=r"(v) : "l"(S->cnt + c * 32) : "memory"); return v; }
__device__ __forceinline__ void signal(Scratch* S, int c, uint32_t inc) { asm volatile("red.release.gpu.global.add.u32 [%0], %1;" :: "l"(S->cnt + c * 32), "r"(inc) : "memory"); }
__device__ __forceinline__ bool reached(Scratch* S, int c, uint32_t ep) { return ld_cnt(S, c) - ep >= EPOCH; }
__device__ __forceinline__ void await(Scratch* S, int c, uint32_t ep) { while (!reached(S, c, ep)) { } }
__device__ __forceinline__ void bar_sync(int id, int n) { asm volatile("bar.sync %0, %1;" :: "r"(id), "r"(n) : "memory"); }
__device__ __forceinline__ void bar_arrive(int id, int n) { asm volatile("bar.arrive %0, %1;" :: "r"(id), "r"(n) : "memory"); }
__device__ __forceinline__ void wg_fence() { asm volatile("wgmma.fence.sync.aligned;" ::: "memory"); }
__device__ __forceinline__ void wg_commit() { asm volatile("wgmma.commit_group.sync.aligned;" ::: "memory"); }
template <int N> __device__ __forceinline__ void wg_wait() { asm volatile("wgmma.wait_group.sync.aligned %0;" :: "n"(N) : "memory"); }
template <int N> __device__ __forceinline__ void pin_regs(float* a) {
#pragma unroll
  for (int i = 0; i < N; i++) asm volatile("" : "+f"(a[i]) :: "memory");
}
__device__ __forceinline__ uint64_t make_desc(uint32_t addr, uint32_t lbo, uint32_t sbo, uint32_t swz) {
  return (uint64_t)((addr & 0x3FFFF) >> 4) | ((uint64_t)(lbo >> 4) << 16) | ((uint64_t)(sbo >> 4) << 32) | ((uint64_t)swz << 62);
}
__device__ __forceinline__ uint32_t pack_bf16(float lo, float hi) { uint32_t r; asm("cvt.rn.bf16x2.f32 %0, %1, %2;" : "=r"(r) : "f"(hi), "f"(lo)); return r; }
__device__ __forceinline__ float bf_lo(uint32_t p) { return __uint_as_float(p << 16); }
__device__ __forceinline__ float bf_hi(uint32_t p) { return __uint_as_float(p & 0xffff0000u); }
__device__ __forceinline__ float round_bf16(float v) { return bf_lo(pack_bf16(v, 0.f)); }
__device__ __forceinline__ uint32_t bmul2(uint32_t a, uint32_t b) { uint32_t r; asm("mul.rn.bf16x2 %0, %1, %2;" : "=r"(r) : "r"(a), "r"(b)); return r; }
__device__ __forceinline__ uint32_t badd2(uint32_t a, uint32_t b) { uint32_t r; asm("add.rn.bf16x2 %0, %1, %2;" : "=r"(r) : "r"(a), "r"(b)); return r; }
__device__ __forceinline__ uint32_t bfma2(uint32_t a, uint32_t b, uint32_t c) { uint32_t r; asm("fma.rn.bf16x2 %0, %1, %2, %3;" : "=r"(r) : "r"(a), "r"(b), "r"(c)); return r; }
__device__ __forceinline__ uint32_t bsub2(uint32_t a, uint32_t b) { uint32_t r; asm("sub.rn.bf16x2 %0, %1, %2;" : "=r"(r) : "r"(a), "r"(b)); return r; }
__device__ __forceinline__ float tanh_fast(float v) { float r; asm("tanh.approx.f32 %0, %1;" : "=f"(r) : "f"(v)); return r; }
__device__ __forceinline__ float gelu_half(float h) {
  return fmaf(h, tanh_fast(h * fmaf(h * h, 8.0f * 0.7978845608028654f * 0.044715f, 2.0f * 0.7978845608028654f)), h);
}
__device__ __forceinline__ float silu_half(float h) { return fmaf(h, tanh_fast(h), h); }
__device__ __forceinline__ uint32_t ldg32(const void* p) { uint32_t v; asm volatile("ld.global.u32 %0, [%1];" : "=r"(v) : "l"(p) : "memory"); return v; }
__device__ __forceinline__ uint32_t lds32(uint32_t a) { uint32_t v; asm volatile("ld.shared.u32 %0, [%1];" : "=r"(v) : "r"(a) : "memory"); return v; }
__device__ __forceinline__ uint32_t lds16(uint32_t a) { uint32_t v; asm volatile("ld.shared.u16 %0, [%1];" : "=r"(v) : "r"(a) : "memory"); return v; }
__device__ __forceinline__ uint4 lds128(uint32_t a) { uint4 v; asm volatile("ld.shared.v4.u32 {%0,%1,%2,%3}, [%4];" : "=r"(v.x), "=r"(v.y), "=r"(v.z), "=r"(v.w) : "r"(a) : "memory"); return v; }
__device__ __forceinline__ void sts128(uint32_t a, uint32_t x, uint32_t y, uint32_t z, uint32_t w) {
  asm volatile("st.shared.v4.u32 [%0], {%1,%2,%3,%4};" :: "r"(a), "r"(x), "r"(y), "r"(z), "r"(w) : "memory");
}
__device__ __forceinline__ void sts32(uint32_t a, uint32_t v) { asm volatile("st.shared.u32 [%0], %1;" :: "r"(a), "r"(v) : "memory"); }
__device__ __forceinline__ void ldsm4(uint32_t* r, uint32_t a) {
  asm volatile("ldmatrix.sync.aligned.m8n8.x4.shared.b16 {%0,%1,%2,%3}, [%4];" : "=r"(r[0]), "=r"(r[1]), "=r"(r[2]), "=r"(r[3]) : "r"(a) : "memory");
}
__device__ __forceinline__ void ldsm2(uint32_t* r, uint32_t a) {
  asm volatile("ldmatrix.sync.aligned.m8n8.x2.shared.b16 {%0,%1}, [%2];" : "=r"(r[0]), "=r"(r[1]) : "r"(a) : "memory");
}
__device__ __forceinline__ void ldsm4t(uint32_t* r, uint32_t a) {
  asm volatile("ldmatrix.sync.aligned.m8n8.x4.trans.shared.b16 {%0,%1,%2,%3}, [%4];" : "=r"(r[0]), "=r"(r[1]), "=r"(r[2]), "=r"(r[3]) : "r"(a) : "memory");
}
__device__ __forceinline__ void ldsm2t(uint32_t* r, uint32_t a) {
  asm volatile("ldmatrix.sync.aligned.m8n8.x2.trans.shared.b16 {%0,%1}, [%2];" : "=r"(r[0]), "=r"(r[1]) : "r"(a) : "memory");
}
__device__ __forceinline__ void stsm4(uint32_t a, uint32_t r0, uint32_t r1, uint32_t r2, uint32_t r3) {
  asm volatile("stmatrix.sync.aligned.m8n8.x4.shared.b16 [%0], {%1,%2,%3,%4};" :: "r"(a), "r"(r0), "r"(r1), "r"(r2), "r"(r3) : "memory");
}
__device__ __forceinline__ void stsm2(uint32_t a, uint32_t r0, uint32_t r1) {
  asm volatile("stmatrix.sync.aligned.m8n8.x2.shared.b16 [%0], {%1,%2};" :: "r"(a), "r"(r0), "r"(r1) : "memory");
}
__device__ __forceinline__ void stsm4t(uint32_t a, uint32_t r0, uint32_t r1, uint32_t r2, uint32_t r3) {
  asm volatile("stmatrix.sync.aligned.m8n8.x4.trans.shared.b16 [%0], {%1,%2,%3,%4};" :: "r"(a), "r"(r0), "r"(r1), "r"(r2), "r"(r3) : "memory");
}

__device__ __forceinline__ void wgmma_ss_n144_t10(float* d, uint64_t da, uint64_t db, int sd) {
  asm volatile("{ .reg .pred p; setp.ne.b32 p, %74, 0;\n"
      "wgmma.mma_async.sync.aligned.m64n144k16.f32.bf16.bf16 {"
      "%0,%1,%2,%3,%4,%5,%6,%7,%8,%9,%10,%11,%12,%13,%14,%15,"
      "%16,%17,%18,%19,%20,%21,%22,%23,%24,%25,%26,%27,%28,%29,%30,%31,"
      "%32,%33,%34,%35,%36,%37,%38,%39,%40,%41,%42,%43,%44,%45,%46,%47,"
      "%48,%49,%50,%51,%52,%53,%54,%55,%56,%57,%58,%59,%60,%61,%62,%63,"
      "%64,%65,%66,%67,%68,%69,%70,%71"
      "}, %72, %73, p, 1, 1, 1, 0; }"
    : "+f"(d[0]), "+f"(d[1]), "+f"(d[2]), "+f"(d[3]), "+f"(d[4]), "+f"(d[5]), "+f"(d[6]), "+f"(d[7]),
      "+f"(d[8]), "+f"(d[9]), "+f"(d[10]), "+f"(d[11]), "+f"(d[12]), "+f"(d[13]), "+f"(d[14]), "+f"(d[15]),
      "+f"(d[16]), "+f"(d[17]), "+f"(d[18]), "+f"(d[19]), "+f"(d[20]), "+f"(d[21]), "+f"(d[22]), "+f"(d[23]),
      "+f"(d[24]), "+f"(d[25]), "+f"(d[26]), "+f"(d[27]), "+f"(d[28]), "+f"(d[29]), "+f"(d[30]), "+f"(d[31]),
      "+f"(d[32]), "+f"(d[33]), "+f"(d[34]), "+f"(d[35]), "+f"(d[36]), "+f"(d[37]), "+f"(d[38]), "+f"(d[39]),
      "+f"(d[40]), "+f"(d[41]), "+f"(d[42]), "+f"(d[43]), "+f"(d[44]), "+f"(d[45]), "+f"(d[46]), "+f"(d[47]),
      "+f"(d[48]), "+f"(d[49]), "+f"(d[50]), "+f"(d[51]), "+f"(d[52]), "+f"(d[53]), "+f"(d[54]), "+f"(d[55]),
      "+f"(d[56]), "+f"(d[57]), "+f"(d[58]), "+f"(d[59]), "+f"(d[60]), "+f"(d[61]), "+f"(d[62]), "+f"(d[63]),
      "+f"(d[64]), "+f"(d[65]), "+f"(d[66]), "+f"(d[67]), "+f"(d[68]), "+f"(d[69]), "+f"(d[70]), "+f"(d[71])
    : "l"(da), "l"(db), "r"(sd));
}

__device__ __forceinline__ void wgmma_ss_n160_t11(float* d, uint64_t da, uint64_t db, int sd) {
  asm volatile("{ .reg .pred p; setp.ne.b32 p, %82, 0;\n"
      "wgmma.mma_async.sync.aligned.m64n160k16.f32.bf16.bf16 {"
      "%0,%1,%2,%3,%4,%5,%6,%7,%8,%9,%10,%11,%12,%13,%14,%15,"
      "%16,%17,%18,%19,%20,%21,%22,%23,%24,%25,%26,%27,%28,%29,%30,%31,"
      "%32,%33,%34,%35,%36,%37,%38,%39,%40,%41,%42,%43,%44,%45,%46,%47,"
      "%48,%49,%50,%51,%52,%53,%54,%55,%56,%57,%58,%59,%60,%61,%62,%63,"
      "%64,%65,%66,%67,%68,%69,%70,%71,%72,%73,%74,%75,%76,%77,%78,%79"
      "}, %80, %81, p, 1, 1, 1, 1; }"
    : "+f"(d[0]), "+f"(d[1]), "+f"(d[2]), "+f"(d[3]), "+f"(d[4]), "+f"(d[5]), "+f"(d[6]), "+f"(d[7]),
      "+f"(d[8]), "+f"(d[9]), "+f"(d[10]), "+f"(d[11]), "+f"(d[12]), "+f"(d[13]), "+f"(d[14]), "+f"(d[15]),
      "+f"(d[16]), "+f"(d[17]), "+f"(d[18]), "+f"(d[19]), "+f"(d[20]), "+f"(d[21]), "+f"(d[22]), "+f"(d[23]),
      "+f"(d[24]), "+f"(d[25]), "+f"(d[26]), "+f"(d[27]), "+f"(d[28]), "+f"(d[29]), "+f"(d[30]), "+f"(d[31]),
      "+f"(d[32]), "+f"(d[33]), "+f"(d[34]), "+f"(d[35]), "+f"(d[36]), "+f"(d[37]), "+f"(d[38]), "+f"(d[39]),
      "+f"(d[40]), "+f"(d[41]), "+f"(d[42]), "+f"(d[43]), "+f"(d[44]), "+f"(d[45]), "+f"(d[46]), "+f"(d[47]),
      "+f"(d[48]), "+f"(d[49]), "+f"(d[50]), "+f"(d[51]), "+f"(d[52]), "+f"(d[53]), "+f"(d[54]), "+f"(d[55]),
      "+f"(d[56]), "+f"(d[57]), "+f"(d[58]), "+f"(d[59]), "+f"(d[60]), "+f"(d[61]), "+f"(d[62]), "+f"(d[63]),
      "+f"(d[64]), "+f"(d[65]), "+f"(d[66]), "+f"(d[67]), "+f"(d[68]), "+f"(d[69]), "+f"(d[70]), "+f"(d[71]),
      "+f"(d[72]), "+f"(d[73]), "+f"(d[74]), "+f"(d[75]), "+f"(d[76]), "+f"(d[77]), "+f"(d[78]), "+f"(d[79])
    : "l"(da), "l"(db), "r"(sd));
}

__device__ __forceinline__ void wgmma_ss_n96_t11(float* d, uint64_t da, uint64_t db, int sd) {
  asm volatile("{ .reg .pred p; setp.ne.b32 p, %50, 0;\n"
      "wgmma.mma_async.sync.aligned.m64n96k16.f32.bf16.bf16 {"
      "%0,%1,%2,%3,%4,%5,%6,%7,%8,%9,%10,%11,%12,%13,%14,%15,"
      "%16,%17,%18,%19,%20,%21,%22,%23,%24,%25,%26,%27,%28,%29,%30,%31,"
      "%32,%33,%34,%35,%36,%37,%38,%39,%40,%41,%42,%43,%44,%45,%46,%47"
      "}, %48, %49, p, 1, 1, 1, 1; }"
    : "+f"(d[0]), "+f"(d[1]), "+f"(d[2]), "+f"(d[3]), "+f"(d[4]), "+f"(d[5]), "+f"(d[6]), "+f"(d[7]),
      "+f"(d[8]), "+f"(d[9]), "+f"(d[10]), "+f"(d[11]), "+f"(d[12]), "+f"(d[13]), "+f"(d[14]), "+f"(d[15]),
      "+f"(d[16]), "+f"(d[17]), "+f"(d[18]), "+f"(d[19]), "+f"(d[20]), "+f"(d[21]), "+f"(d[22]), "+f"(d[23]),
      "+f"(d[24]), "+f"(d[25]), "+f"(d[26]), "+f"(d[27]), "+f"(d[28]), "+f"(d[29]), "+f"(d[30]), "+f"(d[31]),
      "+f"(d[32]), "+f"(d[33]), "+f"(d[34]), "+f"(d[35]), "+f"(d[36]), "+f"(d[37]), "+f"(d[38]), "+f"(d[39]),
      "+f"(d[40]), "+f"(d[41]), "+f"(d[42]), "+f"(d[43]), "+f"(d[44]), "+f"(d[45]), "+f"(d[46]), "+f"(d[47])
    : "l"(da), "l"(db), "r"(sd));
}

__device__ __forceinline__ void wgmma_rs_n16(float* d, const uint32_t* a, uint64_t db, int sd) {
  asm volatile("{ .reg .pred p; setp.ne.b32 p, %13, 0;\n"
      "wgmma.mma_async.sync.aligned.m64n16k16.f32.bf16.bf16 {"
      "%0,%1,%2,%3,%4,%5,%6,%7"
      "}, {%8,%9,%10,%11}, %12, p, 1, 1, 0; }"
    : "+f"(d[0]), "+f"(d[1]), "+f"(d[2]), "+f"(d[3]), "+f"(d[4]), "+f"(d[5]), "+f"(d[6]), "+f"(d[7])
    : "r"(a[0]), "r"(a[1]), "r"(a[2]), "r"(a[3]), "l"(db), "r"(sd));
}

__device__ __forceinline__ void wgmma_rs_n32(float* d, const uint32_t* a, uint64_t db, int sd) {
  asm volatile("{ .reg .pred p; setp.ne.b32 p, %21, 0;\n"
      "wgmma.mma_async.sync.aligned.m64n32k16.f32.bf16.bf16 {"
      "%0,%1,%2,%3,%4,%5,%6,%7,%8,%9,%10,%11,%12,%13,%14,%15"
      "}, {%16,%17,%18,%19}, %20, p, 1, 1, 0; }"
    : "+f"(d[0]), "+f"(d[1]), "+f"(d[2]), "+f"(d[3]), "+f"(d[4]), "+f"(d[5]), "+f"(d[6]), "+f"(d[7]),
      "+f"(d[8]), "+f"(d[9]), "+f"(d[10]), "+f"(d[11]), "+f"(d[12]), "+f"(d[13]), "+f"(d[14]), "+f"(d[15])
    : "r"(a[0]), "r"(a[1]), "r"(a[2]), "r"(a[3]), "l"(db), "r"(sd));
}

__device__ __forceinline__ void wgmma_rs_n48(float* d, const uint32_t* a, uint64_t db, int sd) {
  asm volatile("{ .reg .pred p; setp.ne.b32 p, %29, 0;\n"
      "wgmma.mma_async.sync.aligned.m64n48k16.f32.bf16.bf16 {"
      "%0,%1,%2,%3,%4,%5,%6,%7,%8,%9,%10,%11,%12,%13,%14,%15,"
      "%16,%17,%18,%19,%20,%21,%22,%23"
      "}, {%24,%25,%26,%27}, %28, p, 1, 1, 0; }"
    : "+f"(d[0]), "+f"(d[1]), "+f"(d[2]), "+f"(d[3]), "+f"(d[4]), "+f"(d[5]), "+f"(d[6]), "+f"(d[7]),
      "+f"(d[8]), "+f"(d[9]), "+f"(d[10]), "+f"(d[11]), "+f"(d[12]), "+f"(d[13]), "+f"(d[14]), "+f"(d[15]),
      "+f"(d[16]), "+f"(d[17]), "+f"(d[18]), "+f"(d[19]), "+f"(d[20]), "+f"(d[21]), "+f"(d[22]), "+f"(d[23])
    : "r"(a[0]), "r"(a[1]), "r"(a[2]), "r"(a[3]), "l"(db), "r"(sd));
}

__device__ __forceinline__ void wgmma_rs_n64(float* d, const uint32_t* a, uint64_t db, int sd) {
  asm volatile("{ .reg .pred p; setp.ne.b32 p, %37, 0;\n"
      "wgmma.mma_async.sync.aligned.m64n64k16.f32.bf16.bf16 {"
      "%0,%1,%2,%3,%4,%5,%6,%7,%8,%9,%10,%11,%12,%13,%14,%15,"
      "%16,%17,%18,%19,%20,%21,%22,%23,%24,%25,%26,%27,%28,%29,%30,%31"
      "}, {%32,%33,%34,%35}, %36, p, 1, 1, 0; }"
    : "+f"(d[0]), "+f"(d[1]), "+f"(d[2]), "+f"(d[3]), "+f"(d[4]), "+f"(d[5]), "+f"(d[6]), "+f"(d[7]),
      "+f"(d[8]), "+f"(d[9]), "+f"(d[10]), "+f"(d[11]), "+f"(d[12]), "+f"(d[13]), "+f"(d[14]), "+f"(d[15]),
      "+f"(d[16]), "+f"(d[17]), "+f"(d[18]), "+f"(d[19]), "+f"(d[20]), "+f"(d[21]), "+f"(d[22]), "+f"(d[23]),
      "+f"(d[24]), "+f"(d[25]), "+f"(d[26]), "+f"(d[27]), "+f"(d[28]), "+f"(d[29]), "+f"(d[30]), "+f"(d[31])
    : "r"(a[0]), "r"(a[1]), "r"(a[2]), "r"(a[3]), "l"(db), "r"(sd));
}

__device__ __forceinline__ void wgmma_rs_n80(float* d, const uint32_t* a, uint64_t db, int sd) {
  asm volatile("{ .reg .pred p; setp.ne.b32 p, %45, 0;\n"
      "wgmma.mma_async.sync.aligned.m64n80k16.f32.bf16.bf16 {"
      "%0,%1,%2,%3,%4,%5,%6,%7,%8,%9,%10,%11,%12,%13,%14,%15,"
      "%16,%17,%18,%19,%20,%21,%22,%23,%24,%25,%26,%27,%28,%29,%30,%31,"
      "%32,%33,%34,%35,%36,%37,%38,%39"
      "}, {%40,%41,%42,%43}, %44, p, 1, 1, 0; }"
    : "+f"(d[0]), "+f"(d[1]), "+f"(d[2]), "+f"(d[3]), "+f"(d[4]), "+f"(d[5]), "+f"(d[6]), "+f"(d[7]),
      "+f"(d[8]), "+f"(d[9]), "+f"(d[10]), "+f"(d[11]), "+f"(d[12]), "+f"(d[13]), "+f"(d[14]), "+f"(d[15]),
      "+f"(d[16]), "+f"(d[17]), "+f"(d[18]), "+f"(d[19]), "+f"(d[20]), "+f"(d[21]), "+f"(d[22]), "+f"(d[23]),
      "+f"(d[24]), "+f"(d[25]), "+f"(d[26]), "+f"(d[27]), "+f"(d[28]), "+f"(d[29]), "+f"(d[30]), "+f"(d[31]),
      "+f"(d[32]), "+f"(d[33]), "+f"(d[34]), "+f"(d[35]), "+f"(d[36]), "+f"(d[37]), "+f"(d[38]), "+f"(d[39])
    : "r"(a[0]), "r"(a[1]), "r"(a[2]), "r"(a[3]), "l"(db), "r"(sd));
}

__device__ __forceinline__ void wgmma_rs_n96(float* d, const uint32_t* a, uint64_t db, int sd) {
  asm volatile("{ .reg .pred p; setp.ne.b32 p, %53, 0;\n"
      "wgmma.mma_async.sync.aligned.m64n96k16.f32.bf16.bf16 {"
      "%0,%1,%2,%3,%4,%5,%6,%7,%8,%9,%10,%11,%12,%13,%14,%15,"
      "%16,%17,%18,%19,%20,%21,%22,%23,%24,%25,%26,%27,%28,%29,%30,%31,"
      "%32,%33,%34,%35,%36,%37,%38,%39,%40,%41,%42,%43,%44,%45,%46,%47"
      "}, {%48,%49,%50,%51}, %52, p, 1, 1, 0; }"
    : "+f"(d[0]), "+f"(d[1]), "+f"(d[2]), "+f"(d[3]), "+f"(d[4]), "+f"(d[5]), "+f"(d[6]), "+f"(d[7]),
      "+f"(d[8]), "+f"(d[9]), "+f"(d[10]), "+f"(d[11]), "+f"(d[12]), "+f"(d[13]), "+f"(d[14]), "+f"(d[15]),
      "+f"(d[16]), "+f"(d[17]), "+f"(d[18]), "+f"(d[19]), "+f"(d[20]), "+f"(d[21]), "+f"(d[22]), "+f"(d[23]),
      "+f"(d[24]), "+f"(d[25]), "+f"(d[26]), "+f"(d[27]), "+f"(d[28]), "+f"(d[29]), "+f"(d[30]), "+f"(d[31]),
      "+f"(d[32]), "+f"(d[33]), "+f"(d[34]), "+f"(d[35]), "+f"(d[36]), "+f"(d[37]), "+f"(d[38]), "+f"(d[39]),
      "+f"(d[40]), "+f"(d[41]), "+f"(d[42]), "+f"(d[43]), "+f"(d[44]), "+f"(d[45]), "+f"(d[46]), "+f"(d[47])
    : "r"(a[0]), "r"(a[1]), "r"(a[2]), "r"(a[3]), "l"(db), "r"(sd));
}

__device__ __forceinline__ void wgmma_rs_n112(float* d, const uint32_t* a, uint64_t db, int sd) {
  asm volatile("{ .reg .pred p; setp.ne.b32 p, %61, 0;\n"
      "wgmma.mma_async.sync.aligned.m64n112k16.f32.bf16.bf16 {"
      "%0,%1,%2,%3,%4,%5,%6,%7,%8,%9,%10,%11,%12,%13,%14,%15,"
      "%16,%17,%18,%19,%20,%21,%22,%23,%24,%25,%26,%27,%28,%29,%30,%31,"
      "%32,%33,%34,%35,%36,%37,%38,%39,%40,%41,%42,%43,%44,%45,%46,%47,"
      "%48,%49,%50,%51,%52,%53,%54,%55"
      "}, {%56,%57,%58,%59}, %60, p, 1, 1, 0; }"
    : "+f"(d[0]), "+f"(d[1]), "+f"(d[2]), "+f"(d[3]), "+f"(d[4]), "+f"(d[5]), "+f"(d[6]), "+f"(d[7]),
      "+f"(d[8]), "+f"(d[9]), "+f"(d[10]), "+f"(d[11]), "+f"(d[12]), "+f"(d[13]), "+f"(d[14]), "+f"(d[15]),
      "+f"(d[16]), "+f"(d[17]), "+f"(d[18]), "+f"(d[19]), "+f"(d[20]), "+f"(d[21]), "+f"(d[22]), "+f"(d[23]),
      "+f"(d[24]), "+f"(d[25]), "+f"(d[26]), "+f"(d[27]), "+f"(d[28]), "+f"(d[29]), "+f"(d[30]), "+f"(d[31]),
      "+f"(d[32]), "+f"(d[33]), "+f"(d[34]), "+f"(d[35]), "+f"(d[36]), "+f"(d[37]), "+f"(d[38]), "+f"(d[39]),
      "+f"(d[40]), "+f"(d[41]), "+f"(d[42]), "+f"(d[43]), "+f"(d[44]), "+f"(d[45]), "+f"(d[46]), "+f"(d[47]),
      "+f"(d[48]), "+f"(d[49]), "+f"(d[50]), "+f"(d[51]), "+f"(d[52]), "+f"(d[53]), "+f"(d[54]), "+f"(d[55])
    : "r"(a[0]), "r"(a[1]), "r"(a[2]), "r"(a[3]), "l"(db), "r"(sd));
}

__device__ __forceinline__ void wgmma_rs_n128(float* d, const uint32_t* a, uint64_t db, int sd) {
  asm volatile("{ .reg .pred p; setp.ne.b32 p, %69, 0;\n"
      "wgmma.mma_async.sync.aligned.m64n128k16.f32.bf16.bf16 {"
      "%0,%1,%2,%3,%4,%5,%6,%7,%8,%9,%10,%11,%12,%13,%14,%15,"
      "%16,%17,%18,%19,%20,%21,%22,%23,%24,%25,%26,%27,%28,%29,%30,%31,"
      "%32,%33,%34,%35,%36,%37,%38,%39,%40,%41,%42,%43,%44,%45,%46,%47,"
      "%48,%49,%50,%51,%52,%53,%54,%55,%56,%57,%58,%59,%60,%61,%62,%63"
      "}, {%64,%65,%66,%67}, %68, p, 1, 1, 0; }"
    : "+f"(d[0]), "+f"(d[1]), "+f"(d[2]), "+f"(d[3]), "+f"(d[4]), "+f"(d[5]), "+f"(d[6]), "+f"(d[7]),
      "+f"(d[8]), "+f"(d[9]), "+f"(d[10]), "+f"(d[11]), "+f"(d[12]), "+f"(d[13]), "+f"(d[14]), "+f"(d[15]),
      "+f"(d[16]), "+f"(d[17]), "+f"(d[18]), "+f"(d[19]), "+f"(d[20]), "+f"(d[21]), "+f"(d[22]), "+f"(d[23]),
      "+f"(d[24]), "+f"(d[25]), "+f"(d[26]), "+f"(d[27]), "+f"(d[28]), "+f"(d[29]), "+f"(d[30]), "+f"(d[31]),
      "+f"(d[32]), "+f"(d[33]), "+f"(d[34]), "+f"(d[35]), "+f"(d[36]), "+f"(d[37]), "+f"(d[38]), "+f"(d[39]),
      "+f"(d[40]), "+f"(d[41]), "+f"(d[42]), "+f"(d[43]), "+f"(d[44]), "+f"(d[45]), "+f"(d[46]), "+f"(d[47]),
      "+f"(d[48]), "+f"(d[49]), "+f"(d[50]), "+f"(d[51]), "+f"(d[52]), "+f"(d[53]), "+f"(d[54]), "+f"(d[55]),
      "+f"(d[56]), "+f"(d[57]), "+f"(d[58]), "+f"(d[59]), "+f"(d[60]), "+f"(d[61]), "+f"(d[62]), "+f"(d[63])
    : "r"(a[0]), "r"(a[1]), "r"(a[2]), "r"(a[3]), "l"(db), "r"(sd));
}

__device__ __forceinline__ void wgmma_rs_n144(float* d, const uint32_t* a, uint64_t db, int sd) {
  asm volatile("{ .reg .pred p; setp.ne.b32 p, %77, 0;\n"
      "wgmma.mma_async.sync.aligned.m64n144k16.f32.bf16.bf16 {"
      "%0,%1,%2,%3,%4,%5,%6,%7,%8,%9,%10,%11,%12,%13,%14,%15,"
      "%16,%17,%18,%19,%20,%21,%22,%23,%24,%25,%26,%27,%28,%29,%30,%31,"
      "%32,%33,%34,%35,%36,%37,%38,%39,%40,%41,%42,%43,%44,%45,%46,%47,"
      "%48,%49,%50,%51,%52,%53,%54,%55,%56,%57,%58,%59,%60,%61,%62,%63,"
      "%64,%65,%66,%67,%68,%69,%70,%71"
      "}, {%72,%73,%74,%75}, %76, p, 1, 1, 0; }"
    : "+f"(d[0]), "+f"(d[1]), "+f"(d[2]), "+f"(d[3]), "+f"(d[4]), "+f"(d[5]), "+f"(d[6]), "+f"(d[7]),
      "+f"(d[8]), "+f"(d[9]), "+f"(d[10]), "+f"(d[11]), "+f"(d[12]), "+f"(d[13]), "+f"(d[14]), "+f"(d[15]),
      "+f"(d[16]), "+f"(d[17]), "+f"(d[18]), "+f"(d[19]), "+f"(d[20]), "+f"(d[21]), "+f"(d[22]), "+f"(d[23]),
      "+f"(d[24]), "+f"(d[25]), "+f"(d[26]), "+f"(d[27]), "+f"(d[28]), "+f"(d[29]), "+f"(d[30]), "+f"(d[31]),
      "+f"(d[32]), "+f"(d[33]), "+f"(d[34]), "+f"(d[35]), "+f"(d[36]), "+f"(d[37]), "+f"(d[38]), "+f"(d[39]),
      "+f"(d[40]), "+f"(d[41]), "+f"(d[42]), "+f"(d[43]), "+f"(d[44]), "+f"(d[45]), "+f"(d[46]), "+f"(d[47]),
      "+f"(d[48]), "+f"(d[49]), "+f"(d[50]), "+f"(d[51]), "+f"(d[52]), "+f"(d[53]), "+f"(d[54]), "+f"(d[55]),
      "+f"(d[56]), "+f"(d[57]), "+f"(d[58]), "+f"(d[59]), "+f"(d[60]), "+f"(d[61]), "+f"(d[62]), "+f"(d[63]),
      "+f"(d[64]), "+f"(d[65]), "+f"(d[66]), "+f"(d[67]), "+f"(d[68]), "+f"(d[69]), "+f"(d[70]), "+f"(d[71])
    : "r"(a[0]), "r"(a[1]), "r"(a[2]), "r"(a[3]), "l"(db), "r"(sd));
}

__device__ __forceinline__ void wgmma_rs_n160(float* d, const uint32_t* a, uint64_t db, int sd) {
  asm volatile("{ .reg .pred p; setp.ne.b32 p, %85, 0;\n"
      "wgmma.mma_async.sync.aligned.m64n160k16.f32.bf16.bf16 {"
      "%0,%1,%2,%3,%4,%5,%6,%7,%8,%9,%10,%11,%12,%13,%14,%15,"
      "%16,%17,%18,%19,%20,%21,%22,%23,%24,%25,%26,%27,%28,%29,%30,%31,"
      "%32,%33,%34,%35,%36,%37,%38,%39,%40,%41,%42,%43,%44,%45,%46,%47,"
      "%48,%49,%50,%51,%52,%53,%54,%55,%56,%57,%58,%59,%60,%61,%62,%63,"
      "%64,%65,%66,%67,%68,%69,%70,%71,%72,%73,%74,%75,%76,%77,%78,%79"
      "}, {%80,%81,%82,%83}, %84, p, 1, 1, 0; }"
    : "+f"(d[0]), "+f"(d[1]), "+f"(d[2]), "+f"(d[3]), "+f"(d[4]), "+f"(d[5]), "+f"(d[6]), "+f"(d[7]),
      "+f"(d[8]), "+f"(d[9]), "+f"(d[10]), "+f"(d[11]), "+f"(d[12]), "+f"(d[13]), "+f"(d[14]), "+f"(d[15]),
      "+f"(d[16]), "+f"(d[17]), "+f"(d[18]), "+f"(d[19]), "+f"(d[20]), "+f"(d[21]), "+f"(d[22]), "+f"(d[23]),
      "+f"(d[24]), "+f"(d[25]), "+f"(d[26]), "+f"(d[27]), "+f"(d[28]), "+f"(d[29]), "+f"(d[30]), "+f"(d[31]),
      "+f"(d[32]), "+f"(d[33]), "+f"(d[34]), "+f"(d[35]), "+f"(d[36]), "+f"(d[37]), "+f"(d[38]), "+f"(d[39]),
      "+f"(d[40]), "+f"(d[41]), "+f"(d[42]), "+f"(d[43]), "+f"(d[44]), "+f"(d[45]), "+f"(d[46]), "+f"(d[47]),
      "+f"(d[48]), "+f"(d[49]), "+f"(d[50]), "+f"(d[51]), "+f"(d[52]), "+f"(d[53]), "+f"(d[54]), "+f"(d[55]),
      "+f"(d[56]), "+f"(d[57]), "+f"(d[58]), "+f"(d[59]), "+f"(d[60]), "+f"(d[61]), "+f"(d[62]), "+f"(d[63]),
      "+f"(d[64]), "+f"(d[65]), "+f"(d[66]), "+f"(d[67]), "+f"(d[68]), "+f"(d[69]), "+f"(d[70]), "+f"(d[71]),
      "+f"(d[72]), "+f"(d[73]), "+f"(d[74]), "+f"(d[75]), "+f"(d[76]), "+f"(d[77]), "+f"(d[78]), "+f"(d[79])
    : "r"(a[0]), "r"(a[1]), "r"(a[2]), "r"(a[3]), "l"(db), "r"(sd));
}

__device__ __forceinline__ void wgmma_rs_n176(float* d, const uint32_t* a, uint64_t db, int sd) {
  asm volatile("{ .reg .pred p; setp.ne.b32 p, %93, 0;\n"
      "wgmma.mma_async.sync.aligned.m64n176k16.f32.bf16.bf16 {"
      "%0,%1,%2,%3,%4,%5,%6,%7,%8,%9,%10,%11,%12,%13,%14,%15,"
      "%16,%17,%18,%19,%20,%21,%22,%23,%24,%25,%26,%27,%28,%29,%30,%31,"
      "%32,%33,%34,%35,%36,%37,%38,%39,%40,%41,%42,%43,%44,%45,%46,%47,"
      "%48,%49,%50,%51,%52,%53,%54,%55,%56,%57,%58,%59,%60,%61,%62,%63,"
      "%64,%65,%66,%67,%68,%69,%70,%71,%72,%73,%74,%75,%76,%77,%78,%79,"
      "%80,%81,%82,%83,%84,%85,%86,%87"
      "}, {%88,%89,%90,%91}, %92, p, 1, 1, 0; }"
    : "+f"(d[0]), "+f"(d[1]), "+f"(d[2]), "+f"(d[3]), "+f"(d[4]), "+f"(d[5]), "+f"(d[6]), "+f"(d[7]),
      "+f"(d[8]), "+f"(d[9]), "+f"(d[10]), "+f"(d[11]), "+f"(d[12]), "+f"(d[13]), "+f"(d[14]), "+f"(d[15]),
      "+f"(d[16]), "+f"(d[17]), "+f"(d[18]), "+f"(d[19]), "+f"(d[20]), "+f"(d[21]), "+f"(d[22]), "+f"(d[23]),
      "+f"(d[24]), "+f"(d[25]), "+f"(d[26]), "+f"(d[27]), "+f"(d[28]), "+f"(d[29]), "+f"(d[30]), "+f"(d[31]),
      "+f"(d[32]), "+f"(d[33]), "+f"(d[34]), "+f"(d[35]), "+f"(d[36]), "+f"(d[37]), "+f"(d[38]), "+f"(d[39]),
      "+f"(d[40]), "+f"(d[41]), "+f"(d[42]), "+f"(d[43]), "+f"(d[44]), "+f"(d[45]), "+f"(d[46]), "+f"(d[47]),
      "+f"(d[48]), "+f"(d[49]), "+f"(d[50]), "+f"(d[51]), "+f"(d[52]), "+f"(d[53]), "+f"(d[54]), "+f"(d[55]),
      "+f"(d[56]), "+f"(d[57]), "+f"(d[58]), "+f"(d[59]), "+f"(d[60]), "+f"(d[61]), "+f"(d[62]), "+f"(d[63]),
      "+f"(d[64]), "+f"(d[65]), "+f"(d[66]), "+f"(d[67]), "+f"(d[68]), "+f"(d[69]), "+f"(d[70]), "+f"(d[71]),
      "+f"(d[72]), "+f"(d[73]), "+f"(d[74]), "+f"(d[75]), "+f"(d[76]), "+f"(d[77]), "+f"(d[78]), "+f"(d[79]),
      "+f"(d[80]), "+f"(d[81]), "+f"(d[82]), "+f"(d[83]), "+f"(d[84]), "+f"(d[85]), "+f"(d[86]), "+f"(d[87])
    : "r"(a[0]), "r"(a[1]), "r"(a[2]), "r"(a[3]), "l"(db), "r"(sd));
}

__device__ __forceinline__ void wgmma_rs_n192(float* d, const uint32_t* a, uint64_t db, int sd) {
  asm volatile("{ .reg .pred p; setp.ne.b32 p, %101, 0;\n"
      "wgmma.mma_async.sync.aligned.m64n192k16.f32.bf16.bf16 {"
      "%0,%1,%2,%3,%4,%5,%6,%7,%8,%9,%10,%11,%12,%13,%14,%15,"
      "%16,%17,%18,%19,%20,%21,%22,%23,%24,%25,%26,%27,%28,%29,%30,%31,"
      "%32,%33,%34,%35,%36,%37,%38,%39,%40,%41,%42,%43,%44,%45,%46,%47,"
      "%48,%49,%50,%51,%52,%53,%54,%55,%56,%57,%58,%59,%60,%61,%62,%63,"
      "%64,%65,%66,%67,%68,%69,%70,%71,%72,%73,%74,%75,%76,%77,%78,%79,"
      "%80,%81,%82,%83,%84,%85,%86,%87,%88,%89,%90,%91,%92,%93,%94,%95"
      "}, {%96,%97,%98,%99}, %100, p, 1, 1, 0; }"
    : "+f"(d[0]), "+f"(d[1]), "+f"(d[2]), "+f"(d[3]), "+f"(d[4]), "+f"(d[5]), "+f"(d[6]), "+f"(d[7]),
      "+f"(d[8]), "+f"(d[9]), "+f"(d[10]), "+f"(d[11]), "+f"(d[12]), "+f"(d[13]), "+f"(d[14]), "+f"(d[15]),
      "+f"(d[16]), "+f"(d[17]), "+f"(d[18]), "+f"(d[19]), "+f"(d[20]), "+f"(d[21]), "+f"(d[22]), "+f"(d[23]),
      "+f"(d[24]), "+f"(d[25]), "+f"(d[26]), "+f"(d[27]), "+f"(d[28]), "+f"(d[29]), "+f"(d[30]), "+f"(d[31]),
      "+f"(d[32]), "+f"(d[33]), "+f"(d[34]), "+f"(d[35]), "+f"(d[36]), "+f"(d[37]), "+f"(d[38]), "+f"(d[39]),
      "+f"(d[40]), "+f"(d[41]), "+f"(d[42]), "+f"(d[43]), "+f"(d[44]), "+f"(d[45]), "+f"(d[46]), "+f"(d[47]),
      "+f"(d[48]), "+f"(d[49]), "+f"(d[50]), "+f"(d[51]), "+f"(d[52]), "+f"(d[53]), "+f"(d[54]), "+f"(d[55]),
      "+f"(d[56]), "+f"(d[57]), "+f"(d[58]), "+f"(d[59]), "+f"(d[60]), "+f"(d[61]), "+f"(d[62]), "+f"(d[63]),
      "+f"(d[64]), "+f"(d[65]), "+f"(d[66]), "+f"(d[67]), "+f"(d[68]), "+f"(d[69]), "+f"(d[70]), "+f"(d[71]),
      "+f"(d[72]), "+f"(d[73]), "+f"(d[74]), "+f"(d[75]), "+f"(d[76]), "+f"(d[77]), "+f"(d[78]), "+f"(d[79]),
      "+f"(d[80]), "+f"(d[81]), "+f"(d[82]), "+f"(d[83]), "+f"(d[84]), "+f"(d[85]), "+f"(d[86]), "+f"(d[87]),
      "+f"(d[88]), "+f"(d[89]), "+f"(d[90]), "+f"(d[91]), "+f"(d[92]), "+f"(d[93]), "+f"(d[94]), "+f"(d[95])
    : "r"(a[0]), "r"(a[1]), "r"(a[2]), "r"(a[3]), "l"(db), "r"(sd));
}

__device__ __forceinline__ void wgmma_rs_n208(float* d, const uint32_t* a, uint64_t db, int sd) {
  asm volatile("{ .reg .pred p; setp.ne.b32 p, %109, 0;\n"
      "wgmma.mma_async.sync.aligned.m64n208k16.f32.bf16.bf16 {"
      "%0,%1,%2,%3,%4,%5,%6,%7,%8,%9,%10,%11,%12,%13,%14,%15,"
      "%16,%17,%18,%19,%20,%21,%22,%23,%24,%25,%26,%27,%28,%29,%30,%31,"
      "%32,%33,%34,%35,%36,%37,%38,%39,%40,%41,%42,%43,%44,%45,%46,%47,"
      "%48,%49,%50,%51,%52,%53,%54,%55,%56,%57,%58,%59,%60,%61,%62,%63,"
      "%64,%65,%66,%67,%68,%69,%70,%71,%72,%73,%74,%75,%76,%77,%78,%79,"
      "%80,%81,%82,%83,%84,%85,%86,%87,%88,%89,%90,%91,%92,%93,%94,%95,"
      "%96,%97,%98,%99,%100,%101,%102,%103"
      "}, {%104,%105,%106,%107}, %108, p, 1, 1, 0; }"
    : "+f"(d[0]), "+f"(d[1]), "+f"(d[2]), "+f"(d[3]), "+f"(d[4]), "+f"(d[5]), "+f"(d[6]), "+f"(d[7]),
      "+f"(d[8]), "+f"(d[9]), "+f"(d[10]), "+f"(d[11]), "+f"(d[12]), "+f"(d[13]), "+f"(d[14]), "+f"(d[15]),
      "+f"(d[16]), "+f"(d[17]), "+f"(d[18]), "+f"(d[19]), "+f"(d[20]), "+f"(d[21]), "+f"(d[22]), "+f"(d[23]),
      "+f"(d[24]), "+f"(d[25]), "+f"(d[26]), "+f"(d[27]), "+f"(d[28]), "+f"(d[29]), "+f"(d[30]), "+f"(d[31]),
      "+f"(d[32]), "+f"(d[33]), "+f"(d[34]), "+f"(d[35]), "+f"(d[36]), "+f"(d[37]), "+f"(d[38]), "+f"(d[39]),
      "+f"(d[40]), "+f"(d[41]), "+f"(d[42]), "+f"(d[43]), "+f"(d[44]), "+f"(d[45]), "+f"(d[46]), "+f"(d[47]),
      "+f"(d[48]), "+f"(d[49]), "+f"(d[50]), "+f"(d[51]), "+f"(d[52]), "+f"(d[53]), "+f"(d[54]), "+f"(d[55]),
      "+f"(d[56]), "+f"(d[57]), "+f"(d[58]), "+f"(d[59]), "+f"(d[60]), "+f"(d[61]), "+f"(d[62]), "+f"(d[63]),
      "+f"(d[64]), "+f"(d[65]), "+f"(d[66]), "+f"(d[67]), "+f"(d[68]), "+f"(d[69]), "+f"(d[70]), "+f"(d[71]),
      "+f"(d[72]), "+f"(d[73]), "+f"(d[74]), "+f"(d[75]), "+f"(d[76]), "+f"(d[77]), "+f"(d[78]), "+f"(d[79]),
      "+f"(d[80]), "+f"(d[81]), "+f"(d[82]), "+f"(d[83]), "+f"(d[84]), "+f"(d[85]), "+f"(d[86]), "+f"(d[87]),
      "+f"(d[88]), "+f"(d[89]), "+f"(d[90]), "+f"(d[91]), "+f"(d[92]), "+f"(d[93]), "+f"(d[94]), "+f"(d[95]),
      "+f"(d[96]), "+f"(d[97]), "+f"(d[98]), "+f"(d[99]), "+f"(d[100]), "+f"(d[101]), "+f"(d[102]), "+f"(d[103])
    : "r"(a[0]), "r"(a[1]), "r"(a[2]), "r"(a[3]), "l"(db), "r"(sd));
}

__device__ __forceinline__ void wgmma_rs_n224(float* d, const uint32_t* a, uint64_t db, int sd) {
  asm volatile("{ .reg .pred p; setp.ne.b32 p, %117, 0;\n"
      "wgmma.mma_async.sync.aligned.m64n224k16.f32.bf16.bf16 {"
      "%0,%1,%2,%3,%4,%5,%6,%7,%8,%9,%10,%11,%12,%13,%14,%15,"
      "%16,%17,%18,%19,%20,%21,%22,%23,%24,%25,%26,%27,%28,%29,%30,%31,"
      "%32,%33,%34,%35,%36,%37,%38,%39,%40,%41,%42,%43,%44,%45,%46,%47,"
      "%48,%49,%50,%51,%52,%53,%54,%55,%56,%57,%58,%59,%60,%61,%62,%63,"
      "%64,%65,%66,%67,%68,%69,%70,%71,%72,%73,%74,%75,%76,%77,%78,%79,"
      "%80,%81,%82,%83,%84,%85,%86,%87,%88,%89,%90,%91,%92,%93,%94,%95,"
      "%96,%97,%98,%99,%100,%101,%102,%103,%104,%105,%106,%107,%108,%109,%110,%111"
      "}, {%112,%113,%114,%115}, %116, p, 1, 1, 0; }"
    : "+f"(d[0]), "+f"(d[1]), "+f"(d[2]), "+f"(d[3]), "+f"(d[4]), "+f"(d[5]), "+f"(d[6]), "+f"(d[7]),
      "+f"(d[8]), "+f"(d[9]), "+f"(d[10]), "+f"(d[11]), "+f"(d[12]), "+f"(d[13]), "+f"(d[14]), "+f"(d[15]),
      "+f"(d[16]), "+f"(d[17]), "+f"(d[18]), "+f"(d[19]), "+f"(d[20]), "+f"(d[21]), "+f"(d[22]), "+f"(d[23]),
      "+f"(d[24]), "+f"(d[25]), "+f"(d[26]), "+f"(d[27]), "+f"(d[28]), "+f"(d[29]), "+f"(d[30]), "+f"(d[31]),
      "+f"(d[32]), "+f"(d[33]), "+f"(d[34]), "+f"(d[35]), "+f"(d[36]), "+f"(d[37]), "+f"(d[38]), "+f"(d[39]),
      "+f"(d[40]), "+f"(d[41]), "+f"(d[42]), "+f"(d[43]), "+f"(d[44]), "+f"(d[45]), "+f"(d[46]), "+f"(d[47]),
      "+f"(d[48]), "+f"(d[49]), "+f"(d[50]), "+f"(d[51]), "+f"(d[52]), "+f"(d[53]), "+f"(d[54]), "+f"(d[55]),
      "+f"(d[56]), "+f"(d[57]), "+f"(d[58]), "+f"(d[59]), "+f"(d[60]), "+f"(d[61]), "+f"(d[62]), "+f"(d[63]),
      "+f"(d[64]), "+f"(d[65]), "+f"(d[66]), "+f"(d[67]), "+f"(d[68]), "+f"(d[69]), "+f"(d[70]), "+f"(d[71]),
      "+f"(d[72]), "+f"(d[73]), "+f"(d[74]), "+f"(d[75]), "+f"(d[76]), "+f"(d[77]), "+f"(d[78]), "+f"(d[79]),
      "+f"(d[80]), "+f"(d[81]), "+f"(d[82]), "+f"(d[83]), "+f"(d[84]), "+f"(d[85]), "+f"(d[86]), "+f"(d[87]),
      "+f"(d[88]), "+f"(d[89]), "+f"(d[90]), "+f"(d[91]), "+f"(d[92]), "+f"(d[93]), "+f"(d[94]), "+f"(d[95]),
      "+f"(d[96]), "+f"(d[97]), "+f"(d[98]), "+f"(d[99]), "+f"(d[100]), "+f"(d[101]), "+f"(d[102]), "+f"(d[103]),
      "+f"(d[104]), "+f"(d[105]), "+f"(d[106]), "+f"(d[107]), "+f"(d[108]), "+f"(d[109]), "+f"(d[110]), "+f"(d[111])
    : "r"(a[0]), "r"(a[1]), "r"(a[2]), "r"(a[3]), "l"(db), "r"(sd));
}

__device__ __forceinline__ void wgmma_rs_n240(float* d, const uint32_t* a, uint64_t db, int sd) {
  asm volatile("{ .reg .pred p; setp.ne.b32 p, %125, 0;\n"
      "wgmma.mma_async.sync.aligned.m64n240k16.f32.bf16.bf16 {"
      "%0,%1,%2,%3,%4,%5,%6,%7,%8,%9,%10,%11,%12,%13,%14,%15,"
      "%16,%17,%18,%19,%20,%21,%22,%23,%24,%25,%26,%27,%28,%29,%30,%31,"
      "%32,%33,%34,%35,%36,%37,%38,%39,%40,%41,%42,%43,%44,%45,%46,%47,"
      "%48,%49,%50,%51,%52,%53,%54,%55,%56,%57,%58,%59,%60,%61,%62,%63,"
      "%64,%65,%66,%67,%68,%69,%70,%71,%72,%73,%74,%75,%76,%77,%78,%79,"
      "%80,%81,%82,%83,%84,%85,%86,%87,%88,%89,%90,%91,%92,%93,%94,%95,"
      "%96,%97,%98,%99,%100,%101,%102,%103,%104,%105,%106,%107,%108,%109,%110,%111,"
      "%112,%113,%114,%115,%116,%117,%118,%119"
      "}, {%120,%121,%122,%123}, %124, p, 1, 1, 0; }"
    : "+f"(d[0]), "+f"(d[1]), "+f"(d[2]), "+f"(d[3]), "+f"(d[4]), "+f"(d[5]), "+f"(d[6]), "+f"(d[7]),
      "+f"(d[8]), "+f"(d[9]), "+f"(d[10]), "+f"(d[11]), "+f"(d[12]), "+f"(d[13]), "+f"(d[14]), "+f"(d[15]),
      "+f"(d[16]), "+f"(d[17]), "+f"(d[18]), "+f"(d[19]), "+f"(d[20]), "+f"(d[21]), "+f"(d[22]), "+f"(d[23]),
      "+f"(d[24]), "+f"(d[25]), "+f"(d[26]), "+f"(d[27]), "+f"(d[28]), "+f"(d[29]), "+f"(d[30]), "+f"(d[31]),
      "+f"(d[32]), "+f"(d[33]), "+f"(d[34]), "+f"(d[35]), "+f"(d[36]), "+f"(d[37]), "+f"(d[38]), "+f"(d[39]),
      "+f"(d[40]), "+f"(d[41]), "+f"(d[42]), "+f"(d[43]), "+f"(d[44]), "+f"(d[45]), "+f"(d[46]), "+f"(d[47]),
      "+f"(d[48]), "+f"(d[49]), "+f"(d[50]), "+f"(d[51]), "+f"(d[52]), "+f"(d[53]), "+f"(d[54]), "+f"(d[55]),
      "+f"(d[56]), "+f"(d[57]), "+f"(d[58]), "+f"(d[59]), "+f"(d[60]), "+f"(d[61]), "+f"(d[62]), "+f"(d[63]),
      "+f"(d[64]), "+f"(d[65]), "+f"(d[66]), "+f"(d[67]), "+f"(d[68]), "+f"(d[69]), "+f"(d[70]), "+f"(d[71]),
      "+f"(d[72]), "+f"(d[73]), "+f"(d[74]), "+f"(d[75]), "+f"(d[76]), "+f"(d[77]), "+f"(d[78]), "+f"(d[79]),
      "+f"(d[80]), "+f"(d[81]), "+f"(d[82]), "+f"(d[83]), "+f"(d[84]), "+f"(d[85]), "+f"(d[86]), "+f"(d[87]),
      "+f"(d[88]), "+f"(d[89]), "+f"(d[90]), "+f"(d[91]), "+f"(d[92]), "+f"(d[93]), "+f"(d[94]), "+f"(d[95]),
      "+f"(d[96]), "+f"(d[97]), "+f"(d[98]), "+f"(d[99]), "+f"(d[100]), "+f"(d[101]), "+f"(d[102]), "+f"(d[103]),
      "+f"(d[104]), "+f"(d[105]), "+f"(d[106]), "+f"(d[107]), "+f"(d[108]), "+f"(d[109]), "+f"(d[110]), "+f"(d[111]),
      "+f"(d[112]), "+f"(d[113]), "+f"(d[114]), "+f"(d[115]), "+f"(d[116]), "+f"(d[117]), "+f"(d[118]), "+f"(d[119])
    : "r"(a[0]), "r"(a[1]), "r"(a[2]), "r"(a[3]), "l"(db), "r"(sd));
}

__device__ __forceinline__ void wgmma_rs_n256(float* d, const uint32_t* a, uint64_t db, int sd) {
  asm volatile("{ .reg .pred p; setp.ne.b32 p, %133, 0;\n"
      "wgmma.mma_async.sync.aligned.m64n256k16.f32.bf16.bf16 {"
      "%0,%1,%2,%3,%4,%5,%6,%7,%8,%9,%10,%11,%12,%13,%14,%15,"
      "%16,%17,%18,%19,%20,%21,%22,%23,%24,%25,%26,%27,%28,%29,%30,%31,"
      "%32,%33,%34,%35,%36,%37,%38,%39,%40,%41,%42,%43,%44,%45,%46,%47,"
      "%48,%49,%50,%51,%52,%53,%54,%55,%56,%57,%58,%59,%60,%61,%62,%63,"
      "%64,%65,%66,%67,%68,%69,%70,%71,%72,%73,%74,%75,%76,%77,%78,%79,"
      "%80,%81,%82,%83,%84,%85,%86,%87,%88,%89,%90,%91,%92,%93,%94,%95,"
      "%96,%97,%98,%99,%100,%101,%102,%103,%104,%105,%106,%107,%108,%109,%110,%111,"
      "%112,%113,%114,%115,%116,%117,%118,%119,%120,%121,%122,%123,%124,%125,%126,%127"
      "}, {%128,%129,%130,%131}, %132, p, 1, 1, 0; }"
    : "+f"(d[0]), "+f"(d[1]), "+f"(d[2]), "+f"(d[3]), "+f"(d[4]), "+f"(d[5]), "+f"(d[6]), "+f"(d[7]),
      "+f"(d[8]), "+f"(d[9]), "+f"(d[10]), "+f"(d[11]), "+f"(d[12]), "+f"(d[13]), "+f"(d[14]), "+f"(d[15]),
      "+f"(d[16]), "+f"(d[17]), "+f"(d[18]), "+f"(d[19]), "+f"(d[20]), "+f"(d[21]), "+f"(d[22]), "+f"(d[23]),
      "+f"(d[24]), "+f"(d[25]), "+f"(d[26]), "+f"(d[27]), "+f"(d[28]), "+f"(d[29]), "+f"(d[30]), "+f"(d[31]),
      "+f"(d[32]), "+f"(d[33]), "+f"(d[34]), "+f"(d[35]), "+f"(d[36]), "+f"(d[37]), "+f"(d[38]), "+f"(d[39]),
      "+f"(d[40]), "+f"(d[41]), "+f"(d[42]), "+f"(d[43]), "+f"(d[44]), "+f"(d[45]), "+f"(d[46]), "+f"(d[47]),
      "+f"(d[48]), "+f"(d[49]), "+f"(d[50]), "+f"(d[51]), "+f"(d[52]), "+f"(d[53]), "+f"(d[54]), "+f"(d[55]),
      "+f"(d[56]), "+f"(d[57]), "+f"(d[58]), "+f"(d[59]), "+f"(d[60]), "+f"(d[61]), "+f"(d[62]), "+f"(d[63]),
      "+f"(d[64]), "+f"(d[65]), "+f"(d[66]), "+f"(d[67]), "+f"(d[68]), "+f"(d[69]), "+f"(d[70]), "+f"(d[71]),
      "+f"(d[72]), "+f"(d[73]), "+f"(d[74]), "+f"(d[75]), "+f"(d[76]), "+f"(d[77]), "+f"(d[78]), "+f"(d[79]),
      "+f"(d[80]), "+f"(d[81]), "+f"(d[82]), "+f"(d[83]), "+f"(d[84]), "+f"(d[85]), "+f"(d[86]), "+f"(d[87]),
      "+f"(d[88]), "+f"(d[89]), "+f"(d[90]), "+f"(d[91]), "+f"(d[92]), "+f"(d[93]), "+f"(d[94]), "+f"(d[95]),
      "+f"(d[96]), "+f"(d[97]), "+f"(d[98]), "+f"(d[99]), "+f"(d[100]), "+f"(d[101]), "+f"(d[102]), "+f"(d[103]),
      "+f"(d[104]), "+f"(d[105]), "+f"(d[106]), "+f"(d[107]), "+f"(d[108]), "+f"(d[109]), "+f"(d[110]), "+f"(d[111]),
      "+f"(d[112]), "+f"(d[113]), "+f"(d[114]), "+f"(d[115]), "+f"(d[116]), "+f"(d[117]), "+f"(d[118]), "+f"(d[119]),
      "+f"(d[120]), "+f"(d[121]), "+f"(d[122]), "+f"(d[123]), "+f"(d[124]), "+f"(d[125]), "+f"(d[126]), "+f"(d[127])
    : "r"(a[0]), "r"(a[1]), "r"(a[2]), "r"(a[3]), "l"(db), "r"(sd));
}

__device__ __forceinline__ void ln_finish(float mean, float var, float& mb, float& rinv) {
  mb = round_bf16(mean);
  float sd;
  asm("sqrt.approx.ftz.f32 %0, %1;" : "=f"(sd) : "f"(round_bf16(round_bf16(var) + 1e-5f)));
  asm("rcp.approx.ftz.f32 %0, %1;" : "=f"(rinv) : "f"(round_bf16(sd)));
}
__device__ __forceinline__ uint32_t sum4(uint32_t a, uint32_t b, uint32_t c, uint32_t d) { return badd2(badd2(badd2(d, c), b), a); }
struct Ring {
  uint32_t s, ph;
  __device__ __forceinline__ void next() { if (++s == NSTAGE) { s = 0; ph ^= 1; } }
};

template <int J> __device__ __forceinline__ void conv_lda(uint32_t* a, uint32_t base, bool on) {
  asm volatile("{ .reg .pred p; setp.ne.u32 p, %3, 0;\n @p ld.shared.u32 %0, [%2 + %4];\n @p ld.shared.u32 %1, [%2 + %5]; }"
               : "+r"(a[2 * J]), "+r"(a[2 * J + 1]) : "r"(base), "r"((uint32_t)on), "n"((J >> 1) * 256 + (J & 1) * 16), "n"((J >> 1) * 256 + (J & 1) * 16 + 128) : "memory");
}
template <int J = 0> __device__ __forceinline__ void conv_lda_all(uint32_t* a, uint32_t base) {
  conv_lda<J>(a, base, true);
  if constexpr (J < 31) conv_lda_all<J + 1>(a, base);
}
__device__ __forceinline__ void conv_mma(float* acc, const uint32_t* a, uint64_t db) {
  wgmma_rs_n256(acc, a, db, 0);
  wgmma_rs_n240(acc, a + 4, db + 16, 1);
  wgmma_rs_n224(acc, a + 8, db + 32, 1);
  wgmma_rs_n208(acc, a + 12, db + 48, 1);
  wgmma_rs_n192(acc, a + 16, db + 64, 1);
  wgmma_rs_n176(acc, a + 20, db + 80, 1);
  wgmma_rs_n160(acc, a + 24, db + 96, 1);
  wgmma_rs_n144(acc, a + 28, db + 112, 1);
  wgmma_rs_n128(acc, a + 32, db + 128, 1);
  wgmma_rs_n112(acc, a + 36, db + 144, 1);
  wgmma_rs_n96(acc, a + 40, db + 160, 1);
  wgmma_rs_n80(acc, a + 44, db + 176, 1);
  wgmma_rs_n64(acc, a + 48, db + 192, 1);
  wgmma_rs_n48(acc, a + 52, db + 208, 1);
  wgmma_rs_n32(acc, a + 56, db + 224, 1);
  wgmma_rs_n16(acc, a + 60, db + 240, 1);
}
__device__ __forceinline__ uint32_t conv_part(const float* acc, int j) {
  const int q = 31 - j;
  return q == 31 ? pack_bf16(acc[124], acc[125]) : pack_bf16(acc[4 * q] + acc[(4 * q + 6) & 127], acc[4 * q + 1] + acc[(4 * q + 7) & 127]);
}
template <int J = 0> __device__ __forceinline__ void conv_drain(const float* acc, uint32_t wr, uint32_t* a, uint32_t ka, bool more) {
  conv_lda<J>(a, ka, more);
  sts32(wr + J * 128, conv_part(acc, J));
  if constexpr (J < 31) conv_drain<J + 1>(acc, wr, a, ka, more);
}
__device__ __forceinline__ uint4 conv_sum(const uint4* p) {
  return make_uint4(sum4(p[0].x, p[1].x, p[2].x, p[3].x), sum4(p[0].y, p[1].y, p[2].y, p[3].y), sum4(p[0].z, p[1].z, p[2].z, p[3].z),
                    sum4(p[0].w, p[1].w, p[2].w, p[3].w));
}
__device__ __forceinline__ int g2k(int rank, int kb) { return (rank * G2_KB + (kb < 6 ? 6 * kb : kb - 5 + (kb - 6) / 5)) * 64; }

template <int NV> __device__ __forceinline__ void gelu_stage(float* acc, const float* hb, uint32_t sa, int passes, uint32_t bar) {
#pragma unroll
  for (int i = 0; i < NV; i++) acc[i] = fmaf(acc[i], 0.5f, hb[(i >> 1) & 1]);
#pragma unroll 1
  for (; passes > 0; passes--, sa += NV * 256) {
#pragma unroll
    for (int i = 0; i < NV; i += 8)
      stsm4t(sa + i * 256, pack_bf16(gelu_half(acc[i]), gelu_half(acc[i + 1])), pack_bf16(gelu_half(acc[i + 2]), gelu_half(acc[i + 3])),
             pack_bf16(gelu_half(acc[i + 4]), gelu_half(acc[i + 5])), pack_bf16(gelu_half(acc[i + 6]), gelu_half(acc[i + 7])));
    __syncwarp();
    if (bar) mbar_arrive(bar);
    bar = 0;
    float half = 0.5f;
    asm volatile("" : "+f"(half));
#pragma unroll
    for (int i = 0; i < NV; i++) acc[i] = fmaf(acc[NV + i], half, hb[2 + ((i >> 1) & 1)]);
  }
}

__global__ void __cluster_dims__(2, 1, 1) __launch_bounds__(384, 1) fused_kernel(const __grid_constant__ Hot H, const __grid_constant__ Params P) {
  extern __shared__ __align__(1024) uint8_t smem_raw[];
  const uint32_t t0 = clk();
  const uint32_t sb = smem_u32(smem_raw);
  const int tid = threadIdx.x, lane = tid & 31;
  const int bid = blockIdx.x, rank = bid & 1;
  const Role& R = P.role[bid];
  Scratch* const S = H.S;
  uint32_t xr[18];
  const int row = bid * 16 + (tid >> 4);
  if (tid < 256 && bid < 128) {
    const char* src = reinterpret_cast<const char*>(H.x) + row * (D_ * 2) + (lane & 15) * 8;
#pragma unroll
    for (int j = 0; j < 9; j++) asm volatile("ld.global.nc.v2.u32 {%0,%1}, [%2];" : "=r"(xr[2 * j]), "=r"(xr[2 * j + 1]) : "l"(src + 128 * j));
  }
  const int warp = __shfl_sync(0xffffffffu, tid >> 5, 0);

  if (warp >= 8) {
    const bool one = elect_one();
    if (warp == 8 && one) {
#pragma unroll
      for (int b = B_FULL; b <= B_DONE; b += 8) mbar_init(sb + b, b < B_EMPTY ? 1 : b < B_SFREE ? 2 : b < B_CEMPTY ? 3 : b < B_G1DONE ? 4 : 8);
      asm volatile("fence.mbarrier_init.release.cluster;" ::: "memory");
    }
    __syncwarp();
    asm volatile("barrier.cluster.arrive.relaxed.aligned;" ::: "memory");
    asm volatile("setmaxnreg.dec.sync.aligned.u32 56;");
    asm volatile("barrier.cluster.wait.aligned;" ::: "memory");
    const bool left = R.at == 15;
    if (warp == 8) {
      const uint32_t ep = ldg32(S->cnt + C_EPOCH * 32);
      if (one) {
#pragma unroll 1
        for (int i = 0; i < 10; i++) asm volatile("prefetch.tensormap [%0];" :: "l"(&P.m_w1 + i) : "memory");
#pragma unroll 1
        for (int s = 0; s < NWE; s++) {
          mbar_expect_tx(sb + B_FULL + 8 * s, G1_BYTES);
          tma3d(sb + s * SLOT, &P.m_w1 + left, 0, s * 64, R.fg, sb + B_FULL + 8 * s);
        }
      }
      __syncwarp();
      if (bid < 128) bar_sync(2, 288);
      if (one) {
        TLREC(31);
        signal(S, C_H, EPOCH / 132);
        TLREC(1);
        const uint32_t boff = left ? 24576 : 16384;
        int kr = bid < 128 ? -2 : KV_ROUNDS + 1, ks = 0;
        auto kv_step = [&]() {
          if (ks == 0) {
            bulk_wait_all();
            if (kr < KV_ROUNDS - 2) {
              const int q = (kr + 2) % 3;
              const uint32_t in = sb + kv_buf(q), fb = sb + B_UFULL + 8 * q;
              mbar_expect_tx(fb, 3840 + 3264 + 768);
              tma2d(in, &P.m_k, (kr + 2) * 96, bid * 16 - 4, fb);
              tma2d(in + 3840, &P.m_v, (kr + 2) * 96, bid * 16 - 1, fb);
              bulk_load(in + 7168, H.shift_k + (kr + 2) * 384, 768, fb);
            }
            if (kr == KV_ROUNDS) { mbar_arrive(sb + B_KVDONE); kr++; }
          } else if (kr >= 0) {
            if (!mbar_test(sb + B_KFULL + 8 * (kr % 3), kr >= 3)) return;
            fence_async_smem();
            tma3d_store(&P.m_ub, sb + kv_buf(kr % 3) + (ks - 1) * 3072, 16 * (127 - bid), kr * 48, 2 * ks - 2);
            bulk_commit();
          }
          if (++ks == 3) { kr++; ks = kr == KV_ROUNDS - 2 || kr == KV_ROUNDS - 1; }
        };
        if (bid >= 128) mbar_arrive(sb + B_KVDONE);
        Ring r{0, 1};
#pragma unroll 1
        for (int kb = NWE - NW0; kb < G1_KB || kr <= KV_ROUNDS; kb++) {
          if (kb < G1_KB) {
          const int kw = kb < 0 ? kb + NW0 : kb, s = kb < 0 ? kw : r.s;
          const uint32_t fb = sb + B_FULL + 8 * s;
          if (kb < 0 || kb >= NW0) {
            mbar_wait(sb + B_EMPTY + 8 * s, r.ph);
            mbar_expect_tx(fb, G1_BYTES);
            tma3d(sb + s * SLOT, &P.m_w1 + left, 0, kw * 64, R.fg, fb);
            if (kb < 0) continue;
          }
          if (kb == 0) { await(S, C_H, ep); fence_async_global(); TLREC(2); }
          bulk_load(sb + s * SLOT + boff, S->h + (kb * 18 + R.at) * 2048, G1_BYTES - boff, fb);
          if (kb == 23) {
#pragma unroll 1
            for (int i = 0; i < 2; i++) {
              sts128(sb + cv_taps(i), 0, 0, 0, 0); sts128(sb + cv_taps(i) + 16, 0, 0, 0, 0);
              bulk_load(sb + cv_taps(i) + 32, H.ssm_k + (R.ch + i) * S_, 4096, sb + B_MISC);
            }
            mbar_expect_tx(sb + B_MISC, boff / 64 + 1152 + 8192);
            bulk_load(sb + SM_B1, H.b1 + R.fg * 64, boff / 64, sb + B_MISC);
            bulk_load(sb + SM_D, H.ssm_D, 1152, sb + B_MISC);
          }
          r.next();
          }
          if (kb >= KV0 && kr <= KV_ROUNDS) kv_step();
        }
        await(S, C_KV, ep);
        fence_async_global();
#pragma unroll 1
        for (int i = 0; i < R.ncv; i++) {
          if (i == 2) {
            if (R.sg >= 0) {
#pragma unroll 1
              for (int s = 2; s < NSTAGE; s++) {
                mbar_wait(sb + B_EMPTY + 8 * s, ((G1_KB / NSTAGE) - 1) & 1);
                mbar_expect_tx(sb + B_FULL + 8 * s, G2_BYTES);
                tma3d(sb + s * SLOT, &P.m_w2, 0, (rank * G2_KB + 6 * (s - 2)) * 64, R.sg, sb + B_FULL + 8 * s);
              }
            }
            mbar_wait(sb + B_G1DONE, 0);
          }
          const uint32_t kt = sb + cv_taps(i), b8 = sb + 8 * (i & 3);
          mbar_wait(b8 + B_CEMPTY, ((i >> 2) & 1) ^ 1);
          if (i < 2) mbar_arrive(b8 + B_KFULL);
          else {
            sts128(kt, 0, 0, 0, 0); sts128(kt + 16, 0, 0, 0, 0);
            mbar_expect_tx(b8 + B_KFULL, 4096);
            bulk_load(kt + 32, H.ssm_k + (R.ch + i) * S_, 4096, b8 + B_KFULL);
          }
          mbar_expect_tx(b8 + B_UFULL, 8192);
          bulk_load(sb + cv_in(i), S->ub + (R.ch + i) * 4096, 8192, b8 + B_UFULL);
        }
        if (R.sg >= 0) {
          mbar_expect_tx(sb + B_XY, 2 * 18432 + 2048 + 256);
          mbar_expect_tx(sb + B_XFULL, 9216);
          mbar_expect_tx(sb + B_XFULL + 8, 9216);
#pragma unroll 1
          for (int kb = 0; kb < G2_KB; kb++, r.next()) {
            const int k0 = g2k(rank, kb);
            const uint32_t fb = sb + B_FULL + 8 * r.s, slot = sb + r.s * SLOT;
            if (!(kb & ~4)) { await(S, C_U + (kb >> 2), ep); fence_async_global(); if (!kb) TLREC(6); }
            if (kb >= NSTAGE - 2) {
              mbar_wait(sb + B_EMPTY + 8 * r.s, r.ph);
              if (kb == SYNCA) asm volatile("red.relaxed.gpu.global.add.u32 [%0], %1;" :: "l"(S->cnt + C_SYNC * 32), "r"(EPOCH / 128) : "memory");
              if (kb == SYNCKB) await(S, C_SYNC, ep);
              mbar_expect_tx(fb, G2_BYTES);
              tma3d(slot, &P.m_w2, 0, k0, R.sg, fb);
            }
            tma2d(slot + 16384, &P.m_uld, k0, R.ds * 8, fb);
            tma2d(slot + 16384 + 9216, &P.m_uld, k0, R.dk * 8, fb);
            const uint32_t nx = kb - 8;
            if (nx == 0) { mbar_wait(sb + B_KVDONE, 1); fence_async_smem(); }
            if (nx < 8) tma2d(sb + SM_CV + nx * 2304, &P.m_x, R.dk * 8, R.sg * 64 + nx * 16, sb + B_XY);
          }
          bulk_load(sb + SM_ST, S->stats + R.sg * 64, 2048, sb + B_XY);
          bulk_load(sb + SM_B2, P.b2 + R.sg * 64, 256, sb + B_XY);
          await(S, C_Y, ep);
          fence_async_global();
          TLREC(19);
          tma3d(sb + SM_DED, &P.m_y, 0, R.dk * 8, R.sg, sb + B_XY);
          if (bid == 0) asm volatile("red.relaxed.gpu.global.add.u32 [%0], %1;" :: "l"(S->cnt + C_EPOCH * 32), "r"(EPOCH) : "memory");
        }
      }
    } else {
      if (bid < 128) {
        const int ht = tid - 288, hf = ht >= 48, pr = ht - 48 * hf;
        const uint32_t st = (1 - hf) * 1536 + pr * 32, sw = (pr & 4) * 4;
#pragma unroll 1
        for (int r = 0; r < KV_ROUNDS; r++) {
          const int q = r % 3;
          const uint32_t in = sb + kv_buf(q);
          {
            mbar_wait_guarded(sb + B_UFULL + 8 * q, t0, r >= 3);
            uint32_t kk[12], vv[9];
#pragma unroll
            for (int j = 0; j < 12; j++) kk[j] = lds32(in + hf * 1536 + pr * 4 + j * 192);
#pragma unroll
            for (int j = 0; j < 9; j++) vv[j] = lds32(in + 3840 + hf * 1536 + pr * 4 + j * 192);
            const uint4 w = lds128(in + 7168 + pr * 16);
            const uint32_t w0 = __byte_perm(w.x, w.z, 0x5410), w1 = __byte_perm(w.x, w.z, 0x7632);
            const uint32_t w2 = __byte_perm(w.y, w.w, 0x5410), w3 = __byte_perm(w.y, w.w, 0x7632);
#pragma unroll
            for (int j = 0; j < 9; j++)
              vv[j] = bmul2(badd2(badd2(badd2(bmul2(kk[j], w3), bmul2(kk[j + 1], w2)), bmul2(kk[j + 2], w1)), bmul2(kk[j + 3], w0)), vv[j]);
            bar_sync(1, 96);
#pragma unroll
            for (int c = 0; c < 2; c++)
#pragma unroll
              for (int pi = 0; pi < 2; pi++) {
                const uint32_t sel = c ? 0x7632 : 0x5410;
                sts128(in + st + c * 3072 + (pi * 16 ^ sw), __byte_perm(vv[7 + pi], vv[6 + pi], sel), __byte_perm(vv[5 + pi], vv[4 + pi], sel),
                       __byte_perm(vv[3 + pi], vv[2 + pi], sel), __byte_perm(vv[1 + pi], vv[pi], sel));
              }
            bar_sync(1, 96);
            if (ht == 0) mbar_arrive(sb + B_KFULL + 8 * q);
          }
          __syncwarp();
        }
      }
      if (one) {
        if (warp < 11) {
          const int wg = warp - 9;
#pragma unroll 1
          for (int j = 0; j <= (left ? 3 + 3 * wg : 5); j++) {
            if (j == 0 || j == 2 + left) {
              mbar_wait_guarded(sb + B_STG + 8 * wg + (j ? 0 : 16), t0);
              fence_async_smem();
              TLREC(13 + wg);
            }
            const int hi = left && j >= 3;
            if (j < (left ? 3 + 3 * wg : 5))
              tma2d_store(&P.m_ust, sb + (wg ? SM_ST1 : SM_DED) + j * 4096, (R.fg + wg + hi) * 64, (R.at + j - 3 * hi) * 32);
          }
          bulk_commit();
          bulk_wait_all();
          mbar_arrive(sb + B_STORED + 8 * wg);
          if (wg) mbar_arrive(sb + B_EMPTY);
          asm volatile("mbarrier.arrive.shared::cta.b64 _, [%0], 3;" :: "r"(sb + B_SFREE + 8 * wg) : "memory");
          signal(S, C_U + wg, EPOCH / 132);
          TLREC(15 + wg);
        } else {
          mbar_wait_guarded(sb + B_KVDONE, t0);
          signal(S, C_KV, EPOCH / 132);
          TLREC(27);
        }
      }
      __syncwarp();
#pragma unroll 1
      for (int i = 0; i < R.ncv; i++) {
        const uint32_t red = sb + cv_red(i, R.ncv) + (tid - 288) * 16;
        uint4* yo = reinterpret_cast<uint4*>(S->y + (R.ch + i) * S_) + (tid - 288);
        mbar_wait_guarded(sb + B_STORED + 8 * (i & 1), t0);
        mbar_wait_guarded(sb + B_STG + 8 * (i & 1) + (i + 2 < R.ncv ? 0 : 16), t0, i + 2 >= R.ncv || !(i & 2));
        uint4 p[2][4];
#pragma unroll
        for (int x = 0; x < 8; x++) p[x >> 2][x & 3] = lds128(red + (x & 3) * CV_REDW + (x >> 2) * 1536);
        yo[0] = conv_sum(p[0]);
        if (warp < 11) {
#pragma unroll
          for (int x = 0; x < 4; x++) p[0][x] = lds128(red + x * CV_REDW + 3072);
          yo[192] = conv_sum(p[0]);
        }
        yo[96] = conv_sum(p[1]);
        __syncwarp();
        if (one) mbar_arrive(sb + (i + 4 == R.ncv ? B_PDONE : B_SFREE + 8 * (i & 1)));
        if (i + 3 == R.ncv) {
          bar_sync(1, 96);
          if (warp == 11 && one) { fence_async_smem(); mbar_arrive(sb + B_EMPTY + 8); }
          __syncwarp();
        }
      }
      bar_sync(1, 96);
      if (warp == 11 && one) {
        TLREC(7);
        mbar_arrive(sb + B_KVDONE);
        signal(S, C_Y, EPOCH / 132);
        if (R.sg >= 0) mbar_wait_guarded(sb + B_DONE, t0);
      }
    }
    TLEND();
  } else {
    asm volatile("barrier.cluster.arrive.relaxed.aligned;" ::: "memory");
    if (bid < 128) {
      float c[36], s[4];
#pragma unroll
      for (int i = 0; i < 18; i++) { c[2 * i] = bf_lo(xr[i]); c[2 * i + 1] = bf_hi(xr[i]); }
#pragma unroll
      for (int i = 0; i < 36; i++) s[i & 3] = i < 4 ? c[i] : s[i & 3] + c[i];
      const float ml = ((s[0] + s[1]) + (s[2] + s[3])) * (1.0f / 36.0f);
#pragma unroll
      for (int i = 0; i < 36; i++) { c[i] -= ml; s[i & 3] = i < 4 ? c[i] * c[i] : fmaf(c[i], c[i], s[i & 3]); }
      float m = ml, q = (s[0] + s[1]) + (s[2] + s[3]), n2 = 18.f;
#pragma unroll
      for (int o = 1; o < 16; o <<= 1) {
        const float mo = __shfl_xor_sync(0xffffffffu, m, o), qo = __shfl_xor_sync(0xffffffffu, q, o);
        const float dl = m - mo;
        q = fmaf(dl * dl, n2, q + qo);
        m = fmaf(dl, -0.5f, m);
        n2 *= 2.f;
      }
      const float var = q * (1.0f / 576.0f);
      float mb, rinv, mb2, rinv2;
      ln_finish(m, var, mb, rinv);
      ln_finish((m - mb) * rinv, var * rinv * rinv, mb2, rinv2);
      const float ca = rinv * rinv2, cb = fmaf(ml - mb, rinv, -mb2) * rinv2;
      uint2* dst = reinterpret_cast<uint2*>(S->h) + ((row >> 6) * 18 + ((lane >> 3) & 1)) * 512 + (row & 63) * 8 + ((lane & 7) ^ (row & 6));
#pragma unroll
      for (int j = 0; j < 9; j++)
        dst[1024 * j] = make_uint2(pack_bf16(fmaf(c[4 * j], ca, cb), fmaf(c[4 * j + 1], ca, cb)), pack_bf16(fmaf(c[4 * j + 2], ca, cb), fmaf(c[4 * j + 3], ca, cb)));
      const uint32_t rh = pack_bf16(rinv, rinv);
      if (!(lane & 15)) S->stats[row] = make_uint4(pack_bf16(mb, mb), rh, pack_bf16(rinv - bf_lo(rh), rinv - bf_lo(rh)), 0);
      __syncwarp();
      bar_arrive(2, 288);
    }
    asm volatile("setmaxnreg.inc.sync.aligned.u32 224;");
    asm volatile("barrier.cluster.wait.aligned;" ::: "memory");
    const int wg = warp >> 2, w = warp & 3, g = lane >> 2, t = lane & 3, wtid = tid & 127;
    const bool elect = wtid == 0;
    const uint64_t da0 = make_desc(sb + wg * 8192, 8192, 1024, 1);
    const uint32_t swz = ((lane >> 4) * 8 + (lane & 7)) * 128 + (((2 * w + ((lane >> 3) & 1)) ^ (lane & 7)) << 4);
    const uint32_t stg = sb + (wg ? SM_ST1 : SM_DED), ka0 = (8 * w + g + t + 1) * 4;
    uint32_t a[64];
    {
      auto mainloop = [&](auto&& mma) {
        Ring r{0, 0};
        uint32_t rel = 0;
#pragma unroll 1
        for (int kb = 0; kb < G1_KB; kb++, r.next()) {
          if (kb == G1_KB - G1_TAIL && wg) {
            wg_wait<0>();
            if (elect) mbar_arrive(rel);
            rel = 0;
            if (PRE1) {
              mbar_wait(sb + B_MISC, 0);
              conv_lda_all(a, sb + SM_CV + 16384 + CV_K + ka0);
            }
            bar_sync(5, 256);
          }
          mbar_wait(sb + B_FULL + 8 * r.s, r.ph);
          if (kb == 0 && warp == 0) TLREC(3);
          wg_fence();
          mma(r.s * (SLOT >> 4), kb);
          wg_commit();
          if (kb == G1_KB - 1) break;
          wg_wait<1>();
          if (elect && rel) mbar_arrive(rel);
          rel = sb + B_EMPTY + 8 * r.s;
        }
        bar_arrive(5, 256);
        wg_wait<0>();
      };
      float hb[4];
      auto staged = [&](int second) {
        if (!w) TLREC(4 + wg);
        if (lane == 0) mbar_arrive(sb + B_G1DONE);
        mbar_wait(sb + B_MISC, 0);
#pragma unroll
        for (int i = 0; i < 4; i++) hb[i] = 0.5f * bf_lo(lds16(sb + SM_B1 + (warp * 16 + g + (i & 1) * 8 + (i >> 1) * second) * 2));
        mbar_wait(sb + B_KVDONE, 0);
        if (wg) mbar_wait(sb + B_G1DONE, 0);
      };
      if (R.at != 15) {
        const uint64_t db0 = make_desc(sb + 16384, 4096, 512, 2);
        float acc[80];
        mainloop([&](uint32_t o, int kb) {
          wgmma_ss_n160_t11(acc, da0 + o, db0 + o, kb);
#pragma unroll
          for (int k = 1; k < 4; k++) wgmma_ss_n160_t11(acc, da0 + o + k * 128, db0 + o + k * 64, 1);
        });
        pin_regs<80>(acc);
        staged(0);
        gelu_stage<40>(acc, hb, stg + swz, 2, lane ? 0 : sb + B_STG + 8 * wg + 16);
      } else {
        const uint64_t db0 = make_desc(sb + 24576, 4096, 512, 2);
        float acc[96];
        auto block = [&](float* d, uint64_t da, uint64_t db, int kb) {
          wgmma_ss_n96_t11(d, da, db, kb);
#pragma unroll
          for (int k = 1; k < 4; k++) wgmma_ss_n96_t11(d, da + k * 128, db + k * 64, 1);
        };
        if (wg) mainloop([&](uint32_t o, int kb) { block(acc, da0 + o, db0 + o, kb); block(acc + 48, da0 + o + 512, db0 + o, kb); });
        else mainloop([&](uint32_t o, int kb) { block(acc, da0 + o, db0 + o, kb); });
        pin_regs<96>(acc);
        staged(64);
        gelu_stage<48>(acc, hb, stg + swz, 1 + wg, lane ? 0 : sb + B_STG + 8 * wg + 16);
      }
      __syncwarp();
      if (lane == 0) mbar_arrive(sb + B_STG + 8 * wg);
    }
    {
      if (!wg || !PRE1) conv_lda_all(a, sb + SM_CV + 16384 + wg * CV_K + ka0);
#pragma unroll 1
      for (int i = wg; i < R.ncv; i += 2) {
        const bool more = i + 2 < R.ncv;
        const uint32_t dd = lds16(sb + SM_D + (R.ch + i) * 2);
        a[0] = badd2(a[0], ka0 == 32 ? dd : 0); a[2] = badd2(a[2], ka0 == 16 ? dd : 0);
        float acc[128];
        mbar_wait(sb + B_UFULL + 8 * (i & 3), (i >> 2) & 1);
        bar_sync(5 + wg, 256);
        const bool last = i + 1 == R.ncv;
        if (last && elect) mbar_arrive(sb + B_EMPTY);
        if (!w && i < 4) TLREC(22 + i);
        wg_fence();
        conv_mma(acc, a, make_desc(sb + cv_in(i), 4096, 128, 0));
        wg_commit();
        if (!last) bar_arrive(5 + (wg ^ 1), 256);
        if (more) {
          mbar_wait(sb + B_SFREE + 8 * wg, (i >> 1) & 1);
          mbar_wait(sb + B_KFULL + 8 * ((i + 2) & 3), ((i + 2) >> 2) & 1);
        } else if (last) mbar_wait(sb + B_PDONE, 0);
        wg_wait<0>();
        pin_regs<128>(acc);
        if (lane == 0) mbar_arrive(sb + B_CEMPTY + 8 * (i & 3));
        if (last && elect) mbar_arrive(sb + B_EMPTY + 8);
        const uint32_t red = sb + cv_red(i, R.ncv), ka = sb + cv_taps(i + 2) + ka0;
        if (lane < 8 * w) sts32(red + w * CV_REDW + lane * 4, 0);
        const uint32_t wr = red + w * CV_REDW + (8 * (3 - t + w) + g) * 4;
        conv_drain(acc, wr, a, ka, more);
        __syncwarp();
        if (lane == 0) mbar_arrive(sb + B_STG + 8 * wg + (more ? 0 : 16));
      }
      if (!w) TLREC(20 + wg);
    }
    if (R.sg >= 0) {
      const int srow = R.sg * 64 + warp * 16;
      const uint64_t db0 = make_desc(sb + 16384, 16, 1024, 1);
      const uint32_t xo = sb + SM_CV + warp * 2304, xa = xo + (lane & 15) * 144;
      float acc[72];
      Ring r{G1_KB % NSTAGE, (G1_KB / NSTAGE) & 1};
      uint32_t rel = 0;
#pragma unroll 1
      for (int kb = 0; kb < G2_KB; kb++, r.next()) {
        if (kb == G2_KB - G2_TAIL && wg) {
          wg_wait<0>();
          if (elect) mbar_arrive_remote(rel);
          rel = 0;
          bar_sync(7, 256);
        }
        mbar_wait(sb + B_FULL + 8 * r.s, r.ph);
        if (kb == 0 && !w) TLREC(17 + wg);
        if (kb == 8 && warp == 0) TLREC(26);
        if (kb == 20 && warp == 0) TLREC(8);
        if (kb == 27 && warp == 0) TLREC(30);
        const uint64_t da = da0 + r.s * (SLOT >> 4), db = db0 + r.s * (SLOT >> 4);
        wg_fence();
        wgmma_ss_n144_t10(acc, da, db, kb);
#pragma unroll
        for (int k = 1; k < 4; k++) wgmma_ss_n144_t10(acc, da + k * 128, db + k * 2, 1);
        wg_commit();
        if (kb == G2_KB - 1) break;
        wg_wait<1>();
        if (elect && rel) mbar_arrive_remote(rel);
        rel = kb == G2_KB - NSTAGE ? mapa(sb + B_XRDY, rank ^ 1) : sb + B_EMPTY + 8 * r.s;
      }
      if (!wg) bar_arrive(7, 256);
      const uint32_t xz = sb + XSLOT * SLOT + wg * 10240 + wtid * 16;
      const uint32_t rz = mapa(xz, rank ^ 1), rb = mapa(sb + B_XFULL + 8 * wg, rank ^ 1);
      mbar_wait(sb + B_XRDY, 0);
      wg_wait<0>();
      pin_regs<72>(acc);
      if (!w) TLREC(28 + wg);
#pragma unroll
      for (int i = 0; i < 32; i += 8)
        asm volatile("st.async.weak.shared::cluster.mbarrier::complete_tx::bytes.v4.b32 [%0], {%1,%2,%3,%4}, [%5];"
                     :: "r"(rz + i * 256), "r"(pack_bf16(acc[i], acc[i + 1])), "r"(pack_bf16(acc[i + 2], acc[i + 3])),
                        "r"(pack_bf16(acc[i + 4], acc[i + 5])), "r"(pack_bf16(acc[i + 6], acc[i + 7])), "r"(rb) : "memory");
      asm volatile("st.async.weak.shared::cluster.mbarrier::complete_tx::bytes.v2.b32 [%0], {%1,%2}, [%3];"
                   :: "r"(rz + 8192), "r"(pack_bf16(acc[32], acc[33])), "r"(pack_bf16(acc[34], acc[35])), "r"(rb) : "memory");
      uint32_t xx[18], ss[18];
      mbar_wait(sb + B_XY, 0);
      {
        const uint32_t ya = sb + SM_DED + wg * 9216 + swz;
        const uint4 st0 = lds128(sb + SM_ST + (warp * 16 + g) * 16), st1 = lds128(sb + SM_ST + (warp * 16 + g + 8) * 16);
        const float hb0 = 0.5f * bf_lo(lds16(sb + SM_B2 + (warp * 16 + g) * 2)), hb1 = 0.5f * bf_lo(lds16(sb + SM_B2 + (warp * 16 + g + 8) * 2));
#pragma unroll
        for (int q = 0; q < 8; q += 2) { ldsm4(xx + 2 * q, xa + (lane >> 4) * 16 + q * 16); ldsm4t(ss + 2 * q, ya + q * 1024); }
        ldsm2(xx + 16, xa + 128);
        ldsm2t(ss + 16, ya + 8 * 1024);
#pragma unroll
        for (int i = 0; i < 18; i++) {
          const uint4& st = (i & 1) ? st1 : st0;
          const uint32_t c = bsub2(xx[i], st.x);
          ss[i] = bmul2(bfma2(c, st.y, bmul2(c, st.z)), ss[i]);
        }
#pragma unroll
        for (int i = 36; i < 72; i++) acc[i] = fmaf(acc[i], 0.5f, (i & 2) ? hb1 : hb0);
      }
      char* const op = reinterpret_cast<char*>(P.out) + srow * (D_ * 2) + R.dk * 16 + lane * 16;
      uint32_t oo[5];
#pragma unroll
      for (int j = 0; j < 5; j++) oo[j] = ((lane + 32 * j) * 57 >> 9) * (D_ * 2 - 144) + j * 512;
      mbar_wait_cluster(sb + B_XFULL + 8 * wg, 0);
      if (!w) TLREC(9 + wg);
#pragma unroll
      for (int q = 0; q < 5; q++) {
        const uint4 v = lds128(xz + q * 2048);
        const uint32_t pv[4] = {v.x, v.y, v.z, v.w};
#pragma unroll
        for (int i = 4 * q; i < 4 * q + 4 && i < 18; i++)
          xx[i] = bfma2(ss[i], pack_bf16(silu_half(fmaf(bf_lo(pv[i & 3]), 0.5f, acc[36 + 2 * i])), silu_half(fmaf(bf_hi(pv[i & 3]), 0.5f, acc[37 + 2 * i]))), xx[i]);
        if (q < 4) stsm4(xa + (lane >> 4) * 16 + q * 32, xx[4 * q], xx[4 * q + 1], xx[4 * q + 2], xx[4 * q + 3]);
        else stsm2(xa + 128, xx[16], xx[17]);
      }
      __syncwarp();
      if (lane == 0) mbar_arrive(sb + B_DONE);
#pragma unroll
      for (int j = 0; j < 5; j++)
        if (j < 4 || lane < 16) *reinterpret_cast<uint4*>(op + oo[j]) = lds128(xo + (lane + 32 * j) * 16);
      if (!w) TLREC(11 + wg);
    }
    TLEND();
  }
}

typedef CUresult (*EncodeFn)(CUtensorMap*, CUtensorMapDataType, cuuint32_t, void*, const cuuint64_t*, const cuuint64_t*, const cuuint32_t*,
                             const cuuint32_t*, CUtensorMapInterleave, CUtensorMapSwizzle, CUtensorMapL2promotion, CUtensorMapFloatOOBfill);

void make_map(EncodeFn fn, CUtensorMap* m, const void* ptr, int rank, const cuuint64_t* dims, const cuuint64_t* strides, const cuuint32_t* box,
              CUtensorMapSwizzle sw) {
  const cuuint32_t es[3] = {1, 1, 1};
  fn(m, CU_TENSOR_MAP_DATA_TYPE_BFLOAT16, rank, const_cast<void*>(ptr), dims, strides, box, es, CU_TENSOR_MAP_INTERLEAVE_NONE, sw,
     CU_TENSOR_MAP_L2_PROMOTION_L2_256B, CU_TENSOR_MAP_FLOAT_OOB_FILL_NONE);
}

void make_roles(Role* R) {
  int nl = 0, ch = 0;
  for (int gi = 0; gi < 8; gi++)
    for (int b = 0; b < 132; b++) {
      const int c = b >> 1, rank = b & 1;
      int g, idx;
      if (c < 4) { g = 0; idx = 4 + c; }
      else if (c < 36) { g = (c - 4) & 7; idx = (c - 4) >> 3; }
      else if (c < 64) { g = 1 + (c - 36) % 7; idx = 4 + (c - 36) / 7; }
      else { g = c - 58; idx = 8; }
      if (g != gi) continue;
      Role& r = R[b];
      r.sg = (int8_t)(idx < 8 ? 2 * (2 * g + (idx >> 2)) : -1);
      r.dk = (int8_t)((idx & 3) * 18 + rank * 9);
      r.ds = (int8_t)((idx & 3) * 18 + (rank ^ 1) * 9);
      if (idx < (g < 2 ? 6 : 7)) {
        const int c1 = (g < 2 ? 6 * g : 7 * g - 2) + idx;
        r.fg = (int8_t)((2 * (c1 / 3) + rank) * 2); r.at = (int8_t)(c1 % 3 * 5); r.ncv = NCV_REG;
      } else {
        r.fg = (int8_t)(3 * nl++); r.at = 15; r.ncv = idx < 8 ? NCV_LEFT : NCV_LONG;
      }
      r.ch = (int16_t)ch;
      ch += r.ncv;
    }
}

}

extern "C" void kernel_launch(void* const* d_in, const int* in_sizes, int n_in, void* d_out, int out_size) {
  static Params P;
  static Hot H;
  static const void* cached[5] = {nullptr, nullptr, nullptr, nullptr, nullptr};
  const void* now[5] = {d_in[0], d_in[1], d_in[2], d_in[7], d_in[9]};
  bool same = true;
  for (int i = 0; i < 5; i++) { same = same && cached[i] == now[i]; cached[i] = now[i]; }
  if (!same) {
    void* fp = nullptr;
    cudaDriverEntryPointQueryResult qr;
    cudaGetDriverEntryPoint("cuTensorMapEncodeTiled", &fp, cudaEnableDefault, &qr);
    EncodeFn fn = (EncodeFn)fp;
    void* ps;
    cudaGetSymbolAddress(&ps, g_scratch);
    H.S = (Scratch*)ps;
    const void *pu = (char*)ps + offsetof(Scratch, u), *py = (char*)ps + offsetof(Scratch, y), *pb = (char*)ps + offsetof(Scratch, ub);
    { cuuint64_t d[3] = {64, S_, F_ / 64}, s[2] = {F_ * 2, 128}; cuuint32_t b[3] = {64, 64, 2}; make_map(fn, &P.m_w1, d_in[7], 3, d, s, b, CU_TENSOR_MAP_SWIZZLE_128B);
      b[2] = 3; make_map(fn, &P.m_w1l, d_in[7], 3, d, s, b, CU_TENSOR_MAP_SWIZZLE_128B); }
    { cuuint64_t d[2] = {F_, D_}, s[1] = {F_ * 2}; cuuint32_t b[2] = {64, 32}; make_map(fn, &P.m_ust, pu, 2, d, s, b, CU_TENSOR_MAP_SWIZZLE_128B); }
    { cuuint64_t d[3] = {64, F_, S_ / 64}, s[2] = {S_ * 2, 128}; cuuint32_t b[3] = {64, 64, 2}; make_map(fn, &P.m_w2, d_in[9], 3, d, s, b, CU_TENSOR_MAP_SWIZZLE_128B); }
    { cuuint64_t d[2] = {F_, D_}, s[1] = {F_ * 2}; cuuint32_t b[2] = {64, 72}; make_map(fn, &P.m_uld, pu, 2, d, s, b, CU_TENSOR_MAP_SWIZZLE_128B); }
    { cuuint64_t d[2] = {D_, S_}, s[1] = {D_ * 2}; cuuint32_t b[2] = {72, 16}; make_map(fn, &P.m_x, d_in[0], 2, d, s, b, CU_TENSOR_MAP_SWIZZLE_NONE);
      b[0] = 96; b[1] = 20; make_map(fn, &P.m_k, d_in[1], 2, d, s, b, CU_TENSOR_MAP_SWIZZLE_NONE);
      b[1] = 17; make_map(fn, &P.m_v, d_in[2], 2, d, s, b, CU_TENSOR_MAP_SWIZZLE_NONE); }
    { cuuint64_t d[3] = {64, D_, S_ / 64}, s[2] = {S_ * 2, 128}; cuuint32_t b[3] = {64, 72, 2}; make_map(fn, &P.m_y, py, 3, d, s, b, CU_TENSOR_MAP_SWIZZLE_128B); }
    { cuuint64_t d[3] = {2048, D_ / 2, 4}, s[2] = {16384, 4096}; cuuint32_t b[3] = {16, 48, 2}; make_map(fn, &P.m_ub, pb, 3, d, s, b, CU_TENSOR_MAP_SWIZZLE_32B); }
    make_roles(P.role);
    cudaFuncSetAttribute(fused_kernel, cudaFuncAttributeMaxDynamicSharedMemorySize, SM_TOTAL);
  }
  H.x = (const __nv_bfloat16*)d_in[0];
  H.shift_k = (const __nv_bfloat16*)d_in[3]; H.ssm_k = (const __nv_bfloat16*)d_in[4]; H.ssm_D = (const __nv_bfloat16*)d_in[5];
  H.b1 = (const __nv_bfloat16*)d_in[8]; P.b2 = (const __nv_bfloat16*)d_in[10]; P.out = (__nv_bfloat16*)d_out;
  fused_kernel<<<132, 384, SM_TOTAL>>>(H, P);
}
```

```cpp
#include <cuda_runtime.h>
#include <cuda.h>
#include <cuda_bf16.h>
#include <stddef.h>
#include <stdint.h>

namespace {

constexpr int S_ = 2048, D_ = 576, F_ = 4608;
constexpr int NSTAGE = 5, SLOT = 36864;
constexpr int G1_KB = 32, G2_KB = 36;
constexpr int G1_BYTES = 36864, G2_BYTES = 16384 + 18432;
#define NCV_LEFT 4
constexpr int NCV_REG = 4, NCV_LONG = (D_ - 108 * NCV_REG - 20 * NCV_LEFT) / 4;
static_assert(108 * NCV_REG + 20 * NCV_LEFT + 4 * NCV_LONG == D_, "conv split");
constexpr int KV_ROUNDS = 6;
#define XP 2
constexpr int NWE = 1, NW0 = 2;
constexpr int G1_TAIL = 4, G2_TAIL = 3;
constexpr int SYNCA = 5, SYNCKB = 8;
constexpr int PRE1 = 1;
constexpr int KV0 = 5;

constexpr int CV_K = 4224, CV_REDW = 2112 * 2;
constexpr int SM_DED = NSTAGE * SLOT;
constexpr int SM_CV = SM_DED + 20480;
constexpr int SM_ST1 = 0;
constexpr int SM_ST = SM_CV + 18432, SM_B2 = SM_ST + 2048;
constexpr int SM_B1 = SM_CV + 2 * (8192 + CV_K), SM_D = SM_B1 + 384;
constexpr int SM_BAR = SM_D + 1152;
constexpr int SM_TOTAL = SM_BAR + 768;
static_assert(G1_KB % NSTAGE == 2, "slots 0 and 1 hold the last GEMM1 k-blocks and the last two of the first GEMM2 stages");
static_assert(NCV_REG == 4 && NCV_LEFT == 4 && NCV_LONG % 4 == 0, "the last two channels use buffers 2 and 3");
constexpr int XSLOT = (G1_KB + G2_KB) % NSTAGE;
__device__ __forceinline__ uint32_t kv_buf(int q) { return q == 2 ? SM_DED : SM_CV + q * 8192; }
__device__ __forceinline__ uint32_t cv_red(int i, int n) { return i + 2 == n ? SM_CV : (i & 1) && i + 1 < n ? SLOT + 16384 : SM_DED; }
__device__ __forceinline__ uint32_t cv_in(int i) { return (i & 2 ? SLOT : SM_CV) + (i & 1) * 8192; }
__device__ __forceinline__ uint32_t cv_taps(int i) { return (i & 2 ? SM_ST1 + 24576 : SM_CV + 16384) + (i & 1) * CV_K; }
constexpr int bar_at(int i) { return SM_BAR + 8 * i; }
constexpr int B_FULL = bar_at(0)  , B_KFULL = bar_at(5)  , B_UFULL = bar_at(9)  , B_KVDONE = bar_at(13), B_STORED = bar_at(14)  ,
              B_XFULL = bar_at(16)  , B_XY = bar_at(20), B_MISC = bar_at(21),
              B_EMPTY = bar_at(22)  , B_XRDY = bar_at(27),
              B_SFREE = bar_at(28)  , B_PDONE = bar_at(30),
              B_CEMPTY = bar_at(31)  , B_STG = bar_at(35)  ,
              B_G1DONE = bar_at(39), B_DONE = bar_at(40);
constexpr int C_H = 0, C_KV = 1, C_U = 2  , C_Y = 4, C_SYNC = 5, C_EPOCH = 6, C_COUNT = 7;
constexpr uint32_t EPOCH = 128 * 33;

struct Scratch {
  uint32_t cnt[C_COUNT * 32];
  alignas(1024) uint4 stats[S_];
  alignas(1024) __nv_bfloat16 h[S_ * D_];
  alignas(1024) __nv_bfloat16 ub[D_ * 4096];
  alignas(1024) __nv_bfloat16 y[D_ * S_];
  alignas(1024) __nv_bfloat16 u[D_ * F_];
};
__device__ Scratch g_scratch;

struct Hot {
  const __nv_bfloat16 *x, *shift_k, *ssm_k, *ssm_D, *b1;
  Scratch* S;
};
struct Role {
  int8_t fg;
  int8_t at;
  int8_t sg;
  int8_t dk, ds;
  int8_t ncv;
  int16_t ch;
};
struct Params {
  const __nv_bfloat16* b2;
  __nv_bfloat16* out;
  Role role[132];
  CUtensorMap m_w1, m_w1l, m_ust, m_w2, m_uld, m_x, m_y, m_k, m_v, m_ub;
};

#define TLREC(i) do { } while (0)
#define TLEND() do { } while (0)

__device__ __forceinline__ uint32_t smem_u32(const void* p) { return (uint32_t)__cvta_generic_to_shared(p); }
__device__ __forceinline__ void mbar_init(uint32_t bar, uint32_t cnt) { asm volatile("mbarrier.init.shared::cta.b64 [%0], %1;" :: "r"(bar), "r"(cnt) : "memory"); }
__device__ __forceinline__ void mbar_expect_tx(uint32_t bar, uint32_t bytes) { asm volatile("mbarrier.arrive.expect_tx.shared::cta.b64 _, [%0], %1;" :: "r"(bar), "r"(bytes) : "memory"); }
__device__ __forceinline__ void mbar_arrive(uint32_t bar) { asm volatile("mbarrier.arrive.shared::cta.b64 _, [%0];" :: "r"(bar) : "memory"); }
__device__ __forceinline__ uint32_t mapa(uint32_t addr, uint32_t cta) { uint32_t r; asm volatile("mapa.shared::cluster.u32 %0, %1, %2;" : "=r"(r) : "r"(addr), "r"(cta)); return r; }
__device__ __forceinline__ void mbar_arrive_remote(uint32_t rbar) { asm volatile("mbarrier.arrive.shared::cluster.b64 _, [%0];" :: "r"(rbar) : "memory"); }
__device__ __forceinline__ uint32_t clk() { uint32_t c; asm volatile("mov.u32 %0, %%clock;" : "=r"(c)); return c; }
__device__ __forceinline__ bool elect_one() {
  uint32_t p; asm volatile("{ .reg .pred p; elect.sync _|p, 0xffffffff; selp.u32 %0, 1, 0, p; }" : "=r"(p)); return p;
}
__device__ __forceinline__ void guard(uint32_t t0) { if ((int32_t)(clk() - t0) < 0) __trap(); }
__device__ __forceinline__ void mbar_wait(uint32_t bar, uint32_t parity) {
  asm volatile("{\n .reg .pred p;\n W_%=:\n mbarrier.try_wait.parity.shared::cta.b64 p, [%0], %1;\n @!p bra W_%=;\n }" :: "r"(bar), "r"(parity) : "memory");
}
__device__ __forceinline__ void mbar_wait_cluster(uint32_t bar, uint32_t parity) {
  asm volatile("{\n .reg .pred p;\n W_%=:\n mbarrier.try_wait.parity.acquire.cluster.shared::cta.b64 p, [%0], %1;\n @!p bra W_%=;\n }" :: "r"(bar), "r"(parity) : "memory");
}
__device__ __forceinline__ bool mbar_try(uint32_t bar, uint32_t parity) {
  uint32_t ok;
  asm volatile("{ .reg .pred p; mbarrier.try_wait.parity.shared::cta.b64 p, [%1], %2, 100000; selp.u32 %0, 1, 0, p; }" : "=r"(ok) : "r"(bar), "r"(parity) : "memory");
  return ok;
}
__device__ __forceinline__ bool mbar_test(uint32_t bar, uint32_t parity) {
  uint32_t ok;
  asm volatile("{ .reg .pred p; mbarrier.test_wait.parity.shared::cta.b64 p, [%1], %2; selp.u32 %0, 1, 0, p; }" : "=r"(ok) : "r"(bar), "r"(parity) : "memory");
  return ok;
}
__device__ __forceinline__ void mbar_wait_guarded(uint32_t bar, uint32_t t0, uint32_t parity = 0) { while (!mbar_try(bar, parity)) guard(t0); }
__device__ __forceinline__ void tma2d(uint32_t dst, const CUtensorMap* m, int c0, int c1, uint32_t bar) {
  asm volatile("cp.async.bulk.tensor.2d.shared::cluster.global.mbarrier::complete_tx::bytes [%0], [%1, {%3, %4}], [%2];"
               :: "r"(dst), "l"(m), "r"(bar), "r"(c0), "r"(c1) : "memory");
}
__device__ __forceinline__ void tma3d(uint32_t dst, const CUtensorMap* m, int c0, int c1, int c2, uint32_t bar) {
  asm volatile("cp.async.bulk.tensor.3d.shared::cluster.global.mbarrier::complete_tx::bytes [%0], [%1, {%3, %4, %5}], [%2];"
               :: "r"(dst), "l"(m), "r"(bar), "r"(c0), "r"(c1), "r"(c2) : "memory");
}
__device__ __forceinline__ void tma2d_store(const CUtensorMap* m, uint32_t src, int c0, int c1) {
  asm volatile("cp.async.bulk.tensor.2d.global.shared::cta.bulk_group [%0, {%2, %3}], [%1];" :: "l"(m), "r"(src), "r"(c0), "r"(c1) : "memory");
}
__device__ __forceinline__ void bulk_load(uint32_t dst, const void* src, uint32_t bytes, uint32_t bar) {
  asm volatile("cp.async.bulk.shared::cluster.global.mbarrier::complete_tx::bytes [%0], [%1], %2, [%3];" :: "r"(dst), "l"(src), "r"(bytes), "r"(bar) : "memory");
}
__device__ __forceinline__ void tma3d_store(const CUtensorMap* m, uint32_t src, int c0, int c1, int c2) {
  asm volatile("cp.async.bulk.tensor.3d.global.shared::cta.bulk_group [%0, {%2, %3, %4}], [%1];" :: "l"(m), "r"(src), "r"(c0), "r"(c1), "r"(c2) : "memory");
}
__device__ __forceinline__ void bulk_commit() { asm volatile("cp.async.bulk.commit_group;" ::: "memory"); }
__device__ __forceinline__ void bulk_wait_all() { asm volatile("cp.async.bulk.wait_group 0;" ::: "memory"); }
__device__ __forceinline__ void fence_async_smem() { asm volatile("fence.proxy.async.shared::cta;" ::: "memory"); }
__device__ __forceinline__ void fence_async_global() { asm volatile("fence.proxy.async.global;" ::: "memory"); }
__device__ __forceinline__ uint32_t ld_cnt(Scratch* S, int c) { uint32_t v; asm volatile("ld.relaxed.gpu.global.u32 %0, [%1];" : "=r"(v) : "l"(S->cnt + c * 32) : "memory"); return v; }
__device__ __forceinline__ void signal(Scratch* S, int c, uint32_t inc) { asm volatile("red.release.gpu.global.add.u32 [%0], %1;" :: "l"(S->cnt + c * 32), "r"(inc) : "memory"); }
__device__ __forceinline__ bool reached(Scratch* S, int c, uint32_t ep) { return ld_cnt(S, c) - ep >= EPOCH; }
__device__ __forceinline__ void await(Scratch* S, int c, uint32_t ep) { while (!reached(S, c, ep)) { } }
__device__ __forceinline__ void bar_sync(int id, int n) { asm volatile("bar.sync %0, %1;" :: "r"(id), "r"(n) : "memory"); }
__device__ __forceinline__ void bar_arrive(int id, int n) { asm volatile("bar.arrive %0, %1;" :: "r"(id), "r"(n) : "memory"); }
__device__ __forceinline__ void wg_fence() { asm volatile("wgmma.fence.sync.aligned;" ::: "memory"); }
__device__ __forceinline__ void wg_commit() { asm volatile("wgmma.commit_group.sync.aligned;" ::: "memory"); }
template <int N> __device__ __forceinline__ void wg_wait() { asm volatile("wgmma.wait_group.sync.aligned %0;" :: "n"(N) : "memory"); }
template <int N> __device__ __forceinline__ void pin_regs(float* a) {
#pragma unroll
  for (int i = 0; i < N; i++) asm volatile("" : "+f"(a[i]) :: "memory");
}
__device__ __forceinline__ uint64_t make_desc(uint32_t addr, uint32_t lbo, uint32_t sbo, uint32_t swz) {
  return (uint64_t)((addr & 0x3FFFF) >> 4) | ((uint64_t)(lbo >> 4) << 16) | ((uint64_t)(sbo >> 4) << 32) | ((uint64_t)swz << 62);
}
__device__ __forceinline__ uint32_t pack_bf16(float lo, float hi) { uint32_t r; asm("cvt.rn.bf16x2.f32 %0, %1, %2;" : "=r"(r) : "f"(hi), "f"(lo)); return r; }
__device__ __forceinline__ float bf_lo(uint32_t p) { return __uint_as_float(p << 16); }
__device__ __forceinline__ float bf_hi(uint32_t p) { return __uint_as_float(p & 0xffff0000u); }
__device__ __forceinline__ float round_bf16(float v) { return bf_lo(pack_bf16(v, 0.f)); }
__device__ __forceinline__ uint32_t bmul2(uint32_t a, uint32_t b) { uint32_t r; asm("mul.rn.bf16x2 %0, %1, %2;" : "=r"(r) : "r"(a), "r"(b)); return r; }
__device__ __forceinline__ uint32_t badd2(uint32_t a, uint32_t b) { uint32_t r; asm("add.rn.bf16x2 %0, %1, %2;" : "=r"(r) : "r"(a), "r"(b)); return r; }
__device__ __forceinline__ uint32_t bfma2(uint32_t a, uint32_t b, uint32_t c) { uint32_t r; asm("fma.rn.bf16x2 %0, %1, %2, %3;" : "=r"(r) : "r"(a), "r"(b), "r"(c)); return r; }
__device__ __forceinline__ uint32_t bsub2(uint32_t a, uint32_t b) { uint32_t r; asm("sub.rn.bf16x2 %0, %1, %2;" : "=r"(r) : "r"(a), "r"(b)); return r; }
__device__ __forceinline__ float tanh_fast(float v) { float r; asm("tanh.approx.f32 %0, %1;" : "=f"(r) : "f"(v)); return r; }
__device__ __forceinline__ float gelu_half(float h) {
  return fmaf(h, tanh_fast(h * fmaf(h * h, 8.0f * 0.7978845608028654f * 0.044715f, 2.0f * 0.7978845608028654f)), h);
}
__device__ __forceinline__ float silu_half(float h) { return fmaf(h, tanh_fast(h), h); }
__device__ __forceinline__ uint32_t ldg32(const void* p) { uint32_t v; asm volatile("ld.global.u32 %0, [%1];" : "=r"(v) : "l"(p) : "memory"); return v; }
__device__ __forceinline__ uint32_t lds32(uint32_t a) { uint32_t v; asm volatile("ld.shared.u32 %0, [%1];" : "=r"(v) : "r"(a) : "memory"); return v; }
__device__ __forceinline__ uint32_t lds16(uint32_t a) { uint32_t v; asm volatile("ld.shared.u16 %0, [%1];" : "=r"(v) : "r"(a) : "memory"); return v; }
__device__ __forceinline__ uint4 lds128(uint32_t a) { uint4 v; asm volatile("ld.shared.v4.u32 {%0,%1,%2,%3}, [%4];" : "=r"(v.x), "=r"(v.y), "=r"(v.z), "=r"(v.w) : "r"(a) : "memory"); return v; }
__device__ __forceinline__ void sts128(uint32_t a, uint32_t x, uint32_t y, uint32_t z, uint32_t w) {
  asm volatile("st.shared.v4.u32 [%0], {%1,%2,%3,%4};" :: "r"(a), "r"(x), "r"(y), "r"(z), "r"(w) : "memory");
}
__device__ __forceinline__ void sts32(uint32_t a, uint32_t v) { asm volatile("st.shared.u32 [%0], %1;" :: "r"(a), "r"(v) : "memory"); }
__device__ __forceinline__ void ldsm4(uint32_t* r, uint32_t a) {
  asm volatile("ldmatrix.sync.aligned.m8n8.x4.shared.b16 {%0,%1,%2,%3}, [%4];" : "=r"(r[0]), "=r"(r[1]), "=r"(r[2]), "=r"(r[3]) : "r"(a) : "memory");
}
__device__ __forceinline__ void ldsm2(uint32_t* r, uint32_t a) {
  asm volatile("ldmatrix.sync.aligned.m8n8.x2.shared.b16 {%0,%1}, [%2];" : "=r"(r[0]), "=r"(r[1]) : "r"(a) : "memory");
}
__device__ __forceinline__ void ldsm4t(uint32_t* r, uint32_t a) {
  asm volatile("ldmatrix.sync.aligned.m8n8.x4.trans.shared.b16 {%0,%1,%2,%3}, [%4];" : "=r"(r[0]), "=r"(r[1]), "=r"(r[2]), "=r"(r[3]) : "r"(a) : "memory");
}
__device__ __forceinline__ void ldsm2t(uint32_t* r, uint32_t a) {
  asm volatile("ldmatrix.sync.aligned.m8n8.x2.trans.shared.b16 {%0,%1}, [%2];" : "=r"(r[0]), "=r"(r[1]) : "r"(a) : "memory");
}
__device__ __forceinline__ void stsm4(uint32_t a, uint32_t r0, uint32_t r1, uint32_t r2, uint32_t r3) {
  asm volatile("stmatrix.sync.aligned.m8n8.x4.shared.b16 [%0], {%1,%2,%3,%4};" :: "r"(a), "r"(r0), "r"(r1), "r"(r2), "r"(r3) : "memory");
}
__device__ __forceinline__ void stsm2(uint32_t a, uint32_t r0, uint32_t r1) {
  asm volatile("stmatrix.sync.aligned.m8n8.x2.shared.b16 [%0], {%1,%2};" :: "r"(a), "r"(r0), "r"(r1) : "memory");
}
__device__ __forceinline__ void stsm4t(uint32_t a, uint32_t r0, uint32_t r1, uint32_t r2, uint32_t r3) {
  asm volatile("stmatrix.sync.aligned.m8n8.x4.trans.shared.b16 [%0], {%1,%2,%3,%4};" :: "r"(a), "r"(r0), "r"(r1), "r"(r2), "r"(r3) : "memory");
}

__device__ __forceinline__ void wgmma_ss_n144_t10(float* d, uint64_t da, uint64_t db, int sd) {
  asm volatile("{ .reg .pred p; setp.ne.b32 p, %74, 0;\n"
      "wgmma.mma_async.sync.aligned.m64n144k16.f32.bf16.bf16 {"
      "%0,%1,%2,%3,%4,%5,%6,%7,%8,%9,%10,%11,%12,%13,%14,%15,"
      "%16,%17,%18,%19,%20,%21,%22,%23,%24,%25,%26,%27,%28,%29,%30,%31,"
      "%32,%33,%34,%35,%36,%37,%38,%39,%40,%41,%42,%43,%44,%45,%46,%47,"
      "%48,%49,%50,%51,%52,%53,%54,%55,%56,%57,%58,%59,%60,%61,%62,%63,"
      "%64,%65,%66,%67,%68,%69,%70,%71"
      "}, %72, %73, p, 1, 1, 1, 0; }"
    : "+f"(d[0]), "+f"(d[1]), "+f"(d[2]), "+f"(d[3]), "+f"(d[4]), "+f"(d[5]), "+f"(d[6]), "+f"(d[7]),
      "+f"(d[8]), "+f"(d[9]), "+f"(d[10]), "+f"(d[11]), "+f"(d[12]), "+f"(d[13]), "+f"(d[14]), "+f"(d[15]),
      "+f"(d[16]), "+f"(d[17]), "+f"(d[18]), "+f"(d[19]), "+f"(d[20]), "+f"(d[21]), "+f"(d[22]), "+f"(d[23]),
      "+f"(d[24]), "+f"(d[25]), "+f"(d[26]), "+f"(d[27]), "+f"(d[28]), "+f"(d[29]), "+f"(d[30]), "+f"(d[31]),
      "+f"(d[32]), "+f"(d[33]), "+f"(d[34]), "+f"(d[35]), "+f"(d[36]), "+f"(d[37]), "+f"(d[38]), "+f"(d[39]),
      "+f"(d[40]), "+f"(d[41]), "+f"(d[42]), "+f"(d[43]), "+f"(d[44]), "+f"(d[45]), "+f"(d[46]), "+f"(d[47]),
      "+f"(d[48]), "+f"(d[49]), "+f"(d[50]), "+f"(d[51]), "+f"(d[52]), "+f"(d[53]), "+f"(d[54]), "+f"(d[55]),
      "+f"(d[56]), "+f"(d[57]), "+f"(d[58]), "+f"(d[59]), "+f"(d[60]), "+f"(d[61]), "+f"(d[62]), "+f"(d[63]),
      "+f"(d[64]), "+f"(d[65]), "+f"(d[66]), "+f"(d[67]), "+f"(d[68]), "+f"(d[69]), "+f"(d[70]), "+f"(d[71])
    : "l"(da), "l"(db), "r"(sd));
}

__device__ __forceinline__ void wgmma_ss_n160_t11(float* d, uint64_t da, uint64_t db, int sd) {
  asm volatile("{ .reg .pred p; setp.ne.b32 p, %82, 0;\n"
      "wgmma.mma_async.sync.aligned.m64n160k16.f32.bf16.bf16 {"
      "%0,%1,%2,%3,%4,%5,%6,%7,%8,%9,%10,%11,%12,%13,%14,%15,"
      "%16,%17,%18,%19,%20,%21,%22,%23,%24,%25,%26,%27,%28,%29,%30,%31,"
      "%32,%33,%34,%35,%36,%37,%38,%39,%40,%41,%42,%43,%44,%45,%46,%47,"
      "%48,%49,%50,%51,%52,%53,%54,%55,%56,%57,%58,%59,%60,%61,%62,%63,"
      "%64,%65,%66,%67,%68,%69,%70,%71,%72,%73,%74,%75,%76,%77,%78,%79"
      "}, %80, %81, p, 1, 1, 1, 1; }"
    : "+f"(d[0]), "+f"(d[1]), "+f"(d[2]), "+f"(d[3]), "+f"(d[4]), "+f"(d[5]), "+f"(d[6]), "+f"(d[7]),
      "+f"(d[8]), "+f"(d[9]), "+f"(d[10]), "+f"(d[11]), "+f"(d[12]), "+f"(d[13]), "+f"(d[14]), "+f"(d[15]),
      "+f"(d[16]), "+f"(d[17]), "+f"(d[18]), "+f"(d[19]), "+f"(d[20]), "+f"(d[21]), "+f"(d[22]), "+f"(d[23]),
      "+f"(d[24]), "+f"(d[25]), "+f"(d[26]), "+f"(d[27]), "+f"(d[28]), "+f"(d[29]), "+f"(d[30]), "+f"(d[31]),
      "+f"(d[32]), "+f"(d[33]), "+f"(d[34]), "+f"(d[35]), "+f"(d[36]), "+f"(d[37]), "+f"(d[38]), "+f"(d[39]),
      "+f"(d[40]), "+f"(d[41]), "+f"(d[42]), "+f"(d[43]), "+f"(d[44]), "+f"(d[45]), "+f"(d[46]), "+f"(d[47]),
      "+f"(d[48]), "+f"(d[49]), "+f"(d[50]), "+f"(d[51]), "+f"(d[52]), "+f"(d[53]), "+f"(d[54]), "+f"(d[55]),
      "+f"(d[56]), "+f"(d[57]), "+f"(d[58]), "+f"(d[59]), "+f"(d[60]), "+f"(d[61]), "+f"(d[62]), "+f"(d[63]),
      "+f"(d[64]), "+f"(d[65]), "+f"(d[66]), "+f"(d[67]), "+f"(d[68]), "+f"(d[69]), "+f"(d[70]), "+f"(d[71]),
      "+f"(d[72]), "+f"(d[73]), "+f"(d[74]), "+f"(d[75]), "+f"(d[76]), "+f"(d[77]), "+f"(d[78]), "+f"(d[79])
    : "l"(da), "l"(db), "r"(sd));
}

__device__ __forceinline__ void wgmma_ss_n96_t11(float* d, uint64_t da, uint64_t db, int sd) {
  asm volatile("{ .reg .pred p; setp.ne.b32 p, %50, 0;\n"
      "wgmma.mma_async.sync.aligned.m64n96k16.f32.bf16.bf16 {"
      "%0,%1,%2,%3,%4,%5,%6,%7,%8,%9,%10,%11,%12,%13,%14,%15,"
      "%16,%17,%18,%19,%20,%21,%22,%23,%24,%25,%26,%27,%28,%29,%30,%31,"
      "%32,%33,%34,%35,%36,%37,%38,%39,%40,%41,%42,%43,%44,%45,%46,%47"
      "}, %48, %49, p, 1, 1, 1, 1; }"
    : "+f"(d[0]), "+f"(d[1]), "+f"(d[2]), "+f"(d[3]), "+f"(d[4]), "+f"(d[5]), "+f"(d[6]), "+f"(d[7]),
      "+f"(d[8]), "+f"(d[9]), "+f"(d[10]), "+f"(d[11]), "+f"(d[12]), "+f"(d[13]), "+f"(d[14]), "+f"(d[15]),
      "+f"(d[16]), "+f"(d[17]), "+f"(d[18]), "+f"(d[19]), "+f"(d[20]), "+f"(d[21]), "+f"(d[22]), "+f"(d[23]),
      "+f"(d[24]), "+f"(d[25]), "+f"(d[26]), "+f"(d[27]), "+f"(d[28]), "+f"(d[29]), "+f"(d[30]), "+f"(d[31]),
      "+f"(d[32]), "+f"(d[33]), "+f"(d[34]), "+f"(d[35]), "+f"(d[36]), "+f"(d[37]), "+f"(d[38]), "+f"(d[39]),
      "+f"(d[40]), "+f"(d[41]), "+f"(d[42]), "+f"(d[43]), "+f"(d[44]), "+f"(d[45]), "+f"(d[46]), "+f"(d[47])
    : "l"(da), "l"(db), "r"(sd));
}

__device__ __forceinline__ void wgmma_rs_n16(float* d, const uint32_t* a, uint64_t db, int sd) {
  asm volatile("{ .reg .pred p; setp.ne.b32 p, %13, 0;\n"
      "wgmma.mma_async.sync.aligned.m64n16k16.f32.bf16.bf16 {"
      "%0,%1,%2,%3,%4,%5,%6,%7"
      "}, {%8,%9,%10,%11}, %12, p, 1, 1, 0; }"
    : "+f"(d[0]), "+f"(d[1]), "+f"(d[2]), "+f"(d[3]), "+f"(d[4]), "+f"(d[5]), "+f"(d[6]), "+f"(d[7])
    : "r"(a[0]), "r"(a[1]), "r"(a[2]), "r"(a[3]), "l"(db), "r"(sd));
}

__device__ __forceinline__ void wgmma_rs_n32(float* d, const uint32_t* a, uint64_t db, int sd) {
  asm volatile("{ .reg .pred p; setp.ne.b32 p, %21, 0;\n"
      "wgmma.mma_async.sync.aligned.m64n32k16.f32.bf16.bf16 {"
      "%0,%1,%2,%3,%4,%5,%6,%7,%8,%9,%10,%11,%12,%13,%14,%15"
      "}, {%16,%17,%18,%19}, %20, p, 1, 1, 0; }"
    : "+f"(d[0]), "+f"(d[1]), "+f"(d[2]), "+f"(d[3]), "+f"(d[4]), "+f"(d[5]), "+f"(d[6]), "+f"(d[7]),
      "+f"(d[8]), "+f"(d[9]), "+f"(d[10]), "+f"(d[11]), "+f"(d[12]), "+f"(d[13]), "+f"(d[14]), "+f"(d[15])
    : "r"(a[0]), "r"(a[1]), "r"(a[2]), "r"(a[3]), "l"(db), "r"(sd));
}

__device__ __forceinline__ void wgmma_rs_n48(float* d, const uint32_t* a, uint64_t db, int sd) {
  asm volatile("{ .reg .pred p; setp.ne.b32 p, %29, 0;\n"
      "wgmma.mma_async.sync.aligned.m64n48k16.f32.bf16.bf16 {"
      "%0,%1,%2,%3,%4,%5,%6,%7,%8,%9,%10,%11,%12,%13,%14,%15,"
      "%16,%17,%18,%19,%20,%21,%22,%23"
      "}, {%24,%25,%26,%27}, %28, p, 1, 1, 0; }"
    : "+f"(d[0]), "+f"(d[1]), "+f"(d[2]), "+f"(d[3]), "+f"(d[4]), "+f"(d[5]), "+f"(d[6]), "+f"(d[7]),
      "+f"(d[8]), "+f"(d[9]), "+f"(d[10]), "+f"(d[11]), "+f"(d[12]), "+f"(d[13]), "+f"(d[14]), "+f"(d[15]),
      "+f"(d[16]), "+f"(d[17]), "+f"(d[18]), "+f"(d[19]), "+f"(d[20]), "+f"(d[21]), "+f"(d[22]), "+f"(d[23])
    : "r"(a[0]), "r"(a[1]), "r"(a[2]), "r"(a[3]), "l"(db), "r"(sd));
}

__device__ __forceinline__ void wgmma_rs_n64(float* d, const uint32_t* a, uint64_t db, int sd) {
  asm volatile("{ .reg .pred p; setp.ne.b32 p, %37, 0;\n"
      "wgmma.mma_async.sync.aligned.m64n64k16.f32.bf16.bf16 {"
      "%0,%1,%2,%3,%4,%5,%6,%7,%8,%9,%10,%11,%12,%13,%14,%15,"
      "%16,%17,%18,%19,%20,%21,%22,%23,%24,%25,%26,%27,%28,%29,%30,%31"
      "}, {%32,%33,%34,%35}, %36, p, 1, 1, 0; }"
    : "+f"(d[0]), "+f"(d[1]), "+f"(d[2]), "+f"(d[3]), "+f"(d[4]), "+f"(d[5]), "+f"(d[6]), "+f"(d[7]),
      "+f"(d[8]), "+f"(d[9]), "+f"(d[10]), "+f"(d[11]), "+f"(d[12]), "+f"(d[13]), "+f"(d[14]), "+f"(d[15]),
      "+f"(d[16]), "+f"(d[17]), "+f"(d[18]), "+f"(d[19]), "+f"(d[20]), "+f"(d[21]), "+f"(d[22]), "+f"(d[23]),
      "+f"(d[24]), "+f"(d[25]), "+f"(d[26]), "+f"(d[27]), "+f"(d[28]), "+f"(d[29]), "+f"(d[30]), "+f"(d[31])
    : "r"(a[0]), "r"(a[1]), "r"(a[2]), "r"(a[3]), "l"(db), "r"(sd));
}

__device__ __forceinline__ void wgmma_rs_n80(float* d, const uint32_t* a, uint64_t db, int sd) {
  asm volatile("{ .reg .pred p; setp.ne.b32 p, %45, 0;\n"
      "wgmma.mma_async.sync.aligned.m64n80k16.f32.bf16.bf16 {"
      "%0,%1,%2,%3,%4,%5,%6,%7,%8,%9,%10,%11,%12,%13,%14,%15,"
      "%16,%17,%18,%19,%20,%21,%22,%23,%24,%25,%26,%27,%28,%29,%30,%31,"
      "%32,%33,%34,%35,%36,%37,%38,%39"
      "}, {%40,%41,%42,%43}, %44, p, 1, 1, 0; }"
    : "+f"(d[0]), "+f"(d[1]), "+f"(d[2]), "+f"(d[3]), "+f"(d[4]), "+f"(d[5]), "+f"(d[6]), "+f"(d[7]),
      "+f"(d[8]), "+f"(d[9]), "+f"(d[10]), "+f"(d[11]), "+f"(d[12]), "+f"(d[13]), "+f"(d[14]), "+f"(d[15]),
      "+f"(d[16]), "+f"(d[17]), "+f"(d[18]), "+f"(d[19]), "+f"(d[20]), "+f"(d[21]), "+f"(d[22]), "+f"(d[23]),
      "+f"(d[24]), "+f"(d[25]), "+f"(d[26]), "+f"(d[27]), "+f"(d[28]), "+f"(d[29]), "+f"(d[30]), "+f"(d[31]),
      "+f"(d[32]), "+f"(d[33]), "+f"(d[34]), "+f"(d[35]), "+f"(d[36]), "+f"(d[37]), "+f"(d[38]), "+f"(d[39])
    : "r"(a[0]), "r"(a[1]), "r"(a[2]), "r"(a[3]), "l"(db), "r"(sd));
}

__device__ __forceinline__ void wgmma_rs_n96(float* d, const uint32_t* a, uint64_t db, int sd) {
  asm volatile("{ .reg .pred p; setp.ne.b32 p, %53, 0;\n"
      "wgmma.mma_async.sync.aligned.m64n96k16.f32.bf16.bf16 {"
      "%0,%1,%2,%3,%4,%5,%6,%7,%8,%9,%10,%11,%12,%13,%14,%15,"
      "%16,%17,%18,%19,%20,%21,%22,%23,%24,%25,%26,%27,%28,%29,%30,%31,"
      "%32,%33,%34,%35,%36,%37,%38,%39,%40,%41,%42,%43,%44,%45,%46,%47"
      "}, {%48,%49,%50,%51}, %52, p, 1, 1, 0; }"
    : "+f"(d[0]), "+f"(d[1]), "+f"(d[2]), "+f"(d[3]), "+f"(d[4]), "+f"(d[5]), "+f"(d[6]), "+f"(d[7]),
      "+f"(d[8]), "+f"(d[9]), "+f"(d[10]), "+f"(d[11]), "+f"(d[12]), "+f"(d[13]), "+f"(d[14]), "+f"(d[15]),
      "+f"(d[16]), "+f"(d[17]), "+f"(d[18]), "+f"(d[19]), "+f"(d[20]), "+f"(d[21]), "+f"(d[22]), "+f"(d[23]),
      "+f"(d[24]), "+f"(d[25]), "+f"(d[26]), "+f"(d[27]), "+f"(d[28]), "+f"(d[29]), "+f"(d[30]), "+f"(d[31]),
      "+f"(d[32]), "+f"(d[33]), "+f"(d[34]), "+f"(d[35]), "+f"(d[36]), "+f"(d[37]), "+f"(d[38]), "+f"(d[39]),
      "+f"(d[40]), "+f"(d[41]), "+f"(d[42]), "+f"(d[43]), "+f"(d[44]), "+f"(d[45]), "+f"(d[46]), "+f"(d[47])
    : "r"(a[0]), "r"(a[1]), "r"(a[2]), "r"(a[3]), "l"(db), "r"(sd));
}

__device__ __forceinline__ void wgmma_rs_n112(float* d, const uint32_t* a, uint64_t db, int sd) {
  asm volatile("{ .reg .pred p; setp.ne.b32 p, %61, 0;\n"
      "wgmma.mma_async.sync.aligned.m64n112k16.f32.bf16.bf16 {"
      "%0,%1,%2,%3,%4,%5,%6,%7,%8,%9,%10,%11,%12,%13,%14,%15,"
      "%16,%17,%18,%19,%20,%21,%22,%23,%24,%25,%26,%27,%28,%29,%30,%31,"
      "%32,%33,%34,%35,%36,%37,%38,%39,%40,%41,%42,%43,%44,%45,%46,%47,"
      "%48,%49,%50,%51,%52,%53,%54,%55"
      "}, {%56,%57,%58,%59}, %60, p, 1, 1, 0; }"
    : "+f"(d[0]), "+f"(d[1]), "+f"(d[2]), "+f"(d[3]), "+f"(d[4]), "+f"(d[5]), "+f"(d[6]), "+f"(d[7]),
      "+f"(d[8]), "+f"(d[9]), "+f"(d[10]), "+f"(d[11]), "+f"(d[12]), "+f"(d[13]), "+f"(d[14]), "+f"(d[15]),
      "+f"(d[16]), "+f"(d[17]), "+f"(d[18]), "+f"(d[19]), "+f"(d[20]), "+f"(d[21]), "+f"(d[22]), "+f"(d[23]),
      "+f"(d[24]), "+f"(d[25]), "+f"(d[26]), "+f"(d[27]), "+f"(d[28]), "+f"(d[29]), "+f"(d[30]), "+f"(d[31]),
      "+f"(d[32]), "+f"(d[33]), "+f"(d[34]), "+f"(d[35]), "+f"(d[36]), "+f"(d[37]), "+f"(d[38]), "+f"(d[39]),
      "+f"(d[40]), "+f"(d[41]), "+f"(d[42]), "+f"(d[43]), "+f"(d[44]), "+f"(d[45]), "+f"(d[46]), "+f"(d[47]),
      "+f"(d[48]), "+f"(d[49]), "+f"(d[50]), "+f"(d[51]), "+f"(d[52]), "+f"(d[53]), "+f"(d[54]), "+f"(d[55])
    : "r"(a[0]), "r"(a[1]), "r"(a[2]), "r"(a[3]), "l"(db), "r"(sd));
}

__device__ __forceinline__ void wgmma_rs_n128(float* d, const uint32_t* a, uint64_t db, int sd) {
  asm volatile("{ .reg .pred p; setp.ne.b32 p, %69, 0;\n"
      "wgmma.mma_async.sync.aligned.m64n128k16.f32.bf16.bf16 {"
      "%0,%1,%2,%3,%4,%5,%6,%7,%8,%9,%10,%11,%12,%13,%14,%15,"
      "%16,%17,%18,%19,%20,%21,%22,%23,%24,%25,%26,%27,%28,%29,%30,%31,"
      "%32,%33,%34,%35,%36,%37,%38,%39,%40,%41,%42,%43,%44,%45,%46,%47,"
      "%48,%49,%50,%51,%52,%53,%54,%55,%56,%57,%58,%59,%60,%61,%62,%63"
      "}, {%64,%65,%66,%67}, %68, p, 1, 1, 0; }"
    : "+f"(d[0]), "+f"(d[1]), "+f"(d[2]), "+f"(d[3]), "+f"(d[4]), "+f"(d[5]), "+f"(d[6]), "+f"(d[7]),
      "+f"(d[8]), "+f"(d[9]), "+f"(d[10]), "+f"(d[11]), "+f"(d[12]), "+f"(d[13]), "+f"(d[14]), "+f"(d[15]),
      "+f"(d[16]), "+f"(d[17]), "+f"(d[18]), "+f"(d[19]), "+f"(d[20]), "+f"(d[21]), "+f"(d[22]), "+f"(d[23]),
      "+f"(d[24]), "+f"(d[25]), "+f"(d[26]), "+f"(d[27]), "+f"(d[28]), "+f"(d[29]), "+f"(d[30]), "+f"(d[31]),
      "+f"(d[32]), "+f"(d[33]), "+f"(d[34]), "+f"(d[35]), "+f"(d[36]), "+f"(d[37]), "+f"(d[38]), "+f"(d[39]),
      "+f"(d[40]), "+f"(d[41]), "+f"(d[42]), "+f"(d[43]), "+f"(d[44]), "+f"(d[45]), "+f"(d[46]), "+f"(d[47]),
      "+f"(d[48]), "+f"(d[49]), "+f"(d[50]), "+f"(d[51]), "+f"(d[52]), "+f"(d[53]), "+f"(d[54]), "+f"(d[55]),
      "+f"(d[56]), "+f"(d[57]), "+f"(d[58]), "+f"(d[59]), "+f"(d[60]), "+f"(d[61]), "+f"(d[62]), "+f"(d[63])
    : "r"(a[0]), "r"(a[1]), "r"(a[2]), "r"(a[3]), "l"(db), "r"(sd));
}

__device__ __forceinline__ void wgmma_rs_n144(float* d, const uint32_t* a, uint64_t db, int sd) {
  asm volatile("{ .reg .pred p; setp.ne.b32 p, %77, 0;\n"
      "wgmma.mma_async.sync.aligned.m64n144k16.f32.bf16.bf16 {"
      "%0,%1,%2,%3,%4,%5,%6,%7,%8,%9,%10,%11,%12,%13,%14,%15,"
      "%16,%17,%18,%19,%20,%21,%22,%23,%24,%25,%26,%27,%28,%29,%30,%31,"
      "%32,%33,%34,%35,%36,%37,%38,%39,%40,%41,%42,%43,%44,%45,%46,%47,"
      "%48,%49,%50,%51,%52,%53,%54,%55,%56,%57,%58,%59,%60,%61,%62,%63,"
      "%64,%65,%66,%67,%68,%69,%70,%71"
      "}, {%72,%73,%74,%75}, %76, p, 1, 1, 0; }"
    : "+f"(d[0]), "+f"(d[1]), "+f"(d[2]), "+f"(d[3]), "+f"(d[4]), "+f"(d[5]), "+f"(d[6]), "+f"(d[7]),
      "+f"(d[8]), "+f"(d[9]), "+f"(d[10]), "+f"(d[11]), "+f"(d[12]), "+f"(d[13]), "+f"(d[14]), "+f"(d[15]),
      "+f"(d[16]), "+f"(d[17]), "+f"(d[18]), "+f"(d[19]), "+f"(d[20]), "+f"(d[21]), "+f"(d[22]), "+f"(d[23]),
      "+f"(d[24]), "+f"(d[25]), "+f"(d[26]), "+f"(d[27]), "+f"(d[28]), "+f"(d[29]), "+f"(d[30]), "+f"(d[31]),
      "+f"(d[32]), "+f"(d[33]), "+f"(d[34]), "+f"(d[35]), "+f"(d[36]), "+f"(d[37]), "+f"(d[38]), "+f"(d[39]),
      "+f"(d[40]), "+f"(d[41]), "+f"(d[42]), "+f"(d[43]), "+f"(d[44]), "+f"(d[45]), "+f"(d[46]), "+f"(d[47]),
      "+f"(d[48]), "+f"(d[49]), "+f"(d[50]), "+f"(d[51]), "+f"(d[52]), "+f"(d[53]), "+f"(d[54]), "+f"(d[55]),
      "+f"(d[56]), "+f"(d[57]), "+f"(d[58]), "+f"(d[59]), "+f"(d[60]), "+f"(d[61]), "+f"(d[62]), "+f"(d[63]),
      "+f"(d[64]), "+f"(d[65]), "+f"(d[66]), "+f"(d[67]), "+f"(d[68]), "+f"(d[69]), "+f"(d[70]), "+f"(d[71])
    : "r"(a[0]), "r"(a[1]), "r"(a[2]), "r"(a[3]), "l"(db), "r"(sd));
}

__device__ __forceinline__ void wgmma_rs_n160(float* d, const uint32_t* a, uint64_t db, int sd) {
  asm volatile("{ .reg .pred p; setp.ne.b32 p, %85, 0;\n"
      "wgmma.mma_async.sync.aligned.m64n160k16.f32.bf16.bf16 {"
      "%0,%1,%2,%3,%4,%5,%6,%7,%8,%9,%10,%11,%12,%13,%14,%15,"
      "%16,%17,%18,%19,%20,%21,%22,%23,%24,%25,%26,%27,%28,%29,%30,%31,"
      "%32,%33,%34,%35,%36,%37,%38,%39,%40,%41,%42,%43,%44,%45,%46,%47,"
      "%48,%49,%50,%51,%52,%53,%54,%55,%56,%57,%58,%59,%60,%61,%62,%63,"
      "%64,%65,%66,%67,%68,%69,%70,%71,%72,%73,%74,%75,%76,%77,%78,%79"
      "}, {%80,%81,%82,%83}, %84, p, 1, 1, 0; }"
    : "+f"(d[0]), "+f"(d[1]), "+f"(d[2]), "+f"(d[3]), "+f"(d[4]), "+f"(d[5]), "+f"(d[6]), "+f"(d[7]),
      "+f"(d[8]), "+f"(d[9]), "+f"(d[10]), "+f"(d[11]), "+f"(d[12]), "+f"(d[13]), "+f"(d[14]), "+f"(d[15]),
      "+f"(d[16]), "+f"(d[17]), "+f"(d[18]), "+f"(d[19]), "+f"(d[20]), "+f"(d[21]), "+f"(d[22]), "+f"(d[23]),
      "+f"(d[24]), "+f"(d[25]), "+f"(d[26]), "+f"(d[27]), "+f"(d[28]), "+f"(d[29]), "+f"(d[30]), "+f"(d[31]),
      "+f"(d[32]), "+f"(d[33]), "+f"(d[34]), "+f"(d[35]), "+f"(d[36]), "+f"(d[37]), "+f"(d[38]), "+f"(d[39]),
      "+f"(d[40]), "+f"(d[41]), "+f"(d[42]), "+f"(d[43]), "+f"(d[44]), "+f"(d[45]), "+f"(d[46]), "+f"(d[47]),
      "+f"(d[48]), "+f"(d[49]), "+f"(d[50]), "+f"(d[51]), "+f"(d[52]), "+f"(d[53]), "+f"(d[54]), "+f"(d[55]),
      "+f"(d[56]), "+f"(d[57]), "+f"(d[58]), "+f"(d[59]), "+f"(d[60]), "+f"(d[61]), "+f"(d[62]), "+f"(d[63]),
      "+f"(d[64]), "+f"(d[65]), "+f"(d[66]), "+f"(d[67]), "+f"(d[68]), "+f"(d[69]), "+f"(d[70]), "+f"(d[71]),
      "+f"(d[72]), "+f"(d[73]), "+f"(d[74]), "+f"(d[75]), "+f"(d[76]), "+f"(d[77]), "+f"(d[78]), "+f"(d[79])
    : "r"(a[0]), "r"(a[1]), "r"(a[2]), "r"(a[3]), "l"(db), "r"(sd));
}

__device__ __forceinline__ void wgmma_rs_n176(float* d, const uint32_t* a, uint64_t db, int sd) {
  asm volatile("{ .reg .pred p; setp.ne.b32 p, %93, 0;\n"
      "wgmma.mma_async.sync.aligned.m64n176k16.f32.bf16.bf16 {"
      "%0,%1,%2,%3,%4,%5,%6,%7,%8,%9,%10,%11,%12,%13,%14,%15,"
      "%16,%17,%18,%19,%20,%21,%22,%23,%24,%25,%26,%27,%28,%29,%30,%31,"
      "%32,%33,%34,%35,%36,%37,%38,%39,%40,%41,%42,%43,%44,%45,%46,%47,"
      "%48,%49,%50,%51,%52,%53,%54,%55,%56,%57,%58,%59,%60,%61,%62,%63,"
      "%64,%65,%66,%67,%68,%69,%70,%71,%72,%73,%74,%75,%76,%77,%78,%79,"
      "%80,%81,%82,%83,%84,%85,%86,%87"
      "}, {%88,%89,%90,%91}, %92, p, 1, 1, 0; }"
    : "+f"(d[0]), "+f"(d[1]), "+f"(d[2]), "+f"(d[3]), "+f"(d[4]), "+f"(d[5]), "+f"(d[6]), "+f"(d[7]),
      "+f"(d[8]), "+f"(d[9]), "+f"(d[10]), "+f"(d[11]), "+f"(d[12]), "+f"(d[13]), "+f"(d[14]), "+f"(d[15]),
      "+f"(d[16]), "+f"(d[17]), "+f"(d[18]), "+f"(d[19]), "+f"(d[20]), "+f"(d[21]), "+f"(d[22]), "+f"(d[23]),
      "+f"(d[24]), "+f"(d[25]), "+f"(d[26]), "+f"(d[27]), "+f"(d[28]), "+f"(d[29]), "+f"(d[30]), "+f"(d[31]),
      "+f"(d[32]), "+f"(d[33]), "+f"(d[34]), "+f"(d[35]), "+f"(d[36]), "+f"(d[37]), "+f"(d[38]), "+f"(d[39]),
      "+f"(d[40]), "+f"(d[41]), "+f"(d[42]), "+f"(d[43]), "+f"(d[44]), "+f"(d[45]), "+f"(d[46]), "+f"(d[47]),
      "+f"(d[48]), "+f"(d[49]), "+f"(d[50]), "+f"(d[51]), "+f"(d[52]), "+f"(d[53]), "+f"(d[54]), "+f"(d[55]),
      "+f"(d[56]), "+f"(d[57]), "+f"(d[58]), "+f"(d[59]), "+f"(d[60]), "+f"(d[61]), "+f"(d[62]), "+f"(d[63]),
      "+f"(d[64]), "+f"(d[65]), "+f"(d[66]), "+f"(d[67]), "+f"(d[68]), "+f"(d[69]), "+f"(d[70]), "+f"(d[71]),
      "+f"(d[72]), "+f"(d[73]), "+f"(d[74]), "+f"(d[75]), "+f"(d[76]), "+f"(d[77]), "+f"(d[78]), "+f"(d[79]),
      "+f"(d[80]), "+f"(d[81]), "+f"(d[82]), "+f"(d[83]), "+f"(d[84]), "+f"(d[85]), "+f"(d[86]), "+f"(d[87])
    : "r"(a[0]), "r"(a[1]), "r"(a[2]), "r"(a[3]), "l"(db), "r"(sd));
}

__device__ __forceinline__ void wgmma_rs_n192(float* d, const uint32_t* a, uint64_t db, int sd) {
  asm volatile("{ .reg .pred p; setp.ne.b32 p, %101, 0;\n"
      "wgmma.mma_async.sync.aligned.m64n192k16.f32.bf16.bf16 {"
      "%0,%1,%2,%3,%4,%5,%6,%7,%8,%9,%10,%11,%12,%13,%14,%15,"
      "%16,%17,%18,%19,%20,%21,%22,%23,%24,%25,%26,%27,%28,%29,%30,%31,"
      "%32,%33,%34,%35,%36,%37,%38,%39,%40,%41,%42,%43,%44,%45,%46,%47,"
      "%48,%49,%50,%51,%52,%53,%54,%55,%56,%57,%58,%59,%60,%61,%62,%63,"
      "%64,%65,%66,%67,%68,%69,%70,%71,%72,%73,%74,%75,%76,%77,%78,%79,"
      "%80,%81,%82,%83,%84,%85,%86,%87,%88,%89,%90,%91,%92,%93,%94,%95"
      "}, {%96,%97,%98,%99}, %100, p, 1, 1, 0; }"
    : "+f"(d[0]), "+f"(d[1]), "+f"(d[2]), "+f"(d[3]), "+f"(d[4]), "+f"(d[5]), "+f"(d[6]), "+f"(d[7]),
      "+f"(d[8]), "+f"(d[9]), "+f"(d[10]), "+f"(d[11]), "+f"(d[12]), "+f"(d[13]), "+f"(d[14]), "+f"(d[15]),
      "+f"(d[16]), "+f"(d[17]), "+f"(d[18]), "+f"(d[19]), "+f"(d[20]), "+f"(d[21]), "+f"(d[22]), "+f"(d[23]),
      "+f"(d[24]), "+f"(d[25]), "+f"(d[26]), "+f"(d[27]), "+f"(d[28]), "+f"(d[29]), "+f"(d[30]), "+f"(d[31]),
      "+f"(d[32]), "+f"(d[33]), "+f"(d[34]), "+f"(d[35]), "+f"(d[36]), "+f"(d[37]), "+f"(d[38]), "+f"(d[39]),
      "+f"(d[40]), "+f"(d[41]), "+f"(d[42]), "+f"(d[43]), "+f"(d[44]), "+f"(d[45]), "+f"(d[46]), "+f"(d[47]),
      "+f"(d[48]), "+f"(d[49]), "+f"(d[50]), "+f"(d[51]), "+f"(d[52]), "+f"(d[53]), "+f"(d[54]), "+f"(d[55]),
      "+f"(d[56]), "+f"(d[57]), "+f"(d[58]), "+f"(d[59]), "+f"(d[60]), "+f"(d[61]), "+f"(d[62]), "+f"(d[63]),
      "+f"(d[64]), "+f"(d[65]), "+f"(d[66]), "+f"(d[67]), "+f"(d[68]), "+f"(d[69]), "+f"(d[70]), "+f"(d[71]),
      "+f"(d[72]), "+f"(d[73]), "+f"(d[74]), "+f"(d[75]), "+f"(d[76]), "+f"(d[77]), "+f"(d[78]), "+f"(d[79]),
      "+f"(d[80]), "+f"(d[81]), "+f"(d[82]), "+f"(d[83]), "+f"(d[84]), "+f"(d[85]), "+f"(d[86]), "+f"(d[87]),
      "+f"(d[88]), "+f"(d[89]), "+f"(d[90]), "+f"(d[91]), "+f"(d[92]), "+f"(d[93]), "+f"(d[94]), "+f"(d[95])
    : "r"(a[0]), "r"(a[1]), "r"(a[2]), "r"(a[3]), "l"(db), "r"(sd));
}

__device__ __forceinline__ void wgmma_rs_n208(float* d, const uint32_t* a, uint64_t db, int sd) {
  asm volatile("{ .reg .pred p; setp.ne.b32 p, %109, 0;\n"
      "wgmma.mma_async.sync.aligned.m64n208k16.f32.bf16.bf16 {"
      "%0,%1,%2,%3,%4,%5,%6,%7,%8,%9,%10,%11,%12,%13,%14,%15,"
      "%16,%17,%18,%19,%20,%21,%22,%23,%24,%25,%26,%27,%28,%29,%30,%31,"
      "%32,%33,%34,%35,%36,%37,%38,%39,%40,%41,%42,%43,%44,%45,%46,%47,"
      "%48,%49,%50,%51,%52,%53,%54,%55,%56,%57,%58,%59,%60,%61,%62,%63,"
      "%64,%65,%66,%67,%68,%69,%70,%71,%72,%73,%74,%75,%76,%77,%78,%79,"
      "%80,%81,%82,%83,%84,%85,%86,%87,%88,%89,%90,%91,%92,%93,%94,%95,"
      "%96,%97,%98,%99,%100,%101,%102,%103"
      "}, {%104,%105,%106,%107}, %108, p, 1, 1, 0; }"
    : "+f"(d[0]), "+f"(d[1]), "+f"(d[2]), "+f"(d[3]), "+f"(d[4]), "+f"(d[5]), "+f"(d[6]), "+f"(d[7]),
      "+f"(d[8]), "+f"(d[9]), "+f"(d[10]), "+f"(d[11]), "+f"(d[12]), "+f"(d[13]), "+f"(d[14]), "+f"(d[15]),
      "+f"(d[16]), "+f"(d[17]), "+f"(d[18]), "+f"(d[19]), "+f"(d[20]), "+f"(d[21]), "+f"(d[22]), "+f"(d[23]),
      "+f"(d[24]), "+f"(d[25]), "+f"(d[26]), "+f"(d[27]), "+f"(d[28]), "+f"(d[29]), "+f"(d[30]), "+f"(d[31]),
      "+f"(d[32]), "+f"(d[33]), "+f"(d[34]), "+f"(d[35]), "+f"(d[36]), "+f"(d[37]), "+f"(d[38]), "+f"(d[39]),
      "+f"(d[40]), "+f"(d[41]), "+f"(d[42]), "+f"(d[43]), "+f"(d[44]), "+f"(d[45]), "+f"(d[46]), "+f"(d[47]),
      "+f"(d[48]), "+f"(d[49]), "+f"(d[50]), "+f"(d[51]), "+f"(d[52]), "+f"(d[53]), "+f"(d[54]), "+f"(d[55]),
      "+f"(d[56]), "+f"(d[57]), "+f"(d[58]), "+f"(d[59]), "+f"(d[60]), "+f"(d[61]), "+f"(d[62]), "+f"(d[63]),
      "+f"(d[64]), "+f"(d[65]), "+f"(d[66]), "+f"(d[67]), "+f"(d[68]), "+f"(d[69]), "+f"(d[70]), "+f"(d[71]),
      "+f"(d[72]), "+f"(d[73]), "+f"(d[74]), "+f"(d[75]), "+f"(d[76]), "+f"(d[77]), "+f"(d[78]), "+f"(d[79]),
      "+f"(d[80]), "+f"(d[81]), "+f"(d[82]), "+f"(d[83]), "+f"(d[84]), "+f"(d[85]), "+f"(d[86]), "+f"(d[87]),
      "+f"(d[88]), "+f"(d[89]), "+f"(d[90]), "+f"(d[91]), "+f"(d[92]), "+f"(d[93]), "+f"(d[94]), "+f"(d[95]),
      "+f"(d[96]), "+f"(d[97]), "+f"(d[98]), "+f"(d[99]), "+f"(d[100]), "+f"(d[101]), "+f"(d[102]), "+f"(d[103])
    : "r"(a[0]), "r"(a[1]), "r"(a[2]), "r"(a[3]), "l"(db), "r"(sd));
}

__device__ __forceinline__ void wgmma_rs_n224(float* d, const uint32_t* a, uint64_t db, int sd) {
  asm volatile("{ .reg .pred p; setp.ne.b32 p, %117, 0;\n"
      "wgmma.mma_async.sync.aligned.m64n224k16.f32.bf16.bf16 {"
      "%0,%1,%2,%3,%4,%5,%6,%7,%8,%9,%10,%11,%12,%13,%14,%15,"
      "%16,%17,%18,%19,%20,%21,%22,%23,%24,%25,%26,%27,%28,%29,%30,%31,"
      "%32,%33,%34,%35,%36,%37,%38,%39,%40,%41,%42,%43,%44,%45,%46,%47,"
      "%48,%49,%50,%51,%52,%53,%54,%55,%56,%57,%58,%59,%60,%61,%62,%63,"
      "%64,%65,%66,%67,%68,%69,%70,%71,%72,%73,%74,%75,%76,%77,%78,%79,"
      "%80,%81,%82,%83,%84,%85,%86,%87,%88,%89,%90,%91,%92,%93,%94,%95,"
      "%96,%97,%98,%99,%100,%101,%102,%103,%104,%105,%106,%107,%108,%109,%110,%111"
      "}, {%112,%113,%114,%115}, %116, p, 1, 1, 0; }"
    : "+f"(d[0]), "+f"(d[1]), "+f"(d[2]), "+f"(d[3]), "+f"(d[4]), "+f"(d[5]), "+f"(d[6]), "+f"(d[7]),
      "+f"(d[8]), "+f"(d[9]), "+f"(d[10]), "+f"(d[11]), "+f"(d[12]), "+f"(d[13]), "+f"(d[14]), "+f"(d[15]),
      "+f"(d[16]), "+f"(d[17]), "+f"(d[18]), "+f"(d[19]), "+f"(d[20]), "+f"(d[21]), "+f"(d[22]), "+f"(d[23]),
      "+f"(d[24]), "+f"(d[25]), "+f"(d[26]), "+f"(d[27]), "+f"(d[28]), "+f"(d[29]), "+f"(d[30]), "+f"(d[31]),
      "+f"(d[32]), "+f"(d[33]), "+f"(d[34]), "+f"(d[35]), "+f"(d[36]), "+f"(d[37]), "+f"(d[38]), "+f"(d[39]),
      "+f"(d[40]), "+f"(d[41]), "+f"(d[42]), "+f"(d[43]), "+f"(d[44]), "+f"(d[45]), "+f"(d[46]), "+f"(d[47]),
      "+f"(d[48]), "+f"(d[49]), "+f"(d[50]), "+f"(d[51]), "+f"(d[52]), "+f"(d[53]), "+f"(d[54]), "+f"(d[55]),
      "+f"(d[56]), "+f"(d[57]), "+f"(d[58]), "+f"(d[59]), "+f"(d[60]), "+f"(d[61]), "+f"(d[62]), "+f"(d[63]),
      "+f"(d[64]), "+f"(d[65]), "+f"(d[66]), "+f"(d[67]), "+f"(d[68]), "+f"(d[69]), "+f"(d[70]), "+f"(d[71]),
      "+f"(d[72]), "+f"(d[73]), "+f"(d[74]), "+f"(d[75]), "+f"(d[76]), "+f"(d[77]), "+f"(d[78]), "+f"(d[79]),
      "+f"(d[80]), "+f"(d[81]), "+f"(d[82]), "+f"(d[83]), "+f"(d[84]), "+f"(d[85]), "+f"(d[86]), "+f"(d[87]),
      "+f"(d[88]), "+f"(d[89]), "+f"(d[90]), "+f"(d[91]), "+f"(d[92]), "+f"(d[93]), "+f"(d[94]), "+f"(d[95]),
      "+f"(d[96]), "+f"(d[97]), "+f"(d[98]), "+f"(d[99]), "+f"(d[100]), "+f"(d[101]), "+f"(d[102]), "+f"(d[103]),
      "+f"(d[104]), "+f"(d[105]), "+f"(d[106]), "+f"(d[107]), "+f"(d[108]), "+f"(d[109]), "+f"(d[110]), "+f"(d[111])
    : "r"(a[0]), "r"(a[1]), "r"(a[2]), "r"(a[3]), "l"(db), "r"(sd));
}

__device__ __forceinline__ void wgmma_rs_n240(float* d, const uint32_t* a, uint64_t db, int sd) {
  asm volatile("{ .reg .pred p; setp.ne.b32 p, %125, 0;\n"
      "wgmma.mma_async.sync.aligned.m64n240k16.f32.bf16.bf16 {"
      "%0,%1,%2,%3,%4,%5,%6,%7,%8,%9,%10,%11,%12,%13,%14,%15,"
      "%16,%17,%18,%19,%20,%21,%22,%23,%24,%25,%26,%27,%28,%29,%30,%31,"
      "%32,%33,%34,%35,%36,%37,%38,%39,%40,%41,%42,%43,%44,%45,%46,%47,"
      "%48,%49,%50,%51,%52,%53,%54,%55,%56,%57,%58,%59,%60,%61,%62,%63,"
      "%64,%65,%66,%67,%68,%69,%70,%71,%72,%73,%74,%75,%76,%77,%78,%79,"
      "%80,%81,%82,%83,%84,%85,%86,%87,%88,%89,%90,%91,%92,%93,%94,%95,"
      "%96,%97,%98,%99,%100,%101,%102,%103,%104,%105,%106,%107,%108,%109,%110,%111,"
      "%112,%113,%114,%115,%116,%117,%118,%119"
      "}, {%120,%121,%122,%123}, %124, p, 1, 1, 0; }"
    : "+f"(d[0]), "+f"(d[1]), "+f"(d[2]), "+f"(d[3]), "+f"(d[4]), "+f"(d[5]), "+f"(d[6]), "+f"(d[7]),
      "+f"(d[8]), "+f"(d[9]), "+f"(d[10]), "+f"(d[11]), "+f"(d[12]), "+f"(d[13]), "+f"(d[14]), "+f"(d[15]),
      "+f"(d[16]), "+f"(d[17]), "+f"(d[18]), "+f"(d[19]), "+f"(d[20]), "+f"(d[21]), "+f"(d[22]), "+f"(d[23]),
      "+f"(d[24]), "+f"(d[25]), "+f"(d[26]), "+f"(d[27]), "+f"(d[28]), "+f"(d[29]), "+f"(d[30]), "+f"(d[31]),
      "+f"(d[32]), "+f"(d[33]), "+f"(d[34]), "+f"(d[35]), "+f"(d[36]), "+f"(d[37]), "+f"(d[38]), "+f"(d[39]),
      "+f"(d[40]), "+f"(d[41]), "+f"(d[42]), "+f"(d[43]), "+f"(d[44]), "+f"(d[45]), "+f"(d[46]), "+f"(d[47]),
      "+f"(d[48]), "+f"(d[49]), "+f"(d[50]), "+f"(d[51]), "+f"(d[52]), "+f"(d[53]), "+f"(d[54]), "+f"(d[55]),
      "+f"(d[56]), "+f"(d[57]), "+f"(d[58]), "+f"(d[59]), "+f"(d[60]), "+f"(d[61]), "+f"(d[62]), "+f"(d[63]),
      "+f"(d[64]), "+f"(d[65]), "+f"(d[66]), "+f"(d[67]), "+f"(d[68]), "+f"(d[69]), "+f"(d[70]), "+f"(d[71]),
      "+f"(d[72]), "+f"(d[73]), "+f"(d[74]), "+f"(d[75]), "+f"(d[76]), "+f"(d[77]), "+f"(d[78]), "+f"(d[79]),
      "+f"(d[80]), "+f"(d[81]), "+f"(d[82]), "+f"(d[83]), "+f"(d[84]), "+f"(d[85]), "+f"(d[86]), "+f"(d[87]),
      "+f"(d[88]), "+f"(d[89]), "+f"(d[90]), "+f"(d[91]), "+f"(d[92]), "+f"(d[93]), "+f"(d[94]), "+f"(d[95]),
      "+f"(d[96]), "+f"(d[97]), "+f"(d[98]), "+f"(d[99]), "+f"(d[100]), "+f"(d[101]), "+f"(d[102]), "+f"(d[103]),
      "+f"(d[104]), "+f"(d[105]), "+f"(d[106]), "+f"(d[107]), "+f"(d[108]), "+f"(d[109]), "+f"(d[110]), "+f"(d[111]),
      "+f"(d[112]), "+f"(d[113]), "+f"(d[114]), "+f"(d[115]), "+f"(d[116]), "+f"(d[117]), "+f"(d[118]), "+f"(d[119])
    : "r"(a[0]), "r"(a[1]), "r"(a[2]), "r"(a[3]), "l"(db), "r"(sd));
}

__device__ __forceinline__ void wgmma_rs_n256(float* d, const uint32_t* a, uint64_t db, int sd) {
  asm volatile("{ .reg .pred p; setp.ne.b32 p, %133, 0;\n"
      "wgmma.mma_async.sync.aligned.m64n256k16.f32.bf16.bf16 {"
      "%0,%1,%2,%3,%4,%5,%6,%7,%8,%9,%10,%11,%12,%13,%14,%15,"
      "%16,%17,%18,%19,%20,%21,%22,%23,%24,%25,%26,%27,%28,%29,%30,%31,"
      "%32,%33,%34,%35,%36,%37,%38,%39,%40,%41,%42,%43,%44,%45,%46,%47,"
      "%48,%49,%50,%51,%52,%53,%54,%55,%56,%57,%58,%59,%60,%61,%62,%63,"
      "%64,%65,%66,%67,%68,%69,%70,%71,%72,%73,%74,%75,%76,%77,%78,%79,"
      "%80,%81,%82,%83,%84,%85,%86,%87,%88,%89,%90,%91,%92,%93,%94,%95,"
      "%96,%97,%98,%99,%100,%101,%102,%103,%104,%105,%106,%107,%108,%109,%110,%111,"
      "%112,%113,%114,%115,%116,%117,%118,%119,%120,%121,%122,%123,%124,%125,%126,%127"
      "}, {%128,%129,%130,%131}, %132, p, 1, 1, 0; }"
    : "+f"(d[0]), "+f"(d[1]), "+f"(d[2]), "+f"(d[3]), "+f"(d[4]), "+f"(d[5]), "+f"(d[6]), "+f"(d[7]),
      "+f"(d[8]), "+f"(d[9]), "+f"(d[10]), "+f"(d[11]), "+f"(d[12]), "+f"(d[13]), "+f"(d[14]), "+f"(d[15]),
      "+f"(d[16]), "+f"(d[17]), "+f"(d[18]), "+f"(d[19]), "+f"(d[20]), "+f"(d[21]), "+f"(d[22]), "+f"(d[23]),
      "+f"(d[24]), "+f"(d[25]), "+f"(d[26]), "+f"(d[27]), "+f"(d[28]), "+f"(d[29]), "+f"(d[30]), "+f"(d[31]),
      "+f"(d[32]), "+f"(d[33]), "+f"(d[34]), "+f"(d[35]), "+f"(d[36]), "+f"(d[37]), "+f"(d[38]), "+f"(d[39]),
      "+f"(d[40]), "+f"(d[41]), "+f"(d[42]), "+f"(d[43]), "+f"(d[44]), "+f"(d[45]), "+f"(d[46]), "+f"(d[47]),
      "+f"(d[48]), "+f"(d[49]), "+f"(d[50]), "+f"(d[51]), "+f"(d[52]), "+f"(d[53]), "+f"(d[54]), "+f"(d[55]),
      "+f"(d[56]), "+f"(d[57]), "+f"(d[58]), "+f"(d[59]), "+f"(d[60]), "+f"(d[61]), "+f"(d[62]), "+f"(d[63]),
      "+f"(d[64]), "+f"(d[65]), "+f"(d[66]), "+f"(d[67]), "+f"(d[68]), "+f"(d[69]), "+f"(d[70]), "+f"(d[71]),
      "+f"(d[72]), "+f"(d[73]), "+f"(d[74]), "+f"(d[75]), "+f"(d[76]), "+f"(d[77]), "+f"(d[78]), "+f"(d[79]),
      "+f"(d[80]), "+f"(d[81]), "+f"(d[82]), "+f"(d[83]), "+f"(d[84]), "+f"(d[85]), "+f"(d[86]), "+f"(d[87]),
      "+f"(d[88]), "+f"(d[89]), "+f"(d[90]), "+f"(d[91]), "+f"(d[92]), "+f"(d[93]), "+f"(d[94]), "+f"(d[95]),
      "+f"(d[96]), "+f"(d[97]), "+f"(d[98]), "+f"(d[99]), "+f"(d[100]), "+f"(d[101]), "+f"(d[102]), "+f"(d[103]),
      "+f"(d[104]), "+f"(d[105]), "+f"(d[106]), "+f"(d[107]), "+f"(d[108]), "+f"(d[109]), "+f"(d[110]), "+f"(d[111]),
      "+f"(d[112]), "+f"(d[113]), "+f"(d[114]), "+f"(d[115]), "+f"(d[116]), "+f"(d[117]), "+f"(d[118]), "+f"(d[119]),
      "+f"(d[120]), "+f"(d[121]), "+f"(d[122]), "+f"(d[123]), "+f"(d[124]), "+f"(d[125]), "+f"(d[126]), "+f"(d[127])
    : "r"(a[0]), "r"(a[1]), "r"(a[2]), "r"(a[3]), "l"(db), "r"(sd));
}

__device__ __forceinline__ void ln_finish(float mean, float var, float& mb, float& rinv) {
  mb = round_bf16(mean);
  float sd;
  asm("sqrt.approx.ftz.f32 %0, %1;" : "=f"(sd) : "f"(round_bf16(round_bf16(var) + 1e-5f)));
  asm("rcp.approx.ftz.f32 %0, %1;" : "=f"(rinv) : "f"(round_bf16(sd)));
}
__device__ __forceinline__ uint32_t sum4(uint32_t a, uint32_t b, uint32_t c, uint32_t d) { return badd2(badd2(badd2(d, c), b), a); }
struct Ring {
  uint32_t s, ph;
  __device__ __forceinline__ void next() { if (++s == NSTAGE) { s = 0; ph ^= 1; } }
};

template <int J> __device__ __forceinline__ void conv_lda(uint32_t* a, uint32_t base, bool on) {
  asm volatile("{ .reg .pred p; setp.ne.u32 p, %3, 0;\n @p ld.shared.u32 %0, [%2 + %4];\n @p ld.shared.u32 %1, [%2 + %5]; }"
               : "+r"(a[2 * J]), "+r"(a[2 * J + 1]) : "r"(base), "r"((uint32_t)on), "n"((J >> 1) * 256 + (J & 1) * 16), "n"((J >> 1) * 256 + (J & 1) * 16 + 128) : "memory");
}
template <int J = 0> __device__ __forceinline__ void conv_lda_all(uint32_t* a, uint32_t base) {
  conv_lda<J>(a, base, true);
  if constexpr (J < 31) conv_lda_all<J + 1>(a, base);
}
__device__ __forceinline__ void conv_mma(float* acc, const uint32_t* a, uint64_t db) {
  wgmma_rs_n256(acc, a, db, 0);
  wgmma_rs_n240(acc, a + 4, db + 16, 1);
  wgmma_rs_n224(acc, a + 8, db + 32, 1);
  wgmma_rs_n208(acc, a + 12, db + 48, 1);
  wgmma_rs_n192(acc, a + 16, db + 64, 1);
  wgmma_rs_n176(acc, a + 20, db + 80, 1);
  wgmma_rs_n160(acc, a + 24, db + 96, 1);
  wgmma_rs_n144(acc, a + 28, db + 112, 1);
  wgmma_rs_n128(acc, a + 32, db + 128, 1);
  wgmma_rs_n112(acc, a + 36, db + 144, 1);
  wgmma_rs_n96(acc, a + 40, db + 160, 1);
  wgmma_rs_n80(acc, a + 44, db + 176, 1);
  wgmma_rs_n64(acc, a + 48, db + 192, 1);
  wgmma_rs_n48(acc, a + 52, db + 208, 1);
  wgmma_rs_n32(acc, a + 56, db + 224, 1);
  wgmma_rs_n16(acc, a + 60, db + 240, 1);
}
__device__ __forceinline__ uint32_t conv_part(const float* acc, int j) {
  const int q = 31 - j;
  return q == 31 ? pack_bf16(acc[124], acc[125]) : pack_bf16(acc[4 * q] + acc[(4 * q + 6) & 127], acc[4 * q + 1] + acc[(4 * q + 7) & 127]);
}
template <int J = 0> __device__ __forceinline__ void conv_drain(const float* acc, uint32_t wr, uint32_t* a, uint32_t ka, bool more) {
  conv_lda<J>(a, ka, more);
  sts32(wr + J * 128, conv_part(acc, J));
  if constexpr (J < 31) conv_drain<J + 1>(acc, wr, a, ka, more);
}
__device__ __forceinline__ uint4 conv_sum(const uint4* p) {
  return make_uint4(sum4(p[0].x, p[1].x, p[2].x, p[3].x), sum4(p[0].y, p[1].y, p[2].y, p[3].y), sum4(p[0].z, p[1].z, p[2].z, p[3].z),
                    sum4(p[0].w, p[1].w, p[2].w, p[3].w));
}
__device__ __forceinline__ int g2k(int rank, int kb) { return (rank * G2_KB + (kb < 6 ? 6 * kb : kb - 5 + (kb - 6) / 5)) * 64; }

template <int NV> __device__ __forceinline__ void gelu_stage(float* acc, const float* hb, uint32_t sa, int passes, uint32_t bar) {
#pragma unroll
  for (int i = 0; i < NV; i++) acc[i] = fmaf(acc[i], 0.5f, hb[(i >> 1) & 1]);
#pragma unroll 1
  for (; passes > 0; passes--, sa += NV * 256) {
#pragma unroll
    for (int i = 0; i < NV; i += 8)
      stsm4t(sa + i * 256, pack_bf16(gelu_half(acc[i]), gelu_half(acc[i + 1])), pack_bf16(gelu_half(acc[i + 2]), gelu_half(acc[i + 3])),
             pack_bf16(gelu_half(acc[i + 4]), gelu_half(acc[i + 5])), pack_bf16(gelu_half(acc[i + 6]), gelu_half(acc[i + 7])));
    __syncwarp();
    if (bar) mbar_arrive(bar);
    bar = 0;
    float half = 0.5f;
    asm volatile("" : "+f"(half));
#pragma unroll
    for (int i = 0; i < NV; i++) acc[i] = fmaf(acc[NV + i], half, hb[2 + ((i >> 1) & 1)]);
  }
}

__global__ void __cluster_dims__(2, 1, 1) __launch_bounds__(384, 1) fused_kernel(const __grid_constant__ Hot H, const __grid_constant__ Params P) {
  extern __shared__ __align__(1024) uint8_t smem_raw[];
  const uint32_t t0 = clk();
  const uint32_t sb = smem_u32(smem_raw);
  const int tid = threadIdx.x, lane = tid & 31;
  const int bid = blockIdx.x, rank = bid & 1;
  const Role& R = P.role[bid];
  Scratch* const S = H.S;
  uint32_t xr[18];
  const int row = bid * 16 + (tid >> 4);
  if (tid < 256 && bid < 128) {
    const char* src = reinterpret_cast<const char*>(H.x) + row * (D_ * 2) + (lane & 15) * 8;
#pragma unroll
    for (int j = 0; j < 9; j++) asm volatile("ld.global.nc.v2.u32 {%0,%1}, [%2];" : "=r"(xr[2 * j]), "=r"(xr[2 * j + 1]) : "l"(src + 128 * j));
  }
  const int warp = __shfl_sync(0xffffffffu, tid >> 5, 0);

  if (warp >= 8) {
    const bool one = elect_one();
    if (warp == 8 && one) {
#pragma unroll
      for (int b = B_FULL; b <= B_DONE; b += 8) mbar_init(sb + b, b < B_EMPTY ? 1 : b < B_SFREE ? 2 : b < B_CEMPTY ? 3 : b < B_G1DONE ? 4 : 8);
      asm volatile("fence.mbarrier_init.release.cluster;" ::: "memory");
    }
    __syncwarp();
    asm volatile("barrier.cluster.arrive.relaxed.aligned;" ::: "memory");
    asm volatile("setmaxnreg.dec.sync.aligned.u32 56;");
    asm volatile("barrier.cluster.wait.aligned;" ::: "memory");
    const bool left = R.at == 15;
    if (warp == 8) {
      const uint32_t ep = ldg32(S->cnt + C_EPOCH * 32);
      if (one) {
#pragma unroll 1
        for (int i = 0; i < 10; i++) asm volatile("prefetch.tensormap [%0];" :: "l"(&P.m_w1 + i) : "memory");
#pragma unroll 1
        for (int s = 0; s < NWE; s++) {
          mbar_expect_tx(sb + B_FULL + 8 * s, G1_BYTES);
          tma3d(sb + s * SLOT, &P.m_w1 + left, 0, s * 64, R.fg, sb + B_FULL + 8 * s);
        }
      }
      __syncwarp();
      if (bid < 128) bar_sync(2, 288);
      if (one) {
        TLREC(31);
        signal(S, C_H, EPOCH / 132);
        TLREC(1);
        const uint32_t boff = left ? 24576 : 16384;
        int kr = bid < 128 ? -2 : KV_ROUNDS + 1, ks = 0;
        auto kv_step = [&]() {
          if (ks == 0) {
            bulk_wait_all();
            if (kr < KV_ROUNDS - 2) {
              const int q = (kr + 2) % 3;
              const uint32_t in = sb + kv_buf(q), fb = sb + B_UFULL + 8 * q;
              mbar_expect_tx(fb, 3840 + 3264 + 768);
              tma2d(in, &P.m_k, (kr + 2) * 96, bid * 16 - 4, fb);
              tma2d(in + 3840, &P.m_v, (kr + 2) * 96, bid * 16 - 1, fb);
              bulk_load(in + 7168, H.shift_k + (kr + 2) * 384, 768, fb);
            }
            if (kr == KV_ROUNDS) { mbar_arrive(sb + B_KVDONE); kr++; }
          } else if (kr >= 0) {
            if (!mbar_test(sb + B_KFULL + 8 * (kr % 3), kr >= 3)) return;
            fence_async_smem();
            tma3d_store(&P.m_ub, sb + kv_buf(kr % 3) + (ks - 1) * 3072, 16 * (127 - bid), kr * 48, 2 * ks - 2);
            bulk_commit();
          }
          if (++ks == 3) { kr++; ks = kr == KV_ROUNDS - 2 || kr == KV_ROUNDS - 1; }
        };
        if (bid >= 128) mbar_arrive(sb + B_KVDONE);
        Ring r{0, 1};
#pragma unroll 1
        for (int kb = NWE - NW0; kb < G1_KB || kr <= KV_ROUNDS; kb++) {
          if (kb < G1_KB) {
          const int kw = kb < 0 ? kb + NW0 : kb, s = kb < 0 ? kw : r.s;
          const uint32_t fb = sb + B_FULL + 8 * s;
          if (kb < 0 || kb >= NW0) {
            mbar_wait(sb + B_EMPTY + 8 * s, r.ph);
            mbar_expect_tx(fb, G1_BYTES);
            tma3d(sb + s * SLOT, &P.m_w1 + left, 0, kw * 64, R.fg, fb);
            if (kb < 0) continue;
          }
          if (kb == 0) { await(S, C_H, ep); fence_async_global(); TLREC(2); }
          bulk_load(sb + s * SLOT + boff, S->h + (kb * 18 + R.at) * 2048, G1_BYTES - boff, fb);
          if (kb == 23) {
#pragma unroll 1
            for (int i = 0; i < 2; i++) {
              sts128(sb + cv_taps(i), 0, 0, 0, 0); sts128(sb + cv_taps(i) + 16, 0, 0, 0, 0);
              bulk_load(sb + cv_taps(i) + 32, H.ssm_k + (R.ch + i) * S_, 4096, sb + B_MISC);
            }
            mbar_expect_tx(sb + B_MISC, boff / 64 + 1152 + 8192);
            bulk_load(sb + SM_B1, H.b1 + R.fg * 64, boff / 64, sb + B_MISC);
            bulk_load(sb + SM_D, H.ssm_D, 1152, sb + B_MISC);
          }
          r.next();
          }
          if (kb >= KV0 && kr <= KV_ROUNDS) kv_step();
        }
        await(S, C_KV, ep);
        fence_async_global();
#pragma unroll 1
        for (int i = 0; i < R.ncv; i++) {
          if (i == 2) {
            if (R.sg >= 0) {
#pragma unroll 1
              for (int s = 2; s < NSTAGE; s++) {
                mbar_wait(sb + B_EMPTY + 8 * s, ((G1_KB / NSTAGE) - 1) & 1);
                mbar_expect_tx(sb + B_FULL + 8 * s, G2_BYTES);
                tma3d(sb + s * SLOT, &P.m_w2, 0, (rank * G2_KB + 6 * (s - 2)) * 64, R.sg, sb + B_FULL + 8 * s);
              }
            }
            mbar_wait(sb + B_G1DONE, 0);
          }
          const uint32_t kt = sb + cv_taps(i), b8 = sb + 8 * (i & 3);
          mbar_wait(b8 + B_CEMPTY, ((i >> 2) & 1) ^ 1);
          if (i < 2) mbar_arrive(b8 + B_KFULL);
          else {
            sts128(kt, 0, 0, 0, 0); sts128(kt + 16, 0, 0, 0, 0);
            mbar_expect_tx(b8 + B_KFULL, 4096);
            bulk_load(kt + 32, H.ssm_k + (R.ch + i) * S_, 4096, b8 + B_KFULL);
          }
          mbar_expect_tx(b8 + B_UFULL, 8192);
          bulk_load(sb + cv_in(i), S->ub + (R.ch + i) * 4096, 8192, b8 + B_UFULL);
        }
        if (R.sg >= 0) {
          mbar_expect_tx(sb + B_XY, 2 * 18432 + 2048 + 256);
#pragma unroll
          for (int i = 0; i < 4; i++) mbar_expect_tx(sb + B_XFULL + 8 * i, i & 1 ? 9216 - XP * 2048 : XP * 2048);
#pragma unroll 1
          for (int kb = 0; kb < G2_KB; kb++, r.next()) {
            const int k0 = g2k(rank, kb);
            const uint32_t fb = sb + B_FULL + 8 * r.s, slot = sb + r.s * SLOT;
            if (!(kb & ~4)) { await(S, C_U + (kb >> 2), ep); fence_async_global(); if (!kb) TLREC(6); }
            if (kb >= NSTAGE - 2) {
              mbar_wait(sb + B_EMPTY + 8 * r.s, r.ph);
              if (kb == SYNCA) asm volatile("red.relaxed.gpu.global.add.u32 [%0], %1;" :: "l"(S->cnt + C_SYNC * 32), "r"(EPOCH / 128) : "memory");
              if (kb == SYNCKB) await(S, C_SYNC, ep);
              mbar_expect_tx(fb, G2_BYTES);
              tma3d(slot, &P.m_w2, 0, k0, R.sg, fb);
            }
            tma2d(slot + 16384, &P.m_uld, k0, R.ds * 8, fb);
            tma2d(slot + 16384 + 9216, &P.m_uld, k0, R.dk * 8, fb);
            const uint32_t nx = kb - 8;
            if (nx == 0) { mbar_wait(sb + B_KVDONE, 1); fence_async_smem(); }
            if (nx < 8) tma2d(sb + SM_CV + nx * 2304, &P.m_x, R.dk * 8, R.sg * 64 + nx * 16, sb + B_XY);
          }
          bulk_load(sb + SM_ST, S->stats + R.sg * 64, 2048, sb + B_XY);
          bulk_load(sb + SM_B2, P.b2 + R.sg * 64, 256, sb + B_XY);
          await(S, C_Y, ep);
          fence_async_global();
          TLREC(19);
          tma3d(sb + SM_DED, &P.m_y, 0, R.dk * 8, R.sg, sb + B_XY);
          if (bid == 0) asm volatile("red.relaxed.gpu.global.add.u32 [%0], %1;" :: "l"(S->cnt + C_EPOCH * 32), "r"(EPOCH) : "memory");
        }
      }
    } else {
      if (bid < 128) {
        const int ht = tid - 288, hf = ht >= 48, pr = ht - 48 * hf;
        const uint32_t st = (1 - hf) * 1536 + pr * 32, sw = (pr & 4) * 4;
#pragma unroll 1
        for (int r = 0; r < KV_ROUNDS; r++) {
          const int q = r % 3;
          const uint32_t in = sb + kv_buf(q);
          {
            mbar_wait_guarded(sb + B_UFULL + 8 * q, t0, r >= 3);
            uint32_t kk[12], vv[9];
#pragma unroll
            for (int j = 0; j < 12; j++) kk[j] = lds32(in + hf * 1536 + pr * 4 + j * 192);
#pragma unroll
            for (int j = 0; j < 9; j++) vv[j] = lds32(in + 3840 + hf * 1536 + pr * 4 + j * 192);
            const uint4 w = lds128(in + 7168 + pr * 16);
            const uint32_t w0 = __byte_perm(w.x, w.z, 0x5410), w1 = __byte_perm(w.x, w.z, 0x7632);
            const uint32_t w2 = __byte_perm(w.y, w.w, 0x5410), w3 = __byte_perm(w.y, w.w, 0x7632);
#pragma unroll
            for (int j = 0; j < 9; j++)
              vv[j] = bmul2(badd2(badd2(badd2(bmul2(kk[j], w3), bmul2(kk[j + 1], w2)), bmul2(kk[j + 2], w1)), bmul2(kk[j + 3], w0)), vv[j]);
            bar_sync(1, 96);
#pragma unroll
            for (int c = 0; c < 2; c++)
#pragma unroll
              for (int pi = 0; pi < 2; pi++) {
                const uint32_t sel = c ? 0x7632 : 0x5410;
                sts128(in + st + c * 3072 + (pi * 16 ^ sw), __byte_perm(vv[7 + pi], vv[6 + pi], sel), __byte_perm(vv[5 + pi], vv[4 + pi], sel),
                       __byte_perm(vv[3 + pi], vv[2 + pi], sel), __byte_perm(vv[1 + pi], vv[pi], sel));
              }
            bar_sync(1, 96);
            if (ht == 0) mbar_arrive(sb + B_KFULL + 8 * q);
          }
          __syncwarp();
        }
      }
      if (one) {
        if (warp < 11) {
          const int wg = warp - 9;
#pragma unroll 1
          for (int j = 0; j <= (left ? 3 + 3 * wg : 5); j++) {
            if (j == 0 || j == 2 + left) {
              mbar_wait_guarded(sb + B_STG + 8 * wg + (j ? 0 : 16), t0);
              fence_async_smem();
              TLREC(13 + wg);
            }
            const int hi = left && j >= 3;
            if (j < (left ? 3 + 3 * wg : 5))
              tma2d_store(&P.m_ust, sb + (wg ? SM_ST1 : SM_DED) + j * 4096, (R.fg + wg + hi) * 64, (R.at + j - 3 * hi) * 32);
          }
          bulk_commit();
          bulk_wait_all();
          mbar_arrive(sb + B_STORED + 8 * wg);
          if (wg) mbar_arrive(sb + B_EMPTY);
          asm volatile("mbarrier.arrive.shared::cta.b64 _, [%0], 3;" :: "r"(sb + B_SFREE + 8 * wg) : "memory");
          signal(S, C_U + wg, EPOCH / 132);
          TLREC(15 + wg);
        } else {
          mbar_wait_guarded(sb + B_KVDONE, t0);
          signal(S, C_KV, EPOCH / 132);
          TLREC(27);
        }
      }
      __syncwarp();
#pragma unroll 1
      for (int i = 0; i < R.ncv; i++) {
        const uint32_t red = sb + cv_red(i, R.ncv) + (tid - 288) * 16;
        uint4* yo = reinterpret_cast<uint4*>(S->y + (R.ch + i) * S_) + (tid - 288);
        mbar_wait_guarded(sb + B_STORED + 8 * (i & 1), t0);
        mbar_wait_guarded(sb + B_STG + 8 * (i & 1) + (i + 2 < R.ncv ? 0 : 16), t0, i + 2 >= R.ncv || !(i & 2));
        uint4 p[2][4];
#pragma unroll
        for (int x = 0; x < 8; x++) p[x >> 2][x & 3] = lds128(red + (x & 3) * CV_REDW + (x >> 2) * 1536);
        yo[0] = conv_sum(p[0]);
        if (warp < 11) {
#pragma unroll
          for (int x = 0; x < 4; x++) p[0][x] = lds128(red + x * CV_REDW + 3072);
          yo[192] = conv_sum(p[0]);
        }
        yo[96] = conv_sum(p[1]);
        __syncwarp();
        if (one) mbar_arrive(sb + (i + 4 == R.ncv ? B_PDONE : B_SFREE + 8 * (i & 1)));
        if (i + 3 == R.ncv) {
          bar_sync(1, 96);
          if (warp == 11 && one) { fence_async_smem(); mbar_arrive(sb + B_EMPTY + 8); }
          __syncwarp();
        }
      }
      bar_sync(1, 96);
      if (warp == 11 && one) {
        TLREC(7);
        mbar_arrive(sb + B_KVDONE);
        signal(S, C_Y, EPOCH / 132);
        if (R.sg >= 0) mbar_wait_guarded(sb + B_DONE, t0);
      }
    }
    TLEND();
  } else {
    asm volatile("barrier.cluster.arrive.relaxed.aligned;" ::: "memory");
    if (bid < 128) {
      float c[36], s[4];
#pragma unroll
      for (int i = 0; i < 18; i++) { c[2 * i] = bf_lo(xr[i]); c[2 * i + 1] = bf_hi(xr[i]); }
#pragma unroll
      for (int i = 0; i < 36; i++) s[i & 3] = i < 4 ? c[i] : s[i & 3] + c[i];
      const float ml = ((s[0] + s[1]) + (s[2] + s[3])) * (1.0f / 36.0f);
#pragma unroll
      for (int i = 0; i < 36; i++) { c[i] -= ml; s[i & 3] = i < 4 ? c[i] * c[i] : fmaf(c[i], c[i], s[i & 3]); }
      float m = ml, q = (s[0] + s[1]) + (s[2] + s[3]), n2 = 18.f;
#pragma unroll
      for (int o = 1; o < 16; o <<= 1) {
        const float mo = __shfl_xor_sync(0xffffffffu, m, o), qo = __shfl_xor_sync(0xffffffffu, q, o);
        const float dl = m - mo;
        q = fmaf(dl * dl, n2, q + qo);
        m = fmaf(dl, -0.5f, m);
        n2 *= 2.f;
      }
      const float var = q * (1.0f / 576.0f);
      float mb, rinv, mb2, rinv2;
      ln_finish(m, var, mb, rinv);
      ln_finish((m - mb) * rinv, var * rinv * rinv, mb2, rinv2);
      const float ca = rinv * rinv2, cb = fmaf(ml - mb, rinv, -mb2) * rinv2;
      uint2* dst = reinterpret_cast<uint2*>(S->h) + ((row >> 6) * 18 + ((lane >> 3) & 1)) * 512 + (row & 63) * 8 + ((lane & 7) ^ (row & 6));
#pragma unroll
      for (int j = 0; j < 9; j++)
        dst[1024 * j] = make_uint2(pack_bf16(fmaf(c[4 * j], ca, cb), fmaf(c[4 * j + 1], ca, cb)), pack_bf16(fmaf(c[4 * j + 2], ca, cb), fmaf(c[4 * j + 3], ca, cb)));
      const uint32_t rh = pack_bf16(rinv, rinv);
      if (!(lane & 15)) S->stats[row] = make_uint4(pack_bf16(mb, mb), rh, pack_bf16(rinv - bf_lo(rh), rinv - bf_lo(rh)), 0);
      __syncwarp();
      bar_arrive(2, 288);
    }
    asm volatile("setmaxnreg.inc.sync.aligned.u32 224;");
    asm volatile("barrier.cluster.wait.aligned;" ::: "memory");
    const int wg = warp >> 2, w = warp & 3, g = lane >> 2, t = lane & 3, wtid = tid & 127;
    const bool elect = wtid == 0;
    const uint64_t da0 = make_desc(sb + wg * 8192, 8192, 1024, 1);
    const uint32_t swz = ((lane >> 4) * 8 + (lane & 7)) * 128 + (((2 * w + ((lane >> 3) & 1)) ^ (lane & 7)) << 4);
    const uint32_t stg = sb + (wg ? SM_ST1 : SM_DED), ka0 = (8 * w + g + t + 1) * 4;
    uint32_t a[64];
    {
      auto mainloop = [&](auto&& mma) {
        Ring r{0, 0};
        uint32_t rel = 0;
#pragma unroll 1
        for (int kb = 0; kb < G1_KB; kb++, r.next()) {
          if (kb == G1_KB - G1_TAIL && wg) {
            wg_wait<0>();
            if (elect) mbar_arrive(rel);
            rel = 0;
            if (PRE1) {
              mbar_wait(sb + B_MISC, 0);
              conv_lda_all(a, sb + SM_CV + 16384 + CV_K + ka0);
            }
            bar_sync(5, 256);
          }
          mbar_wait(sb + B_FULL + 8 * r.s, r.ph);
          if (kb == 0 && warp == 0) TLREC(3);
          wg_fence();
          mma(r.s * (SLOT >> 4), kb);
          wg_commit();
          if (kb == G1_KB - 1) break;
          wg_wait<1>();
          if (elect && rel) mbar_arrive(rel);
          rel = sb + B_EMPTY + 8 * r.s;
        }
        bar_arrive(5, 256);
        wg_wait<0>();
      };
      float hb[4];
      auto staged = [&](int second) {
        if (!w) TLREC(4 + wg);
        if (lane == 0) mbar_arrive(sb + B_G1DONE);
        mbar_wait(sb + B_MISC, 0);
#pragma unroll
        for (int i = 0; i < 4; i++) hb[i] = 0.5f * bf_lo(lds16(sb + SM_B1 + (warp * 16 + g + (i & 1) * 8 + (i >> 1) * second) * 2));
        mbar_wait(sb + B_KVDONE, 0);
        if (wg) mbar_wait(sb + B_G1DONE, 0);
      };
      if (R.at != 15) {
        const uint64_t db0 = make_desc(sb + 16384, 4096, 512, 2);
        float acc[80];
        mainloop([&](uint32_t o, int kb) {
          wgmma_ss_n160_t11(acc, da0 + o, db0 + o, kb);
#pragma unroll
          for (int k = 1; k < 4; k++) wgmma_ss_n160_t11(acc, da0 + o + k * 128, db0 + o + k * 64, 1);
        });
        pin_regs<80>(acc);
        staged(0);
        gelu_stage<40>(acc, hb, stg + swz, 2, lane ? 0 : sb + B_STG + 8 * wg + 16);
      } else {
        const uint64_t db0 = make_desc(sb + 24576, 4096, 512, 2);
        float acc[96];
        auto block = [&](float* d, uint64_t da, uint64_t db, int kb) {
          wgmma_ss_n96_t11(d, da, db, kb);
#pragma unroll
          for (int k = 1; k < 4; k++) wgmma_ss_n96_t11(d, da + k * 128, db + k * 64, 1);
        };
        if (wg) mainloop([&](uint32_t o, int kb) { block(acc, da0 + o, db0 + o, kb); block(acc + 48, da0 + o + 512, db0 + o, kb); });
        else mainloop([&](uint32_t o, int kb) { block(acc, da0 + o, db0 + o, kb); });
        pin_regs<96>(acc);
        staged(64);
        gelu_stage<48>(acc, hb, stg + swz, 1 + wg, lane ? 0 : sb + B_STG + 8 * wg + 16);
      }
      __syncwarp();
      if (lane == 0) mbar_arrive(sb + B_STG + 8 * wg);
    }
    {
      if (!wg || !PRE1) conv_lda_all(a, sb + SM_CV + 16384 + wg * CV_K + ka0);
#pragma unroll 1
      for (int i = wg; i < R.ncv; i += 2) {
        const bool more = i + 2 < R.ncv;
        const uint32_t dd = lds16(sb + SM_D + (R.ch + i) * 2);
        a[0] = badd2(a[0], ka0 == 32 ? dd : 0); a[2] = badd2(a[2], ka0 == 16 ? dd : 0);
        float acc[128];
        mbar_wait(sb + B_UFULL + 8 * (i & 3), (i >> 2) & 1);
        bar_sync(5 + wg, 256);
        const bool last = i + 1 == R.ncv;
        if (last && elect) mbar_arrive(sb + B_EMPTY);
        if (!w && i < 4) TLREC(22 + i);
        wg_fence();
        conv_mma(acc, a, make_desc(sb + cv_in(i), 4096, 128, 0));
        wg_commit();
        if (!last) bar_arrive(5 + (wg ^ 1), 256);
        if (more) {
          mbar_wait(sb + B_SFREE + 8 * wg, (i >> 1) & 1);
          mbar_wait(sb + B_KFULL + 8 * ((i + 2) & 3), ((i + 2) >> 2) & 1);
        } else if (last) mbar_wait(sb + B_PDONE, 0);
        wg_wait<0>();
        pin_regs<128>(acc);
        if (lane == 0) mbar_arrive(sb + B_CEMPTY + 8 * (i & 3));
        if (last && elect) mbar_arrive(sb + B_EMPTY + 8);
        const uint32_t red = sb + cv_red(i, R.ncv), ka = sb + cv_taps(i + 2) + ka0;
        if (lane < 8 * w) sts32(red + w * CV_REDW + lane * 4, 0);
        const uint32_t wr = red + w * CV_REDW + (8 * (3 - t + w) + g) * 4;
        conv_drain(acc, wr, a, ka, more);
        __syncwarp();
        if (lane == 0) mbar_arrive(sb + B_STG + 8 * wg + (more ? 0 : 16));
      }
      if (!w) TLREC(20 + wg);
    }
    if (R.sg >= 0) {
      const int srow = R.sg * 64 + warp * 16;
      const uint64_t db0 = make_desc(sb + 16384, 16, 1024, 1);
      const uint32_t xo = sb + SM_CV + warp * 2304, xa = xo + (lane & 15) * 144;
      float acc[72];
      Ring r{G1_KB % NSTAGE, (G1_KB / NSTAGE) & 1};
      uint32_t rel = 0;
#pragma unroll 1
      for (int kb = 0; kb < G2_KB; kb++, r.next()) {
        if (kb == G2_KB - G2_TAIL && wg) {
          wg_wait<0>();
          if (elect) mbar_arrive_remote(rel);
          rel = 0;
          bar_sync(7, 256);
        }
        mbar_wait(sb + B_FULL + 8 * r.s, r.ph);
        if (kb == 0 && !w) TLREC(17 + wg);
        if (kb == 8 && warp == 0) TLREC(26);
        if (kb == 20 && warp == 0) TLREC(8);
        if (kb == 27 && warp == 0) TLREC(30);
        const uint64_t da = da0 + r.s * (SLOT >> 4), db = db0 + r.s * (SLOT >> 4);
        wg_fence();
        wgmma_ss_n144_t10(acc, da, db, kb);
#pragma unroll
        for (int k = 1; k < 4; k++) wgmma_ss_n144_t10(acc, da + k * 128, db + k * 2, 1);
        wg_commit();
        if (kb == G2_KB - 1) break;
        wg_wait<1>();
        if (elect && rel) mbar_arrive_remote(rel);
        rel = kb == G2_KB - NSTAGE ? mapa(sb + B_XRDY, rank ^ 1) : sb + B_EMPTY + 8 * r.s;
      }
      if (!wg) bar_arrive(7, 256);
      const uint32_t xz = sb + XSLOT * SLOT + wg * 10240 + wtid * 16;
      const uint32_t rz = mapa(xz, rank ^ 1), rb = mapa(sb + B_XFULL + 16 * wg, rank ^ 1);
      mbar_wait(sb + B_XRDY, 0);
      wg_wait<0>();
      pin_regs<72>(acc);
      if (!w) TLREC(28 + wg);
#pragma unroll
      for (int i = 0; i < 32; i += 8)
        asm volatile("st.async.weak.shared::cluster.mbarrier::complete_tx::bytes.v4.b32 [%0], {%1,%2,%3,%4}, [%5];"
                     :: "r"(rz + i * 256), "r"(pack_bf16(acc[i], acc[i + 1])), "r"(pack_bf16(acc[i + 2], acc[i + 3])),
                        "r"(pack_bf16(acc[i + 4], acc[i + 5])), "r"(pack_bf16(acc[i + 6], acc[i + 7])), "r"(rb + (i < 8 * XP ? 0 : 8)) : "memory");
      asm volatile("st.async.weak.shared::cluster.mbarrier::complete_tx::bytes.v2.b32 [%0], {%1,%2}, [%3];"
                   :: "r"(rz + 8192), "r"(pack_bf16(acc[32], acc[33])), "r"(pack_bf16(acc[34], acc[35])), "r"(rb + 8) : "memory");
      uint32_t xx[18], ss[18];
      mbar_wait(sb + B_XY, 0);
      {
        const uint32_t ya = sb + SM_DED + wg * 9216 + swz;
        const uint4 st0 = lds128(sb + SM_ST + (warp * 16 + g) * 16), st1 = lds128(sb + SM_ST + (warp * 16 + g + 8) * 16);
        const float hb0 = 0.5f * bf_lo(lds16(sb + SM_B2 + (warp * 16 + g) * 2)), hb1 = 0.5f * bf_lo(lds16(sb + SM_B2 + (warp * 16 + g + 8) * 2));
#pragma unroll
        for (int q = 0; q < 8; q += 2) { ldsm4(xx + 2 * q, xa + (lane >> 4) * 16 + q * 16); ldsm4t(ss + 2 * q, ya + q * 1024); }
        ldsm2(xx + 16, xa + 128);
        ldsm2t(ss + 16, ya + 8 * 1024);
#pragma unroll
        for (int i = 0; i < 18; i++) {
          const uint4& st = (i & 1) ? st1 : st0;
          const uint32_t c = bsub2(xx[i], st.x);
          ss[i] = bmul2(bfma2(c, st.y, bmul2(c, st.z)), ss[i]);
        }
#pragma unroll
        for (int i = 36; i < 72; i++) acc[i] = fmaf(acc[i], 0.5f, (i & 2) ? hb1 : hb0);
      }
      char* const op = reinterpret_cast<char*>(P.out) + srow * (D_ * 2) + R.dk * 16 + lane * 16;
      uint32_t oo[5];
#pragma unroll
      for (int j = 0; j < 5; j++) oo[j] = ((lane + 32 * j) * 57 >> 9) * (D_ * 2 - 144) + j * 512;
#pragma unroll
      for (int q = 0; q < 5; q++) {
        if (q == 0 || q == XP) mbar_wait_cluster(sb + B_XFULL + 16 * wg + (q ? 8 : 0), 0);
        if (!w && !q) TLREC(9 + wg);
        const uint4 v = lds128(xz + q * 2048);
        const uint32_t pv[4] = {v.x, v.y, v.z, v.w};
#pragma unroll
        for (int i = 4 * q; i < 4 * q + 4 && i < 18; i++)
          xx[i] = bfma2(ss[i], pack_bf16(silu_half(fmaf(bf_lo(pv[i & 3]), 0.5f, acc[36 + 2 * i])), silu_half(fmaf(bf_hi(pv[i & 3]), 0.5f, acc[37 + 2 * i]))), xx[i]);
        if (q < 4) stsm4(xa + (lane >> 4) * 16 + q * 32, xx[4 * q], xx[4 * q + 1], xx[4 * q + 2], xx[4 * q + 3]);
        else stsm2(xa + 128, xx[16], xx[17]);
      }
      __syncwarp();
      if (lane == 0) mbar_arrive(sb + B_DONE);
#pragma unroll
      for (int j = 0; j < 5; j++)
        if (j < 4 || lane < 16) *reinterpret_cast<uint4*>(op + oo[j]) = lds128(xo + (lane + 32 * j) * 16);
      if (!w) TLREC(11 + wg);
    }
    TLEND();
  }
}

typedef CUresult (*EncodeFn)(CUtensorMap*, CUtensorMapDataType, cuuint32_t, void*, const cuuint64_t*, const cuuint64_t*, const cuuint32_t*,
                             const cuuint32_t*, CUtensorMapInterleave, CUtensorMapSwizzle, CUtensorMapL2promotion, CUtensorMapFloatOOBfill);

void make_map(EncodeFn fn, CUtensorMap* m, const void* ptr, int rank, const cuuint64_t* dims, const cuuint64_t* strides, const cuuint32_t* box,
              CUtensorMapSwizzle sw) {
  const cuuint32_t es[3] = {1, 1, 1};
  fn(m, CU_TENSOR_MAP_DATA_TYPE_BFLOAT16, rank, const_cast<void*>(ptr), dims, strides, box, es, CU_TENSOR_MAP_INTERLEAVE_NONE, sw,
     CU_TENSOR_MAP_L2_PROMOTION_L2_256B, CU_TENSOR_MAP_FLOAT_OOB_FILL_NONE);
}

void make_roles(Role* R) {
  int nl = 0, ch = 0;
  for (int gi = 0; gi < 8; gi++)
    for (int b = 0; b < 132; b++) {
      const int c = b >> 1, rank = b & 1;
      int g, idx;
      if (c < 4) { g = 0; idx = 4 + c; }
      else if (c < 36) { g = (c - 4) & 7; idx = (c - 4) >> 3; }
      else if (c < 64) { g = 1 + (c - 36) % 7; idx = 4 + (c - 36) / 7; }
      else { g = c - 58; idx = 8; }
      if (g != gi) continue;
      Role& r = R[b];
      r.sg = (int8_t)(idx < 8 ? 2 * (2 * g + (idx >> 2)) : -1);
      r.dk = (int8_t)((idx & 3) * 18 + rank * 9);
      r.ds = (int8_t)((idx & 3) * 18 + (rank ^ 1) * 9);
      if (idx < (g < 2 ? 6 : 7)) {
        const int c1 = (g < 2 ? 6 * g : 7 * g - 2) + idx;
        r.fg = (int8_t)((2 * (c1 / 3) + rank) * 2); r.at = (int8_t)(c1 % 3 * 5); r.ncv = NCV_REG;
      } else {
        r.fg = (int8_t)(3 * nl++); r.at = 15; r.ncv = idx < 8 ? NCV_LEFT : NCV_LONG;
      }
      r.ch = (int16_t)ch;
      ch += r.ncv;
    }
}

}

extern "C" void kernel_launch(void* const* d_in, const int* in_sizes, int n_in, void* d_out, int out_size) {
  static Params P;
  static Hot H;
  static const void* cached[5] = {nullptr, nullptr, nullptr, nullptr, nullptr};
  const void* now[5] = {d_in[0], d_in[1], d_in[2], d_in[7], d_in[9]};
  bool same = true;
  for (int i = 0; i < 5; i++) { same = same && cached[i] == now[i]; cached[i] = now[i]; }
  if (!same) {
    void* fp = nullptr;
    cudaDriverEntryPointQueryResult qr;
    cudaGetDriverEntryPoint("cuTensorMapEncodeTiled", &fp, cudaEnableDefault, &qr);
    EncodeFn fn = (EncodeFn)fp;
    void* ps;
    cudaGetSymbolAddress(&ps, g_scratch);
    H.S = (Scratch*)ps;
    const void *pu = (char*)ps + offsetof(Scratch, u), *py = (char*)ps + offsetof(Scratch, y), *pb = (char*)ps + offsetof(Scratch, ub);
    { cuuint64_t d[3] = {64, S_, F_ / 64}, s[2] = {F_ * 2, 128}; cuuint32_t b[3] = {64, 64, 2}; make_map(fn, &P.m_w1, d_in[7], 3, d, s, b, CU_TENSOR_MAP_SWIZZLE_128B);
      b[2] = 3; make_map(fn, &P.m_w1l, d_in[7], 3, d, s, b, CU_TENSOR_MAP_SWIZZLE_128B); }
    { cuuint64_t d[2] = {F_, D_}, s[1] = {F_ * 2}; cuuint32_t b[2] = {64, 32}; make_map(fn, &P.m_ust, pu, 2, d, s, b, CU_TENSOR_MAP_SWIZZLE_128B); }
    { cuuint64_t d[3] = {64, F_, S_ / 64}, s[2] = {S_ * 2, 128}; cuuint32_t b[3] = {64, 64, 2}; make_map(fn, &P.m_w2, d_in[9], 3, d, s, b, CU_TENSOR_MAP_SWIZZLE_128B); }
    { cuuint64_t d[2] = {F_, D_}, s[1] = {F_ * 2}; cuuint32_t b[2] = {64, 72}; make_map(fn, &P.m_uld, pu, 2, d, s, b, CU_TENSOR_MAP_SWIZZLE_128B); }
    { cuuint64_t d[2] = {D_, S_}, s[1] = {D_ * 2}; cuuint32_t b[2] = {72, 16}; make_map(fn, &P.m_x, d_in[0], 2, d, s, b, CU_TENSOR_MAP_SWIZZLE_NONE);
      b[0] = 96; b[1] = 20; make_map(fn, &P.m_k, d_in[1], 2, d, s, b, CU_TENSOR_MAP_SWIZZLE_NONE);
      b[1] = 17; make_map(fn, &P.m_v, d_in[2], 2, d, s, b, CU_TENSOR_MAP_SWIZZLE_NONE); }
    { cuuint64_t d[3] = {64, D_, S_ / 64}, s[2] = {S_ * 2, 128}; cuuint32_t b[3] = {64, 72, 2}; make_map(fn, &P.m_y, py, 3, d, s, b, CU_TENSOR_MAP_SWIZZLE_128B); }
    { cuuint64_t d[3] = {2048, D_ / 2, 4}, s[2] = {16384, 4096}; cuuint32_t b[3] = {16, 48, 2}; make_map(fn, &P.m_ub, pb, 3, d, s, b, CU_TENSOR_MAP_SWIZZLE_32B); }
    make_roles(P.role);
    cudaFuncSetAttribute(fused_kernel, cudaFuncAttributeMaxDynamicSharedMemorySize, SM_TOTAL);
  }
  H.x = (const __nv_bfloat16*)d_in[0];
  H.shift_k = (const __nv_bfloat16*)d_in[3]; H.ssm_k = (const __nv_bfloat16*)d_in[4]; H.ssm_D = (const __nv_bfloat16*)d_in[5];
  H.b1 = (const __nv_bfloat16*)d_in[8]; P.b2 = (const __nv_bfloat16*)d_in[10]; P.out = (__nv_bfloat16*)d_out;
  fused_kernel<<<132, 384, SM_TOTAL>>>(H, P);
}
```

```cpp
#include <cuda_runtime.h>
#include <cuda.h>
#include <cuda_bf16.h>
#include <stddef.h>
#include <stdint.h>

namespace {

constexpr int S_ = 2048, D_ = 576, F_ = 4608;
constexpr int NSTAGE = 5, SLOT = 36864;
constexpr int G1_KB = 32, G2_KB = 36;
constexpr int G1_BYTES = 36864, G2_BYTES = 16384 + 18432;
#define NCV_LEFT 4
constexpr int NCV_REG = 4, NCV_LONG = (D_ - 108 * NCV_REG - 20 * NCV_LEFT) / 4;
static_assert(108 * NCV_REG + 20 * NCV_LEFT + 4 * NCV_LONG == D_, "conv split");
constexpr int KV_ROUNDS = 6;
#define XP 2
#define TUNED(name, idx, val) constexpr int name = val
constexpr int NWE = 1, NW0 = 2;
constexpr int G1_TAIL = 4, G2_TAIL = 3;
constexpr int KV0 = 5;
#define ER1 4
#define ER2 4

constexpr int CV_K = 4224, CV_REDW = 2112 * 2;
constexpr int SM_DED = NSTAGE * SLOT;
constexpr int SM_CV = SM_DED + 20480;
constexpr int SM_ST1 = 0;
constexpr int SM_ST = SM_CV + 18432, SM_B2 = SM_ST + 2048;
constexpr int SM_B1 = SM_CV + 2 * (8192 + CV_K), SM_D = SM_B1 + 384;
constexpr int SM_BAR = SM_D + 1152;
constexpr int SM_TOTAL = SM_BAR + 768;
static_assert(G1_KB % NSTAGE == 2, "slots 0 and 1 hold the last GEMM1 k-blocks and the last two of the first GEMM2 stages");
static_assert(NCV_REG == 4 && NCV_LEFT == 4 && NCV_LONG % 4 == 0, "the last two channels use buffers 2 and 3");
constexpr int XSLOT = (G1_KB + G2_KB) % NSTAGE;
__device__ __forceinline__ uint32_t kv_buf(int q) { return q == 2 ? SM_DED : SM_CV + q * 8192; }
__device__ __forceinline__ uint32_t cv_red(int i, int n) { return i + 2 == n ? SM_CV : (i & 1) && i + 1 < n ? SLOT + 16384 : SM_DED; }
__device__ __forceinline__ uint32_t cv_in(int i) { return (i & 2 ? SLOT : SM_CV) + (i & 1) * 8192; }
__device__ __forceinline__ uint32_t cv_taps(int i) { return (i & 2 ? SM_ST1 + 24576 : SM_CV + 16384) + (i & 1) * CV_K; }
constexpr int bar_at(int i) { return SM_BAR + 8 * i; }
constexpr int B_FULL = bar_at(0)  , B_KFULL = bar_at(5)  , B_UFULL = bar_at(9)  , B_KVDONE = bar_at(13), B_STORED = bar_at(14)  ,
              B_XFULL = bar_at(16)  , B_XY = bar_at(20), B_MISC = bar_at(21),
              B_EMPTY = bar_at(22)  , B_XRDY = bar_at(27),
              B_SFREE = bar_at(28)  , B_PDONE = bar_at(30),
              B_CEMPTY = bar_at(31)  , B_STG = bar_at(35)  ,
              B_G1DONE = bar_at(39), B_DONE = bar_at(40);
constexpr int C_H = 0, C_KV = 1, C_U = 2  , C_Y = 4, C_SYNC = 5, C_EPOCH = 6, C_COUNT = 7;
constexpr uint32_t EPOCH = 128 * 33;

struct Scratch {
  uint32_t cnt[C_COUNT * 32];
  alignas(1024) uint4 stats[S_];
  alignas(1024) __nv_bfloat16 h[S_ * D_];
  alignas(1024) __nv_bfloat16 ub[D_ * 4096];
  alignas(1024) __nv_bfloat16 y[D_ * S_];
  alignas(1024) __nv_bfloat16 u[D_ * F_];
};
__device__ Scratch g_scratch;

struct Hot {
  const __nv_bfloat16 *x, *shift_k, *ssm_k, *ssm_D, *b1;
  Scratch* S;
};
struct Role {
  int8_t fg;
  int8_t at;
  int8_t sg;
  int8_t dk, ds;
  int8_t ncv;
  int16_t ch;
};
struct Params {
  const __nv_bfloat16* b2;
  __nv_bfloat16* out;
  Role role[132];
  CUtensorMap m_w1, m_w1l, m_w2, m_x, m_y, m_k, m_v, m_ub;
};

#define TLREC(i) do { } while (0)
#define TLEND() do { } while (0)

__device__ __forceinline__ uint32_t smem_u32(const void* p) { return (uint32_t)__cvta_generic_to_shared(p); }
__device__ __forceinline__ void mbar_init(uint32_t bar, uint32_t cnt) { asm volatile("mbarrier.init.shared::cta.b64 [%0], %1;" :: "r"(bar), "r"(cnt) : "memory"); }
__device__ __forceinline__ void mbar_expect_tx(uint32_t bar, uint32_t bytes) { asm volatile("mbarrier.arrive.expect_tx.shared::cta.b64 _, [%0], %1;" :: "r"(bar), "r"(bytes) : "memory"); }
__device__ __forceinline__ void mbar_arrive(uint32_t bar) { asm volatile("mbarrier.arrive.shared::cta.b64 _, [%0];" :: "r"(bar) : "memory"); }
__device__ __forceinline__ uint32_t mapa(uint32_t addr, uint32_t cta) { uint32_t r; asm volatile("mapa.shared::cluster.u32 %0, %1, %2;" : "=r"(r) : "r"(addr), "r"(cta)); return r; }
__device__ __forceinline__ void mbar_arrive_remote(uint32_t rbar) { asm volatile("mbarrier.arrive.shared::cluster.b64 _, [%0];" :: "r"(rbar) : "memory"); }
__device__ __forceinline__ uint32_t clk() { uint32_t c; asm volatile("mov.u32 %0, %%clock;" : "=r"(c)); return c; }
__device__ __forceinline__ bool elect_one() {
  uint32_t p; asm volatile("{ .reg .pred p; elect.sync _|p, 0xffffffff; selp.u32 %0, 1, 0, p; }" : "=r"(p)); return p;
}
__device__ __forceinline__ void guard(uint32_t t0) { if ((int32_t)(clk() - t0) < 0) __trap(); }
__device__ __forceinline__ void mbar_wait(uint32_t bar, uint32_t parity) {
  asm volatile("{\n .reg .pred p;\n W_%=:\n mbarrier.try_wait.parity.shared::cta.b64 p, [%0], %1;\n @!p bra W_%=;\n }" :: "r"(bar), "r"(parity) : "memory");
}
__device__ __forceinline__ void mbar_wait_cluster(uint32_t bar, uint32_t parity) {
  asm volatile("{\n .reg .pred p;\n W_%=:\n mbarrier.try_wait.parity.acquire.cluster.shared::cta.b64 p, [%0], %1;\n @!p bra W_%=;\n }" :: "r"(bar), "r"(parity) : "memory");
}
__device__ __forceinline__ bool mbar_try(uint32_t bar, uint32_t parity) {
  uint32_t ok;
  asm volatile("{ .reg .pred p; mbarrier.try_wait.parity.shared::cta.b64 p, [%1], %2, 100000; selp.u32 %0, 1, 0, p; }" : "=r"(ok) : "r"(bar), "r"(parity) : "memory");
  return ok;
}
__device__ __forceinline__ bool mbar_test(uint32_t bar, uint32_t parity) {
  uint32_t ok;
  asm volatile("{ .reg .pred p; mbarrier.test_wait.parity.shared::cta.b64 p, [%1], %2; selp.u32 %0, 1, 0, p; }" : "=r"(ok) : "r"(bar), "r"(parity) : "memory");
  return ok;
}
__device__ __forceinline__ void mbar_wait_guarded(uint32_t bar, uint32_t t0, uint32_t parity = 0) { while (!mbar_try(bar, parity)) guard(t0); }
__device__ __forceinline__ void tma2d(uint32_t dst, const CUtensorMap* m, int c0, int c1, uint32_t bar) {
  asm volatile("cp.async.bulk.tensor.2d.shared::cluster.global.mbarrier::complete_tx::bytes [%0], [%1, {%3, %4}], [%2];"
               :: "r"(dst), "l"(m), "r"(bar), "r"(c0), "r"(c1) : "memory");
}
__device__ __forceinline__ void tma3d(uint32_t dst, const CUtensorMap* m, int c0, int c1, int c2, uint32_t bar) {
  asm volatile("cp.async.bulk.tensor.3d.shared::cluster.global.mbarrier::complete_tx::bytes [%0], [%1, {%3, %4, %5}], [%2];"
               :: "r"(dst), "l"(m), "r"(bar), "r"(c0), "r"(c1), "r"(c2) : "memory");
}
__device__ __forceinline__ void bulk_store(void* dst, uint32_t src, uint32_t bytes) {
  asm volatile("cp.async.bulk.global.shared::cta.bulk_group [%0], [%1], %2;" :: "l"(dst), "r"(src), "r"(bytes) : "memory");
}
__device__ __forceinline__ void bulk_load(uint32_t dst, const void* src, uint32_t bytes, uint32_t bar) {
  asm volatile("cp.async.bulk.shared::cluster.global.mbarrier::complete_tx::bytes [%0], [%1], %2, [%3];" :: "r"(dst), "l"(src), "r"(bytes), "r"(bar) : "memory");
}
__device__ __forceinline__ void tma3d_store(const CUtensorMap* m, uint32_t src, int c0, int c1, int c2) {
  asm volatile("cp.async.bulk.tensor.3d.global.shared::cta.bulk_group [%0, {%2, %3, %4}], [%1];" :: "l"(m), "r"(src), "r"(c0), "r"(c1), "r"(c2) : "memory");
}
__device__ __forceinline__ void bulk_commit() { asm volatile("cp.async.bulk.commit_group;" ::: "memory"); }
__device__ __forceinline__ void bulk_wait_all() { asm volatile("cp.async.bulk.wait_group 0;" ::: "memory"); }
__device__ __forceinline__ void fence_async_smem() { asm volatile("fence.proxy.async.shared::cta;" ::: "memory"); }
__device__ __forceinline__ void fence_async_global() { asm volatile("fence.proxy.async.global;" ::: "memory"); }
__device__ __forceinline__ uint32_t ld_cnt(Scratch* S, int c) { uint32_t v; asm volatile("ld.relaxed.gpu.global.u32 %0, [%1];" : "=r"(v) : "l"(S->cnt + c * 32) : "memory"); return v; }
__device__ __forceinline__ void signal(Scratch* S, int c, uint32_t inc) { asm volatile("red.release.gpu.global.add.u32 [%0], %1;" :: "l"(S->cnt + c * 32), "r"(inc) : "memory"); }
__device__ __forceinline__ bool reached(Scratch* S, int c, uint32_t ep) { return ld_cnt(S, c) - ep >= EPOCH; }
__device__ __forceinline__ void await(Scratch* S, int c, uint32_t ep) { while (!reached(S, c, ep)) { } }
__device__ __forceinline__ void bar_sync(int id, int n) { asm volatile("bar.sync %0, %1;" :: "r"(id), "r"(n) : "memory"); }
__device__ __forceinline__ void bar_arrive(int id, int n) { asm volatile("bar.arrive %0, %1;" :: "r"(id), "r"(n) : "memory"); }
__device__ __forceinline__ void wg_fence() { asm volatile("wgmma.fence.sync.aligned;" ::: "memory"); }
__device__ __forceinline__ void wg_commit() { asm volatile("wgmma.commit_group.sync.aligned;" ::: "memory"); }
template <int N> __device__ __forceinline__ void wg_wait() { asm volatile("wgmma.wait_group.sync.aligned %0;" :: "n"(N) : "memory"); }
template <int N> __device__ __forceinline__ void pin_regs(float* a) {
#pragma unroll
  for (int i = 0; i < N; i++) asm volatile("" : "+f"(a[i]) :: "memory");
}
__device__ __forceinline__ uint64_t make_desc(uint32_t addr, uint32_t lbo, uint32_t sbo, uint32_t swz) {
  return (uint64_t)((addr & 0x3FFFF) >> 4) | ((uint64_t)(lbo >> 4) << 16) | ((uint64_t)(sbo >> 4) << 32) | ((uint64_t)swz << 62);
}
__device__ __forceinline__ uint32_t pack_bf16(float lo, float hi) { uint32_t r; asm("cvt.rn.bf16x2.f32 %0, %1, %2;" : "=r"(r) : "f"(hi), "f"(lo)); return r; }
__device__ __forceinline__ float bf_lo(uint32_t p) { return __uint_as_float(p << 16); }
__device__ __forceinline__ float bf_hi(uint32_t p) { return __uint_as_float(p & 0xffff0000u); }
__device__ __forceinline__ float round_bf16(float v) { return bf_lo(pack_bf16(v, 0.f)); }
__device__ __forceinline__ uint32_t bmul2(uint32_t a, uint32_t b) { uint32_t r; asm("mul.rn.bf16x2 %0, %1, %2;" : "=r"(r) : "r"(a), "r"(b)); return r; }
__device__ __forceinline__ uint32_t badd2(uint32_t a, uint32_t b) { uint32_t r; asm("add.rn.bf16x2 %0, %1, %2;" : "=r"(r) : "r"(a), "r"(b)); return r; }
__device__ __forceinline__ uint32_t bfma2(uint32_t a, uint32_t b, uint32_t c) { uint32_t r; asm("fma.rn.bf16x2 %0, %1, %2, %3;" : "=r"(r) : "r"(a), "r"(b), "r"(c)); return r; }
__device__ __forceinline__ uint32_t bsub2(uint32_t a, uint32_t b) { uint32_t r; asm("sub.rn.bf16x2 %0, %1, %2;" : "=r"(r) : "r"(a), "r"(b)); return r; }
__device__ __forceinline__ float tanh_fast(float v) { float r; asm("tanh.approx.f32 %0, %1;" : "=f"(r) : "f"(v)); return r; }
__device__ __forceinline__ float gelu_half(float h) {
  return fmaf(h, tanh_fast(h * fmaf(h * h, 8.0f * 0.7978845608028654f * 0.044715f, 2.0f * 0.7978845608028654f)), h);
}
__device__ __forceinline__ float silu_half(float h) { return fmaf(h, tanh_fast(h), h); }
__device__ __forceinline__ uint32_t ldg32(const void* p) { uint32_t v; asm volatile("ld.global.u32 %0, [%1];" : "=r"(v) : "l"(p) : "memory"); return v; }
__device__ __forceinline__ uint32_t lds32(uint32_t a) { uint32_t v; asm volatile("ld.shared.u32 %0, [%1];" : "=r"(v) : "r"(a) : "memory"); return v; }
__device__ __forceinline__ uint32_t lds16(uint32_t a) { uint32_t v; asm volatile("ld.shared.u16 %0, [%1];" : "=r"(v) : "r"(a) : "memory"); return v; }
__device__ __forceinline__ uint4 lds128(uint32_t a) { uint4 v; asm volatile("ld.shared.v4.u32 {%0,%1,%2,%3}, [%4];" : "=r"(v.x), "=r"(v.y), "=r"(v.z), "=r"(v.w) : "r"(a) : "memory"); return v; }
__device__ __forceinline__ void sts128(uint32_t a, uint32_t x, uint32_t y, uint32_t z, uint32_t w) {
  asm volatile("st.shared.v4.u32 [%0], {%1,%2,%3,%4};" :: "r"(a), "r"(x), "r"(y), "r"(z), "r"(w) : "memory");
}
__device__ __forceinline__ void sts32(uint32_t a, uint32_t v) { asm volatile("st.shared.u32 [%0], %1;" :: "r"(a), "r"(v) : "memory"); }
__device__ __forceinline__ void ldsm4(uint32_t* r, uint32_t a) {
  asm volatile("ldmatrix.sync.aligned.m8n8.x4.shared.b16 {%0,%1,%2,%3}, [%4];" : "=r"(r[0]), "=r"(r[1]), "=r"(r[2]), "=r"(r[3]) : "r"(a) : "memory");
}
__device__ __forceinline__ void ldsm2(uint32_t* r, uint32_t a) {
  asm volatile("ldmatrix.sync.aligned.m8n8.x2.shared.b16 {%0,%1}, [%2];" : "=r"(r[0]), "=r"(r[1]) : "r"(a) : "memory");
}
__device__ __forceinline__ void ldsm4t(uint32_t* r, uint32_t a) {
  asm volatile("ldmatrix.sync.aligned.m8n8.x4.trans.shared.b16 {%0,%1,%2,%3}, [%4];" : "=r"(r[0]), "=r"(r[1]), "=r"(r[2]), "=r"(r[3]) : "r"(a) : "memory");
}
__device__ __forceinline__ void ldsm2t(uint32_t* r, uint32_t a) {
  asm volatile("ldmatrix.sync.aligned.m8n8.x2.trans.shared.b16 {%0,%1}, [%2];" : "=r"(r[0]), "=r"(r[1]) : "r"(a) : "memory");
}
__device__ __forceinline__ void stsm4(uint32_t a, uint32_t r0, uint32_t r1, uint32_t r2, uint32_t r3) {
  asm volatile("stmatrix.sync.aligned.m8n8.x4.shared.b16 [%0], {%1,%2,%3,%4};" :: "r"(a), "r"(r0), "r"(r1), "r"(r2), "r"(r3) : "memory");
}
__device__ __forceinline__ void stsm2(uint32_t a, uint32_t r0, uint32_t r1) {
  asm volatile("stmatrix.sync.aligned.m8n8.x2.shared.b16 [%0], {%1,%2};" :: "r"(a), "r"(r0), "r"(r1) : "memory");
}
__device__ __forceinline__ void stsm4t(uint32_t a, uint32_t r0, uint32_t r1, uint32_t r2, uint32_t r3) {
  asm volatile("stmatrix.sync.aligned.m8n8.x4.trans.shared.b16 [%0], {%1,%2,%3,%4};" :: "r"(a), "r"(r0), "r"(r1), "r"(r2), "r"(r3) : "memory");
}

__device__ __forceinline__ void wgmma_ss_n144_t10(float* d, uint64_t da, uint64_t db, int sd) {
  asm volatile("{ .reg .pred p; setp.ne.b32 p, %74, 0;\n"
      "wgmma.mma_async.sync.aligned.m64n144k16.f32.bf16.bf16 {"
      "%0,%1,%2,%3,%4,%5,%6,%7,%8,%9,%10,%11,%12,%13,%14,%15,"
      "%16,%17,%18,%19,%20,%21,%22,%23,%24,%25,%26,%27,%28,%29,%30,%31,"
      "%32,%33,%34,%35,%36,%37,%38,%39,%40,%41,%42,%43,%44,%45,%46,%47,"
      "%48,%49,%50,%51,%52,%53,%54,%55,%56,%57,%58,%59,%60,%61,%62,%63,"
      "%64,%65,%66,%67,%68,%69,%70,%71"
      "}, %72, %73, p, 1, 1, 1, 0; }"
    : "+f"(d[0]), "+f"(d[1]), "+f"(d[2]), "+f"(d[3]), "+f"(d[4]), "+f"(d[5]), "+f"(d[6]), "+f"(d[7]),
      "+f"(d[8]), "+f"(d[9]), "+f"(d[10]), "+f"(d[11]), "+f"(d[12]), "+f"(d[13]), "+f"(d[14]), "+f"(d[15]),
      "+f"(d[16]), "+f"(d[17]), "+f"(d[18]), "+f"(d[19]), "+f"(d[20]), "+f"(d[21]), "+f"(d[22]), "+f"(d[23]),
      "+f"(d[24]), "+f"(d[25]), "+f"(d[26]), "+f"(d[27]), "+f"(d[28]), "+f"(d[29]), "+f"(d[30]), "+f"(d[31]),
      "+f"(d[32]), "+f"(d[33]), "+f"(d[34]), "+f"(d[35]), "+f"(d[36]), "+f"(d[37]), "+f"(d[38]), "+f"(d[39]),
      "+f"(d[40]), "+f"(d[41]), "+f"(d[42]), "+f"(d[43]), "+f"(d[44]), "+f"(d[45]), "+f"(d[46]), "+f"(d[47]),
      "+f"(d[48]), "+f"(d[49]), "+f"(d[50]), "+f"(d[51]), "+f"(d[52]), "+f"(d[53]), "+f"(d[54]), "+f"(d[55]),
      "+f"(d[56]), "+f"(d[57]), "+f"(d[58]), "+f"(d[59]), "+f"(d[60]), "+f"(d[61]), "+f"(d[62]), "+f"(d[63]),
      "+f"(d[64]), "+f"(d[65]), "+f"(d[66]), "+f"(d[67]), "+f"(d[68]), "+f"(d[69]), "+f"(d[70]), "+f"(d[71])
    : "l"(da), "l"(db), "r"(sd));
}

__device__ __forceinline__ void wgmma_ss_n160_t11(float* d, uint64_t da, uint64_t db, int sd) {
  asm volatile("{ .reg .pred p; setp.ne.b32 p, %82, 0;\n"
      "wgmma.mma_async.sync.aligned.m64n160k16.f32.bf16.bf16 {"
      "%0,%1,%2,%3,%4,%5,%6,%7,%8,%9,%10,%11,%12,%13,%14,%15,"
      "%16,%17,%18,%19,%20,%21,%22,%23,%24,%25,%26,%27,%28,%29,%30,%31,"
      "%32,%33,%34,%35,%36,%37,%38,%39,%40,%41,%42,%43,%44,%45,%46,%47,"
      "%48,%49,%50,%51,%52,%53,%54,%55,%56,%57,%58,%59,%60,%61,%62,%63,"
      "%64,%65,%66,%67,%68,%69,%70,%71,%72,%73,%74,%75,%76,%77,%78,%79"
      "}, %80, %81, p, 1, 1, 1, 1; }"
    : "+f"(d[0]), "+f"(d[1]), "+f"(d[2]), "+f"(d[3]), "+f"(d[4]), "+f"(d[5]), "+f"(d[6]), "+f"(d[7]),
      "+f"(d[8]), "+f"(d[9]), "+f"(d[10]), "+f"(d[11]), "+f"(d[12]), "+f"(d[13]), "+f"(d[14]), "+f"(d[15]),
      "+f"(d[16]), "+f"(d[17]), "+f"(d[18]), "+f"(d[19]), "+f"(d[20]), "+f"(d[21]), "+f"(d[22]), "+f"(d[23]),
      "+f"(d[24]), "+f"(d[25]), "+f"(d[26]), "+f"(d[27]), "+f"(d[28]), "+f"(d[29]), "+f"(d[30]), "+f"(d[31]),
      "+f"(d[32]), "+f"(d[33]), "+f"(d[34]), "+f"(d[35]), "+f"(d[36]), "+f"(d[37]), "+f"(d[38]), "+f"(d[39]),
      "+f"(d[40]), "+f"(d[41]), "+f"(d[42]), "+f"(d[43]), "+f"(d[44]), "+f"(d[45]), "+f"(d[46]), "+f"(d[47]),
      "+f"(d[48]), "+f"(d[49]), "+f"(d[50]), "+f"(d[51]), "+f"(d[52]), "+f"(d[53]), "+f"(d[54]), "+f"(d[55]),
      "+f"(d[56]), "+f"(d[57]), "+f"(d[58]), "+f"(d[59]), "+f"(d[60]), "+f"(d[61]), "+f"(d[62]), "+f"(d[63]),
      "+f"(d[64]), "+f"(d[65]), "+f"(d[66]), "+f"(d[67]), "+f"(d[68]), "+f"(d[69]), "+f"(d[70]), "+f"(d[71]),
      "+f"(d[72]), "+f"(d[73]), "+f"(d[74]), "+f"(d[75]), "+f"(d[76]), "+f"(d[77]), "+f"(d[78]), "+f"(d[79])
    : "l"(da), "l"(db), "r"(sd));
}

__device__ __forceinline__ void wgmma_ss_n96_t11(float* d, uint64_t da, uint64_t db, int sd) {
  asm volatile("{ .reg .pred p; setp.ne.b32 p, %50, 0;\n"
      "wgmma.mma_async.sync.aligned.m64n96k16.f32.bf16.bf16 {"
      "%0,%1,%2,%3,%4,%5,%6,%7,%8,%9,%10,%11,%12,%13,%14,%15,"
      "%16,%17,%18,%19,%20,%21,%22,%23,%24,%25,%26,%27,%28,%29,%30,%31,"
      "%32,%33,%34,%35,%36,%37,%38,%39,%40,%41,%42,%43,%44,%45,%46,%47"
      "}, %48, %49, p, 1, 1, 1, 1; }"
    : "+f"(d[0]), "+f"(d[1]), "+f"(d[2]), "+f"(d[3]), "+f"(d[4]), "+f"(d[5]), "+f"(d[6]), "+f"(d[7]),
      "+f"(d[8]), "+f"(d[9]), "+f"(d[10]), "+f"(d[11]), "+f"(d[12]), "+f"(d[13]), "+f"(d[14]), "+f"(d[15]),
      "+f"(d[16]), "+f"(d[17]), "+f"(d[18]), "+f"(d[19]), "+f"(d[20]), "+f"(d[21]), "+f"(d[22]), "+f"(d[23]),
      "+f"(d[24]), "+f"(d[25]), "+f"(d[26]), "+f"(d[27]), "+f"(d[28]), "+f"(d[29]), "+f"(d[30]), "+f"(d[31]),
      "+f"(d[32]), "+f"(d[33]), "+f"(d[34]), "+f"(d[35]), "+f"(d[36]), "+f"(d[37]), "+f"(d[38]), "+f"(d[39]),
      "+f"(d[40]), "+f"(d[41]), "+f"(d[42]), "+f"(d[43]), "+f"(d[44]), "+f"(d[45]), "+f"(d[46]), "+f"(d[47])
    : "l"(da), "l"(db), "r"(sd));
}

__device__ __forceinline__ void wgmma_rs_n16(float* d, const uint32_t* a, uint64_t db, int sd) {
  asm volatile("{ .reg .pred p; setp.ne.b32 p, %13, 0;\n"
      "wgmma.mma_async.sync.aligned.m64n16k16.f32.bf16.bf16 {"
      "%0,%1,%2,%3,%4,%5,%6,%7"
      "}, {%8,%9,%10,%11}, %12, p, 1, 1, 0; }"
    : "+f"(d[0]), "+f"(d[1]), "+f"(d[2]), "+f"(d[3]), "+f"(d[4]), "+f"(d[5]), "+f"(d[6]), "+f"(d[7])
    : "r"(a[0]), "r"(a[1]), "r"(a[2]), "r"(a[3]), "l"(db), "r"(sd));
}

__device__ __forceinline__ void wgmma_rs_n32(float* d, const uint32_t* a, uint64_t db, int sd) {
  asm volatile("{ .reg .pred p; setp.ne.b32 p, %21, 0;\n"
      "wgmma.mma_async.sync.aligned.m64n32k16.f32.bf16.bf16 {"
      "%0,%1,%2,%3,%4,%5,%6,%7,%8,%9,%10,%11,%12,%13,%14,%15"
      "}, {%16,%17,%18,%19}, %20, p, 1, 1, 0; }"
    : "+f"(d[0]), "+f"(d[1]), "+f"(d[2]), "+f"(d[3]), "+f"(d[4]), "+f"(d[5]), "+f"(d[6]), "+f"(d[7]),
      "+f"(d[8]), "+f"(d[9]), "+f"(d[10]), "+f"(d[11]), "+f"(d[12]), "+f"(d[13]), "+f"(d[14]), "+f"(d[15])
    : "r"(a[0]), "r"(a[1]), "r"(a[2]), "r"(a[3]), "l"(db), "r"(sd));
}

__device__ __forceinline__ void wgmma_rs_n48(float* d, const uint32_t* a, uint64_t db, int sd) {
  asm volatile("{ .reg .pred p; setp.ne.b32 p, %29, 0;\n"
      "wgmma.mma_async.sync.aligned.m64n48k16.f32.bf16.bf16 {"
      "%0,%1,%2,%3,%4,%5,%6,%7,%8,%9,%10,%11,%12,%13,%14,%15,"
      "%16,%17,%18,%19,%20,%21,%22,%23"
      "}, {%24,%25,%26,%27}, %28, p, 1, 1, 0; }"
    : "+f"(d[0]), "+f"(d[1]), "+f"(d[2]), "+f"(d[3]), "+f"(d[4]), "+f"(d[5]), "+f"(d[6]), "+f"(d[7]),
      "+f"(d[8]), "+f"(d[9]), "+f"(d[10]), "+f"(d[11]), "+f"(d[12]), "+f"(d[13]), "+f"(d[14]), "+f"(d[15]),
      "+f"(d[16]), "+f"(d[17]), "+f"(d[18]), "+f"(d[19]), "+f"(d[20]), "+f"(d[21]), "+f"(d[22]), "+f"(d[23])
    : "r"(a[0]), "r"(a[1]), "r"(a[2]), "r"(a[3]), "l"(db), "r"(sd));
}

__device__ __forceinline__ void wgmma_rs_n64(float* d, const uint32_t* a, uint64_t db, int sd) {
  asm volatile("{ .reg .pred p; setp.ne.b32 p, %37, 0;\n"
      "wgmma.mma_async.sync.aligned.m64n64k16.f32.bf16.bf16 {"
      "%0,%1,%2,%3,%4,%5,%6,%7,%8,%9,%10,%11,%12,%13,%14,%15,"
      "%16,%17,%18,%19,%20,%21,%22,%23,%24,%25,%26,%27,%28,%29,%30,%31"
      "}, {%32,%33,%34,%35}, %36, p, 1, 1, 0; }"
    : "+f"(d[0]), "+f"(d[1]), "+f"(d[2]), "+f"(d[3]), "+f"(d[4]), "+f"(d[5]), "+f"(d[6]), "+f"(d[7]),
      "+f"(d[8]), "+f"(d[9]), "+f"(d[10]), "+f"(d[11]), "+f"(d[12]), "+f"(d[13]), "+f"(d[14]), "+f"(d[15]),
      "+f"(d[16]), "+f"(d[17]), "+f"(d[18]), "+f"(d[19]), "+f"(d[20]), "+f"(d[21]), "+f"(d[22]), "+f"(d[23]),
      "+f"(d[24]), "+f"(d[25]), "+f"(d[26]), "+f"(d[27]), "+f"(d[28]), "+f"(d[29]), "+f"(d[30]), "+f"(d[31])
    : "r"(a[0]), "r"(a[1]), "r"(a[2]), "r"(a[3]), "l"(db), "r"(sd));
}

__device__ __forceinline__ void wgmma_rs_n80(float* d, const uint32_t* a, uint64_t db, int sd) {
  asm volatile("{ .reg .pred p; setp.ne.b32 p, %45, 0;\n"
      "wgmma.mma_async.sync.aligned.m64n80k16.f32.bf16.bf16 {"
      "%0,%1,%2,%3,%4,%5,%6,%7,%8,%9,%10,%11,%12,%13,%14,%15,"
      "%16,%17,%18,%19,%20,%21,%22,%23,%24,%25,%26,%27,%28,%29,%30,%31,"
      "%32,%33,%34,%35,%36,%37,%38,%39"
      "}, {%40,%41,%42,%43}, %44, p, 1, 1, 0; }"
    : "+f"(d[0]), "+f"(d[1]), "+f"(d[2]), "+f"(d[3]), "+f"(d[4]), "+f"(d[5]), "+f"(d[6]), "+f"(d[7]),
      "+f"(d[8]), "+f"(d[9]), "+f"(d[10]), "+f"(d[11]), "+f"(d[12]), "+f"(d[13]), "+f"(d[14]), "+f"(d[15]),
      "+f"(d[16]), "+f"(d[17]), "+f"(d[18]), "+f"(d[19]), "+f"(d[20]), "+f"(d[21]), "+f"(d[22]), "+f"(d[23]),
      "+f"(d[24]), "+f"(d[25]), "+f"(d[26]), "+f"(d[27]), "+f"(d[28]), "+f"(d[29]), "+f"(d[30]), "+f"(d[31]),
      "+f"(d[32]), "+f"(d[33]), "+f"(d[34]), "+f"(d[35]), "+f"(d[36]), "+f"(d[37]), "+f"(d[38]), "+f"(d[39])
    : "r"(a[0]), "r"(a[1]), "r"(a[2]), "r"(a[3]), "l"(db), "r"(sd));
}

__device__ __forceinline__ void wgmma_rs_n96(float* d, const uint32_t* a, uint64_t db, int sd) {
  asm volatile("{ .reg .pred p; setp.ne.b32 p, %53, 0;\n"
      "wgmma.mma_async.sync.aligned.m64n96k16.f32.bf16.bf16 {"
      "%0,%1,%2,%3,%4,%5,%6,%7,%8,%9,%10,%11,%12,%13,%14,%15,"
      "%16,%17,%18,%19,%20,%21,%22,%23,%24,%25,%26,%27,%28,%29,%30,%31,"
      "%32,%33,%34,%35,%36,%37,%38,%39,%40,%41,%42,%43,%44,%45,%46,%47"
      "}, {%48,%49,%50,%51}, %52, p, 1, 1, 0; }"
    : "+f"(d[0]), "+f"(d[1]), "+f"(d[2]), "+f"(d[3]), "+f"(d[4]), "+f"(d[5]), "+f"(d[6]), "+f"(d[7]),
      "+f"(d[8]), "+f"(d[9]), "+f"(d[10]), "+f"(d[11]), "+f"(d[12]), "+f"(d[13]), "+f"(d[14]), "+f"(d[15]),
      "+f"(d[16]), "+f"(d[17]), "+f"(d[18]), "+f"(d[19]), "+f"(d[20]), "+f"(d[21]), "+f"(d[22]), "+f"(d[23]),
      "+f"(d[24]), "+f"(d[25]), "+f"(d[26]), "+f"(d[27]), "+f"(d[28]), "+f"(d[29]), "+f"(d[30]), "+f"(d[31]),
      "+f"(d[32]), "+f"(d[33]), "+f"(d[34]), "+f"(d[35]), "+f"(d[36]), "+f"(d[37]), "+f"(d[38]), "+f"(d[39]),
      "+f"(d[40]), "+f"(d[41]), "+f"(d[42]), "+f"(d[43]), "+f"(d[44]), "+f"(d[45]), "+f"(d[46]), "+f"(d[47])
    : "r"(a[0]), "r"(a[1]), "r"(a[2]), "r"(a[3]), "l"(db), "r"(sd));
}

__device__ __forceinline__ void wgmma_rs_n112(float* d, const uint32_t* a, uint64_t db, int sd) {
  asm volatile("{ .reg .pred p; setp.ne.b32 p, %61, 0;\n"
      "wgmma.mma_async.sync.aligned.m64n112k16.f32.bf16.bf16 {"
      "%0,%1,%2,%3,%4,%5,%6,%7,%8,%9,%10,%11,%12,%13,%14,%15,"
      "%16,%17,%18,%19,%20,%21,%22,%23,%24,%25,%26,%27,%28,%29,%30,%31,"
      "%32,%33,%34,%35,%36,%37,%38,%39,%40,%41,%42,%43,%44,%45,%46,%47,"
      "%48,%49,%50,%51,%52,%53,%54,%55"
      "}, {%56,%57,%58,%59}, %60, p, 1, 1, 0; }"
    : "+f"(d[0]), "+f"(d[1]), "+f"(d[2]), "+f"(d[3]), "+f"(d[4]), "+f"(d[5]), "+f"(d[6]), "+f"(d[7]),
      "+f"(d[8]), "+f"(d[9]), "+f"(d[10]), "+f"(d[11]), "+f"(d[12]), "+f"(d[13]), "+f"(d[14]), "+f"(d[15]),
      "+f"(d[16]), "+f"(d[17]), "+f"(d[18]), "+f"(d[19]), "+f"(d[20]), "+f"(d[21]), "+f"(d[22]), "+f"(d[23]),
      "+f"(d[24]), "+f"(d[25]), "+f"(d[26]), "+f"(d[27]), "+f"(d[28]), "+f"(d[29]), "+f"(d[30]), "+f"(d[31]),
      "+f"(d[32]), "+f"(d[33]), "+f"(d[34]), "+f"(d[35]), "+f"(d[36]), "+f"(d[37]), "+f"(d[38]), "+f"(d[39]),
      "+f"(d[40]), "+f"(d[41]), "+f"(d[42]), "+f"(d[43]), "+f"(d[44]), "+f"(d[45]), "+f"(d[46]), "+f"(d[47]),
      "+f"(d[48]), "+f"(d[49]), "+f"(d[50]), "+f"(d[51]), "+f"(d[52]), "+f"(d[53]), "+f"(d[54]), "+f"(d[55])
    : "r"(a[0]), "r"(a[1]), "r"(a[2]), "r"(a[3]), "l"(db), "r"(sd));
}

__device__ __forceinline__ void wgmma_rs_n128(float* d, const uint32_t* a, uint64_t db, int sd) {
  asm volatile("{ .reg .pred p; setp.ne.b32 p, %69, 0;\n"
      "wgmma.mma_async.sync.aligned.m64n128k16.f32.bf16.bf16 {"
      "%0,%1,%2,%3,%4,%5,%6,%7,%8,%9,%10,%11,%12,%13,%14,%15,"
      "%16,%17,%18,%19,%20,%21,%22,%23,%24,%25,%26,%27,%28,%29,%30,%31,"
      "%32,%33,%34,%35,%36,%37,%38,%39,%40,%41,%42,%43,%44,%45,%46,%47,"
      "%48,%49,%50,%51,%52,%53,%54,%55,%56,%57,%58,%59,%60,%61,%62,%63"
      "}, {%64,%65,%66,%67}, %68, p, 1, 1, 0; }"
    : "+f"(d[0]), "+f"(d[1]), "+f"(d[2]), "+f"(d[3]), "+f"(d[4]), "+f"(d[5]), "+f"(d[6]), "+f"(d[7]),
      "+f"(d[8]), "+f"(d[9]), "+f"(d[10]), "+f"(d[11]), "+f"(d[12]), "+f"(d[13]), "+f"(d[14]), "+f"(d[15]),
      "+f"(d[16]), "+f"(d[17]), "+f"(d[18]), "+f"(d[19]), "+f"(d[20]), "+f"(d[21]), "+f"(d[22]), "+f"(d[23]),
      "+f"(d[24]), "+f"(d[25]), "+f"(d[26]), "+f"(d[27]), "+f"(d[28]), "+f"(d[29]), "+f"(d[30]), "+f"(d[31]),
      "+f"(d[32]), "+f"(d[33]), "+f"(d[34]), "+f"(d[35]), "+f"(d[36]), "+f"(d[37]), "+f"(d[38]), "+f"(d[39]),
      "+f"(d[40]), "+f"(d[41]), "+f"(d[42]), "+f"(d[43]), "+f"(d[44]), "+f"(d[45]), "+f"(d[46]), "+f"(d[47]),
      "+f"(d[48]), "+f"(d[49]), "+f"(d[50]), "+f"(d[51]), "+f"(d[52]), "+f"(d[53]), "+f"(d[54]), "+f"(d[55]),
      "+f"(d[56]), "+f"(d[57]), "+f"(d[58]), "+f"(d[59]), "+f"(d[60]), "+f"(d[61]), "+f"(d[62]), "+f"(d[63])
    : "r"(a[0]), "r"(a[1]), "r"(a[2]), "r"(a[3]), "l"(db), "r"(sd));
}

__device__ __forceinline__ void wgmma_rs_n144(float* d, const uint32_t* a, uint64_t db, int sd) {
  asm volatile("{ .reg .pred p; setp.ne.b32 p, %77, 0;\n"
      "wgmma.mma_async.sync.aligned.m64n144k16.f32.bf16.bf16 {"
      "%0,%1,%2,%3,%4,%5,%6,%7,%8,%9,%10,%11,%12,%13,%14,%15,"
      "%16,%17,%18,%19,%20,%21,%22,%23,%24,%25,%26,%27,%28,%29,%30,%31,"
      "%32,%33,%34,%35,%36,%37,%38,%39,%40,%41,%42,%43,%44,%45,%46,%47,"
      "%48,%49,%50,%51,%52,%53,%54,%55,%56,%57,%58,%59,%60,%61,%62,%63,"
      "%64,%65,%66,%67,%68,%69,%70,%71"
      "}, {%72,%73,%74,%75}, %76, p, 1, 1, 0; }"
    : "+f"(d[0]), "+f"(d[1]), "+f"(d[2]), "+f"(d[3]), "+f"(d[4]), "+f"(d[5]), "+f"(d[6]), "+f"(d[7]),
      "+f"(d[8]), "+f"(d[9]), "+f"(d[10]), "+f"(d[11]), "+f"(d[12]), "+f"(d[13]), "+f"(d[14]), "+f"(d[15]),
      "+f"(d[16]), "+f"(d[17]), "+f"(d[18]), "+f"(d[19]), "+f"(d[20]), "+f"(d[21]), "+f"(d[22]), "+f"(d[23]),
      "+f"(d[24]), "+f"(d[25]), "+f"(d[26]), "+f"(d[27]), "+f"(d[28]), "+f"(d[29]), "+f"(d[30]), "+f"(d[31]),
      "+f"(d[32]), "+f"(d[33]), "+f"(d[34]), "+f"(d[35]), "+f"(d[36]), "+f"(d[37]), "+f"(d[38]), "+f"(d[39]),
      "+f"(d[40]), "+f"(d[41]), "+f"(d[42]), "+f"(d[43]), "+f"(d[44]), "+f"(d[45]), "+f"(d[46]), "+f"(d[47]),
      "+f"(d[48]), "+f"(d[49]), "+f"(d[50]), "+f"(d[51]), "+f"(d[52]), "+f"(d[53]), "+f"(d[54]), "+f"(d[55]),
      "+f"(d[56]), "+f"(d[57]), "+f"(d[58]), "+f"(d[59]), "+f"(d[60]), "+f"(d[61]), "+f"(d[62]), "+f"(d[63]),
      "+f"(d[64]), "+f"(d[65]), "+f"(d[66]), "+f"(d[67]), "+f"(d[68]), "+f"(d[69]), "+f"(d[70]), "+f"(d[71])
    : "r"(a[0]), "r"(a[1]), "r"(a[2]), "r"(a[3]), "l"(db), "r"(sd));
}

__device__ __forceinline__ void wgmma_rs_n160(float* d, const uint32_t* a, uint64_t db, int sd) {
  asm volatile("{ .reg .pred p; setp.ne.b32 p, %85, 0;\n"
      "wgmma.mma_async.sync.aligned.m64n160k16.f32.bf16.bf16 {"
      "%0,%1,%2,%3,%4,%5,%6,%7,%8,%9,%10,%11,%12,%13,%14,%15,"
      "%16,%17,%18,%19,%20,%21,%22,%23,%24,%25,%26,%27,%28,%29,%30,%31,"
      "%32,%33,%34,%35,%36,%37,%38,%39,%40,%41,%42,%43,%44,%45,%46,%47,"
      "%48,%49,%50,%51,%52,%53,%54,%55,%56,%57,%58,%59,%60,%61,%62,%63,"
      "%64,%65,%66,%67,%68,%69,%70,%71,%72,%73,%74,%75,%76,%77,%78,%79"
      "}, {%80,%81,%82,%83}, %84, p, 1, 1, 0; }"
    : "+f"(d[0]), "+f"(d[1]), "+f"(d[2]), "+f"(d[3]), "+f"(d[4]), "+f"(d[5]), "+f"(d[6]), "+f"(d[7]),
      "+f"(d[8]), "+f"(d[9]), "+f"(d[10]), "+f"(d[11]), "+f"(d[12]), "+f"(d[13]), "+f"(d[14]), "+f"(d[15]),
      "+f"(d[16]), "+f"(d[17]), "+f"(d[18]), "+f"(d[19]), "+f"(d[20]), "+f"(d[21]), "+f"(d[22]), "+f"(d[23]),
      "+f"(d[24]), "+f"(d[25]), "+f"(d[26]), "+f"(d[27]), "+f"(d[28]), "+f"(d[29]), "+f"(d[30]), "+f"(d[31]),
      "+f"(d[32]), "+f"(d[33]), "+f"(d[34]), "+f"(d[35]), "+f"(d[36]), "+f"(d[37]), "+f"(d[38]), "+f"(d[39]),
      "+f"(d[40]), "+f"(d[41]), "+f"(d[42]), "+f"(d[43]), "+f"(d[44]), "+f"(d[45]), "+f"(d[46]), "+f"(d[47]),
      "+f"(d[48]), "+f"(d[49]), "+f"(d[50]), "+f"(d[51]), "+f"(d[52]), "+f"(d[53]), "+f"(d[54]), "+f"(d[55]),
      "+f"(d[56]), "+f"(d[57]), "+f"(d[58]), "+f"(d[59]), "+f"(d[60]), "+f"(d[61]), "+f"(d[62]), "+f"(d[63]),
      "+f"(d[64]), "+f"(d[65]), "+f"(d[66]), "+f"(d[67]), "+f"(d[68]), "+f"(d[69]), "+f"(d[70]), "+f"(d[71]),
      "+f"(d[72]), "+f"(d[73]), "+f"(d[74]), "+f"(d[75]), "+f"(d[76]), "+f"(d[77]), "+f"(d[78]), "+f"(d[79])
    : "r"(a[0]), "r"(a[1]), "r"(a[2]), "r"(a[3]), "l"(db), "r"(sd));
}

__device__ __forceinline__ void wgmma_rs_n176(float* d, const uint32_t* a, uint64_t db, int sd) {
  asm volatile("{ .reg .pred p; setp.ne.b32 p, %93, 0;\n"
      "wgmma.mma_async.sync.aligned.m64n176k16.f32.bf16.bf16 {"
      "%0,%1,%2,%3,%4,%5,%6,%7,%8,%9,%10,%11,%12,%13,%14,%15,"
      "%16,%17,%18,%19,%20,%21,%22,%23,%24,%25,%26,%27,%28,%29,%30,%31,"
      "%32,%33,%34,%35,%36,%37,%38,%39,%40,%41,%42,%43,%44,%45,%46,%47,"
      "%48,%49,%50,%51,%52,%53,%54,%55,%56,%57,%58,%59,%60,%61,%62,%63,"
      "%64,%65,%66,%67,%68,%69,%70,%71,%72,%73,%74,%75,%76,%77,%78,%79,"
      "%80,%81,%82,%83,%84,%85,%86,%87"
      "}, {%88,%89,%90,%91}, %92, p, 1, 1, 0; }"
    : "+f"(d[0]), "+f"(d[1]), "+f"(d[2]), "+f"(d[3]), "+f"(d[4]), "+f"(d[5]), "+f"(d[6]), "+f"(d[7]),
      "+f"(d[8]), "+f"(d[9]), "+f"(d[10]), "+f"(d[11]), "+f"(d[12]), "+f"(d[13]), "+f"(d[14]), "+f"(d[15]),
      "+f"(d[16]), "+f"(d[17]), "+f"(d[18]), "+f"(d[19]), "+f"(d[20]), "+f"(d[21]), "+f"(d[22]), "+f"(d[23]),
      "+f"(d[24]), "+f"(d[25]), "+f"(d[26]), "+f"(d[27]), "+f"(d[28]), "+f"(d[29]), "+f"(d[30]), "+f"(d[31]),
      "+f"(d[32]), "+f"(d[33]), "+f"(d[34]), "+f"(d[35]), "+f"(d[36]), "+f"(d[37]), "+f"(d[38]), "+f"(d[39]),
      "+f"(d[40]), "+f"(d[41]), "+f"(d[42]), "+f"(d[43]), "+f"(d[44]), "+f"(d[45]), "+f"(d[46]), "+f"(d[47]),
      "+f"(d[48]), "+f"(d[49]), "+f"(d[50]), "+f"(d[51]), "+f"(d[52]), "+f"(d[53]), "+f"(d[54]), "+f"(d[55]),
      "+f"(d[56]), "+f"(d[57]), "+f"(d[58]), "+f"(d[59]), "+f"(d[60]), "+f"(d[61]), "+f"(d[62]), "+f"(d[63]),
      "+f"(d[64]), "+f"(d[65]), "+f"(d[66]), "+f"(d[67]), "+f"(d[68]), "+f"(d[69]), "+f"(d[70]), "+f"(d[71]),
      "+f"(d[72]), "+f"(d[73]), "+f"(d[74]), "+f"(d[75]), "+f"(d[76]), "+f"(d[77]), "+f"(d[78]), "+f"(d[79]),
      "+f"(d[80]), "+f"(d[81]), "+f"(d[82]), "+f"(d[83]), "+f"(d[84]), "+f"(d[85]), "+f"(d[86]), "+f"(d[87])
    : "r"(a[0]), "r"(a[1]), "r"(a[2]), "r"(a[3]), "l"(db), "r"(sd));
}

__device__ __forceinline__ void wgmma_rs_n192(float* d, const uint32_t* a, uint64_t db, int sd) {
  asm volatile("{ .reg .pred p; setp.ne.b32 p, %101, 0;\n"
      "wgmma.mma_async.sync.aligned.m64n192k16.f32.bf16.bf16 {"
      "%0,%1,%2,%3,%4,%5,%6,%7,%8,%9,%10,%11,%12,%13,%14,%15,"
      "%16,%17,%18,%19,%20,%21,%22,%23,%24,%25,%26,%27,%28,%29,%30,%31,"
      "%32,%33,%34,%35,%36,%37,%38,%39,%40,%41,%42,%43,%44,%45,%46,%47,"
      "%48,%49,%50,%51,%52,%53,%54,%55,%56,%57,%58,%59,%60,%61,%62,%63,"
      "%64,%65,%66,%67,%68,%69,%70,%71,%72,%73,%74,%75,%76,%77,%78,%79,"
      "%80,%81,%82,%83,%84,%85,%86,%87,%88,%89,%90,%91,%92,%93,%94,%95"
      "}, {%96,%97,%98,%99}, %100, p, 1, 1, 0; }"
    : "+f"(d[0]), "+f"(d[1]), "+f"(d[2]), "+f"(d[3]), "+f"(d[4]), "+f"(d[5]), "+f"(d[6]), "+f"(d[7]),
      "+f"(d[8]), "+f"(d[9]), "+f"(d[10]), "+f"(d[11]), "+f"(d[12]), "+f"(d[13]), "+f"(d[14]), "+f"(d[15]),
      "+f"(d[16]), "+f"(d[17]), "+f"(d[18]), "+f"(d[19]), "+f"(d[20]), "+f"(d[21]), "+f"(d[22]), "+f"(d[23]),
      "+f"(d[24]), "+f"(d[25]), "+f"(d[26]), "+f"(d[27]), "+f"(d[28]), "+f"(d[29]), "+f"(d[30]), "+f"(d[31]),
      "+f"(d[32]), "+f"(d[33]), "+f"(d[34]), "+f"(d[35]), "+f"(d[36]), "+f"(d[37]), "+f"(d[38]), "+f"(d[39]),
      "+f"(d[40]), "+f"(d[41]), "+f"(d[42]), "+f"(d[43]), "+f"(d[44]), "+f"(d[45]), "+f"(d[46]), "+f"(d[47]),
      "+f"(d[48]), "+f"(d[49]), "+f"(d[50]), "+f"(d[51]), "+f"(d[52]), "+f"(d[53]), "+f"(d[54]), "+f"(d[55]),
      "+f"(d[56]), "+f"(d[57]), "+f"(d[58]), "+f"(d[59]), "+f"(d[60]), "+f"(d[61]), "+f"(d[62]), "+f"(d[63]),
      "+f"(d[64]), "+f"(d[65]), "+f"(d[66]), "+f"(d[67]), "+f"(d[68]), "+f"(d[69]), "+f"(d[70]), "+f"(d[71]),
      "+f"(d[72]), "+f"(d[73]), "+f"(d[74]), "+f"(d[75]), "+f"(d[76]), "+f"(d[77]), "+f"(d[78]), "+f"(d[79]),
      "+f"(d[80]), "+f"(d[81]), "+f"(d[82]), "+f"(d[83]), "+f"(d[84]), "+f"(d[85]), "+f"(d[86]), "+f"(d[87]),
      "+f"(d[88]), "+f"(d[89]), "+f"(d[90]), "+f"(d[91]), "+f"(d[92]), "+f"(d[93]), "+f"(d[94]), "+f"(d[95])
    : "r"(a[0]), "r"(a[1]), "r"(a[2]), "r"(a[3]), "l"(db), "r"(sd));
}

__device__ __forceinline__ void wgmma_rs_n208(float* d, const uint32_t* a, uint64_t db, int sd) {
  asm volatile("{ .reg .pred p; setp.ne.b32 p, %109, 0;\n"
      "wgmma.mma_async.sync.aligned.m64n208k16.f32.bf16.bf16 {"
      "%0,%1,%2,%3,%4,%5,%6,%7,%8,%9,%10,%11,%12,%13,%14,%15,"
      "%16,%17,%18,%19,%20,%21,%22,%23,%24,%25,%26,%27,%28,%29,%30,%31,"
      "%32,%33,%34,%35,%36,%37,%38,%39,%40,%41,%42,%43,%44,%45,%46,%47,"
      "%48,%49,%50,%51,%52,%53,%54,%55,%56,%57,%58,%59,%60,%61,%62,%63,"
      "%64,%65,%66,%67,%68,%69,%70,%71,%72,%73,%74,%75,%76,%77,%78,%79,"
      "%80,%81,%82,%83,%84,%85,%86,%87,%88,%89,%90,%91,%92,%93,%94,%95,"
      "%96,%97,%98,%99,%100,%101,%102,%103"
      "}, {%104,%105,%106,%107}, %108, p, 1, 1, 0; }"
    : "+f"(d[0]), "+f"(d[1]), "+f"(d[2]), "+f"(d[3]), "+f"(d[4]), "+f"(d[5]), "+f"(d[6]), "+f"(d[7]),
      "+f"(d[8]), "+f"(d[9]), "+f"(d[10]), "+f"(d[11]), "+f"(d[12]), "+f"(d[13]), "+f"(d[14]), "+f"(d[15]),
      "+f"(d[16]), "+f"(d[17]), "+f"(d[18]), "+f"(d[19]), "+f"(d[20]), "+f"(d[21]), "+f"(d[22]), "+f"(d[23]),
      "+f"(d[24]), "+f"(d[25]), "+f"(d[26]), "+f"(d[27]), "+f"(d[28]), "+f"(d[29]), "+f"(d[30]), "+f"(d[31]),
      "+f"(d[32]), "+f"(d[33]), "+f"(d[34]), "+f"(d[35]), "+f"(d[36]), "+f"(d[37]), "+f"(d[38]), "+f"(d[39]),
      "+f"(d[40]), "+f"(d[41]), "+f"(d[42]), "+f"(d[43]), "+f"(d[44]), "+f"(d[45]), "+f"(d[46]), "+f"(d[47]),
      "+f"(d[48]), "+f"(d[49]), "+f"(d[50]), "+f"(d[51]), "+f"(d[52]), "+f"(d[53]), "+f"(d[54]), "+f"(d[55]),
      "+f"(d[56]), "+f"(d[57]), "+f"(d[58]), "+f"(d[59]), "+f"(d[60]), "+f"(d[61]), "+f"(d[62]), "+f"(d[63]),
      "+f"(d[64]), "+f"(d[65]), "+f"(d[66]), "+f"(d[67]), "+f"(d[68]), "+f"(d[69]), "+f"(d[70]), "+f"(d[71]),
      "+f"(d[72]), "+f"(d[73]), "+f"(d[74]), "+f"(d[75]), "+f"(d[76]), "+f"(d[77]), "+f"(d[78]), "+f"(d[79]),
      "+f"(d[80]), "+f"(d[81]), "+f"(d[82]), "+f"(d[83]), "+f"(d[84]), "+f"(d[85]), "+f"(d[86]), "+f"(d[87]),
      "+f"(d[88]), "+f"(d[89]), "+f"(d[90]), "+f"(d[91]), "+f"(d[92]), "+f"(d[93]), "+f"(d[94]), "+f"(d[95]),
      "+f"(d[96]), "+f"(d[97]), "+f"(d[98]), "+f"(d[99]), "+f"(d[100]), "+f"(d[101]), "+f"(d[102]), "+f"(d[103])
    : "r"(a[0]), "r"(a[1]), "r"(a[2]), "r"(a[3]), "l"(db), "r"(sd));
}

__device__ __forceinline__ void wgmma_rs_n224(float* d, const uint32_t* a, uint64_t db, int sd) {
  asm volatile("{ .reg .pred p; setp.ne.b32 p, %117, 0;\n"
      "wgmma.mma_async.sync.aligned.m64n224k16.f32.bf16.bf16 {"
      "%0,%1,%2,%3,%4,%5,%6,%7,%8,%9,%10,%11,%12,%13,%14,%15,"
      "%16,%17,%18,%19,%20,%21,%22,%23,%24,%25,%26,%27,%28,%29,%30,%31,"
      "%32,%33,%34,%35,%36,%37,%38,%39,%40,%41,%42,%43,%44,%45,%46,%47,"
      "%48,%49,%50,%51,%52,%53,%54,%55,%56,%57,%58,%59,%60,%61,%62,%63,"
      "%64,%65,%66,%67,%68,%69,%70,%71,%72,%73,%74,%75,%76,%77,%78,%79,"
      "%80,%81,%82,%83,%84,%85,%86,%87,%88,%89,%90,%91,%92,%93,%94,%95,"
      "%96,%97,%98,%99,%100,%101,%102,%103,%104,%105,%106,%107,%108,%109,%110,%111"
      "}, {%112,%113,%114,%115}, %116, p, 1, 1, 0; }"
    : "+f"(d[0]), "+f"(d[1]), "+f"(d[2]), "+f"(d[3]), "+f"(d[4]), "+f"(d[5]), "+f"(d[6]), "+f"(d[7]),
      "+f"(d[8]), "+f"(d[9]), "+f"(d[10]), "+f"(d[11]), "+f"(d[12]), "+f"(d[13]), "+f"(d[14]), "+f"(d[15]),
      "+f"(d[16]), "+f"(d[17]), "+f"(d[18]), "+f"(d[19]), "+f"(d[20]), "+f"(d[21]), "+f"(d[22]), "+f"(d[23]),
      "+f"(d[24]), "+f"(d[25]), "+f"(d[26]), "+f"(d[27]), "+f"(d[28]), "+f"(d[29]), "+f"(d[30]), "+f"(d[31]),
      "+f"(d[32]), "+f"(d[33]), "+f"(d[34]), "+f"(d[35]), "+f"(d[36]), "+f"(d[37]), "+f"(d[38]), "+f"(d[39]),
      "+f"(d[40]), "+f"(d[41]), "+f"(d[42]), "+f"(d[43]), "+f"(d[44]), "+f"(d[45]), "+f"(d[46]), "+f"(d[47]),
      "+f"(d[48]), "+f"(d[49]), "+f"(d[50]), "+f"(d[51]), "+f"(d[52]), "+f"(d[53]), "+f"(d[54]), "+f"(d[55]),
      "+f"(d[56]), "+f"(d[57]), "+f"(d[58]), "+f"(d[59]), "+f"(d[60]), "+f"(d[61]), "+f"(d[62]), "+f"(d[63]),
      "+f"(d[64]), "+f"(d[65]), "+f"(d[66]), "+f"(d[67]), "+f"(d[68]), "+f"(d[69]), "+f"(d[70]), "+f"(d[71]),
      "+f"(d[72]), "+f"(d[73]), "+f"(d[74]), "+f"(d[75]), "+f"(d[76]), "+f"(d[77]), "+f"(d[78]), "+f"(d[79]),
      "+f"(d[80]), "+f"(d[81]), "+f"(d[82]), "+f"(d[83]), "+f"(d[84]), "+f"(d[85]), "+f"(d[86]), "+f"(d[87]),
      "+f"(d[88]), "+f"(d[89]), "+f"(d[90]), "+f"(d[91]), "+f"(d[92]), "+f"(d[93]), "+f"(d[94]), "+f"(d[95]),
      "+f"(d[96]), "+f"(d[97]), "+f"(d[98]), "+f"(d[99]), "+f"(d[100]), "+f"(d[101]), "+f"(d[102]), "+f"(d[103]),
      "+f"(d[104]), "+f"(d[105]), "+f"(d[106]), "+f"(d[107]), "+f"(d[108]), "+f"(d[109]), "+f"(d[110]), "+f"(d[111])
    : "r"(a[0]), "r"(a[1]), "r"(a[2]), "r"(a[3]), "l"(db), "r"(sd));
}

__device__ __forceinline__ void wgmma_rs_n240(float* d, const uint32_t* a, uint64_t db, int sd) {
  asm volatile("{ .reg .pred p; setp.ne.b32 p, %125, 0;\n"
      "wgmma.mma_async.sync.aligned.m64n240k16.f32.bf16.bf16 {"
      "%0,%1,%2,%3,%4,%5,%6,%7,%8,%9,%10,%11,%12,%13,%14,%15,"
      "%16,%17,%18,%19,%20,%21,%22,%23,%24,%25,%26,%27,%28,%29,%30,%31,"
      "%32,%33,%34,%35,%36,%37,%38,%39,%40,%41,%42,%43,%44,%45,%46,%47,"
      "%48,%49,%50,%51,%52,%53,%54,%55,%56,%57,%58,%59,%60,%61,%62,%63,"
      "%64,%65,%66,%67,%68,%69,%70,%71,%72,%73,%74,%75,%76,%77,%78,%79,"
      "%80,%81,%82,%83,%84,%85,%86,%87,%88,%89,%90,%91,%92,%93,%94,%95,"
      "%96,%97,%98,%99,%100,%101,%102,%103,%104,%105,%106,%107,%108,%109,%110,%111,"
      "%112,%113,%114,%115,%116,%117,%118,%119"
      "}, {%120,%121,%122,%123}, %124, p, 1, 1, 0; }"
    : "+f"(d[0]), "+f"(d[1]), "+f"(d[2]), "+f"(d[3]), "+f"(d[4]), "+f"(d[5]), "+f"(d[6]), "+f"(d[7]),
      "+f"(d[8]), "+f"(d[9]), "+f"(d[10]), "+f"(d[11]), "+f"(d[12]), "+f"(d[13]), "+f"(d[14]), "+f"(d[15]),
      "+f"(d[16]), "+f"(d[17]), "+f"(d[18]), "+f"(d[19]), "+f"(d[20]), "+f"(d[21]), "+f"(d[22]), "+f"(d[23]),
      "+f"(d[24]), "+f"(d[25]), "+f"(d[26]), "+f"(d[27]), "+f"(d[28]), "+f"(d[29]), "+f"(d[30]), "+f"(d[31]),
      "+f"(d[32]), "+f"(d[33]), "+f"(d[34]), "+f"(d[35]), "+f"(d[36]), "+f"(d[37]), "+f"(d[38]), "+f"(d[39]),
      "+f"(d[40]), "+f"(d[41]), "+f"(d[42]), "+f"(d[43]), "+f"(d[44]), "+f"(d[45]), "+f"(d[46]), "+f"(d[47]),
      "+f"(d[48]), "+f"(d[49]), "+f"(d[50]), "+f"(d[51]), "+f"(d[52]), "+f"(d[53]), "+f"(d[54]), "+f"(d[55]),
      "+f"(d[56]), "+f"(d[57]), "+f"(d[58]), "+f"(d[59]), "+f"(d[60]), "+f"(d[61]), "+f"(d[62]), "+f"(d[63]),
      "+f"(d[64]), "+f"(d[65]), "+f"(d[66]), "+f"(d[67]), "+f"(d[68]), "+f"(d[69]), "+f"(d[70]), "+f"(d[71]),
      "+f"(d[72]), "+f"(d[73]), "+f"(d[74]), "+f"(d[75]), "+f"(d[76]), "+f"(d[77]), "+f"(d[78]), "+f"(d[79]),
      "+f"(d[80]), "+f"(d[81]), "+f"(d[82]), "+f"(d[83]), "+f"(d[84]), "+f"(d[85]), "+f"(d[86]), "+f"(d[87]),
      "+f"(d[88]), "+f"(d[89]), "+f"(d[90]), "+f"(d[91]), "+f"(d[92]), "+f"(d[93]), "+f"(d[94]), "+f"(d[95]),
      "+f"(d[96]), "+f"(d[97]), "+f"(d[98]), "+f"(d[99]), "+f"(d[100]), "+f"(d[101]), "+f"(d[102]), "+f"(d[103]),
      "+f"(d[104]), "+f"(d[105]), "+f"(d[106]), "+f"(d[107]), "+f"(d[108]), "+f"(d[109]), "+f"(d[110]), "+f"(d[111]),
      "+f"(d[112]), "+f"(d[113]), "+f"(d[114]), "+f"(d[115]), "+f"(d[116]), "+f"(d[117]), "+f"(d[118]), "+f"(d[119])
    : "r"(a[0]), "r"(a[1]), "r"(a[2]), "r"(a[3]), "l"(db), "r"(sd));
}

__device__ __forceinline__ void wgmma_rs_n256(float* d, const uint32_t* a, uint64_t db, int sd) {
  asm volatile("{ .reg .pred p; setp.ne.b32 p, %133, 0;\n"
      "wgmma.mma_async.sync.aligned.m64n256k16.f32.bf16.bf16 {"
      "%0,%1,%2,%3,%4,%5,%6,%7,%8,%9,%10,%11,%12,%13,%14,%15,"
      "%16,%17,%18,%19,%20,%21,%22,%23,%24,%25,%26,%27,%28,%29,%30,%31,"
      "%32,%33,%34,%35,%36,%37,%38,%39,%40,%41,%42,%43,%44,%45,%46,%47,"
      "%48,%49,%50,%51,%52,%53,%54,%55,%56,%57,%58,%59,%60,%61,%62,%63,"
      "%64,%65,%66,%67,%68,%69,%70,%71,%72,%73,%74,%75,%76,%77,%78,%79,"
      "%80,%81,%82,%83,%84,%85,%86,%87,%88,%89,%90,%91,%92,%93,%94,%95,"
      "%96,%97,%98,%99,%100,%101,%102,%103,%104,%105,%106,%107,%108,%109,%110,%111,"
      "%112,%113,%114,%115,%116,%117,%118,%119,%120,%121,%122,%123,%124,%125,%126,%127"
      "}, {%128,%129,%130,%131}, %132, p, 1, 1, 0; }"
    : "+f"(d[0]), "+f"(d[1]), "+f"(d[2]), "+f"(d[3]), "+f"(d[4]), "+f"(d[5]), "+f"(d[6]), "+f"(d[7]),
      "+f"(d[8]), "+f"(d[9]), "+f"(d[10]), "+f"(d[11]), "+f"(d[12]), "+f"(d[13]), "+f"(d[14]), "+f"(d[15]),
      "+f"(d[16]), "+f"(d[17]), "+f"(d[18]), "+f"(d[19]), "+f"(d[20]), "+f"(d[21]), "+f"(d[22]), "+f"(d[23]),
      "+f"(d[24]), "+f"(d[25]), "+f"(d[26]), "+f"(d[27]), "+f"(d[28]), "+f"(d[29]), "+f"(d[30]), "+f"(d[31]),
      "+f"(d[32]), "+f"(d[33]), "+f"(d[34]), "+f"(d[35]), "+f"(d[36]), "+f"(d[37]), "+f"(d[38]), "+f"(d[39]),
      "+f"(d[40]), "+f"(d[41]), "+f"(d[42]), "+f"(d[43]), "+f"(d[44]), "+f"(d[45]), "+f"(d[46]), "+f"(d[47]),
      "+f"(d[48]), "+f"(d[49]), "+f"(d[50]), "+f"(d[51]), "+f"(d[52]), "+f"(d[53]), "+f"(d[54]), "+f"(d[55]),
      "+f"(d[56]), "+f"(d[57]), "+f"(d[58]), "+f"(d[59]), "+f"(d[60]), "+f"(d[61]), "+f"(d[62]), "+f"(d[63]),
      "+f"(d[64]), "+f"(d[65]), "+f"(d[66]), "+f"(d[67]), "+f"(d[68]), "+f"(d[69]), "+f"(d[70]), "+f"(d[71]),
      "+f"(d[72]), "+f"(d[73]), "+f"(d[74]), "+f"(d[75]), "+f"(d[76]), "+f"(d[77]), "+f"(d[78]), "+f"(d[79]),
      "+f"(d[80]), "+f"(d[81]), "+f"(d[82]), "+f"(d[83]), "+f"(d[84]), "+f"(d[85]), "+f"(d[86]), "+f"(d[87]),
      "+f"(d[88]), "+f"(d[89]), "+f"(d[90]), "+f"(d[91]), "+f"(d[92]), "+f"(d[93]), "+f"(d[94]), "+f"(d[95]),
      "+f"(d[96]), "+f"(d[97]), "+f"(d[98]), "+f"(d[99]), "+f"(d[100]), "+f"(d[101]), "+f"(d[102]), "+f"(d[103]),
      "+f"(d[104]), "+f"(d[105]), "+f"(d[106]), "+f"(d[107]), "+f"(d[108]), "+f"(d[109]), "+f"(d[110]), "+f"(d[111]),
      "+f"(d[112]), "+f"(d[113]), "+f"(d[114]), "+f"(d[115]), "+f"(d[116]), "+f"(d[117]), "+f"(d[118]), "+f"(d[119]),
      "+f"(d[120]), "+f"(d[121]), "+f"(d[122]), "+f"(d[123]), "+f"(d[124]), "+f"(d[125]), "+f"(d[126]), "+f"(d[127])
    : "r"(a[0]), "r"(a[1]), "r"(a[2]), "r"(a[3]), "l"(db), "r"(sd));
}

__device__ __forceinline__ void ln_finish(float mean, float var, float& mb, float& rinv) {
  mb = round_bf16(mean);
  float sd;
  asm("sqrt.approx.ftz.f32 %0, %1;" : "=f"(sd) : "f"(round_bf16(round_bf16(var) + 1e-5f)));
  asm("rcp.approx.ftz.f32 %0, %1;" : "=f"(rinv) : "f"(round_bf16(sd)));
}
__device__ __forceinline__ uint32_t sum4(uint32_t a, uint32_t b, uint32_t c, uint32_t d) { return badd2(badd2(badd2(d, c), b), a); }
struct Ring {
  uint32_t s, ph;
  __device__ __forceinline__ void next() { if (++s == NSTAGE) { s = 0; ph ^= 1; } }
};

template <int J> __device__ __forceinline__ void conv_lda(uint32_t* a, uint32_t base, bool on) {
  asm volatile("{ .reg .pred p; setp.ne.u32 p, %3, 0;\n @p ld.shared.u32 %0, [%2 + %4];\n @p ld.shared.u32 %1, [%2 + %5]; }"
               : "+r"(a[2 * J]), "+r"(a[2 * J + 1]) : "r"(base), "r"((uint32_t)on), "n"((J >> 1) * 256 + (J & 1) * 16), "n"((J >> 1) * 256 + (J & 1) * 16 + 128) : "memory");
}
template <int J = 0> __device__ __forceinline__ void conv_lda_all(uint32_t* a, uint32_t base) {
  conv_lda<J>(a, base, true);
  if constexpr (J < 31) conv_lda_all<J + 1>(a, base);
}
__device__ __forceinline__ void conv_mma(float* acc, const uint32_t* a, uint64_t db) {
  wgmma_rs_n256(acc, a, db, 0);
  wgmma_rs_n240(acc, a + 4, db + 16, 1);
  wgmma_rs_n224(acc, a + 8, db + 32, 1);
  wgmma_rs_n208(acc, a + 12, db + 48, 1);
  wgmma_rs_n192(acc, a + 16, db + 64, 1);
  wgmma_rs_n176(acc, a + 20, db + 80, 1);
  wgmma_rs_n160(acc, a + 24, db + 96, 1);
  wgmma_rs_n144(acc, a + 28, db + 112, 1);
  wgmma_rs_n128(acc, a + 32, db + 128, 1);
  wgmma_rs_n112(acc, a + 36, db + 144, 1);
  wgmma_rs_n96(acc, a + 40, db + 160, 1);
  wgmma_rs_n80(acc, a + 44, db + 176, 1);
  wgmma_rs_n64(acc, a + 48, db + 192, 1);
  wgmma_rs_n48(acc, a + 52, db + 208, 1);
  wgmma_rs_n32(acc, a + 56, db + 224, 1);
  wgmma_rs_n16(acc, a + 60, db + 240, 1);
}
__device__ __forceinline__ uint32_t conv_part(const float* acc, int j) {
  const int q = 31 - j;
  return q == 31 ? pack_bf16(acc[124], acc[125]) : pack_bf16(acc[4 * q] + acc[(4 * q + 6) & 127], acc[4 * q + 1] + acc[(4 * q + 7) & 127]);
}
template <int J = 0> __device__ __forceinline__ void conv_drain(const float* acc, uint32_t wr, uint32_t* a, uint32_t ka, bool more) {
  conv_lda<J>(a, ka, more);
  sts32(wr + J * 128, conv_part(acc, J));
  if constexpr (J < 31) conv_drain<J + 1>(acc, wr, a, ka, more);
}
__device__ __forceinline__ uint4 conv_sum(const uint4* p) {
  return make_uint4(sum4(p[0].x, p[1].x, p[2].x, p[3].x), sum4(p[0].y, p[1].y, p[2].y, p[3].y), sum4(p[0].z, p[1].z, p[2].z, p[3].z),
                    sum4(p[0].w, p[1].w, p[2].w, p[3].w));
}
__device__ __forceinline__ int g2k(int rank, int kb) { return (rank * G2_KB + (kb < 6 ? 6 * kb : kb - 5 + (kb - 6) / 5)) * 64; }

template <int NV> __device__ __forceinline__ void gelu_stage(float* acc, const float* hb, uint32_t sa, int passes, uint32_t bar) {
#pragma unroll
  for (int i = 0; i < NV; i++) acc[i] = fmaf(acc[i], 0.5f, hb[(i >> 1) & 1]);
#pragma unroll 1
  for (; passes > 0; passes--, sa += NV * 256) {
#pragma unroll
    for (int i = 0; i < NV; i += 8)
      stsm4t(sa + i * 256, pack_bf16(gelu_half(acc[i]), gelu_half(acc[i + 1])), pack_bf16(gelu_half(acc[i + 2]), gelu_half(acc[i + 3])),
             pack_bf16(gelu_half(acc[i + 4]), gelu_half(acc[i + 5])), pack_bf16(gelu_half(acc[i + 6]), gelu_half(acc[i + 7])));
    __syncwarp();
    if (bar) mbar_arrive(bar);
    bar = 0;
    float half = 0.5f;
    asm volatile("" : "+f"(half));
#pragma unroll
    for (int i = 0; i < NV; i++) acc[i] = fmaf(acc[NV + i], half, hb[2 + ((i >> 1) & 1)]);
  }
}

__global__ void __cluster_dims__(2, 1, 1) __launch_bounds__(384, 1) fused_kernel(const __grid_constant__ Hot H, const __grid_constant__ Params P) {
  extern __shared__ __align__(1024) uint8_t smem_raw[];
  const uint32_t t0 = clk();
  const uint32_t sb = smem_u32(smem_raw);
  const int tid = threadIdx.x, lane = tid & 31;
  const int bid = blockIdx.x, rank = bid & 1;
  const Role& R = P.role[bid];
  Scratch* const S = H.S;
  uint32_t xr[18];
  const int row = bid * 16 + (tid >> 4);
  if (tid < 256 && bid < 128) {
    const char* src = reinterpret_cast<const char*>(H.x) + row * (D_ * 2) + (lane & 15) * 8;
#pragma unroll
    for (int j = 0; j < 9; j++) asm volatile("ld.global.nc.v2.u32 {%0,%1}, [%2];" : "=r"(xr[2 * j]), "=r"(xr[2 * j + 1]) : "l"(src + 128 * j));
  }
  const int warp = __shfl_sync(0xffffffffu, tid >> 5, 0);

  if (warp >= 8) {
    const bool one = elect_one();
    if (warp == 8 && one) {
#pragma unroll
      for (int b = B_FULL; b <= B_DONE; b += 8) mbar_init(sb + b, b < B_EMPTY ? 1 : b < B_SFREE ? 2 : b < B_CEMPTY ? 3 : b < B_G1DONE ? 4 : 8);
      asm volatile("fence.mbarrier_init.release.cluster;" ::: "memory");
    }
    __syncwarp();
    asm volatile("barrier.cluster.arrive.relaxed.aligned;" ::: "memory");
    asm volatile("setmaxnreg.dec.sync.aligned.u32 56;");
    asm volatile("barrier.cluster.wait.aligned;" ::: "memory");
    const bool left = R.at == 15;
    if (warp == 8) {
      const uint32_t ep = ldg32(S->cnt + C_EPOCH * 32);
      if (one) {
#pragma unroll 1
        for (int i = 0; i < 8; i++) asm volatile("prefetch.tensormap [%0];" :: "l"(&P.m_w1 + i) : "memory");
#pragma unroll 1
        for (int s = 0; s < NWE; s++) {
          mbar_expect_tx(sb + B_FULL + 8 * s, G1_BYTES);
          tma3d(sb + s * SLOT, &P.m_w1 + left, 0, s * 64, R.fg, sb + B_FULL + 8 * s);
        }
      }
      __syncwarp();
      if (bid < 128) bar_sync(2, 288);
      if (one) {
        TLREC(31);
        signal(S, C_H, EPOCH / 132);
        TLREC(1);
        const uint32_t boff = left ? 24576 : 16384;
        int kr = bid < 128 ? -2 : KV_ROUNDS + 1, ks = 0;
        auto kv_step = [&]() {
          if (ks == 0) {
            bulk_wait_all();
            if (kr < KV_ROUNDS - 2) {
              const int q = (kr + 2) % 3;
              const uint32_t in = sb + kv_buf(q), fb = sb + B_UFULL + 8 * q;
              mbar_expect_tx(fb, 3840 + 3264 + 768);
              tma2d(in, &P.m_k, (kr + 2) * 96, bid * 16 - 4, fb);
              tma2d(in + 3840, &P.m_v, (kr + 2) * 96, bid * 16 - 1, fb);
              bulk_load(in + 7168, H.shift_k + (kr + 2) * 384, 768, fb);
            }
            if (kr == KV_ROUNDS) { mbar_arrive(sb + B_KVDONE); kr++; }
          } else if (kr >= 0) {
            if (!mbar_test(sb + B_KFULL + 8 * (kr % 3), kr >= 3)) return;
            fence_async_smem();
            tma3d_store(&P.m_ub, sb + kv_buf(kr % 3) + (ks - 1) * 3072, 16 * (127 - bid), kr * 48, 2 * ks - 2);
            bulk_commit();
          }
          if (++ks == 3) { kr++; ks = kr == KV_ROUNDS - 2 || kr == KV_ROUNDS - 1; }
        };
        if (bid >= 128) mbar_arrive(sb + B_KVDONE);
        Ring r{0, 1};
#pragma unroll 1
        for (int kb = NWE - NW0; kb < G1_KB || kr <= KV_ROUNDS; kb++) {
          if (kb < G1_KB) {
          const int kw = kb < 0 ? kb + NW0 : kb, s = kb < 0 ? kw : r.s;
          const uint32_t fb = sb + B_FULL + 8 * s;
          if (kb < 0 || kb >= NW0) {
            mbar_wait(sb + B_EMPTY + 8 * s, r.ph);
            mbar_expect_tx(fb, G1_BYTES);
            tma3d(sb + s * SLOT, &P.m_w1 + left, 0, kw * 64, R.fg, fb);
            if (kb < 0) continue;
          }
          if (kb == 0) { await(S, C_H, ep); fence_async_global(); TLREC(2); }
          bulk_load(sb + s * SLOT + boff, S->h + (kb * 18 + R.at) * 2048, G1_BYTES - boff, fb);
          if (kb == 23) {
#pragma unroll 1
            for (int i = 0; i < 2; i++) {
              sts128(sb + cv_taps(i), 0, 0, 0, 0); sts128(sb + cv_taps(i) + 16, 0, 0, 0, 0);
              bulk_load(sb + cv_taps(i) + 32, H.ssm_k + (R.ch + i) * S_, 4096, sb + B_MISC);
            }
            mbar_expect_tx(sb + B_MISC, boff / 64 + 1152 + 8192);
            bulk_load(sb + SM_B1, H.b1 + R.fg * 64, boff / 64, sb + B_MISC);
            bulk_load(sb + SM_D, H.ssm_D, 1152, sb + B_MISC);
          }
          r.next();
          }
          if (kb >= KV0 && kr <= KV_ROUNDS) kv_step();
        }
        await(S, C_KV, ep);
        fence_async_global();
#pragma unroll 1
        for (int i = 0; i < R.ncv; i++) {
          if (i == 2) {
            if (R.sg >= 0) {
#pragma unroll 1
              for (int s = 2; s < NSTAGE; s++) {
                mbar_wait(sb + B_EMPTY + 8 * s, ((G1_KB / NSTAGE) - 1) & 1);
                mbar_expect_tx(sb + B_FULL + 8 * s, G2_BYTES);
                tma3d(sb + s * SLOT, &P.m_w2, 0, (rank * G2_KB + 6 * (s - 2)) * 64, R.sg, sb + B_FULL + 8 * s);
              }
            }
            mbar_wait(sb + B_G1DONE, 0);
          }
          const uint32_t kt = sb + cv_taps(i), b8 = sb + 8 * (i & 3);
          mbar_wait(b8 + B_CEMPTY, ((i >> 2) & 1) ^ 1);
          if (i < 2) mbar_arrive(b8 + B_KFULL);
          else {
            sts128(kt, 0, 0, 0, 0); sts128(kt + 16, 0, 0, 0, 0);
            mbar_expect_tx(b8 + B_KFULL, 4096);
            bulk_load(kt + 32, H.ssm_k + (R.ch + i) * S_, 4096, b8 + B_KFULL);
          }
          mbar_expect_tx(b8 + B_UFULL, 8192);
          bulk_load(sb + cv_in(i), S->ub + (R.ch + i) * 4096, 8192, b8 + B_UFULL);
        }
        if (R.sg >= 0) {
          mbar_expect_tx(sb + B_XY, 2 * 18432 + 2048 + 256);
#pragma unroll
          for (int i = 0; i < 4; i++) mbar_expect_tx(sb + B_XFULL + 8 * i, i & 1 ? 9216 - XP * 2048 : XP * 2048);
          TUNED(SYNCA, 0, 5); TUNED(SYNCKB, 1, 7);
#pragma unroll 1
          for (int kb = 0; kb < G2_KB; kb++, r.next()) {
            const int k0 = g2k(rank, kb);
            const uint32_t fb = sb + B_FULL + 8 * r.s, slot = sb + r.s * SLOT;
            if (!(kb & ~4)) { await(S, C_U + (kb >> 2), ep); fence_async_global(); if (!kb) TLREC(6); }
            if (kb >= NSTAGE - 2) {
              mbar_wait(sb + B_EMPTY + 8 * r.s, r.ph);
              if (kb == SYNCA) asm volatile("red.relaxed.gpu.global.add.u32 [%0], %1;" :: "l"(S->cnt + C_SYNC * 32), "r"(EPOCH / 128) : "memory");
              if (kb == SYNCKB) await(S, C_SYNC, ep);
              mbar_expect_tx(fb, G2_BYTES);
              tma3d(slot, &P.m_w2, 0, k0, R.sg, fb);
            }
            bulk_load(slot + 16384, S->u + k0 * D_ + R.ds * 512, 9216, fb);
            bulk_load(slot + 16384 + 9216, S->u + k0 * D_ + R.dk * 512, 9216, fb);
            const uint32_t nx = kb - 8;
            if (nx == 0) { mbar_wait(sb + B_KVDONE, 1); fence_async_smem(); }
            if (nx < 8) tma2d(sb + SM_CV + nx * 2304, &P.m_x, R.dk * 8, R.sg * 64 + nx * 16, sb + B_XY);
          }
          bulk_load(sb + SM_ST, S->stats + R.sg * 64, 2048, sb + B_XY);
          bulk_load(sb + SM_B2, P.b2 + R.sg * 64, 256, sb + B_XY);
          await(S, C_Y, ep);
          fence_async_global();
          TLREC(19);
          tma3d(sb + SM_DED, &P.m_y, 0, R.dk * 8, R.sg, sb + B_XY);
          if (bid == 0) asm volatile("red.relaxed.gpu.global.add.u32 [%0], %1;" :: "l"(S->cnt + C_EPOCH * 32), "r"(EPOCH) : "memory");
        }
      }
    } else {
      if (bid < 128) {
        const int ht = tid - 288, hf = ht >= 48, pr = ht - 48 * hf;
        const uint32_t st = (1 - hf) * 1536 + pr * 32, sw = (pr & 4) * 4;
#pragma unroll 1
        for (int r = 0; r < KV_ROUNDS; r++) {
          const int q = r % 3;
          const uint32_t in = sb + kv_buf(q);
          {
            mbar_wait_guarded(sb + B_UFULL + 8 * q, t0, r >= 3);
            uint32_t kk[12], vv[9];
#pragma unroll
            for (int j = 0; j < 12; j++) kk[j] = lds32(in + hf * 1536 + pr * 4 + j * 192);
#pragma unroll
            for (int j = 0; j < 9; j++) vv[j] = lds32(in + 3840 + hf * 1536 + pr * 4 + j * 192);
            const uint4 w = lds128(in + 7168 + pr * 16);
            const uint32_t w0 = __byte_perm(w.x, w.z, 0x5410), w1 = __byte_perm(w.x, w.z, 0x7632);
            const uint32_t w2 = __byte_perm(w.y, w.w, 0x5410), w3 = __byte_perm(w.y, w.w, 0x7632);
#pragma unroll
            for (int j = 0; j < 9; j++)
              vv[j] = bmul2(badd2(badd2(badd2(bmul2(kk[j], w3), bmul2(kk[j + 1], w2)), bmul2(kk[j + 2], w1)), bmul2(kk[j + 3], w0)), vv[j]);
            bar_sync(1, 96);
#pragma unroll
            for (int c = 0; c < 2; c++)
#pragma unroll
              for (int pi = 0; pi < 2; pi++) {
                const uint32_t sel = c ? 0x7632 : 0x5410;
                sts128(in + st + c * 3072 + (pi * 16 ^ sw), __byte_perm(vv[7 + pi], vv[6 + pi], sel), __byte_perm(vv[5 + pi], vv[4 + pi], sel),
                       __byte_perm(vv[3 + pi], vv[2 + pi], sel), __byte_perm(vv[1 + pi], vv[pi], sel));
              }
            bar_sync(1, 96);
            if (ht == 0) mbar_arrive(sb + B_KFULL + 8 * q);
          }
          __syncwarp();
        }
      }
      if (one) {
        if (warp < 11) {
          const int wg = warp - 9;
          const uint32_t bytes = left ? 12288 : 10240;
#pragma unroll 1
          for (int j = 0; j < 2; j++) {
            mbar_wait_guarded(sb + B_STG + 8 * wg + (j ? 0 : 16), t0);
            fence_async_smem();
            TLREC(13 + wg);
            if (!j || wg || !left)
              bulk_store(S->u + (R.fg + wg) * (64 * D_) + R.at * 2048 + j * (left ? 64 * D_ : 5120), sb + (wg ? SM_ST1 : SM_DED) + j * bytes, bytes);
          }
          bulk_commit();
          bulk_wait_all();
          mbar_arrive(sb + B_STORED + 8 * wg);
          if (wg) mbar_arrive(sb + B_EMPTY);
          asm volatile("mbarrier.arrive.shared::cta.b64 _, [%0], 3;" :: "r"(sb + B_SFREE + 8 * wg) : "memory");
          signal(S, C_U + wg, EPOCH / 132);
          TLREC(15 + wg);
        } else {
          mbar_wait_guarded(sb + B_KVDONE, t0);
          signal(S, C_KV, EPOCH / 132);
          TLREC(27);
        }
      }
      __syncwarp();
#pragma unroll 1
      for (int i = 0; i < R.ncv; i++) {
        const uint32_t red = sb + cv_red(i, R.ncv) + (tid - 288) * 16;
        uint4* yo = reinterpret_cast<uint4*>(S->y + (R.ch + i) * S_) + (tid - 288);
        mbar_wait_guarded(sb + B_STORED + 8 * (i & 1), t0);
        mbar_wait_guarded(sb + B_STG + 8 * (i & 1) + (i + 2 < R.ncv ? 0 : 16), t0, i + 2 >= R.ncv || !(i & 2));
        uint4 p[2][4];
#pragma unroll
        for (int x = 0; x < 8; x++) p[x >> 2][x & 3] = lds128(red + (x & 3) * CV_REDW + (x >> 2) * 1536);
        yo[0] = conv_sum(p[0]);
        if (warp < 11) {
#pragma unroll
          for (int x = 0; x < 4; x++) p[0][x] = lds128(red + x * CV_REDW + 3072);
          yo[192] = conv_sum(p[0]);
        }
        yo[96] = conv_sum(p[1]);
        __syncwarp();
        if (one) mbar_arrive(sb + (i + 4 == R.ncv ? B_PDONE : B_SFREE + 8 * (i & 1)));
        if (i + 3 == R.ncv) {
          bar_sync(1, 96);
          if (warp == 11 && one) { fence_async_smem(); mbar_arrive(sb + B_EMPTY + 8); }
          __syncwarp();
        }
      }
      bar_sync(1, 96);
      if (warp == 11 && one) {
        TLREC(7);
        mbar_arrive(sb + B_KVDONE);
        signal(S, C_Y, EPOCH / 132);
        if (R.sg >= 0) mbar_wait_guarded(sb + B_DONE, t0);
      }
    }
    TLEND();
  } else {
    asm volatile("barrier.cluster.arrive.relaxed.aligned;" ::: "memory");
    if (bid < 128) {
      float c[36], s[4];
#pragma unroll
      for (int i = 0; i < 18; i++) { c[2 * i] = bf_lo(xr[i]); c[2 * i + 1] = bf_hi(xr[i]); }
#pragma unroll
      for (int i = 0; i < 36; i++) s[i & 3] = i < 4 ? c[i] : s[i & 3] + c[i];
      const float ml = ((s[0] + s[1]) + (s[2] + s[3])) * (1.0f / 36.0f);
#pragma unroll
      for (int i = 0; i < 36; i++) { c[i] -= ml; s[i & 3] = i < 4 ? c[i] * c[i] : fmaf(c[i], c[i], s[i & 3]); }
      float m = ml, q = (s[0] + s[1]) + (s[2] + s[3]), n2 = 18.f;
#pragma unroll
      for (int o = 1; o < 16; o <<= 1) {
        const float mo = __shfl_xor_sync(0xffffffffu, m, o), qo = __shfl_xor_sync(0xffffffffu, q, o);
        const float dl = m - mo;
        q = fmaf(dl * dl, n2, q + qo);
        m = fmaf(dl, -0.5f, m);
        n2 *= 2.f;
      }
      const float var = q * (1.0f / 576.0f);
      float mb, rinv, mb2, rinv2;
      ln_finish(m, var, mb, rinv);
      ln_finish((m - mb) * rinv, var * rinv * rinv, mb2, rinv2);
      const float ca = rinv * rinv2, cb = fmaf(ml - mb, rinv, -mb2) * rinv2;
      uint2* dst = reinterpret_cast<uint2*>(S->h) + ((row >> 6) * 18 + ((lane >> 3) & 1)) * 512 + (row & 63) * 8 + ((lane & 7) ^ (row & 6));
#pragma unroll
      for (int j = 0; j < 9; j++)
        dst[1024 * j] = make_uint2(pack_bf16(fmaf(c[4 * j], ca, cb), fmaf(c[4 * j + 1], ca, cb)), pack_bf16(fmaf(c[4 * j + 2], ca, cb), fmaf(c[4 * j + 3], ca, cb)));
      const uint32_t rh = pack_bf16(rinv, rinv);
      if (!(lane & 15)) S->stats[row] = make_uint4(pack_bf16(mb, mb), rh, pack_bf16(rinv - bf_lo(rh), rinv - bf_lo(rh)), 0);
      __syncwarp();
      bar_arrive(2, 288);
    }
    asm volatile("setmaxnreg.inc.sync.aligned.u32 224;");
    asm volatile("barrier.cluster.wait.aligned;" ::: "memory");
    const int wg = warp >> 2, w = warp & 3, g = lane >> 2, t = lane & 3, wtid = tid & 127;
    const bool elect = wtid == 0;
    const uint64_t da0 = make_desc(sb + wg * 8192, 8192, 1024, 1);
    const uint32_t swz = ((lane >> 4) * 8 + (lane & 7)) * 128 + (((2 * w + ((lane >> 3) & 1)) ^ (lane & 7)) << 4);
    const uint32_t stg = sb + (wg ? SM_ST1 : SM_DED), ka0 = (8 * w + g + t + 1) * 4;
    uint32_t a[64];
    {
      auto mainloop = [&](auto&& mma) {
        Ring r{0, 0};
        uint32_t rel = 0;
#pragma unroll 1
        for (int kb = 0; kb < G1_KB; kb++, r.next()) {
          if (kb == G1_KB - G1_TAIL && wg) {
            wg_wait<0>();
            if (elect) mbar_arrive(rel);
            rel = 0;
            {
              mbar_wait(sb + B_MISC, 0);
              conv_lda_all(a, sb + SM_CV + 16384 + CV_K + ka0);
            }
            bar_sync(5, 256);
          }
          mbar_wait(sb + B_FULL + 8 * r.s, r.ph);
          if (kb == 0 && warp == 0) TLREC(3);
          wg_fence();
          mma(r.s * (SLOT >> 4), kb, 0);
          wg_commit();
          if (ER1 == 4 && kb == G1_KB - 1) break;
          wg_wait<1>();
          if (elect && rel && kb != G1_KB - 1) mbar_arrive(rel);
          if (ER1 < 4) { wg_fence(); mma(r.s * (SLOT >> 4), kb, 1); wg_commit(); }
          rel = sb + B_EMPTY + 8 * r.s;
        }
        bar_arrive(5, 256);
        wg_wait<0>();
      };
      float hb[4];
      auto staged = [&](int second) {
        if (!w) TLREC(4 + wg);
        if (lane == 0) mbar_arrive(sb + B_G1DONE);
        mbar_wait(sb + B_MISC, 0);
#pragma unroll
        for (int i = 0; i < 4; i++) hb[i] = 0.5f * bf_lo(lds16(sb + SM_B1 + (warp * 16 + g + (i & 1) * 8 + (i >> 1) * second) * 2));
        mbar_wait(sb + B_KVDONE, 0);
        if (wg) mbar_wait(sb + B_G1DONE, 0);
      };
      if (R.at != 15) {
        const uint64_t db0 = make_desc(sb + 16384, 4096, 512, 2);
        float acc[80];
        mainloop([&](uint32_t o, int kb, int part) {
#pragma unroll
          for (int k = part ? ER1 : 0; k < (part ? 4 : ER1); k++) wgmma_ss_n160_t11(acc, da0 + o + k * 128, db0 + o + k * 64, k ? 1 : kb);
        });
        pin_regs<80>(acc);
        staged(0);
        gelu_stage<40>(acc, hb, stg + swz, 2, lane ? 0 : sb + B_STG + 8 * wg + 16);
      } else {
        const uint64_t db0 = make_desc(sb + 24576, 4096, 512, 2);
        float acc[96];
        auto block = [&](float* d, uint64_t da, uint64_t db, int kb, int part) {
#pragma unroll
          for (int k = part ? ER1 : 0; k < (part ? 4 : ER1); k++) wgmma_ss_n96_t11(d, da + k * 128, db + k * 64, k ? 1 : kb);
        };
        if (wg) mainloop([&](uint32_t o, int kb, int part) { block(acc, da0 + o, db0 + o, kb, part); block(acc + 48, da0 + o + 512, db0 + o, kb, part); });
        else mainloop([&](uint32_t o, int kb, int part) { block(acc, da0 + o, db0 + o, kb, part); });
        pin_regs<96>(acc);
        staged(64);
        gelu_stage<48>(acc, hb, stg + swz, 1 + wg, lane ? 0 : sb + B_STG + 8 * wg + 16);
      }
      __syncwarp();
      if (lane == 0) mbar_arrive(sb + B_STG + 8 * wg);
    }
    {
      if (!wg) conv_lda_all(a, sb + SM_CV + 16384 + wg * CV_K + ka0);
#pragma unroll 1
      for (int i = wg; i < R.ncv; i += 2) {
        const bool more = i + 2 < R.ncv;
        const uint32_t dd = lds16(sb + SM_D + (R.ch + i) * 2);
        a[0] = badd2(a[0], ka0 == 32 ? dd : 0); a[2] = badd2(a[2], ka0 == 16 ? dd : 0);
        float acc[128];
        mbar_wait(sb + B_UFULL + 8 * (i & 3), (i >> 2) & 1);
        bar_sync(5 + wg, 256);
        const bool last = i + 1 == R.ncv;
        if (last && elect) mbar_arrive(sb + B_EMPTY);
        if (!w && i < 4) TLREC(22 + i);
        wg_fence();
        conv_mma(acc, a, make_desc(sb + cv_in(i), 4096, 128, 0));
        wg_commit();
        if (!last) bar_arrive(5 + (wg ^ 1), 256);
        if (more) {
          mbar_wait(sb + B_SFREE + 8 * wg, (i >> 1) & 1);
          mbar_wait(sb + B_KFULL + 8 * ((i + 2) & 3), ((i + 2) >> 2) & 1);
        } else if (last) mbar_wait(sb + B_PDONE, 0);
        wg_wait<0>();
        pin_regs<128>(acc);
        if (lane == 0) mbar_arrive(sb + B_CEMPTY + 8 * (i & 3));
        if (last && elect) mbar_arrive(sb + B_EMPTY + 8);
        const uint32_t red = sb + cv_red(i, R.ncv), ka = sb + cv_taps(i + 2) + ka0;
        if (lane < 8 * w) sts32(red + w * CV_REDW + lane * 4, 0);
        const uint32_t wr = red + w * CV_REDW + (8 * (3 - t + w) + g) * 4;
        conv_drain(acc, wr, a, ka, more);
        __syncwarp();
        if (lane == 0) mbar_arrive(sb + B_STG + 8 * wg + (more ? 0 : 16));
      }
      if (!w) TLREC(20 + wg);
    }
    if (R.sg >= 0) {
      const int srow = R.sg * 64 + warp * 16;
      const uint64_t db0 = make_desc(sb + 16384, 16, 1024, 1);
      const uint32_t xo = sb + SM_CV + warp * 2304, xa = xo + (lane & 15) * 144;
      float acc[72];
      Ring r{G1_KB % NSTAGE, (G1_KB / NSTAGE) & 1};
      uint32_t rel = 0;
#pragma unroll 1
      for (int kb = 0; kb < G2_KB; kb++, r.next()) {
        if (kb == G2_KB - G2_TAIL && wg) {
          wg_wait<0>();
          if (elect) mbar_arrive_remote(rel);
          rel = 0;
          bar_sync(7, 256);
        }
        mbar_wait(sb + B_FULL + 8 * r.s, r.ph);
        if (kb == 0 && !w) TLREC(17 + wg);
        if (kb == 8 && warp == 0) TLREC(26);
        if (kb == 20 && warp == 0) TLREC(8);
        if (kb == 27 && warp == 0) TLREC(30);
        const uint64_t da = da0 + r.s * (SLOT >> 4), db = db0 + r.s * (SLOT >> 4);
        wg_fence();
        wgmma_ss_n144_t10(acc, da, db, kb);
#pragma unroll
        for (int k = 1; k < ER2; k++) wgmma_ss_n144_t10(acc, da + k * 128, db + k * 2, 1);
        wg_commit();
        if (ER2 == 4 && kb == G2_KB - 1) break;
        wg_wait<1>();
        if (elect && rel) mbar_arrive_remote(rel);
        if (ER2 < 4) {
          wg_fence();
#pragma unroll
          for (int k = ER2; k < 4; k++) wgmma_ss_n144_t10(acc, da + k * 128, db + k * 2, 1);
          wg_commit();
        }
        rel = kb == G2_KB - NSTAGE ? mapa(sb + B_XRDY, rank ^ 1) : sb + B_EMPTY + 8 * r.s;
      }
      if (!wg) bar_arrive(7, 256);
      const uint32_t xz = sb + XSLOT * SLOT + wg * 10240 + wtid * 16;
      const uint32_t rz = mapa(xz, rank ^ 1), rb = mapa(sb + B_XFULL + 16 * wg, rank ^ 1);
      mbar_wait(sb + B_XRDY, 0);
      wg_wait<0>();
      pin_regs<72>(acc);
      if (!w) TLREC(28 + wg);
#pragma unroll
      for (int i = 0; i < 32; i += 8)
        asm volatile("st.async.weak.shared::cluster.mbarrier::complete_tx::bytes.v4.b32 [%0], {%1,%2,%3,%4}, [%5];"
                     :: "r"(rz + i * 256), "r"(pack_bf16(acc[i], acc[i + 1])), "r"(pack_bf16(acc[i + 2], acc[i + 3])),
                        "r"(pack_bf16(acc[i + 4], acc[i + 5])), "r"(pack_bf16(acc[i + 6], acc[i + 7])), "r"(rb + (i < 8 * XP ? 0 : 8)) : "memory");
      asm volatile("st.async.weak.shared::cluster.mbarrier::complete_tx::bytes.v2.b32 [%0], {%1,%2}, [%3];"
                   :: "r"(rz + 8192), "r"(pack_bf16(acc[32], acc[33])), "r"(pack_bf16(acc[34], acc[35])), "r"(rb + 8) : "memory");
      uint32_t xx[18], ss[18];
      mbar_wait(sb + B_XY, 0);
      {
        const uint32_t ya = sb + SM_DED + wg * 9216 + swz;
        const uint4 st0 = lds128(sb + SM_ST + (warp * 16 + g) * 16), st1 = lds128(sb + SM_ST + (warp * 16 + g + 8) * 16);
        const float hb0 = 0.5f * bf_lo(lds16(sb + SM_B2 + (warp * 16 + g) * 2)), hb1 = 0.5f * bf_lo(lds16(sb + SM_B2 + (warp * 16 + g + 8) * 2));
#pragma unroll
        for (int q = 0; q < 8; q += 2) { ldsm4(xx + 2 * q, xa + (lane >> 4) * 16 + q * 16); ldsm4t(ss + 2 * q, ya + q * 1024); }
        ldsm2(xx + 16, xa + 128);
        ldsm2t(ss + 16, ya + 8 * 1024);
#pragma unroll
        for (int i = 0; i < 18; i++) {
          const uint4& st = (i & 1) ? st1 : st0;
          const uint32_t c = bsub2(xx[i], st.x);
          ss[i] = bmul2(bfma2(c, st.y, bmul2(c, st.z)), ss[i]);
        }
#pragma unroll
        for (int i = 36; i < 72; i++) acc[i] = fmaf(acc[i], 0.5f, (i & 2) ? hb1 : hb0);
      }
      char* const op = reinterpret_cast<char*>(P.out) + srow * (D_ * 2) + R.dk * 16 + lane * 16;
      uint32_t oo[5];
#pragma unroll
      for (int j = 0; j < 5; j++) oo[j] = ((lane + 32 * j) * 57 >> 9) * (D_ * 2 - 144) + j * 512;
#pragma unroll
      for (int q = 0; q < 5; q++) {
        if (q == 0 || q == XP) mbar_wait_cluster(sb + B_XFULL + 16 * wg + (q ? 8 : 0), 0);
        if (!w && !q) TLREC(9 + wg);
        const uint4 v = lds128(xz + q * 2048);
        const uint32_t pv[4] = {v.x, v.y, v.z, v.w};
#pragma unroll
        for (int i = 4 * q; i < 4 * q + 4 && i < 18; i++)
          xx[i] = bfma2(ss[i], pack_bf16(silu_half(fmaf(bf_lo(pv[i & 3]), 0.5f, acc[36 + 2 * i])), silu_half(fmaf(bf_hi(pv[i & 3]), 0.5f, acc[37 + 2 * i]))), xx[i]);
        if (q < 4) stsm4(xa + (lane >> 4) * 16 + q * 32, xx[4 * q], xx[4 * q + 1], xx[4 * q + 2], xx[4 * q + 3]);
        else stsm2(xa + 128, xx[16], xx[17]);
      }
      __syncwarp();
      if (lane == 0) mbar_arrive(sb + B_DONE);
#pragma unroll
      for (int j = 0; j < 5; j++)
        if (j < 4 || lane < 16) *reinterpret_cast<uint4*>(op + oo[j]) = lds128(xo + (lane + 32 * j) * 16);
      if (!w) TLREC(11 + wg);
    }
    TLEND();
  }
}

typedef CUresult (*EncodeFn)(CUtensorMap*, CUtensorMapDataType, cuuint32_t, void*, const cuuint64_t*, const cuuint64_t*, const cuuint32_t*,
                             const cuuint32_t*, CUtensorMapInterleave, CUtensorMapSwizzle, CUtensorMapL2promotion, CUtensorMapFloatOOBfill);

void make_map(EncodeFn fn, CUtensorMap* m, const void* ptr, int rank, const cuuint64_t* dims, const cuuint64_t* strides, const cuuint32_t* box,
              CUtensorMapSwizzle sw) {
  const cuuint32_t es[3] = {1, 1, 1};
  fn(m, CU_TENSOR_MAP_DATA_TYPE_BFLOAT16, rank, const_cast<void*>(ptr), dims, strides, box, es, CU_TENSOR_MAP_INTERLEAVE_NONE, sw,
     CU_TENSOR_MAP_L2_PROMOTION_L2_256B, CU_TENSOR_MAP_FLOAT_OOB_FILL_NONE);
}

void make_roles(Role* R) {
  int nl = 0, ch = 0;
  for (int gi = 0; gi < 8; gi++)
    for (int b = 0; b < 132; b++) {
      const int c = b >> 1, rank = b & 1;
      int g, idx;
      if (c < 4) { g = 0; idx = 4 + c; }
      else if (c < 36) { g = (c - 4) & 7; idx = (c - 4) >> 3; }
      else if (c < 64) { g = 1 + (c - 36) % 7; idx = 4 + (c - 36) / 7; }
      else { g = c - 58; idx = 8; }
      if (g != gi) continue;
      Role& r = R[b];
      r.sg = (int8_t)(idx < 8 ? 2 * (2 * g + (idx >> 2)) : -1);
      r.dk = (int8_t)((idx & 3) * 18 + rank * 9);
      r.ds = (int8_t)((idx & 3) * 18 + (rank ^ 1) * 9);
      if (idx < (g < 2 ? 6 : 7)) {
        const int c1 = (g < 2 ? 6 * g : 7 * g - 2) + idx;
        r.fg = (int8_t)((2 * (c1 / 3) + rank) * 2); r.at = (int8_t)(c1 % 3 * 5); r.ncv = NCV_REG;
      } else {
        r.fg = (int8_t)(3 * nl++); r.at = 15; r.ncv = idx < 8 ? NCV_LEFT : NCV_LONG;
      }
      r.ch = (int16_t)ch;
      ch += r.ncv;
    }
}

}

extern "C" void kernel_launch(void* const* d_in, const int* in_sizes, int n_in, void* d_out, int out_size) {
  static Params P;
  static Hot H;
  static const void* cached[5] = {nullptr, nullptr, nullptr, nullptr, nullptr};
  const void* now[5] = {d_in[0], d_in[1], d_in[2], d_in[7], d_in[9]};
  bool same = true;
  for (int i = 0; i < 5; i++) { same = same && cached[i] == now[i]; cached[i] = now[i]; }
  if (!same) {
    void* fp = nullptr;
    cudaDriverEntryPointQueryResult qr;
    cudaGetDriverEntryPoint("cuTensorMapEncodeTiled", &fp, cudaEnableDefault, &qr);
    EncodeFn fn = (EncodeFn)fp;
    void* ps;
    cudaGetSymbolAddress(&ps, g_scratch);
    H.S = (Scratch*)ps;
    const void *py = (char*)ps + offsetof(Scratch, y), *pb = (char*)ps + offsetof(Scratch, ub);
    { cuuint64_t d[3] = {64, S_, F_ / 64}, s[2] = {F_ * 2, 128}; cuuint32_t b[3] = {64, 64, 2}; make_map(fn, &P.m_w1, d_in[7], 3, d, s, b, CU_TENSOR_MAP_SWIZZLE_128B);
      b[2] = 3; make_map(fn, &P.m_w1l, d_in[7], 3, d, s, b, CU_TENSOR_MAP_SWIZZLE_128B); }
    { cuuint64_t d[3] = {64, F_, S_ / 64}, s[2] = {S_ * 2, 128}; cuuint32_t b[3] = {64, 64, 2}; make_map(fn, &P.m_w2, d_in[9], 3, d, s, b, CU_TENSOR_MAP_SWIZZLE_128B); }
    { cuuint64_t d[2] = {D_, S_}, s[1] = {D_ * 2}; cuuint32_t b[2] = {72, 16}; make_map(fn, &P.m_x, d_in[0], 2, d, s, b, CU_TENSOR_MAP_SWIZZLE_NONE);
      b[0] = 96; b[1] = 20; make_map(fn, &P.m_k, d_in[1], 2, d, s, b, CU_TENSOR_MAP_SWIZZLE_NONE);
      b[1] = 17; make_map(fn, &P.m_v, d_in[2], 2, d, s, b, CU_TENSOR_MAP_SWIZZLE_NONE); }
    { cuuint64_t d[3] = {64, D_, S_ / 64}, s[2] = {S_ * 2, 128}; cuuint32_t b[3] = {64, 72, 2}; make_map(fn, &P.m_y, py, 3, d, s, b, CU_TENSOR_MAP_SWIZZLE_128B); }
    { cuuint64_t d[3] = {2048, D_ / 2, 4}, s[2] = {16384, 4096}; cuuint32_t b[3] = {16, 48, 2}; make_map(fn, &P.m_ub, pb, 3, d, s, b, CU_TENSOR_MAP_SWIZZLE_32B); }
    make_roles(P.role);
    cudaFuncSetAttribute(fused_kernel, cudaFuncAttributeMaxDynamicSharedMemorySize, SM_TOTAL);
  }
  H.x = (const __nv_bfloat16*)d_in[0];
  H.shift_k = (const __nv_bfloat16*)d_in[3]; H.ssm_k = (const __nv_bfloat16*)d_in[4]; H.ssm_D = (const __nv_bfloat16*)d_in[5];
  H.b1 = (const __nv_bfloat16*)d_in[8]; P.b2 = (const __nv_bfloat16*)d_in[10]; P.out = (__nv_bfloat16*)d_out;
  fused_kernel<<<132, 384, SM_TOTAL>>>(H, P);
}
```

```cpp
#include <cuda_runtime.h>
#include <cuda.h>
#include <cuda_bf16.h>
#include <stddef.h>
#include <stdint.h>

namespace {

constexpr int S_ = 2048, D_ = 576, F_ = 4608;
constexpr int NSTAGE = 5, SLOT = 36864;
constexpr int G1_KB = 32, G2_KB = 36;
constexpr int G1_BYTES = 36864, G2_BYTES = 16384 + 18432;
#define NCV_LEFT 4
constexpr int NCV_REG = 4, NCV_LONG = (D_ - 108 * NCV_REG - 20 * NCV_LEFT) / 4;
static_assert(108 * NCV_REG + 20 * NCV_LEFT + 4 * NCV_LONG == D_, "conv split");
constexpr int KV_ROUNDS = 6;
#define XP 2
#define TUNED(name, idx, val) constexpr int name = val
constexpr int G1_TAIL = 4, G2_TAIL = 3;
constexpr int KV0 = 5;

constexpr int CV_K = 4224, CV_REDW = 2112 * 2;
constexpr int SM_DED = NSTAGE * SLOT;
constexpr int SM_CV = SM_DED + 20480;
constexpr int SM_ST1 = 0;
constexpr int SM_ST = SM_CV + 18432, SM_B2 = SM_ST + 2048;
constexpr int SM_B1 = SM_CV + 2 * (8192 + CV_K), SM_D = SM_B1 + 384;
constexpr int SM_BAR = SM_D + 1152;
constexpr int SM_TOTAL = SM_BAR + 768;
static_assert(G1_KB % NSTAGE == 2, "slots 0 and 1 hold the last GEMM1 k-blocks and the last two of the first GEMM2 stages");
static_assert(NCV_REG == 4 && NCV_LEFT == 4 && NCV_LONG % 4 == 0, "the last two channels use buffers 2 and 3");
constexpr int XSLOT = (G1_KB + G2_KB) % NSTAGE;
__device__ __forceinline__ uint32_t kv_buf(int q) { return q == 2 ? SM_DED : SM_CV + q * 8192; }
__device__ __forceinline__ uint32_t cv_red(int i, int n) { return i + 2 == n ? SM_CV : (i & 1) && i + 1 < n ? SLOT + 16384 : SM_DED; }
__device__ __forceinline__ uint32_t cv_in(int i) { return (i & 2 ? SLOT : SM_CV) + (i & 1) * 8192; }
__device__ __forceinline__ uint32_t cv_taps(int i) { return (i & 2 ? SM_ST1 + 24576 : SM_CV + 16384) + (i & 1) * CV_K; }
constexpr int bar_at(int i) { return SM_BAR + 8 * i; }
constexpr int B_FULL = bar_at(0)  , B_KFULL = bar_at(5)  , B_UFULL = bar_at(9)  , B_KVDONE = bar_at(13), B_STORED = bar_at(14)  ,
              B_XFULL = bar_at(16)  , B_XY = bar_at(20), B_MISC = bar_at(21),
              B_EMPTY = bar_at(22)  , B_XRDY = bar_at(27),
              B_SFREE = bar_at(28)  , B_PDONE = bar_at(30),
              B_CEMPTY = bar_at(31)  , B_STG = bar_at(35)  ,
              B_G1DONE = bar_at(39), B_DONE = bar_at(40);
constexpr int C_H = 0, C_KV = 1, C_U = 2  , C_Y = 4, C_SYNC = 5, C_EPOCH = 6, C_COUNT = 7;
constexpr uint32_t EPOCH = 128 * 33;

struct Scratch {
  uint32_t cnt[C_COUNT * 32];
  alignas(1024) uint4 stats[S_];
  alignas(1024) __nv_bfloat16 h[S_ * D_];
  alignas(1024) __nv_bfloat16 ub[D_ * 4096];
  alignas(1024) __nv_bfloat16 y[D_ * S_];
  alignas(1024) __nv_bfloat16 u[D_ * F_];
};
__device__ Scratch g_scratch;

struct Hot {
  const __nv_bfloat16 *x, *shift_k, *ssm_k, *ssm_D, *b1;
  Scratch* S;
};
struct Role {
  int8_t fg;
  int8_t at;
  int8_t sg;
  int8_t dk, ds;
  int8_t ncv;
  int16_t ch;
};
struct Params {
  const __nv_bfloat16* b2;
  __nv_bfloat16* out;
  Role role[132];
  CUtensorMap m_w1, m_w1l, m_w2, m_x, m_y, m_k, m_v, m_ub;
};

#define TLREC(i) do { } while (0)
#define TLEND() do { } while (0)

__device__ __forceinline__ uint32_t smem_u32(const void* p) { return (uint32_t)__cvta_generic_to_shared(p); }
__device__ __forceinline__ void mbar_init(uint32_t bar, uint32_t cnt) { asm volatile("mbarrier.init.shared::cta.b64 [%0], %1;" :: "r"(bar), "r"(cnt) : "memory"); }
__device__ __forceinline__ void mbar_expect_tx(uint32_t bar, uint32_t bytes) { asm volatile("mbarrier.arrive.expect_tx.shared::cta.b64 _, [%0], %1;" :: "r"(bar), "r"(bytes) : "memory"); }
__device__ __forceinline__ void mbar_arrive(uint32_t bar) { asm volatile("mbarrier.arrive.shared::cta.b64 _, [%0];" :: "r"(bar) : "memory"); }
__device__ __forceinline__ uint32_t mapa(uint32_t addr, uint32_t cta) { uint32_t r; asm volatile("mapa.shared::cluster.u32 %0, %1, %2;" : "=r"(r) : "r"(addr), "r"(cta)); return r; }
__device__ __forceinline__ void mbar_arrive_remote(uint32_t rbar) { asm volatile("mbarrier.arrive.shared::cluster.b64 _, [%0];" :: "r"(rbar) : "memory"); }
__device__ __forceinline__ uint32_t clk() { uint32_t c; asm volatile("mov.u32 %0, %%clock;" : "=r"(c)); return c; }
__device__ __forceinline__ bool elect_one() {
  uint32_t p; asm volatile("{ .reg .pred p; elect.sync _|p, 0xffffffff; selp.u32 %0, 1, 0, p; }" : "=r"(p)); return p;
}
__device__ __forceinline__ void guard(uint32_t t0) { if ((int32_t)(clk() - t0) < 0) __trap(); }
__device__ __forceinline__ void mbar_wait(uint32_t bar, uint32_t parity) {
  asm volatile("{\n .reg .pred p;\n W_%=:\n mbarrier.try_wait.parity.shared::cta.b64 p, [%0], %1;\n @!p bra W_%=;\n }" :: "r"(bar), "r"(parity) : "memory");
}
__device__ __forceinline__ void mbar_wait_cluster(uint32_t bar, uint32_t parity) {
  asm volatile("{\n .reg .pred p;\n W_%=:\n mbarrier.try_wait.parity.acquire.cluster.shared::cta.b64 p, [%0], %1;\n @!p bra W_%=;\n }" :: "r"(bar), "r"(parity) : "memory");
}
__device__ __forceinline__ bool mbar_try(uint32_t bar, uint32_t parity) {
  uint32_t ok;
  asm volatile("{ .reg .pred p; mbarrier.try_wait.parity.shared::cta.b64 p, [%1], %2, 100000; selp.u32 %0, 1, 0, p; }" : "=r"(ok) : "r"(bar), "r"(parity) : "memory");
  return ok;
}
__device__ __forceinline__ bool mbar_test(uint32_t bar, uint32_t parity) {
  uint32_t ok;
  asm volatile("{ .reg .pred p; mbarrier.test_wait.parity.shared::cta.b64 p, [%1], %2; selp.u32 %0, 1, 0, p; }" : "=r"(ok) : "r"(bar), "r"(parity) : "memory");
  return ok;
}
__device__ __forceinline__ void mbar_wait_guarded(uint32_t bar, uint32_t t0, uint32_t parity = 0) { while (!mbar_try(bar, parity)) guard(t0); }
__device__ __forceinline__ void tma2d(uint32_t dst, const CUtensorMap* m, int c0, int c1, uint32_t bar) {
  asm volatile("cp.async.bulk.tensor.2d.shared::cluster.global.mbarrier::complete_tx::bytes [%0], [%1, {%3, %4}], [%2];"
               :: "r"(dst), "l"(m), "r"(bar), "r"(c0), "r"(c1) : "memory");
}
__device__ __forceinline__ void tma3d(uint32_t dst, const CUtensorMap* m, int c0, int c1, int c2, uint32_t bar) {
  asm volatile("cp.async.bulk.tensor.3d.shared::cluster.global.mbarrier::complete_tx::bytes [%0], [%1, {%3, %4, %5}], [%2];"
               :: "r"(dst), "l"(m), "r"(bar), "r"(c0), "r"(c1), "r"(c2) : "memory");
}
__device__ __forceinline__ void bulk_store(void* dst, uint32_t src, uint32_t bytes) {
  asm volatile("cp.async.bulk.global.shared::cta.bulk_group [%0], [%1], %2;" :: "l"(dst), "r"(src), "r"(bytes) : "memory");
}
__device__ __forceinline__ void bulk_load(uint32_t dst, const void* src, uint32_t bytes, uint32_t bar) {
  asm volatile("cp.async.bulk.shared::cluster.global.mbarrier::complete_tx::bytes [%0], [%1], %2, [%3];" :: "r"(dst), "l"(src), "r"(bytes), "r"(bar) : "memory");
}
__device__ __forceinline__ void tma3d_store(const CUtensorMap* m, uint32_t src, int c0, int c1, int c2) {
  asm volatile("cp.async.bulk.tensor.3d.global.shared::cta.bulk_group [%0, {%2, %3, %4}], [%1];" :: "l"(m), "r"(src), "r"(c0), "r"(c1), "r"(c2) : "memory");
}
__device__ __forceinline__ void bulk_commit() { asm volatile("cp.async.bulk.commit_group;" ::: "memory"); }
__device__ __forceinline__ void bulk_wait_all() { asm volatile("cp.async.bulk.wait_group 0;" ::: "memory"); }
__device__ __forceinline__ void fence_async_smem() { asm volatile("fence.proxy.async.shared::cta;" ::: "memory"); }
__device__ __forceinline__ void fence_async_global() { asm volatile("fence.proxy.async.global;" ::: "memory"); }
__device__ __forceinline__ uint32_t ld_cnt(Scratch* S, int c) { uint32_t v; asm volatile("ld.relaxed.gpu.global.u32 %0, [%1];" : "=r"(v) : "l"(S->cnt + c * 32) : "memory"); return v; }
__device__ __forceinline__ void signal(Scratch* S, int c, uint32_t inc) { asm volatile("red.release.gpu.global.add.u32 [%0], %1;" :: "l"(S->cnt + c * 32), "r"(inc) : "memory"); }
__device__ __forceinline__ bool reached(Scratch* S, int c, uint32_t ep) { return ld_cnt(S, c) - ep >= EPOCH; }
__device__ __forceinline__ void await(Scratch* S, int c, uint32_t ep) { while (!reached(S, c, ep)) { } }
__device__ __forceinline__ void bar_sync(int id, int n) { asm volatile("bar.sync %0, %1;" :: "r"(id), "r"(n) : "memory"); }
__device__ __forceinline__ void bar_arrive(int id, int n) { asm volatile("bar.arrive %0, %1;" :: "r"(id), "r"(n) : "memory"); }
__device__ __forceinline__ void wg_fence() { asm volatile("wgmma.fence.sync.aligned;" ::: "memory"); }
__device__ __forceinline__ void wg_commit() { asm volatile("wgmma.commit_group.sync.aligned;" ::: "memory"); }
template <int N> __device__ __forceinline__ void wg_wait() { asm volatile("wgmma.wait_group.sync.aligned %0;" :: "n"(N) : "memory"); }
template <int N> __device__ __forceinline__ void pin_regs(float* a) {
#pragma unroll
  for (int i = 0; i < N; i++) asm volatile("" : "+f"(a[i]) :: "memory");
}
__device__ __forceinline__ uint64_t make_desc(uint32_t addr, uint32_t lbo, uint32_t sbo, uint32_t swz) {
  return (uint64_t)((addr & 0x3FFFF) >> 4) | ((uint64_t)(lbo >> 4) << 16) | ((uint64_t)(sbo >> 4) << 32) | ((uint64_t)swz << 62);
}
__device__ __forceinline__ uint32_t pack_bf16(float lo, float hi) { uint32_t r; asm("cvt.rn.bf16x2.f32 %0, %1, %2;" : "=r"(r) : "f"(hi), "f"(lo)); return r; }
__device__ __forceinline__ float bf_lo(uint32_t p) { return __uint_as_float(p << 16); }
__device__ __forceinline__ float bf_hi(uint32_t p) { return __uint_as_float(p & 0xffff0000u); }
__device__ __forceinline__ float round_bf16(float v) { return bf_lo(pack_bf16(v, 0.f)); }
__device__ __forceinline__ uint32_t bmul2(uint32_t a, uint32_t b) { uint32_t r; asm("mul.rn.bf16x2 %0, %1, %2;" : "=r"(r) : "r"(a), "r"(b)); return r; }
__device__ __forceinline__ uint32_t badd2(uint32_t a, uint32_t b) { uint32_t r; asm("add.rn.bf16x2 %0, %1, %2;" : "=r"(r) : "r"(a), "r"(b)); return r; }
__device__ __forceinline__ uint32_t bfma2(uint32_t a, uint32_t b, uint32_t c) { uint32_t r; asm("fma.rn.bf16x2 %0, %1, %2, %3;" : "=r"(r) : "r"(a), "r"(b), "r"(c)); return r; }
__device__ __forceinline__ uint32_t bsub2(uint32_t a, uint32_t b) { uint32_t r; asm("sub.rn.bf16x2 %0, %1, %2;" : "=r"(r) : "r"(a), "r"(b)); return r; }
__device__ __forceinline__ float tanh_fast(float v) { float r; asm("tanh.approx.f32 %0, %1;" : "=f"(r) : "f"(v)); return r; }
__device__ __forceinline__ float gelu_half(float h) {
  return fmaf(h, tanh_fast(h * fmaf(h * h, 8.0f * 0.7978845608028654f * 0.044715f, 2.0f * 0.7978845608028654f)), h);
}
__device__ __forceinline__ float silu_half(float h) { return fmaf(h, tanh_fast(h), h); }
__device__ __forceinline__ uint32_t ldg32(const void* p) { uint32_t v; asm volatile("ld.global.u32 %0, [%1];" : "=r"(v) : "l"(p) : "memory"); return v; }
__device__ __forceinline__ uint32_t lds32(uint32_t a) { uint32_t v; asm volatile("ld.shared.u32 %0, [%1];" : "=r"(v) : "r"(a) : "memory"); return v; }
__device__ __forceinline__ uint32_t lds16(uint32_t a) { uint32_t v; asm volatile("ld.shared.u16 %0, [%1];" : "=r"(v) : "r"(a) : "memory"); return v; }
__device__ __forceinline__ uint4 lds128(uint32_t a) { uint4 v; asm volatile("ld.shared.v4.u32 {%0,%1,%2,%3}, [%4];" : "=r"(v.x), "=r"(v.y), "=r"(v.z), "=r"(v.w) : "r"(a) : "memory"); return v; }
__device__ __forceinline__ void sts128(uint32_t a, uint32_t x, uint32_t y, uint32_t z, uint32_t w) {
  asm volatile("st.shared.v4.u32 [%0], {%1,%2,%3,%4};" :: "r"(a), "r"(x), "r"(y), "r"(z), "r"(w) : "memory");
}
__device__ __forceinline__ void sts32(uint32_t a, uint32_t v) { asm volatile("st.shared.u32 [%0], %1;" :: "r"(a), "r"(v) : "memory"); }
__device__ __forceinline__ void ldsm4(uint32_t* r, uint32_t a) {
  asm volatile("ldmatrix.sync.aligned.m8n8.x4.shared.b16 {%0,%1,%2,%3}, [%4];" : "=r"(r[0]), "=r"(r[1]), "=r"(r[2]), "=r"(r[3]) : "r"(a) : "memory");
}
__device__ __forceinline__ void ldsm2(uint32_t* r, uint32_t a) {
  asm volatile("ldmatrix.sync.aligned.m8n8.x2.shared.b16 {%0,%1}, [%2];" : "=r"(r[0]), "=r"(r[1]) : "r"(a) : "memory");
}
__device__ __forceinline__ void ldsm4t(uint32_t* r, uint32_t a) {
  asm volatile("ldmatrix.sync.aligned.m8n8.x4.trans.shared.b16 {%0,%1,%2,%3}, [%4];" : "=r"(r[0]), "=r"(r[1]), "=r"(r[2]), "=r"(r[3]) : "r"(a) : "memory");
}
__device__ __forceinline__ void ldsm2t(uint32_t* r, uint32_t a) {
  asm volatile("ldmatrix.sync.aligned.m8n8.x2.trans.shared.b16 {%0,%1}, [%2];" : "=r"(r[0]), "=r"(r[1]) : "r"(a) : "memory");
}
__device__ __forceinline__ void stsm4(uint32_t a, uint32_t r0, uint32_t r1, uint32_t r2, uint32_t r3) {
  asm volatile("stmatrix.sync.aligned.m8n8.x4.shared.b16 [%0], {%1,%2,%3,%4};" :: "r"(a), "r"(r0), "r"(r1), "r"(r2), "r"(r3) : "memory");
}
__device__ __forceinline__ void stsm2(uint32_t a, uint32_t r0, uint32_t r1) {
  asm volatile("stmatrix.sync.aligned.m8n8.x2.shared.b16 [%0], {%1,%2};" :: "r"(a), "r"(r0), "r"(r1) : "memory");
}
__device__ __forceinline__ void stsm4t(uint32_t a, uint32_t r0, uint32_t r1, uint32_t r2, uint32_t r3) {
  asm volatile("stmatrix.sync.aligned.m8n8.x4.trans.shared.b16 [%0], {%1,%2,%3,%4};" :: "r"(a), "r"(r0), "r"(r1), "r"(r2), "r"(r3) : "memory");
}

__device__ __forceinline__ void wgmma_ss_n144_t10(float* d, uint64_t da, uint64_t db, int sd) {
  asm volatile("{ .reg .pred p; setp.ne.b32 p, %74, 0;\n"
      "wgmma.mma_async.sync.aligned.m64n144k16.f32.bf16.bf16 {"
      "%0,%1,%2,%3,%4,%5,%6,%7,%8,%9,%10,%11,%12,%13,%14,%15,"
      "%16,%17,%18,%19,%20,%21,%22,%23,%24,%25,%26,%27,%28,%29,%30,%31,"
      "%32,%33,%34,%35,%36,%37,%38,%39,%40,%41,%42,%43,%44,%45,%46,%47,"
      "%48,%49,%50,%51,%52,%53,%54,%55,%56,%57,%58,%59,%60,%61,%62,%63,"
      "%64,%65,%66,%67,%68,%69,%70,%71"
      "}, %72, %73, p, 1, 1, 1, 0; }"
    : "+f"(d[0]), "+f"(d[1]), "+f"(d[2]), "+f"(d[3]), "+f"(d[4]), "+f"(d[5]), "+f"(d[6]), "+f"(d[7]),
      "+f"(d[8]), "+f"(d[9]), "+f"(d[10]), "+f"(d[11]), "+f"(d[12]), "+f"(d[13]), "+f"(d[14]), "+f"(d[15]),
      "+f"(d[16]), "+f"(d[17]), "+f"(d[18]), "+f"(d[19]), "+f"(d[20]), "+f"(d[21]), "+f"(d[22]), "+f"(d[23]),
      "+f"(d[24]), "+f"(d[25]), "+f"(d[26]), "+f"(d[27]), "+f"(d[28]), "+f"(d[29]), "+f"(d[30]), "+f"(d[31]),
      "+f"(d[32]), "+f"(d[33]), "+f"(d[34]), "+f"(d[35]), "+f"(d[36]), "+f"(d[37]), "+f"(d[38]), "+f"(d[39]),
      "+f"(d[40]), "+f"(d[41]), "+f"(d[42]), "+f"(d[43]), "+f"(d[44]), "+f"(d[45]), "+f"(d[46]), "+f"(d[47]),
      "+f"(d[48]), "+f"(d[49]), "+f"(d[50]), "+f"(d[51]), "+f"(d[52]), "+f"(d[53]), "+f"(d[54]), "+f"(d[55]),
      "+f"(d[56]), "+f"(d[57]), "+f"(d[58]), "+f"(d[59]), "+f"(d[60]), "+f"(d[61]), "+f"(d[62]), "+f"(d[63]),
      "+f"(d[64]), "+f"(d[65]), "+f"(d[66]), "+f"(d[67]), "+f"(d[68]), "+f"(d[69]), "+f"(d[70]), "+f"(d[71])
    : "l"(da), "l"(db), "r"(sd));
}

__device__ __forceinline__ void wgmma_ss_n160_t11(float* d, uint64_t da, uint64_t db, int sd) {
  asm volatile("{ .reg .pred p; setp.ne.b32 p, %82, 0;\n"
      "wgmma.mma_async.sync.aligned.m64n160k16.f32.bf16.bf16 {"
      "%0,%1,%2,%3,%4,%5,%6,%7,%8,%9,%10,%11,%12,%13,%14,%15,"
      "%16,%17,%18,%19,%20,%21,%22,%23,%24,%25,%26,%27,%28,%29,%30,%31,"
      "%32,%33,%34,%35,%36,%37,%38,%39,%40,%41,%42,%43,%44,%45,%46,%47,"
      "%48,%49,%50,%51,%52,%53,%54,%55,%56,%57,%58,%59,%60,%61,%62,%63,"
      "%64,%65,%66,%67,%68,%69,%70,%71,%72,%73,%74,%75,%76,%77,%78,%79"
      "}, %80, %81, p, 1, 1, 1, 1; }"
    : "+f"(d[0]), "+f"(d[1]), "+f"(d[2]), "+f"(d[3]), "+f"(d[4]), "+f"(d[5]), "+f"(d[6]), "+f"(d[7]),
      "+f"(d[8]), "+f"(d[9]), "+f"(d[10]), "+f"(d[11]), "+f"(d[12]), "+f"(d[13]), "+f"(d[14]), "+f"(d[15]),
      "+f"(d[16]), "+f"(d[17]), "+f"(d[18]), "+f"(d[19]), "+f"(d[20]), "+f"(d[21]), "+f"(d[22]), "+f"(d[23]),
      "+f"(d[24]), "+f"(d[25]), "+f"(d[26]), "+f"(d[27]), "+f"(d[28]), "+f"(d[29]), "+f"(d[30]), "+f"(d[31]),
      "+f"(d[32]), "+f"(d[33]), "+f"(d[34]), "+f"(d[35]), "+f"(d[36]), "+f"(d[37]), "+f"(d[38]), "+f"(d[39]),
      "+f"(d[40]), "+f"(d[41]), "+f"(d[42]), "+f"(d[43]), "+f"(d[44]), "+f"(d[45]), "+f"(d[46]), "+f"(d[47]),
      "+f"(d[48]), "+f"(d[49]), "+f"(d[50]), "+f"(d[51]), "+f"(d[52]), "+f"(d[53]), "+f"(d[54]), "+f"(d[55]),
      "+f"(d[56]), "+f"(d[57]), "+f"(d[58]), "+f"(d[59]), "+f"(d[60]), "+f"(d[61]), "+f"(d[62]), "+f"(d[63]),
      "+f"(d[64]), "+f"(d[65]), "+f"(d[66]), "+f"(d[67]), "+f"(d[68]), "+f"(d[69]), "+f"(d[70]), "+f"(d[71]),
      "+f"(d[72]), "+f"(d[73]), "+f"(d[74]), "+f"(d[75]), "+f"(d[76]), "+f"(d[77]), "+f"(d[78]), "+f"(d[79])
    : "l"(da), "l"(db), "r"(sd));
}

__device__ __forceinline__ void wgmma_ss_n96_t11(float* d, uint64_t da, uint64_t db, int sd) {
  asm volatile("{ .reg .pred p; setp.ne.b32 p, %50, 0;\n"
      "wgmma.mma_async.sync.aligned.m64n96k16.f32.bf16.bf16 {"
      "%0,%1,%2,%3,%4,%5,%6,%7,%8,%9,%10,%11,%12,%13,%14,%15,"
      "%16,%17,%18,%19,%20,%21,%22,%23,%24,%25,%26,%27,%28,%29,%30,%31,"
      "%32,%33,%34,%35,%36,%37,%38,%39,%40,%41,%42,%43,%44,%45,%46,%47"
      "}, %48, %49, p, 1, 1, 1, 1; }"
    : "+f"(d[0]), "+f"(d[1]), "+f"(d[2]), "+f"(d[3]), "+f"(d[4]), "+f"(d[5]), "+f"(d[6]), "+f"(d[7]),
      "+f"(d[8]), "+f"(d[9]), "+f"(d[10]), "+f"(d[11]), "+f"(d[12]), "+f"(d[13]), "+f"(d[14]), "+f"(d[15]),
      "+f"(d[16]), "+f"(d[17]), "+f"(d[18]), "+f"(d[19]), "+f"(d[20]), "+f"(d[21]), "+f"(d[22]), "+f"(d[23]),
      "+f"(d[24]), "+f"(d[25]), "+f"(d[26]), "+f"(d[27]), "+f"(d[28]), "+f"(d[29]), "+f"(d[30]), "+f"(d[31]),
      "+f"(d[32]), "+f"(d[33]), "+f"(d[34]), "+f"(d[35]), "+f"(d[36]), "+f"(d[37]), "+f"(d[38]), "+f"(d[39]),
      "+f"(d[40]), "+f"(d[41]), "+f"(d[42]), "+f"(d[43]), "+f"(d[44]), "+f"(d[45]), "+f"(d[46]), "+f"(d[47])
    : "l"(da), "l"(db), "r"(sd));
}

__device__ __forceinline__ void wgmma_rs_n16(float* d, const uint32_t* a, uint64_t db, int sd) {
  asm volatile("{ .reg .pred p; setp.ne.b32 p, %13, 0;\n"
      "wgmma.mma_async.sync.aligned.m64n16k16.f32.bf16.bf16 {"
      "%0,%1,%2,%3,%4,%5,%6,%7"
      "}, {%8,%9,%10,%11}, %12, p, 1, 1, 0; }"
    : "+f"(d[0]), "+f"(d[1]), "+f"(d[2]), "+f"(d[3]), "+f"(d[4]), "+f"(d[5]), "+f"(d[6]), "+f"(d[7])
    : "r"(a[0]), "r"(a[1]), "r"(a[2]), "r"(a[3]), "l"(db), "r"(sd));
}

__device__ __forceinline__ void wgmma_rs_n32(float* d, const uint32_t* a, uint64_t db, int sd) {
  asm volatile("{ .reg .pred p; setp.ne.b32 p, %21, 0;\n"
      "wgmma.mma_async.sync.aligned.m64n32k16.f32.bf16.bf16 {"
      "%0,%1,%2,%3,%4,%5,%6,%7,%8,%9,%10,%11,%12,%13,%14,%15"
      "}, {%16,%17,%18,%19}, %20, p, 1, 1, 0; }"
    : "+f"(d[0]), "+f"(d[1]), "+f"(d[2]), "+f"(d[3]), "+f"(d[4]), "+f"(d[5]), "+f"(d[6]), "+f"(d[7]),
      "+f"(d[8]), "+f"(d[9]), "+f"(d[10]), "+f"(d[11]), "+f"(d[12]), "+f"(d[13]), "+f"(d[14]), "+f"(d[15])
    : "r"(a[0]), "r"(a[1]), "r"(a[2]), "r"(a[3]), "l"(db), "r"(sd));
}

__device__ __forceinline__ void wgmma_rs_n48(float* d, const uint32_t* a, uint64_t db, int sd) {
  asm volatile("{ .reg .pred p; setp.ne.b32 p, %29, 0;\n"
      "wgmma.mma_async.sync.aligned.m64n48k16.f32.bf16.bf16 {"
      "%0,%1,%2,%3,%4,%5,%6,%7,%8,%9,%10,%11,%12,%13,%14,%15,"
      "%16,%17,%18,%19,%20,%21,%22,%23"
      "}, {%24,%25,%26,%27}, %28, p, 1, 1, 0; }"
    : "+f"(d[0]), "+f"(d[1]), "+f"(d[2]), "+f"(d[3]), "+f"(d[4]), "+f"(d[5]), "+f"(d[6]), "+f"(d[7]),
      "+f"(d[8]), "+f"(d[9]), "+f"(d[10]), "+f"(d[11]), "+f"(d[12]), "+f"(d[13]), "+f"(d[14]), "+f"(d[15]),
      "+f"(d[16]), "+f"(d[17]), "+f"(d[18]), "+f"(d[19]), "+f"(d[20]), "+f"(d[21]), "+f"(d[22]), "+f"(d[23])
    : "r"(a[0]), "r"(a[1]), "r"(a[2]), "r"(a[3]), "l"(db), "r"(sd));
}

__device__ __forceinline__ void wgmma_rs_n64(float* d, const uint32_t* a, uint64_t db, int sd) {
  asm volatile("{ .reg .pred p; setp.ne.b32 p, %37, 0;\n"
      "wgmma.mma_async.sync.aligned.m64n64k16.f32.bf16.bf16 {"
      "%0,%1,%2,%3,%4,%5,%6,%7,%8,%9,%10,%11,%12,%13,%14,%15,"
      "%16,%17,%18,%19,%20,%21,%22,%23,%24,%25,%26,%27,%28,%29,%30,%31"
      "}, {%32,%33,%34,%35}, %36, p, 1, 1, 0; }"
    : "+f"(d[0]), "+f"(d[1]), "+f"(d[2]), "+f"(d[3]), "+f"(d[4]), "+f"(d[5]), "+f"(d[6]), "+f"(d[7]),
      "+f"(d[8]), "+f"(d[9]), "+f"(d[10]), "+f"(d[11]), "+f"(d[12]), "+f"(d[13]), "+f"(d[14]), "+f"(d[15]),
      "+f"(d[16]), "+f"(d[17]), "+f"(d[18]), "+f"(d[19]), "+f"(d[20]), "+f"(d[21]), "+f"(d[22]), "+f"(d[23]),
      "+f"(d[24]), "+f"(d[25]), "+f"(d[26]), "+f"(d[27]), "+f"(d[28]), "+f"(d[29]), "+f"(d[30]), "+f"(d[31])
    : "r"(a[0]), "r"(a[1]), "r"(a[2]), "r"(a[3]), "l"(db), "r"(sd));
}

__device__ __forceinline__ void wgmma_rs_n80(float* d, const uint32_t* a, uint64_t db, int sd) {
  asm volatile("{ .reg .pred p; setp.ne.b32 p, %45, 0;\n"
      "wgmma.mma_async.sync.aligned.m64n80k16.f32.bf16.bf16 {"
      "%0,%1,%2,%3,%4,%5,%6,%7,%8,%9,%10,%11,%12,%13,%14,%15,"
      "%16,%17,%18,%19,%20,%21,%22,%23,%24,%25,%26,%27,%28,%29,%30,%31,"
      "%32,%33,%34,%35,%36,%37,%38,%39"
      "}, {%40,%41,%42,%43}, %44, p, 1, 1, 0; }"
    : "+f"(d[0]), "+f"(d[1]), "+f"(d[2]), "+f"(d[3]), "+f"(d[4]), "+f"(d[5]), "+f"(d[6]), "+f"(d[7]),
      "+f"(d[8]), "+f"(d[9]), "+f"(d[10]), "+f"(d[11]), "+f"(d[12]), "+f"(d[13]), "+f"(d[14]), "+f"(d[15]),
      "+f"(d[16]), "+f"(d[17]), "+f"(d[18]), "+f"(d[19]), "+f"(d[20]), "+f"(d[21]), "+f"(d[22]), "+f"(d[23]),
      "+f"(d[24]), "+f"(d[25]), "+f"(d[26]), "+f"(d[27]), "+f"(d[28]), "+f"(d[29]), "+f"(d[30]), "+f"(d[31]),
      "+f"(d[32]), "+f"(d[33]), "+f"(d[34]), "+f"(d[35]), "+f"(d[36]), "+f"(d[37]), "+f"(d[38]), "+f"(d[39])
    : "r"(a[0]), "r"(a[1]), "r"(a[2]), "r"(a[3]), "l"(db), "r"(sd));
}

__device__ __forceinline__ void wgmma_rs_n96(float* d, const uint32_t* a, uint64_t db, int sd) {
  asm volatile("{ .reg .pred p; setp.ne.b32 p, %53, 0;\n"
      "wgmma.mma_async.sync.aligned.m64n96k16.f32.bf16.bf16 {"
      "%0,%1,%2,%3,%4,%5,%6,%7,%8,%9,%10,%11,%12,%13,%14,%15,"
      "%16,%17,%18,%19,%20,%21,%22,%23,%24,%25,%26,%27,%28,%29,%30,%31,"
      "%32,%33,%34,%35,%36,%37,%38,%39,%40,%41,%42,%43,%44,%45,%46,%47"
      "}, {%48,%49,%50,%51}, %52, p, 1, 1, 0; }"
    : "+f"(d[0]), "+f"(d[1]), "+f"(d[2]), "+f"(d[3]), "+f"(d[4]), "+f"(d[5]), "+f"(d[6]), "+f"(d[7]),
      "+f"(d[8]), "+f"(d[9]), "+f"(d[10]), "+f"(d[11]), "+f"(d[12]), "+f"(d[13]), "+f"(d[14]), "+f"(d[15]),
      "+f"(d[16]), "+f"(d[17]), "+f"(d[18]), "+f"(d[19]), "+f"(d[20]), "+f"(d[21]), "+f"(d[22]), "+f"(d[23]),
      "+f"(d[24]), "+f"(d[25]), "+f"(d[26]), "+f"(d[27]), "+f"(d[28]), "+f"(d[29]), "+f"(d[30]), "+f"(d[31]),
      "+f"(d[32]), "+f"(d[33]), "+f"(d[34]), "+f"(d[35]), "+f"(d[36]), "+f"(d[37]), "+f"(d[38]), "+f"(d[39]),
      "+f"(d[40]), "+f"(d[41]), "+f"(d[42]), "+f"(d[43]), "+f"(d[44]), "+f"(d[45]), "+f"(d[46]), "+f"(d[47])
    : "r"(a[0]), "r"(a[1]), "r"(a[2]), "r"(a[3]), "l"(db), "r"(sd));
}

__device__ __forceinline__ void wgmma_rs_n112(float* d, const uint32_t* a, uint64_t db, int sd) {
  asm volatile("{ .reg .pred p; setp.ne.b32 p, %61, 0;\n"
      "wgmma.mma_async.sync.aligned.m64n112k16.f32.bf16.bf16 {"
      "%0,%1,%2,%3,%4,%5,%6,%7,%8,%9,%10,%11,%12,%13,%14,%15,"
      "%16,%17,%18,%19,%20,%21,%22,%23,%24,%25,%26,%27,%28,%29,%30,%31,"
      "%32,%33,%34,%35,%36,%37,%38,%39,%40,%41,%42,%43,%44,%45,%46,%47,"
      "%48,%49,%50,%51,%52,%53,%54,%55"
      "}, {%56,%57,%58,%59}, %60, p, 1, 1, 0; }"
    : "+f"(d[0]), "+f"(d[1]), "+f"(d[2]), "+f"(d[3]), "+f"(d[4]), "+f"(d[5]), "+f"(d[6]), "+f"(d[7]),
      "+f"(d[8]), "+f"(d[9]), "+f"(d[10]), "+f"(d[11]), "+f"(d[12]), "+f"(d[13]), "+f"(d[14]), "+f"(d[15]),
      "+f"(d[16]), "+f"(d[17]), "+f"(d[18]), "+f"(d[19]), "+f"(d[20]), "+f"(d[21]), "+f"(d[22]), "+f"(d[23]),
      "+f"(d[24]), "+f"(d[25]), "+f"(d[26]), "+f"(d[27]), "+f"(d[28]), "+f"(d[29]), "+f"(d[30]), "+f"(d[31]),
      "+f"(d[32]), "+f"(d[33]), "+f"(d[34]), "+f"(d[35]), "+f"(d[36]), "+f"(d[37]), "+f"(d[38]), "+f"(d[39]),
      "+f"(d[40]), "+f"(d[41]), "+f"(d[42]), "+f"(d[43]), "+f"(d[44]), "+f"(d[45]), "+f"(d[46]), "+f"(d[47]),
      "+f"(d[48]), "+f"(d[49]), "+f"(d[50]), "+f"(d[51]), "+f"(d[52]), "+f"(d[53]), "+f"(d[54]), "+f"(d[55])
    : "r"(a[0]), "r"(a[1]), "r"(a[2]), "r"(a[3]), "l"(db), "r"(sd));
}

__device__ __forceinline__ void wgmma_rs_n128(float* d, const uint32_t* a, uint64_t db, int sd) {
  asm volatile("{ .reg .pred p; setp.ne.b32 p, %69, 0;\n"
      "wgmma.mma_async.sync.aligned.m64n128k16.f32.bf16.bf16 {"
      "%0,%1,%2,%3,%4,%5,%6,%7,%8,%9,%10,%11,%12,%13,%14,%15,"
      "%16,%17,%18,%19,%20,%21,%22,%23,%24,%25,%26,%27,%28,%29,%30,%31,"
      "%32,%33,%34,%35,%36,%37,%38,%39,%40,%41,%42,%43,%44,%45,%46,%47,"
      "%48,%49,%50,%51,%52,%53,%54,%55,%56,%57,%58,%59,%60,%61,%62,%63"
      "}, {%64,%65,%66,%67}, %68, p, 1, 1, 0; }"
    : "+f"(d[0]), "+f"(d[1]), "+f"(d[2]), "+f"(d[3]), "+f"(d[4]), "+f"(d[5]), "+f"(d[6]), "+f"(d[7]),
      "+f"(d[8]), "+f"(d[9]), "+f"(d[10]), "+f"(d[11]), "+f"(d[12]), "+f"(d[13]), "+f"(d[14]), "+f"(d[15]),
      "+f"(d[16]), "+f"(d[17]), "+f"(d[18]), "+f"(d[19]), "+f"(d[20]), "+f"(d[21]), "+f"(d[22]), "+f"(d[23]),
      "+f"(d[24]), "+f"(d[25]), "+f"(d[26]), "+f"(d[27]), "+f"(d[28]), "+f"(d[29]), "+f"(d[30]), "+f"(d[31]),
      "+f"(d[32]), "+f"(d[33]), "+f"(d[34]), "+f"(d[35]), "+f"(d[36]), "+f"(d[37]), "+f"(d[38]), "+f"(d[39]),
      "+f"(d[40]), "+f"(d[41]), "+f"(d[42]), "+f"(d[43]), "+f"(d[44]), "+f"(d[45]), "+f"(d[46]), "+f"(d[47]),
      "+f"(d[48]), "+f"(d[49]), "+f"(d[50]), "+f"(d[51]), "+f"(d[52]), "+f"(d[53]), "+f"(d[54]), "+f"(d[55]),
      "+f"(d[56]), "+f"(d[57]), "+f"(d[58]), "+f"(d[59]), "+f"(d[60]), "+f"(d[61]), "+f"(d[62]), "+f"(d[63])
    : "r"(a[0]), "r"(a[1]), "r"(a[2]), "r"(a[3]), "l"(db), "r"(sd));
}

__device__ __forceinline__ void wgmma_rs_n144(float* d, const uint32_t* a, uint64_t db, int sd) {
  asm volatile("{ .reg .pred p; setp.ne.b32 p, %77, 0;\n"
      "wgmma.mma_async.sync.aligned.m64n144k16.f32.bf16.bf16 {"
      "%0,%1,%2,%3,%4,%5,%6,%7,%8,%9,%10,%11,%12,%13,%14,%15,"
      "%16,%17,%18,%19,%20,%21,%22,%23,%24,%25,%26,%27,%28,%29,%30,%31,"
      "%32,%33,%34,%35,%36,%37,%38,%39,%40,%41,%42,%43,%44,%45,%46,%47,"
      "%48,%49,%50,%51,%52,%53,%54,%55,%56,%57,%58,%59,%60,%61,%62,%63,"
      "%64,%65,%66,%67,%68,%69,%70,%71"
      "}, {%72,%73,%74,%75}, %76, p, 1, 1, 0; }"
    : "+f"(d[0]), "+f"(d[1]), "+f"(d[2]), "+f"(d[3]), "+f"(d[4]), "+f"(d[5]), "+f"(d[6]), "+f"(d[7]),
      "+f"(d[8]), "+f"(d[9]), "+f"(d[10]), "+f"(d[11]), "+f"(d[12]), "+f"(d[13]), "+f"(d[14]), "+f"(d[15]),
      "+f"(d[16]), "+f"(d[17]), "+f"(d[18]), "+f"(d[19]), "+f"(d[20]), "+f"(d[21]), "+f"(d[22]), "+f"(d[23]),
      "+f"(d[24]), "+f"(d[25]), "+f"(d[26]), "+f"(d[27]), "+f"(d[28]), "+f"(d[29]), "+f"(d[30]), "+f"(d[31]),
      "+f"(d[32]), "+f"(d[33]), "+f"(d[34]), "+f"(d[35]), "+f"(d[36]), "+f"(d[37]), "+f"(d[38]), "+f"(d[39]),
      "+f"(d[40]), "+f"(d[41]), "+f"(d[42]), "+f"(d[43]), "+f"(d[44]), "+f"(d[45]), "+f"(d[46]), "+f"(d[47]),
      "+f"(d[48]), "+f"(d[49]), "+f"(d[50]), "+f"(d[51]), "+f"(d[52]), "+f"(d[53]), "+f"(d[54]), "+f"(d[55]),
      "+f"(d[56]), "+f"(d[57]), "+f"(d[58]), "+f"(d[59]), "+f"(d[60]), "+f"(d[61]), "+f"(d[62]), "+f"(d[63]),
      "+f"(d[64]), "+f"(d[65]), "+f"(d[66]), "+f"(d[67]), "+f"(d[68]), "+f"(d[69]), "+f"(d[70]), "+f"(d[71])
    : "r"(a[0]), "r"(a[1]), "r"(a[2]), "r"(a[3]), "l"(db), "r"(sd));
}

__device__ __forceinline__ void wgmma_rs_n160(float* d, const uint32_t* a, uint64_t db, int sd) {
  asm volatile("{ .reg .pred p; setp.ne.b32 p, %85, 0;\n"
      "wgmma.mma_async.sync.aligned.m64n160k16.f32.bf16.bf16 {"
      "%0,%1,%2,%3,%4,%5,%6,%7,%8,%9,%10,%11,%12,%13,%14,%15,"
      "%16,%17,%18,%19,%20,%21,%22,%23,%24,%25,%26,%27,%28,%29,%30,%31,"
      "%32,%33,%34,%35,%36,%37,%38,%39,%40,%41,%42,%43,%44,%45,%46,%47,"
      "%48,%49,%50,%51,%52,%53,%54,%55,%56,%57,%58,%59,%60,%61,%62,%63,"
      "%64,%65,%66,%67,%68,%69,%70,%71,%72,%73,%74,%75,%76,%77,%78,%79"
      "}, {%80,%81,%82,%83}, %84, p, 1, 1, 0; }"
    : "+f"(d[0]), "+f"(d[1]), "+f"(d[2]), "+f"(d[3]), "+f"(d[4]), "+f"(d[5]), "+f"(d[6]), "+f"(d[7]),
      "+f"(d[8]), "+f"(d[9]), "+f"(d[10]), "+f"(d[11]), "+f"(d[12]), "+f"(d[13]), "+f"(d[14]), "+f"(d[15]),
      "+f"(d[16]), "+f"(d[17]), "+f"(d[18]), "+f"(d[19]), "+f"(d[20]), "+f"(d[21]), "+f"(d[22]), "+f"(d[23]),
      "+f"(d[24]), "+f"(d[25]), "+f"(d[26]), "+f"(d[27]), "+f"(d[28]), "+f"(d[29]), "+f"(d[30]), "+f"(d[31]),
      "+f"(d[32]), "+f"(d[33]), "+f"(d[34]), "+f"(d[35]), "+f"(d[36]), "+f"(d[37]), "+f"(d[38]), "+f"(d[39]),
      "+f"(d[40]), "+f"(d[41]), "+f"(d[42]), "+f"(d[43]), "+f"(d[44]), "+f"(d[45]), "+f"(d[46]), "+f"(d[47]),
      "+f"(d[48]), "+f"(d[49]), "+f"(d[50]), "+f"(d[51]), "+f"(d[52]), "+f"(d[53]), "+f"(d[54]), "+f"(d[55]),
      "+f"(d[56]), "+f"(d[57]), "+f"(d[58]), "+f"(d[59]), "+f"(d[60]), "+f"(d[61]), "+f"(d[62]), "+f"(d[63]),
      "+f"(d[64]), "+f"(d[65]), "+f"(d[66]), "+f"(d[67]), "+f"(d[68]), "+f"(d[69]), "+f"(d[70]), "+f"(d[71]),
      "+f"(d[72]), "+f"(d[73]), "+f"(d[74]), "+f"(d[75]), "+f"(d[76]), "+f"(d[77]), "+f"(d[78]), "+f"(d[79])
    : "r"(a[0]), "r"(a[1]), "r"(a[2]), "r"(a[3]), "l"(db), "r"(sd));
}

__device__ __forceinline__ void wgmma_rs_n176(float* d, const uint32_t* a, uint64_t db, int sd) {
  asm volatile("{ .reg .pred p; setp.ne.b32 p, %93, 0;\n"
      "wgmma.mma_async.sync.aligned.m64n176k16.f32.bf16.bf16 {"
      "%0,%1,%2,%3,%4,%5,%6,%7,%8,%9,%10,%11,%12,%13,%14,%15,"
      "%16,%17,%18,%19,%20,%21,%22,%23,%24,%25,%26,%27,%28,%29,%30,%31,"
      "%32,%33,%34,%35,%36,%37,%38,%39,%40,%41,%42,%43,%44,%45,%46,%47,"
      "%48,%49,%50,%51,%52,%53,%54,%55,%56,%57,%58,%59,%60,%61,%62,%63,"
      "%64,%65,%66,%67,%68,%69,%70,%71,%72,%73,%74,%75,%76,%77,%78,%79,"
      "%80,%81,%82,%83,%84,%85,%86,%87"
      "}, {%88,%89,%90,%91}, %92, p, 1, 1, 0; }"
    : "+f"(d[0]), "+f"(d[1]), "+f"(d[2]), "+f"(d[3]), "+f"(d[4]), "+f"(d[5]), "+f"(d[6]), "+f"(d[7]),
      "+f"(d[8]), "+f"(d[9]), "+f"(d[10]), "+f"(d[11]), "+f"(d[12]), "+f"(d[13]), "+f"(d[14]), "+f"(d[15]),
      "+f"(d[16]), "+f"(d[17]), "+f"(d[18]), "+f"(d[19]), "+f"(d[20]), "+f"(d[21]), "+f"(d[22]), "+f"(d[23]),
      "+f"(d[24]), "+f"(d[25]), "+f"(d[26]), "+f"(d[27]), "+f"(d[28]), "+f"(d[29]), "+f"(d[30]), "+f"(d[31]),
      "+f"(d[32]), "+f"(d[33]), "+f"(d[34]), "+f"(d[35]), "+f"(d[36]), "+f"(d[37]), "+f"(d[38]), "+f"(d[39]),
      "+f"(d[40]), "+f"(d[41]), "+f"(d[42]), "+f"(d[43]), "+f"(d[44]), "+f"(d[45]), "+f"(d[46]), "+f"(d[47]),
      "+f"(d[48]), "+f"(d[49]), "+f"(d[50]), "+f"(d[51]), "+f"(d[52]), "+f"(d[53]), "+f"(d[54]), "+f"(d[55]),
      "+f"(d[56]), "+f"(d[57]), "+f"(d[58]), "+f"(d[59]), "+f"(d[60]), "+f"(d[61]), "+f"(d[62]), "+f"(d[63]),
      "+f"(d[64]), "+f"(d[65]), "+f"(d[66]), "+f"(d[67]), "+f"(d[68]), "+f"(d[69]), "+f"(d[70]), "+f"(d[71]),
      "+f"(d[72]), "+f"(d[73]), "+f"(d[74]), "+f"(d[75]), "+f"(d[76]), "+f"(d[77]), "+f"(d[78]), "+f"(d[79]),
      "+f"(d[80]), "+f"(d[81]), "+f"(d[82]), "+f"(d[83]), "+f"(d[84]), "+f"(d[85]), "+f"(d[86]), "+f"(d[87])
    : "r"(a[0]), "r"(a[1]), "r"(a[2]), "r"(a[3]), "l"(db), "r"(sd));
}

__device__ __forceinline__ void wgmma_rs_n192(float* d, const uint32_t* a, uint64_t db, int sd) {
  asm volatile("{ .reg .pred p; setp.ne.b32 p, %101, 0;\n"
      "wgmma.mma_async.sync.aligned.m64n192k16.f32.bf16.bf16 {"
      "%0,%1,%2,%3,%4,%5,%6,%7,%8,%9,%10,%11,%12,%13,%14,%15,"
      "%16,%17,%18,%19,%20,%21,%22,%23,%24,%25,%26,%27,%28,%29,%30,%31,"
      "%32,%33,%34,%35,%36,%37,%38,%39,%40,%41,%42,%43,%44,%45,%46,%47,"
      "%48,%49,%50,%51,%52,%53,%54,%55,%56,%57,%58,%59,%60,%61,%62,%63,"
      "%64,%65,%66,%67,%68,%69,%70,%71,%72,%73,%74,%75,%76,%77,%78,%79,"
      "%80,%81,%82,%83,%84,%85,%86,%87,%88,%89,%90,%91,%92,%93,%94,%95"
      "}, {%96,%97,%98,%99}, %100, p, 1, 1, 0; }"
    : "+f"(d[0]), "+f"(d[1]), "+f"(d[2]), "+f"(d[3]), "+f"(d[4]), "+f"(d[5]), "+f"(d[6]), "+f"(d[7]),
      "+f"(d[8]), "+f"(d[9]), "+f"(d[10]), "+f"(d[11]), "+f"(d[12]), "+f"(d[13]), "+f"(d[14]), "+f"(d[15]),
      "+f"(d[16]), "+f"(d[17]), "+f"(d[18]), "+f"(d[19]), "+f"(d[20]), "+f"(d[21]), "+f"(d[22]), "+f"(d[23]),
      "+f"(d[24]), "+f"(d[25]), "+f"(d[26]), "+f"(d[27]), "+f"(d[28]), "+f"(d[29]), "+f"(d[30]), "+f"(d[31]),
      "+f"(d[32]), "+f"(d[33]), "+f"(d[34]), "+f"(d[35]), "+f"(d[36]), "+f"(d[37]), "+f"(d[38]), "+f"(d[39]),
      "+f"(d[40]), "+f"(d[41]), "+f"(d[42]), "+f"(d[43]), "+f"(d[44]), "+f"(d[45]), "+f"(d[46]), "+f"(d[47]),
      "+f"(d[48]), "+f"(d[49]), "+f"(d[50]), "+f"(d[51]), "+f"(d[52]), "+f"(d[53]), "+f"(d[54]), "+f"(d[55]),
      "+f"(d[56]), "+f"(d[57]), "+f"(d[58]), "+f"(d[59]), "+f"(d[60]), "+f"(d[61]), "+f"(d[62]), "+f"(d[63]),
      "+f"(d[64]), "+f"(d[65]), "+f"(d[66]), "+f"(d[67]), "+f"(d[68]), "+f"(d[69]), "+f"(d[70]), "+f"(d[71]),
      "+f"(d[72]), "+f"(d[73]), "+f"(d[74]), "+f"(d[75]), "+f"(d[76]), "+f"(d[77]), "+f"(d[78]), "+f"(d[79]),
      "+f"(d[80]), "+f"(d[81]), "+f"(d[82]), "+f"(d[83]), "+f"(d[84]), "+f"(d[85]), "+f"(d[86]), "+f"(d[87]),
      "+f"(d[88]), "+f"(d[89]), "+f"(d[90]), "+f"(d[91]), "+f"(d[92]), "+f"(d[93]), "+f"(d[94]), "+f"(d[95])
    : "r"(a[0]), "r"(a[1]), "r"(a[2]), "r"(a[3]), "l"(db), "r"(sd));
}

__device__ __forceinline__ void wgmma_rs_n208(float* d, const uint32_t* a, uint64_t db, int sd) {
  asm volatile("{ .reg .pred p; setp.ne.b32 p, %109, 0;\n"
      "wgmma.mma_async.sync.aligned.m64n208k16.f32.bf16.bf16 {"
      "%0,%1,%2,%3,%4,%5,%6,%7,%8,%9,%10,%11,%12,%13,%14,%15,"
      "%16,%17,%18,%19,%20,%21,%22,%23,%24,%25,%26,%27,%28,%29,%30,%31,"
      "%32,%33,%34,%35,%36,%37,%38,%39,%40,%41,%42,%43,%44,%45,%46,%47,"
      "%48,%49,%50,%51,%52,%53,%54,%55,%56,%57,%58,%59,%60,%61,%62,%63,"
      "%64,%65,%66,%67,%68,%69,%70,%71,%72,%73,%74,%75,%76,%77,%78,%79,"
      "%80,%81,%82,%83,%84,%85,%86,%87,%88,%89,%90,%91,%92,%93,%94,%95,"
      "%96,%97,%98,%99,%100,%101,%102,%103"
      "}, {%104,%105,%106,%107}, %108, p, 1, 1, 0; }"
    : "+f"(d[0]), "+f"(d[1]), "+f"(d[2]), "+f"(d[3]), "+f"(d[4]), "+f"(d[5]), "+f"(d[6]), "+f"(d[7]),
      "+f"(d[8]), "+f"(d[9]), "+f"(d[10]), "+f"(d[11]), "+f"(d[12]), "+f"(d[13]), "+f"(d[14]), "+f"(d[15]),
      "+f"(d[16]), "+f"(d[17]), "+f"(d[18]), "+f"(d[19]), "+f"(d[20]), "+f"(d[21]), "+f"(d[22]), "+f"(d[23]),
      "+f"(d[24]), "+f"(d[25]), "+f"(d[26]), "+f"(d[27]), "+f"(d[28]), "+f"(d[29]), "+f"(d[30]), "+f"(d[31]),
      "+f"(d[32]), "+f"(d[33]), "+f"(d[34]), "+f"(d[35]), "+f"(d[36]), "+f"(d[37]), "+f"(d[38]), "+f"(d[39]),
      "+f"(d[40]), "+f"(d[41]), "+f"(d[42]), "+f"(d[43]), "+f"(d[44]), "+f"(d[45]), "+f"(d[46]), "+f"(d[47]),
      "+f"(d[48]), "+f"(d[49]), "+f"(d[50]), "+f"(d[51]), "+f"(d[52]), "+f"(d[53]), "+f"(d[54]), "+f"(d[55]),
      "+f"(d[56]), "+f"(d[57]), "+f"(d[58]), "+f"(d[59]), "+f"(d[60]), "+f"(d[61]), "+f"(d[62]), "+f"(d[63]),
      "+f"(d[64]), "+f"(d[65]), "+f"(d[66]), "+f"(d[67]), "+f"(d[68]), "+f"(d[69]), "+f"(d[70]), "+f"(d[71]),
      "+f"(d[72]), "+f"(d[73]), "+f"(d[74]), "+f"(d[75]), "+f"(d[76]), "+f"(d[77]), "+f"(d[78]), "+f"(d[79]),
      "+f"(d[80]), "+f"(d[81]), "+f"(d[82]), "+f"(d[83]), "+f"(d[84]), "+f"(d[85]), "+f"(d[86]), "+f"(d[87]),
      "+f"(d[88]), "+f"(d[89]), "+f"(d[90]), "+f"(d[91]), "+f"(d[92]), "+f"(d[93]), "+f"(d[94]), "+f"(d[95]),
      "+f"(d[96]), "+f"(d[97]), "+f"(d[98]), "+f"(d[99]), "+f"(d[100]), "+f"(d[101]), "+f"(d[102]), "+f"(d[103])
    : "r"(a[0]), "r"(a[1]), "r"(a[2]), "r"(a[3]), "l"(db), "r"(sd));
}

__device__ __forceinline__ void wgmma_rs_n224(float* d, const uint32_t* a, uint64_t db, int sd) {
  asm volatile("{ .reg .pred p; setp.ne.b32 p, %117, 0;\n"
      "wgmma.mma_async.sync.aligned.m64n224k16.f32.bf16.bf16 {"
      "%0,%1,%2,%3,%4,%5,%6,%7,%8,%9,%10,%11,%12,%13,%14,%15,"
      "%16,%17,%18,%19,%20,%21,%22,%23,%24,%25,%26,%27,%28,%29,%30,%31,"
      "%32,%33,%34,%35,%36,%37,%38,%39,%40,%41,%42,%43,%44,%45,%46,%47,"
      "%48,%49,%50,%51,%52,%53,%54,%55,%56,%57,%58,%59,%60,%61,%62,%63,"
      "%64,%65,%66,%67,%68,%69,%70,%71,%72,%73,%74,%75,%76,%77,%78,%79,"
      "%80,%81,%82,%83,%84,%85,%86,%87,%88,%89,%90,%91,%92,%93,%94,%95,"
      "%96,%97,%98,%99,%100,%101,%102,%103,%104,%105,%106,%107,%108,%109,%110,%111"
      "}, {%112,%113,%114,%115}, %116, p, 1, 1, 0; }"
    : "+f"(d[0]), "+f"(d[1]), "+f"(d[2]), "+f"(d[3]), "+f"(d[4]), "+f"(d[5]), "+f"(d[6]), "+f"(d[7]),
      "+f"(d[8]), "+f"(d[9]), "+f"(d[10]), "+f"(d[11]), "+f"(d[12]), "+f"(d[13]), "+f"(d[14]), "+f"(d[15]),
      "+f"(d[16]), "+f"(d[17]), "+f"(d[18]), "+f"(d[19]), "+f"(d[20]), "+f"(d[21]), "+f"(d[22]), "+f"(d[23]),
      "+f"(d[24]), "+f"(d[25]), "+f"(d[26]), "+f"(d[27]), "+f"(d[28]), "+f"(d[29]), "+f"(d[30]), "+f"(d[31]),
      "+f"(d[32]), "+f"(d[33]), "+f"(d[34]), "+f"(d[35]), "+f"(d[36]), "+f"(d[37]), "+f"(d[38]), "+f"(d[39]),
      "+f"(d[40]), "+f"(d[41]), "+f"(d[42]), "+f"(d[43]), "+f"(d[44]), "+f"(d[45]), "+f"(d[46]), "+f"(d[47]),
      "+f"(d[48]), "+f"(d[49]), "+f"(d[50]), "+f"(d[51]), "+f"(d[52]), "+f"(d[53]), "+f"(d[54]), "+f"(d[55]),
      "+f"(d[56]), "+f"(d[57]), "+f"(d[58]), "+f"(d[59]), "+f"(d[60]), "+f"(d[61]), "+f"(d[62]), "+f"(d[63]),
      "+f"(d[64]), "+f"(d[65]), "+f"(d[66]), "+f"(d[67]), "+f"(d[68]), "+f"(d[69]), "+f"(d[70]), "+f"(d[71]),
      "+f"(d[72]), "+f"(d[73]), "+f"(d[74]), "+f"(d[75]), "+f"(d[76]), "+f"(d[77]), "+f"(d[78]), "+f"(d[79]),
      "+f"(d[80]), "+f"(d[81]), "+f"(d[82]), "+f"(d[83]), "+f"(d[84]), "+f"(d[85]), "+f"(d[86]), "+f"(d[87]),
      "+f"(d[88]), "+f"(d[89]), "+f"(d[90]), "+f"(d[91]), "+f"(d[92]), "+f"(d[93]), "+f"(d[94]), "+f"(d[95]),
      "+f"(d[96]), "+f"(d[97]), "+f"(d[98]), "+f"(d[99]), "+f"(d[100]), "+f"(d[101]), "+f"(d[102]), "+f"(d[103]),
      "+f"(d[104]), "+f"(d[105]), "+f"(d[106]), "+f"(d[107]), "+f"(d[108]), "+f"(d[109]), "+f"(d[110]), "+f"(d[111])
    : "r"(a[0]), "r"(a[1]), "r"(a[2]), "r"(a[3]), "l"(db), "r"(sd));
}

__device__ __forceinline__ void wgmma_rs_n240(float* d, const uint32_t* a, uint64_t db, int sd) {
  asm volatile("{ .reg .pred p; setp.ne.b32 p, %125, 0;\n"
      "wgmma.mma_async.sync.aligned.m64n240k16.f32.bf16.bf16 {"
      "%0,%1,%2,%3,%4,%5,%6,%7,%8,%9,%10,%11,%12,%13,%14,%15,"
      "%16,%17,%18,%19,%20,%21,%22,%23,%24,%25,%26,%27,%28,%29,%30,%31,"
      "%32,%33,%34,%35,%36,%37,%38,%39,%40,%41,%42,%43,%44,%45,%46,%47,"
      "%48,%49,%50,%51,%52,%53,%54,%55,%56,%57,%58,%59,%60,%61,%62,%63,"
      "%64,%65,%66,%67,%68,%69,%70,%71,%72,%73,%74,%75,%76,%77,%78,%79,"
      "%80,%81,%82,%83,%84,%85,%86,%87,%88,%89,%90,%91,%92,%93,%94,%95,"
      "%96,%97,%98,%99,%100,%101,%102,%103,%104,%105,%106,%107,%108,%109,%110,%111,"
      "%112,%113,%114,%115,%116,%117,%118,%119"
      "}, {%120,%121,%122,%123}, %124, p, 1, 1, 0; }"
    : "+f"(d[0]), "+f"(d[1]), "+f"(d[2]), "+f"(d[3]), "+f"(d[4]), "+f"(d[5]), "+f"(d[6]), "+f"(d[7]),
      "+f"(d[8]), "+f"(d[9]), "+f"(d[10]), "+f"(d[11]), "+f"(d[12]), "+f"(d[13]), "+f"(d[14]), "+f"(d[15]),
      "+f"(d[16]), "+f"(d[17]), "+f"(d[18]), "+f"(d[19]), "+f"(d[20]), "+f"(d[21]), "+f"(d[22]), "+f"(d[23]),
      "+f"(d[24]), "+f"(d[25]), "+f"(d[26]), "+f"(d[27]), "+f"(d[28]), "+f"(d[29]), "+f"(d[30]), "+f"(d[31]),
      "+f"(d[32]), "+f"(d[33]), "+f"(d[34]), "+f"(d[35]), "+f"(d[36]), "+f"(d[37]), "+f"(d[38]), "+f"(d[39]),
      "+f"(d[40]), "+f"(d[41]), "+f"(d[42]), "+f"(d[43]), "+f"(d[44]), "+f"(d[45]), "+f"(d[46]), "+f"(d[47]),
      "+f"(d[48]), "+f"(d[49]), "+f"(d[50]), "+f"(d[51]), "+f"(d[52]), "+f"(d[53]), "+f"(d[54]), "+f"(d[55]),
      "+f"(d[56]), "+f"(d[57]), "+f"(d[58]), "+f"(d[59]), "+f"(d[60]), "+f"(d[61]), "+f"(d[62]), "+f"(d[63]),
      "+f"(d[64]), "+f"(d[65]), "+f"(d[66]), "+f"(d[67]), "+f"(d[68]), "+f"(d[69]), "+f"(d[70]), "+f"(d[71]),
      "+f"(d[72]), "+f"(d[73]), "+f"(d[74]), "+f"(d[75]), "+f"(d[76]), "+f"(d[77]), "+f"(d[78]), "+f"(d[79]),
      "+f"(d[80]), "+f"(d[81]), "+f"(d[82]), "+f"(d[83]), "+f"(d[84]), "+f"(d[85]), "+f"(d[86]), "+f"(d[87]),
      "+f"(d[88]), "+f"(d[89]), "+f"(d[90]), "+f"(d[91]), "+f"(d[92]), "+f"(d[93]), "+f"(d[94]), "+f"(d[95]),
      "+f"(d[96]), "+f"(d[97]), "+f"(d[98]), "+f"(d[99]), "+f"(d[100]), "+f"(d[101]), "+f"(d[102]), "+f"(d[103]),
      "+f"(d[104]), "+f"(d[105]), "+f"(d[106]), "+f"(d[107]), "+f"(d[108]), "+f"(d[109]), "+f"(d[110]), "+f"(d[111]),
      "+f"(d[112]), "+f"(d[113]), "+f"(d[114]), "+f"(d[115]), "+f"(d[116]), "+f"(d[117]), "+f"(d[118]), "+f"(d[119])
    : "r"(a[0]), "r"(a[1]), "r"(a[2]), "r"(a[3]), "l"(db), "r"(sd));
}

__device__ __forceinline__ void wgmma_rs_n256(float* d, const uint32_t* a, uint64_t db, int sd) {
  asm volatile("{ .reg .pred p; setp.ne.b32 p, %133, 0;\n"
      "wgmma.mma_async.sync.aligned.m64n256k16.f32.bf16.bf16 {"
      "%0,%1,%2,%3,%4,%5,%6,%7,%8,%9,%10,%11,%12,%13,%14,%15,"
      "%16,%17,%18,%19,%20,%21,%22,%23,%24,%25,%26,%27,%28,%29,%30,%31,"
      "%32,%33,%34,%35,%36,%37,%38,%39,%40,%41,%42,%43,%44,%45,%46,%47,"
      "%48,%49,%50,%51,%52,%53,%54,%55,%56,%57,%58,%59,%60,%61,%62,%63,"
      "%64,%65,%66,%67,%68,%69,%70,%71,%72,%73,%74,%75,%76,%77,%78,%79,"
      "%80,%81,%82,%83,%84,%85,%86,%87,%88,%89,%90,%91,%92,%93,%94,%95,"
      "%96,%97,%98,%99,%100,%101,%102,%103,%104,%105,%106,%107,%108,%109,%110,%111,"
      "%112,%113,%114,%115,%116,%117,%118,%119,%120,%121,%122,%123,%124,%125,%126,%127"
      "}, {%128,%129,%130,%131}, %132, p, 1, 1, 0; }"
    : "+f"(d[0]), "+f"(d[1]), "+f"(d[2]), "+f"(d[3]), "+f"(d[4]), "+f"(d[5]), "+f"(d[6]), "+f"(d[7]),
      "+f"(d[8]), "+f"(d[9]), "+f"(d[10]), "+f"(d[11]), "+f"(d[12]), "+f"(d[13]), "+f"(d[14]), "+f"(d[15]),
      "+f"(d[16]), "+f"(d[17]), "+f"(d[18]), "+f"(d[19]), "+f"(d[20]), "+f"(d[21]), "+f"(d[22]), "+f"(d[23]),
      "+f"(d[24]), "+f"(d[25]), "+f"(d[26]), "+f"(d[27]), "+f"(d[28]), "+f"(d[29]), "+f"(d[30]), "+f"(d[31]),
      "+f"(d[32]), "+f"(d[33]), "+f"(d[34]), "+f"(d[35]), "+f"(d[36]), "+f"(d[37]), "+f"(d[38]), "+f"(d[39]),
      "+f"(d[40]), "+f"(d[41]), "+f"(d[42]), "+f"(d[43]), "+f"(d[44]), "+f"(d[45]), "+f"(d[46]), "+f"(d[47]),
      "+f"(d[48]), "+f"(d[49]), "+f"(d[50]), "+f"(d[51]), "+f"(d[52]), "+f"(d[53]), "+f"(d[54]), "+f"(d[55]),
      "+f"(d[56]), "+f"(d[57]), "+f"(d[58]), "+f"(d[59]), "+f"(d[60]), "+f"(d[61]), "+f"(d[62]), "+f"(d[63]),
      "+f"(d[64]), "+f"(d[65]), "+f"(d[66]), "+f"(d[67]), "+f"(d[68]), "+f"(d[69]), "+f"(d[70]), "+f"(d[71]),
      "+f"(d[72]), "+f"(d[73]), "+f"(d[74]), "+f"(d[75]), "+f"(d[76]), "+f"(d[77]), "+f"(d[78]), "+f"(d[79]),
      "+f"(d[80]), "+f"(d[81]), "+f"(d[82]), "+f"(d[83]), "+f"(d[84]), "+f"(d[85]), "+f"(d[86]), "+f"(d[87]),
      "+f"(d[88]), "+f"(d[89]), "+f"(d[90]), "+f"(d[91]), "+f"(d[92]), "+f"(d[93]), "+f"(d[94]), "+f"(d[95]),
      "+f"(d[96]), "+f"(d[97]), "+f"(d[98]), "+f"(d[99]), "+f"(d[100]), "+f"(d[101]), "+f"(d[102]), "+f"(d[103]),
      "+f"(d[104]), "+f"(d[105]), "+f"(d[106]), "+f"(d[107]), "+f"(d[108]), "+f"(d[109]), "+f"(d[110]), "+f"(d[111]),
      "+f"(d[112]), "+f"(d[113]), "+f"(d[114]), "+f"(d[115]), "+f"(d[116]), "+f"(d[117]), "+f"(d[118]), "+f"(d[119]),
      "+f"(d[120]), "+f"(d[121]), "+f"(d[122]), "+f"(d[123]), "+f"(d[124]), "+f"(d[125]), "+f"(d[126]), "+f"(d[127])
    : "r"(a[0]), "r"(a[1]), "r"(a[2]), "r"(a[3]), "l"(db), "r"(sd));
}

__device__ __forceinline__ void ln_finish(float mean, float var, float& mb, float& rinv) {
  mb = round_bf16(mean);
  float sd;
  asm("sqrt.approx.ftz.f32 %0, %1;" : "=f"(sd) : "f"(round_bf16(round_bf16(var) + 1e-5f)));
  asm("rcp.approx.ftz.f32 %0, %1;" : "=f"(rinv) : "f"(round_bf16(sd)));
}
__device__ __forceinline__ uint32_t sum4(uint32_t a, uint32_t b, uint32_t c, uint32_t d) { return badd2(badd2(badd2(d, c), b), a); }
struct Ring {
  uint32_t s, ph;
  __device__ __forceinline__ void next() { if (++s == NSTAGE) { s = 0; ph ^= 1; } }
};

template <int J> __device__ __forceinline__ void conv_lda(uint32_t* a, uint32_t base, bool on) {
  asm volatile("{ .reg .pred p; setp.ne.u32 p, %3, 0;\n @p ld.shared.u32 %0, [%2 + %4];\n @p ld.shared.u32 %1, [%2 + %5]; }"
               : "+r"(a[2 * J]), "+r"(a[2 * J + 1]) : "r"(base), "r"((uint32_t)on), "n"((J >> 1) * 256 + (J & 1) * 16), "n"((J >> 1) * 256 + (J & 1) * 16 + 128) : "memory");
}
template <int J = 0> __device__ __forceinline__ void conv_lda_all(uint32_t* a, uint32_t base) {
  conv_lda<J>(a, base, true);
  if constexpr (J < 31) conv_lda_all<J + 1>(a, base);
}
__device__ __forceinline__ void conv_mma(float* acc, const uint32_t* a, uint64_t db) {
  wgmma_rs_n256(acc, a, db, 0);
  wgmma_rs_n240(acc, a + 4, db + 16, 1);
  wgmma_rs_n224(acc, a + 8, db + 32, 1);
  wgmma_rs_n208(acc, a + 12, db + 48, 1);
  wgmma_rs_n192(acc, a + 16, db + 64, 1);
  wgmma_rs_n176(acc, a + 20, db + 80, 1);
  wgmma_rs_n160(acc, a + 24, db + 96, 1);
  wgmma_rs_n144(acc, a + 28, db + 112, 1);
  wgmma_rs_n128(acc, a + 32, db + 128, 1);
  wgmma_rs_n112(acc, a + 36, db + 144, 1);
  wgmma_rs_n96(acc, a + 40, db + 160, 1);
  wgmma_rs_n80(acc, a + 44, db + 176, 1);
  wgmma_rs_n64(acc, a + 48, db + 192, 1);
  wgmma_rs_n48(acc, a + 52, db + 208, 1);
  wgmma_rs_n32(acc, a + 56, db + 224, 1);
  wgmma_rs_n16(acc, a + 60, db + 240, 1);
}
__device__ __forceinline__ uint32_t conv_part(const float* acc, int j) {
  const int q = 31 - j;
  return q == 31 ? pack_bf16(acc[124], acc[125]) : pack_bf16(acc[4 * q] + acc[(4 * q + 6) & 127], acc[4 * q + 1] + acc[(4 * q + 7) & 127]);
}
template <int J = 0> __device__ __forceinline__ void conv_drain(const float* acc, uint32_t wr, uint32_t* a, uint32_t ka, bool more) {
  conv_lda<J>(a, ka, more);
  sts32(wr + J * 128, conv_part(acc, J));
  if constexpr (J < 31) conv_drain<J + 1>(acc, wr, a, ka, more);
}
__device__ __forceinline__ uint4 conv_sum(const uint4* p) {
  return make_uint4(sum4(p[0].x, p[1].x, p[2].x, p[3].x), sum4(p[0].y, p[1].y, p[2].y, p[3].y), sum4(p[0].z, p[1].z, p[2].z, p[3].z),
                    sum4(p[0].w, p[1].w, p[2].w, p[3].w));
}
__device__ __forceinline__ int g2k(int rank, int kb) { return (rank * G2_KB + (kb < 6 ? 6 * kb : kb - 5 + (kb - 6) / 5)) * 64; }

template <int NV> __device__ __forceinline__ void gelu_stage(float* acc, const float* hb, uint32_t sa, int passes, uint32_t bar) {
#pragma unroll
  for (int i = 0; i < NV; i++) acc[i] = fmaf(acc[i], 0.5f, hb[(i >> 1) & 1]);
#pragma unroll 1
  for (; passes > 0; passes--, sa += NV * 256) {
#pragma unroll
    for (int i = 0; i < NV; i += 8)
      stsm4t(sa + i * 256, pack_bf16(gelu_half(acc[i]), gelu_half(acc[i + 1])), pack_bf16(gelu_half(acc[i + 2]), gelu_half(acc[i + 3])),
             pack_bf16(gelu_half(acc[i + 4]), gelu_half(acc[i + 5])), pack_bf16(gelu_half(acc[i + 6]), gelu_half(acc[i + 7])));
    __syncwarp();
    if (bar) mbar_arrive(bar);
    bar = 0;
    float half = 0.5f;
    asm volatile("" : "+f"(half));
#pragma unroll
    for (int i = 0; i < NV; i++) acc[i] = fmaf(acc[NV + i], half, hb[2 + ((i >> 1) & 1)]);
  }
}

__global__ void __cluster_dims__(2, 1, 1) __launch_bounds__(384, 1) fused_kernel(const __grid_constant__ Hot H, const __grid_constant__ Params P) {
  extern __shared__ __align__(1024) uint8_t smem_raw[];
  const uint32_t t0 = clk();
  const uint32_t sb = smem_u32(smem_raw);
  const int tid = threadIdx.x, lane = tid & 31;
  const int bid = blockIdx.x, rank = bid & 1;
  const Role& R = P.role[bid];
  Scratch* const S = H.S;
  uint32_t xr[18];
  const int row = bid * 16 + (tid >> 4);
  if (tid < 256 && bid < 128) {
    const char* src = reinterpret_cast<const char*>(H.x) + row * (D_ * 2) + (lane & 15) * 8;
#pragma unroll
    for (int j = 0; j < 9; j++) asm volatile("ld.global.nc.v2.u32 {%0,%1}, [%2];" : "=r"(xr[2 * j]), "=r"(xr[2 * j + 1]) : "l"(src + 128 * j));
  }
  if (tid == 256) asm volatile("prefetch.tensormap [%0];" :: "l"(&P.m_w1 + (R.at == 15)) : "memory");
  const int warp = __shfl_sync(0xffffffffu, tid >> 5, 0);

  if (warp >= 8) {
    const bool one = elect_one(), left = R.at == 15;
    TUNED(NWE, 2, 1); TUNED(NW0, 3, 2);
    if (warp == 8 && one) {
#pragma unroll
      for (int b = B_FULL; b < B_KFULL; b += 8) mbar_init(sb + b, 1);
#pragma unroll 1
      for (int s = 0; s < NWE; s++) {
        mbar_expect_tx(sb + B_FULL + 8 * s, G1_BYTES);
        fence_async_smem();
        tma3d(sb + s * SLOT, &P.m_w1 + left, 0, s * 64, R.fg, sb + B_FULL + 8 * s);
      }
#pragma unroll
      for (int b = B_KFULL; b <= B_DONE; b += 8) mbar_init(sb + b, b < B_EMPTY ? 1 : b < B_SFREE ? 2 : b < B_CEMPTY ? 3 : b < B_G1DONE ? 4 : 8);
      asm volatile("fence.mbarrier_init.release.cluster;" ::: "memory");
    }
    __syncwarp();
    asm volatile("barrier.cluster.arrive.relaxed.aligned;" ::: "memory");
    asm volatile("setmaxnreg.dec.sync.aligned.u32 56;");
    asm volatile("barrier.cluster.wait.aligned;" ::: "memory");
    if (warp == 8) {
      const uint32_t ep = ldg32(S->cnt + C_EPOCH * 32);
      if (one) {
#pragma unroll 1
        for (int i = 0; i < 6; i++) asm volatile("prefetch.tensormap [%0];" :: "l"(&P.m_w2 + i) : "memory");
      }
      __syncwarp();
      if (bid < 128) bar_sync(2, 288);
      if (one) {
        TLREC(31);
        signal(S, C_H, EPOCH / 132);
        TLREC(1);
        const uint32_t boff = left ? 24576 : 16384;
        int kr = bid < 128 ? -2 : KV_ROUNDS + 1, ks = 0;
        auto kv_step = [&]() {
          if (ks == 0) {
            bulk_wait_all();
            if (kr < KV_ROUNDS - 2) {
              const int q = (kr + 2) % 3;
              const uint32_t in = sb + kv_buf(q), fb = sb + B_UFULL + 8 * q;
              mbar_expect_tx(fb, 3840 + 3264 + 768);
              tma2d(in, &P.m_k, (kr + 2) * 96, bid * 16 - 4, fb);
              tma2d(in + 3840, &P.m_v, (kr + 2) * 96, bid * 16 - 1, fb);
              bulk_load(in + 7168, H.shift_k + (kr + 2) * 384, 768, fb);
            }
            if (kr == KV_ROUNDS) { mbar_arrive(sb + B_KVDONE); kr++; }
          } else if (kr >= 0) {
            if (!mbar_test(sb + B_KFULL + 8 * (kr % 3), kr >= 3)) return;
            fence_async_smem();
            tma3d_store(&P.m_ub, sb + kv_buf(kr % 3) + (ks - 1) * 3072, 16 * (127 - bid), kr * 48, 2 * ks - 2);
            bulk_commit();
          }
          if (++ks == 3) { kr++; ks = kr == KV_ROUNDS - 2 || kr == KV_ROUNDS - 1; }
        };
        if (bid >= 128) mbar_arrive(sb + B_KVDONE);
        Ring r{0, 1};
#pragma unroll 1
        for (int kb = NWE - NW0; kb < G1_KB || kr <= KV_ROUNDS; kb++) {
          if (kb < G1_KB) {
          const int kw = kb < 0 ? kb + NW0 : kb, s = kb < 0 ? kw : r.s;
          const uint32_t fb = sb + B_FULL + 8 * s;
          if (kb < 0 || kb >= NW0) {
            mbar_wait(sb + B_EMPTY + 8 * s, r.ph);
            mbar_expect_tx(fb, G1_BYTES);
            tma3d(sb + s * SLOT, &P.m_w1 + left, 0, kw * 64, R.fg, fb);
            if (kb < 0) continue;
          }
          if (kb == 0) { await(S, C_H, ep); fence_async_global(); TLREC(2); }
          bulk_load(sb + s * SLOT + boff, S->h + (kb * 18 + R.at) * 2048, G1_BYTES - boff, fb);
          if (kb == 23) {
#pragma unroll 1
            for (int i = 0; i < 2; i++) {
              sts128(sb + cv_taps(i), 0, 0, 0, 0); sts128(sb + cv_taps(i) + 16, 0, 0, 0, 0);
              bulk_load(sb + cv_taps(i) + 32, H.ssm_k + (R.ch + i) * S_, 4096, sb + B_MISC);
            }
            mbar_expect_tx(sb + B_MISC, boff / 64 + 1152 + 8192);
            bulk_load(sb + SM_B1, H.b1 + R.fg * 64, boff / 64, sb + B_MISC);
            bulk_load(sb + SM_D, H.ssm_D, 1152, sb + B_MISC);
          }
          r.next();
          }
          if (kb >= KV0 && kr <= KV_ROUNDS) kv_step();
        }
        await(S, C_KV, ep);
        fence_async_global();
#pragma unroll 1
        for (int i = 0; i < R.ncv; i++) {
          if (i == 2) {
            if (R.sg >= 0) {
#pragma unroll 1
              for (int s = 2; s < NSTAGE; s++) {
                mbar_wait(sb + B_EMPTY + 8 * s, ((G1_KB / NSTAGE) - 1) & 1);
                mbar_expect_tx(sb + B_FULL + 8 * s, G2_BYTES);
                tma3d(sb + s * SLOT, &P.m_w2, 0, (rank * G2_KB + 6 * (s - 2)) * 64, R.sg, sb + B_FULL + 8 * s);
              }
            }
            mbar_wait(sb + B_G1DONE, 0);
          }
          const uint32_t kt = sb + cv_taps(i), b8 = sb + 8 * (i & 3);
          mbar_wait(b8 + B_CEMPTY, ((i >> 2) & 1) ^ 1);
          if (i < 2) mbar_arrive(b8 + B_KFULL);
          else {
            sts128(kt, 0, 0, 0, 0); sts128(kt + 16, 0, 0, 0, 0);
            mbar_expect_tx(b8 + B_KFULL, 4096);
            bulk_load(kt + 32, H.ssm_k + (R.ch + i) * S_, 4096, b8 + B_KFULL);
          }
          mbar_expect_tx(b8 + B_UFULL, 8192);
          bulk_load(sb + cv_in(i), S->ub + (R.ch + i) * 4096, 8192, b8 + B_UFULL);
        }
        if (R.sg >= 0) {
          mbar_expect_tx(sb + B_XY, 2 * 18432 + 2048 + 256);
#pragma unroll
          for (int i = 0; i < 4; i++) mbar_expect_tx(sb + B_XFULL + 8 * i, i & 1 ? 9216 - XP * 2048 : XP * 2048);
          TUNED(SYNCA, 0, 5); TUNED(SYNCKB, 1, 7);
#pragma unroll 1
          for (int kb = 0; kb < G2_KB; kb++, r.next()) {
            const int k0 = g2k(rank, kb);
            const uint32_t fb = sb + B_FULL + 8 * r.s, slot = sb + r.s * SLOT;
            if (!(kb & ~4)) { await(S, C_U + (kb >> 2), ep); fence_async_global(); if (!kb) TLREC(6); }
            if (kb >= NSTAGE - 2) {
              mbar_wait(sb + B_EMPTY + 8 * r.s, r.ph);
              if (kb == SYNCA) asm volatile("red.relaxed.gpu.global.add.u32 [%0], %1;" :: "l"(S->cnt + C_SYNC * 32), "r"(EPOCH / 128) : "memory");
              if (kb == SYNCKB) await(S, C_SYNC, ep);
              mbar_expect_tx(fb, G2_BYTES);
              tma3d(slot, &P.m_w2, 0, k0, R.sg, fb);
            }
            bulk_load(slot + 16384, S->u + k0 * D_ + R.ds * 512, 9216, fb);
            bulk_load(slot + 16384 + 9216, S->u + k0 * D_ + R.dk * 512, 9216, fb);
            const uint32_t nx = kb - 8;
            if (nx == 0) { mbar_wait(sb + B_KVDONE, 1); fence_async_smem(); }
            if (nx < 8) tma2d(sb + SM_CV + nx * 2304, &P.m_x, R.dk * 8, R.sg * 64 + nx * 16, sb + B_XY);
          }
          bulk_load(sb + SM_ST, S->stats + R.sg * 64, 2048, sb + B_XY);
          bulk_load(sb + SM_B2, P.b2 + R.sg * 64, 256, sb + B_XY);
          await(S, C_Y, ep);
          fence_async_global();
          TLREC(19);
          tma3d(sb + SM_DED, &P.m_y, 0, R.dk * 8, R.sg, sb + B_XY);
          if (bid == 0) asm volatile("red.relaxed.gpu.global.add.u32 [%0], %1;" :: "l"(S->cnt + C_EPOCH * 32), "r"(EPOCH) : "memory");
        }
      }
    } else {
      if (bid < 128) {
        const int ht = tid - 288, hf = ht >= 48, pr = ht - 48 * hf;
        const uint32_t st = (1 - hf) * 1536 + pr * 32, sw = (pr & 4) * 4;
#pragma unroll 1
        for (int r = 0; r < KV_ROUNDS; r++) {
          const int q = r % 3;
          const uint32_t in = sb + kv_buf(q);
          {
            mbar_wait_guarded(sb + B_UFULL + 8 * q, t0, r >= 3);
            uint32_t kk[12], vv[9];
#pragma unroll
            for (int j = 0; j < 12; j++) kk[j] = lds32(in + hf * 1536 + pr * 4 + j * 192);
#pragma unroll
            for (int j = 0; j < 9; j++) vv[j] = lds32(in + 3840 + hf * 1536 + pr * 4 + j * 192);
            const uint4 w = lds128(in + 7168 + pr * 16);
            const uint32_t w0 = __byte_perm(w.x, w.z, 0x5410), w1 = __byte_perm(w.x, w.z, 0x7632);
            const uint32_t w2 = __byte_perm(w.y, w.w, 0x5410), w3 = __byte_perm(w.y, w.w, 0x7632);
#pragma unroll
            for (int j = 0; j < 9; j++)
              vv[j] = bmul2(badd2(badd2(badd2(bmul2(kk[j], w3), bmul2(kk[j + 1], w2)), bmul2(kk[j + 2], w1)), bmul2(kk[j + 3], w0)), vv[j]);
            bar_sync(1, 96);
#pragma unroll
            for (int c = 0; c < 2; c++)
#pragma unroll
              for (int pi = 0; pi < 2; pi++) {
                const uint32_t sel = c ? 0x7632 : 0x5410;
                sts128(in + st + c * 3072 + (pi * 16 ^ sw), __byte_perm(vv[7 + pi], vv[6 + pi], sel), __byte_perm(vv[5 + pi], vv[4 + pi], sel),
                       __byte_perm(vv[3 + pi], vv[2 + pi], sel), __byte_perm(vv[1 + pi], vv[pi], sel));
              }
            bar_sync(1, 96);
            if (ht == 0) mbar_arrive(sb + B_KFULL + 8 * q);
          }
          __syncwarp();
        }
      }
      if (one) {
        if (warp < 11) {
          const int wg = warp - 9;
          const uint32_t bytes = left ? 12288 : 10240;
#pragma unroll 1
          for (int j = 0; j < 2; j++) {
            mbar_wait_guarded(sb + B_STG + 8 * wg + (j ? 0 : 16), t0);
            fence_async_smem();
            TLREC(13 + wg);
            if (!j || wg || !left)
              bulk_store(S->u + (R.fg + wg) * (64 * D_) + R.at * 2048 + j * (left ? 64 * D_ : 5120), sb + (wg ? SM_ST1 : SM_DED) + j * bytes, bytes);
          }
          bulk_commit();
          bulk_wait_all();
          mbar_arrive(sb + B_STORED + 8 * wg);
          if (wg) mbar_arrive(sb + B_EMPTY);
          asm volatile("mbarrier.arrive.shared::cta.b64 _, [%0], 3;" :: "r"(sb + B_SFREE + 8 * wg) : "memory");
          signal(S, C_U + wg, EPOCH / 132);
          TLREC(15 + wg);
        } else {
          mbar_wait_guarded(sb + B_KVDONE, t0);
          signal(S, C_KV, EPOCH / 132);
          TLREC(27);
        }
      }
      __syncwarp();
#pragma unroll 1
      for (int i = 0; i < R.ncv; i++) {
        const uint32_t red = sb + cv_red(i, R.ncv) + (tid - 288) * 16;
        uint4* yo = reinterpret_cast<uint4*>(S->y + (R.ch + i) * S_) + (tid - 288);
        mbar_wait_guarded(sb + B_STORED + 8 * (i & 1), t0);
        mbar_wait_guarded(sb + B_STG + 8 * (i & 1) + (i + 2 < R.ncv ? 0 : 16), t0, i + 2 >= R.ncv || !(i & 2));
        uint4 p[2][4];
#pragma unroll
        for (int x = 0; x < 8; x++) p[x >> 2][x & 3] = lds128(red + (x & 3) * CV_REDW + (x >> 2) * 1536);
        yo[0] = conv_sum(p[0]);
        if (warp < 11) {
#pragma unroll
          for (int x = 0; x < 4; x++) p[0][x] = lds128(red + x * CV_REDW + 3072);
          yo[192] = conv_sum(p[0]);
        }
        yo[96] = conv_sum(p[1]);
        __syncwarp();
        if (one) mbar_arrive(sb + (i + 4 == R.ncv ? B_PDONE : B_SFREE + 8 * (i & 1)));
        if (i + 3 == R.ncv) {
          bar_sync(1, 96);
          if (warp == 11 && one) { fence_async_smem(); mbar_arrive(sb + B_EMPTY + 8); }
          __syncwarp();
        }
      }
      bar_sync(1, 96);
      if (warp == 11 && one) {
        TLREC(7);
        mbar_arrive(sb + B_KVDONE);
        signal(S, C_Y, EPOCH / 132);
        if (R.sg >= 0) mbar_wait_guarded(sb + B_DONE, t0);
      }
    }
    TLEND();
  } else {
    asm volatile("barrier.cluster.arrive.relaxed.aligned;" ::: "memory");
    if (bid < 128) {
      float c[36], s[4];
#pragma unroll
      for (int i = 0; i < 18; i++) { c[2 * i] = bf_lo(xr[i]); c[2 * i + 1] = bf_hi(xr[i]); }
#pragma unroll
      for (int i = 0; i < 36; i++) s[i & 3] = i < 4 ? c[i] : s[i & 3] + c[i];
      const float ml = ((s[0] + s[1]) + (s[2] + s[3])) * (1.0f / 36.0f);
#pragma unroll
      for (int i = 0; i < 36; i++) { c[i] -= ml; s[i & 3] = i < 4 ? c[i] * c[i] : fmaf(c[i], c[i], s[i & 3]); }
      float m = ml, q = (s[0] + s[1]) + (s[2] + s[3]), n2 = 18.f;
#pragma unroll
      for (int o = 1; o < 16; o <<= 1) {
        const float mo = __shfl_xor_sync(0xffffffffu, m, o), qo = __shfl_xor_sync(0xffffffffu, q, o);
        const float dl = m - mo;
        q = fmaf(dl * dl, n2, q + qo);
        m = fmaf(dl, -0.5f, m);
        n2 *= 2.f;
      }
      const float var = q * (1.0f / 576.0f);
      float mb, rinv, mb2, rinv2;
      ln_finish(m, var, mb, rinv);
      ln_finish((m - mb) * rinv, var * rinv * rinv, mb2, rinv2);
      const float ca = rinv * rinv2, cb = fmaf(ml - mb, rinv, -mb2) * rinv2;
      uint2* dst = reinterpret_cast<uint2*>(S->h) + ((row >> 6) * 18 + ((lane >> 3) & 1)) * 512 + (row & 63) * 8 + ((lane & 7) ^ (row & 6));
#pragma unroll
      for (int j = 0; j < 9; j++)
        dst[1024 * j] = make_uint2(pack_bf16(fmaf(c[4 * j], ca, cb), fmaf(c[4 * j + 1], ca, cb)), pack_bf16(fmaf(c[4 * j + 2], ca, cb), fmaf(c[4 * j + 3], ca, cb)));
      const uint32_t rh = pack_bf16(rinv, rinv);
      if (!(lane & 15)) S->stats[row] = make_uint4(pack_bf16(mb, mb), rh, pack_bf16(rinv - bf_lo(rh), rinv - bf_lo(rh)), 0);
      __syncwarp();
      bar_arrive(2, 288);
    }
    asm volatile("setmaxnreg.inc.sync.aligned.u32 224;");
    asm volatile("barrier.cluster.wait.aligned;" ::: "memory");
    const int wg = warp >> 2, w = warp & 3, g = lane >> 2, t = lane & 3, wtid = tid & 127;
    const bool elect = wtid == 0;
    const uint64_t da0 = make_desc(sb + wg * 8192, 8192, 1024, 1);
    const uint32_t swz = ((lane >> 4) * 8 + (lane & 7)) * 128 + (((2 * w + ((lane >> 3) & 1)) ^ (lane & 7)) << 4);
    const uint32_t stg = sb + (wg ? SM_ST1 : SM_DED), ka0 = (8 * w + g + t + 1) * 4;
    uint32_t a[64];
    {
      auto mainloop = [&](auto&& mma) {
        Ring r{0, 0};
        uint32_t rel = 0;
#pragma unroll 1
        for (int kb = 0; kb < G1_KB; kb++, r.next()) {
          if (kb == G1_KB - G1_TAIL && wg) {
            wg_wait<0>();
            if (elect) mbar_arrive(rel);
            rel = 0;
            {
              mbar_wait(sb + B_MISC, 0);
              conv_lda_all(a, sb + SM_CV + 16384 + CV_K + ka0);
            }
            bar_sync(5, 256);
          }
          mbar_wait(sb + B_FULL + 8 * r.s, r.ph);
          if (kb == 0 && warp == 0) TLREC(3);
          wg_fence();
          mma(r.s * (SLOT >> 4), kb);
          wg_commit();
          if (kb == G1_KB - 1) break;
          wg_wait<1>();
          if (elect && rel) mbar_arrive(rel);
          rel = sb + B_EMPTY + 8 * r.s;
        }
        bar_arrive(5, 256);
        wg_wait<0>();
      };
      float hb[4];
      auto staged = [&](int second) {
        if (!w) TLREC(4 + wg);
        if (lane == 0) mbar_arrive(sb + B_G1DONE);
        mbar_wait(sb + B_MISC, 0);
#pragma unroll
        for (int i = 0; i < 4; i++) hb[i] = 0.5f * bf_lo(lds16(sb + SM_B1 + (warp * 16 + g + (i & 1) * 8 + (i >> 1) * second) * 2));
        mbar_wait(sb + B_KVDONE, 0);
        if (wg) mbar_wait(sb + B_G1DONE, 0);
      };
      if (R.at != 15) {
        const uint64_t db0 = make_desc(sb + 16384, 4096, 512, 2);
        float acc[80];
        mainloop([&](uint32_t o, int kb) {
#pragma unroll
          for (int k = 0; k < 4; k++) wgmma_ss_n160_t11(acc, da0 + o + k * 128, db0 + o + k * 64, k ? 1 : kb);
        });
        pin_regs<80>(acc);
        staged(0);
        gelu_stage<40>(acc, hb, stg + swz, 2, lane ? 0 : sb + B_STG + 8 * wg + 16);
      } else {
        const uint64_t db0 = make_desc(sb + 24576, 4096, 512, 2);
        float acc[96];
        auto block = [&](float* d, uint64_t da, uint64_t db, int kb) {
#pragma unroll
          for (int k = 0; k < 4; k++) wgmma_ss_n96_t11(d, da + k * 128, db + k * 64, k ? 1 : kb);
        };
        if (wg) mainloop([&](uint32_t o, int kb) { block(acc, da0 + o, db0 + o, kb); block(acc + 48, da0 + o + 512, db0 + o, kb); });
        else mainloop([&](uint32_t o, int kb) { block(acc, da0 + o, db0 + o, kb); });
        pin_regs<96>(acc);
        staged(64);
        gelu_stage<48>(acc, hb, stg + swz, 1 + wg, lane ? 0 : sb + B_STG + 8 * wg + 16);
      }
      __syncwarp();
      if (lane == 0) mbar_arrive(sb + B_STG + 8 * wg);
    }
    {
      if (!wg) conv_lda_all(a, sb + SM_CV + 16384 + wg * CV_K + ka0);
#pragma unroll 1
      for (int i = wg; i < R.ncv; i += 2) {
        const bool more = i + 2 < R.ncv;
        const uint32_t dd = lds16(sb + SM_D + (R.ch + i) * 2);
        a[0] = badd2(a[0], ka0 == 32 ? dd : 0); a[2] = badd2(a[2], ka0 == 16 ? dd : 0);
        float acc[128];
        mbar_wait(sb + B_UFULL + 8 * (i & 3), (i >> 2) & 1);
        bar_sync(5 + wg, 256);
        const bool last = i + 1 == R.ncv;
        if (last && elect) mbar_arrive(sb + B_EMPTY);
        if (!w && i < 4) TLREC(22 + i);
        wg_fence();
        conv_mma(acc, a, make_desc(sb + cv_in(i), 4096, 128, 0));
        wg_commit();
        if (!last) bar_arrive(5 + (wg ^ 1), 256);
        if (more) {
          mbar_wait(sb + B_SFREE + 8 * wg, (i >> 1) & 1);
          mbar_wait(sb + B_KFULL + 8 * ((i + 2) & 3), ((i + 2) >> 2) & 1);
        } else if (last) mbar_wait(sb + B_PDONE, 0);
        wg_wait<0>();
        pin_regs<128>(acc);
        if (lane == 0) mbar_arrive(sb + B_CEMPTY + 8 * (i & 3));
        if (last && elect) mbar_arrive(sb + B_EMPTY + 8);
        const uint32_t red = sb + cv_red(i, R.ncv), ka = sb + cv_taps(i + 2) + ka0;
        if (lane < 8 * w) sts32(red + w * CV_REDW + lane * 4, 0);
        const uint32_t wr = red + w * CV_REDW + (8 * (3 - t + w) + g) * 4;
        conv_drain(acc, wr, a, ka, more);
        __syncwarp();
        if (lane == 0) mbar_arrive(sb + B_STG + 8 * wg + (more ? 0 : 16));
      }
      if (!w) TLREC(20 + wg);
    }
    if (R.sg >= 0) {
      const int srow = R.sg * 64 + warp * 16;
      const uint64_t db0 = make_desc(sb + 16384, 16, 1024, 1);
      const uint32_t xo = sb + SM_CV + warp * 2304, xa = xo + (lane & 15) * 144;
      float acc[72];
      Ring r{G1_KB % NSTAGE, (G1_KB / NSTAGE) & 1};
      bar_sync(8, 256);
      uint32_t rel = 0;
#pragma unroll 1
      for (int kb = 0; kb < G2_KB; kb++, r.next()) {
        if (kb == G2_KB - G2_TAIL && wg) {
          wg_wait<0>();
          if (elect) mbar_arrive_remote(rel);
          rel = 0;
          bar_sync(7, 256);
        }
        mbar_wait(sb + B_FULL + 8 * r.s, r.ph);
        if (kb == 0 && !w) TLREC(17 + wg);
        if (kb == 8 && warp == 0) TLREC(26);
        if (kb == 20 && warp == 0) TLREC(8);
        if (kb == 27 && warp == 0) TLREC(30);
        const uint64_t da = da0 + r.s * (SLOT >> 4), db = db0 + r.s * (SLOT >> 4);
        wg_fence();
        wgmma_ss_n144_t10(acc, da, db, kb);
#pragma unroll
        for (int k = 1; k < 4; k++) wgmma_ss_n144_t10(acc, da + k * 128, db + k * 2, 1);
        wg_commit();
        if (kb == G2_KB - 1) break;
        wg_wait<1>();
        if (elect && rel) mbar_arrive_remote(rel);
        rel = kb == G2_KB - NSTAGE ? mapa(sb + B_XRDY, rank ^ 1) : sb + B_EMPTY + 8 * r.s;
      }
      if (!wg) bar_arrive(7, 256);
      const uint32_t xz = sb + XSLOT * SLOT + wg * 10240 + wtid * 16;
      const uint32_t rz = mapa(xz, rank ^ 1), rb = mapa(sb + B_XFULL + 16 * wg, rank ^ 1);
      mbar_wait(sb + B_XRDY, 0);
      wg_wait<0>();
      pin_regs<72>(acc);
      if (!w) TLREC(28 + wg);
#pragma unroll
      for (int i = 0; i < 32; i += 8)
        asm volatile("st.async.weak.shared::cluster.mbarrier::complete_tx::bytes.v4.b32 [%0], {%1,%2,%3,%4}, [%5];"
                     :: "r"(rz + i * 256), "r"(pack_bf16(acc[i], acc[i + 1])), "r"(pack_bf16(acc[i + 2], acc[i + 3])),
                        "r"(pack_bf16(acc[i + 4], acc[i + 5])), "r"(pack_bf16(acc[i + 6], acc[i + 7])), "r"(rb + (i < 8 * XP ? 0 : 8)) : "memory");
      asm volatile("st.async.weak.shared::cluster.mbarrier::complete_tx::bytes.v2.b32 [%0], {%1,%2}, [%3];"
                   :: "r"(rz + 8192), "r"(pack_bf16(acc[32], acc[33])), "r"(pack_bf16(acc[34], acc[35])), "r"(rb + 8) : "memory");
      uint32_t xx[18], ss[18];
      mbar_wait(sb + B_XY, 0);
      {
        const uint32_t ya = sb + SM_DED + wg * 9216 + swz;
        const uint4 st0 = lds128(sb + SM_ST + (warp * 16 + g) * 16), st1 = lds128(sb + SM_ST + (warp * 16 + g + 8) * 16);
        const float hb0 = 0.5f * bf_lo(lds16(sb + SM_B2 + (warp * 16 + g) * 2)), hb1 = 0.5f * bf_lo(lds16(sb + SM_B2 + (warp * 16 + g + 8) * 2));
#pragma unroll
        for (int q = 0; q < 8; q += 2) { ldsm4(xx + 2 * q, xa + (lane >> 4) * 16 + q * 16); ldsm4t(ss + 2 * q, ya + q * 1024); }
        ldsm2(xx + 16, xa + 128);
        ldsm2t(ss + 16, ya + 8 * 1024);
#pragma unroll
        for (int i = 0; i < 18; i++) {
          const uint4& st = (i & 1) ? st1 : st0;
          const uint32_t c = bsub2(xx[i], st.x);
          ss[i] = bmul2(bfma2(c, st.y, bmul2(c, st.z)), ss[i]);
        }
#pragma unroll
        for (int i = 36; i < 72; i++) acc[i] = fmaf(acc[i], 0.5f, (i & 2) ? hb1 : hb0);
      }
      char* const op = reinterpret_cast<char*>(P.out) + srow * (D_ * 2) + R.dk * 16 + lane * 16;
      uint32_t oo[5];
#pragma unroll
      for (int j = 0; j < 5; j++) oo[j] = ((lane + 32 * j) * 57 >> 9) * (D_ * 2 - 144) + j * 512;
#pragma unroll
      for (int q = 0; q < 5; q++) {
        if (q == 0 || q == XP) mbar_wait_cluster(sb + B_XFULL + 16 * wg + (q ? 8 : 0), 0);
        if (!w && !q) TLREC(9 + wg);
        const uint4 v = lds128(xz + q * 2048);
        const uint32_t pv[4] = {v.x, v.y, v.z, v.w};
#pragma unroll
        for (int i = 4 * q; i < 4 * q + 4 && i < 18; i++)
          xx[i] = bfma2(ss[i], pack_bf16(silu_half(fmaf(bf_lo(pv[i & 3]), 0.5f, acc[36 + 2 * i])), silu_half(fmaf(bf_hi(pv[i & 3]), 0.5f, acc[37 + 2 * i]))), xx[i]);
        if (q < 4) stsm4(xa + (lane >> 4) * 16 + q * 32, xx[4 * q], xx[4 * q + 1], xx[4 * q + 2], xx[4 * q + 3]);
        else stsm2(xa + 128, xx[16], xx[17]);
      }
      __syncwarp();
      if (lane == 0) mbar_arrive(sb + B_DONE);
#pragma unroll
      for (int j = 0; j < 5; j++)
        if (j < 4 || lane < 16) *reinterpret_cast<uint4*>(op + oo[j]) = lds128(xo + (lane + 32 * j) * 16);
      if (!w) TLREC(11 + wg);
    }
    TLEND();
  }
}

typedef CUresult (*EncodeFn)(CUtensorMap*, CUtensorMapDataType, cuuint32_t, void*, const cuuint64_t*, const cuuint64_t*, const cuuint32_t*,
                             const cuuint32_t*, CUtensorMapInterleave, CUtensorMapSwizzle, CUtensorMapL2promotion, CUtensorMapFloatOOBfill);

void make_map(EncodeFn fn, CUtensorMap* m, const void* ptr, int rank, const cuuint64_t* dims, const cuuint64_t* strides, const cuuint32_t* box,
              CUtensorMapSwizzle sw) {
  const cuuint32_t es[3] = {1, 1, 1};
  fn(m, CU_TENSOR_MAP_DATA_TYPE_BFLOAT16, rank, const_cast<void*>(ptr), dims, strides, box, es, CU_TENSOR_MAP_INTERLEAVE_NONE, sw,
     CU_TENSOR_MAP_L2_PROMOTION_L2_256B, CU_TENSOR_MAP_FLOAT_OOB_FILL_NONE);
}

void make_roles(Role* R) {
  int nl = 0, ch = 0;
  for (int gi = 0; gi < 8; gi++)
    for (int b = 0; b < 132; b++) {
      const int c = b >> 1, rank = b & 1;
      int g, idx;
      if (c < 4) { g = 0; idx = 4 + c; }
      else if (c < 36) { g = (c - 4) & 7; idx = (c - 4) >> 3; }
      else if (c < 64) { g = 1 + (c - 36) % 7; idx = 4 + (c - 36) / 7; }
      else { g = c - 58; idx = 8; }
      if (g != gi) continue;
      Role& r = R[b];
      r.sg = (int8_t)(idx < 8 ? 2 * (2 * g + (idx >> 2)) : -1);
      r.dk = (int8_t)((idx & 3) * 18 + rank * 9);
      r.ds = (int8_t)((idx & 3) * 18 + (rank ^ 1) * 9);
      if (idx < (g < 2 ? 6 : 7)) {
        const int c1 = (g < 2 ? 6 * g : 7 * g - 2) + idx;
        r.fg = (int8_t)((2 * (c1 / 3) + rank) * 2); r.at = (int8_t)(c1 % 3 * 5); r.ncv = NCV_REG;
      } else {
        r.fg = (int8_t)(3 * nl++); r.at = 15; r.ncv = idx < 8 ? NCV_LEFT : NCV_LONG;
      }
      r.ch = (int16_t)ch;
      ch += r.ncv;
    }
}

}

extern "C" void kernel_launch(void* const* d_in, const int* in_sizes, int n_in, void* d_out, int out_size) {
  static Params P;
  static Hot H;
  static const void* cached[5] = {nullptr, nullptr, nullptr, nullptr, nullptr};
  const void* now[5] = {d_in[0], d_in[1], d_in[2], d_in[7], d_in[9]};
  bool same = true;
  for (int i = 0; i < 5; i++) { same = same && cached[i] == now[i]; cached[i] = now[i]; }
  if (!same) {
    void* fp = nullptr;
    cudaDriverEntryPointQueryResult qr;
    cudaGetDriverEntryPoint("cuTensorMapEncodeTiled", &fp, cudaEnableDefault, &qr);
    EncodeFn fn = (EncodeFn)fp;
    void* ps;
    cudaGetSymbolAddress(&ps, g_scratch);
    H.S = (Scratch*)ps;
    const void *py = (char*)ps + offsetof(Scratch, y), *pb = (char*)ps + offsetof(Scratch, ub);
    { cuuint64_t d[3] = {64, S_, F_ / 64}, s[2] = {F_ * 2, 128}; cuuint32_t b[3] = {64, 64, 2}; make_map(fn, &P.m_w1, d_in[7], 3, d, s, b, CU_TENSOR_MAP_SWIZZLE_128B);
      b[2] = 3; make_map(fn, &P.m_w1l, d_in[7], 3, d, s, b, CU_TENSOR_MAP_SWIZZLE_128B); }
    { cuuint64_t d[3] = {64, F_, S_ / 64}, s[2] = {S_ * 2, 128}; cuuint32_t b[3] = {64, 64, 2}; make_map(fn, &P.m_w2, d_in[9], 3, d, s, b, CU_TENSOR_MAP_SWIZZLE_128B); }
    { cuuint64_t d[2] = {D_, S_}, s[1] = {D_ * 2}; cuuint32_t b[2] = {72, 16}; make_map(fn, &P.m_x, d_in[0], 2, d, s, b, CU_TENSOR_MAP_SWIZZLE_NONE);
      b[0] = 96; b[1] = 20; make_map(fn, &P.m_k, d_in[1], 2, d, s, b, CU_TENSOR_MAP_SWIZZLE_NONE);
      b[1] = 17; make_map(fn, &P.m_v, d_in[2], 2, d, s, b, CU_TENSOR_MAP_SWIZZLE_NONE); }
    { cuuint64_t d[3] = {64, D_, S_ / 64}, s[2] = {S_ * 2, 128}; cuuint32_t b[3] = {64, 72, 2}; make_map(fn, &P.m_y, py, 3, d, s, b, CU_TENSOR_MAP_SWIZZLE_128B); }
    { cuuint64_t d[3] = {2048, D_ / 2, 4}, s[2] = {16384, 4096}; cuuint32_t b[3] = {16, 48, 2}; make_map(fn, &P.m_ub, pb, 3, d, s, b, CU_TENSOR_MAP_SWIZZLE_32B); }
    make_roles(P.role);
    cudaFuncSetAttribute(fused_kernel, cudaFuncAttributeMaxDynamicSharedMemorySize, SM_TOTAL);
  }
  H.x = (const __nv_bfloat16*)d_in[0];
  H.shift_k = (const __nv_bfloat16*)d_in[3]; H.ssm_k = (const __nv_bfloat16*)d_in[4]; H.ssm_D = (const __nv_bfloat16*)d_in[5];
  H.b1 = (const __nv_bfloat16*)d_in[8]; P.b2 = (const __nv_bfloat16*)d_in[10]; P.out = (__nv_bfloat16*)d_out;
  fused_kernel<<<132, 384, SM_TOTAL>>>(H, P);
}
```

```cpp
#include <cuda_runtime.h>
#include <cuda.h>
#include <cuda_bf16.h>
#include <stddef.h>
#include <stdint.h>

namespace {

constexpr int S_ = 2048, D_ = 576, F_ = 4608;
constexpr int NSTAGE = 5, SLOT = 36864;
constexpr int G1_KB = 32, G2_KB = 36;
constexpr int G1_BYTES = 36864, G2_BYTES = 16384 + 18432;
#define NCV_LEFT 4
constexpr int NCV_REG = 4, NCV_LONG = (D_ - 108 * NCV_REG - 20 * NCV_LEFT) / 4;
static_assert(108 * NCV_REG + 20 * NCV_LEFT + 4 * NCV_LONG == D_, "conv split");
constexpr int KV_ROUNDS = 6;
#define XP 2
#define TUNED(name, idx, val) constexpr int name = val
constexpr int G1_TAIL = 4, G2_TAIL = 3;
constexpr int KV0 = 5;

constexpr int CV_K = 4224, CV_REDW = 2112 * 2;
constexpr int SM_DED = NSTAGE * SLOT;
constexpr int SM_CV = SM_DED + 20480;
constexpr int SM_ST1 = 0;
constexpr int SM_ST = SM_CV + 18432, SM_B2 = SM_ST + 2048;
constexpr int SM_B1 = SM_CV + 2 * (8192 + CV_K), SM_D = SM_B1 + 384;
constexpr int SM_BAR = SM_D + 1152;
constexpr int SM_TOTAL = SM_BAR + 768;
static_assert(G1_KB % NSTAGE == 2, "slots 0 and 1 hold the last GEMM1 k-blocks and the last two of the first GEMM2 stages");
static_assert(NCV_REG == 4 && NCV_LEFT == 4 && NCV_LONG % 4 == 0, "the last two channels use buffers 2 and 3");
constexpr int XSLOT = (G1_KB + G2_KB) % NSTAGE;
__device__ __forceinline__ uint32_t kv_buf(int q) { return q == 2 ? SM_DED : SM_CV + q * 8192; }
__device__ __forceinline__ uint32_t cv_red(int i, int n) { return i + 2 == n ? SM_CV : (i & 1) && i + 1 < n ? SLOT + 16384 : SM_DED; }
__device__ __forceinline__ uint32_t cv_in(int i) { return (i & 2 ? SLOT : SM_CV) + (i & 1) * 8192; }
__device__ __forceinline__ uint32_t cv_taps(int i) { return (i & 2 ? SM_ST1 + 24576 : SM_CV + 16384) + (i & 1) * CV_K; }
constexpr int bar_at(int i) { return SM_BAR + 8 * i; }
constexpr int B_FULL = bar_at(0)  , B_KFULL = bar_at(5)  , B_UFULL = bar_at(9)  , B_KVDONE = bar_at(13), B_STORED = bar_at(14)  ,
              B_XFULL = bar_at(16)  , B_XY = bar_at(20), B_MISC = bar_at(21),
              B_EMPTY = bar_at(22)  , B_XRDY = bar_at(27),
              B_SFREE = bar_at(28)  , B_PDONE = bar_at(30),
              B_CEMPTY = bar_at(31)  , B_STG = bar_at(35)  ,
              B_G1DONE = bar_at(39), B_DONE = bar_at(40);
constexpr int C_H = 0, C_KV = 1, C_U = 2  , C_Y = 4, C_SYNC = 5, C_EPOCH = 6, C_COUNT = 7;
constexpr uint32_t EPOCH = 128 * 33;

struct Scratch {
  uint32_t cnt[C_COUNT * 32];
  alignas(1024) uint4 stats[S_];
  alignas(1024) __nv_bfloat16 h[S_ * D_];
  alignas(1024) __nv_bfloat16 ub[D_ * 4096];
  alignas(1024) __nv_bfloat16 y[D_ * S_];
  alignas(1024) __nv_bfloat16 u[D_ * F_];
};
__device__ Scratch g_scratch;

struct Hot {
  const __nv_bfloat16 *x, *shift_k, *ssm_k, *ssm_D, *b1;
  Scratch* S;
};
struct Role {
  int8_t fg;
  int8_t at;
  int8_t sg;
  int8_t dk, ds;
  int8_t ncv;
  int16_t ch;
};
struct Params {
  const __nv_bfloat16* b2;
  __nv_bfloat16* out;
  Role role[132];
  CUtensorMap m_w1, m_w1l, m_w2, m_x, m_y, m_k, m_v, m_ub;
};

#define TLREC(i) do { } while (0)
#define TLEND() do { } while (0)

__device__ __forceinline__ uint32_t smem_u32(const void* p) { return (uint32_t)__cvta_generic_to_shared(p); }
__device__ __forceinline__ void mbar_init(uint32_t bar, uint32_t cnt) { asm volatile("mbarrier.init.shared::cta.b64 [%0], %1;" :: "r"(bar), "r"(cnt) : "memory"); }
__device__ __forceinline__ void mbar_expect_tx(uint32_t bar, uint32_t bytes) { asm volatile("mbarrier.arrive.expect_tx.shared::cta.b64 _, [%0], %1;" :: "r"(bar), "r"(bytes) : "memory"); }
__device__ __forceinline__ void mbar_arrive(uint32_t bar) { asm volatile("mbarrier.arrive.shared::cta.b64 _, [%0];" :: "r"(bar) : "memory"); }
__device__ __forceinline__ uint32_t mapa(uint32_t addr, uint32_t cta) { uint32_t r; asm volatile("mapa.shared::cluster.u32 %0, %1, %2;" : "=r"(r) : "r"(addr), "r"(cta)); return r; }
__device__ __forceinline__ void mbar_arrive_remote(uint32_t rbar) { asm volatile("mbarrier.arrive.shared::cluster.b64 _, [%0];" :: "r"(rbar) : "memory"); }
__device__ __forceinline__ uint32_t clk() { uint32_t c; asm volatile("mov.u32 %0, %%clock;" : "=r"(c)); return c; }
__device__ __forceinline__ bool elect_one() {
  uint32_t p; asm volatile("{ .reg .pred p; elect.sync _|p, 0xffffffff; selp.u32 %0, 1, 0, p; }" : "=r"(p)); return p;
}
__device__ __forceinline__ void guard(uint32_t t0) { if ((int32_t)(clk() - t0) < 0) __trap(); }
__device__ __forceinline__ void mbar_wait(uint32_t bar, uint32_t parity) {
  asm volatile("{\n .reg .pred p;\n W_%=:\n mbarrier.try_wait.parity.shared::cta.b64 p, [%0], %1;\n @!p bra W_%=;\n }" :: "r"(bar), "r"(parity) : "memory");
}
__device__ __forceinline__ void mbar_wait_cluster(uint32_t bar, uint32_t parity) {
  asm volatile("{\n .reg .pred p;\n W_%=:\n mbarrier.try_wait.parity.acquire.cluster.shared::cta.b64 p, [%0], %1;\n @!p bra W_%=;\n }" :: "r"(bar), "r"(parity) : "memory");
}
__device__ __forceinline__ bool mbar_try(uint32_t bar, uint32_t parity) {
  uint32_t ok;
  asm volatile("{ .reg .pred p; mbarrier.try_wait.parity.shared::cta.b64 p, [%1], %2, 100000; selp.u32 %0, 1, 0, p; }" : "=r"(ok) : "r"(bar), "r"(parity) : "memory");
  return ok;
}
__device__ __forceinline__ bool mbar_test(uint32_t bar, uint32_t parity) {
  uint32_t ok;
  asm volatile("{ .reg .pred p; mbarrier.test_wait.parity.shared::cta.b64 p, [%1], %2; selp.u32 %0, 1, 0, p; }" : "=r"(ok) : "r"(bar), "r"(parity) : "memory");
  return ok;
}
__device__ __forceinline__ void mbar_wait_guarded(uint32_t bar, uint32_t t0, uint32_t parity = 0) { while (!mbar_try(bar, parity)) guard(t0); }
__device__ __forceinline__ void tma2d(uint32_t dst, const CUtensorMap* m, int c0, int c1, uint32_t bar) {
  asm volatile("cp.async.bulk.tensor.2d.shared::cluster.global.mbarrier::complete_tx::bytes [%0], [%1, {%3, %4}], [%2];"
               :: "r"(dst), "l"(m), "r"(bar), "r"(c0), "r"(c1) : "memory");
}
__device__ __forceinline__ void tma3d(uint32_t dst, const CUtensorMap* m, int c0, int c1, int c2, uint32_t bar) {
  asm volatile("cp.async.bulk.tensor.3d.shared::cluster.global.mbarrier::complete_tx::bytes [%0], [%1, {%3, %4, %5}], [%2];"
               :: "r"(dst), "l"(m), "r"(bar), "r"(c0), "r"(c1), "r"(c2) : "memory");
}
__device__ __forceinline__ void bulk_store(void* dst, uint32_t src, uint32_t bytes) {
  asm volatile("cp.async.bulk.global.shared::cta.bulk_group [%0], [%1], %2;" :: "l"(dst), "r"(src), "r"(bytes) : "memory");
}
__device__ __forceinline__ void bulk_load(uint32_t dst, const void* src, uint32_t bytes, uint32_t bar) {
  asm volatile("cp.async.bulk.shared::cluster.global.mbarrier::complete_tx::bytes [%0], [%1], %2, [%3];" :: "r"(dst), "l"(src), "r"(bytes), "r"(bar) : "memory");
}
__device__ __forceinline__ void tma3d_store(const CUtensorMap* m, uint32_t src, int c0, int c1, int c2) {
  asm volatile("cp.async.bulk.tensor.3d.global.shared::cta.bulk_group [%0, {%2, %3, %4}], [%1];" :: "l"(m), "r"(src), "r"(c0), "r"(c1), "r"(c2) : "memory");
}
__device__ __forceinline__ void bulk_commit() { asm volatile("cp.async.bulk.commit_group;" ::: "memory"); }
__device__ __forceinline__ void bulk_wait_all() { asm volatile("cp.async.bulk.wait_group 0;" ::: "memory"); }
__device__ __forceinline__ void fence_async_smem() { asm volatile("fence.proxy.async.shared::cta;" ::: "memory"); }
__device__ __forceinline__ void fence_async_global() { asm volatile("fence.proxy.async.global;" ::: "memory"); }
__device__ __forceinline__ uint32_t ld_cnt(Scratch* S, int c) { uint32_t v; asm volatile("ld.relaxed.gpu.global.u32 %0, [%1];" : "=r"(v) : "l"(S->cnt + c * 32) : "memory"); return v; }
__device__ __forceinline__ void signal(Scratch* S, int c, uint32_t inc) { asm volatile("red.release.gpu.global.add.u32 [%0], %1;" :: "l"(S->cnt + c * 32), "r"(inc) : "memory"); }
__device__ __forceinline__ bool reached(Scratch* S, int c, uint32_t ep) { return ld_cnt(S, c) - ep >= EPOCH; }
__device__ __forceinline__ void await(Scratch* S, int c, uint32_t ep) { while (!reached(S, c, ep)) { } }
__device__ __forceinline__ void bar_sync(int id, int n) { asm volatile("bar.sync %0, %1;" :: "r"(id), "r"(n) : "memory"); }
__device__ __forceinline__ void bar_arrive(int id, int n) { asm volatile("bar.arrive %0, %1;" :: "r"(id), "r"(n) : "memory"); }
__device__ __forceinline__ void wg_fence() { asm volatile("wgmma.fence.sync.aligned;" ::: "memory"); }
__device__ __forceinline__ void wg_commit() { asm volatile("wgmma.commit_group.sync.aligned;" ::: "memory"); }
template <int N> __device__ __forceinline__ void wg_wait() { asm volatile("wgmma.wait_group.sync.aligned %0;" :: "n"(N) : "memory"); }
template <int N> __device__ __forceinline__ void pin_regs(float* a) {
#pragma unroll
  for (int i = 0; i < N; i++) asm volatile("" : "+f"(a[i]) :: "memory");
}
__device__ __forceinline__ uint64_t make_desc(uint32_t addr, uint32_t lbo, uint32_t sbo, uint32_t swz) {
  return (uint64_t)((addr & 0x3FFFF) >> 4) | ((uint64_t)(lbo >> 4) << 16) | ((uint64_t)(sbo >> 4) << 32) | ((uint64_t)swz << 62);
}
__device__ __forceinline__ uint32_t pack_bf16(float lo, float hi) { uint32_t r; asm("cvt.rn.bf16x2.f32 %0, %1, %2;" : "=r"(r) : "f"(hi), "f"(lo)); return r; }
__device__ __forceinline__ float bf_lo(uint32_t p) { return __uint_as_float(p << 16); }
__device__ __forceinline__ float bf_hi(uint32_t p) { return __uint_as_float(p & 0xffff0000u); }
__device__ __forceinline__ float round_bf16(float v) { return bf_lo(pack_bf16(v, 0.f)); }
__device__ __forceinline__ uint32_t bmul2(uint32_t a, uint32_t b) { uint32_t r; asm("mul.rn.bf16x2 %0, %1, %2;" : "=r"(r) : "r"(a), "r"(b)); return r; }
__device__ __forceinline__ uint32_t badd2(uint32_t a, uint32_t b) { uint32_t r; asm("add.rn.bf16x2 %0, %1, %2;" : "=r"(r) : "r"(a), "r"(b)); return r; }
__device__ __forceinline__ uint32_t bfma2(uint32_t a, uint32_t b, uint32_t c) { uint32_t r; asm("fma.rn.bf16x2 %0, %1, %2, %3;" : "=r"(r) : "r"(a), "r"(b), "r"(c)); return r; }
__device__ __forceinline__ uint32_t bsub2(uint32_t a, uint32_t b) { uint32_t r; asm("sub.rn.bf16x2 %0, %1, %2;" : "=r"(r) : "r"(a), "r"(b)); return r; }
__device__ __forceinline__ float tanh_fast(float v) { float r; asm("tanh.approx.f32 %0, %1;" : "=f"(r) : "f"(v)); return r; }
__device__ __forceinline__ float gelu_half(float h) {
  return fmaf(h, tanh_fast(h * fmaf(h * h, 8.0f * 0.7978845608028654f * 0.044715f, 2.0f * 0.7978845608028654f)), h);
}
__device__ __forceinline__ float silu_half(float h) { return fmaf(h, tanh_fast(h), h); }
__device__ __forceinline__ uint32_t ldg32(const void* p) { uint32_t v; asm volatile("ld.global.u32 %0, [%1];" : "=r"(v) : "l"(p) : "memory"); return v; }
__device__ __forceinline__ uint32_t lds32(uint32_t a) { uint32_t v; asm volatile("ld.shared.u32 %0, [%1];" : "=r"(v) : "r"(a) : "memory"); return v; }
__device__ __forceinline__ uint32_t lds16(uint32_t a) { uint32_t v; asm volatile("ld.shared.u16 %0, [%1];" : "=r"(v) : "r"(a) : "memory"); return v; }
__device__ __forceinline__ uint4 lds128(uint32_t a) { uint4 v; asm volatile("ld.shared.v4.u32 {%0,%1,%2,%3}, [%4];" : "=r"(v.x), "=r"(v.y), "=r"(v.z), "=r"(v.w) : "r"(a) : "memory"); return v; }
__device__ __forceinline__ void sts128(uint32_t a, uint32_t x, uint32_t y, uint32_t z, uint32_t w) {
  asm volatile("st.shared.v4.u32 [%0], {%1,%2,%3,%4};" :: "r"(a), "r"(x), "r"(y), "r"(z), "r"(w) : "memory");
}
__device__ __forceinline__ void sts32(uint32_t a, uint32_t v) { asm volatile("st.shared.u32 [%0], %1;" :: "r"(a), "r"(v) : "memory"); }
__device__ __forceinline__ void ldsm4(uint32_t* r, uint32_t a) {
  asm volatile("ldmatrix.sync.aligned.m8n8.x4.shared.b16 {%0,%1,%2,%3}, [%4];" : "=r"(r[0]), "=r"(r[1]), "=r"(r[2]), "=r"(r[3]) : "r"(a) : "memory");
}
__device__ __forceinline__ void ldsm2(uint32_t* r, uint32_t a) {
  asm volatile("ldmatrix.sync.aligned.m8n8.x2.shared.b16 {%0,%1}, [%2];" : "=r"(r[0]), "=r"(r[1]) : "r"(a) : "memory");
}
__device__ __forceinline__ void ldsm4t(uint32_t* r, uint32_t a) {
  asm volatile("ldmatrix.sync.aligned.m8n8.x4.trans.shared.b16 {%0,%1,%2,%3}, [%4];" : "=r"(r[0]), "=r"(r[1]), "=r"(r[2]), "=r"(r[3]) : "r"(a) : "memory");
}
__device__ __forceinline__ void ldsm2t(uint32_t* r, uint32_t a) {
  asm volatile("ldmatrix.sync.aligned.m8n8.x2.trans.shared.b16 {%0,%1}, [%2];" : "=r"(r[0]), "=r"(r[1]) : "r"(a) : "memory");
}
__device__ __forceinline__ void stsm4(uint32_t a, uint32_t r0, uint32_t r1, uint32_t r2, uint32_t r3) {
  asm volatile("stmatrix.sync.aligned.m8n8.x4.shared.b16 [%0], {%1,%2,%3,%4};" :: "r"(a), "r"(r0), "r"(r1), "r"(r2), "r"(r3) : "memory");
}
__device__ __forceinline__ void stsm2(uint32_t a, uint32_t r0, uint32_t r1) {
  asm volatile("stmatrix.sync.aligned.m8n8.x2.shared.b16 [%0], {%1,%2};" :: "r"(a), "r"(r0), "r"(r1) : "memory");
}
__device__ __forceinline__ void stsm4t(uint32_t a, uint32_t r0, uint32_t r1, uint32_t r2, uint32_t r3) {
  asm volatile("stmatrix.sync.aligned.m8n8.x4.trans.shared.b16 [%0], {%1,%2,%3,%4};" :: "r"(a), "r"(r0), "r"(r1), "r"(r2), "r"(r3) : "memory");
}

__device__ __forceinline__ void wgmma_ss_n144_t10(float* d, uint64_t da, uint64_t db, int sd) {
  asm volatile("{ .reg .pred p; setp.ne.b32 p, %74, 0;\n"
      "wgmma.mma_async.sync.aligned.m64n144k16.f32.bf16.bf16 {"
      "%0,%1,%2,%3,%4,%5,%6,%7,%8,%9,%10,%11,%12,%13,%14,%15,"
      "%16,%17,%18,%19,%20,%21,%22,%23,%24,%25,%26,%27,%28,%29,%30,%31,"
      "%32,%33,%34,%35,%36,%37,%38,%39,%40,%41,%42,%43,%44,%45,%46,%47,"
      "%48,%49,%50,%51,%52,%53,%54,%55,%56,%57,%58,%59,%60,%61,%62,%63,"
      "%64,%65,%66,%67,%68,%69,%70,%71"
      "}, %72, %73, p, 1, 1, 1, 0; }"
    : "+f"(d[0]), "+f"(d[1]), "+f"(d[2]), "+f"(d[3]), "+f"(d[4]), "+f"(d[5]), "+f"(d[6]), "+f"(d[7]),
      "+f"(d[8]), "+f"(d[9]), "+f"(d[10]), "+f"(d[11]), "+f"(d[12]), "+f"(d[13]), "+f"(d[14]), "+f"(d[15]),
      "+f"(d[16]), "+f"(d[17]), "+f"(d[18]), "+f"(d[19]), "+f"(d[20]), "+f"(d[21]), "+f"(d[22]), "+f"(d[23]),
      "+f"(d[24]), "+f"(d[25]), "+f"(d[26]), "+f"(d[27]), "+f"(d[28]), "+f"(d[29]), "+f"(d[30]), "+f"(d[31]),
      "+f"(d[32]), "+f"(d[33]), "+f"(d[34]), "+f"(d[35]), "+f"(d[36]), "+f"(d[37]), "+f"(d[38]), "+f"(d[39]),
      "+f"(d[40]), "+f"(d[41]), "+f"(d[42]), "+f"(d[43]), "+f"(d[44]), "+f"(d[45]), "+f"(d[46]), "+f"(d[47]),
      "+f"(d[48]), "+f"(d[49]), "+f"(d[50]), "+f"(d[51]), "+f"(d[52]), "+f"(d[53]), "+f"(d[54]), "+f"(d[55]),
      "+f"(d[56]), "+f"(d[57]), "+f"(d[58]), "+f"(d[59]), "+f"(d[60]), "+f"(d[61]), "+f"(d[62]), "+f"(d[63]),
      "+f"(d[64]), "+f"(d[65]), "+f"(d[66]), "+f"(d[67]), "+f"(d[68]), "+f"(d[69]), "+f"(d[70]), "+f"(d[71])
    : "l"(da), "l"(db), "r"(sd));
}

__device__ __forceinline__ void wgmma_ss_n160_t11(float* d, uint64_t da, uint64_t db, int sd) {
  asm volatile("{ .reg .pred p; setp.ne.b32 p, %82, 0;\n"
      "wgmma.mma_async.sync.aligned.m64n160k16.f32.bf16.bf16 {"
      "%0,%1,%2,%3,%4,%5,%6,%7,%8,%9,%10,%11,%12,%13,%14,%15,"
      "%16,%17,%18,%19,%20,%21,%22,%23,%24,%25,%26,%27,%28,%29,%30,%31,"
      "%32,%33,%34,%35,%36,%37,%38,%39,%40,%41,%42,%43,%44,%45,%46,%47,"
      "%48,%49,%50,%51,%52,%53,%54,%55,%56,%57,%58,%59,%60,%61,%62,%63,"
      "%64,%65,%66,%67,%68,%69,%70,%71,%72,%73,%74,%75,%76,%77,%78,%79"
      "}, %80, %81, p, 1, 1, 1, 1; }"
    : "+f"(d[0]), "+f"(d[1]), "+f"(d[2]), "+f"(d[3]), "+f"(d[4]), "+f"(d[5]), "+f"(d[6]), "+f"(d[7]),
      "+f"(d[8]), "+f"(d[9]), "+f"(d[10]), "+f"(d[11]), "+f"(d[12]), "+f"(d[13]), "+f"(d[14]), "+f"(d[15]),
      "+f"(d[16]), "+f"(d[17]), "+f"(d[18]), "+f"(d[19]), "+f"(d[20]), "+f"(d[21]), "+f"(d[22]), "+f"(d[23]),
      "+f"(d[24]), "+f"(d[25]), "+f"(d[26]), "+f"(d[27]), "+f"(d[28]), "+f"(d[29]), "+f"(d[30]), "+f"(d[31]),
      "+f"(d[32]), "+f"(d[33]), "+f"(d[34]), "+f"(d[35]), "+f"(d[36]), "+f"(d[37]), "+f"(d[38]), "+f"(d[39]),
      "+f"(d[40]), "+f"(d[41]), "+f"(d[42]), "+f"(d[43]), "+f"(d[44]), "+f"(d[45]), "+f"(d[46]), "+f"(d[47]),
      "+f"(d[48]), "+f"(d[49]), "+f"(d[50]), "+f"(d[51]), "+f"(d[52]), "+f"(d[53]), "+f"(d[54]), "+f"(d[55]),
      "+f"(d[56]), "+f"(d[57]), "+f"(d[58]), "+f"(d[59]), "+f"(d[60]), "+f"(d[61]), "+f"(d[62]), "+f"(d[63]),
      "+f"(d[64]), "+f"(d[65]), "+f"(d[66]), "+f"(d[67]), "+f"(d[68]), "+f"(d[69]), "+f"(d[70]), "+f"(d[71]),
      "+f"(d[72]), "+f"(d[73]), "+f"(d[74]), "+f"(d[75]), "+f"(d[76]), "+f"(d[77]), "+f"(d[78]), "+f"(d[79])
    : "l"(da), "l"(db), "r"(sd));
}

__device__ __forceinline__ void wgmma_ss_n96_t11(float* d, uint64_t da, uint64_t db, int sd) {
  asm volatile("{ .reg .pred p; setp.ne.b32 p, %50, 0;\n"
      "wgmma.mma_async.sync.aligned.m64n96k16.f32.bf16.bf16 {"
      "%0,%1,%2,%3,%4,%5,%6,%7,%8,%9,%10,%11,%12,%13,%14,%15,"
      "%16,%17,%18,%19,%20,%21,%22,%23,%24,%25,%26,%27,%28,%29,%30,%31,"
      "%32,%33,%34,%35,%36,%37,%38,%39,%40,%41,%42,%43,%44,%45,%46,%47"
      "}, %48, %49, p, 1, 1, 1, 1; }"
    : "+f"(d[0]), "+f"(d[1]), "+f"(d[2]), "+f"(d[3]), "+f"(d[4]), "+f"(d[5]), "+f"(d[6]), "+f"(d[7]),
      "+f"(d[8]), "+f"(d[9]), "+f"(d[10]), "+f"(d[11]), "+f"(d[12]), "+f"(d[13]), "+f"(d[14]), "+f"(d[15]),
      "+f"(d[16]), "+f"(d[17]), "+f"(d[18]), "+f"(d[19]), "+f"(d[20]), "+f"(d[21]), "+f"(d[22]), "+f"(d[23]),
      "+f"(d[24]), "+f"(d[25]), "+f"(d[26]), "+f"(d[27]), "+f"(d[28]), "+f"(d[29]), "+f"(d[30]), "+f"(d[31]),
      "+f"(d[32]), "+f"(d[33]), "+f"(d[34]), "+f"(d[35]), "+f"(d[36]), "+f"(d[37]), "+f"(d[38]), "+f"(d[39]),
      "+f"(d[40]), "+f"(d[41]), "+f"(d[42]), "+f"(d[43]), "+f"(d[44]), "+f"(d[45]), "+f"(d[46]), "+f"(d[47])
    : "l"(da), "l"(db), "r"(sd));
}

__device__ __forceinline__ void wgmma_rs_n16(float* d, const uint32_t* a, uint64_t db, int sd) {
  asm volatile("{ .reg .pred p; setp.ne.b32 p, %13, 0;\n"
      "wgmma.mma_async.sync.aligned.m64n16k16.f32.bf16.bf16 {"
      "%0,%1,%2,%3,%4,%5,%6,%7"
      "}, {%8,%9,%10,%11}, %12, p, 1, 1, 0; }"
    : "+f"(d[0]), "+f"(d[1]), "+f"(d[2]), "+f"(d[3]), "+f"(d[4]), "+f"(d[5]), "+f"(d[6]), "+f"(d[7])
    : "r"(a[0]), "r"(a[1]), "r"(a[2]), "r"(a[3]), "l"(db), "r"(sd));
}

__device__ __forceinline__ void wgmma_rs_n32(float* d, const uint32_t* a, uint64_t db, int sd) {
  asm volatile("{ .reg .pred p; setp.ne.b32 p, %21, 0;\n"
      "wgmma.mma_async.sync.aligned.m64n32k16.f32.bf16.bf16 {"
      "%0,%1,%2,%3,%4,%5,%6,%7,%8,%9,%10,%11,%12,%13,%14,%15"
      "}, {%16,%17,%18,%19}, %20, p, 1, 1, 0; }"
    : "+f"(d[0]), "+f"(d[1]), "+f"(d[2]), "+f"(d[3]), "+f"(d[4]), "+f"(d[5]), "+f"(d[6]), "+f"(d[7]),
      "+f"(d[8]), "+f"(d[9]), "+f"(d[10]), "+f"(d[11]), "+f"(d[12]), "+f"(d[13]), "+f"(d[14]), "+f"(d[15])
    : "r"(a[0]), "r"(a[1]), "r"(a[2]), "r"(a[3]), "l"(db), "r"(sd));
}

__device__ __forceinline__ void wgmma_rs_n48(float* d, const uint32_t* a, uint64_t db, int sd) {
  asm volatile("{ .reg .pred p; setp.ne.b32 p, %29, 0;\n"
      "wgmma.mma_async.sync.aligned.m64n48k16.f32.bf16.bf16 {"
      "%0,%1,%2,%3,%4,%5,%6,%7,%8,%9,%10,%11,%12,%13,%14,%15,"
      "%16,%17,%18,%19,%20,%21,%22,%23"
      "}, {%24,%25,%26,%27}, %28, p, 1, 1, 0; }"
    : "+f"(d[0]), "+f"(d[1]), "+f"(d[2]), "+f"(d[3]), "+f"(d[4]), "+f"(d[5]), "+f"(d[6]), "+f"(d[7]),
      "+f"(d[8]), "+f"(d[9]), "+f"(d[10]), "+f"(d[11]), "+f"(d[12]), "+f"(d[13]), "+f"(d[14]), "+f"(d[15]),
      "+f"(d[16]), "+f"(d[17]), "+f"(d[18]), "+f"(d[19]), "+f"(d[20]), "+f"(d[21]), "+f"(d[22]), "+f"(d[23])
    : "r"(a[0]), "r"(a[1]), "r"(a[2]), "r"(a[3]), "l"(db), "r"(sd));
}

__device__ __forceinline__ void wgmma_rs_n64(float* d, const uint32_t* a, uint64_t db, int sd) {
  asm volatile("{ .reg .pred p; setp.ne.b32 p, %37, 0;\n"
      "wgmma.mma_async.sync.aligned.m64n64k16.f32.bf16.bf16 {"
      "%0,%1,%2,%3,%4,%5,%6,%7,%8,%9,%10,%11,%12,%13,%14,%15,"
      "%16,%17,%18,%19,%20,%21,%22,%23,%24,%25,%26,%27,%28,%29,%30,%31"
      "}, {%32,%33,%34,%35}, %36, p, 1, 1, 0; }"
    : "+f"(d[0]), "+f"(d[1]), "+f"(d[2]), "+f"(d[3]), "+f"(d[4]), "+f"(d[5]), "+f"(d[6]), "+f"(d[7]),
      "+f"(d[8]), "+f"(d[9]), "+f"(d[10]), "+f"(d[11]), "+f"(d[12]), "+f"(d[13]), "+f"(d[14]), "+f"(d[15]),
      "+f"(d[16]), "+f"(d[17]), "+f"(d[18]), "+f"(d[19]), "+f"(d[20]), "+f"(d[21]), "+f"(d[22]), "+f"(d[23]),
      "+f"(d[24]), "+f"(d[25]), "+f"(d[26]), "+f"(d[27]), "+f"(d[28]), "+f"(d[29]), "+f"(d[30]), "+f"(d[31])
    : "r"(a[0]), "r"(a[1]), "r"(a[2]), "r"(a[3]), "l"(db), "r"(sd));
}

__device__ __forceinline__ void wgmma_rs_n80(float* d, const uint32_t* a, uint64_t db, int sd) {
  asm volatile("{ .reg .pred p; setp.ne.b32 p, %45, 0;\n"
      "wgmma.mma_async.sync.aligned.m64n80k16.f32.bf16.bf16 {"
      "%0,%1,%2,%3,%4,%5,%6,%7,%8,%9,%10,%11,%12,%13,%14,%15,"
      "%16,%17,%18,%19,%20,%21,%22,%23,%24,%25,%26,%27,%28,%29,%30,%31,"
      "%32,%33,%34,%35,%36,%37,%38,%39"
      "}, {%40,%41,%42,%43}, %44, p, 1, 1, 0; }"
    : "+f"(d[0]), "+f"(d[1]), "+f"(d[2]), "+f"(d[3]), "+f"(d[4]), "+f"(d[5]), "+f"(d[6]), "+f"(d[7]),
      "+f"(d[8]), "+f"(d[9]), "+f"(d[10]), "+f"(d[11]), "+f"(d[12]), "+f"(d[13]), "+f"(d[14]), "+f"(d[15]),
      "+f"(d[16]), "+f"(d[17]), "+f"(d[18]), "+f"(d[19]), "+f"(d[20]), "+f"(d[21]), "+f"(d[22]), "+f"(d[23]),
      "+f"(d[24]), "+f"(d[25]), "+f"(d[26]), "+f"(d[27]), "+f"(d[28]), "+f"(d[29]), "+f"(d[30]), "+f"(d[31]),
      "+f"(d[32]), "+f"(d[33]), "+f"(d[34]), "+f"(d[35]), "+f"(d[36]), "+f"(d[37]), "+f"(d[38]), "+f"(d[39])
    : "r"(a[0]), "r"(a[1]), "r"(a[2]), "r"(a[3]), "l"(db), "r"(sd));
}

__device__ __forceinline__ void wgmma_rs_n96(float* d, const uint32_t* a, uint64_t db, int sd) {
  asm volatile("{ .reg .pred p; setp.ne.b32 p, %53, 0;\n"
      "wgmma.mma_async.sync.aligned.m64n96k16.f32.bf16.bf16 {"
      "%0,%1,%2,%3,%4,%5,%6,%7,%8,%9,%10,%11,%12,%13,%14,%15,"
      "%16,%17,%18,%19,%20,%21,%22,%23,%24,%25,%26,%27,%28,%29,%30,%31,"
      "%32,%33,%34,%35,%36,%37,%38,%39,%40,%41,%42,%43,%44,%45,%46,%47"
      "}, {%48,%49,%50,%51}, %52, p, 1, 1, 0; }"
    : "+f"(d[0]), "+f"(d[1]), "+f"(d[2]), "+f"(d[3]), "+f"(d[4]), "+f"(d[5]), "+f"(d[6]), "+f"(d[7]),
      "+f"(d[8]), "+f"(d[9]), "+f"(d[10]), "+f"(d[11]), "+f"(d[12]), "+f"(d[13]), "+f"(d[14]), "+f"(d[15]),
      "+f"(d[16]), "+f"(d[17]), "+f"(d[18]), "+f"(d[19]), "+f"(d[20]), "+f"(d[21]), "+f"(d[22]), "+f"(d[23]),
      "+f"(d[24]), "+f"(d[25]), "+f"(d[26]), "+f"(d[27]), "+f"(d[28]), "+f"(d[29]), "+f"(d[30]), "+f"(d[31]),
      "+f"(d[32]), "+f"(d[33]), "+f"(d[34]), "+f"(d[35]), "+f"(d[36]), "+f"(d[37]), "+f"(d[38]), "+f"(d[39]),
      "+f"(d[40]), "+f"(d[41]), "+f"(d[42]), "+f"(d[43]), "+f"(d[44]), "+f"(d[45]), "+f"(d[46]), "+f"(d[47])
    : "r"(a[0]), "r"(a[1]), "r"(a[2]), "r"(a[3]), "l"(db), "r"(sd));
}

__device__ __forceinline__ void wgmma_rs_n112(float* d, const uint32_t* a, uint64_t db, int sd) {
  asm volatile("{ .reg .pred p; setp.ne.b32 p, %61, 0;\n"
      "wgmma.mma_async.sync.aligned.m64n112k16.f32.bf16.bf16 {"
      "%0,%1,%2,%3,%4,%5,%6,%7,%8,%9,%10,%11,%12,%13,%14,%15,"
      "%16,%17,%18,%19,%20,%21,%22,%23,%24,%25,%26,%27,%28,%29,%30,%31,"
      "%32,%33,%34,%35,%36,%37,%38,%39,%40,%41,%42,%43,%44,%45,%46,%47,"
      "%48,%49,%50,%51,%52,%53,%54,%55"
      "}, {%56,%57,%58,%59}, %60, p, 1, 1, 0; }"
    : "+f"(d[0]), "+f"(d[1]), "+f"(d[2]), "+f"(d[3]), "+f"(d[4]), "+f"(d[5]), "+f"(d[6]), "+f"(d[7]),
      "+f"(d[8]), "+f"(d[9]), "+f"(d[10]), "+f"(d[11]), "+f"(d[12]), "+f"(d[13]), "+f"(d[14]), "+f"(d[15]),
      "+f"(d[16]), "+f"(d[17]), "+f"(d[18]), "+f"(d[19]), "+f"(d[20]), "+f"(d[21]), "+f"(d[22]), "+f"(d[23]),
      "+f"(d[24]), "+f"(d[25]), "+f"(d[26]), "+f"(d[27]), "+f"(d[28]), "+f"(d[29]), "+f"(d[30]), "+f"(d[31]),
      "+f"(d[32]), "+f"(d[33]), "+f"(d[34]), "+f"(d[35]), "+f"(d[36]), "+f"(d[37]), "+f"(d[38]), "+f"(d[39]),
      "+f"(d[40]), "+f"(d[41]), "+f"(d[42]), "+f"(d[43]), "+f"(d[44]), "+f"(d[45]), "+f"(d[46]), "+f"(d[47]),
      "+f"(d[48]), "+f"(d[49]), "+f"(d[50]), "+f"(d[51]), "+f"(d[52]), "+f"(d[53]), "+f"(d[54]), "+f"(d[55])
    : "r"(a[0]), "r"(a[1]), "r"(a[2]), "r"(a[3]), "l"(db), "r"(sd));
}

__device__ __forceinline__ void wgmma_rs_n128(float* d, const uint32_t* a, uint64_t db, int sd) {
  asm volatile("{ .reg .pred p; setp.ne.b32 p, %69, 0;\n"
      "wgmma.mma_async.sync.aligned.m64n128k16.f32.bf16.bf16 {"
      "%0,%1,%2,%3,%4,%5,%6,%7,%8,%9,%10,%11,%12,%13,%14,%15,"
      "%16,%17,%18,%19,%20,%21,%22,%23,%24,%25,%26,%27,%28,%29,%30,%31,"
      "%32,%33,%34,%35,%36,%37,%38,%39,%40,%41,%42,%43,%44,%45,%46,%47,"
      "%48,%49,%50,%51,%52,%53,%54,%55,%56,%57,%58,%59,%60,%61,%62,%63"
      "}, {%64,%65,%66,%67}, %68, p, 1, 1, 0; }"
    : "+f"(d[0]), "+f"(d[1]), "+f"(d[2]), "+f"(d[3]), "+f"(d[4]), "+f"(d[5]), "+f"(d[6]), "+f"(d[7]),
      "+f"(d[8]), "+f"(d[9]), "+f"(d[10]), "+f"(d[11]), "+f"(d[12]), "+f"(d[13]), "+f"(d[14]), "+f"(d[15]),
      "+f"(d[16]), "+f"(d[17]), "+f"(d[18]), "+f"(d[19]), "+f"(d[20]), "+f"(d[21]), "+f"(d[22]), "+f"(d[23]),
      "+f"(d[24]), "+f"(d[25]), "+f"(d[26]), "+f"(d[27]), "+f"(d[28]), "+f"(d[29]), "+f"(d[30]), "+f"(d[31]),
      "+f"(d[32]), "+f"(d[33]), "+f"(d[34]), "+f"(d[35]), "+f"(d[36]), "+f"(d[37]), "+f"(d[38]), "+f"(d[39]),
      "+f"(d[40]), "+f"(d[41]), "+f"(d[42]), "+f"(d[43]), "+f"(d[44]), "+f"(d[45]), "+f"(d[46]), "+f"(d[47]),
      "+f"(d[48]), "+f"(d[49]), "+f"(d[50]), "+f"(d[51]), "+f"(d[52]), "+f"(d[53]), "+f"(d[54]), "+f"(d[55]),
      "+f"(d[56]), "+f"(d[57]), "+f"(d[58]), "+f"(d[59]), "+f"(d[60]), "+f"(d[61]), "+f"(d[62]), "+f"(d[63])
    : "r"(a[0]), "r"(a[1]), "r"(a[2]), "r"(a[3]), "l"(db), "r"(sd));
}

__device__ __forceinline__ void wgmma_rs_n144(float* d, const uint32_t* a, uint64_t db, int sd) {
  asm volatile("{ .reg .pred p; setp.ne.b32 p, %77, 0;\n"
      "wgmma.mma_async.sync.aligned.m64n144k16.f32.bf16.bf16 {"
      "%0,%1,%2,%3,%4,%5,%6,%7,%8,%9,%10,%11,%12,%13,%14,%15,"
      "%16,%17,%18,%19,%20,%21,%22,%23,%24,%25,%26,%27,%28,%29,%30,%31,"
      "%32,%33,%34,%35,%36,%37,%38,%39,%40,%41,%42,%43,%44,%45,%46,%47,"
      "%48,%49,%50,%51,%52,%53,%54,%55,%56,%57,%58,%59,%60,%61,%62,%63,"
      "%64,%65,%66,%67,%68,%69,%70,%71"
      "}, {%72,%73,%74,%75}, %76, p, 1, 1, 0; }"
    : "+f"(d[0]), "+f"(d[1]), "+f"(d[2]), "+f"(d[3]), "+f"(d[4]), "+f"(d[5]), "+f"(d[6]), "+f"(d[7]),
      "+f"(d[8]), "+f"(d[9]), "+f"(d[10]), "+f"(d[11]), "+f"(d[12]), "+f"(d[13]), "+f"(d[14]), "+f"(d[15]),
      "+f"(d[16]), "+f"(d[17]), "+f"(d[18]), "+f"(d[19]), "+f"(d[20]), "+f"(d[21]), "+f"(d[22]), "+f"(d[23]),
      "+f"(d[24]), "+f"(d[25]), "+f"(d[26]), "+f"(d[27]), "+f"(d[28]), "+f"(d[29]), "+f"(d[30]), "+f"(d[31]),
      "+f"(d[32]), "+f"(d[33]), "+f"(d[34]), "+f"(d[35]), "+f"(d[36]), "+f"(d[37]), "+f"(d[38]), "+f"(d[39]),
      "+f"(d[40]), "+f"(d[41]), "+f"(d[42]), "+f"(d[43]), "+f"(d[44]), "+f"(d[45]), "+f"(d[46]), "+f"(d[47]),
      "+f"(d[48]), "+f"(d[49]), "+f"(d[50]), "+f"(d[51]), "+f"(d[52]), "+f"(d[53]), "+f"(d[54]), "+f"(d[55]),
      "+f"(d[56]), "+f"(d[57]), "+f"(d[58]), "+f"(d[59]), "+f"(d[60]), "+f"(d[61]), "+f"(d[62]), "+f"(d[63]),
      "+f"(d[64]), "+f"(d[65]), "+f"(d[66]), "+f"(d[67]), "+f"(d[68]), "+f"(d[69]), "+f"(d[70]), "+f"(d[71])
    : "r"(a[0]), "r"(a[1]), "r"(a[2]), "r"(a[3]), "l"(db), "r"(sd));
}

__device__ __forceinline__ void wgmma_rs_n160(float* d, const uint32_t* a, uint64_t db, int sd) {
  asm volatile("{ .reg .pred p; setp.ne.b32 p, %85, 0;\n"
      "wgmma.mma_async.sync.aligned.m64n160k16.f32.bf16.bf16 {"
      "%0,%1,%2,%3,%4,%5,%6,%7,%8,%9,%10,%11,%12,%13,%14,%15,"
      "%16,%17,%18,%19,%20,%21,%22,%23,%24,%25,%26,%27,%28,%29,%30,%31,"
      "%32,%33,%34,%35,%36,%37,%38,%39,%40,%41,%42,%43,%44,%45,%46,%47,"
      "%48,%49,%50,%51,%52,%53,%54,%55,%56,%57,%58,%59,%60,%61,%62,%63,"
      "%64,%65,%66,%67,%68,%69,%70,%71,%72,%73,%74,%75,%76,%77,%78,%79"
      "}, {%80,%81,%82,%83}, %84, p, 1, 1, 0; }"
    : "+f"(d[0]), "+f"(d[1]), "+f"(d[2]), "+f"(d[3]), "+f"(d[4]), "+f"(d[5]), "+f"(d[6]), "+f"(d[7]),
      "+f"(d[8]), "+f"(d[9]), "+f"(d[10]), "+f"(d[11]), "+f"(d[12]), "+f"(d[13]), "+f"(d[14]), "+f"(d[15]),
      "+f"(d[16]), "+f"(d[17]), "+f"(d[18]), "+f"(d[19]), "+f"(d[20]), "+f"(d[21]), "+f"(d[22]), "+f"(d[23]),
      "+f"(d[24]), "+f"(d[25]), "+f"(d[26]), "+f"(d[27]), "+f"(d[28]), "+f"(d[29]), "+f"(d[30]), "+f"(d[31]),
      "+f"(d[32]), "+f"(d[33]), "+f"(d[34]), "+f"(d[35]), "+f"(d[36]), "+f"(d[37]), "+f"(d[38]), "+f"(d[39]),
      "+f"(d[40]), "+f"(d[41]), "+f"(d[42]), "+f"(d[43]), "+f"(d[44]), "+f"(d[45]), "+f"(d[46]), "+f"(d[47]),
      "+f"(d[48]), "+f"(d[49]), "+f"(d[50]), "+f"(d[51]), "+f"(d[52]), "+f"(d[53]), "+f"(d[54]), "+f"(d[55]),
      "+f"(d[56]), "+f"(d[57]), "+f"(d[58]), "+f"(d[59]), "+f"(d[60]), "+f"(d[61]), "+f"(d[62]), "+f"(d[63]),
      "+f"(d[64]), "+f"(d[65]), "+f"(d[66]), "+f"(d[67]), "+f"(d[68]), "+f"(d[69]), "+f"(d[70]), "+f"(d[71]),
      "+f"(d[72]), "+f"(d[73]), "+f"(d[74]), "+f"(d[75]), "+f"(d[76]), "+f"(d[77]), "+f"(d[78]), "+f"(d[79])
    : "r"(a[0]), "r"(a[1]), "r"(a[2]), "r"(a[3]), "l"(db), "r"(sd));
}

__device__ __forceinline__ void wgmma_rs_n176(float* d, const uint32_t* a, uint64_t db, int sd) {
  asm volatile("{ .reg .pred p; setp.ne.b32 p, %93, 0;\n"
      "wgmma.mma_async.sync.aligned.m64n176k16.f32.bf16.bf16 {"
      "%0,%1,%2,%3,%4,%5,%6,%7,%8,%9,%10,%11,%12,%13,%14,%15,"
      "%16,%17,%18,%19,%20,%21,%22,%23,%24,%25,%26,%27,%28,%29,%30,%31,"
      "%32,%33,%34,%35,%36,%37,%38,%39,%40,%41,%42,%43,%44,%45,%46,%47,"
      "%48,%49,%50,%51,%52,%53,%54,%55,%56,%57,%58,%59,%60,%61,%62,%63,"
      "%64,%65,%66,%67,%68,%69,%70,%71,%72,%73,%74,%75,%76,%77,%78,%79,"
      "%80,%81,%82,%83,%84,%85,%86,%87"
      "}, {%88,%89,%90,%91}, %92, p, 1, 1, 0; }"
    : "+f"(d[0]), "+f"(d[1]), "+f"(d[2]), "+f"(d[3]), "+f"(d[4]), "+f"(d[5]), "+f"(d[6]), "+f"(d[7]),
      "+f"(d[8]), "+f"(d[9]), "+f"(d[10]), "+f"(d[11]), "+f"(d[12]), "+f"(d[13]), "+f"(d[14]), "+f"(d[15]),
      "+f"(d[16]), "+f"(d[17]), "+f"(d[18]), "+f"(d[19]), "+f"(d[20]), "+f"(d[21]), "+f"(d[22]), "+f"(d[23]),
      "+f"(d[24]), "+f"(d[25]), "+f"(d[26]), "+f"(d[27]), "+f"(d[28]), "+f"(d[29]), "+f"(d[30]), "+f"(d[31]),
      "+f"(d[32]), "+f"(d[33]), "+f"(d[34]), "+f"(d[35]), "+f"(d[36]), "+f"(d[37]), "+f"(d[38]), "+f"(d[39]),
      "+f"(d[40]), "+f"(d[41]), "+f"(d[42]), "+f"(d[43]), "+f"(d[44]), "+f"(d[45]), "+f"(d[46]), "+f"(d[47]),
      "+f"(d[48]), "+f"(d[49]), "+f"(d[50]), "+f"(d[51]), "+f"(d[52]), "+f"(d[53]), "+f"(d[54]), "+f"(d[55]),
      "+f"(d[56]), "+f"(d[57]), "+f"(d[58]), "+f"(d[59]), "+f"(d[60]), "+f"(d[61]), "+f"(d[62]), "+f"(d[63]),
      "+f"(d[64]), "+f"(d[65]), "+f"(d[66]), "+f"(d[67]), "+f"(d[68]), "+f"(d[69]), "+f"(d[70]), "+f"(d[71]),
      "+f"(d[72]), "+f"(d[73]), "+f"(d[74]), "+f"(d[75]), "+f"(d[76]), "+f"(d[77]), "+f"(d[78]), "+f"(d[79]),
      "+f"(d[80]), "+f"(d[81]), "+f"(d[82]), "+f"(d[83]), "+f"(d[84]), "+f"(d[85]), "+f"(d[86]), "+f"(d[87])
    : "r"(a[0]), "r"(a[1]), "r"(a[2]), "r"(a[3]), "l"(db), "r"(sd));
}

__device__ __forceinline__ void wgmma_rs_n192(float* d, const uint32_t* a, uint64_t db, int sd) {
  asm volatile("{ .reg .pred p; setp.ne.b32 p, %101, 0;\n"
      "wgmma.mma_async.sync.aligned.m64n192k16.f32.bf16.bf16 {"
      "%0,%1,%2,%3,%4,%5,%6,%7,%8,%9,%10,%11,%12,%13,%14,%15,"
      "%16,%17,%18,%19,%20,%21,%22,%23,%24,%25,%26,%27,%28,%29,%30,%31,"
      "%32,%33,%34,%35,%36,%37,%38,%39,%40,%41,%42,%43,%44,%45,%46,%47,"
      "%48,%49,%50,%51,%52,%53,%54,%55,%56,%57,%58,%59,%60,%61,%62,%63,"
      "%64,%65,%66,%67,%68,%69,%70,%71,%72,%73,%74,%75,%76,%77,%78,%79,"
      "%80,%81,%82,%83,%84,%85,%86,%87,%88,%89,%90,%91,%92,%93,%94,%95"
      "}, {%96,%97,%98,%99}, %100, p, 1, 1, 0; }"
    : "+f"(d[0]), "+f"(d[1]), "+f"(d[2]), "+f"(d[3]), "+f"(d[4]), "+f"(d[5]), "+f"(d[6]), "+f"(d[7]),
      "+f"(d[8]), "+f"(d[9]), "+f"(d[10]), "+f"(d[11]), "+f"(d[12]), "+f"(d[13]), "+f"(d[14]), "+f"(d[15]),
      "+f"(d[16]), "+f"(d[17]), "+f"(d[18]), "+f"(d[19]), "+f"(d[20]), "+f"(d[21]), "+f"(d[22]), "+f"(d[23]),
      "+f"(d[24]), "+f"(d[25]), "+f"(d[26]), "+f"(d[27]), "+f"(d[28]), "+f"(d[29]), "+f"(d[30]), "+f"(d[31]),
      "+f"(d[32]), "+f"(d[33]), "+f"(d[34]), "+f"(d[35]), "+f"(d[36]), "+f"(d[37]), "+f"(d[38]), "+f"(d[39]),
      "+f"(d[40]), "+f"(d[41]), "+f"(d[42]), "+f"(d[43]), "+f"(d[44]), "+f"(d[45]), "+f"(d[46]), "+f"(d[47]),
      "+f"(d[48]), "+f"(d[49]), "+f"(d[50]), "+f"(d[51]), "+f"(d[52]), "+f"(d[53]), "+f"(d[54]), "+f"(d[55]),
      "+f"(d[56]), "+f"(d[57]), "+f"(d[58]), "+f"(d[59]), "+f"(d[60]), "+f"(d[61]), "+f"(d[62]), "+f"(d[63]),
      "+f"(d[64]), "+f"(d[65]), "+f"(d[66]), "+f"(d[67]), "+f"(d[68]), "+f"(d[69]), "+f"(d[70]), "+f"(d[71]),
      "+f"(d[72]), "+f"(d[73]), "+f"(d[74]), "+f"(d[75]), "+f"(d[76]), "+f"(d[77]), "+f"(d[78]), "+f"(d[79]),
      "+f"(d[80]), "+f"(d[81]), "+f"(d[82]), "+f"(d[83]), "+f"(d[84]), "+f"(d[85]), "+f"(d[86]), "+f"(d[87]),
      "+f"(d[88]), "+f"(d[89]), "+f"(d[90]), "+f"(d[91]), "+f"(d[92]), "+f"(d[93]), "+f"(d[94]), "+f"(d[95])
    : "r"(a[0]), "r"(a[1]), "r"(a[2]), "r"(a[3]), "l"(db), "r"(sd));
}

__device__ __forceinline__ void wgmma_rs_n208(float* d, const uint32_t* a, uint64_t db, int sd) {
  asm volatile("{ .reg .pred p; setp.ne.b32 p, %109, 0;\n"
      "wgmma.mma_async.sync.aligned.m64n208k16.f32.bf16.bf16 {"
      "%0,%1,%2,%3,%4,%5,%6,%7,%8,%9,%10,%11,%12,%13,%14,%15,"
      "%16,%17,%18,%19,%20,%21,%22,%23,%24,%25,%26,%27,%28,%29,%30,%31,"
      "%32,%33,%34,%35,%36,%37,%38,%39,%40,%41,%42,%43,%44,%45,%46,%47,"
      "%48,%49,%50,%51,%52,%53,%54,%55,%56,%57,%58,%59,%60,%61,%62,%63,"
      "%64,%65,%66,%67,%68,%69,%70,%71,%72,%73,%74,%75,%76,%77,%78,%79,"
      "%80,%81,%82,%83,%84,%85,%86,%87,%88,%89,%90,%91,%92,%93,%94,%95,"
      "%96,%97,%98,%99,%100,%101,%102,%103"
      "}, {%104,%105,%106,%107}, %108, p, 1, 1, 0; }"
    : "+f"(d[0]), "+f"(d[1]), "+f"(d[2]), "+f"(d[3]), "+f"(d[4]), "+f"(d[5]), "+f"(d[6]), "+f"(d[7]),
      "+f"(d[8]), "+f"(d[9]), "+f"(d[10]), "+f"(d[11]), "+f"(d[12]), "+f"(d[13]), "+f"(d[14]), "+f"(d[15]),
      "+f"(d[16]), "+f"(d[17]), "+f"(d[18]), "+f"(d[19]), "+f"(d[20]), "+f"(d[21]), "+f"(d[22]), "+f"(d[23]),
      "+f"(d[24]), "+f"(d[25]), "+f"(d[26]), "+f"(d[27]), "+f"(d[28]), "+f"(d[29]), "+f"(d[30]), "+f"(d[31]),
      "+f"(d[32]), "+f"(d[33]), "+f"(d[34]), "+f"(d[35]), "+f"(d[36]), "+f"(d[37]), "+f"(d[38]), "+f"(d[39]),
      "+f"(d[40]), "+f"(d[41]), "+f"(d[42]), "+f"(d[43]), "+f"(d[44]), "+f"(d[45]), "+f"(d[46]), "+f"(d[47]),
      "+f"(d[48]), "+f"(d[49]), "+f"(d[50]), "+f"(d[51]), "+f"(d[52]), "+f"(d[53]), "+f"(d[54]), "+f"(d[55]),
      "+f"(d[56]), "+f"(d[57]), "+f"(d[58]), "+f"(d[59]), "+f"(d[60]), "+f"(d[61]), "+f"(d[62]), "+f"(d[63]),
      "+f"(d[64]), "+f"(d[65]), "+f"(d[66]), "+f"(d[67]), "+f"(d[68]), "+f"(d[69]), "+f"(d[70]), "+f"(d[71]),
      "+f"(d[72]), "+f"(d[73]), "+f"(d[74]), "+f"(d[75]), "+f"(d[76]), "+f"(d[77]), "+f"(d[78]), "+f"(d[79]),
      "+f"(d[80]), "+f"(d[81]), "+f"(d[82]), "+f"(d[83]), "+f"(d[84]), "+f"(d[85]), "+f"(d[86]), "+f"(d[87]),
      "+f"(d[88]), "+f"(d[89]), "+f"(d[90]), "+f"(d[91]), "+f"(d[92]), "+f"(d[93]), "+f"(d[94]), "+f"(d[95]),
      "+f"(d[96]), "+f"(d[97]), "+f"(d[98]), "+f"(d[99]), "+f"(d[100]), "+f"(d[101]), "+f"(d[102]), "+f"(d[103])
    : "r"(a[0]), "r"(a[1]), "r"(a[2]), "r"(a[3]), "l"(db), "r"(sd));
}

__device__ __forceinline__ void wgmma_rs_n224(float* d, const uint32_t* a, uint64_t db, int sd) {
  asm volatile("{ .reg .pred p; setp.ne.b32 p, %117, 0;\n"
      "wgmma.mma_async.sync.aligned.m64n224k16.f32.bf16.bf16 {"
      "%0,%1,%2,%3,%4,%5,%6,%7,%8,%9,%10,%11,%12,%13,%14,%15,"
      "%16,%17,%18,%19,%20,%21,%22,%23,%24,%25,%26,%27,%28,%29,%30,%31,"
      "%32,%33,%34,%35,%36,%37,%38,%39,%40,%41,%42,%43,%44,%45,%46,%47,"
      "%48,%49,%50,%51,%52,%53,%54,%55,%56,%57,%58,%59,%60,%61,%62,%63,"
      "%64,%65,%66,%67,%68,%69,%70,%71,%72,%73,%74,%75,%76,%77,%78,%79,"
      "%80,%81,%82,%83,%84,%85,%86,%87,%88,%89,%90,%91,%92,%93,%94,%95,"
      "%96,%97,%98,%99,%100,%101,%102,%103,%104,%105,%106,%107,%108,%109,%110,%111"
      "}, {%112,%113,%114,%115}, %116, p, 1, 1, 0; }"
    : "+f"(d[0]), "+f"(d[1]), "+f"(d[2]), "+f"(d[3]), "+f"(d[4]), "+f"(d[5]), "+f"(d[6]), "+f"(d[7]),
      "+f"(d[8]), "+f"(d[9]), "+f"(d[10]), "+f"(d[11]), "+f"(d[12]), "+f"(d[13]), "+f"(d[14]), "+f"(d[15]),
      "+f"(d[16]), "+f"(d[17]), "+f"(d[18]), "+f"(d[19]), "+f"(d[20]), "+f"(d[21]), "+f"(d[22]), "+f"(d[23]),
      "+f"(d[24]), "+f"(d[25]), "+f"(d[26]), "+f"(d[27]), "+f"(d[28]), "+f"(d[29]), "+f"(d[30]), "+f"(d[31]),
      "+f"(d[32]), "+f"(d[33]), "+f"(d[34]), "+f"(d[35]), "+f"(d[36]), "+f"(d[37]), "+f"(d[38]), "+f"(d[39]),
      "+f"(d[40]), "+f"(d[41]), "+f"(d[42]), "+f"(d[43]), "+f"(d[44]), "+f"(d[45]), "+f"(d[46]), "+f"(d[47]),
      "+f"(d[48]), "+f"(d[49]), "+f"(d[50]), "+f"(d[51]), "+f"(d[52]), "+f"(d[53]), "+f"(d[54]), "+f"(d[55]),
      "+f"(d[56]), "+f"(d[57]), "+f"(d[58]), "+f"(d[59]), "+f"(d[60]), "+f"(d[61]), "+f"(d[62]), "+f"(d[63]),
      "+f"(d[64]), "+f"(d[65]), "+f"(d[66]), "+f"(d[67]), "+f"(d[68]), "+f"(d[69]), "+f"(d[70]), "+f"(d[71]),
      "+f"(d[72]), "+f"(d[73]), "+f"(d[74]), "+f"(d[75]), "+f"(d[76]), "+f"(d[77]), "+f"(d[78]), "+f"(d[79]),
      "+f"(d[80]), "+f"(d[81]), "+f"(d[82]), "+f"(d[83]), "+f"(d[84]), "+f"(d[85]), "+f"(d[86]), "+f"(d[87]),
      "+f"(d[88]), "+f"(d[89]), "+f"(d[90]), "+f"(d[91]), "+f"(d[92]), "+f"(d[93]), "+f"(d[94]), "+f"(d[95]),
      "+f"(d[96]), "+f"(d[97]), "+f"(d[98]), "+f"(d[99]), "+f"(d[100]), "+f"(d[101]), "+f"(d[102]), "+f"(d[103]),
      "+f"(d[104]), "+f"(d[105]), "+f"(d[106]), "+f"(d[107]), "+f"(d[108]), "+f"(d[109]), "+f"(d[110]), "+f"(d[111])
    : "r"(a[0]), "r"(a[1]), "r"(a[2]), "r"(a[3]), "l"(db), "r"(sd));
}

__device__ __forceinline__ void wgmma_rs_n240(float* d, const uint32_t* a, uint64_t db, int sd) {
  asm volatile("{ .reg .pred p; setp.ne.b32 p, %125, 0;\n"
      "wgmma.mma_async.sync.aligned.m64n240k16.f32.bf16.bf16 {"
      "%0,%1,%2,%3,%4,%5,%6,%7,%8,%9,%10,%11,%12,%13,%14,%15,"
      "%16,%17,%18,%19,%20,%21,%22,%23,%24,%25,%26,%27,%28,%29,%30,%31,"
      "%32,%33,%34,%35,%36,%37,%38,%39,%40,%41,%42,%43,%44,%45,%46,%47,"
      "%48,%49,%50,%51,%52,%53,%54,%55,%56,%57,%58,%59,%60,%61,%62,%63,"
      "%64,%65,%66,%67,%68,%69,%70,%71,%72,%73,%74,%75,%76,%77,%78,%79,"
      "%80,%81,%82,%83,%84,%85,%86,%87,%88,%89,%90,%91,%92,%93,%94,%95,"
      "%96,%97,%98,%99,%100,%101,%102,%103,%104,%105,%106,%107,%108,%109,%110,%111,"
      "%112,%113,%114,%115,%116,%117,%118,%119"
      "}, {%120,%121,%122,%123}, %124, p, 1, 1, 0; }"
    : "+f"(d[0]), "+f"(d[1]), "+f"(d[2]), "+f"(d[3]), "+f"(d[4]), "+f"(d[5]), "+f"(d[6]), "+f"(d[7]),
      "+f"(d[8]), "+f"(d[9]), "+f"(d[10]), "+f"(d[11]), "+f"(d[12]), "+f"(d[13]), "+f"(d[14]), "+f"(d[15]),
      "+f"(d[16]), "+f"(d[17]), "+f"(d[18]), "+f"(d[19]), "+f"(d[20]), "+f"(d[21]), "+f"(d[22]), "+f"(d[23]),
      "+f"(d[24]), "+f"(d[25]), "+f"(d[26]), "+f"(d[27]), "+f"(d[28]), "+f"(d[29]), "+f"(d[30]), "+f"(d[31]),
      "+f"(d[32]), "+f"(d[33]), "+f"(d[34]), "+f"(d[35]), "+f"(d[36]), "+f"(d[37]), "+f"(d[38]), "+f"(d[39]),
      "+f"(d[40]), "+f"(d[41]), "+f"(d[42]), "+f"(d[43]), "+f"(d[44]), "+f"(d[45]), "+f"(d[46]), "+f"(d[47]),
      "+f"(d[48]), "+f"(d[49]), "+f"(d[50]), "+f"(d[51]), "+f"(d[52]), "+f"(d[53]), "+f"(d[54]), "+f"(d[55]),
      "+f"(d[56]), "+f"(d[57]), "+f"(d[58]), "+f"(d[59]), "+f"(d[60]), "+f"(d[61]), "+f"(d[62]), "+f"(d[63]),
      "+f"(d[64]), "+f"(d[65]), "+f"(d[66]), "+f"(d[67]), "+f"(d[68]), "+f"(d[69]), "+f"(d[70]), "+f"(d[71]),
      "+f"(d[72]), "+f"(d[73]), "+f"(d[74]), "+f"(d[75]), "+f"(d[76]), "+f"(d[77]), "+f"(d[78]), "+f"(d[79]),
      "+f"(d[80]), "+f"(d[81]), "+f"(d[82]), "+f"(d[83]), "+f"(d[84]), "+f"(d[85]), "+f"(d[86]), "+f"(d[87]),
      "+f"(d[88]), "+f"(d[89]), "+f"(d[90]), "+f"(d[91]), "+f"(d[92]), "+f"(d[93]), "+f"(d[94]), "+f"(d[95]),
      "+f"(d[96]), "+f"(d[97]), "+f"(d[98]), "+f"(d[99]), "+f"(d[100]), "+f"(d[101]), "+f"(d[102]), "+f"(d[103]),
      "+f"(d[104]), "+f"(d[105]), "+f"(d[106]), "+f"(d[107]), "+f"(d[108]), "+f"(d[109]), "+f"(d[110]), "+f"(d[111]),
      "+f"(d[112]), "+f"(d[113]), "+f"(d[114]), "+f"(d[115]), "+f"(d[116]), "+f"(d[117]), "+f"(d[118]), "+f"(d[119])
    : "r"(a[0]), "r"(a[1]), "r"(a[2]), "r"(a[3]), "l"(db), "r"(sd));
}

__device__ __forceinline__ void wgmma_rs_n256(float* d, const uint32_t* a, uint64_t db, int sd) {
  asm volatile("{ .reg .pred p; setp.ne.b32 p, %133, 0;\n"
      "wgmma.mma_async.sync.aligned.m64n256k16.f32.bf16.bf16 {"
      "%0,%1,%2,%3,%4,%5,%6,%7,%8,%9,%10,%11,%12,%13,%14,%15,"
      "%16,%17,%18,%19,%20,%21,%22,%23,%24,%25,%26,%27,%28,%29,%30,%31,"
      "%32,%33,%34,%35,%36,%37,%38,%39,%40,%41,%42,%43,%44,%45,%46,%47,"
      "%48,%49,%50,%51,%52,%53,%54,%55,%56,%57,%58,%59,%60,%61,%62,%63,"
      "%64,%65,%66,%67,%68,%69,%70,%71,%72,%73,%74,%75,%76,%77,%78,%79,"
      "%80,%81,%82,%83,%84,%85,%86,%87,%88,%89,%90,%91,%92,%93,%94,%95,"
      "%96,%97,%98,%99,%100,%101,%102,%103,%104,%105,%106,%107,%108,%109,%110,%111,"
      "%112,%113,%114,%115,%116,%117,%118,%119,%120,%121,%122,%123,%124,%125,%126,%127"
      "}, {%128,%129,%130,%131}, %132, p, 1, 1, 0; }"
    : "+f"(d[0]), "+f"(d[1]), "+f"(d[2]), "+f"(d[3]), "+f"(d[4]), "+f"(d[5]), "+f"(d[6]), "+f"(d[7]),
      "+f"(d[8]), "+f"(d[9]), "+f"(d[10]), "+f"(d[11]), "+f"(d[12]), "+f"(d[13]), "+f"(d[14]), "+f"(d[15]),
      "+f"(d[16]), "+f"(d[17]), "+f"(d[18]), "+f"(d[19]), "+f"(d[20]), "+f"(d[21]), "+f"(d[22]), "+f"(d[23]),
      "+f"(d[24]), "+f"(d[25]), "+f"(d[26]), "+f"(d[27]), "+f"(d[28]), "+f"(d[29]), "+f"(d[30]), "+f"(d[31]),
      "+f"(d[32]), "+f"(d[33]), "+f"(d[34]), "+f"(d[35]), "+f"(d[36]), "+f"(d[37]), "+f"(d[38]), "+f"(d[39]),
      "+f"(d[40]), "+f"(d[41]), "+f"(d[42]), "+f"(d[43]), "+f"(d[44]), "+f"(d[45]), "+f"(d[46]), "+f"(d[47]),
      "+f"(d[48]), "+f"(d[49]), "+f"(d[50]), "+f"(d[51]), "+f"(d[52]), "+f"(d[53]), "+f"(d[54]), "+f"(d[55]),
      "+f"(d[56]), "+f"(d[57]), "+f"(d[58]), "+f"(d[59]), "+f"(d[60]), "+f"(d[61]), "+f"(d[62]), "+f"(d[63]),
      "+f"(d[64]), "+f"(d[65]), "+f"(d[66]), "+f"(d[67]), "+f"(d[68]), "+f"(d[69]), "+f"(d[70]), "+f"(d[71]),
      "+f"(d[72]), "+f"(d[73]), "+f"(d[74]), "+f"(d[75]), "+f"(d[76]), "+f"(d[77]), "+f"(d[78]), "+f"(d[79]),
      "+f"(d[80]), "+f"(d[81]), "+f"(d[82]), "+f"(d[83]), "+f"(d[84]), "+f"(d[85]), "+f"(d[86]), "+f"(d[87]),
      "+f"(d[88]), "+f"(d[89]), "+f"(d[90]), "+f"(d[91]), "+f"(d[92]), "+f"(d[93]), "+f"(d[94]), "+f"(d[95]),
      "+f"(d[96]), "+f"(d[97]), "+f"(d[98]), "+f"(d[99]), "+f"(d[100]), "+f"(d[101]), "+f"(d[102]), "+f"(d[103]),
      "+f"(d[104]), "+f"(d[105]), "+f"(d[106]), "+f"(d[107]), "+f"(d[108]), "+f"(d[109]), "+f"(d[110]), "+f"(d[111]),
      "+f"(d[112]), "+f"(d[113]), "+f"(d[114]), "+f"(d[115]), "+f"(d[116]), "+f"(d[117]), "+f"(d[118]), "+f"(d[119]),
      "+f"(d[120]), "+f"(d[121]), "+f"(d[122]), "+f"(d[123]), "+f"(d[124]), "+f"(d[125]), "+f"(d[126]), "+f"(d[127])
    : "r"(a[0]), "r"(a[1]), "r"(a[2]), "r"(a[3]), "l"(db), "r"(sd));
}

__device__ __forceinline__ void ln_finish(float mean, float var, float& mb, float& rinv) {
  mb = round_bf16(mean);
  float sd;
  asm("sqrt.approx.ftz.f32 %0, %1;" : "=f"(sd) : "f"(round_bf16(round_bf16(var) + 1e-5f)));
  asm("rcp.approx.ftz.f32 %0, %1;" : "=f"(rinv) : "f"(round_bf16(sd)));
}
__device__ __forceinline__ uint32_t sum4(uint32_t a, uint32_t b, uint32_t c, uint32_t d) { return badd2(badd2(badd2(d, c), b), a); }
struct Ring {
  uint32_t s, ph;
  __device__ __forceinline__ void next() { if (++s == NSTAGE) { s = 0; ph ^= 1; } }
};

template <int J> __device__ __forceinline__ void conv_lda(uint32_t* a, uint32_t base) {
  a[2 * J] = lds32(base + (J >> 1) * 256 + (J & 1) * 16); a[2 * J + 1] = lds32(base + (J >> 1) * 256 + (J & 1) * 16 + 128);
}
template <int J = 0> __device__ __forceinline__ void conv_lda_all(uint32_t* a, uint32_t base) {
  conv_lda<J>(a, base);
  if constexpr (J < 31) conv_lda_all<J + 1>(a, base);
}
__device__ __forceinline__ void conv_mma(float* acc, const uint32_t* a, uint64_t db) {
  wgmma_rs_n256(acc, a, db, 0);
  wgmma_rs_n240(acc, a + 4, db + 16, 1);
  wgmma_rs_n224(acc, a + 8, db + 32, 1);
  wgmma_rs_n208(acc, a + 12, db + 48, 1);
  wgmma_rs_n192(acc, a + 16, db + 64, 1);
  wgmma_rs_n176(acc, a + 20, db + 80, 1);
  wgmma_rs_n160(acc, a + 24, db + 96, 1);
  wgmma_rs_n144(acc, a + 28, db + 112, 1);
  wgmma_rs_n128(acc, a + 32, db + 128, 1);
  wgmma_rs_n112(acc, a + 36, db + 144, 1);
  wgmma_rs_n96(acc, a + 40, db + 160, 1);
  wgmma_rs_n80(acc, a + 44, db + 176, 1);
  wgmma_rs_n64(acc, a + 48, db + 192, 1);
  wgmma_rs_n48(acc, a + 52, db + 208, 1);
  wgmma_rs_n32(acc, a + 56, db + 224, 1);
  wgmma_rs_n16(acc, a + 60, db + 240, 1);
}
__device__ __forceinline__ uint32_t conv_part(const float* acc, int j) {
  const int q = 31 - j;
  return q == 31 ? pack_bf16(acc[124], acc[125]) : pack_bf16(acc[4 * q] + acc[(4 * q + 6) & 127], acc[4 * q + 1] + acc[(4 * q + 7) & 127]);
}
template <bool MORE, int J = 0> __device__ __forceinline__ void conv_drain(const float* acc, uint32_t wr, uint32_t* a, uint32_t ka) {
  if (MORE) conv_lda<J>(a, ka);
  sts32(wr + J * 128, conv_part(acc, J));
  if constexpr (J < 31) conv_drain<MORE, J + 1>(acc, wr, a, ka);
}
__device__ __forceinline__ uint4 conv_sum(const uint4* p) {
  return make_uint4(sum4(p[0].x, p[1].x, p[2].x, p[3].x), sum4(p[0].y, p[1].y, p[2].y, p[3].y), sum4(p[0].z, p[1].z, p[2].z, p[3].z),
                    sum4(p[0].w, p[1].w, p[2].w, p[3].w));
}
__device__ __forceinline__ int g2k(int rank, int kb) { return (rank * G2_KB + (kb < 6 ? 6 * kb : kb - 5 + (kb - 6) / 5)) * 64; }

template <int NV> __device__ __forceinline__ void gelu_stage(float* acc, const float* hb, uint32_t sa, int passes, uint32_t bar) {
#pragma unroll
  for (int i = 0; i < NV; i++) acc[i] = fmaf(acc[i], 0.5f, hb[(i >> 1) & 1]);
#pragma unroll 1
  for (; passes > 0; passes--, sa += NV * 256) {
#pragma unroll
    for (int i = 0; i < NV; i += 8)
      stsm4t(sa + i * 256, pack_bf16(gelu_half(acc[i]), gelu_half(acc[i + 1])), pack_bf16(gelu_half(acc[i + 2]), gelu_half(acc[i + 3])),
             pack_bf16(gelu_half(acc[i + 4]), gelu_half(acc[i + 5])), pack_bf16(gelu_half(acc[i + 6]), gelu_half(acc[i + 7])));
    __syncwarp();
    if (bar) mbar_arrive(bar);
    bar = 0;
    float half = 0.5f;
    asm volatile("" : "+f"(half));
#pragma unroll
    for (int i = 0; i < NV; i++) acc[i] = fmaf(acc[NV + i], half, hb[2 + ((i >> 1) & 1)]);
  }
}

__global__ void __cluster_dims__(2, 1, 1) __launch_bounds__(384, 1) fused_kernel(const __grid_constant__ Hot H, const __grid_constant__ Params P) {
  extern __shared__ __align__(1024) uint8_t smem_raw[];
  const uint32_t t0 = clk();
  const uint32_t sb = smem_u32(smem_raw);
  const int tid = threadIdx.x, lane = tid & 31;
  const int bid = blockIdx.x, rank = bid & 1;
  const Role& R = P.role[bid];
  Scratch* const S = H.S;
  uint32_t xr[18];
  const int row = bid * 16 + (tid >> 4);
  if (tid < 256 && bid < 128) {
    const char* src = reinterpret_cast<const char*>(H.x) + row * (D_ * 2) + (lane & 15) * 8;
#pragma unroll
    for (int j = 0; j < 9; j++) asm volatile("ld.global.nc.v2.u32 {%0,%1}, [%2];" : "=r"(xr[2 * j]), "=r"(xr[2 * j + 1]) : "l"(src + 128 * j));
  }
  if (tid == 256) asm volatile("prefetch.tensormap [%0];" :: "l"(&P.m_w1 + (R.at == 15)) : "memory");
  const int warp = __shfl_sync(0xffffffffu, tid >> 5, 0);

  if (warp >= 8) {
    const bool one = elect_one(), left = R.at == 15;
    TUNED(NWE, 2, 1); TUNED(NW0, 3, 2);
    if (warp == 8 && one) {
#pragma unroll
      for (int b = B_FULL; b < B_KFULL; b += 8) mbar_init(sb + b, 1);
#pragma unroll 1
      for (int s = 0; s < NWE; s++) {
        mbar_expect_tx(sb + B_FULL + 8 * s, G1_BYTES);
        fence_async_smem();
        tma3d(sb + s * SLOT, &P.m_w1 + left, 0, s * 64, R.fg, sb + B_FULL + 8 * s);
      }
#pragma unroll
      for (int b = B_KFULL; b <= B_DONE; b += 8) mbar_init(sb + b, b < B_EMPTY ? 1 : b < B_SFREE ? 2 : b < B_CEMPTY ? 3 : b < B_G1DONE ? 4 : 8);
      asm volatile("fence.mbarrier_init.release.cluster;" ::: "memory");
    }
    __syncwarp();
    asm volatile("barrier.cluster.arrive.relaxed.aligned;" ::: "memory");
    asm volatile("setmaxnreg.dec.sync.aligned.u32 56;");
    asm volatile("barrier.cluster.wait.aligned;" ::: "memory");
    if (warp == 8) {
      const uint32_t ep = ldg32(S->cnt + C_EPOCH * 32);
      if (one) {
#pragma unroll 1
        for (int i = 0; i < 6; i++) asm volatile("prefetch.tensormap [%0];" :: "l"(&P.m_w2 + i) : "memory");
      }
      __syncwarp();
      if (bid < 128) bar_sync(2, 288);
      if (one) {
        TLREC(31);
        signal(S, C_H, EPOCH / 132);
        TLREC(1);
        const uint32_t boff = left ? 24576 : 16384;
        int kr = bid < 128 ? -2 : KV_ROUNDS + 1, ks = 0;
        auto kv_step = [&]() {
          if (ks == 0) {
            bulk_wait_all();
            if (kr < KV_ROUNDS - 2) {
              const int q = (kr + 2) % 3;
              const uint32_t in = sb + kv_buf(q), fb = sb + B_UFULL + 8 * q;
              mbar_expect_tx(fb, 3840 + 3264 + 768);
              tma2d(in, &P.m_k, (kr + 2) * 96, bid * 16 - 4, fb);
              tma2d(in + 3840, &P.m_v, (kr + 2) * 96, bid * 16 - 1, fb);
              bulk_load(in + 7168, H.shift_k + (kr + 2) * 384, 768, fb);
            }
            if (kr == KV_ROUNDS) { mbar_arrive(sb + B_KVDONE); kr++; }
          } else if (kr >= 0) {
            if (!mbar_test(sb + B_KFULL + 8 * (kr % 3), kr >= 3)) return;
            fence_async_smem();
            tma3d_store(&P.m_ub, sb + kv_buf(kr % 3) + (ks - 1) * 3072, 16 * (127 - bid), kr * 48, 2 * ks - 2);
            bulk_commit();
          }
          if (++ks == 3) { kr++; ks = kr == KV_ROUNDS - 2 || kr == KV_ROUNDS - 1; }
        };
        if (bid >= 128) mbar_arrive(sb + B_KVDONE);
        Ring r{0, 1};
#pragma unroll 1
        for (int kb = NWE - NW0; kb < G1_KB || kr <= KV_ROUNDS; kb++) {
          if (kb < G1_KB) {
          const int kw = kb < 0 ? kb + NW0 : kb, s = kb < 0 ? kw : r.s;
          const uint32_t fb = sb + B_FULL + 8 * s;
          if (kb < 0 || kb >= NW0) {
            mbar_wait(sb + B_EMPTY + 8 * s, r.ph);
            mbar_expect_tx(fb, G1_BYTES);
            tma3d(sb + s * SLOT, &P.m_w1 + left, 0, kw * 64, R.fg, fb);
            if (kb < 0) continue;
          }
          if (kb == 0) { await(S, C_H, ep); fence_async_global(); TLREC(2); }
          bulk_load(sb + s * SLOT + boff, S->h + (kb * 18 + R.at) * 2048, G1_BYTES - boff, fb);
          if (kb == 23) {
#pragma unroll 1
            for (int i = 0; i < 2; i++) {
              sts128(sb + cv_taps(i), 0, 0, 0, 0); sts128(sb + cv_taps(i) + 16, 0, 0, 0, 0);
              bulk_load(sb + cv_taps(i) + 32, H.ssm_k + (R.ch + i) * S_, 4096, sb + B_MISC);
            }
            mbar_expect_tx(sb + B_MISC, boff / 64 + 1152 + 8192);
            bulk_load(sb + SM_B1, H.b1 + R.fg * 64, boff / 64, sb + B_MISC);
            bulk_load(sb + SM_D, H.ssm_D, 1152, sb + B_MISC);
          }
          r.next();
          }
          if (kb >= KV0 && kr <= KV_ROUNDS) kv_step();
        }
        await(S, C_KV, ep);
        fence_async_global();
#pragma unroll 1
        for (int i = 0; i < R.ncv; i++) {
          if (i == 2) {
            if (R.sg >= 0) {
#pragma unroll 1
              for (int s = 2; s < NSTAGE; s++) {
                mbar_wait(sb + B_EMPTY + 8 * s, ((G1_KB / NSTAGE) - 1) & 1);
                mbar_expect_tx(sb + B_FULL + 8 * s, G2_BYTES);
                tma3d(sb + s * SLOT, &P.m_w2, 0, (rank * G2_KB + 6 * (s - 2)) * 64, R.sg, sb + B_FULL + 8 * s);
              }
            }
            mbar_wait(sb + B_G1DONE, 0);
          }
          const uint32_t kt = sb + cv_taps(i), b8 = sb + 8 * (i & 3);
          mbar_wait(b8 + B_CEMPTY, ((i >> 2) & 1) ^ 1);
          if (i < 2) mbar_arrive(b8 + B_KFULL);
          else {
            sts128(kt, 0, 0, 0, 0); sts128(kt + 16, 0, 0, 0, 0);
            mbar_expect_tx(b8 + B_KFULL, 4096);
            bulk_load(kt + 32, H.ssm_k + (R.ch + i) * S_, 4096, b8 + B_KFULL);
          }
          mbar_expect_tx(b8 + B_UFULL, 8192);
          bulk_load(sb + cv_in(i), S->ub + (R.ch + i) * 4096, 8192, b8 + B_UFULL);
        }
        if (R.sg >= 0) {
          mbar_expect_tx(sb + B_XY, 2 * 18432 + 2048 + 256);
#pragma unroll
          for (int i = 0; i < 4; i++) mbar_expect_tx(sb + B_XFULL + 8 * i, i & 1 ? 9216 - XP * 2048 : XP * 2048);
          TUNED(SYNCA, 0, 5); TUNED(SYNCKB, 1, 7);
#pragma unroll 1
          for (int kb = 0; kb < G2_KB; kb++, r.next()) {
            const int k0 = g2k(rank, kb);
            const uint32_t fb = sb + B_FULL + 8 * r.s, slot = sb + r.s * SLOT;
            if (!(kb & ~4)) { await(S, C_U + (kb >> 2), ep); fence_async_global(); if (!kb) TLREC(6); }
            if (kb >= NSTAGE - 2) {
              if (kb == SYNCKB) await(S, C_SYNC, ep);
              mbar_wait(sb + B_EMPTY + 8 * r.s, r.ph);
              if (kb == SYNCA) asm volatile("red.relaxed.gpu.global.add.u32 [%0], %1;" :: "l"(S->cnt + C_SYNC * 32), "r"(EPOCH / 128) : "memory");
              mbar_expect_tx(fb, G2_BYTES);
              tma3d(slot, &P.m_w2, 0, k0, R.sg, fb);
            }
            bulk_load(slot + 16384, S->u + k0 * D_ + R.ds * 512, 9216, fb);
            bulk_load(slot + 16384 + 9216, S->u + k0 * D_ + R.dk * 512, 9216, fb);
            const uint32_t nx = kb - 8;
            if (nx == 0) { mbar_wait(sb + B_KVDONE, 1); fence_async_smem(); }
            if (nx < 8) tma2d(sb + SM_CV + nx * 2304, &P.m_x, R.dk * 8, R.sg * 64 + nx * 16, sb + B_XY);
          }
          bulk_load(sb + SM_ST, S->stats + R.sg * 64, 2048, sb + B_XY);
          bulk_load(sb + SM_B2, P.b2 + R.sg * 64, 256, sb + B_XY);
          await(S, C_Y, ep);
          fence_async_global();
          TLREC(19);
          tma3d(sb + SM_DED, &P.m_y, 0, R.dk * 8, R.sg, sb + B_XY);
          if (bid == 0) asm volatile("red.relaxed.gpu.global.add.u32 [%0], %1;" :: "l"(S->cnt + C_EPOCH * 32), "r"(EPOCH) : "memory");
        }
      }
    } else {
      if (bid < 128) {
        const int ht = tid - 288, hf = ht >= 48, pr = ht - 48 * hf;
        const uint32_t st = (1 - hf) * 1536 + pr * 32, sw = (pr & 4) * 4;
#pragma unroll 1
        for (int r = 0; r < KV_ROUNDS; r++) {
          const int q = r % 3;
          const uint32_t in = sb + kv_buf(q);
          {
            mbar_wait_guarded(sb + B_UFULL + 8 * q, t0, r >= 3);
            uint32_t kk[12], vv[9];
#pragma unroll
            for (int j = 0; j < 12; j++) kk[j] = lds32(in + hf * 1536 + pr * 4 + j * 192);
#pragma unroll
            for (int j = 0; j < 9; j++) vv[j] = lds32(in + 3840 + hf * 1536 + pr * 4 + j * 192);
            const uint4 w = lds128(in + 7168 + pr * 16);
            const uint32_t w0 = __byte_perm(w.x, w.z, 0x5410), w1 = __byte_perm(w.x, w.z, 0x7632);
            const uint32_t w2 = __byte_perm(w.y, w.w, 0x5410), w3 = __byte_perm(w.y, w.w, 0x7632);
#pragma unroll
            for (int j = 0; j < 9; j++)
              vv[j] = bmul2(badd2(badd2(badd2(bmul2(kk[j], w3), bmul2(kk[j + 1], w2)), bmul2(kk[j + 2], w1)), bmul2(kk[j + 3], w0)), vv[j]);
            bar_sync(1, 96);
#pragma unroll
            for (int c = 0; c < 2; c++)
#pragma unroll
              for (int pi = 0; pi < 2; pi++) {
                const uint32_t sel = c ? 0x7632 : 0x5410;
                sts128(in + st + c * 3072 + (pi * 16 ^ sw), __byte_perm(vv[7 + pi], vv[6 + pi], sel), __byte_perm(vv[5 + pi], vv[4 + pi], sel),
                       __byte_perm(vv[3 + pi], vv[2 + pi], sel), __byte_perm(vv[1 + pi], vv[pi], sel));
              }
            bar_sync(1, 96);
            if (ht == 0) mbar_arrive(sb + B_KFULL + 8 * q);
          }
          __syncwarp();
        }
      }
      if (one) {
        if (warp < 11) {
          const int wg = warp - 9;
          const uint32_t bytes = left ? 12288 : 10240;
#pragma unroll 1
          for (int j = 0; j < 2; j++) {
            mbar_wait_guarded(sb + B_STG + 8 * wg + (j ? 0 : 16), t0);
            fence_async_smem();
            TLREC(13 + wg);
            if (!j || wg || !left)
              bulk_store(S->u + (R.fg + wg) * (64 * D_) + R.at * 2048 + j * (left ? 64 * D_ : 5120), sb + (wg ? SM_ST1 : SM_DED) + j * bytes, bytes);
          }
          bulk_commit();
          bulk_wait_all();
          mbar_arrive(sb + B_STORED + 8 * wg);
          if (wg) mbar_arrive(sb + B_EMPTY);
          asm volatile("mbarrier.arrive.shared::cta.b64 _, [%0], 3;" :: "r"(sb + B_SFREE + 8 * wg) : "memory");
          signal(S, C_U + wg, EPOCH / 132);
          TLREC(15 + wg);
        } else {
          mbar_wait_guarded(sb + B_KVDONE, t0);
          signal(S, C_KV, EPOCH / 132);
          TLREC(27);
        }
      }
      __syncwarp();
#pragma unroll 1
      for (int i = 0; i < R.ncv; i++) {
        const uint32_t red = sb + cv_red(i, R.ncv) + (tid - 288) * 16;
        uint4* yo = reinterpret_cast<uint4*>(S->y + (R.ch + i) * S_) + (tid - 288);
        mbar_wait_guarded(sb + B_STORED + 8 * (i & 1), t0);
        mbar_wait_guarded(sb + B_STG + 8 * (i & 1) + (i + 2 < R.ncv ? 0 : 16), t0, i + 2 >= R.ncv || !(i & 2));
        uint4 p[2][4];
#pragma unroll
        for (int x = 0; x < 8; x++) p[x >> 2][x & 3] = lds128(red + (x & 3) * CV_REDW + (x >> 2) * 1536);
        yo[0] = conv_sum(p[0]);
        if (warp < 11) {
#pragma unroll
          for (int x = 0; x < 4; x++) p[0][x] = lds128(red + x * CV_REDW + 3072);
          yo[192] = conv_sum(p[0]);
        }
        yo[96] = conv_sum(p[1]);
        __syncwarp();
        if (one) mbar_arrive(sb + (i + 4 == R.ncv ? B_PDONE : B_SFREE + 8 * (i & 1)));
        if (i + 3 == R.ncv) {
          bar_sync(1, 96);
          if (warp == 11 && one) { fence_async_smem(); mbar_arrive(sb + B_EMPTY + 8); }
          __syncwarp();
        }
      }
      bar_sync(1, 96);
      if (warp == 11 && one) {
        TLREC(7);
        mbar_arrive(sb + B_KVDONE);
        signal(S, C_Y, EPOCH / 132);
        if (R.sg >= 0) mbar_wait_guarded(sb + B_DONE, t0);
      }
    }
    TLEND();
  } else {
    asm volatile("barrier.cluster.arrive.relaxed.aligned;" ::: "memory");
    if (bid < 128) {
      float c[36], s[4];
#pragma unroll
      for (int i = 0; i < 18; i++) { c[2 * i] = bf_lo(xr[i]); c[2 * i + 1] = bf_hi(xr[i]); }
#pragma unroll
      for (int i = 0; i < 36; i++) s[i & 3] = i < 4 ? c[i] : s[i & 3] + c[i];
      const float ml = ((s[0] + s[1]) + (s[2] + s[3])) * (1.0f / 36.0f);
#pragma unroll
      for (int i = 0; i < 36; i++) { c[i] -= ml; s[i & 3] = i < 4 ? c[i] * c[i] : fmaf(c[i], c[i], s[i & 3]); }
      float m = ml, q = (s[0] + s[1]) + (s[2] + s[3]), n2 = 18.f;
#pragma unroll
      for (int o = 1; o < 16; o <<= 1) {
        const float mo = __shfl_xor_sync(0xffffffffu, m, o), qo = __shfl_xor_sync(0xffffffffu, q, o);
        const float dl = m - mo;
        q = fmaf(dl * dl, n2, q + qo);
        m = fmaf(dl, -0.5f, m);
        n2 *= 2.f;
      }
      const float var = q * (1.0f / 576.0f);
      float mb, rinv, mb2, rinv2;
      ln_finish(m, var, mb, rinv);
      ln_finish((m - mb) * rinv, var * rinv * rinv, mb2, rinv2);
      const float ca = rinv * rinv2, cb = fmaf(ml - mb, rinv, -mb2) * rinv2;
      uint2* dst = reinterpret_cast<uint2*>(S->h) + ((row >> 6) * 18 + ((lane >> 3) & 1)) * 512 + (row & 63) * 8 + ((lane & 7) ^ (row & 6));
#pragma unroll
      for (int j = 0; j < 9; j++)
        dst[1024 * j] = make_uint2(pack_bf16(fmaf(c[4 * j], ca, cb), fmaf(c[4 * j + 1], ca, cb)), pack_bf16(fmaf(c[4 * j + 2], ca, cb), fmaf(c[4 * j + 3], ca, cb)));
      const uint32_t rh = pack_bf16(rinv, rinv);
      if (!(lane & 15)) S->stats[row] = make_uint4(pack_bf16(mb, mb), rh, pack_bf16(rinv - bf_lo(rh), rinv - bf_lo(rh)), 0);
      __syncwarp();
      bar_arrive(2, 288);
    }
    asm volatile("setmaxnreg.inc.sync.aligned.u32 224;");
    asm volatile("barrier.cluster.wait.aligned;" ::: "memory");
    const int wg = warp >> 2, w = warp & 3, g = lane >> 2, t = lane & 3, wtid = tid & 127;
    const bool elect = wtid == 0;
    const uint64_t da0 = make_desc(sb + wg * 8192, 8192, 1024, 1);
    const uint32_t swz = ((lane >> 4) * 8 + (lane & 7)) * 128 + (((2 * w + ((lane >> 3) & 1)) ^ (lane & 7)) << 4);
    const uint32_t stg = sb + (wg ? SM_ST1 : SM_DED), ka0 = (8 * w + g + t + 1) * 4;
    uint32_t a[64];
    {
      auto mainloop = [&](auto&& mma) {
        Ring r{0, 0};
        uint32_t rel = 0;
#pragma unroll 1
        for (int kb = 0; kb < G1_KB; kb++, r.next()) {
          if (kb == G1_KB - G1_TAIL && wg) {
            wg_wait<0>();
            if (elect) mbar_arrive(rel);
            rel = 0;
            {
              mbar_wait(sb + B_MISC, 0);
              conv_lda_all(a, sb + SM_CV + 16384 + CV_K + ka0);
            }
            bar_sync(5, 256);
          }
          mbar_wait(sb + B_FULL + 8 * r.s, r.ph);
          if (kb == 0 && warp == 0) TLREC(3);
          wg_fence();
          mma(r.s * (SLOT >> 4), kb);
          wg_commit();
          if (kb == G1_KB - 1) break;
          wg_wait<1>();
          if (elect && rel) mbar_arrive(rel);
          rel = sb + B_EMPTY + 8 * r.s;
        }
        bar_arrive(5, 256);
        wg_wait<0>();
      };
      float hb[4];
      auto staged = [&](int second) {
        if (!w) TLREC(4 + wg);
        if (lane == 0) mbar_arrive(sb + B_G1DONE);
        mbar_wait(sb + B_MISC, 0);
#pragma unroll
        for (int i = 0; i < 4; i++) hb[i] = 0.5f * bf_lo(lds16(sb + SM_B1 + (warp * 16 + g + (i & 1) * 8 + (i >> 1) * second) * 2));
        mbar_wait(sb + B_KVDONE, 0);
        if (wg) mbar_wait(sb + B_G1DONE, 0);
      };
      if (R.at != 15) {
        const uint64_t db0 = make_desc(sb + 16384, 4096, 512, 2);
        float acc[80];
        mainloop([&](uint32_t o, int kb) {
#pragma unroll
          for (int k = 0; k < 4; k++) wgmma_ss_n160_t11(acc, da0 + o + k * 128, db0 + o + k * 64, k ? 1 : kb);
        });
        pin_regs<80>(acc);
        staged(0);
        gelu_stage<40>(acc, hb, stg + swz, 2, lane ? 0 : sb + B_STG + 8 * wg + 16);
      } else {
        const uint64_t db0 = make_desc(sb + 24576, 4096, 512, 2);
        float acc[96];
        auto block = [&](float* d, uint64_t da, uint64_t db, int kb) {
#pragma unroll
          for (int k = 0; k < 4; k++) wgmma_ss_n96_t11(d, da + k * 128, db + k * 64, k ? 1 : kb);
        };
        if (wg) mainloop([&](uint32_t o, int kb) { block(acc, da0 + o, db0 + o, kb); block(acc + 48, da0 + o + 512, db0 + o, kb); });
        else mainloop([&](uint32_t o, int kb) { block(acc, da0 + o, db0 + o, kb); });
        pin_regs<96>(acc);
        staged(64);
        gelu_stage<48>(acc, hb, stg + swz, 1 + wg, lane ? 0 : sb + B_STG + 8 * wg + 16);
      }
      __syncwarp();
      if (lane == 0) mbar_arrive(sb + B_STG + 8 * wg);
    }
    {
      if (!wg) conv_lda_all(a, sb + SM_CV + 16384 + wg * CV_K + ka0);
#pragma unroll 1
      for (int i = wg; i < R.ncv; i += 2) {
        const bool more = i + 2 < R.ncv;
        const uint32_t dd = lds16(sb + SM_D + (R.ch + i) * 2);
        a[0] = badd2(a[0], ka0 == 32 ? dd : 0); a[2] = badd2(a[2], ka0 == 16 ? dd : 0);
        float acc[128];
        mbar_wait(sb + B_UFULL + 8 * (i & 3), (i >> 2) & 1);
        bar_sync(5 + wg, 256);
        const bool last = i + 1 == R.ncv;
        if (last && elect) mbar_arrive(sb + B_EMPTY);
        if (!w && i < 4) TLREC(22 + i);
        wg_fence();
        conv_mma(acc, a, make_desc(sb + cv_in(i), 4096, 128, 0));
        wg_commit();
        if (!last) bar_arrive(5 + (wg ^ 1), 256);
        if (more) {
          mbar_wait(sb + B_SFREE + 8 * wg, (i >> 1) & 1);
          mbar_wait(sb + B_KFULL + 8 * ((i + 2) & 3), ((i + 2) >> 2) & 1);
        } else if (last) mbar_wait(sb + B_PDONE, 0);
        wg_wait<0>();
        pin_regs<128>(acc);
        if (lane == 0) mbar_arrive(sb + B_CEMPTY + 8 * (i & 3));
        if (last && elect) mbar_arrive(sb + B_EMPTY + 8);
        const uint32_t red = sb + cv_red(i, R.ncv), ka = sb + cv_taps(i + 2) + ka0;
        if (lane < 8 * w) sts32(red + w * CV_REDW + lane * 4, 0);
        const uint32_t wr = red + w * CV_REDW + (8 * (3 - t + w) + g) * 4;
        if (more) conv_drain<true>(acc, wr, a, ka); else conv_drain<false>(acc, wr, a, ka);
        __syncwarp();
        if (lane == 0) mbar_arrive(sb + B_STG + 8 * wg + (more ? 0 : 16));
      }
      if (!w) TLREC(20 + wg);
    }
    if (R.sg >= 0) {
      const int srow = R.sg * 64 + warp * 16;
      const uint64_t db0 = make_desc(sb + 16384, 16, 1024, 1);
      const uint32_t xo = sb + SM_CV + warp * 2304, xa = xo + (lane & 15) * 144;
      float acc[72];
      Ring r{G1_KB % NSTAGE, (G1_KB / NSTAGE) & 1};
      bar_sync(8, 256);
      uint32_t rel = 0;
#pragma unroll 1
      for (int kb = 0; kb < G2_KB; kb++, r.next()) {
        if (kb == G2_KB - G2_TAIL && wg) {
          wg_wait<0>();
          if (elect) mbar_arrive_remote(rel);
          rel = 0;
          bar_sync(7, 256);
        }
        mbar_wait(sb + B_FULL + 8 * r.s, r.ph);
        if (kb == 0 && !w) TLREC(17 + wg);
        if (kb == 8 && warp == 0) TLREC(26);
        if (kb == 20 && warp == 0) TLREC(8);
        if (kb == 27 && warp == 0) TLREC(30);
        const uint64_t da = da0 + r.s * (SLOT >> 4), db = db0 + r.s * (SLOT >> 4);
        wg_fence();
        wgmma_ss_n144_t10(acc, da, db, kb);
#pragma unroll
        for (int k = 1; k < 4; k++) wgmma_ss_n144_t10(acc, da + k * 128, db + k * 2, 1);
        wg_commit();
        if (kb == G2_KB - 1) break;
        wg_wait<1>();
        if (elect && rel) mbar_arrive_remote(rel);
        rel = kb == G2_KB - NSTAGE ? mapa(sb + B_XRDY, rank ^ 1) : sb + B_EMPTY + 8 * r.s;
      }
      if (!wg) bar_arrive(7, 256);
      const uint32_t xz = sb + XSLOT * SLOT + wg * 10240 + wtid * 16;
      const uint32_t rz = mapa(xz, rank ^ 1), rb = mapa(sb + B_XFULL + 16 * wg, rank ^ 1);
      mbar_wait(sb + B_XRDY, 0);
      wg_wait<0>();
      pin_regs<72>(acc);
      if (!w) TLREC(28 + wg);
#pragma unroll
      for (int i = 0; i < 32; i += 8)
        asm volatile("st.async.weak.shared::cluster.mbarrier::complete_tx::bytes.v4.b32 [%0], {%1,%2,%3,%4}, [%5];"
                     :: "r"(rz + i * 256), "r"(pack_bf16(acc[i], acc[i + 1])), "r"(pack_bf16(acc[i + 2], acc[i + 3])),
                        "r"(pack_bf16(acc[i + 4], acc[i + 5])), "r"(pack_bf16(acc[i + 6], acc[i + 7])), "r"(rb + (i < 8 * XP ? 0 : 8)) : "memory");
      asm volatile("st.async.weak.shared::cluster.mbarrier::complete_tx::bytes.v2.b32 [%0], {%1,%2}, [%3];"
                   :: "r"(rz + 8192), "r"(pack_bf16(acc[32], acc[33])), "r"(pack_bf16(acc[34], acc[35])), "r"(rb + 8) : "memory");
      uint32_t xx[18], ss[18];
      mbar_wait(sb + B_XY, 0);
      {
        const uint32_t ya = sb + SM_DED + wg * 9216 + swz;
        const uint4 st0 = lds128(sb + SM_ST + (warp * 16 + g) * 16), st1 = lds128(sb + SM_ST + (warp * 16 + g + 8) * 16);
        const float hb0 = 0.5f * bf_lo(lds16(sb + SM_B2 + (warp * 16 + g) * 2)), hb1 = 0.5f * bf_lo(lds16(sb + SM_B2 + (warp * 16 + g + 8) * 2));
#pragma unroll
        for (int q = 0; q < 8; q += 2) { ldsm4(xx + 2 * q, xa + (lane >> 4) * 16 + q * 16); ldsm4t(ss + 2 * q, ya + q * 1024); }
        ldsm2(xx + 16, xa + 128);
        ldsm2t(ss + 16, ya + 8 * 1024);
#pragma unroll
        for (int i = 0; i < 18; i++) {
          const uint4& st = (i & 1) ? st1 : st0;
          const uint32_t c = bsub2(xx[i], st.x);
          ss[i] = bmul2(bfma2(c, st.y, bmul2(c, st.z)), ss[i]);
        }
#pragma unroll
        for (int i = 36; i < 72; i++) acc[i] = fmaf(acc[i], 0.5f, (i & 2) ? hb1 : hb0);
      }
      char* const op = reinterpret_cast<char*>(P.out) + srow * (D_ * 2) + R.dk * 16 + lane * 16;
      uint32_t oo[5];
#pragma unroll
      for (int j = 0; j < 5; j++) oo[j] = ((lane + 32 * j) * 57 >> 9) * (D_ * 2 - 144) + j * 512;
#pragma unroll
      for (int q = 0; q < 5; q++) {
        if (q == 0 || q == XP) mbar_wait_cluster(sb + B_XFULL + 16 * wg + (q ? 8 : 0), 0);
        if (!w && !q) TLREC(9 + wg);
        const uint4 v = lds128(xz + q * 2048);
        const uint32_t pv[4] = {v.x, v.y, v.z, v.w};
#pragma unroll
        for (int i = 4 * q; i < 4 * q + 4 && i < 18; i++)
          xx[i] = bfma2(ss[i], pack_bf16(silu_half(fmaf(bf_lo(pv[i & 3]), 0.5f, acc[36 + 2 * i])), silu_half(fmaf(bf_hi(pv[i & 3]), 0.5f, acc[37 + 2 * i]))), xx[i]);
        if (q < 4) stsm4(xa + (lane >> 4) * 16 + q * 32, xx[4 * q], xx[4 * q + 1], xx[4 * q + 2], xx[4 * q + 3]);
        else stsm2(xa + 128, xx[16], xx[17]);
      }
      __syncwarp();
      if (lane == 0) mbar_arrive(sb + B_DONE);
#pragma unroll
      for (int j = 0; j < 5; j++)
        if (j < 4 || lane < 16) *reinterpret_cast<uint4*>(op + oo[j]) = lds128(xo + (lane + 32 * j) * 16);
      if (!w) TLREC(11 + wg);
    }
    TLEND();
  }
}

typedef CUresult (*EncodeFn)(CUtensorMap*, CUtensorMapDataType, cuuint32_t, void*, const cuuint64_t*, const cuuint64_t*, const cuuint32_t*,
                             const cuuint32_t*, CUtensorMapInterleave, CUtensorMapSwizzle, CUtensorMapL2promotion, CUtensorMapFloatOOBfill);

void make_map(EncodeFn fn, CUtensorMap* m, const void* ptr, int rank, const cuuint64_t* dims, const cuuint64_t* strides, const cuuint32_t* box,
              CUtensorMapSwizzle sw) {
  const cuuint32_t es[3] = {1, 1, 1};
  fn(m, CU_TENSOR_MAP_DATA_TYPE_BFLOAT16, rank, const_cast<void*>(ptr), dims, strides, box, es, CU_TENSOR_MAP_INTERLEAVE_NONE, sw,
     CU_TENSOR_MAP_L2_PROMOTION_L2_256B, CU_TENSOR_MAP_FLOAT_OOB_FILL_NONE);
}

void make_roles(Role* R) {
  int nl = 0, ch = 0;
  for (int gi = 0; gi < 8; gi++)
    for (int b = 0; b < 132; b++) {
      const int c = b >> 1, rank = b & 1;
      int g, idx;
      if (c < 4) { g = 0; idx = 4 + c; }
      else if (c < 36) { g = (c - 4) & 7; idx = (c - 4) >> 3; }
      else if (c < 64) { g = 1 + (c - 36) % 7; idx = 4 + (c - 36) / 7; }
      else { g = c - 58; idx = 8; }
      if (g != gi) continue;
      Role& r = R[b];
      r.sg = (int8_t)(idx < 8 ? 2 * (2 * g + (idx >> 2)) : -1);
      r.dk = (int8_t)((idx & 3) * 18 + rank * 9);
      r.ds = (int8_t)((idx & 3) * 18 + (rank ^ 1) * 9);
      if (idx < (g < 2 ? 6 : 7)) {
        const int c1 = (g < 2 ? 6 * g : 7 * g - 2) + idx;
        r.fg = (int8_t)((2 * (c1 / 3) + rank) * 2); r.at = (int8_t)(c1 % 3 * 5); r.ncv = NCV_REG;
      } else {
        r.fg = (int8_t)(3 * nl++); r.at = 15; r.ncv = idx < 8 ? NCV_LEFT : NCV_LONG;
      }
      r.ch = (int16_t)ch;
      ch += r.ncv;
    }
}

}

extern "C" void kernel_launch(void* const* d_in, const int* in_sizes, int n_in, void* d_out, int out_size) {
  static Params P;
  static Hot H;
  static const void* cached[5] = {nullptr, nullptr, nullptr, nullptr, nullptr};
  const void* now[5] = {d_in[0], d_in[1], d_in[2], d_in[7], d_in[9]};
  bool same = true;
  for (int i = 0; i < 5; i++) { same = same && cached[i] == now[i]; cached[i] = now[i]; }
  if (!same) {
    void* fp = nullptr;
    cudaDriverEntryPointQueryResult qr;
    cudaGetDriverEntryPoint("cuTensorMapEncodeTiled", &fp, cudaEnableDefault, &qr);
    EncodeFn fn = (EncodeFn)fp;
    void* ps;
    cudaGetSymbolAddress(&ps, g_scratch);
    H.S = (Scratch*)ps;
    const void *py = (char*)ps + offsetof(Scratch, y), *pb = (char*)ps + offsetof(Scratch, ub);
    { cuuint64_t d[3] = {64, S_, F_ / 64}, s[2] = {F_ * 2, 128}; cuuint32_t b[3] = {64, 64, 2}; make_map(fn, &P.m_w1, d_in[7], 3, d, s, b, CU_TENSOR_MAP_SWIZZLE_128B);
      b[2] = 3; make_map(fn, &P.m_w1l, d_in[7], 3, d, s, b, CU_TENSOR_MAP_SWIZZLE_128B); }
    { cuuint64_t d[3] = {64, F_, S_ / 64}, s[2] = {S_ * 2, 128}; cuuint32_t b[3] = {64, 64, 2}; make_map(fn, &P.m_w2, d_in[9], 3, d, s, b, CU_TENSOR_MAP_SWIZZLE_128B); }
    { cuuint64_t d[2] = {D_, S_}, s[1] = {D_ * 2}; cuuint32_t b[2] = {72, 16}; make_map(fn, &P.m_x, d_in[0], 2, d, s, b, CU_TENSOR_MAP_SWIZZLE_NONE);
      b[0] = 96; b[1] = 20; make_map(fn, &P.m_k, d_in[1], 2, d, s, b, CU_TENSOR_MAP_SWIZZLE_NONE);
      b[1] = 17; make_map(fn, &P.m_v, d_in[2], 2, d, s, b, CU_TENSOR_MAP_SWIZZLE_NONE); }
    { cuuint64_t d[3] = {64, D_, S_ / 64}, s[2] = {S_ * 2, 128}; cuuint32_t b[3] = {64, 72, 2}; make_map(fn, &P.m_y, py, 3, d, s, b, CU_TENSOR_MAP_SWIZZLE_128B); }
    { cuuint64_t d[3] = {2048, D_ / 2, 4}, s[2] = {16384, 4096}; cuuint32_t b[3] = {16, 48, 2}; make_map(fn, &P.m_ub, pb, 3, d, s, b, CU_TENSOR_MAP_SWIZZLE_32B); }
    make_roles(P.role);
    cudaFuncSetAttribute(fused_kernel, cudaFuncAttributeMaxDynamicSharedMemorySize, SM_TOTAL);
  }
  H.x = (const __nv_bfloat16*)d_in[0];
  H.shift_k = (const __nv_bfloat16*)d_in[3]; H.ssm_k = (const __nv_bfloat16*)d_in[4]; H.ssm_D = (const __nv_bfloat16*)d_in[5];
  H.b1 = (const __nv_bfloat16*)d_in[8]; P.b2 = (const __nv_bfloat16*)d_in[10]; P.out = (__nv_bfloat16*)d_out;
  fused_kernel<<<132, 384, SM_TOTAL>>>(H, P);
}
```

```cpp
#include <cuda_runtime.h>
#include <cuda.h>
#include <cuda_bf16.h>
#include <stddef.h>
#include <stdint.h>

namespace {

constexpr int S_ = 2048, D_ = 576, F_ = 4608;
constexpr int NSTAGE = 5, SLOT = 36864;
constexpr int G1_KB = 32, G2_KB = 36;
constexpr int G1_BYTES = 36864, G2_BYTES = 16384 + 18432;
#define NCV_LEFT 4
constexpr int NCV_REG = 4, NCV_LONG = (D_ - 108 * NCV_REG - 20 * NCV_LEFT) / 4;
static_assert(108 * NCV_REG + 20 * NCV_LEFT + 4 * NCV_LONG == D_, "conv split");
constexpr int KV_ROUNDS = 6;
#define XP 2
#define TUNED(name, idx, val) constexpr int name = val
constexpr int G1_TAIL = 4, G2_TAIL = 3;
constexpr int KV0 = 5;

constexpr int CV_K = 4224, CV_REDW = 2112 * 2;
constexpr int SM_DED = NSTAGE * SLOT;
constexpr int SM_CV = SM_DED + 20480;
constexpr int SM_ST1 = 0;
constexpr int SM_ST = SM_CV + 18432, SM_B2 = SM_ST + 2048;
constexpr int SM_B1 = SM_CV + 2 * (8192 + CV_K), SM_D = SM_B1 + 384;
constexpr int SM_BAR = SM_D + 1152;
constexpr int SM_TOTAL = SM_BAR + 768;
static_assert(G1_KB % NSTAGE == 2, "slots 0 and 1 hold the last GEMM1 k-blocks and the last two of the first GEMM2 stages");
static_assert(NCV_REG == 4 && NCV_LEFT == 4 && NCV_LONG % 4 == 0, "the last two channels use buffers 2 and 3");
constexpr int XSLOT = (G1_KB + G2_KB) % NSTAGE;
__device__ __forceinline__ uint32_t kv_buf(int q) { return q == 2 ? SM_DED : SM_CV + q * 8192; }
__device__ __forceinline__ uint32_t cv_red(int i, int n) { return i + 2 == n ? SM_CV : (i & 1) && i + 1 < n ? SLOT + 16384 : SM_DED; }
__device__ __forceinline__ uint32_t cv_in(int i) { return (i & 2 ? SLOT : SM_CV) + (i & 1) * 8192; }
__device__ __forceinline__ uint32_t cv_taps(int i) { return (i & 2 ? SM_ST1 + 24576 : SM_CV + 16384) + (i & 1) * CV_K; }
constexpr int bar_at(int i) { return SM_BAR + 8 * i; }
constexpr int B_FULL = bar_at(0)  , B_KFULL = bar_at(5)  , B_UFULL = bar_at(9)  , B_KVDONE = bar_at(13), B_STORED = bar_at(14)  ,
              B_XFULL = bar_at(16)  , B_XY = bar_at(20), B_MISC = bar_at(21),
              B_EMPTY = bar_at(22)  , B_XRDY = bar_at(27),
              B_SFREE = bar_at(28)  , B_PDONE = bar_at(30),
              B_CEMPTY = bar_at(31)  , B_STG = bar_at(35)  ,
              B_G1DONE = bar_at(39), B_DONE = bar_at(40);
constexpr int C_H = 0, C_KV = 1, C_U = 2  , C_Y = 4, C_SYNC = 5, C_EPOCH = 6, C_COUNT = 7;
constexpr uint32_t EPOCH = 128 * 33;

struct Scratch {
  uint32_t cnt[C_COUNT * 32];
  alignas(1024) uint4 stats[S_];
  alignas(1024) __nv_bfloat16 h[S_ * D_];
  alignas(1024) __nv_bfloat16 ub[D_ * 4096];
  alignas(1024) __nv_bfloat16 y[D_ * S_];
  alignas(1024) __nv_bfloat16 u[D_ * F_];
};
__device__ Scratch g_scratch;

struct Hot {
  const __nv_bfloat16 *x, *shift_k, *ssm_k, *ssm_D, *b1;
  Scratch* S;
};
struct Role {
  int8_t fg;
  int8_t at;
  int8_t sg;
  int8_t dk, ds;
  int8_t ncv;
  int16_t ch;
};
struct Params {
  const __nv_bfloat16* b2;
  __nv_bfloat16* out;
  Role role[132];
  CUtensorMap m_w1, m_w1l, m_w2, m_x, m_y, m_k, m_v, m_ub;
};

#define TLREC(i) do { } while (0)
#define TLEND() do { } while (0)

__device__ __forceinline__ uint32_t smem_u32(const void* p) { return (uint32_t)__cvta_generic_to_shared(p); }
__device__ __forceinline__ void mbar_init(uint32_t bar, uint32_t cnt) { asm volatile("mbarrier.init.shared::cta.b64 [%0], %1;" :: "r"(bar), "r"(cnt) : "memory"); }
__device__ __forceinline__ void mbar_expect_tx(uint32_t bar, uint32_t bytes) { asm volatile("mbarrier.arrive.expect_tx.shared::cta.b64 _, [%0], %1;" :: "r"(bar), "r"(bytes) : "memory"); }
__device__ __forceinline__ void mbar_arrive(uint32_t bar) { asm volatile("mbarrier.arrive.shared::cta.b64 _, [%0];" :: "r"(bar) : "memory"); }
__device__ __forceinline__ uint32_t mapa(uint32_t addr, uint32_t cta) { uint32_t r; asm volatile("mapa.shared::cluster.u32 %0, %1, %2;" : "=r"(r) : "r"(addr), "r"(cta)); return r; }
__device__ __forceinline__ void mbar_arrive_remote(uint32_t rbar) { asm volatile("mbarrier.arrive.shared::cluster.b64 _, [%0];" :: "r"(rbar) : "memory"); }
__device__ __forceinline__ uint32_t clk() { uint32_t c; asm volatile("mov.u32 %0, %%clock;" : "=r"(c)); return c; }
__device__ __forceinline__ bool elect_one() {
  uint32_t p; asm volatile("{ .reg .pred p; elect.sync _|p, 0xffffffff; selp.u32 %0, 1, 0, p; }" : "=r"(p)); return p;
}
__device__ __forceinline__ void guard(uint32_t t0) { if ((int32_t)(clk() - t0) < 0) __trap(); }
__device__ __forceinline__ void mbar_wait(uint32_t bar, uint32_t parity) {
  asm volatile("{\n .reg .pred p;\n W_%=:\n mbarrier.try_wait.parity.shared::cta.b64 p, [%0], %1;\n @!p bra W_%=;\n }" :: "r"(bar), "r"(parity) : "memory");
}
__device__ __forceinline__ void mbar_wait_cluster(uint32_t bar, uint32_t parity) {
  asm volatile("{\n .reg .pred p;\n W_%=:\n mbarrier.try_wait.parity.acquire.cluster.shared::cta.b64 p, [%0], %1;\n @!p bra W_%=;\n }" :: "r"(bar), "r"(parity) : "memory");
}
__device__ __forceinline__ bool mbar_try(uint32_t bar, uint32_t parity) {
  uint32_t ok;
  asm volatile("{ .reg .pred p; mbarrier.try_wait.parity.shared::cta.b64 p, [%1], %2, 100000; selp.u32 %0, 1, 0, p; }" : "=r"(ok) : "r"(bar), "r"(parity) : "memory");
  return ok;
}
__device__ __forceinline__ bool mbar_test(uint32_t bar, uint32_t parity) {
  uint32_t ok;
  asm volatile("{ .reg .pred p; mbarrier.test_wait.parity.shared::cta.b64 p, [%1], %2; selp.u32 %0, 1, 0, p; }" : "=r"(ok) : "r"(bar), "r"(parity) : "memory");
  return ok;
}
__device__ __forceinline__ void mbar_wait_guarded(uint32_t bar, uint32_t t0, uint32_t parity = 0) { while (!mbar_try(bar, parity)) guard(t0); }
__device__ __forceinline__ void tma2d(uint32_t dst, const CUtensorMap* m, int c0, int c1, uint32_t bar) {
  asm volatile("cp.async.bulk.tensor.2d.shared::cluster.global.mbarrier::complete_tx::bytes [%0], [%1, {%3, %4}], [%2];"
               :: "r"(dst), "l"(m), "r"(bar), "r"(c0), "r"(c1) : "memory");
}
__device__ __forceinline__ void tma3d(uint32_t dst, const CUtensorMap* m, int c0, int c1, int c2, uint32_t bar) {
  asm volatile("cp.async.bulk.tensor.3d.shared::cluster.global.mbarrier::complete_tx::bytes [%0], [%1, {%3, %4, %5}], [%2];"
               :: "r"(dst), "l"(m), "r"(bar), "r"(c0), "r"(c1), "r"(c2) : "memory");
}
__device__ __forceinline__ void bulk_store(void* dst, uint32_t src, uint32_t bytes) {
  asm volatile("cp.async.bulk.global.shared::cta.bulk_group [%0], [%1], %2;" :: "l"(dst), "r"(src), "r"(bytes) : "memory");
}
__device__ __forceinline__ void bulk_load(uint32_t dst, const void* src, uint32_t bytes, uint32_t bar) {
  asm volatile("cp.async.bulk.shared::cluster.global.mbarrier::complete_tx::bytes [%0], [%1], %2, [%3];" :: "r"(dst), "l"(src), "r"(bytes), "r"(bar) : "memory");
}
__device__ __forceinline__ void tma3d_store(const CUtensorMap* m, uint32_t src, int c0, int c1, int c2) {
  asm volatile("cp.async.bulk.tensor.3d.global.shared::cta.bulk_group [%0, {%2, %3, %4}], [%1];" :: "l"(m), "r"(src), "r"(c0), "r"(c1), "r"(c2) : "memory");
}
__device__ __forceinline__ void bulk_commit() { asm volatile("cp.async.bulk.commit_group;" ::: "memory"); }
__device__ __forceinline__ void bulk_wait_all() { asm volatile("cp.async.bulk.wait_group 0;" ::: "memory"); }
__device__ __forceinline__ void fence_async_smem() { asm volatile("fence.proxy.async.shared::cta;" ::: "memory"); }
__device__ __forceinline__ void fence_async_global() { asm volatile("fence.proxy.async.global;" ::: "memory"); }
__device__ __forceinline__ uint32_t ld_cnt(Scratch* S, int c) { uint32_t v; asm volatile("ld.relaxed.gpu.global.u32 %0, [%1];" : "=r"(v) : "l"(S->cnt + c * 32) : "memory"); return v; }
__device__ __forceinline__ void signal(Scratch* S, int c, uint32_t inc) { asm volatile("red.release.gpu.global.add.u32 [%0], %1;" :: "l"(S->cnt + c * 32), "r"(inc) : "memory"); }
__device__ __forceinline__ bool reached(Scratch* S, int c, uint32_t ep) { return ld_cnt(S, c) - ep >= EPOCH; }
__device__ __forceinline__ void await(Scratch* S, int c, uint32_t ep) { while (!reached(S, c, ep)) { } }
__device__ __forceinline__ void bar_sync(int id, int n) { asm volatile("bar.sync %0, %1;" :: "r"(id), "r"(n) : "memory"); }
__device__ __forceinline__ void bar_arrive(int id, int n) { asm volatile("bar.arrive %0, %1;" :: "r"(id), "r"(n) : "memory"); }
__device__ __forceinline__ void wg_fence() { asm volatile("wgmma.fence.sync.aligned;" ::: "memory"); }
__device__ __forceinline__ void wg_commit() { asm volatile("wgmma.commit_group.sync.aligned;" ::: "memory"); }
template <int N> __device__ __forceinline__ void wg_wait() { asm volatile("wgmma.wait_group.sync.aligned %0;" :: "n"(N) : "memory"); }
template <int N> __device__ __forceinline__ void pin_regs(float* a) {
#pragma unroll
  for (int i = 0; i < N; i++) asm volatile("" : "+f"(a[i]) :: "memory");
}
__device__ __forceinline__ uint64_t make_desc(uint32_t addr, uint32_t lbo, uint32_t sbo, uint32_t swz) {
  return (uint64_t)((addr & 0x3FFFF) >> 4) | ((uint64_t)(lbo >> 4) << 16) | ((uint64_t)(sbo >> 4) << 32) | ((uint64_t)swz << 62);
}
__device__ __forceinline__ uint32_t pack_bf16(float lo, float hi) { uint32_t r; asm("cvt.rn.bf16x2.f32 %0, %1, %2;" : "=r"(r) : "f"(hi), "f"(lo)); return r; }
__device__ __forceinline__ float bf_lo(uint32_t p) { return __uint_as_float(p << 16); }
__device__ __forceinline__ float bf_hi(uint32_t p) { return __uint_as_float(p & 0xffff0000u); }
__device__ __forceinline__ float round_bf16(float v) { return bf_lo(pack_bf16(v, 0.f)); }
__device__ __forceinline__ uint32_t bmul2(uint32_t a, uint32_t b) { uint32_t r; asm("mul.rn.bf16x2 %0, %1, %2;" : "=r"(r) : "r"(a), "r"(b)); return r; }
__device__ __forceinline__ uint32_t badd2(uint32_t a, uint32_t b) { uint32_t r; asm("add.rn.bf16x2 %0, %1, %2;" : "=r"(r) : "r"(a), "r"(b)); return r; }
__device__ __forceinline__ uint32_t bfma2(uint32_t a, uint32_t b, uint32_t c) { uint32_t r; asm("fma.rn.bf16x2 %0, %1, %2, %3;" : "=r"(r) : "r"(a), "r"(b), "r"(c)); return r; }
__device__ __forceinline__ uint32_t bsub2(uint32_t a, uint32_t b) { uint32_t r; asm("sub.rn.bf16x2 %0, %1, %2;" : "=r"(r) : "r"(a), "r"(b)); return r; }
__device__ __forceinline__ float tanh_fast(float v) { float r; asm("tanh.approx.f32 %0, %1;" : "=f"(r) : "f"(v)); return r; }
__device__ __forceinline__ float gelu_half(float h) {
  return fmaf(h, tanh_fast(h * fmaf(h * h, 8.0f * 0.7978845608028654f * 0.044715f, 2.0f * 0.7978845608028654f)), h);
}
__device__ __forceinline__ float silu_half(float h) { return fmaf(h, tanh_fast(h), h); }
__device__ __forceinline__ uint32_t ldg32(const void* p) { uint32_t v; asm volatile("ld.global.u32 %0, [%1];" : "=r"(v) : "l"(p) : "memory"); return v; }
__device__ __forceinline__ uint32_t lds32(uint32_t a) { uint32_t v; asm volatile("ld.shared.u32 %0, [%1];" : "=r"(v) : "r"(a) : "memory"); return v; }
__device__ __forceinline__ uint32_t lds16(uint32_t a) { uint32_t v; asm volatile("ld.shared.u16 %0, [%1];" : "=r"(v) : "r"(a) : "memory"); return v; }
__device__ __forceinline__ uint4 lds128(uint32_t a) { uint4 v; asm volatile("ld.shared.v4.u32 {%0,%1,%2,%3}, [%4];" : "=r"(v.x), "=r"(v.y), "=r"(v.z), "=r"(v.w) : "r"(a) : "memory"); return v; }
__device__ __forceinline__ void sts128(uint32_t a, uint32_t x, uint32_t y, uint32_t z, uint32_t w) {
  asm volatile("st.shared.v4.u32 [%0], {%1,%2,%3,%4};" :: "r"(a), "r"(x), "r"(y), "r"(z), "r"(w) : "memory");
}
__device__ __forceinline__ void sts32(uint32_t a, uint32_t v) { asm volatile("st.shared.u32 [%0], %1;" :: "r"(a), "r"(v) : "memory"); }
__device__ __forceinline__ void ldsm4(uint32_t* r, uint32_t a) {
  asm volatile("ldmatrix.sync.aligned.m8n8.x4.shared.b16 {%0,%1,%2,%3}, [%4];" : "=r"(r[0]), "=r"(r[1]), "=r"(r[2]), "=r"(r[3]) : "r"(a) : "memory");
}
__device__ __forceinline__ void ldsm2(uint32_t* r, uint32_t a) {
  asm volatile("ldmatrix.sync.aligned.m8n8.x2.shared.b16 {%0,%1}, [%2];" : "=r"(r[0]), "=r"(r[1]) : "r"(a) : "memory");
}
__device__ __forceinline__ void ldsm4t(uint32_t* r, uint32_t a) {
  asm volatile("ldmatrix.sync.aligned.m8n8.x4.trans.shared.b16 {%0,%1,%2,%3}, [%4];" : "=r"(r[0]), "=r"(r[1]), "=r"(r[2]), "=r"(r[3]) : "r"(a) : "memory");
}
__device__ __forceinline__ void ldsm2t(uint32_t* r, uint32_t a) {
  asm volatile("ldmatrix.sync.aligned.m8n8.x2.trans.shared.b16 {%0,%1}, [%2];" : "=r"(r[0]), "=r"(r[1]) : "r"(a) : "memory");
}
__device__ __forceinline__ void stsm4(uint32_t a, uint32_t r0, uint32_t r1, uint32_t r2, uint32_t r3) {
  asm volatile("stmatrix.sync.aligned.m8n8.x4.shared.b16 [%0], {%1,%2,%3,%4};" :: "r"(a), "r"(r0), "r"(r1), "r"(r2), "r"(r3) : "memory");
}
__device__ __forceinline__ void stsm2(uint32_t a, uint32_t r0, uint32_t r1) {
  asm volatile("stmatrix.sync.aligned.m8n8.x2.shared.b16 [%0], {%1,%2};" :: "r"(a), "r"(r0), "r"(r1) : "memory");
}
__device__ __forceinline__ void stsm4t(uint32_t a, uint32_t r0, uint32_t r1, uint32_t r2, uint32_t r3) {
  asm volatile("stmatrix.sync.aligned.m8n8.x4.trans.shared.b16 [%0], {%1,%2,%3,%4};" :: "r"(a), "r"(r0), "r"(r1), "r"(r2), "r"(r3) : "memory");
}

__device__ __forceinline__ void wgmma_ss_n144_t10(float* d, uint64_t da, uint64_t db, int sd) {
  asm volatile("{ .reg .pred p; setp.ne.b32 p, %74, 0;\n"
      "wgmma.mma_async.sync.aligned.m64n144k16.f32.bf16.bf16 {"
      "%0,%1,%2,%3,%4,%5,%6,%7,%8,%9,%10,%11,%12,%13,%14,%15,"
      "%16,%17,%18,%19,%20,%21,%22,%23,%24,%25,%26,%27,%28,%29,%30,%31,"
      "%32,%33,%34,%35,%36,%37,%38,%39,%40,%41,%42,%43,%44,%45,%46,%47,"
      "%48,%49,%50,%51,%52,%53,%54,%55,%56,%57,%58,%59,%60,%61,%62,%63,"
      "%64,%65,%66,%67,%68,%69,%70,%71"
      "}, %72, %73, p, 1, 1, 1, 0; }"
    : "+f"(d[0]), "+f"(d[1]), "+f"(d[2]), "+f"(d[3]), "+f"(d[4]), "+f"(d[5]), "+f"(d[6]), "+f"(d[7]),
      "+f"(d[8]), "+f"(d[9]), "+f"(d[10]), "+f"(d[11]), "+f"(d[12]), "+f"(d[13]), "+f"(d[14]), "+f"(d[15]),
      "+f"(d[16]), "+f"(d[17]), "+f"(d[18]), "+f"(d[19]), "+f"(d[20]), "+f"(d[21]), "+f"(d[22]), "+f"(d[23]),
      "+f"(d[24]), "+f"(d[25]), "+f"(d[26]), "+f"(d[27]), "+f"(d[28]), "+f"(d[29]), "+f"(d[30]), "+f"(d[31]),
      "+f"(d[32]), "+f"(d[33]), "+f"(d[34]), "+f"(d[35]), "+f"(d[36]), "+f"(d[37]), "+f"(d[38]), "+f"(d[39]),
      "+f"(d[40]), "+f"(d[41]), "+f"(d[42]), "+f"(d[43]), "+f"(d[44]), "+f"(d[45]), "+f"(d[46]), "+f"(d[47]),
      "+f"(d[48]), "+f"(d[49]), "+f"(d[50]), "+f"(d[51]), "+f"(d[52]), "+f"(d[53]), "+f"(d[54]), "+f"(d[55]),
      "+f"(d[56]), "+f"(d[57]), "+f"(d[58]), "+f"(d[59]), "+f"(d[60]), "+f"(d[61]), "+f"(d[62]), "+f"(d[63]),
      "+f"(d[64]), "+f"(d[65]), "+f"(d[66]), "+f"(d[67]), "+f"(d[68]), "+f"(d[69]), "+f"(d[70]), "+f"(d[71])
    : "l"(da), "l"(db), "r"(sd));
}

__device__ __forceinline__ void wgmma_ss_n160_t11(float* d, uint64_t da, uint64_t db, int sd) {
  asm volatile("{ .reg .pred p; setp.ne.b32 p, %82, 0;\n"
      "wgmma.mma_async.sync.aligned.m64n160k16.f32.bf16.bf16 {"
      "%0,%1,%2,%3,%4,%5,%6,%7,%8,%9,%10,%11,%12,%13,%14,%15,"
      "%16,%17,%18,%19,%20,%21,%22,%23,%24,%25,%26,%27,%28,%29,%30,%31,"
      "%32,%33,%34,%35,%36,%37,%38,%39,%40,%41,%42,%43,%44,%45,%46,%47,"
      "%48,%49,%50,%51,%52,%53,%54,%55,%56,%57,%58,%59,%60,%61,%62,%63,"
      "%64,%65,%66,%67,%68,%69,%70,%71,%72,%73,%74,%75,%76,%77,%78,%79"
      "}, %80, %81, p, 1, 1, 1, 1; }"
    : "+f"(d[0]), "+f"(d[1]), "+f"(d[2]), "+f"(d[3]), "+f"(d[4]), "+f"(d[5]), "+f"(d[6]), "+f"(d[7]),
      "+f"(d[8]), "+f"(d[9]), "+f"(d[10]), "+f"(d[11]), "+f"(d[12]), "+f"(d[13]), "+f"(d[14]), "+f"(d[15]),
      "+f"(d[16]), "+f"(d[17]), "+f"(d[18]), "+f"(d[19]), "+f"(d[20]), "+f"(d[21]), "+f"(d[22]), "+f"(d[23]),
      "+f"(d[24]), "+f"(d[25]), "+f"(d[26]), "+f"(d[27]), "+f"(d[28]), "+f"(d[29]), "+f"(d[30]), "+f"(d[31]),
      "+f"(d[32]), "+f"(d[33]), "+f"(d[34]), "+f"(d[35]), "+f"(d[36]), "+f"(d[37]), "+f"(d[38]), "+f"(d[39]),
      "+f"(d[40]), "+f"(d[41]), "+f"(d[42]), "+f"(d[43]), "+f"(d[44]), "+f"(d[45]), "+f"(d[46]), "+f"(d[47]),
      "+f"(d[48]), "+f"(d[49]), "+f"(d[50]), "+f"(d[51]), "+f"(d[52]), "+f"(d[53]), "+f"(d[54]), "+f"(d[55]),
      "+f"(d[56]), "+f"(d[57]), "+f"(d[58]), "+f"(d[59]), "+f"(d[60]), "+f"(d[61]), "+f"(d[62]), "+f"(d[63]),
      "+f"(d[64]), "+f"(d[65]), "+f"(d[66]), "+f"(d[67]), "+f"(d[68]), "+f"(d[69]), "+f"(d[70]), "+f"(d[71]),
      "+f"(d[72]), "+f"(d[73]), "+f"(d[74]), "+f"(d[75]), "+f"(d[76]), "+f"(d[77]), "+f"(d[78]), "+f"(d[79])
    : "l"(da), "l"(db), "r"(sd));
}

__device__ __forceinline__ void wgmma_ss_n96_t11(float* d, uint64_t da, uint64_t db, int sd) {
  asm volatile("{ .reg .pred p; setp.ne.b32 p, %50, 0;\n"
      "wgmma.mma_async.sync.aligned.m64n96k16.f32.bf16.bf16 {"
      "%0,%1,%2,%3,%4,%5,%6,%7,%8,%9,%10,%11,%12,%13,%14,%15,"
      "%16,%17,%18,%19,%20,%21,%22,%23,%24,%25,%26,%27,%28,%29,%30,%31,"
      "%32,%33,%34,%35,%36,%37,%38,%39,%40,%41,%42,%43,%44,%45,%46,%47"
      "}, %48, %49, p, 1, 1, 1, 1; }"
    : "+f"(d[0]), "+f"(d[1]), "+f"(d[2]), "+f"(d[3]), "+f"(d[4]), "+f"(d[5]), "+f"(d[6]), "+f"(d[7]),
      "+f"(d[8]), "+f"(d[9]), "+f"(d[10]), "+f"(d[11]), "+f"(d[12]), "+f"(d[13]), "+f"(d[14]), "+f"(d[15]),
      "+f"(d[16]), "+f"(d[17]), "+f"(d[18]), "+f"(d[19]), "+f"(d[20]), "+f"(d[21]), "+f"(d[22]), "+f"(d[23]),
      "+f"(d[24]), "+f"(d[25]), "+f"(d[26]), "+f"(d[27]), "+f"(d[28]), "+f"(d[29]), "+f"(d[30]), "+f"(d[31]),
      "+f"(d[32]), "+f"(d[33]), "+f"(d[34]), "+f"(d[35]), "+f"(d[36]), "+f"(d[37]), "+f"(d[38]), "+f"(d[39]),
      "+f"(d[40]), "+f"(d[41]), "+f"(d[42]), "+f"(d[43]), "+f"(d[44]), "+f"(d[45]), "+f"(d[46]), "+f"(d[47])
    : "l"(da), "l"(db), "r"(sd));
}

__device__ __forceinline__ void wgmma_rs_n16(float* d, const uint32_t* a, uint64_t db, int sd) {
  asm volatile("{ .reg .pred p; setp.ne.b32 p, %13, 0;\n"
      "wgmma.mma_async.sync.aligned.m64n16k16.f32.bf16.bf16 {"
      "%0,%1,%2,%3,%4,%5,%6,%7"
      "}, {%8,%9,%10,%11}, %12, p, 1, 1, 0; }"
    : "+f"(d[0]), "+f"(d[1]), "+f"(d[2]), "+f"(d[3]), "+f"(d[4]), "+f"(d[5]), "+f"(d[6]), "+f"(d[7])
    : "r"(a[0]), "r"(a[1]), "r"(a[2]), "r"(a[3]), "l"(db), "r"(sd));
}

__device__ __forceinline__ void wgmma_rs_n32(float* d, const uint32_t* a, uint64_t db, int sd) {
  asm volatile("{ .reg .pred p; setp.ne.b32 p, %21, 0;\n"
      "wgmma.mma_async.sync.aligned.m64n32k16.f32.bf16.bf16 {"
      "%0,%1,%2,%3,%4,%5,%6,%7,%8,%9,%10,%11,%12,%13,%14,%15"
      "}, {%16,%17,%18,%19}, %20, p, 1, 1, 0; }"
    : "+f"(d[0]), "+f"(d[1]), "+f"(d[2]), "+f"(d[3]), "+f"(d[4]), "+f"(d[5]), "+f"(d[6]), "+f"(d[7]),
      "+f"(d[8]), "+f"(d[9]), "+f"(d[10]), "+f"(d[11]), "+f"(d[12]), "+f"(d[13]), "+f"(d[14]), "+f"(d[15])
    : "r"(a[0]), "r"(a[1]), "r"(a[2]), "r"(a[3]), "l"(db), "r"(sd));
}

__device__ __forceinline__ void wgmma_rs_n48(float* d, const uint32_t* a, uint64_t db, int sd) {
  asm volatile("{ .reg .pred p; setp.ne.b32 p, %29, 0;\n"
      "wgmma.mma_async.sync.aligned.m64n48k16.f32.bf16.bf16 {"
      "%0,%1,%2,%3,%4,%5,%6,%7,%8,%9,%10,%11,%12,%13,%14,%15,"
      "%16,%17,%18,%19,%20,%21,%22,%23"
      "}, {%24,%25,%26,%27}, %28, p, 1, 1, 0; }"
    : "+f"(d[0]), "+f"(d[1]), "+f"(d[2]), "+f"(d[3]), "+f"(d[4]), "+f"(d[5]), "+f"(d[6]), "+f"(d[7]),
      "+f"(d[8]), "+f"(d[9]), "+f"(d[10]), "+f"(d[11]), "+f"(d[12]), "+f"(d[13]), "+f"(d[14]), "+f"(d[15]),
      "+f"(d[16]), "+f"(d[17]), "+f"(d[18]), "+f"(d[19]), "+f"(d[20]), "+f"(d[21]), "+f"(d[22]), "+f"(d[23])
    : "r"(a[0]), "r"(a[1]), "r"(a[2]), "r"(a[3]), "l"(db), "r"(sd));
}

__device__ __forceinline__ void wgmma_rs_n64(float* d, const uint32_t* a, uint64_t db, int sd) {
  asm volatile("{ .reg .pred p; setp.ne.b32 p, %37, 0;\n"
      "wgmma.mma_async.sync.aligned.m64n64k16.f32.bf16.bf16 {"
      "%0,%1,%2,%3,%4,%5,%6,%7,%8,%9,%10,%11,%12,%13,%14,%15,"
      "%16,%17,%18,%19,%20,%21,%22,%23,%24,%25,%26,%27,%28,%29,%30,%31"
      "}, {%32,%33,%34,%35}, %36, p, 1, 1, 0; }"
    : "+f"(d[0]), "+f"(d[1]), "+f"(d[2]), "+f"(d[3]), "+f"(d[4]), "+f"(d[5]), "+f"(d[6]), "+f"(d[7]),
      "+f"(d[8]), "+f"(d[9]), "+f"(d[10]), "+f"(d[11]), "+f"(d[12]), "+f"(d[13]), "+f"(d[14]), "+f"(d[15]),
      "+f"(d[16]), "+f"(d[17]), "+f"(d[18]), "+f"(d[19]), "+f"(d[20]), "+f"(d[21]), "+f"(d[22]), "+f"(d[23]),
      "+f"(d[24]), "+f"(d[25]), "+f"(d[26]), "+f"(d[27]), "+f"(d[28]), "+f"(d[29]), "+f"(d[30]), "+f"(d[31])
    : "r"(a[0]), "r"(a[1]), "r"(a[2]), "r"(a[3]), "l"(db), "r"(sd));
}

__device__ __forceinline__ void wgmma_rs_n80(float* d, const uint32_t* a, uint64_t db, int sd) {
  asm volatile("{ .reg .pred p; setp.ne.b32 p, %45, 0;\n"
      "wgmma.mma_async.sync.aligned.m64n80k16.f32.bf16.bf16 {"
      "%0,%1,%2,%3,%4,%5,%6,%7,%8,%9,%10,%11,%12,%13,%14,%15,"
      "%16,%17,%18,%19,%20,%21,%22,%23,%24,%25,%26,%27,%28,%29,%30,%31,"
      "%32,%33,%34,%35,%36,%37,%38,%39"
      "}, {%40,%41,%42,%43}, %44, p, 1, 1, 0; }"
    : "+f"(d[0]), "+f"(d[1]), "+f"(d[2]), "+f"(d[3]), "+f"(d[4]), "+f"(d[5]), "+f"(d[6]), "+f"(d[7]),
      "+f"(d[8]), "+f"(d[9]), "+f"(d[10]), "+f"(d[11]), "+f"(d[12]), "+f"(d[13]), "+f"(d[14]), "+f"(d[15]),
      "+f"(d[16]), "+f"(d[17]), "+f"(d[18]), "+f"(d[19]), "+f"(d[20]), "+f"(d[21]), "+f"(d[22]), "+f"(d[23]),
      "+f"(d[24]), "+f"(d[25]), "+f"(d[26]), "+f"(d[27]), "+f"(d[28]), "+f"(d[29]), "+f"(d[30]), "+f"(d[31]),
      "+f"(d[32]), "+f"(d[33]), "+f"(d[34]), "+f"(d[35]), "+f"(d[36]), "+f"(d[37]), "+f"(d[38]), "+f"(d[39])
    : "r"(a[0]), "r"(a[1]), "r"(a[2]), "r"(a[3]), "l"(db), "r"(sd));
}

__device__ __forceinline__ void wgmma_rs_n96(float* d, const uint32_t* a, uint64_t db, int sd) {
  asm volatile("{ .reg .pred p; setp.ne.b32 p, %53, 0;\n"
      "wgmma.mma_async.sync.aligned.m64n96k16.f32.bf16.bf16 {"
      "%0,%1,%2,%3,%4,%5,%6,%7,%8,%9,%10,%11,%12,%13,%14,%15,"
      "%16,%17,%18,%19,%20,%21,%22,%23,%24,%25,%26,%27,%28,%29,%30,%31,"
      "%32,%33,%34,%35,%36,%37,%38,%39,%40,%41,%42,%43,%44,%45,%46,%47"
      "}, {%48,%49,%50,%51}, %52, p, 1, 1, 0; }"
    : "+f"(d[0]), "+f"(d[1]), "+f"(d[2]), "+f"(d[3]), "+f"(d[4]), "+f"(d[5]), "+f"(d[6]), "+f"(d[7]),
      "+f"(d[8]), "+f"(d[9]), "+f"(d[10]), "+f"(d[11]), "+f"(d[12]), "+f"(d[13]), "+f"(d[14]), "+f"(d[15]),
      "+f"(d[16]), "+f"(d[17]), "+f"(d[18]), "+f"(d[19]), "+f"(d[20]), "+f"(d[21]), "+f"(d[22]), "+f"(d[23]),
      "+f"(d[24]), "+f"(d[25]), "+f"(d[26]), "+f"(d[27]), "+f"(d[28]), "+f"(d[29]), "+f"(d[30]), "+f"(d[31]),
      "+f"(d[32]), "+f"(d[33]), "+f"(d[34]), "+f"(d[35]), "+f"(d[36]), "+f"(d[37]), "+f"(d[38]), "+f"(d[39]),
      "+f"(d[40]), "+f"(d[41]), "+f"(d[42]), "+f"(d[43]), "+f"(d[44]), "+f"(d[45]), "+f"(d[46]), "+f"(d[47])
    : "r"(a[0]), "r"(a[1]), "r"(a[2]), "r"(a[3]), "l"(db), "r"(sd));
}

__device__ __forceinline__ void wgmma_rs_n112(float* d, const uint32_t* a, uint64_t db, int sd) {
  asm volatile("{ .reg .pred p; setp.ne.b32 p, %61, 0;\n"
      "wgmma.mma_async.sync.aligned.m64n112k16.f32.bf16.bf16 {"
      "%0,%1,%2,%3,%4,%5,%6,%7,%8,%9,%10,%11,%12,%13,%14,%15,"
      "%16,%17,%18,%19,%20,%21,%22,%23,%24,%25,%26,%27,%28,%29,%30,%31,"
      "%32,%33,%34,%35,%36,%37,%38,%39,%40,%41,%42,%43,%44,%45,%46,%47,"
      "%48,%49,%50,%51,%52,%53,%54,%55"
      "}, {%56,%57,%58,%59}, %60, p, 1, 1, 0; }"
    : "+f"(d[0]), "+f"(d[1]), "+f"(d[2]), "+f"(d[3]), "+f"(d[4]), "+f"(d[5]), "+f"(d[6]), "+f"(d[7]),
      "+f"(d[8]), "+f"(d[9]), "+f"(d[10]), "+f"(d[11]), "+f"(d[12]), "+f"(d[13]), "+f"(d[14]), "+f"(d[15]),
      "+f"(d[16]), "+f"(d[17]), "+f"(d[18]), "+f"(d[19]), "+f"(d[20]), "+f"(d[21]), "+f"(d[22]), "+f"(d[23]),
      "+f"(d[24]), "+f"(d[25]), "+f"(d[26]), "+f"(d[27]), "+f"(d[28]), "+f"(d[29]), "+f"(d[30]), "+f"(d[31]),
      "+f"(d[32]), "+f"(d[33]), "+f"(d[34]), "+f"(d[35]), "+f"(d[36]), "+f"(d[37]), "+f"(d[38]), "+f"(d[39]),
      "+f"(d[40]), "+f"(d[41]), "+f"(d[42]), "+f"(d[43]), "+f"(d[44]), "+f"(d[45]), "+f"(d[46]), "+f"(d[47]),
      "+f"(d[48]), "+f"(d[49]), "+f"(d[50]), "+f"(d[51]), "+f"(d[52]), "+f"(d[53]), "+f"(d[54]), "+f"(d[55])
    : "r"(a[0]), "r"(a[1]), "r"(a[2]), "r"(a[3]), "l"(db), "r"(sd));
}

__device__ __forceinline__ void wgmma_rs_n128(float* d, const uint32_t* a, uint64_t db, int sd) {
  asm volatile("{ .reg .pred p; setp.ne.b32 p, %69, 0;\n"
      "wgmma.mma_async.sync.aligned.m64n128k16.f32.bf16.bf16 {"
      "%0,%1,%2,%3,%4,%5,%6,%7,%8,%9,%10,%11,%12,%13,%14,%15,"
      "%16,%17,%18,%19,%20,%21,%22,%23,%24,%25,%26,%27,%28,%29,%30,%31,"
      "%32,%33,%34,%35,%36,%37,%38,%39,%40,%41,%42,%43,%44,%45,%46,%47,"
      "%48,%49,%50,%51,%52,%53,%54,%55,%56,%57,%58,%59,%60,%61,%62,%63"
      "}, {%64,%65,%66,%67}, %68, p, 1, 1, 0; }"
    : "+f"(d[0]), "+f"(d[1]), "+f"(d[2]), "+f"(d[3]), "+f"(d[4]), "+f"(d[5]), "+f"(d[6]), "+f"(d[7]),
      "+f"(d[8]), "+f"(d[9]), "+f"(d[10]), "+f"(d[11]), "+f"(d[12]), "+f"(d[13]), "+f"(d[14]), "+f"(d[15]),
      "+f"(d[16]), "+f"(d[17]), "+f"(d[18]), "+f"(d[19]), "+f"(d[20]), "+f"(d[21]), "+f"(d[22]), "+f"(d[23]),
      "+f"(d[24]), "+f"(d[25]), "+f"(d[26]), "+f"(d[27]), "+f"(d[28]), "+f"(d[29]), "+f"(d[30]), "+f"(d[31]),
      "+f"(d[32]), "+f"(d[33]), "+f"(d[34]), "+f"(d[35]), "+f"(d[36]), "+f"(d[37]), "+f"(d[38]), "+f"(d[39]),
      "+f"(d[40]), "+f"(d[41]), "+f"(d[42]), "+f"(d[43]), "+f"(d[44]), "+f"(d[45]), "+f"(d[46]), "+f"(d[47]),
      "+f"(d[48]), "+f"(d[49]), "+f"(d[50]), "+f"(d[51]), "+f"(d[52]), "+f"(d[53]), "+f"(d[54]), "+f"(d[55]),
      "+f"(d[56]), "+f"(d[57]), "+f"(d[58]), "+f"(d[59]), "+f"(d[60]), "+f"(d[61]), "+f"(d[62]), "+f"(d[63])
    : "r"(a[0]), "r"(a[1]), "r"(a[2]), "r"(a[3]), "l"(db), "r"(sd));
}

__device__ __forceinline__ void wgmma_rs_n144(float* d, const uint32_t* a, uint64_t db, int sd) {
  asm volatile("{ .reg .pred p; setp.ne.b32 p, %77, 0;\n"
      "wgmma.mma_async.sync.aligned.m64n144k16.f32.bf16.bf16 {"
      "%0,%1,%2,%3,%4,%5,%6,%7,%8,%9,%10,%11,%12,%13,%14,%15,"
      "%16,%17,%18,%19,%20,%21,%22,%23,%24,%25,%26,%27,%28,%29,%30,%31,"
      "%32,%33,%34,%35,%36,%37,%38,%39,%40,%41,%42,%43,%44,%45,%46,%47,"
      "%48,%49,%50,%51,%52,%53,%54,%55,%56,%57,%58,%59,%60,%61,%62,%63,"
      "%64,%65,%66,%67,%68,%69,%70,%71"
      "}, {%72,%73,%74,%75}, %76, p, 1, 1, 0; }"
    : "+f"(d[0]), "+f"(d[1]), "+f"(d[2]), "+f"(d[3]), "+f"(d[4]), "+f"(d[5]), "+f"(d[6]), "+f"(d[7]),
      "+f"(d[8]), "+f"(d[9]), "+f"(d[10]), "+f"(d[11]), "+f"(d[12]), "+f"(d[13]), "+f"(d[14]), "+f"(d[15]),
      "+f"(d[16]), "+f"(d[17]), "+f"(d[18]), "+f"(d[19]), "+f"(d[20]), "+f"(d[21]), "+f"(d[22]), "+f"(d[23]),
      "+f"(d[24]), "+f"(d[25]), "+f"(d[26]), "+f"(d[27]), "+f"(d[28]), "+f"(d[29]), "+f"(d[30]), "+f"(d[31]),
      "+f"(d[32]), "+f"(d[33]), "+f"(d[34]), "+f"(d[35]), "+f"(d[36]), "+f"(d[37]), "+f"(d[38]), "+f"(d[39]),
      "+f"(d[40]), "+f"(d[41]), "+f"(d[42]), "+f"(d[43]), "+f"(d[44]), "+f"(d[45]), "+f"(d[46]), "+f"(d[47]),
      "+f"(d[48]), "+f"(d[49]), "+f"(d[50]), "+f"(d[51]), "+f"(d[52]), "+f"(d[53]), "+f"(d[54]), "+f"(d[55]),
      "+f"(d[56]), "+f"(d[57]), "+f"(d[58]), "+f"(d[59]), "+f"(d[60]), "+f"(d[61]), "+f"(d[62]), "+f"(d[63]),
      "+f"(d[64]), "+f"(d[65]), "+f"(d[66]), "+f"(d[67]), "+f"(d[68]), "+f"(d[69]), "+f"(d[70]), "+f"(d[71])
    : "r"(a[0]), "r"(a[1]), "r"(a[2]), "r"(a[3]), "l"(db), "r"(sd));
}

__device__ __forceinline__ void wgmma_rs_n160(float* d, const uint32_t* a, uint64_t db, int sd) {
  asm volatile("{ .reg .pred p; setp.ne.b32 p, %85, 0;\n"
      "wgmma.mma_async.sync.aligned.m64n160k16.f32.bf16.bf16 {"
      "%0,%1,%2,%3,%4,%5,%6,%7,%8,%9,%10,%11,%12,%13,%14,%15,"
      "%16,%17,%18,%19,%20,%21,%22,%23,%24,%25,%26,%27,%28,%29,%30,%31,"
      "%32,%33,%34,%35,%36,%37,%38,%39,%40,%41,%42,%43,%44,%45,%46,%47,"
      "%48,%49,%50,%51,%52,%53,%54,%55,%56,%57,%58,%59,%60,%61,%62,%63,"
      "%64,%65,%66,%67,%68,%69,%70,%71,%72,%73,%74,%75,%76,%77,%78,%79"
      "}, {%80,%81,%82,%83}, %84, p, 1, 1, 0; }"
    : "+f"(d[0]), "+f"(d[1]), "+f"(d[2]), "+f"(d[3]), "+f"(d[4]), "+f"(d[5]), "+f"(d[6]), "+f"(d[7]),
      "+f"(d[8]), "+f"(d[9]), "+f"(d[10]), "+f"(d[11]), "+f"(d[12]), "+f"(d[13]), "+f"(d[14]), "+f"(d[15]),
      "+f"(d[16]), "+f"(d[17]), "+f"(d[18]), "+f"(d[19]), "+f"(d[20]), "+f"(d[21]), "+f"(d[22]), "+f"(d[23]),
      "+f"(d[24]), "+f"(d[25]), "+f"(d[26]), "+f"(d[27]), "+f"(d[28]), "+f"(d[29]), "+f"(d[30]), "+f"(d[31]),
      "+f"(d[32]), "+f"(d[33]), "+f"(d[34]), "+f"(d[35]), "+f"(d[36]), "+f"(d[37]), "+f"(d[38]), "+f"(d[39]),
      "+f"(d[40]), "+f"(d[41]), "+f"(d[42]), "+f"(d[43]), "+f"(d[44]), "+f"(d[45]), "+f"(d[46]), "+f"(d[47]),
      "+f"(d[48]), "+f"(d[49]), "+f"(d[50]), "+f"(d[51]), "+f"(d[52]), "+f"(d[53]), "+f"(d[54]), "+f"(d[55]),
      "+f"(d[56]), "+f"(d[57]), "+f"(d[58]), "+f"(d[59]), "+f"(d[60]), "+f"(d[61]), "+f"(d[62]), "+f"(d[63]),
      "+f"(d[64]), "+f"(d[65]), "+f"(d[66]), "+f"(d[67]), "+f"(d[68]), "+f"(d[69]), "+f"(d[70]), "+f"(d[71]),
      "+f"(d[72]), "+f"(d[73]), "+f"(d[74]), "+f"(d[75]), "+f"(d[76]), "+f"(d[77]), "+f"(d[78]), "+f"(d[79])
    : "r"(a[0]), "r"(a[1]), "r"(a[2]), "r"(a[3]), "l"(db), "r"(sd));
}

__device__ __forceinline__ void wgmma_rs_n176(float* d, const uint32_t* a, uint64_t db, int sd) {
  asm volatile("{ .reg .pred p; setp.ne.b32 p, %93, 0;\n"
      "wgmma.mma_async.sync.aligned.m64n176k16.f32.bf16.bf16 {"
      "%0,%1,%2,%3,%4,%5,%6,%7,%8,%9,%10,%11,%12,%13,%14,%15,"
      "%16,%17,%18,%19,%20,%21,%22,%23,%24,%25,%26,%27,%28,%29,%30,%31,"
      "%32,%33,%34,%35,%36,%37,%38,%39,%40,%41,%42,%43,%44,%45,%46,%47,"
      "%48,%49,%50,%51,%52,%53,%54,%55,%56,%57,%58,%59,%60,%61,%62,%63,"
      "%64,%65,%66,%67,%68,%69,%70,%71,%72,%73,%74,%75,%76,%77,%78,%79,"
      "%80,%81,%82,%83,%84,%85,%86,%87"
      "}, {%88,%89,%90,%91}, %92, p, 1, 1, 0; }"
    : "+f"(d[0]), "+f"(d[1]), "+f"(d[2]), "+f"(d[3]), "+f"(d[4]), "+f"(d[5]), "+f"(d[6]), "+f"(d[7]),
      "+f"(d[8]), "+f"(d[9]), "+f"(d[10]), "+f"(d[11]), "+f"(d[12]), "+f"(d[13]), "+f"(d[14]), "+f"(d[15]),
      "+f"(d[16]), "+f"(d[17]), "+f"(d[18]), "+f"(d[19]), "+f"(d[20]), "+f"(d[21]), "+f"(d[22]), "+f"(d[23]),
      "+f"(d[24]), "+f"(d[25]), "+f"(d[26]), "+f"(d[27]), "+f"(d[28]), "+f"(d[29]), "+f"(d[30]), "+f"(d[31]),
      "+f"(d[32]), "+f"(d[33]), "+f"(d[34]), "+f"(d[35]), "+f"(d[36]), "+f"(d[37]), "+f"(d[38]), "+f"(d[39]),
      "+f"(d[40]), "+f"(d[41]), "+f"(d[42]), "+f"(d[43]), "+f"(d[44]), "+f"(d[45]), "+f"(d[46]), "+f"(d[47]),
      "+f"(d[48]), "+f"(d[49]), "+f"(d[50]), "+f"(d[51]), "+f"(d[52]), "+f"(d[53]), "+f"(d[54]), "+f"(d[55]),
      "+f"(d[56]), "+f"(d[57]), "+f"(d[58]), "+f"(d[59]), "+f"(d[60]), "+f"(d[61]), "+f"(d[62]), "+f"(d[63]),
      "+f"(d[64]), "+f"(d[65]), "+f"(d[66]), "+f"(d[67]), "+f"(d[68]), "+f"(d[69]), "+f"(d[70]), "+f"(d[71]),
      "+f"(d[72]), "+f"(d[73]), "+f"(d[74]), "+f"(d[75]), "+f"(d[76]), "+f"(d[77]), "+f"(d[78]), "+f"(d[79]),
      "+f"(d[80]), "+f"(d[81]), "+f"(d[82]), "+f"(d[83]), "+f"(d[84]), "+f"(d[85]), "+f"(d[86]), "+f"(d[87])
    : "r"(a[0]), "r"(a[1]), "r"(a[2]), "r"(a[3]), "l"(db), "r"(sd));
}

__device__ __forceinline__ void wgmma_rs_n192(float* d, const uint32_t* a, uint64_t db, int sd) {
  asm volatile("{ .reg .pred p; setp.ne.b32 p, %101, 0;\n"
      "wgmma.mma_async.sync.aligned.m64n192k16.f32.bf16.bf16 {"
      "%0,%1,%2,%3,%4,%5,%6,%7,%8,%9,%10,%11,%12,%13,%14,%15,"
      "%16,%17,%18,%19,%20,%21,%22,%23,%24,%25,%26,%27,%28,%29,%30,%31,"
      "%32,%33,%34,%35,%36,%37,%38,%39,%40,%41,%42,%43,%44,%45,%46,%47,"
      "%48,%49,%50,%51,%52,%53,%54,%55,%56,%57,%58,%59,%60,%61,%62,%63,"
      "%64,%65,%66,%67,%68,%69,%70,%71,%72,%73,%74,%75,%76,%77,%78,%79,"
      "%80,%81,%82,%83,%84,%85,%86,%87,%88,%89,%90,%91,%92,%93,%94,%95"
      "}, {%96,%97,%98,%99}, %100, p, 1, 1, 0; }"
    : "+f"(d[0]), "+f"(d[1]), "+f"(d[2]), "+f"(d[3]), "+f"(d[4]), "+f"(d[5]), "+f"(d[6]), "+f"(d[7]),
      "+f"(d[8]), "+f"(d[9]), "+f"(d[10]), "+f"(d[11]), "+f"(d[12]), "+f"(d[13]), "+f"(d[14]), "+f"(d[15]),
      "+f"(d[16]), "+f"(d[17]), "+f"(d[18]), "+f"(d[19]), "+f"(d[20]), "+f"(d[21]), "+f"(d[22]), "+f"(d[23]),
      "+f"(d[24]), "+f"(d[25]), "+f"(d[26]), "+f"(d[27]), "+f"(d[28]), "+f"(d[29]), "+f"(d[30]), "+f"(d[31]),
      "+f"(d[32]), "+f"(d[33]), "+f"(d[34]), "+f"(d[35]), "+f"(d[36]), "+f"(d[37]), "+f"(d[38]), "+f"(d[39]),
      "+f"(d[40]), "+f"(d[41]), "+f"(d[42]), "+f"(d[43]), "+f"(d[44]), "+f"(d[45]), "+f"(d[46]), "+f"(d[47]),
      "+f"(d[48]), "+f"(d[49]), "+f"(d[50]), "+f"(d[51]), "+f"(d[52]), "+f"(d[53]), "+f"(d[54]), "+f"(d[55]),
      "+f"(d[56]), "+f"(d[57]), "+f"(d[58]), "+f"(d[59]), "+f"(d[60]), "+f"(d[61]), "+f"(d[62]), "+f"(d[63]),
      "+f"(d[64]), "+f"(d[65]), "+f"(d[66]), "+f"(d[67]), "+f"(d[68]), "+f"(d[69]), "+f"(d[70]), "+f"(d[71]),
      "+f"(d[72]), "+f"(d[73]), "+f"(d[74]), "+f"(d[75]), "+f"(d[76]), "+f"(d[77]), "+f"(d[78]), "+f"(d[79]),
      "+f"(d[80]), "+f"(d[81]), "+f"(d[82]), "+f"(d[83]), "+f"(d[84]), "+f"(d[85]), "+f"(d[86]), "+f"(d[87]),
      "+f"(d[88]), "+f"(d[89]), "+f"(d[90]), "+f"(d[91]), "+f"(d[92]), "+f"(d[93]), "+f"(d[94]), "+f"(d[95])
    : "r"(a[0]), "r"(a[1]), "r"(a[2]), "r"(a[3]), "l"(db), "r"(sd));
}

__device__ __forceinline__ void wgmma_rs_n208(float* d, const uint32_t* a, uint64_t db, int sd) {
  asm volatile("{ .reg .pred p; setp.ne.b32 p, %109, 0;\n"
      "wgmma.mma_async.sync.aligned.m64n208k16.f32.bf16.bf16 {"
      "%0,%1,%2,%3,%4,%5,%6,%7,%8,%9,%10,%11,%12,%13,%14,%15,"
      "%16,%17,%18,%19,%20,%21,%22,%23,%24,%25,%26,%27,%28,%29,%30,%31,"
      "%32,%33,%34,%35,%36,%37,%38,%39,%40,%41,%42,%43,%44,%45,%46,%47,"
      "%48,%49,%50,%51,%52,%53,%54,%55,%56,%57,%58,%59,%60,%61,%62,%63,"
      "%64,%65,%66,%67,%68,%69,%70,%71,%72,%73,%74,%75,%76,%77,%78,%79,"
      "%80,%81,%82,%83,%84,%85,%86,%87,%88,%89,%90,%91,%92,%93,%94,%95,"
      "%96,%97,%98,%99,%100,%101,%102,%103"
      "}, {%104,%105,%106,%107}, %108, p, 1, 1, 0; }"
    : "+f"(d[0]), "+f"(d[1]), "+f"(d[2]), "+f"(d[3]), "+f"(d[4]), "+f"(d[5]), "+f"(d[6]), "+f"(d[7]),
      "+f"(d[8]), "+f"(d[9]), "+f"(d[10]), "+f"(d[11]), "+f"(d[12]), "+f"(d[13]), "+f"(d[14]), "+f"(d[15]),
      "+f"(d[16]), "+f"(d[17]), "+f"(d[18]), "+f"(d[19]), "+f"(d[20]), "+f"(d[21]), "+f"(d[22]), "+f"(d[23]),
      "+f"(d[24]), "+f"(d[25]), "+f"(d[26]), "+f"(d[27]), "+f"(d[28]), "+f"(d[29]), "+f"(d[30]), "+f"(d[31]),
      "+f"(d[32]), "+f"(d[33]), "+f"(d[34]), "+f"(d[35]), "+f"(d[36]), "+f"(d[37]), "+f"(d[38]), "+f"(d[39]),
      "+f"(d[40]), "+f"(d[41]), "+f"(d[42]), "+f"(d[43]), "+f"(d[44]), "+f"(d[45]), "+f"(d[46]), "+f"(d[47]),
      "+f"(d[48]), "+f"(d[49]), "+f"(d[50]), "+f"(d[51]), "+f"(d[52]), "+f"(d[53]), "+f"(d[54]), "+f"(d[55]),
      "+f"(d[56]), "+f"(d[57]), "+f"(d[58]), "+f"(d[59]), "+f"(d[60]), "+f"(d[61]), "+f"(d[62]), "+f"(d[63]),
      "+f"(d[64]), "+f"(d[65]), "+f"(d[66]), "+f"(d[67]), "+f"(d[68]), "+f"(d[69]), "+f"(d[70]), "+f"(d[71]),
      "+f"(d[72]), "+f"(d[73]), "+f"(d[74]), "+f"(d[75]), "+f"(d[76]), "+f"(d[77]), "+f"(d[78]), "+f"(d[79]),
      "+f"(d[80]), "+f"(d[81]), "+f"(d[82]), "+f"(d[83]), "+f"(d[84]), "+f"(d[85]), "+f"(d[86]), "+f"(d[87]),
      "+f"(d[88]), "+f"(d[89]), "+f"(d[90]), "+f"(d[91]), "+f"(d[92]), "+f"(d[93]), "+f"(d[94]), "+f"(d[95]),
      "+f"(d[96]), "+f"(d[97]), "+f"(d[98]), "+f"(d[99]), "+f"(d[100]), "+f"(d[101]), "+f"(d[102]), "+f"(d[103])
    : "r"(a[0]), "r"(a[1]), "r"(a[2]), "r"(a[3]), "l"(db), "r"(sd));
}

__device__ __forceinline__ void wgmma_rs_n224(float* d, const uint32_t* a, uint64_t db, int sd) {
  asm volatile("{ .reg .pred p; setp.ne.b32 p, %117, 0;\n"
      "wgmma.mma_async.sync.aligned.m64n224k16.f32.bf16.bf16 {"
      "%0,%1,%2,%3,%4,%5,%6,%7,%8,%9,%10,%11,%12,%13,%14,%15,"
      "%16,%17,%18,%19,%20,%21,%22,%23,%24,%25,%26,%27,%28,%29,%30,%31,"
      "%32,%33,%34,%35,%36,%37,%38,%39,%40,%41,%42,%43,%44,%45,%46,%47,"
      "%48,%49,%50,%51,%52,%53,%54,%55,%56,%57,%58,%59,%60,%61,%62,%63,"
      "%64,%65,%66,%67,%68,%69,%70,%71,%72,%73,%74,%75,%76,%77,%78,%79,"
      "%80,%81,%82,%83,%84,%85,%86,%87,%88,%89,%90,%91,%92,%93,%94,%95,"
      "%96,%97,%98,%99,%100,%101,%102,%103,%104,%105,%106,%107,%108,%109,%110,%111"
      "}, {%112,%113,%114,%115}, %116, p, 1, 1, 0; }"
    : "+f"(d[0]), "+f"(d[1]), "+f"(d[2]), "+f"(d[3]), "+f"(d[4]), "+f"(d[5]), "+f"(d[6]), "+f"(d[7]),
      "+f"(d[8]), "+f"(d[9]), "+f"(d[10]), "+f"(d[11]), "+f"(d[12]), "+f"(d[13]), "+f"(d[14]), "+f"(d[15]),
      "+f"(d[16]), "+f"(d[17]), "+f"(d[18]), "+f"(d[19]), "+f"(d[20]), "+f"(d[21]), "+f"(d[22]), "+f"(d[23]),
      "+f"(d[24]), "+f"(d[25]), "+f"(d[26]), "+f"(d[27]), "+f"(d[28]), "+f"(d[29]), "+f"(d[30]), "+f"(d[31]),
      "+f"(d[32]), "+f"(d[33]), "+f"(d[34]), "+f"(d[35]), "+f"(d[36]), "+f"(d[37]), "+f"(d[38]), "+f"(d[39]),
      "+f"(d[40]), "+f"(d[41]), "+f"(d[42]), "+f"(d[43]), "+f"(d[44]), "+f"(d[45]), "+f"(d[46]), "+f"(d[47]),
      "+f"(d[48]), "+f"(d[49]), "+f"(d[50]), "+f"(d[51]), "+f"(d[52]), "+f"(d[53]), "+f"(d[54]), "+f"(d[55]),
      "+f"(d[56]), "+f"(d[57]), "+f"(d[58]), "+f"(d[59]), "+f"(d[60]), "+f"(d[61]), "+f"(d[62]), "+f"(d[63]),
      "+f"(d[64]), "+f"(d[65]), "+f"(d[66]), "+f"(d[67]), "+f"(d[68]), "+f"(d[69]), "+f"(d[70]), "+f"(d[71]),
      "+f"(d[72]), "+f"(d[73]), "+f"(d[74]), "+f"(d[75]), "+f"(d[76]), "+f"(d[77]), "+f"(d[78]), "+f"(d[79]),
      "+f"(d[80]), "+f"(d[81]), "+f"(d[82]), "+f"(d[83]), "+f"(d[84]), "+f"(d[85]), "+f"(d[86]), "+f"(d[87]),
      "+f"(d[88]), "+f"(d[89]), "+f"(d[90]), "+f"(d[91]), "+f"(d[92]), "+f"(d[93]), "+f"(d[94]), "+f"(d[95]),
      "+f"(d[96]), "+f"(d[97]), "+f"(d[98]), "+f"(d[99]), "+f"(d[100]), "+f"(d[101]), "+f"(d[102]), "+f"(d[103]),
      "+f"(d[104]), "+f"(d[105]), "+f"(d[106]), "+f"(d[107]), "+f"(d[108]), "+f"(d[109]), "+f"(d[110]), "+f"(d[111])
    : "r"(a[0]), "r"(a[1]), "r"(a[2]), "r"(a[3]), "l"(db), "r"(sd));
}

__device__ __forceinline__ void wgmma_rs_n240(float* d, const uint32_t* a, uint64_t db, int sd) {
  asm volatile("{ .reg .pred p; setp.ne.b32 p, %125, 0;\n"
      "wgmma.mma_async.sync.aligned.m64n240k16.f32.bf16.bf16 {"
      "%0,%1,%2,%3,%4,%5,%6,%7,%8,%9,%10,%11,%12,%13,%14,%15,"
      "%16,%17,%18,%19,%20,%21,%22,%23,%24,%25,%26,%27,%28,%29,%30,%31,"
      "%32,%33,%34,%35,%36,%37,%38,%39,%40,%41,%42,%43,%44,%45,%46,%47,"
      "%48,%49,%50,%51,%52,%53,%54,%55,%56,%57,%58,%59,%60,%61,%62,%63,"
      "%64,%65,%66,%67,%68,%69,%70,%71,%72,%73,%74,%75,%76,%77,%78,%79,"
      "%80,%81,%82,%83,%84,%85,%86,%87,%88,%89,%90,%91,%92,%93,%94,%95,"
      "%96,%97,%98,%99,%100,%101,%102,%103,%104,%105,%106,%107,%108,%109,%110,%111,"
      "%112,%113,%114,%115,%116,%117,%118,%119"
      "}, {%120,%121,%122,%123}, %124, p, 1, 1, 0; }"
    : "+f"(d[0]), "+f"(d[1]), "+f"(d[2]), "+f"(d[3]), "+f"(d[4]), "+f"(d[5]), "+f"(d[6]), "+f"(d[7]),
      "+f"(d[8]), "+f"(d[9]), "+f"(d[10]), "+f"(d[11]), "+f"(d[12]), "+f"(d[13]), "+f"(d[14]), "+f"(d[15]),
      "+f"(d[16]), "+f"(d[17]), "+f"(d[18]), "+f"(d[19]), "+f"(d[20]), "+f"(d[21]), "+f"(d[22]), "+f"(d[23]),
      "+f"(d[24]), "+f"(d[25]), "+f"(d[26]), "+f"(d[27]), "+f"(d[28]), "+f"(d[29]), "+f"(d[30]), "+f"(d[31]),
      "+f"(d[32]), "+f"(d[33]), "+f"(d[34]), "+f"(d[35]), "+f"(d[36]), "+f"(d[37]), "+f"(d[38]), "+f"(d[39]),
      "+f"(d[40]), "+f"(d[41]), "+f"(d[42]), "+f"(d[43]), "+f"(d[44]), "+f"(d[45]), "+f"(d[46]), "+f"(d[47]),
      "+f"(d[48]), "+f"(d[49]), "+f"(d[50]), "+f"(d[51]), "+f"(d[52]), "+f"(d[53]), "+f"(d[54]), "+f"(d[55]),
      "+f"(d[56]), "+f"(d[57]), "+f"(d[58]), "+f"(d[59]), "+f"(d[60]), "+f"(d[61]), "+f"(d[62]), "+f"(d[63]),
      "+f"(d[64]), "+f"(d[65]), "+f"(d[66]), "+f"(d[67]), "+f"(d[68]), "+f"(d[69]), "+f"(d[70]), "+f"(d[71]),
      "+f"(d[72]), "+f"(d[73]), "+f"(d[74]), "+f"(d[75]), "+f"(d[76]), "+f"(d[77]), "+f"(d[78]), "+f"(d[79]),
      "+f"(d[80]), "+f"(d[81]), "+f"(d[82]), "+f"(d[83]), "+f"(d[84]), "+f"(d[85]), "+f"(d[86]), "+f"(d[87]),
      "+f"(d[88]), "+f"(d[89]), "+f"(d[90]), "+f"(d[91]), "+f"(d[92]), "+f"(d[93]), "+f"(d[94]), "+f"(d[95]),
      "+f"(d[96]), "+f"(d[97]), "+f"(d[98]), "+f"(d[99]), "+f"(d[100]), "+f"(d[101]), "+f"(d[102]), "+f"(d[103]),
      "+f"(d[104]), "+f"(d[105]), "+f"(d[106]), "+f"(d[107]), "+f"(d[108]), "+f"(d[109]), "+f"(d[110]), "+f"(d[111]),
      "+f"(d[112]), "+f"(d[113]), "+f"(d[114]), "+f"(d[115]), "+f"(d[116]), "+f"(d[117]), "+f"(d[118]), "+f"(d[119])
    : "r"(a[0]), "r"(a[1]), "r"(a[2]), "r"(a[3]), "l"(db), "r"(sd));
}

__device__ __forceinline__ void wgmma_rs_n256(float* d, const uint32_t* a, uint64_t db, int sd) {
  asm volatile("{ .reg .pred p; setp.ne.b32 p, %133, 0;\n"
      "wgmma.mma_async.sync.aligned.m64n256k16.f32.bf16.bf16 {"
      "%0,%1,%2,%3,%4,%5,%6,%7,%8,%9,%10,%11,%12,%13,%14,%15,"
      "%16,%17,%18,%19,%20,%21,%22,%23,%24,%25,%26,%27,%28,%29,%30,%31,"
      "%32,%33,%34,%35,%36,%37,%38,%39,%40,%41,%42,%43,%44,%45,%46,%47,"
      "%48,%49,%50,%51,%52,%53,%54,%55,%56,%57,%58,%59,%60,%61,%62,%63,"
      "%64,%65,%66,%67,%68,%69,%70,%71,%72,%73,%74,%75,%76,%77,%78,%79,"
      "%80,%81,%82,%83,%84,%85,%86,%87,%88,%89,%90,%91,%92,%93,%94,%95,"
      "%96,%97,%98,%99,%100,%101,%102,%103,%104,%105,%106,%107,%108,%109,%110,%111,"
      "%112,%113,%114,%115,%116,%117,%118,%119,%120,%121,%122,%123,%124,%125,%126,%127"
      "}, {%128,%129,%130,%131}, %132, p, 1, 1, 0; }"
    : "+f"(d[0]), "+f"(d[1]), "+f"(d[2]), "+f"(d[3]), "+f"(d[4]), "+f"(d[5]), "+f"(d[6]), "+f"(d[7]),
      "+f"(d[8]), "+f"(d[9]), "+f"(d[10]), "+f"(d[11]), "+f"(d[12]), "+f"(d[13]), "+f"(d[14]), "+f"(d[15]),
      "+f"(d[16]), "+f"(d[17]), "+f"(d[18]), "+f"(d[19]), "+f"(d[20]), "+f"(d[21]), "+f"(d[22]), "+f"(d[23]),
      "+f"(d[24]), "+f"(d[25]), "+f"(d[26]), "+f"(d[27]), "+f"(d[28]), "+f"(d[29]), "+f"(d[30]), "+f"(d[31]),
      "+f"(d[32]), "+f"(d[33]), "+f"(d[34]), "+f"(d[35]), "+f"(d[36]), "+f"(d[37]), "+f"(d[38]), "+f"(d[39]),
      "+f"(d[40]), "+f"(d[41]), "+f"(d[42]), "+f"(d[43]), "+f"(d[44]), "+f"(d[45]), "+f"(d[46]), "+f"(d[47]),
      "+f"(d[48]), "+f"(d[49]), "+f"(d[50]), "+f"(d[51]), "+f"(d[52]), "+f"(d[53]), "+f"(d[54]), "+f"(d[55]),
      "+f"(d[56]), "+f"(d[57]), "+f"(d[58]), "+f"(d[59]), "+f"(d[60]), "+f"(d[61]), "+f"(d[62]), "+f"(d[63]),
      "+f"(d[64]), "+f"(d[65]), "+f"(d[66]), "+f"(d[67]), "+f"(d[68]), "+f"(d[69]), "+f"(d[70]), "+f"(d[71]),
      "+f"(d[72]), "+f"(d[73]), "+f"(d[74]), "+f"(d[75]), "+f"(d[76]), "+f"(d[77]), "+f"(d[78]), "+f"(d[79]),
      "+f"(d[80]), "+f"(d[81]), "+f"(d[82]), "+f"(d[83]), "+f"(d[84]), "+f"(d[85]), "+f"(d[86]), "+f"(d[87]),
      "+f"(d[88]), "+f"(d[89]), "+f"(d[90]), "+f"(d[91]), "+f"(d[92]), "+f"(d[93]), "+f"(d[94]), "+f"(d[95]),
      "+f"(d[96]), "+f"(d[97]), "+f"(d[98]), "+f"(d[99]), "+f"(d[100]), "+f"(d[101]), "+f"(d[102]), "+f"(d[103]),
      "+f"(d[104]), "+f"(d[105]), "+f"(d[106]), "+f"(d[107]), "+f"(d[108]), "+f"(d[109]), "+f"(d[110]), "+f"(d[111]),
      "+f"(d[112]), "+f"(d[113]), "+f"(d[114]), "+f"(d[115]), "+f"(d[116]), "+f"(d[117]), "+f"(d[118]), "+f"(d[119]),
      "+f"(d[120]), "+f"(d[121]), "+f"(d[122]), "+f"(d[123]), "+f"(d[124]), "+f"(d[125]), "+f"(d[126]), "+f"(d[127])
    : "r"(a[0]), "r"(a[1]), "r"(a[2]), "r"(a[3]), "l"(db), "r"(sd));
}

__device__ __forceinline__ void ln_finish(float mean, float var, float& mb, float& rinv) {
  mb = round_bf16(mean);
  float sd;
  asm("sqrt.approx.ftz.f32 %0, %1;" : "=f"(sd) : "f"(round_bf16(round_bf16(var) + 1e-5f)));
  asm("rcp.approx.ftz.f32 %0, %1;" : "=f"(rinv) : "f"(round_bf16(sd)));
}
__device__ __forceinline__ uint32_t sum4(uint32_t a, uint32_t b, uint32_t c, uint32_t d) { return badd2(badd2(badd2(d, c), b), a); }
struct Ring {
  uint32_t s, ph;
  __device__ __forceinline__ void next() { if (++s == NSTAGE) { s = 0; ph ^= 1; } }
};

template <int J> __device__ __forceinline__ void conv_lda(uint32_t* a, uint32_t base) {
  a[2 * J] = lds32(base + (J >> 1) * 256 + (J & 1) * 16); a[2 * J + 1] = lds32(base + (J >> 1) * 256 + (J & 1) * 16 + 128);
}
template <int J = 0> __device__ __forceinline__ void conv_lda_all(uint32_t* a, uint32_t base) {
  conv_lda<J>(a, base);
  if constexpr (J < 31) conv_lda_all<J + 1>(a, base);
}
__device__ __forceinline__ void conv_mma(float* acc, const uint32_t* a, uint64_t db) {
  wgmma_rs_n256(acc, a, db, 0);
  wgmma_rs_n240(acc, a + 4, db + 16, 1);
  wgmma_rs_n224(acc, a + 8, db + 32, 1);
  wgmma_rs_n208(acc, a + 12, db + 48, 1);
  wgmma_rs_n192(acc, a + 16, db + 64, 1);
  wgmma_rs_n176(acc, a + 20, db + 80, 1);
  wgmma_rs_n160(acc, a + 24, db + 96, 1);
  wgmma_rs_n144(acc, a + 28, db + 112, 1);
  wgmma_rs_n128(acc, a + 32, db + 128, 1);
  wgmma_rs_n112(acc, a + 36, db + 144, 1);
  wgmma_rs_n96(acc, a + 40, db + 160, 1);
  wgmma_rs_n80(acc, a + 44, db + 176, 1);
  wgmma_rs_n64(acc, a + 48, db + 192, 1);
  wgmma_rs_n48(acc, a + 52, db + 208, 1);
  wgmma_rs_n32(acc, a + 56, db + 224, 1);
  wgmma_rs_n16(acc, a + 60, db + 240, 1);
}
__device__ __forceinline__ uint32_t conv_part(const float* acc, int j) {
  const int q = 31 - j;
  return q == 31 ? pack_bf16(acc[124], acc[125]) : pack_bf16(acc[4 * q] + acc[(4 * q + 6) & 127], acc[4 * q + 1] + acc[(4 * q + 7) & 127]);
}
template <bool MORE, int J = 0> __device__ __forceinline__ void conv_drain(const float* acc, uint32_t wr, uint32_t* a, uint32_t ka) {
  if (MORE) conv_lda<J>(a, ka);
  sts32(wr + J * 128, conv_part(acc, J));
  if constexpr (J < 31) conv_drain<MORE, J + 1>(acc, wr, a, ka);
}
__device__ __forceinline__ uint4 conv_sum(const uint4* p) {
  return make_uint4(sum4(p[0].x, p[1].x, p[2].x, p[3].x), sum4(p[0].y, p[1].y, p[2].y, p[3].y), sum4(p[0].z, p[1].z, p[2].z, p[3].z),
                    sum4(p[0].w, p[1].w, p[2].w, p[3].w));
}
__device__ __forceinline__ int g2k(int rank, int kb) { return (rank * G2_KB + (kb < 6 ? 6 * kb : kb - 5 + (kb - 6) / 5)) * 64; }

template <int NV> __device__ __forceinline__ void gelu_stage(float* acc, const float* hb, uint32_t sa, int passes, uint32_t bar) {
#pragma unroll
  for (int i = 0; i < NV; i++) acc[i] = fmaf(acc[i], 0.5f, hb[(i >> 1) & 1]);
#pragma unroll 1
  for (; passes > 0; passes--, sa += NV * 256) {
#pragma unroll
    for (int i = 0; i < NV; i += 8)
      stsm4t(sa + i * 256, pack_bf16(gelu_half(acc[i]), gelu_half(acc[i + 1])), pack_bf16(gelu_half(acc[i + 2]), gelu_half(acc[i + 3])),
             pack_bf16(gelu_half(acc[i + 4]), gelu_half(acc[i + 5])), pack_bf16(gelu_half(acc[i + 6]), gelu_half(acc[i + 7])));
    __syncwarp();
    if (bar) mbar_arrive(bar);
    bar = 0;
    float half = 0.5f;
    asm volatile("" : "+f"(half));
#pragma unroll
    for (int i = 0; i < NV; i++) acc[i] = fmaf(acc[NV + i], half, hb[2 + ((i >> 1) & 1)]);
  }
}

__global__ void __cluster_dims__(2, 1, 1) __launch_bounds__(384, 1) fused_kernel(const __grid_constant__ Hot H, const __grid_constant__ Params P) {
  extern __shared__ __align__(1024) uint8_t smem_raw[];
  const uint32_t t0 = clk();
  const uint32_t sb = smem_u32(smem_raw);
  const int tid = threadIdx.x, lane = tid & 31;
  const int bid = blockIdx.x, rank = bid & 1;
  const Role& R = P.role[bid];
  Scratch* const S = H.S;
  uint32_t xr[18];
  const int row = bid * 16 + (tid >> 4);
  if (tid < 256 && bid < 128) {
    const char* src = reinterpret_cast<const char*>(H.x) + row * (D_ * 2) + (lane & 15) * 8;
#pragma unroll
    for (int j = 0; j < 9; j++) asm volatile("ld.global.nc.v2.u32 {%0,%1}, [%2];" : "=r"(xr[2 * j]), "=r"(xr[2 * j + 1]) : "l"(src + 128 * j));
  }
  if (tid == 256) asm volatile("prefetch.tensormap [%0];" :: "l"(&P.m_w1 + (R.at == 15)) : "memory");
  const int warp = __shfl_sync(0xffffffffu, tid >> 5, 0);

  if (warp >= 8) {
    const bool one = elect_one(), left = R.at == 15;
    TUNED(NWE, 2, 1); TUNED(NW0, 3, 2);
    if (warp == 8 && one) {
#pragma unroll
      for (int b = B_FULL; b < B_KFULL; b += 8) mbar_init(sb + b, 1);
#pragma unroll 1
      for (int s = 0; s < NWE; s++) {
        mbar_expect_tx(sb + B_FULL + 8 * s, G1_BYTES);
        fence_async_smem();
        tma3d(sb + s * SLOT, &P.m_w1 + left, 0, s * 64, R.fg, sb + B_FULL + 8 * s);
      }
#pragma unroll
      for (int b = B_KFULL; b <= B_DONE; b += 8) mbar_init(sb + b, b < B_EMPTY ? 1 : b < B_SFREE ? 2 : b < B_CEMPTY ? 3 : b < B_G1DONE ? 4 : 8);
      asm volatile("fence.mbarrier_init.release.cluster;" ::: "memory");
    }
    __syncwarp();
    asm volatile("barrier.cluster.arrive.relaxed.aligned;" ::: "memory");
    asm volatile("setmaxnreg.dec.sync.aligned.u32 56;");
    asm volatile("barrier.cluster.wait.aligned;" ::: "memory");
    if (warp == 8) {
      const uint32_t ep = ldg32(S->cnt + C_EPOCH * 32);
      if (one) {
#pragma unroll 1
        for (int i = 0; i < 6; i++) asm volatile("prefetch.tensormap [%0];" :: "l"(&P.m_w2 + i) : "memory");
      }
      __syncwarp();
      if (bid < 128) bar_sync(2, 288);
      if (one) {
        TLREC(31);
        signal(S, C_H, EPOCH / 132);
        TLREC(1);
        const uint32_t boff = left ? 24576 : 16384;
        int kr = bid < 128 ? -2 : KV_ROUNDS + 1, ks = 0;
        auto kv_step = [&]() {
          if (ks == 0) {
            bulk_wait_all();
            if (kr < KV_ROUNDS - 2) {
              const int q = (kr + 2) % 3;
              const uint32_t in = sb + kv_buf(q), fb = sb + B_UFULL + 8 * q;
              mbar_expect_tx(fb, 3840 + 3264 + 768);
              tma2d(in, &P.m_k, (kr + 2) * 96, bid * 16 - 4, fb);
              tma2d(in + 3840, &P.m_v, (kr + 2) * 96, bid * 16 - 1, fb);
              bulk_load(in + 7168, H.shift_k + (kr + 2) * 384, 768, fb);
            }
            if (kr == KV_ROUNDS) { mbar_arrive(sb + B_KVDONE); kr++; }
          } else if (kr >= 0) {
            if (!mbar_test(sb + B_KFULL + 8 * (kr % 3), kr >= 3)) return;
            fence_async_smem();
            tma3d_store(&P.m_ub, sb + kv_buf(kr % 3) + (ks - 1) * 3072, 16 * (127 - bid), kr * 48, 2 * ks - 2);
            bulk_commit();
          }
          if (++ks == 3) { kr++; ks = kr == KV_ROUNDS - 2 || kr == KV_ROUNDS - 1; }
        };
        if (bid >= 128) mbar_arrive(sb + B_KVDONE);
        Ring r{0, 1};
#pragma unroll 1
        for (int kb = NWE - NW0; kb < G1_KB || kr <= KV_ROUNDS; kb++) {
          if (kb < G1_KB) {
          const int kw = kb < 0 ? kb + NW0 : kb, s = kb < 0 ? kw : r.s;
          const uint32_t fb = sb + B_FULL + 8 * s;
          if (kb < 0 || kb >= NW0) {
            mbar_wait(sb + B_EMPTY + 8 * s, r.ph);
            mbar_expect_tx(fb, G1_BYTES);
            tma3d(sb + s * SLOT, &P.m_w1 + left, 0, kw * 64, R.fg, fb);
            if (kb < 0) continue;
          }
          if (kb == 0) { await(S, C_H, ep); fence_async_global(); TLREC(2); }
          bulk_load(sb + s * SLOT + boff, S->h + (kb * 18 + R.at) * 2048, G1_BYTES - boff, fb);
          if (kb == 23) {
#pragma unroll 1
            for (int i = 0; i < 2; i++) {
              sts128(sb + cv_taps(i), 0, 0, 0, 0); sts128(sb + cv_taps(i) + 16, 0, 0, 0, 0);
              bulk_load(sb + cv_taps(i) + 32, H.ssm_k + (R.ch + i) * S_, 4096, sb + B_MISC);
            }
            mbar_expect_tx(sb + B_MISC, boff / 64 + 1152 + 8192);
            bulk_load(sb + SM_B1, H.b1 + R.fg * 64, boff / 64, sb + B_MISC);
            bulk_load(sb + SM_D, H.ssm_D, 1152, sb + B_MISC);
          }
          r.next();
          }
          if (kb >= KV0 && kr <= KV_ROUNDS) kv_step();
        }
        await(S, C_KV, ep);
        fence_async_global();
#pragma unroll 1
        for (int i = 0; i < R.ncv; i++) {
          if (i == 2) {
            if (R.sg >= 0) {
#pragma unroll 1
              for (int s = 2; s < NSTAGE; s++) {
                mbar_wait(sb + B_EMPTY + 8 * s, ((G1_KB / NSTAGE) - 1) & 1);
                mbar_expect_tx(sb + B_FULL + 8 * s, G2_BYTES);
                tma3d(sb + s * SLOT, &P.m_w2, 0, (rank * G2_KB + 6 * (s - 2)) * 64, R.sg, sb + B_FULL + 8 * s);
              }
            }
            mbar_wait(sb + B_G1DONE, 0);
          }
          const uint32_t kt = sb + cv_taps(i), b8 = sb + 8 * (i & 3);
          mbar_wait(b8 + B_CEMPTY, ((i >> 2) & 1) ^ 1);
          if (i < 2) mbar_arrive(b8 + B_KFULL);
          else {
            sts128(kt, 0, 0, 0, 0); sts128(kt + 16, 0, 0, 0, 0);
            mbar_expect_tx(b8 + B_KFULL, 4096);
            bulk_load(kt + 32, H.ssm_k + (R.ch + i) * S_, 4096, b8 + B_KFULL);
          }
          mbar_expect_tx(b8 + B_UFULL, 8192);
          bulk_load(sb + cv_in(i), S->ub + (R.ch + i) * 4096, 8192, b8 + B_UFULL);
        }
        if (R.sg >= 0) {
          mbar_expect_tx(sb + B_XY, 2 * 18432 + 2048 + 256);
#pragma unroll
          for (int i = 0; i < 4; i++) mbar_expect_tx(sb + B_XFULL + 8 * i, i & 1 ? 9216 - XP * 2048 : XP * 2048);
          TUNED(SYNCA, 0, 5); TUNED(SYNCKB, 1, 7);
#pragma unroll 1
          for (int kb = 0; kb < G2_KB; kb++, r.next()) {
            const int k0 = g2k(rank, kb);
            const uint32_t fb = sb + B_FULL + 8 * r.s, slot = sb + r.s * SLOT;
            if (!(kb & ~4)) { await(S, C_U + (kb >> 2), ep); fence_async_global(); if (!kb) TLREC(6); }
            if (kb >= NSTAGE - 2) {
              if (kb == SYNCKB) await(S, C_SYNC, ep);
              mbar_wait(sb + B_EMPTY + 8 * r.s, r.ph);
              if (kb == SYNCA) asm volatile("red.relaxed.gpu.global.add.u32 [%0], %1;" :: "l"(S->cnt + C_SYNC * 32), "r"(EPOCH / 128) : "memory");
              mbar_expect_tx(fb, G2_BYTES);
              tma3d(slot, &P.m_w2, 0, k0, R.sg, fb);
            }
            bulk_load(slot + 16384, S->u + k0 * D_ + R.ds * 512, 9216, fb);
            bulk_load(slot + 16384 + 9216, S->u + k0 * D_ + R.dk * 512, 9216, fb);
            const uint32_t nx = kb - 8;
            if (nx == 0) { mbar_wait(sb + B_KVDONE, 1); fence_async_smem(); }
            if (nx < 8) tma2d(sb + SM_CV + nx * 2304, &P.m_x, R.dk * 8, R.sg * 64 + nx * 16, sb + B_XY);
          }
          bulk_load(sb + SM_ST, S->stats + R.sg * 64, 2048, sb + B_XY);
          bulk_load(sb + SM_B2, P.b2 + R.sg * 64, 256, sb + B_XY);
          await(S, C_Y, ep);
          fence_async_global();
          TLREC(19);
          tma3d(sb + SM_DED, &P.m_y, 0, R.dk * 8, R.sg, sb + B_XY);
          if (bid == 0) asm volatile("red.relaxed.gpu.global.add.u32 [%0], %1;" :: "l"(S->cnt + C_EPOCH * 32), "r"(EPOCH) : "memory");
        }
      }
    } else {
      if (bid < 128) {
        const int ht = tid - 288, hf = ht >= 48, pr = ht - 48 * hf;
        const uint32_t st = (1 - hf) * 1536 + pr * 32, sw = (pr & 4) * 4;
#pragma unroll 1
        for (int r = 0; r < KV_ROUNDS; r++) {
          const int q = r % 3;
          const uint32_t in = sb + kv_buf(q);
          {
            mbar_wait_guarded(sb + B_UFULL + 8 * q, t0, r >= 3);
            uint32_t kk[12], vv[9];
#pragma unroll
            for (int j = 0; j < 12; j++) kk[j] = lds32(in + hf * 1536 + pr * 4 + j * 192);
#pragma unroll
            for (int j = 0; j < 9; j++) vv[j] = lds32(in + 3840 + hf * 1536 + pr * 4 + j * 192);
            const uint4 w = lds128(in + 7168 + pr * 16);
            const uint32_t w0 = __byte_perm(w.x, w.z, 0x5410), w1 = __byte_perm(w.x, w.z, 0x7632);
            const uint32_t w2 = __byte_perm(w.y, w.w, 0x5410), w3 = __byte_perm(w.y, w.w, 0x7632);
#pragma unroll
            for (int j = 0; j < 9; j++)
              vv[j] = bmul2(badd2(badd2(badd2(bmul2(kk[j], w3), bmul2(kk[j + 1], w2)), bmul2(kk[j + 2], w1)), bmul2(kk[j + 3], w0)), vv[j]);
            bar_sync(1, 96);
#pragma unroll
            for (int c = 0; c < 2; c++)
#pragma unroll
              for (int pi = 0; pi < 2; pi++) {
                const uint32_t sel = c ? 0x7632 : 0x5410;
                sts128(in + st + c * 3072 + (pi * 16 ^ sw), __byte_perm(vv[7 + pi], vv[6 + pi], sel), __byte_perm(vv[5 + pi], vv[4 + pi], sel),
                       __byte_perm(vv[3 + pi], vv[2 + pi], sel), __byte_perm(vv[1 + pi], vv[pi], sel));
              }
            bar_sync(1, 96);
            if (ht == 0) mbar_arrive(sb + B_KFULL + 8 * q);
          }
          __syncwarp();
        }
      }
      if (one) {
        if (warp < 11) {
          const int wg = warp - 9;
          const uint32_t bytes = left ? 12288 : 10240;
#pragma unroll 1
          for (int j = 0; j < 2; j++) {
            mbar_wait_guarded(sb + B_STG + 8 * wg + (j ? 0 : 16), t0);
            fence_async_smem();
            TLREC(13 + wg);
            if (!j || wg || !left)
              bulk_store(S->u + (R.fg + wg) * (64 * D_) + R.at * 2048 + j * (left ? 64 * D_ : 5120), sb + (wg ? SM_ST1 : SM_DED) + j * bytes, bytes);
          }
          bulk_commit();
          bulk_wait_all();
          mbar_arrive(sb + B_STORED + 8 * wg);
          if (wg) mbar_arrive(sb + B_EMPTY);
          asm volatile("mbarrier.arrive.shared::cta.b64 _, [%0], 3;" :: "r"(sb + B_SFREE + 8 * wg) : "memory");
          signal(S, C_U + wg, EPOCH / 132);
          TLREC(15 + wg);
        } else {
          mbar_wait_guarded(sb + B_KVDONE, t0);
          signal(S, C_KV, EPOCH / 132);
          TLREC(27);
        }
      }
      __syncwarp();
#pragma unroll 1
      for (int i = 0; i < R.ncv; i++) {
        const uint32_t red = sb + cv_red(i, R.ncv) + (tid - 288) * 16;
        uint4* yo = reinterpret_cast<uint4*>(S->y + (R.ch + i) * S_) + (tid - 288);
        mbar_wait_guarded(sb + B_STORED + 8 * (i & 1), t0);
        mbar_wait_guarded(sb + B_STG + 8 * (i & 1) + (i + 2 < R.ncv ? 0 : 16), t0, i + 2 >= R.ncv || !(i & 2));
        uint4 p[2][4];
#pragma unroll
        for (int x = 0; x < 8; x++) p[x >> 2][x & 3] = lds128(red + (x & 3) * CV_REDW + (x >> 2) * 1536);
        yo[0] = conv_sum(p[0]);
        if (warp < 11) {
#pragma unroll
          for (int x = 0; x < 4; x++) p[0][x] = lds128(red + x * CV_REDW + 3072);
          yo[192] = conv_sum(p[0]);
        }
        yo[96] = conv_sum(p[1]);
        __syncwarp();
        if (one) mbar_arrive(sb + (i + 4 == R.ncv ? B_PDONE : B_SFREE + 8 * (i & 1)));
        if (i + 3 == R.ncv) {
          bar_sync(1, 96);
          if (warp == 11 && one) { fence_async_smem(); mbar_arrive(sb + B_EMPTY + 8); }
          __syncwarp();
        }
      }
      bar_sync(1, 96);
      if (warp == 11 && one) {
        TLREC(7);
        mbar_arrive(sb + B_KVDONE);
        signal(S, C_Y, EPOCH / 132);
        if (R.sg >= 0) mbar_wait_guarded(sb + B_DONE, t0);
      }
    }
    TLEND();
  } else {
    asm volatile("barrier.cluster.arrive.relaxed.aligned;" ::: "memory");
    if (bid < 128) {
      float c[36], s[4];
#pragma unroll
      for (int i = 0; i < 18; i++) { c[2 * i] = bf_lo(xr[i]); c[2 * i + 1] = bf_hi(xr[i]); }
#pragma unroll
      for (int i = 0; i < 36; i++) s[i & 3] = i < 4 ? c[i] : s[i & 3] + c[i];
      const float ml = ((s[0] + s[1]) + (s[2] + s[3])) * (1.0f / 36.0f);
#pragma unroll
      for (int i = 0; i < 36; i++) { c[i] -= ml; s[i & 3] = i < 4 ? c[i] * c[i] : fmaf(c[i], c[i], s[i & 3]); }
      float m = ml, q = (s[0] + s[1]) + (s[2] + s[3]), n2 = 18.f;
#pragma unroll
      for (int o = 1; o < 16; o <<= 1) {
        const float mo = __shfl_xor_sync(0xffffffffu, m, o), qo = __shfl_xor_sync(0xffffffffu, q, o);
        const float dl = m - mo;
        q = fmaf(dl * dl, n2, q + qo);
        m = fmaf(dl, -0.5f, m);
        n2 *= 2.f;
      }
      const float var = q * (1.0f / 576.0f);
      float mb, rinv, mb2, rinv2;
      ln_finish(m, var, mb, rinv);
      ln_finish((m - mb) * rinv, var * rinv * rinv, mb2, rinv2);
      const float ca = rinv * rinv2, cb = fmaf(ml - mb, rinv, -mb2) * rinv2;
      uint2* dst = reinterpret_cast<uint2*>(S->h) + ((row >> 6) * 18 + ((lane >> 3) & 1)) * 512 + (row & 63) * 8 + ((lane & 7) ^ (row & 6));
#pragma unroll
      for (int j = 0; j < 9; j++)
        dst[1024 * j] = make_uint2(pack_bf16(fmaf(c[4 * j], ca, cb), fmaf(c[4 * j + 1], ca, cb)), pack_bf16(fmaf(c[4 * j + 2], ca, cb), fmaf(c[4 * j + 3], ca, cb)));
      const uint32_t rh = pack_bf16(rinv, rinv);
      if (!(lane & 15)) S->stats[row] = make_uint4(pack_bf16(mb, mb), rh, pack_bf16(rinv - bf_lo(rh), rinv - bf_lo(rh)), 0);
      __syncwarp();
      bar_arrive(2, 288);
    }
    asm volatile("setmaxnreg.inc.sync.aligned.u32 224;");
    asm volatile("barrier.cluster.wait.aligned;" ::: "memory");
    const int wg = warp >> 2, w = warp & 3, g = lane >> 2, t = lane & 3, wtid = tid & 127;
    const bool elect = wtid == 0;
    const uint64_t da0 = make_desc(sb + wg * 8192, 8192, 1024, 1);
    const uint32_t swz = ((lane >> 4) * 8 + (lane & 7)) * 128 + (((2 * w + ((lane >> 3) & 1)) ^ (lane & 7)) << 4);
    const uint32_t stg = sb + (wg ? SM_ST1 : SM_DED), ka0 = (8 * w + g + t + 1) * 4;
    uint32_t a[64];
    {
      auto mainloop = [&](auto&& mma) {
        Ring r{0, 0};
        uint32_t rel = 0;
#pragma unroll 1
        for (int kb = 0; kb < G1_KB; kb++, r.next()) {
          if (kb == G1_KB - G1_TAIL && wg) {
            wg_wait<0>();
            if (elect) mbar_arrive(rel);
            rel = 0;
            {
              mbar_wait(sb + B_MISC, 0);
              conv_lda_all(a, sb + SM_CV + 16384 + CV_K + ka0);
            }
            bar_sync(5, 256);
          }
          mbar_wait(sb + B_FULL + 8 * r.s, r.ph);
          if (kb == 0 && warp == 0) TLREC(3);
          wg_fence();
          mma(r.s * (SLOT >> 4), kb);
          wg_commit();
          if (kb == G1_KB - 1) break;
          wg_wait<1>();
          if (elect && rel) mbar_arrive(rel);
          rel = sb + B_EMPTY + 8 * r.s;
        }
        bar_arrive(5, 256);
        wg_wait<0>();
      };
      float hb[4];
      auto staged = [&](int second) {
        if (!w) TLREC(4 + wg);
        if (lane == 0) mbar_arrive(sb + B_G1DONE);
        mbar_wait(sb + B_MISC, 0);
#pragma unroll
        for (int i = 0; i < 4; i++) hb[i] = 0.5f * bf_lo(lds16(sb + SM_B1 + (warp * 16 + g + (i & 1) * 8 + (i >> 1) * second) * 2));
        mbar_wait(sb + B_KVDONE, 0);
        if (wg) mbar_wait(sb + B_G1DONE, 0);
      };
      if (R.at != 15) {
        const uint64_t db0 = make_desc(sb + 16384, 4096, 512, 2);
        float acc[80];
        mainloop([&](uint32_t o, int kb) {
#pragma unroll
          for (int k = 0; k < 4; k++) wgmma_ss_n160_t11(acc, da0 + o + k * 128, db0 + o + k * 64, k ? 1 : kb);
        });
        pin_regs<80>(acc);
        staged(0);
        gelu_stage<40>(acc, hb, stg + swz, 2, lane ? 0 : sb + B_STG + 8 * wg + 16);
      } else {
        const uint64_t db0 = make_desc(sb + 24576, 4096, 512, 2);
        float acc[96];
        auto block = [&](float* d, uint64_t da, uint64_t db, int kb) {
#pragma unroll
          for (int k = 0; k < 4; k++) wgmma_ss_n96_t11(d, da + k * 128, db + k * 64, k ? 1 : kb);
        };
        if (wg) mainloop([&](uint32_t o, int kb) { block(acc, da0 + o, db0 + o, kb); block(acc + 48, da0 + o + 512, db0 + o, kb); });
        else mainloop([&](uint32_t o, int kb) { block(acc, da0 + o, db0 + o, kb); });
        pin_regs<96>(acc);
        staged(64);
        gelu_stage<48>(acc, hb, stg + swz, 1 + wg, lane ? 0 : sb + B_STG + 8 * wg + 16);
      }
      __syncwarp();
      if (lane == 0) mbar_arrive(sb + B_STG + 8 * wg);
    }
    {
      if (!wg) conv_lda_all(a, sb + SM_CV + 16384 + wg * CV_K + ka0);
#pragma unroll 1
      for (int i = wg; i < R.ncv; i += 2) {
        const bool more = i + 2 < R.ncv;
        const uint32_t dd = lds16(sb + SM_D + (R.ch + i) * 2);
        a[0] = badd2(a[0], ka0 == 32 ? dd : 0); a[2] = badd2(a[2], ka0 == 16 ? dd : 0);
        float acc[128];
        mbar_wait(sb + B_UFULL + 8 * (i & 3), (i >> 2) & 1);
        bar_sync(5 + wg, 256);
        const bool last = i + 1 == R.ncv;
        if (last && elect) mbar_arrive(sb + B_EMPTY);
        if (!w && i < 4) TLREC(22 + i);
        wg_fence();
        conv_mma(acc, a, make_desc(sb + cv_in(i), 4096, 128, 0));
        wg_commit();
        if (!last) bar_arrive(5 + (wg ^ 1), 256);
        if (more) {
          mbar_wait(sb + B_SFREE + 8 * wg, (i >> 1) & 1);
          mbar_wait(sb + B_KFULL + 8 * ((i + 2) & 3), ((i + 2) >> 2) & 1);
        } else if (last) mbar_wait(sb + B_PDONE, 0);
        wg_wait<0>();
        pin_regs<128>(acc);
        if (lane == 0) mbar_arrive(sb + B_CEMPTY + 8 * (i & 3));
        if (last && elect) mbar_arrive(sb + B_EMPTY + 8);
        const uint32_t red = sb + cv_red(i, R.ncv), ka = sb + cv_taps(i + 2) + ka0;
        if (lane < 8 * w) sts32(red + w * CV_REDW + lane * 4, 0);
        const uint32_t wr = red + w * CV_REDW + (8 * (3 - t + w) + g) * 4;
        if (more) conv_drain<true>(acc, wr, a, ka); else conv_drain<false>(acc, wr, a, ka);
        __syncwarp();
        if (lane == 0) mbar_arrive(sb + B_STG + 8 * wg + (more ? 0 : 16));
      }
      if (!w) TLREC(20 + wg);
    }
    if (R.sg >= 0) {
      const int srow = R.sg * 64 + warp * 16;
      const uint64_t db0 = make_desc(sb + 16384, 16, 1024, 1);
      const uint32_t xo = sb + SM_CV + warp * 2304, xa = xo + (lane & 15) * 144;
      float acc[72];
      Ring r{G1_KB % NSTAGE, (G1_KB / NSTAGE) & 1};
      bar_sync(8, 256);
      uint32_t rel = 0;
#pragma unroll 1
      for (int kb = 0; kb < G2_KB; kb++, r.next()) {
        if (kb == G2_KB - G2_TAIL && wg) {
          wg_wait<0>();
          if (elect) mbar_arrive_remote(rel);
          rel = 0;
          bar_sync(7, 256);
        }
        mbar_wait(sb + B_FULL + 8 * r.s, r.ph);
        if (kb == 0 && !w) TLREC(17 + wg);
        if (kb == 8 && warp == 0) TLREC(26);
        if (kb == 20 && warp == 0) TLREC(8);
        if (kb == 27 && warp == 0) TLREC(30);
        const uint64_t da = da0 + r.s * (SLOT >> 4), db = db0 + r.s * (SLOT >> 4);
        wg_fence();
        wgmma_ss_n144_t10(acc, da, db, kb);
#pragma unroll
        for (int k = 1; k < 4; k++) wgmma_ss_n144_t10(acc, da + k * 128, db + k * 2, 1);
        wg_commit();
        if (kb == G2_KB - 1) break;
        wg_wait<1>();
        if (elect && rel) mbar_arrive_remote(rel);
        rel = kb == G2_KB - NSTAGE ? mapa(sb + B_XRDY, rank ^ 1) : sb + B_EMPTY + 8 * r.s;
      }
      if (!wg) bar_arrive(7, 256);
      const uint32_t xz = sb + XSLOT * SLOT + wg * 10240 + wtid * 16;
      const uint32_t rz = mapa(xz, rank ^ 1), rb = mapa(sb + B_XFULL + 16 * wg, rank ^ 1);
      mbar_wait(sb + B_XRDY, 0);
      wg_wait<0>();
      pin_regs<72>(acc);
      if (!w) TLREC(28 + wg);
#pragma unroll
      for (int i = 0; i < 32; i += 8)
        asm volatile("st.async.weak.shared::cluster.mbarrier::complete_tx::bytes.v4.b32 [%0], {%1,%2,%3,%4}, [%5];"
                     :: "r"(rz + i * 256), "r"(pack_bf16(acc[i], acc[i + 1])), "r"(pack_bf16(acc[i + 2], acc[i + 3])),
                        "r"(pack_bf16(acc[i + 4], acc[i + 5])), "r"(pack_bf16(acc[i + 6], acc[i + 7])), "r"(rb + (i < 8 * XP ? 0 : 8)) : "memory");
      asm volatile("st.async.weak.shared::cluster.mbarrier::complete_tx::bytes.v2.b32 [%0], {%1,%2}, [%3];"
                   :: "r"(rz + 8192), "r"(pack_bf16(acc[32], acc[33])), "r"(pack_bf16(acc[34], acc[35])), "r"(rb + 8) : "memory");
      uint32_t xx[18], ss[18];
      mbar_wait(sb + B_XY, 0);
      {
        const uint32_t ya = sb + SM_DED + wg * 9216 + swz;
        const uint4 st0 = lds128(sb + SM_ST + (warp * 16 + g) * 16), st1 = lds128(sb + SM_ST + (warp * 16 + g + 8) * 16);
        const float hb0 = 0.5f * bf_lo(lds16(sb + SM_B2 + (warp * 16 + g) * 2)), hb1 = 0.5f * bf_lo(lds16(sb + SM_B2 + (warp * 16 + g + 8) * 2));
#pragma unroll
        for (int q = 0; q < 8; q += 2) { ldsm4(xx + 2 * q, xa + (lane >> 4) * 16 + q * 16); ldsm4t(ss + 2 * q, ya + q * 1024); }
        ldsm2(xx + 16, xa + 128);
        ldsm2t(ss + 16, ya + 8 * 1024);
#pragma unroll
        for (int i = 0; i < 18; i++) {
          const uint4& st = (i & 1) ? st1 : st0;
          const uint32_t c = bsub2(xx[i], st.x);
          ss[i] = bmul2(bfma2(c, st.y, bmul2(c, st.z)), ss[i]);
        }
#pragma unroll
        for (int i = 36; i < 72; i++) acc[i] = fmaf(acc[i], 0.5f, (i & 2) ? hb1 : hb0);
      }
      char* const op = reinterpret_cast<char*>(P.out) + srow * (D_ * 2) + R.dk * 16 + lane * 16;
      uint32_t oo[5];
#pragma unroll
      for (int j = 0; j < 5; j++) oo[j] = ((lane + 32 * j) * 57 >> 9) * (D_ * 2 - 144) + j * 512;
      uint32_t pv[20];
#pragma unroll
      for (int pc = 0; pc < 2; pc++) {
        const int q0 = pc ? XP : 0, q1 = pc ? 5 : XP;
        mbar_wait_cluster(sb + B_XFULL + 16 * wg + 8 * pc, 0);
        if (!w && !pc) TLREC(9 + wg);
#pragma unroll
        for (int q = q0; q < q1; q++) { const uint4 v = lds128(xz + q * 2048); pv[4 * q] = v.x; pv[4 * q + 1] = v.y; pv[4 * q + 2] = v.z; pv[4 * q + 3] = v.w; }
#pragma unroll
        for (int i = 4 * q0; i < 4 * q1 && i < 18; i++)
          xx[i] = bfma2(ss[i], pack_bf16(silu_half(fmaf(bf_lo(pv[i]), 0.5f, acc[36 + 2 * i])), silu_half(fmaf(bf_hi(pv[i]), 0.5f, acc[37 + 2 * i]))), xx[i]);
      }
#pragma unroll
      for (int q = 0; q < 4; q++) stsm4(xa + (lane >> 4) * 16 + q * 32, xx[4 * q], xx[4 * q + 1], xx[4 * q + 2], xx[4 * q + 3]);
      stsm2(xa + 128, xx[16], xx[17]);
      __syncwarp();
      if (lane == 0) mbar_arrive(sb + B_DONE);
#pragma unroll
      for (int j = 0; j < 5; j++)
        if (j < 4 || lane < 16) *reinterpret_cast<uint4*>(op + oo[j]) = lds128(xo + (lane + 32 * j) * 16);
      if (!w) TLREC(11 + wg);
    }
    TLEND();
  }
}

typedef CUresult (*EncodeFn)(CUtensorMap*, CUtensorMapDataType, cuuint32_t, void*, const cuuint64_t*, const cuuint64_t*, const cuuint32_t*,
                             const cuuint32_t*, CUtensorMapInterleave, CUtensorMapSwizzle, CUtensorMapL2promotion, CUtensorMapFloatOOBfill);

void make_map(EncodeFn fn, CUtensorMap* m, const void* ptr, int rank, const cuuint64_t* dims, const cuuint64_t* strides, const cuuint32_t* box,
              CUtensorMapSwizzle sw) {
  const cuuint32_t es[3] = {1, 1, 1};
  fn(m, CU_TENSOR_MAP_DATA_TYPE_BFLOAT16, rank, const_cast<void*>(ptr), dims, strides, box, es, CU_TENSOR_MAP_INTERLEAVE_NONE, sw,
     CU_TENSOR_MAP_L2_PROMOTION_L2_256B, CU_TENSOR_MAP_FLOAT_OOB_FILL_NONE);
}

void make_roles(Role* R) {
  int nl = 0, ch = 0;
  for (int gi = 0; gi < 8; gi++)
    for (int b = 0; b < 132; b++) {
      const int c = b >> 1, rank = b & 1;
      int g, idx;
      if (c < 4) { g = 0; idx = 4 + c; }
      else if (c < 36) { g = (c - 4) & 7; idx = (c - 4) >> 3; }
      else if (c < 64) { g = 1 + (c - 36) % 7; idx = 4 + (c - 36) / 7; }
      else { g = c - 58; idx = 8; }
      if (g != gi) continue;
      Role& r = R[b];
      r.sg = (int8_t)(idx < 8 ? 2 * (2 * g + (idx >> 2)) : -1);
      r.dk = (int8_t)((idx & 3) * 18 + rank * 9);
      r.ds = (int8_t)((idx & 3) * 18 + (rank ^ 1) * 9);
      if (idx < (g < 2 ? 6 : 7)) {
        const int c1 = (g < 2 ? 6 * g : 7 * g - 2) + idx;
        r.fg = (int8_t)((2 * (c1 / 3) + rank) * 2); r.at = (int8_t)(c1 % 3 * 5); r.ncv = NCV_REG;
      } else {
        r.fg = (int8_t)(3 * nl++); r.at = 15; r.ncv = idx < 8 ? NCV_LEFT : NCV_LONG;
      }
      r.ch = (int16_t)ch;
      ch += r.ncv;
    }
}

}

extern "C" void kernel_launch(void* const* d_in, const int* in_sizes, int n_in, void* d_out, int out_size) {
  static Params P;
  static Hot H;
  static const void* cached[5] = {nullptr, nullptr, nullptr, nullptr, nullptr};
  const void* now[5] = {d_in[0], d_in[1], d_in[2], d_in[7], d_in[9]};
  bool same = true;
  for (int i = 0; i < 5; i++) { same = same && cached[i] == now[i]; cached[i] = now[i]; }
  if (!same) {
    void* fp = nullptr;
    cudaDriverEntryPointQueryResult qr;
    cudaGetDriverEntryPoint("cuTensorMapEncodeTiled", &fp, cudaEnableDefault, &qr);
    EncodeFn fn = (EncodeFn)fp;
    void* ps;
    cudaGetSymbolAddress(&ps, g_scratch);
    H.S = (Scratch*)ps;
    const void *py = (char*)ps + offsetof(Scratch, y), *pb = (char*)ps + offsetof(Scratch, ub);
    { cuuint64_t d[3] = {64, S_, F_ / 64}, s[2] = {F_ * 2, 128}; cuuint32_t b[3] = {64, 64, 2}; make_map(fn, &P.m_w1, d_in[7], 3, d, s, b, CU_TENSOR_MAP_SWIZZLE_128B);
      b[2] = 3; make_map(fn, &P.m_w1l, d_in[7], 3, d, s, b, CU_TENSOR_MAP_SWIZZLE_128B); }
    { cuuint64_t d[3] = {64, F_, S_ / 64}, s[2] = {S_ * 2, 128}; cuuint32_t b[3] = {64, 64, 2}; make_map(fn, &P.m_w2, d_in[9], 3, d, s, b, CU_TENSOR_MAP_SWIZZLE_128B); }
    { cuuint64_t d[2] = {D_, S_}, s[1] = {D_ * 2}; cuuint32_t b[2] = {72, 16}; make_map(fn, &P.m_x, d_in[0], 2, d, s, b, CU_TENSOR_MAP_SWIZZLE_NONE);
      b[0] = 96; b[1] = 20; make_map(fn, &P.m_k, d_in[1], 2, d, s, b, CU_TENSOR_MAP_SWIZZLE_NONE);
      b[1] = 17; make_map(fn, &P.m_v, d_in[2], 2, d, s, b, CU_TENSOR_MAP_SWIZZLE_NONE); }
    { cuuint64_t d[3] = {64, D_, S_ / 64}, s[2] = {S_ * 2, 128}; cuuint32_t b[3] = {64, 72, 2}; make_map(fn, &P.m_y, py, 3, d, s, b, CU_TENSOR_MAP_SWIZZLE_128B); }
    { cuuint64_t d[3] = {2048, D_ / 2, 4}, s[2] = {16384, 4096}; cuuint32_t b[3] = {16, 48, 2}; make_map(fn, &P.m_ub, pb, 3, d, s, b, CU_TENSOR_MAP_SWIZZLE_32B); }
    make_roles(P.role);
    cudaFuncSetAttribute(fused_kernel, cudaFuncAttributeMaxDynamicSharedMemorySize, SM_TOTAL);
  }
  H.x = (const __nv_bfloat16*)d_in[0];
  H.shift_k = (const __nv_bfloat16*)d_in[3]; H.ssm_k = (const __nv_bfloat16*)d_in[4]; H.ssm_D = (const __nv_bfloat16*)d_in[5];
  H.b1 = (const __nv_bfloat16*)d_in[8]; P.b2 = (const __nv_bfloat16*)d_in[10]; P.out = (__nv_bfloat16*)d_out;
  fused_kernel<<<132, 384, SM_TOTAL>>>(H, P);
}
```

```cpp
#include <cuda_runtime.h>
#include <cuda.h>
#include <cuda_bf16.h>
#include <stddef.h>
#include <stdint.h>

namespace {

constexpr int S_ = 2048, D_ = 576, F_ = 4608;
constexpr int NSTAGE = 5, SLOT = 36864;
constexpr int G1_KB = 32, G2_KB = 36;
constexpr int G1_BYTES = 36864, G2_BYTES = 16384 + 18432;
#define NCV_LEFT 4
constexpr int NCV_REG = 4, NCV_LONG = (D_ - 108 * NCV_REG - 20 * NCV_LEFT) / 4;
static_assert(108 * NCV_REG + 20 * NCV_LEFT + 4 * NCV_LONG == D_, "conv split");
constexpr int KV_ROUNDS = 6;
#define XP 2
#define TUNED(name, idx, val) constexpr int name = val
constexpr int G1_TAIL = 4, G2_TAIL = 3;
constexpr int KV0 = 5;

constexpr int CV_K = 4224, CV_REDW = 2112 * 2;
constexpr int SM_DED = NSTAGE * SLOT;
constexpr int SM_CV = SM_DED + 20480;
constexpr int SM_ST1 = 0;
constexpr int SM_ST = SM_CV + 18432, SM_B2 = SM_ST + 2048;
constexpr int SM_B1 = SM_CV + 2 * (8192 + CV_K), SM_D = SM_B1 + 384;
constexpr int SM_BAR = SM_D + 1152;
constexpr int SM_TOTAL = SM_BAR + 768;
static_assert(G1_KB % NSTAGE == 2, "slots 0 and 1 hold the last GEMM1 k-blocks and the last two of the first GEMM2 stages");
static_assert(NCV_REG == 4 && NCV_LEFT == 4 && NCV_LONG % 4 == 0, "the last two channels use buffers 2 and 3");
constexpr int XSLOT = (G1_KB + G2_KB) % NSTAGE;
__device__ __forceinline__ uint32_t kv_buf(int q) { return q == 2 ? SM_DED : SM_CV + q * 8192; }
__device__ __forceinline__ uint32_t cv_red(int i, int n) { return i + 2 == n ? SM_CV : (i & 1) && i + 1 < n ? SLOT + 16384 : SM_DED; }
__device__ __forceinline__ uint32_t cv_in(int i) { return (i & 2 ? SLOT : SM_CV) + (i & 1) * 8192; }
__device__ __forceinline__ uint32_t cv_taps(int i) { return (i & 2 ? SM_ST1 + 24576 : SM_CV + 16384) + (i & 1) * CV_K; }
constexpr int bar_at(int i) { return SM_BAR + 8 * i; }
constexpr int B_FULL = bar_at(0)  , B_KFULL = bar_at(5)  , B_UFULL = bar_at(9)  , B_KVDONE = bar_at(13), B_STORED = bar_at(14)  ,
              B_XFULL = bar_at(16)  , B_XY = bar_at(20), B_MISC = bar_at(21),
              B_EMPTY = bar_at(22)  , B_XRDY = bar_at(27),
              B_SFREE = bar_at(28)  , B_PDONE = bar_at(30),
              B_CEMPTY = bar_at(31)  , B_STG = bar_at(35)  ,
              B_G1DONE = bar_at(39), B_DONE = bar_at(40);
constexpr int C_H = 0, C_KV = 1, C_U = 2  , C_Y = 4, C_SYNC = 5, C_EPOCH = 6, C_COUNT = 7;
constexpr uint32_t EPOCH = 128 * 33;

struct Scratch {
  uint32_t cnt[C_COUNT * 32];
  alignas(1024) uint4 stats[S_];
  alignas(1024) __nv_bfloat16 h[S_ * D_];
  alignas(1024) __nv_bfloat16 ub[D_ * 4096];
  alignas(1024) __nv_bfloat16 y[D_ * S_];
  alignas(1024) __nv_bfloat16 u[D_ * F_];
};
__device__ Scratch g_scratch;

struct Hot {
  const __nv_bfloat16 *x, *shift_k, *ssm_k, *ssm_D, *b1;
  Scratch* S;
};
struct Role {
  int8_t fg;
  int8_t at;
  int8_t sg;
  int8_t dk, ds;
  int8_t ncv;
  int16_t ch;
};
struct Params {
  const __nv_bfloat16* b2;
  __nv_bfloat16* out;
  Role role[132];
  CUtensorMap m_w1, m_w1l, m_w2, m_x, m_y, m_k, m_v, m_ub;
};

#define TLREC(i) do { } while (0)
#define TLEND() do { } while (0)

__device__ __forceinline__ uint32_t smem_u32(const void* p) { return (uint32_t)__cvta_generic_to_shared(p); }
__device__ __forceinline__ void mbar_init(uint32_t bar, uint32_t cnt) { asm volatile("mbarrier.init.shared::cta.b64 [%0], %1;" :: "r"(bar), "r"(cnt) : "memory"); }
__device__ __forceinline__ void mbar_expect_tx(uint32_t bar, uint32_t bytes) { asm volatile("mbarrier.arrive.expect_tx.shared::cta.b64 _, [%0], %1;" :: "r"(bar), "r"(bytes) : "memory"); }
__device__ __forceinline__ void mbar_arrive(uint32_t bar) { asm volatile("mbarrier.arrive.shared::cta.b64 _, [%0];" :: "r"(bar) : "memory"); }
__device__ __forceinline__ uint32_t mapa(uint32_t addr, uint32_t cta) { uint32_t r; asm volatile("mapa.shared::cluster.u32 %0, %1, %2;" : "=r"(r) : "r"(addr), "r"(cta)); return r; }
__device__ __forceinline__ void mbar_arrive_remote(uint32_t rbar) { asm volatile("mbarrier.arrive.shared::cluster.b64 _, [%0];" :: "r"(rbar) : "memory"); }
__device__ __forceinline__ uint32_t clk() { uint32_t c; asm volatile("mov.u32 %0, %%clock;" : "=r"(c)); return c; }
__device__ __forceinline__ bool elect_one() {
  uint32_t p; asm volatile("{ .reg .pred p; elect.sync _|p, 0xffffffff; selp.u32 %0, 1, 0, p; }" : "=r"(p)); return p;
}
__device__ __forceinline__ void guard(uint32_t t0) { if ((int32_t)(clk() - t0) < 0) __trap(); }
__device__ __forceinline__ void mbar_wait(uint32_t bar, uint32_t parity) {
  asm volatile("{\n .reg .pred p;\n W_%=:\n mbarrier.try_wait.parity.shared::cta.b64 p, [%0], %1;\n @!p bra W_%=;\n }" :: "r"(bar), "r"(parity) : "memory");
}
__device__ __forceinline__ void mbar_wait_cluster(uint32_t bar, uint32_t parity) {
  asm volatile("{\n .reg .pred p;\n W_%=:\n mbarrier.try_wait.parity.acquire.cluster.shared::cta.b64 p, [%0], %1;\n @!p bra W_%=;\n }" :: "r"(bar), "r"(parity) : "memory");
}
__device__ __forceinline__ bool mbar_try(uint32_t bar, uint32_t parity) {
  uint32_t ok;
  asm volatile("{ .reg .pred p; mbarrier.try_wait.parity.shared::cta.b64 p, [%1], %2, 100000; selp.u32 %0, 1, 0, p; }" : "=r"(ok) : "r"(bar), "r"(parity) : "memory");
  return ok;
}
__device__ __forceinline__ bool mbar_test(uint32_t bar, uint32_t parity) {
  uint32_t ok;
  asm volatile("{ .reg .pred p; mbarrier.test_wait.parity.shared::cta.b64 p, [%1], %2; selp.u32 %0, 1, 0, p; }" : "=r"(ok) : "r"(bar), "r"(parity) : "memory");
  return ok;
}
__device__ __forceinline__ void mbar_wait_guarded(uint32_t bar, uint32_t t0, uint32_t parity = 0) { while (!mbar_try(bar, parity)) guard(t0); }
__device__ __forceinline__ void tma2d(uint32_t dst, const CUtensorMap* m, int c0, int c1, uint32_t bar) {
  asm volatile("cp.async.bulk.tensor.2d.shared::cluster.global.mbarrier::complete_tx::bytes [%0], [%1, {%3, %4}], [%2];"
               :: "r"(dst), "l"(m), "r"(bar), "r"(c0), "r"(c1) : "memory");
}
__device__ __forceinline__ void tma3d(uint32_t dst, const CUtensorMap* m, int c0, int c1, int c2, uint32_t bar) {
  asm volatile("cp.async.bulk.tensor.3d.shared::cluster.global.mbarrier::complete_tx::bytes [%0], [%1, {%3, %4, %5}], [%2];"
               :: "r"(dst), "l"(m), "r"(bar), "r"(c0), "r"(c1), "r"(c2) : "memory");
}
__device__ __forceinline__ uint64_t evict_first() { uint64_t p; asm("createpolicy.fractional.L2::evict_first.b64 %0, 1.0;" : "=l"(p)); return p; }
__device__ __forceinline__ void tma3d_ef(uint32_t dst, const CUtensorMap* m, int c0, int c1, int c2, uint32_t bar) {
  asm volatile("cp.async.bulk.tensor.3d.shared::cluster.global.mbarrier::complete_tx::bytes.L2::cache_hint [%0], [%1, {%3, %4, %5}], [%2], %6;"
               :: "r"(dst), "l"(m), "r"(bar), "r"(c0), "r"(c1), "r"(c2), "l"(evict_first()) : "memory");
}
__device__ __forceinline__ void tma2d_ef(uint32_t dst, const CUtensorMap* m, int c0, int c1, uint32_t bar) {
  asm volatile("cp.async.bulk.tensor.2d.shared::cluster.global.mbarrier::complete_tx::bytes.L2::cache_hint [%0], [%1, {%3, %4}], [%2], %5;"
               :: "r"(dst), "l"(m), "r"(bar), "r"(c0), "r"(c1), "l"(evict_first()) : "memory");
}
__device__ __forceinline__ void bulk_load_ef(uint32_t dst, const void* src, uint32_t bytes, uint32_t bar) {
  asm volatile("cp.async.bulk.shared::cluster.global.mbarrier::complete_tx::bytes.L2::cache_hint [%0], [%1], %2, [%3], %4;"
               :: "r"(dst), "l"(src), "r"(bytes), "r"(bar), "l"(evict_first()) : "memory");
}
__device__ __forceinline__ void bulk_store(void* dst, uint32_t src, uint32_t bytes) {
  asm volatile("cp.async.bulk.global.shared::cta.bulk_group [%0], [%1], %2;" :: "l"(dst), "r"(src), "r"(bytes) : "memory");
}
__device__ __forceinline__ void bulk_load(uint32_t dst, const void* src, uint32_t bytes, uint32_t bar) {
  asm volatile("cp.async.bulk.shared::cluster.global.mbarrier::complete_tx::bytes [%0], [%1], %2, [%3];" :: "r"(dst), "l"(src), "r"(bytes), "r"(bar) : "memory");
}
__device__ __forceinline__ void tma3d_store(const CUtensorMap* m, uint32_t src, int c0, int c1, int c2) {
  asm volatile("cp.async.bulk.tensor.3d.global.shared::cta.bulk_group [%0, {%2, %3, %4}], [%1];" :: "l"(m), "r"(src), "r"(c0), "r"(c1), "r"(c2) : "memory");
}
__device__ __forceinline__ void bulk_commit() { asm volatile("cp.async.bulk.commit_group;" ::: "memory"); }
__device__ __forceinline__ void bulk_wait_all() { asm volatile("cp.async.bulk.wait_group 0;" ::: "memory"); }
__device__ __forceinline__ void fence_async_smem() { asm volatile("fence.proxy.async.shared::cta;" ::: "memory"); }
__device__ __forceinline__ void fence_async_global() { asm volatile("fence.proxy.async.global;" ::: "memory"); }
__device__ __forceinline__ uint32_t ld_cnt(Scratch* S, int c) { uint32_t v; asm volatile("ld.relaxed.gpu.global.u32 %0, [%1];" : "=r"(v) : "l"(S->cnt + c * 32) : "memory"); return v; }
__device__ __forceinline__ void signal(Scratch* S, int c, uint32_t inc) { asm volatile("red.release.gpu.global.add.u32 [%0], %1;" :: "l"(S->cnt + c * 32), "r"(inc) : "memory"); }
__device__ __forceinline__ bool reached(Scratch* S, int c, uint32_t ep) { return ld_cnt(S, c) - ep >= EPOCH; }
__device__ __forceinline__ void await(Scratch* S, int c, uint32_t ep) { while (!reached(S, c, ep)) { } }
__device__ __forceinline__ void bar_sync(int id, int n) { asm volatile("bar.sync %0, %1;" :: "r"(id), "r"(n) : "memory"); }
__device__ __forceinline__ void bar_arrive(int id, int n) { asm volatile("bar.arrive %0, %1;" :: "r"(id), "r"(n) : "memory"); }
__device__ __forceinline__ void wg_fence() { asm volatile("wgmma.fence.sync.aligned;" ::: "memory"); }
__device__ __forceinline__ void wg_commit() { asm volatile("wgmma.commit_group.sync.aligned;" ::: "memory"); }
template <int N> __device__ __forceinline__ void wg_wait() { asm volatile("wgmma.wait_group.sync.aligned %0;" :: "n"(N) : "memory"); }
template <int N> __device__ __forceinline__ void pin_regs(float* a) {
#pragma unroll
  for (int i = 0; i < N; i++) asm volatile("" : "+f"(a[i]) :: "memory");
}
__device__ __forceinline__ uint64_t make_desc(uint32_t addr, uint32_t lbo, uint32_t sbo, uint32_t swz) {
  return (uint64_t)((addr & 0x3FFFF) >> 4) | ((uint64_t)(lbo >> 4) << 16) | ((uint64_t)(sbo >> 4) << 32) | ((uint64_t)swz << 62);
}
__device__ __forceinline__ uint32_t pack_bf16(float lo, float hi) { uint32_t r; asm("cvt.rn.bf16x2.f32 %0, %1, %2;" : "=r"(r) : "f"(hi), "f"(lo)); return r; }
__device__ __forceinline__ float bf_lo(uint32_t p) { return __uint_as_float(p << 16); }
__device__ __forceinline__ float bf_hi(uint32_t p) { return __uint_as_float(p & 0xffff0000u); }
__device__ __forceinline__ float round_bf16(float v) { return bf_lo(pack_bf16(v, 0.f)); }
__device__ __forceinline__ uint32_t bmul2(uint32_t a, uint32_t b) { uint32_t r; asm("mul.rn.bf16x2 %0, %1, %2;" : "=r"(r) : "r"(a), "r"(b)); return r; }
__device__ __forceinline__ uint32_t badd2(uint32_t a, uint32_t b) { uint32_t r; asm("add.rn.bf16x2 %0, %1, %2;" : "=r"(r) : "r"(a), "r"(b)); return r; }
__device__ __forceinline__ uint32_t bfma2(uint32_t a, uint32_t b, uint32_t c) { uint32_t r; asm("fma.rn.bf16x2 %0, %1, %2, %3;" : "=r"(r) : "r"(a), "r"(b), "r"(c)); return r; }
__device__ __forceinline__ uint32_t bsub2(uint32_t a, uint32_t b) { uint32_t r; asm("sub.rn.bf16x2 %0, %1, %2;" : "=r"(r) : "r"(a), "r"(b)); return r; }
__device__ __forceinline__ float tanh_fast(float v) { float r; asm("tanh.approx.f32 %0, %1;" : "=f"(r) : "f"(v)); return r; }
__device__ __forceinline__ float gelu_half(float h) {
  return fmaf(h, tanh_fast(h * fmaf(h * h, 8.0f * 0.7978845608028654f * 0.044715f, 2.0f * 0.7978845608028654f)), h);
}
__device__ __forceinline__ float silu_half(float h) { return fmaf(h, tanh_fast(h), h); }
__device__ __forceinline__ uint32_t ldg32(const void* p) { uint32_t v; asm volatile("ld.global.u32 %0, [%1];" : "=r"(v) : "l"(p) : "memory"); return v; }
__device__ __forceinline__ uint32_t lds32(uint32_t a) { uint32_t v; asm volatile("ld.shared.u32 %0, [%1];" : "=r"(v) : "r"(a) : "memory"); return v; }
__device__ __forceinline__ uint32_t lds16(uint32_t a) { uint32_t v; asm volatile("ld.shared.u16 %0, [%1];" : "=r"(v) : "r"(a) : "memory"); return v; }
__device__ __forceinline__ uint4 lds128(uint32_t a) { uint4 v; asm volatile("ld.shared.v4.u32 {%0,%1,%2,%3}, [%4];" : "=r"(v.x), "=r"(v.y), "=r"(v.z), "=r"(v.w) : "r"(a) : "memory"); return v; }
__device__ __forceinline__ void sts128(uint32_t a, uint32_t x, uint32_t y, uint32_t z, uint32_t w) {
  asm volatile("st.shared.v4.u32 [%0], {%1,%2,%3,%4};" :: "r"(a), "r"(x), "r"(y), "r"(z), "r"(w) : "memory");
}
__device__ __forceinline__ void sts32(uint32_t a, uint32_t v) { asm volatile("st.shared.u32 [%0], %1;" :: "r"(a), "r"(v) : "memory"); }
__device__ __forceinline__ void ldsm4(uint32_t* r, uint32_t a) {
  asm volatile("ldmatrix.sync.aligned.m8n8.x4.shared.b16 {%0,%1,%2,%3}, [%4];" : "=r"(r[0]), "=r"(r[1]), "=r"(r[2]), "=r"(r[3]) : "r"(a) : "memory");
}
__device__ __forceinline__ void ldsm2(uint32_t* r, uint32_t a) {
  asm volatile("ldmatrix.sync.aligned.m8n8.x2.shared.b16 {%0,%1}, [%2];" : "=r"(r[0]), "=r"(r[1]) : "r"(a) : "memory");
}
__device__ __forceinline__ void ldsm4t(uint32_t* r, uint32_t a) {
  asm volatile("ldmatrix.sync.aligned.m8n8.x4.trans.shared.b16 {%0,%1,%2,%3}, [%4];" : "=r"(r[0]), "=r"(r[1]), "=r"(r[2]), "=r"(r[3]) : "r"(a) : "memory");
}
__device__ __forceinline__ void ldsm2t(uint32_t* r, uint32_t a) {
  asm volatile("ldmatrix.sync.aligned.m8n8.x2.trans.shared.b16 {%0,%1}, [%2];" : "=r"(r[0]), "=r"(r[1]) : "r"(a) : "memory");
}
__device__ __forceinline__ void stsm4(uint32_t a, uint32_t r0, uint32_t r1, uint32_t r2, uint32_t r3) {
  asm volatile("stmatrix.sync.aligned.m8n8.x4.shared.b16 [%0], {%1,%2,%3,%4};" :: "r"(a), "r"(r0), "r"(r1), "r"(r2), "r"(r3) : "memory");
}
__device__ __forceinline__ void stsm2(uint32_t a, uint32_t r0, uint32_t r1) {
  asm volatile("stmatrix.sync.aligned.m8n8.x2.shared.b16 [%0], {%1,%2};" :: "r"(a), "r"(r0), "r"(r1) : "memory");
}
__device__ __forceinline__ void stsm4t(uint32_t a, uint32_t r0, uint32_t r1, uint32_t r2, uint32_t r3) {
  asm volatile("stmatrix.sync.aligned.m8n8.x4.trans.shared.b16 [%0], {%1,%2,%3,%4};" :: "r"(a), "r"(r0), "r"(r1), "r"(r2), "r"(r3) : "memory");
}

__device__ __forceinline__ void wgmma_ss_n144_t10(float* d, uint64_t da, uint64_t db, int sd) {
  asm volatile("{ .reg .pred p; setp.ne.b32 p, %74, 0;\n"
      "wgmma.mma_async.sync.aligned.m64n144k16.f32.bf16.bf16 {"
      "%0,%1,%2,%3,%4,%5,%6,%7,%8,%9,%10,%11,%12,%13,%14,%15,"
      "%16,%17,%18,%19,%20,%21,%22,%23,%24,%25,%26,%27,%28,%29,%30,%31,"
      "%32,%33,%34,%35,%36,%37,%38,%39,%40,%41,%42,%43,%44,%45,%46,%47,"
      "%48,%49,%50,%51,%52,%53,%54,%55,%56,%57,%58,%59,%60,%61,%62,%63,"
      "%64,%65,%66,%67,%68,%69,%70,%71"
      "}, %72, %73, p, 1, 1, 1, 0; }"
    : "+f"(d[0]), "+f"(d[1]), "+f"(d[2]), "+f"(d[3]), "+f"(d[4]), "+f"(d[5]), "+f"(d[6]), "+f"(d[7]),
      "+f"(d[8]), "+f"(d[9]), "+f"(d[10]), "+f"(d[11]), "+f"(d[12]), "+f"(d[13]), "+f"(d[14]), "+f"(d[15]),
      "+f"(d[16]), "+f"(d[17]), "+f"(d[18]), "+f"(d[19]), "+f"(d[20]), "+f"(d[21]), "+f"(d[22]), "+f"(d[23]),
      "+f"(d[24]), "+f"(d[25]), "+f"(d[26]), "+f"(d[27]), "+f"(d[28]), "+f"(d[29]), "+f"(d[30]), "+f"(d[31]),
      "+f"(d[32]), "+f"(d[33]), "+f"(d[34]), "+f"(d[35]), "+f"(d[36]), "+f"(d[37]), "+f"(d[38]), "+f"(d[39]),
      "+f"(d[40]), "+f"(d[41]), "+f"(d[42]), "+f"(d[43]), "+f"(d[44]), "+f"(d[45]), "+f"(d[46]), "+f"(d[47]),
      "+f"(d[48]), "+f"(d[49]), "+f"(d[50]), "+f"(d[51]), "+f"(d[52]), "+f"(d[53]), "+f"(d[54]), "+f"(d[55]),
      "+f"(d[56]), "+f"(d[57]), "+f"(d[58]), "+f"(d[59]), "+f"(d[60]), "+f"(d[61]), "+f"(d[62]), "+f"(d[63]),
      "+f"(d[64]), "+f"(d[65]), "+f"(d[66]), "+f"(d[67]), "+f"(d[68]), "+f"(d[69]), "+f"(d[70]), "+f"(d[71])
    : "l"(da), "l"(db), "r"(sd));
}

__device__ __forceinline__ void wgmma_ss_n160_t11(float* d, uint64_t da, uint64_t db, int sd) {
  asm volatile("{ .reg .pred p; setp.ne.b32 p, %82, 0;\n"
      "wgmma.mma_async.sync.aligned.m64n160k16.f32.bf16.bf16 {"
      "%0,%1,%2,%3,%4,%5,%6,%7,%8,%9,%10,%11,%12,%13,%14,%15,"
      "%16,%17,%18,%19,%20,%21,%22,%23,%24,%25,%26,%27,%28,%29,%30,%31,"
      "%32,%33,%34,%35,%36,%37,%38,%39,%40,%41,%42,%43,%44,%45,%46,%47,"
      "%48,%49,%50,%51,%52,%53,%54,%55,%56,%57,%58,%59,%60,%61,%62,%63,"
      "%64,%65,%66,%67,%68,%69,%70,%71,%72,%73,%74,%75,%76,%77,%78,%79"
      "}, %80, %81, p, 1, 1, 1, 1; }"
    : "+f"(d[0]), "+f"(d[1]), "+f"(d[2]), "+f"(d[3]), "+f"(d[4]), "+f"(d[5]), "+f"(d[6]), "+f"(d[7]),
      "+f"(d[8]), "+f"(d[9]), "+f"(d[10]), "+f"(d[11]), "+f"(d[12]), "+f"(d[13]), "+f"(d[14]), "+f"(d[15]),
      "+f"(d[16]), "+f"(d[17]), "+f"(d[18]), "+f"(d[19]), "+f"(d[20]), "+f"(d[21]), "+f"(d[22]), "+f"(d[23]),
      "+f"(d[24]), "+f"(d[25]), "+f"(d[26]), "+f"(d[27]), "+f"(d[28]), "+f"(d[29]), "+f"(d[30]), "+f"(d[31]),
      "+f"(d[32]), "+f"(d[33]), "+f"(d[34]), "+f"(d[35]), "+f"(d[36]), "+f"(d[37]), "+f"(d[38]), "+f"(d[39]),
      "+f"(d[40]), "+f"(d[41]), "+f"(d[42]), "+f"(d[43]), "+f"(d[44]), "+f"(d[45]), "+f"(d[46]), "+f"(d[47]),
      "+f"(d[48]), "+f"(d[49]), "+f"(d[50]), "+f"(d[51]), "+f"(d[52]), "+f"(d[53]), "+f"(d[54]), "+f"(d[55]),
      "+f"(d[56]), "+f"(d[57]), "+f"(d[58]), "+f"(d[59]), "+f"(d[60]), "+f"(d[61]), "+f"(d[62]), "+f"(d[63]),
      "+f"(d[64]), "+f"(d[65]), "+f"(d[66]), "+f"(d[67]), "+f"(d[68]), "+f"(d[69]), "+f"(d[70]), "+f"(d[71]),
      "+f"(d[72]), "+f"(d[73]), "+f"(d[74]), "+f"(d[75]), "+f"(d[76]), "+f"(d[77]), "+f"(d[78]), "+f"(d[79])
    : "l"(da), "l"(db), "r"(sd));
}

__device__ __forceinline__ void wgmma_ss_n96_t11(float* d, uint64_t da, uint64_t db, int sd) {
  asm volatile("{ .reg .pred p; setp.ne.b32 p, %50, 0;\n"
      "wgmma.mma_async.sync.aligned.m64n96k16.f32.bf16.bf16 {"
      "%0,%1,%2,%3,%4,%5,%6,%7,%8,%9,%10,%11,%12,%13,%14,%15,"
      "%16,%17,%18,%19,%20,%21,%22,%23,%24,%25,%26,%27,%28,%29,%30,%31,"
      "%32,%33,%34,%35,%36,%37,%38,%39,%40,%41,%42,%43,%44,%45,%46,%47"
      "}, %48, %49, p, 1, 1, 1, 1; }"
    : "+f"(d[0]), "+f"(d[1]), "+f"(d[2]), "+f"(d[3]), "+f"(d[4]), "+f"(d[5]), "+f"(d[6]), "+f"(d[7]),
      "+f"(d[8]), "+f"(d[9]), "+f"(d[10]), "+f"(d[11]), "+f"(d[12]), "+f"(d[13]), "+f"(d[14]), "+f"(d[15]),
      "+f"(d[16]), "+f"(d[17]), "+f"(d[18]), "+f"(d[19]), "+f"(d[20]), "+f"(d[21]), "+f"(d[22]), "+f"(d[23]),
      "+f"(d[24]), "+f"(d[25]), "+f"(d[26]), "+f"(d[27]), "+f"(d[28]), "+f"(d[29]), "+f"(d[30]), "+f"(d[31]),
      "+f"(d[32]), "+f"(d[33]), "+f"(d[34]), "+f"(d[35]), "+f"(d[36]), "+f"(d[37]), "+f"(d[38]), "+f"(d[39]),
      "+f"(d[40]), "+f"(d[41]), "+f"(d[42]), "+f"(d[43]), "+f"(d[44]), "+f"(d[45]), "+f"(d[46]), "+f"(d[47])
    : "l"(da), "l"(db), "r"(sd));
}

__device__ __forceinline__ void wgmma_rs_n16(float* d, const uint32_t* a, uint64_t db, int sd) {
  asm volatile("{ .reg .pred p; setp.ne.b32 p, %13, 0;\n"
      "wgmma.mma_async.sync.aligned.m64n16k16.f32.bf16.bf16 {"
      "%0,%1,%2,%3,%4,%5,%6,%7"
      "}, {%8,%9,%10,%11}, %12, p, 1, 1, 0; }"
    : "+f"(d[0]), "+f"(d[1]), "+f"(d[2]), "+f"(d[3]), "+f"(d[4]), "+f"(d[5]), "+f"(d[6]), "+f"(d[7])
    : "r"(a[0]), "r"(a[1]), "r"(a[2]), "r"(a[3]), "l"(db), "r"(sd));
}

__device__ __forceinline__ void wgmma_rs_n32(float* d, const uint32_t* a, uint64_t db, int sd) {
  asm volatile("{ .reg .pred p; setp.ne.b32 p, %21, 0;\n"
      "wgmma.mma_async.sync.aligned.m64n32k16.f32.bf16.bf16 {"
      "%0,%1,%2,%3,%4,%5,%6,%7,%8,%9,%10,%11,%12,%13,%14,%15"
      "}, {%16,%17,%18,%19}, %20, p, 1, 1, 0; }"
    : "+f"(d[0]), "+f"(d[1]), "+f"(d[2]), "+f"(d[3]), "+f"(d[4]), "+f"(d[5]), "+f"(d[6]), "+f"(d[7]),
      "+f"(d[8]), "+f"(d[9]), "+f"(d[10]), "+f"(d[11]), "+f"(d[12]), "+f"(d[13]), "+f"(d[14]), "+f"(d[15])
    : "r"(a[0]), "r"(a[1]), "r"(a[2]), "r"(a[3]), "l"(db), "r"(sd));
}

__device__ __forceinline__ void wgmma_rs_n48(float* d, const uint32_t* a, uint64_t db, int sd) {
  asm volatile("{ .reg .pred p; setp.ne.b32 p, %29, 0;\n"
      "wgmma.mma_async.sync.aligned.m64n48k16.f32.bf16.bf16 {"
      "%0,%1,%2,%3,%4,%5,%6,%7,%8,%9,%10,%11,%12,%13,%14,%15,"
      "%16,%17,%18,%19,%20,%21,%22,%23"
      "}, {%24,%25,%26,%27}, %28, p, 1, 1, 0; }"
    : "+f"(d[0]), "+f"(d[1]), "+f"(d[2]), "+f"(d[3]), "+f"(d[4]), "+f"(d[5]), "+f"(d[6]), "+f"(d[7]),
      "+f"(d[8]), "+f"(d[9]), "+f"(d[10]), "+f"(d[11]), "+f"(d[12]), "+f"(d[13]), "+f"(d[14]), "+f"(d[15]),
      "+f"(d[16]), "+f"(d[17]), "+f"(d[18]), "+f"(d[19]), "+f"(d[20]), "+f"(d[21]), "+f"(d[22]), "+f"(d[23])
    : "r"(a[0]), "r"(a[1]), "r"(a[2]), "r"(a[3]), "l"(db), "r"(sd));
}

__device__ __forceinline__ void wgmma_rs_n64(float* d, const uint32_t* a, uint64_t db, int sd) {
  asm volatile("{ .reg .pred p; setp.ne.b32 p, %37, 0;\n"
      "wgmma.mma_async.sync.aligned.m64n64k16.f32.bf16.bf16 {"
      "%0,%1,%2,%3,%4,%5,%6,%7,%8,%9,%10,%11,%12,%13,%14,%15,"
      "%16,%17,%18,%19,%20,%21,%22,%23,%24,%25,%26,%27,%28,%29,%30,%31"
      "}, {%32,%33,%34,%35}, %36, p, 1, 1, 0; }"
    : "+f"(d[0]), "+f"(d[1]), "+f"(d[2]), "+f"(d[3]), "+f"(d[4]), "+f"(d[5]), "+f"(d[6]), "+f"(d[7]),
      "+f"(d[8]), "+f"(d[9]), "+f"(d[10]), "+f"(d[11]), "+f"(d[12]), "+f"(d[13]), "+f"(d[14]), "+f"(d[15]),
      "+f"(d[16]), "+f"(d[17]), "+f"(d[18]), "+f"(d[19]), "+f"(d[20]), "+f"(d[21]), "+f"(d[22]), "+f"(d[23]),
      "+f"(d[24]), "+f"(d[25]), "+f"(d[26]), "+f"(d[27]), "+f"(d[28]), "+f"(d[29]), "+f"(d[30]), "+f"(d[31])
    : "r"(a[0]), "r"(a[1]), "r"(a[2]), "r"(a[3]), "l"(db), "r"(sd));
}

__device__ __forceinline__ void wgmma_rs_n80(float* d, const uint32_t* a, uint64_t db, int sd) {
  asm volatile("{ .reg .pred p; setp.ne.b32 p, %45, 0;\n"
      "wgmma.mma_async.sync.aligned.m64n80k16.f32.bf16.bf16 {"
      "%0,%1,%2,%3,%4,%5,%6,%7,%8,%9,%10,%11,%12,%13,%14,%15,"
      "%16,%17,%18,%19,%20,%21,%22,%23,%24,%25,%26,%27,%28,%29,%30,%31,"
      "%32,%33,%34,%35,%36,%37,%38,%39"
      "}, {%40,%41,%42,%43}, %44, p, 1, 1, 0; }"
    : "+f"(d[0]), "+f"(d[1]), "+f"(d[2]), "+f"(d[3]), "+f"(d[4]), "+f"(d[5]), "+f"(d[6]), "+f"(d[7]),
      "+f"(d[8]), "+f"(d[9]), "+f"(d[10]), "+f"(d[11]), "+f"(d[12]), "+f"(d[13]), "+f"(d[14]), "+f"(d[15]),
      "+f"(d[16]), "+f"(d[17]), "+f"(d[18]), "+f"(d[19]), "+f"(d[20]), "+f"(d[21]), "+f"(d[22]), "+f"(d[23]),
      "+f"(d[24]), "+f"(d[25]), "+f"(d[26]), "+f"(d[27]), "+f"(d[28]), "+f"(d[29]), "+f"(d[30]), "+f"(d[31]),
      "+f"(d[32]), "+f"(d[33]), "+f"(d[34]), "+f"(d[35]), "+f"(d[36]), "+f"(d[37]), "+f"(d[38]), "+f"(d[39])
    : "r"(a[0]), "r"(a[1]), "r"(a[2]), "r"(a[3]), "l"(db), "r"(sd));
}

__device__ __forceinline__ void wgmma_rs_n96(float* d, const uint32_t* a, uint64_t db, int sd) {
  asm volatile("{ .reg .pred p; setp.ne.b32 p, %53, 0;\n"
      "wgmma.mma_async.sync.aligned.m64n96k16.f32.bf16.bf16 {"
      "%0,%1,%2,%3,%4,%5,%6,%7,%8,%9,%10,%11,%12,%13,%14,%15,"
      "%16,%17,%18,%19,%20,%21,%22,%23,%24,%25,%26,%27,%28,%29,%30,%31,"
      "%32,%33,%34,%35,%36,%37,%38,%39,%40,%41,%42,%43,%44,%45,%46,%47"
      "}, {%48,%49,%50,%51}, %52, p, 1, 1, 0; }"
    : "+f"(d[0]), "+f"(d[1]), "+f"(d[2]), "+f"(d[3]), "+f"(d[4]), "+f"(d[5]), "+f"(d[6]), "+f"(d[7]),
      "+f"(d[8]), "+f"(d[9]), "+f"(d[10]), "+f"(d[11]), "+f"(d[12]), "+f"(d[13]), "+f"(d[14]), "+f"(d[15]),
      "+f"(d[16]), "+f"(d[17]), "+f"(d[18]), "+f"(d[19]), "+f"(d[20]), "+f"(d[21]), "+f"(d[22]), "+f"(d[23]),
      "+f"(d[24]), "+f"(d[25]), "+f"(d[26]), "+f"(d[27]), "+f"(d[28]), "+f"(d[29]), "+f"(d[30]), "+f"(d[31]),
      "+f"(d[32]), "+f"(d[33]), "+f"(d[34]), "+f"(d[35]), "+f"(d[36]), "+f"(d[37]), "+f"(d[38]), "+f"(d[39]),
      "+f"(d[40]), "+f"(d[41]), "+f"(d[42]), "+f"(d[43]), "+f"(d[44]), "+f"(d[45]), "+f"(d[46]), "+f"(d[47])
    : "r"(a[0]), "r"(a[1]), "r"(a[2]), "r"(a[3]), "l"(db), "r"(sd));
}

__device__ __forceinline__ void wgmma_rs_n112(float* d, const uint32_t* a, uint64_t db, int sd) {
  asm volatile("{ .reg .pred p; setp.ne.b32 p, %61, 0;\n"
      "wgmma.mma_async.sync.aligned.m64n112k16.f32.bf16.bf16 {"
      "%0,%1,%2,%3,%4,%5,%6,%7,%8,%9,%10,%11,%12,%13,%14,%15,"
      "%16,%17,%18,%19,%20,%21,%22,%23,%24,%25,%26,%27,%28,%29,%30,%31,"
      "%32,%33,%34,%35,%36,%37,%38,%39,%40,%41,%42,%43,%44,%45,%46,%47,"
      "%48,%49,%50,%51,%52,%53,%54,%55"
      "}, {%56,%57,%58,%59}, %60, p, 1, 1, 0; }"
    : "+f"(d[0]), "+f"(d[1]), "+f"(d[2]), "+f"(d[3]), "+f"(d[4]), "+f"(d[5]), "+f"(d[6]), "+f"(d[7]),
      "+f"(d[8]), "+f"(d[9]), "+f"(d[10]), "+f"(d[11]), "+f"(d[12]), "+f"(d[13]), "+f"(d[14]), "+f"(d[15]),
      "+f"(d[16]), "+f"(d[17]), "+f"(d[18]), "+f"(d[19]), "+f"(d[20]), "+f"(d[21]), "+f"(d[22]), "+f"(d[23]),
      "+f"(d[24]), "+f"(d[25]), "+f"(d[26]), "+f"(d[27]), "+f"(d[28]), "+f"(d[29]), "+f"(d[30]), "+f"(d[31]),
      "+f"(d[32]), "+f"(d[33]), "+f"(d[34]), "+f"(d[35]), "+f"(d[36]), "+f"(d[37]), "+f"(d[38]), "+f"(d[39]),
      "+f"(d[40]), "+f"(d[41]), "+f"(d[42]), "+f"(d[43]), "+f"(d[44]), "+f"(d[45]), "+f"(d[46]), "+f"(d[47]),
      "+f"(d[48]), "+f"(d[49]), "+f"(d[50]), "+f"(d[51]), "+f"(d[52]), "+f"(d[53]), "+f"(d[54]), "+f"(d[55])
    : "r"(a[0]), "r"(a[1]), "r"(a[2]), "r"(a[3]), "l"(db), "r"(sd));
}

__device__ __forceinline__ void wgmma_rs_n128(float* d, const uint32_t* a, uint64_t db, int sd) {
  asm volatile("{ .reg .pred p; setp.ne.b32 p, %69, 0;\n"
      "wgmma.mma_async.sync.aligned.m64n128k16.f32.bf16.bf16 {"
      "%0,%1,%2,%3,%4,%5,%6,%7,%8,%9,%10,%11,%12,%13,%14,%15,"
      "%16,%17,%18,%19,%20,%21,%22,%23,%24,%25,%26,%27,%28,%29,%30,%31,"
      "%32,%33,%34,%35,%36,%37,%38,%39,%40,%41,%42,%43,%44,%45,%46,%47,"
      "%48,%49,%50,%51,%52,%53,%54,%55,%56,%57,%58,%59,%60,%61,%62,%63"
      "}, {%64,%65,%66,%67}, %68, p, 1, 1, 0; }"
    : "+f"(d[0]), "+f"(d[1]), "+f"(d[2]), "+f"(d[3]), "+f"(d[4]), "+f"(d[5]), "+f"(d[6]), "+f"(d[7]),
      "+f"(d[8]), "+f"(d[9]), "+f"(d[10]), "+f"(d[11]), "+f"(d[12]), "+f"(d[13]), "+f"(d[14]), "+f"(d[15]),
      "+f"(d[16]), "+f"(d[17]), "+f"(d[18]), "+f"(d[19]), "+f"(d[20]), "+f"(d[21]), "+f"(d[22]), "+f"(d[23]),
      "+f"(d[24]), "+f"(d[25]), "+f"(d[26]), "+f"(d[27]), "+f"(d[28]), "+f"(d[29]), "+f"(d[30]), "+f"(d[31]),
      "+f"(d[32]), "+f"(d[33]), "+f"(d[34]), "+f"(d[35]), "+f"(d[36]), "+f"(d[37]), "+f"(d[38]), "+f"(d[39]),
      "+f"(d[40]), "+f"(d[41]), "+f"(d[42]), "+f"(d[43]), "+f"(d[44]), "+f"(d[45]), "+f"(d[46]), "+f"(d[47]),
      "+f"(d[48]), "+f"(d[49]), "+f"(d[50]), "+f"(d[51]), "+f"(d[52]), "+f"(d[53]), "+f"(d[54]), "+f"(d[55]),
      "+f"(d[56]), "+f"(d[57]), "+f"(d[58]), "+f"(d[59]), "+f"(d[60]), "+f"(d[61]), "+f"(d[62]), "+f"(d[63])
    : "r"(a[0]), "r"(a[1]), "r"(a[2]), "r"(a[3]), "l"(db), "r"(sd));
}

__device__ __forceinline__ void wgmma_rs_n144(float* d, const uint32_t* a, uint64_t db, int sd) {
  asm volatile("{ .reg .pred p; setp.ne.b32 p, %77, 0;\n"
      "wgmma.mma_async.sync.aligned.m64n144k16.f32.bf16.bf16 {"
      "%0,%1,%2,%3,%4,%5,%6,%7,%8,%9,%10,%11,%12,%13,%14,%15,"
      "%16,%17,%18,%19,%20,%21,%22,%23,%24,%25,%26,%27,%28,%29,%30,%31,"
      "%32,%33,%34,%35,%36,%37,%38,%39,%40,%41,%42,%43,%44,%45,%46,%47,"
      "%48,%49,%50,%51,%52,%53,%54,%55,%56,%57,%58,%59,%60,%61,%62,%63,"
      "%64,%65,%66,%67,%68,%69,%70,%71"
      "}, {%72,%73,%74,%75}, %76, p, 1, 1, 0; }"
    : "+f"(d[0]), "+f"(d[1]), "+f"(d[2]), "+f"(d[3]), "+f"(d[4]), "+f"(d[5]), "+f"(d[6]), "+f"(d[7]),
      "+f"(d[8]), "+f"(d[9]), "+f"(d[10]), "+f"(d[11]), "+f"(d[12]), "+f"(d[13]), "+f"(d[14]), "+f"(d[15]),
      "+f"(d[16]), "+f"(d[17]), "+f"(d[18]), "+f"(d[19]), "+f"(d[20]), "+f"(d[21]), "+f"(d[22]), "+f"(d[23]),
      "+f"(d[24]), "+f"(d[25]), "+f"(d[26]), "+f"(d[27]), "+f"(d[28]), "+f"(d[29]), "+f"(d[30]), "+f"(d[31]),
      "+f"(d[32]), "+f"(d[33]), "+f"(d[34]), "+f"(d[35]), "+f"(d[36]), "+f"(d[37]), "+f"(d[38]), "+f"(d[39]),
      "+f"(d[40]), "+f"(d[41]), "+f"(d[42]), "+f"(d[43]), "+f"(d[44]), "+f"(d[45]), "+f"(d[46]), "+f"(d[47]),
      "+f"(d[48]), "+f"(d[49]), "+f"(d[50]), "+f"(d[51]), "+f"(d[52]), "+f"(d[53]), "+f"(d[54]), "+f"(d[55]),
      "+f"(d[56]), "+f"(d[57]), "+f"(d[58]), "+f"(d[59]), "+f"(d[60]), "+f"(d[61]), "+f"(d[62]), "+f"(d[63]),
      "+f"(d[64]), "+f"(d[65]), "+f"(d[66]), "+f"(d[67]), "+f"(d[68]), "+f"(d[69]), "+f"(d[70]), "+f"(d[71])
    : "r"(a[0]), "r"(a[1]), "r"(a[2]), "r"(a[3]), "l"(db), "r"(sd));
}

__device__ __forceinline__ void wgmma_rs_n160(float* d, const uint32_t* a, uint64_t db, int sd) {
  asm volatile("{ .reg .pred p; setp.ne.b32 p, %85, 0;\n"
      "wgmma.mma_async.sync.aligned.m64n160k16.f32.bf16.bf16 {"
      "%0,%1,%2,%3,%4,%5,%6,%7,%8,%9,%10,%11,%12,%13,%14,%15,"
      "%16,%17,%18,%19,%20,%21,%22,%23,%24,%25,%26,%27,%28,%29,%30,%31,"
      "%32,%33,%34,%35,%36,%37,%38,%39,%40,%41,%42,%43,%44,%45,%46,%47,"
      "%48,%49,%50,%51,%52,%53,%54,%55,%56,%57,%58,%59,%60,%61,%62,%63,"
      "%64,%65,%66,%67,%68,%69,%70,%71,%72,%73,%74,%75,%76,%77,%78,%79"
      "}, {%80,%81,%82,%83}, %84, p, 1, 1, 0; }"
    : "+f"(d[0]), "+f"(d[1]), "+f"(d[2]), "+f"(d[3]), "+f"(d[4]), "+f"(d[5]), "+f"(d[6]), "+f"(d[7]),
      "+f"(d[8]), "+f"(d[9]), "+f"(d[10]), "+f"(d[11]), "+f"(d[12]), "+f"(d[13]), "+f"(d[14]), "+f"(d[15]),
      "+f"(d[16]), "+f"(d[17]), "+f"(d[18]), "+f"(d[19]), "+f"(d[20]), "+f"(d[21]), "+f"(d[22]), "+f"(d[23]),
      "+f"(d[24]), "+f"(d[25]), "+f"(d[26]), "+f"(d[27]), "+f"(d[28]), "+f"(d[29]), "+f"(d[30]), "+f"(d[31]),
      "+f"(d[32]), "+f"(d[33]), "+f"(d[34]), "+f"(d[35]), "+f"(d[36]), "+f"(d[37]), "+f"(d[38]), "+f"(d[39]),
      "+f"(d[40]), "+f"(d[41]), "+f"(d[42]), "+f"(d[43]), "+f"(d[44]), "+f"(d[45]), "+f"(d[46]), "+f"(d[47]),
      "+f"(d[48]), "+f"(d[49]), "+f"(d[50]), "+f"(d[51]), "+f"(d[52]), "+f"(d[53]), "+f"(d[54]), "+f"(d[55]),
      "+f"(d[56]), "+f"(d[57]), "+f"(d[58]), "+f"(d[59]), "+f"(d[60]), "+f"(d[61]), "+f"(d[62]), "+f"(d[63]),
      "+f"(d[64]), "+f"(d[65]), "+f"(d[66]), "+f"(d[67]), "+f"(d[68]), "+f"(d[69]), "+f"(d[70]), "+f"(d[71]),
      "+f"(d[72]), "+f"(d[73]), "+f"(d[74]), "+f"(d[75]), "+f"(d[76]), "+f"(d[77]), "+f"(d[78]), "+f"(d[79])
    : "r"(a[0]), "r"(a[1]), "r"(a[2]), "r"(a[3]), "l"(db), "r"(sd));
}

__device__ __forceinline__ void wgmma_rs_n176(float* d, const uint32_t* a, uint64_t db, int sd) {
  asm volatile("{ .reg .pred p; setp.ne.b32 p, %93, 0;\n"
      "wgmma.mma_async.sync.aligned.m64n176k16.f32.bf16.bf16 {"
      "%0,%1,%2,%3,%4,%5,%6,%7,%8,%9,%10,%11,%12,%13,%14,%15,"
      "%16,%17,%18,%19,%20,%21,%22,%23,%24,%25,%26,%27,%28,%29,%30,%31,"
      "%32,%33,%34,%35,%36,%37,%38,%39,%40,%41,%42,%43,%44,%45,%46,%47,"
      "%48,%49,%50,%51,%52,%53,%54,%55,%56,%57,%58,%59,%60,%61,%62,%63,"
      "%64,%65,%66,%67,%68,%69,%70,%71,%72,%73,%74,%75,%76,%77,%78,%79,"
      "%80,%81,%82,%83,%84,%85,%86,%87"
      "}, {%88,%89,%90,%91}, %92, p, 1, 1, 0; }"
    : "+f"(d[0]), "+f"(d[1]), "+f"(d[2]), "+f"(d[3]), "+f"(d[4]), "+f"(d[5]), "+f"(d[6]), "+f"(d[7]),
      "+f"(d[8]), "+f"(d[9]), "+f"(d[10]), "+f"(d[11]), "+f"(d[12]), "+f"(d[13]), "+f"(d[14]), "+f"(d[15]),
      "+f"(d[16]), "+f"(d[17]), "+f"(d[18]), "+f"(d[19]), "+f"(d[20]), "+f"(d[21]), "+f"(d[22]), "+f"(d[23]),
      "+f"(d[24]), "+f"(d[25]), "+f"(d[26]), "+f"(d[27]), "+f"(d[28]), "+f"(d[29]), "+f"(d[30]), "+f"(d[31]),
      "+f"(d[32]), "+f"(d[33]), "+f"(d[34]), "+f"(d[35]), "+f"(d[36]), "+f"(d[37]), "+f"(d[38]), "+f"(d[39]),
      "+f"(d[40]), "+f"(d[41]), "+f"(d[42]), "+f"(d[43]), "+f"(d[44]), "+f"(d[45]), "+f"(d[46]), "+f"(d[47]),
      "+f"(d[48]), "+f"(d[49]), "+f"(d[50]), "+f"(d[51]), "+f"(d[52]), "+f"(d[53]), "+f"(d[54]), "+f"(d[55]),
      "+f"(d[56]), "+f"(d[57]), "+f"(d[58]), "+f"(d[59]), "+f"(d[60]), "+f"(d[61]), "+f"(d[62]), "+f"(d[63]),
      "+f"(d[64]), "+f"(d[65]), "+f"(d[66]), "+f"(d[67]), "+f"(d[68]), "+f"(d[69]), "+f"(d[70]), "+f"(d[71]),
      "+f"(d[72]), "+f"(d[73]), "+f"(d[74]), "+f"(d[75]), "+f"(d[76]), "+f"(d[77]), "+f"(d[78]), "+f"(d[79]),
      "+f"(d[80]), "+f"(d[81]), "+f"(d[82]), "+f"(d[83]), "+f"(d[84]), "+f"(d[85]), "+f"(d[86]), "+f"(d[87])
    : "r"(a[0]), "r"(a[1]), "r"(a[2]), "r"(a[3]), "l"(db), "r"(sd));
}

__device__ __forceinline__ void wgmma_rs_n192(float* d, const uint32_t* a, uint64_t db, int sd) {
  asm volatile("{ .reg .pred p; setp.ne.b32 p, %101, 0;\n"
      "wgmma.mma_async.sync.aligned.m64n192k16.f32.bf16.bf16 {"
      "%0,%1,%2,%3,%4,%5,%6,%7,%8,%9,%10,%11,%12,%13,%14,%15,"
      "%16,%17,%18,%19,%20,%21,%22,%23,%24,%25,%26,%27,%28,%29,%30,%31,"
      "%32,%33,%34,%35,%36,%37,%38,%39,%40,%41,%42,%43,%44,%45,%46,%47,"
      "%48,%49,%50,%51,%52,%53,%54,%55,%56,%57,%58,%59,%60,%61,%62,%63,"
      "%64,%65,%66,%67,%68,%69,%70,%71,%72,%73,%74,%75,%76,%77,%78,%79,"
      "%80,%81,%82,%83,%84,%85,%86,%87,%88,%89,%90,%91,%92,%93,%94,%95"
      "}, {%96,%97,%98,%99}, %100, p, 1, 1, 0; }"
    : "+f"(d[0]), "+f"(d[1]), "+f"(d[2]), "+f"(d[3]), "+f"(d[4]), "+f"(d[5]), "+f"(d[6]), "+f"(d[7]),
      "+f"(d[8]), "+f"(d[9]), "+f"(d[10]), "+f"(d[11]), "+f"(d[12]), "+f"(d[13]), "+f"(d[14]), "+f"(d[15]),
      "+f"(d[16]), "+f"(d[17]), "+f"(d[18]), "+f"(d[19]), "+f"(d[20]), "+f"(d[21]), "+f"(d[22]), "+f"(d[23]),
      "+f"(d[24]), "+f"(d[25]), "+f"(d[26]), "+f"(d[27]), "+f"(d[28]), "+f"(d[29]), "+f"(d[30]), "+f"(d[31]),
      "+f"(d[32]), "+f"(d[33]), "+f"(d[34]), "+f"(d[35]), "+f"(d[36]), "+f"(d[37]), "+f"(d[38]), "+f"(d[39]),
      "+f"(d[40]), "+f"(d[41]), "+f"(d[42]), "+f"(d[43]), "+f"(d[44]), "+f"(d[45]), "+f"(d[46]), "+f"(d[47]),
      "+f"(d[48]), "+f"(d[49]), "+f"(d[50]), "+f"(d[51]), "+f"(d[52]), "+f"(d[53]), "+f"(d[54]), "+f"(d[55]),
      "+f"(d[56]), "+f"(d[57]), "+f"(d[58]), "+f"(d[59]), "+f"(d[60]), "+f"(d[61]), "+f"(d[62]), "+f"(d[63]),
      "+f"(d[64]), "+f"(d[65]), "+f"(d[66]), "+f"(d[67]), "+f"(d[68]), "+f"(d[69]), "+f"(d[70]), "+f"(d[71]),
      "+f"(d[72]), "+f"(d[73]), "+f"(d[74]), "+f"(d[75]), "+f"(d[76]), "+f"(d[77]), "+f"(d[78]), "+f"(d[79]),
      "+f"(d[80]), "+f"(d[81]), "+f"(d[82]), "+f"(d[83]), "+f"(d[84]), "+f"(d[85]), "+f"(d[86]), "+f"(d[87]),
      "+f"(d[88]), "+f"(d[89]), "+f"(d[90]), "+f"(d[91]), "+f"(d[92]), "+f"(d[93]), "+f"(d[94]), "+f"(d[95])
    : "r"(a[0]), "r"(a[1]), "r"(a[2]), "r"(a[3]), "l"(db), "r"(sd));
}

__device__ __forceinline__ void wgmma_rs_n208(float* d, const uint32_t* a, uint64_t db, int sd) {
  asm volatile("{ .reg .pred p; setp.ne.b32 p, %109, 0;\n"
      "wgmma.mma_async.sync.aligned.m64n208k16.f32.bf16.bf16 {"
      "%0,%1,%2,%3,%4,%5,%6,%7,%8,%9,%10,%11,%12,%13,%14,%15,"
      "%16,%17,%18,%19,%20,%21,%22,%23,%24,%25,%26,%27,%28,%29,%30,%31,"
      "%32,%33,%34,%35,%36,%37,%38,%39,%40,%41,%42,%43,%44,%45,%46,%47,"
      "%48,%49,%50,%51,%52,%53,%54,%55,%56,%57,%58,%59,%60,%61,%62,%63,"
      "%64,%65,%66,%67,%68,%69,%70,%71,%72,%73,%74,%75,%76,%77,%78,%79,"
      "%80,%81,%82,%83,%84,%85,%86,%87,%88,%89,%90,%91,%92,%93,%94,%95,"
      "%96,%97,%98,%99,%100,%101,%102,%103"
      "}, {%104,%105,%106,%107}, %108, p, 1, 1, 0; }"
    : "+f"(d[0]), "+f"(d[1]), "+f"(d[2]), "+f"(d[3]), "+f"(d[4]), "+f"(d[5]), "+f"(d[6]), "+f"(d[7]),
      "+f"(d[8]), "+f"(d[9]), "+f"(d[10]), "+f"(d[11]), "+f"(d[12]), "+f"(d[13]), "+f"(d[14]), "+f"(d[15]),
      "+f"(d[16]), "+f"(d[17]), "+f"(d[18]), "+f"(d[19]), "+f"(d[20]), "+f"(d[21]), "+f"(d[22]), "+f"(d[23]),
      "+f"(d[24]), "+f"(d[25]), "+f"(d[26]), "+f"(d[27]), "+f"(d[28]), "+f"(d[29]), "+f"(d[30]), "+f"(d[31]),
      "+f"(d[32]), "+f"(d[33]), "+f"(d[34]), "+f"(d[35]), "+f"(d[36]), "+f"(d[37]), "+f"(d[38]), "+f"(d[39]),
      "+f"(d[40]), "+f"(d[41]), "+f"(d[42]), "+f"(d[43]), "+f"(d[44]), "+f"(d[45]), "+f"(d[46]), "+f"(d[47]),
      "+f"(d[48]), "+f"(d[49]), "+f"(d[50]), "+f"(d[51]), "+f"(d[52]), "+f"(d[53]), "+f"(d[54]), "+f"(d[55]),
      "+f"(d[56]), "+f"(d[57]), "+f"(d[58]), "+f"(d[59]), "+f"(d[60]), "+f"(d[61]), "+f"(d[62]), "+f"(d[63]),
      "+f"(d[64]), "+f"(d[65]), "+f"(d[66]), "+f"(d[67]), "+f"(d[68]), "+f"(d[69]), "+f"(d[70]), "+f"(d[71]),
      "+f"(d[72]), "+f"(d[73]), "+f"(d[74]), "+f"(d[75]), "+f"(d[76]), "+f"(d[77]), "+f"(d[78]), "+f"(d[79]),
      "+f"(d[80]), "+f"(d[81]), "+f"(d[82]), "+f"(d[83]), "+f"(d[84]), "+f"(d[85]), "+f"(d[86]), "+f"(d[87]),
      "+f"(d[88]), "+f"(d[89]), "+f"(d[90]), "+f"(d[91]), "+f"(d[92]), "+f"(d[93]), "+f"(d[94]), "+f"(d[95]),
      "+f"(d[96]), "+f"(d[97]), "+f"(d[98]), "+f"(d[99]), "+f"(d[100]), "+f"(d[101]), "+f"(d[102]), "+f"(d[103])
    : "r"(a[0]), "r"(a[1]), "r"(a[2]), "r"(a[3]), "l"(db), "r"(sd));
}

__device__ __forceinline__ void wgmma_rs_n224(float* d, const uint32_t* a, uint64_t db, int sd) {
  asm volatile("{ .reg .pred p; setp.ne.b32 p, %117, 0;\n"
      "wgmma.mma_async.sync.aligned.m64n224k16.f32.bf16.bf16 {"
      "%0,%1,%2,%3,%4,%5,%6,%7,%8,%9,%10,%11,%12,%13,%14,%15,"
      "%16,%17,%18,%19,%20,%21,%22,%23,%24,%25,%26,%27,%28,%29,%30,%31,"
      "%32,%33,%34,%35,%36,%37,%38,%39,%40,%41,%42,%43,%44,%45,%46,%47,"
      "%48,%49,%50,%51,%52,%53,%54,%55,%56,%57,%58,%59,%60,%61,%62,%63,"
      "%64,%65,%66,%67,%68,%69,%70,%71,%72,%73,%74,%75,%76,%77,%78,%79,"
      "%80,%81,%82,%83,%84,%85,%86,%87,%88,%89,%90,%91,%92,%93,%94,%95,"
      "%96,%97,%98,%99,%100,%101,%102,%103,%104,%105,%106,%107,%108,%109,%110,%111"
      "}, {%112,%113,%114,%115}, %116, p, 1, 1, 0; }"
    : "+f"(d[0]), "+f"(d[1]), "+f"(d[2]), "+f"(d[3]), "+f"(d[4]), "+f"(d[5]), "+f"(d[6]), "+f"(d[7]),
      "+f"(d[8]), "+f"(d[9]), "+f"(d[10]), "+f"(d[11]), "+f"(d[12]), "+f"(d[13]), "+f"(d[14]), "+f"(d[15]),
      "+f"(d[16]), "+f"(d[17]), "+f"(d[18]), "+f"(d[19]), "+f"(d[20]), "+f"(d[21]), "+f"(d[22]), "+f"(d[23]),
      "+f"(d[24]), "+f"(d[25]), "+f"(d[26]), "+f"(d[27]), "+f"(d[28]), "+f"(d[29]), "+f"(d[30]), "+f"(d[31]),
      "+f"(d[32]), "+f"(d[33]), "+f"(d[34]), "+f"(d[35]), "+f"(d[36]), "+f"(d[37]), "+f"(d[38]), "+f"(d[39]),
      "+f"(d[40]), "+f"(d[41]), "+f"(d[42]), "+f"(d[43]), "+f"(d[44]), "+f"(d[45]), "+f"(d[46]), "+f"(d[47]),
      "+f"(d[48]), "+f"(d[49]), "+f"(d[50]), "+f"(d[51]), "+f"(d[52]), "+f"(d[53]), "+f"(d[54]), "+f"(d[55]),
      "+f"(d[56]), "+f"(d[57]), "+f"(d[58]), "+f"(d[59]), "+f"(d[60]), "+f"(d[61]), "+f"(d[62]), "+f"(d[63]),
      "+f"(d[64]), "+f"(d[65]), "+f"(d[66]), "+f"(d[67]), "+f"(d[68]), "+f"(d[69]), "+f"(d[70]), "+f"(d[71]),
      "+f"(d[72]), "+f"(d[73]), "+f"(d[74]), "+f"(d[75]), "+f"(d[76]), "+f"(d[77]), "+f"(d[78]), "+f"(d[79]),
      "+f"(d[80]), "+f"(d[81]), "+f"(d[82]), "+f"(d[83]), "+f"(d[84]), "+f"(d[85]), "+f"(d[86]), "+f"(d[87]),
      "+f"(d[88]), "+f"(d[89]), "+f"(d[90]), "+f"(d[91]), "+f"(d[92]), "+f"(d[93]), "+f"(d[94]), "+f"(d[95]),
      "+f"(d[96]), "+f"(d[97]), "+f"(d[98]), "+f"(d[99]), "+f"(d[100]), "+f"(d[101]), "+f"(d[102]), "+f"(d[103]),
      "+f"(d[104]), "+f"(d[105]), "+f"(d[106]), "+f"(d[107]), "+f"(d[108]), "+f"(d[109]), "+f"(d[110]), "+f"(d[111])
    : "r"(a[0]), "r"(a[1]), "r"(a[2]), "r"(a[3]), "l"(db), "r"(sd));
}

__device__ __forceinline__ void wgmma_rs_n240(float* d, const uint32_t* a, uint64_t db, int sd) {
  asm volatile("{ .reg .pred p; setp.ne.b32 p, %125, 0;\n"
      "wgmma.mma_async.sync.aligned.m64n240k16.f32.bf16.bf16 {"
      "%0,%1,%2,%3,%4,%5,%6,%7,%8,%9,%10,%11,%12,%13,%14,%15,"
      "%16,%17,%18,%19,%20,%21,%22,%23,%24,%25,%26,%27,%28,%29,%30,%31,"
      "%32,%33,%34,%35,%36,%37,%38,%39,%40,%41,%42,%43,%44,%45,%46,%47,"
      "%48,%49,%50,%51,%52,%53,%54,%55,%56,%57,%58,%59,%60,%61,%62,%63,"
      "%64,%65,%66,%67,%68,%69,%70,%71,%72,%73,%74,%75,%76,%77,%78,%79,"
      "%80,%81,%82,%83,%84,%85,%86,%87,%88,%89,%90,%91,%92,%93,%94,%95,"
      "%96,%97,%98,%99,%100,%101,%102,%103,%104,%105,%106,%107,%108,%109,%110,%111,"
      "%112,%113,%114,%115,%116,%117,%118,%119"
      "}, {%120,%121,%122,%123}, %124, p, 1, 1, 0; }"
    : "+f"(d[0]), "+f"(d[1]), "+f"(d[2]), "+f"(d[3]), "+f"(d[4]), "+f"(d[5]), "+f"(d[6]), "+f"(d[7]),
      "+f"(d[8]), "+f"(d[9]), "+f"(d[10]), "+f"(d[11]), "+f"(d[12]), "+f"(d[13]), "+f"(d[14]), "+f"(d[15]),
      "+f"(d[16]), "+f"(d[17]), "+f"(d[18]), "+f"(d[19]), "+f"(d[20]), "+f"(d[21]), "+f"(d[22]), "+f"(d[23]),
      "+f"(d[24]), "+f"(d[25]), "+f"(d[26]), "+f"(d[27]), "+f"(d[28]), "+f"(d[29]), "+f"(d[30]), "+f"(d[31]),
      "+f"(d[32]), "+f"(d[33]), "+f"(d[34]), "+f"(d[35]), "+f"(d[36]), "+f"(d[37]), "+f"(d[38]), "+f"(d[39]),
      "+f"(d[40]), "+f"(d[41]), "+f"(d[42]), "+f"(d[43]), "+f"(d[44]), "+f"(d[45]), "+f"(d[46]), "+f"(d[47]),
      "+f"(d[48]), "+f"(d[49]), "+f"(d[50]), "+f"(d[51]), "+f"(d[52]), "+f"(d[53]), "+f"(d[54]), "+f"(d[55]),
      "+f"(d[56]), "+f"(d[57]), "+f"(d[58]), "+f"(d[59]), "+f"(d[60]), "+f"(d[61]), "+f"(d[62]), "+f"(d[63]),
      "+f"(d[64]), "+f"(d[65]), "+f"(d[66]), "+f"(d[67]), "+f"(d[68]), "+f"(d[69]), "+f"(d[70]), "+f"(d[71]),
      "+f"(d[72]), "+f"(d[73]), "+f"(d[74]), "+f"(d[75]), "+f"(d[76]), "+f"(d[77]), "+f"(d[78]), "+f"(d[79]),
      "+f"(d[80]), "+f"(d[81]), "+f"(d[82]), "+f"(d[83]), "+f"(d[84]), "+f"(d[85]), "+f"(d[86]), "+f"(d[87]),
      "+f"(d[88]), "+f"(d[89]), "+f"(d[90]), "+f"(d[91]), "+f"(d[92]), "+f"(d[93]), "+f"(d[94]), "+f"(d[95]),
      "+f"(d[96]), "+f"(d[97]), "+f"(d[98]), "+f"(d[99]), "+f"(d[100]), "+f"(d[101]), "+f"(d[102]), "+f"(d[103]),
      "+f"(d[104]), "+f"(d[105]), "+f"(d[106]), "+f"(d[107]), "+f"(d[108]), "+f"(d[109]), "+f"(d[110]), "+f"(d[111]),
      "+f"(d[112]), "+f"(d[113]), "+f"(d[114]), "+f"(d[115]), "+f"(d[116]), "+f"(d[117]), "+f"(d[118]), "+f"(d[119])
    : "r"(a[0]), "r"(a[1]), "r"(a[2]), "r"(a[3]), "l"(db), "r"(sd));
}

__device__ __forceinline__ void wgmma_rs_n256(float* d, const uint32_t* a, uint64_t db, int sd) {
  asm volatile("{ .reg .pred p; setp.ne.b32 p, %133, 0;\n"
      "wgmma.mma_async.sync.aligned.m64n256k16.f32.bf16.bf16 {"
      "%0,%1,%2,%3,%4,%5,%6,%7,%8,%9,%10,%11,%12,%13,%14,%15,"
      "%16,%17,%18,%19,%20,%21,%22,%23,%24,%25,%26,%27,%28,%29,%30,%31,"
      "%32,%33,%34,%35,%36,%37,%38,%39,%40,%41,%42,%43,%44,%45,%46,%47,"
      "%48,%49,%50,%51,%52,%53,%54,%55,%56,%57,%58,%59,%60,%61,%62,%63,"
      "%64,%65,%66,%67,%68,%69,%70,%71,%72,%73,%74,%75,%76,%77,%78,%79,"
      "%80,%81,%82,%83,%84,%85,%86,%87,%88,%89,%90,%91,%92,%93,%94,%95,"
      "%96,%97,%98,%99,%100,%101,%102,%103,%104,%105,%106,%107,%108,%109,%110,%111,"
      "%112,%113,%114,%115,%116,%117,%118,%119,%120,%121,%122,%123,%124,%125,%126,%127"
      "}, {%128,%129,%130,%131}, %132, p, 1, 1, 0; }"
    : "+f"(d[0]), "+f"(d[1]), "+f"(d[2]), "+f"(d[3]), "+f"(d[4]), "+f"(d[5]), "+f"(d[6]), "+f"(d[7]),
      "+f"(d[8]), "+f"(d[9]), "+f"(d[10]), "+f"(d[11]), "+f"(d[12]), "+f"(d[13]), "+f"(d[14]), "+f"(d[15]),
      "+f"(d[16]), "+f"(d[17]), "+f"(d[18]), "+f"(d[19]), "+f"(d[20]), "+f"(d[21]), "+f"(d[22]), "+f"(d[23]),
      "+f"(d[24]), "+f"(d[25]), "+f"(d[26]), "+f"(d[27]), "+f"(d[28]), "+f"(d[29]), "+f"(d[30]), "+f"(d[31]),
      "+f"(d[32]), "+f"(d[33]), "+f"(d[34]), "+f"(d[35]), "+f"(d[36]), "+f"(d[37]), "+f"(d[38]), "+f"(d[39]),
      "+f"(d[40]), "+f"(d[41]), "+f"(d[42]), "+f"(d[43]), "+f"(d[44]), "+f"(d[45]), "+f"(d[46]), "+f"(d[47]),
      "+f"(d[48]), "+f"(d[49]), "+f"(d[50]), "+f"(d[51]), "+f"(d[52]), "+f"(d[53]), "+f"(d[54]), "+f"(d[55]),
      "+f"(d[56]), "+f"(d[57]), "+f"(d[58]), "+f"(d[59]), "+f"(d[60]), "+f"(d[61]), "+f"(d[62]), "+f"(d[63]),
      "+f"(d[64]), "+f"(d[65]), "+f"(d[66]), "+f"(d[67]), "+f"(d[68]), "+f"(d[69]), "+f"(d[70]), "+f"(d[71]),
      "+f"(d[72]), "+f"(d[73]), "+f"(d[74]), "+f"(d[75]), "+f"(d[76]), "+f"(d[77]), "+f"(d[78]), "+f"(d[79]),
      "+f"(d[80]), "+f"(d[81]), "+f"(d[82]), "+f"(d[83]), "+f"(d[84]), "+f"(d[85]), "+f"(d[86]), "+f"(d[87]),
      "+f"(d[88]), "+f"(d[89]), "+f"(d[90]), "+f"(d[91]), "+f"(d[92]), "+f"(d[93]), "+f"(d[94]), "+f"(d[95]),
      "+f"(d[96]), "+f"(d[97]), "+f"(d[98]), "+f"(d[99]), "+f"(d[100]), "+f"(d[101]), "+f"(d[102]), "+f"(d[103]),
      "+f"(d[104]), "+f"(d[105]), "+f"(d[106]), "+f"(d[107]), "+f"(d[108]), "+f"(d[109]), "+f"(d[110]), "+f"(d[111]),
      "+f"(d[112]), "+f"(d[113]), "+f"(d[114]), "+f"(d[115]), "+f"(d[116]), "+f"(d[117]), "+f"(d[118]), "+f"(d[119]),
      "+f"(d[120]), "+f"(d[121]), "+f"(d[122]), "+f"(d[123]), "+f"(d[124]), "+f"(d[125]), "+f"(d[126]), "+f"(d[127])
    : "r"(a[0]), "r"(a[1]), "r"(a[2]), "r"(a[3]), "l"(db), "r"(sd));
}

__device__ __forceinline__ void ln_finish(float mean, float var, float& mb, float& rinv) {
  mb = round_bf16(mean);
  float sd;
  asm("sqrt.approx.ftz.f32 %0, %1;" : "=f"(sd) : "f"(round_bf16(round_bf16(var) + 1e-5f)));
  asm("rcp.approx.ftz.f32 %0, %1;" : "=f"(rinv) : "f"(round_bf16(sd)));
}
__device__ __forceinline__ uint32_t sum4(uint32_t a, uint32_t b, uint32_t c, uint32_t d) { return badd2(badd2(badd2(d, c), b), a); }
struct Ring {
  uint32_t s, ph;
  __device__ __forceinline__ void next() { if (++s == NSTAGE) { s = 0; ph ^= 1; } }
};

template <int J> __device__ __forceinline__ void conv_lda(uint32_t* a, uint32_t base) {
  a[2 * J] = lds32(base + (J >> 1) * 256 + (J & 1) * 16); a[2 * J + 1] = lds32(base + (J >> 1) * 256 + (J & 1) * 16 + 128);
}
template <int J = 0> __device__ __forceinline__ void conv_lda_all(uint32_t* a, uint32_t base) {
  conv_lda<J>(a, base);
  if constexpr (J < 31) conv_lda_all<J + 1>(a, base);
}
__device__ __forceinline__ void conv_mma(float* acc, const uint32_t* a, uint64_t db) {
  wgmma_rs_n256(acc, a, db, 0);
  wgmma_rs_n240(acc, a + 4, db + 16, 1);
  wgmma_rs_n224(acc, a + 8, db + 32, 1);
  wgmma_rs_n208(acc, a + 12, db + 48, 1);
  wgmma_rs_n192(acc, a + 16, db + 64, 1);
  wgmma_rs_n176(acc, a + 20, db + 80, 1);
  wgmma_rs_n160(acc, a + 24, db + 96, 1);
  wgmma_rs_n144(acc, a + 28, db + 112, 1);
  wgmma_rs_n128(acc, a + 32, db + 128, 1);
  wgmma_rs_n112(acc, a + 36, db + 144, 1);
  wgmma_rs_n96(acc, a + 40, db + 160, 1);
  wgmma_rs_n80(acc, a + 44, db + 176, 1);
  wgmma_rs_n64(acc, a + 48, db + 192, 1);
  wgmma_rs_n48(acc, a + 52, db + 208, 1);
  wgmma_rs_n32(acc, a + 56, db + 224, 1);
  wgmma_rs_n16(acc, a + 60, db + 240, 1);
}
__device__ __forceinline__ uint32_t conv_part(const float* acc, int j) {
  const int q = 31 - j;
  return q == 31 ? pack_bf16(acc[124], acc[125]) : pack_bf16(acc[4 * q] + acc[(4 * q + 6) & 127], acc[4 * q + 1] + acc[(4 * q + 7) & 127]);
}
template <bool MORE, int J = 0> __device__ __forceinline__ void conv_drain(const float* acc, uint32_t wr, uint32_t* a, uint32_t ka) {
  if (MORE) conv_lda<J>(a, ka);
  sts32(wr + J * 128, conv_part(acc, J));
  if constexpr (J < 31) conv_drain<MORE, J + 1>(acc, wr, a, ka);
}
__device__ __forceinline__ uint4 conv_sum(const uint4* p) {
  return make_uint4(sum4(p[0].x, p[1].x, p[2].x, p[3].x), sum4(p[0].y, p[1].y, p[2].y, p[3].y), sum4(p[0].z, p[1].z, p[2].z, p[3].z),
                    sum4(p[0].w, p[1].w, p[2].w, p[3].w));
}
__device__ __forceinline__ int g2k(int rank, int kb) { return (rank * G2_KB + (kb < 6 ? 6 * kb : kb - 5 + (kb - 6) / 5)) * 64; }

template <int NV> __device__ __forceinline__ void gelu_stage(float* acc, const float* hb, uint32_t sa, int passes, uint32_t bar) {
#pragma unroll
  for (int i = 0; i < NV; i++) acc[i] = fmaf(acc[i], 0.5f, hb[(i >> 1) & 1]);
#pragma unroll 1
  for (; passes > 0; passes--, sa += NV * 256) {
#pragma unroll
    for (int i = 0; i < NV; i += 8)
      stsm4t(sa + i * 256, pack_bf16(gelu_half(acc[i]), gelu_half(acc[i + 1])), pack_bf16(gelu_half(acc[i + 2]), gelu_half(acc[i + 3])),
             pack_bf16(gelu_half(acc[i + 4]), gelu_half(acc[i + 5])), pack_bf16(gelu_half(acc[i + 6]), gelu_half(acc[i + 7])));
    __syncwarp();
    if (bar) mbar_arrive(bar);
    bar = 0;
    float half = 0.5f;
    asm volatile("" : "+f"(half));
#pragma unroll
    for (int i = 0; i < NV; i++) acc[i] = fmaf(acc[NV + i], half, hb[2 + ((i >> 1) & 1)]);
  }
}

__global__ void __cluster_dims__(2, 1, 1) __launch_bounds__(384, 1) fused_kernel(const __grid_constant__ Hot H, const __grid_constant__ Params P) {
  extern __shared__ __align__(1024) uint8_t smem_raw[];
  const uint32_t t0 = clk();
  const uint32_t sb = smem_u32(smem_raw);
  const int tid = threadIdx.x, lane = tid & 31;
  const int bid = blockIdx.x, rank = bid & 1;
  const Role& R = P.role[bid];
  Scratch* const S = H.S;
  uint32_t xr[18];
  const int row = bid * 16 + (tid >> 4);
  if (tid < 256 && bid < 128) {
    const char* src = reinterpret_cast<const char*>(H.x) + row * (D_ * 2) + (lane & 15) * 8;
#pragma unroll
    for (int j = 0; j < 9; j++) asm volatile("ld.global.nc.v2.u32 {%0,%1}, [%2];" : "=r"(xr[2 * j]), "=r"(xr[2 * j + 1]) : "l"(src + 128 * j));
  }
  if (tid == 256) asm volatile("prefetch.tensormap [%0];" :: "l"(&P.m_w1 + (R.at == 15)) : "memory");
  const int warp = __shfl_sync(0xffffffffu, tid >> 5, 0);

  if (warp >= 8) {
    const bool one = elect_one(), left = R.at == 15;
    TUNED(NWE, 2, 1); TUNED(NW0, 3, 2);
    if (warp == 8 && one) {
#pragma unroll
      for (int b = B_FULL; b < B_KFULL; b += 8) mbar_init(sb + b, 1);
#pragma unroll 1
      for (int s = 0; s < NWE; s++) {
        mbar_expect_tx(sb + B_FULL + 8 * s, G1_BYTES);
        fence_async_smem();
        tma3d_ef(sb + s * SLOT, &P.m_w1 + left, 0, s * 64, R.fg, sb + B_FULL + 8 * s);
      }
#pragma unroll
      for (int b = B_KFULL; b <= B_DONE; b += 8) mbar_init(sb + b, b < B_EMPTY ? 1 : b < B_SFREE ? 2 : b < B_CEMPTY ? 3 : b < B_G1DONE ? 4 : 8);
      asm volatile("fence.mbarrier_init.release.cluster;" ::: "memory");
    }
    __syncwarp();
    asm volatile("barrier.cluster.arrive.relaxed.aligned;" ::: "memory");
    asm volatile("setmaxnreg.dec.sync.aligned.u32 56;");
    asm volatile("barrier.cluster.wait.aligned;" ::: "memory");
    if (warp == 8) {
      const uint32_t ep = ldg32(S->cnt + C_EPOCH * 32);
      if (one) {
#pragma unroll 1
        for (int i = 0; i < 6; i++) asm volatile("prefetch.tensormap [%0];" :: "l"(&P.m_w2 + i) : "memory");
      }
      __syncwarp();
      if (bid < 128) bar_sync(2, 288);
      if (one) {
        TLREC(31);
        signal(S, C_H, EPOCH / 132);
        TLREC(1);
        const uint32_t boff = left ? 24576 : 16384;
        int kr = bid < 128 ? -2 : KV_ROUNDS + 1, ks = 0;
        auto kv_step = [&]() {
          if (ks == 0) {
            bulk_wait_all();
            if (kr < KV_ROUNDS - 2) {
              const int q = (kr + 2) % 3;
              const uint32_t in = sb + kv_buf(q), fb = sb + B_UFULL + 8 * q;
              mbar_expect_tx(fb, 3840 + 3264 + 768);
              tma2d(in, &P.m_k, (kr + 2) * 96, bid * 16 - 4, fb);
              tma2d(in + 3840, &P.m_v, (kr + 2) * 96, bid * 16 - 1, fb);
              bulk_load(in + 7168, H.shift_k + (kr + 2) * 384, 768, fb);
            }
            if (kr == KV_ROUNDS) { mbar_arrive(sb + B_KVDONE); kr++; }
          } else if (kr >= 0) {
            if (!mbar_test(sb + B_KFULL + 8 * (kr % 3), kr >= 3)) return;
            fence_async_smem();
            tma3d_store(&P.m_ub, sb + kv_buf(kr % 3) + (ks - 1) * 3072, 16 * (127 - bid), kr * 48, 2 * ks - 2);
            bulk_commit();
          }
          if (++ks == 3) { kr++; ks = kr == KV_ROUNDS - 2 || kr == KV_ROUNDS - 1; }
        };
        if (bid >= 128) mbar_arrive(sb + B_KVDONE);
        Ring r{0, 1};
#pragma unroll 1
        for (int kb = NWE - NW0; kb < G1_KB || kr <= KV_ROUNDS; kb++) {
          if (kb < G1_KB) {
          const int kw = kb < 0 ? kb + NW0 : kb, s = kb < 0 ? kw : r.s;
          const uint32_t fb = sb + B_FULL + 8 * s;
          if (kb < 0 || kb >= NW0) {
            mbar_wait(sb + B_EMPTY + 8 * s, r.ph);
            mbar_expect_tx(fb, G1_BYTES);
            tma3d_ef(sb + s * SLOT, &P.m_w1 + left, 0, kw * 64, R.fg, fb);
            if (kb < 0) continue;
          }
          if (kb == 0) { await(S, C_H, ep); fence_async_global(); TLREC(2); }
          bulk_load(sb + s * SLOT + boff, S->h + (kb * 18 + R.at) * 2048, G1_BYTES - boff, fb);
          if (kb == 23) {
#pragma unroll 1
            for (int i = 0; i < 2; i++) {
              sts128(sb + cv_taps(i), 0, 0, 0, 0); sts128(sb + cv_taps(i) + 16, 0, 0, 0, 0);
              bulk_load(sb + cv_taps(i) + 32, H.ssm_k + (R.ch + i) * S_, 4096, sb + B_MISC);
            }
            mbar_expect_tx(sb + B_MISC, boff / 64 + 1152 + 8192);
            bulk_load(sb + SM_B1, H.b1 + R.fg * 64, boff / 64, sb + B_MISC);
            bulk_load(sb + SM_D, H.ssm_D, 1152, sb + B_MISC);
          }
          r.next();
          }
          if (kb >= KV0 && kr <= KV_ROUNDS) kv_step();
        }
        await(S, C_KV, ep);
        fence_async_global();
#pragma unroll 1
        for (int i = 0; i < R.ncv; i++) {
          if (i == 2) {
            if (R.sg >= 0) {
#pragma unroll 1
              for (int s = 2; s < NSTAGE; s++) {
                mbar_wait(sb + B_EMPTY + 8 * s, ((G1_KB / NSTAGE) - 1) & 1);
                mbar_expect_tx(sb + B_FULL + 8 * s, G2_BYTES);
                tma3d_ef(sb + s * SLOT, &P.m_w2, 0, (rank * G2_KB + 6 * (s - 2)) * 64, R.sg, sb + B_FULL + 8 * s);
              }
            }
            mbar_wait(sb + B_G1DONE, 0);
          }
          const uint32_t kt = sb + cv_taps(i), b8 = sb + 8 * (i & 3);
          mbar_wait(b8 + B_CEMPTY, ((i >> 2) & 1) ^ 1);
          if (i < 2) mbar_arrive(b8 + B_KFULL);
          else {
            sts128(kt, 0, 0, 0, 0); sts128(kt + 16, 0, 0, 0, 0);
            mbar_expect_tx(b8 + B_KFULL, 4096);
            bulk_load(kt + 32, H.ssm_k + (R.ch + i) * S_, 4096, b8 + B_KFULL);
          }
          mbar_expect_tx(b8 + B_UFULL, 8192);
          bulk_load(sb + cv_in(i), S->ub + (R.ch + i) * 4096, 8192, b8 + B_UFULL);
        }
        if (R.sg >= 0) {
          mbar_expect_tx(sb + B_XY, 2 * 18432 + 2048 + 256);
#pragma unroll
          for (int i = 0; i < 4; i++) mbar_expect_tx(sb + B_XFULL + 8 * i, i & 1 ? 9216 - XP * 2048 : XP * 2048);
          TUNED(SYNCA, 0, 5); TUNED(SYNCKB, 1, 7);
#pragma unroll 1
          for (int kb = 0; kb < G2_KB; kb++, r.next()) {
            const int k0 = g2k(rank, kb);
            const uint32_t fb = sb + B_FULL + 8 * r.s, slot = sb + r.s * SLOT;
            if (!(kb & ~4)) { await(S, C_U + (kb >> 2), ep); fence_async_global(); if (!kb) TLREC(6); }
            if (kb >= NSTAGE - 2) {
              if (kb == SYNCKB) await(S, C_SYNC, ep);
              mbar_wait(sb + B_EMPTY + 8 * r.s, r.ph);
              if (kb == SYNCA) asm volatile("red.relaxed.gpu.global.add.u32 [%0], %1;" :: "l"(S->cnt + C_SYNC * 32), "r"(EPOCH / 128) : "memory");
              mbar_expect_tx(fb, G2_BYTES);
              tma3d_ef(slot, &P.m_w2, 0, k0, R.sg, fb);
            }
            bulk_load(slot + 16384, S->u + k0 * D_ + R.ds * 512, 9216, fb);
            bulk_load(slot + 16384 + 9216, S->u + k0 * D_ + R.dk * 512, 9216, fb);
            const uint32_t nx = kb - 8;
            if (nx == 0) { mbar_wait(sb + B_KVDONE, 1); fence_async_smem(); }
            if (nx < 8) tma2d(sb + SM_CV + nx * 2304, &P.m_x, R.dk * 8, R.sg * 64 + nx * 16, sb + B_XY);
          }
          bulk_load(sb + SM_ST, S->stats + R.sg * 64, 2048, sb + B_XY);
          bulk_load(sb + SM_B2, P.b2 + R.sg * 64, 256, sb + B_XY);
          await(S, C_Y, ep);
          fence_async_global();
          TLREC(19);
          tma3d(sb + SM_DED, &P.m_y, 0, R.dk * 8, R.sg, sb + B_XY);
          if (bid == 0) asm volatile("red.relaxed.gpu.global.add.u32 [%0], %1;" :: "l"(S->cnt + C_EPOCH * 32), "r"(EPOCH) : "memory");
        }
      }
    } else {
      if (bid < 128) {
        const int ht = tid - 288, hf = ht >= 48, pr = ht - 48 * hf;
        const uint32_t st = (1 - hf) * 1536 + pr * 32, sw = (pr & 4) * 4;
#pragma unroll 1
        for (int r = 0; r < KV_ROUNDS; r++) {
          const int q = r % 3;
          const uint32_t in = sb + kv_buf(q);
          {
            mbar_wait_guarded(sb + B_UFULL + 8 * q, t0, r >= 3);
            uint32_t kk[12], vv[9];
#pragma unroll
            for (int j = 0; j < 12; j++) kk[j] = lds32(in + hf * 1536 + pr * 4 + j * 192);
#pragma unroll
            for (int j = 0; j < 9; j++) vv[j] = lds32(in + 3840 + hf * 1536 + pr * 4 + j * 192);
            const uint4 w = lds128(in + 7168 + pr * 16);
            const uint32_t w0 = __byte_perm(w.x, w.z, 0x5410), w1 = __byte_perm(w.x, w.z, 0x7632);
            const uint32_t w2 = __byte_perm(w.y, w.w, 0x5410), w3 = __byte_perm(w.y, w.w, 0x7632);
#pragma unroll
            for (int j = 0; j < 9; j++)
              vv[j] = bmul2(badd2(badd2(badd2(bmul2(kk[j], w3), bmul2(kk[j + 1], w2)), bmul2(kk[j + 2], w1)), bmul2(kk[j + 3], w0)), vv[j]);
            bar_sync(1, 96);
#pragma unroll
            for (int c = 0; c < 2; c++)
#pragma unroll
              for (int pi = 0; pi < 2; pi++) {
                const uint32_t sel = c ? 0x7632 : 0x5410;
                sts128(in + st + c * 3072 + (pi * 16 ^ sw), __byte_perm(vv[7 + pi], vv[6 + pi], sel), __byte_perm(vv[5 + pi], vv[4 + pi], sel),
                       __byte_perm(vv[3 + pi], vv[2 + pi], sel), __byte_perm(vv[1 + pi], vv[pi], sel));
              }
            bar_sync(1, 96);
            if (ht == 0) mbar_arrive(sb + B_KFULL + 8 * q);
          }
          __syncwarp();
        }
      }
      if (one) {
        if (warp < 11) {
          const int wg = warp - 9;
          const uint32_t bytes = left ? 12288 : 10240;
#pragma unroll 1
          for (int j = 0; j < 2; j++) {
            mbar_wait_guarded(sb + B_STG + 8 * wg + (j ? 0 : 16), t0);
            fence_async_smem();
            TLREC(13 + wg);
            if (!j || wg || !left)
              bulk_store(S->u + (R.fg + wg) * (64 * D_) + R.at * 2048 + j * (left ? 64 * D_ : 5120), sb + (wg ? SM_ST1 : SM_DED) + j * bytes, bytes);
          }
          bulk_commit();
          bulk_wait_all();
          mbar_arrive(sb + B_STORED + 8 * wg);
          if (wg) mbar_arrive(sb + B_EMPTY);
          asm volatile("mbarrier.arrive.shared::cta.b64 _, [%0], 3;" :: "r"(sb + B_SFREE + 8 * wg) : "memory");
          signal(S, C_U + wg, EPOCH / 132);
          TLREC(15 + wg);
        } else {
          mbar_wait_guarded(sb + B_KVDONE, t0);
          signal(S, C_KV, EPOCH / 132);
          TLREC(27);
        }
      }
      __syncwarp();
#pragma unroll 1
      for (int i = 0; i < R.ncv; i++) {
        const uint32_t red = sb + cv_red(i, R.ncv) + (tid - 288) * 16;
        uint4* yo = reinterpret_cast<uint4*>(S->y + (R.ch + i) * S_) + (tid - 288);
        mbar_wait_guarded(sb + B_STORED + 8 * (i & 1), t0);
        mbar_wait_guarded(sb + B_STG + 8 * (i & 1) + (i + 2 < R.ncv ? 0 : 16), t0, i + 2 >= R.ncv || !(i & 2));
        uint4 p[2][4];
#pragma unroll
        for (int x = 0; x < 8; x++) p[x >> 2][x & 3] = lds128(red + (x & 3) * CV_REDW + (x >> 2) * 1536);
        yo[0] = conv_sum(p[0]);
        if (warp < 11) {
#pragma unroll
          for (int x = 0; x < 4; x++) p[0][x] = lds128(red + x * CV_REDW + 3072);
          yo[192] = conv_sum(p[0]);
        }
        yo[96] = conv_sum(p[1]);
        __syncwarp();
        if (one) mbar_arrive(sb + (i + 4 == R.ncv ? B_PDONE : B_SFREE + 8 * (i & 1)));
        if (i + 3 == R.ncv) {
          bar_sync(1, 96);
          if (warp == 11 && one) { fence_async_smem(); mbar_arrive(sb + B_EMPTY + 8); }
          __syncwarp();
        }
      }
      bar_sync(1, 96);
      if (warp == 11 && one) {
        TLREC(7);
        mbar_arrive(sb + B_KVDONE);
        signal(S, C_Y, EPOCH / 132);
        if (R.sg >= 0) mbar_wait_guarded(sb + B_DONE, t0);
      }
    }
    TLEND();
  } else {
    asm volatile("barrier.cluster.arrive.relaxed.aligned;" ::: "memory");
    if (bid < 128) {
      float c[36], s[4];
#pragma unroll
      for (int i = 0; i < 18; i++) { c[2 * i] = bf_lo(xr[i]); c[2 * i + 1] = bf_hi(xr[i]); }
#pragma unroll
      for (int i = 0; i < 36; i++) s[i & 3] = i < 4 ? c[i] : s[i & 3] + c[i];
      const float ml = ((s[0] + s[1]) + (s[2] + s[3])) * (1.0f / 36.0f);
#pragma unroll
      for (int i = 0; i < 36; i++) { c[i] -= ml; s[i & 3] = i < 4 ? c[i] * c[i] : fmaf(c[i], c[i], s[i & 3]); }
      float m = ml, q = (s[0] + s[1]) + (s[2] + s[3]), n2 = 18.f;
#pragma unroll
      for (int o = 1; o < 16; o <<= 1) {
        const float mo = __shfl_xor_sync(0xffffffffu, m, o), qo = __shfl_xor_sync(0xffffffffu, q, o);
        const float dl = m - mo;
        q = fmaf(dl * dl, n2, q + qo);
        m = fmaf(dl, -0.5f, m);
        n2 *= 2.f;
      }
      const float var = q * (1.0f / 576.0f);
      float mb, rinv, mb2, rinv2;
      ln_finish(m, var, mb, rinv);
      ln_finish((m - mb) * rinv, var * rinv * rinv, mb2, rinv2);
      const float ca = rinv * rinv2, cb = fmaf(ml - mb, rinv, -mb2) * rinv2;
      uint2* dst = reinterpret_cast<uint2*>(S->h) + ((row >> 6) * 18 + ((lane >> 3) & 1)) * 512 + (row & 63) * 8 + ((lane & 7) ^ (row & 6));
#pragma unroll
      for (int j = 0; j < 9; j++)
        dst[1024 * j] = make_uint2(pack_bf16(fmaf(c[4 * j], ca, cb), fmaf(c[4 * j + 1], ca, cb)), pack_bf16(fmaf(c[4 * j + 2], ca, cb), fmaf(c[4 * j + 3], ca, cb)));
      const uint32_t rh = pack_bf16(rinv, rinv);
      if (!(lane & 15)) S->stats[row] = make_uint4(pack_bf16(mb, mb), rh, pack_bf16(rinv - bf_lo(rh), rinv - bf_lo(rh)), 0);
      __syncwarp();
      bar_arrive(2, 288);
    }
    asm volatile("setmaxnreg.inc.sync.aligned.u32 224;");
    asm volatile("barrier.cluster.wait.aligned;" ::: "memory");
    const int wg = warp >> 2, w = warp & 3, g = lane >> 2, t = lane & 3, wtid = tid & 127;
    const bool elect = wtid == 0;
    const uint64_t da0 = make_desc(sb + wg * 8192, 8192, 1024, 1);
    const uint32_t swz = ((lane >> 4) * 8 + (lane & 7)) * 128 + (((2 * w + ((lane >> 3) & 1)) ^ (lane & 7)) << 4);
    const uint32_t stg = sb + (wg ? SM_ST1 : SM_DED), ka0 = (8 * w + g + t + 1) * 4;
    uint32_t a[64];
    {
      auto mainloop = [&](auto&& mma) {
        Ring r{0, 0};
        uint32_t rel = 0;
#pragma unroll 1
        for (int kb = 0; kb < G1_KB; kb++, r.next()) {
          if (kb == G1_KB - G1_TAIL && wg) {
            wg_wait<0>();
            if (elect) mbar_arrive(rel);
            rel = 0;
            {
              mbar_wait(sb + B_MISC, 0);
              conv_lda_all(a, sb + SM_CV + 16384 + CV_K + ka0);
            }
            bar_sync(5, 256);
          }
          mbar_wait(sb + B_FULL + 8 * r.s, r.ph);
          if (kb == 0 && warp == 0) TLREC(3);
          wg_fence();
          mma(r.s * (SLOT >> 4), kb);
          wg_commit();
          if (kb == G1_KB - 1) break;
          wg_wait<1>();
          if (elect && rel) mbar_arrive(rel);
          rel = sb + B_EMPTY + 8 * r.s;
        }
        bar_arrive(5, 256);
        wg_wait<0>();
      };
      float hb[4];
      auto staged = [&](int second) {
        if (!w) TLREC(4 + wg);
        if (lane == 0) mbar_arrive(sb + B_G1DONE);
        mbar_wait(sb + B_MISC, 0);
#pragma unroll
        for (int i = 0; i < 4; i++) hb[i] = 0.5f * bf_lo(lds16(sb + SM_B1 + (warp * 16 + g + (i & 1) * 8 + (i >> 1) * second) * 2));
        mbar_wait(sb + B_KVDONE, 0);
        if (wg) mbar_wait(sb + B_G1DONE, 0);
      };
      if (R.at != 15) {
        const uint64_t db0 = make_desc(sb + 16384, 4096, 512, 2);
        float acc[80];
        mainloop([&](uint32_t o, int kb) {
#pragma unroll
          for (int k = 0; k < 4; k++) wgmma_ss_n160_t11(acc, da0 + o + k * 128, db0 + o + k * 64, k ? 1 : kb);
        });
        pin_regs<80>(acc);
        staged(0);
        gelu_stage<40>(acc, hb, stg + swz, 2, lane ? 0 : sb + B_STG + 8 * wg + 16);
      } else {
        const uint64_t db0 = make_desc(sb + 24576, 4096, 512, 2);
        float acc[96];
        auto block = [&](float* d, uint64_t da, uint64_t db, int kb) {
#pragma unroll
          for (int k = 0; k < 4; k++) wgmma_ss_n96_t11(d, da + k * 128, db + k * 64, k ? 1 : kb);
        };
        if (wg) mainloop([&](uint32_t o, int kb) { block(acc, da0 + o, db0 + o, kb); block(acc + 48, da0 + o + 512, db0 + o, kb); });
        else mainloop([&](uint32_t o, int kb) { block(acc, da0 + o, db0 + o, kb); });
        pin_regs<96>(acc);
        staged(64);
        gelu_stage<48>(acc, hb, stg + swz, 1 + wg, lane ? 0 : sb + B_STG + 8 * wg + 16);
      }
      __syncwarp();
      if (lane == 0) mbar_arrive(sb + B_STG + 8 * wg);
    }
    {
      if (!wg) conv_lda_all(a, sb + SM_CV + 16384 + wg * CV_K + ka0);
#pragma unroll 1
      for (int i = wg; i < R.ncv; i += 2) {
        const bool more = i + 2 < R.ncv;
        const uint32_t dd = lds16(sb + SM_D + (R.ch + i) * 2);
        a[0] = badd2(a[0], ka0 == 32 ? dd : 0); a[2] = badd2(a[2], ka0 == 16 ? dd : 0);
        float acc[128];
        mbar_wait(sb + B_UFULL + 8 * (i & 3), (i >> 2) & 1);
        bar_sync(5 + wg, 256);
        const bool last = i + 1 == R.ncv;
        if (last && elect) mbar_arrive(sb + B_EMPTY);
        if (!w && i < 4) TLREC(22 + i);
        wg_fence();
        conv_mma(acc, a, make_desc(sb + cv_in(i), 4096, 128, 0));
        wg_commit();
        if (!last) bar_arrive(5 + (wg ^ 1), 256);
        if (more) {
          mbar_wait(sb + B_SFREE + 8 * wg, (i >> 1) & 1);
          mbar_wait(sb + B_KFULL + 8 * ((i + 2) & 3), ((i + 2) >> 2) & 1);
        } else if (last) mbar_wait(sb + B_PDONE, 0);
        wg_wait<0>();
        pin_regs<128>(acc);
        if (lane == 0) mbar_arrive(sb + B_CEMPTY + 8 * (i & 3));
        if (last && elect) mbar_arrive(sb + B_EMPTY + 8);
        const uint32_t red = sb + cv_red(i, R.ncv), ka = sb + cv_taps(i + 2) + ka0;
        if (lane < 8 * w) sts32(red + w * CV_REDW + lane * 4, 0);
        const uint32_t wr = red + w * CV_REDW + (8 * (3 - t + w) + g) * 4;
        if (more) conv_drain<true>(acc, wr, a, ka); else conv_drain<false>(acc, wr, a, ka);
        __syncwarp();
        if (lane == 0) mbar_arrive(sb + B_STG + 8 * wg + (more ? 0 : 16));
      }
      if (!w) TLREC(20 + wg);
    }
    if (R.sg >= 0) {
      const int srow = R.sg * 64 + warp * 16;
      const uint64_t db0 = make_desc(sb + 16384, 16, 1024, 1);
      const uint32_t xo = sb + SM_CV + warp * 2304, xa = xo + (lane & 15) * 144;
      float acc[72];
      Ring r{G1_KB % NSTAGE, (G1_KB / NSTAGE) & 1};
      bar_sync(8, 256);
      uint32_t rel = 0;
#pragma unroll 1
      for (int kb = 0; kb < G2_KB; kb++, r.next()) {
        if (kb == G2_KB - G2_TAIL && wg) {
          wg_wait<0>();
          if (elect) mbar_arrive_remote(rel);
          rel = 0;
          bar_sync(7, 256);
        }
        mbar_wait(sb + B_FULL + 8 * r.s, r.ph);
        if (kb == 0 && !w) TLREC(17 + wg);
        if (kb == 8 && warp == 0) TLREC(26);
        if (kb == 20 && warp == 0) TLREC(8);
        if (kb == 27 && warp == 0) TLREC(30);
        const uint64_t da = da0 + r.s * (SLOT >> 4), db = db0 + r.s * (SLOT >> 4);
        wg_fence();
        wgmma_ss_n144_t10(acc, da, db, kb);
#pragma unroll
        for (int k = 1; k < 4; k++) wgmma_ss_n144_t10(acc, da + k * 128, db + k * 2, 1);
        wg_commit();
        if (kb == G2_KB - 1) break;
        wg_wait<1>();
        if (elect && rel) mbar_arrive_remote(rel);
        rel = kb == G2_KB - NSTAGE ? mapa(sb + B_XRDY, rank ^ 1) : sb + B_EMPTY + 8 * r.s;
      }
      if (!wg) bar_arrive(7, 256);
      const uint32_t xz = sb + XSLOT * SLOT + wg * 10240 + wtid * 16;
      const uint32_t rz = mapa(xz, rank ^ 1), rb = mapa(sb + B_XFULL + 16 * wg, rank ^ 1);
      mbar_wait(sb + B_XRDY, 0);
      wg_wait<0>();
      pin_regs<72>(acc);
      if (!w) TLREC(28 + wg);
#pragma unroll
      for (int i = 0; i < 32; i += 8)
        asm volatile("st.async.weak.shared::cluster.mbarrier::complete_tx::bytes.v4.b32 [%0], {%1,%2,%3,%4}, [%5];"
                     :: "r"(rz + i * 256), "r"(pack_bf16(acc[i], acc[i + 1])), "r"(pack_bf16(acc[i + 2], acc[i + 3])),
                        "r"(pack_bf16(acc[i + 4], acc[i + 5])), "r"(pack_bf16(acc[i + 6], acc[i + 7])), "r"(rb + (i < 8 * XP ? 0 : 8)) : "memory");
      asm volatile("st.async.weak.shared::cluster.mbarrier::complete_tx::bytes.v2.b32 [%0], {%1,%2}, [%3];"
                   :: "r"(rz + 8192), "r"(pack_bf16(acc[32], acc[33])), "r"(pack_bf16(acc[34], acc[35])), "r"(rb + 8) : "memory");
      uint32_t xx[18], ss[18];
      mbar_wait(sb + B_XY, 0);
      {
        const uint32_t ya = sb + SM_DED + wg * 9216 + swz;
        const uint4 st0 = lds128(sb + SM_ST + (warp * 16 + g) * 16), st1 = lds128(sb + SM_ST + (warp * 16 + g + 8) * 16);
        const float hb0 = 0.5f * bf_lo(lds16(sb + SM_B2 + (warp * 16 + g) * 2)), hb1 = 0.5f * bf_lo(lds16(sb + SM_B2 + (warp * 16 + g + 8) * 2));
#pragma unroll
        for (int q = 0; q < 8; q += 2) { ldsm4(xx + 2 * q, xa + (lane >> 4) * 16 + q * 16); ldsm4t(ss + 2 * q, ya + q * 1024); }
        ldsm2(xx + 16, xa + 128);
        ldsm2t(ss + 16, ya + 8 * 1024);
#pragma unroll
        for (int i = 0; i < 18; i++) {
          const uint4& st = (i & 1) ? st1 : st0;
          const uint32_t c = bsub2(xx[i], st.x);
          ss[i] = bmul2(bfma2(c, st.y, bmul2(c, st.z)), ss[i]);
        }
#pragma unroll
        for (int i = 36; i < 72; i++) acc[i] = fmaf(acc[i], 0.5f, (i & 2) ? hb1 : hb0);
      }
      char* const op = reinterpret_cast<char*>(P.out) + srow * (D_ * 2) + R.dk * 16 + lane * 16;
      uint32_t oo[5];
#pragma unroll
      for (int j = 0; j < 5; j++) oo[j] = ((lane + 32 * j) * 57 >> 9) * (D_ * 2 - 144) + j * 512;
      uint32_t pv[20];
#pragma unroll
      for (int pc = 0; pc < 2; pc++) {
        const int q0 = pc ? XP : 0, q1 = pc ? 5 : XP;
        mbar_wait_cluster(sb + B_XFULL + 16 * wg + 8 * pc, 0);
        if (!w && !pc) TLREC(9 + wg);
#pragma unroll
        for (int q = q0; q < q1; q++) { const uint4 v = lds128(xz + q * 2048); pv[4 * q] = v.x; pv[4 * q + 1] = v.y; pv[4 * q + 2] = v.z; pv[4 * q + 3] = v.w; }
#pragma unroll
        for (int i = 4 * q0; i < 4 * q1 && i < 18; i++)
          xx[i] = bfma2(ss[i], pack_bf16(silu_half(fmaf(bf_lo(pv[i]), 0.5f, acc[36 + 2 * i])), silu_half(fmaf(bf_hi(pv[i]), 0.5f, acc[37 + 2 * i]))), xx[i]);
      }
#pragma unroll
      for (int q = 0; q < 4; q++) stsm4(xa + (lane >> 4) * 16 + q * 32, xx[4 * q], xx[4 * q + 1], xx[4 * q + 2], xx[4 * q + 3]);
      stsm2(xa + 128, xx[16], xx[17]);
      __syncwarp();
      if (lane == 0) mbar_arrive(sb + B_DONE);
#pragma unroll
      for (int j = 0; j < 5; j++)
        if (j < 4 || lane < 16) *reinterpret_cast<uint4*>(op + oo[j]) = lds128(xo + (lane + 32 * j) * 16);
      if (!w) TLREC(11 + wg);
    }
    TLEND();
  }
}

typedef CUresult (*EncodeFn)(CUtensorMap*, CUtensorMapDataType, cuuint32_t, void*, const cuuint64_t*, const cuuint64_t*, const cuuint32_t*,
                             const cuuint32_t*, CUtensorMapInterleave, CUtensorMapSwizzle, CUtensorMapL2promotion, CUtensorMapFloatOOBfill);

void make_map(EncodeFn fn, CUtensorMap* m, const void* ptr, int rank, const cuuint64_t* dims, const cuuint64_t* strides, const cuuint32_t* box,
              CUtensorMapSwizzle sw) {
  const cuuint32_t es[3] = {1, 1, 1};
  fn(m, CU_TENSOR_MAP_DATA_TYPE_BFLOAT16, rank, const_cast<void*>(ptr), dims, strides, box, es, CU_TENSOR_MAP_INTERLEAVE_NONE, sw,
     CU_TENSOR_MAP_L2_PROMOTION_L2_256B, CU_TENSOR_MAP_FLOAT_OOB_FILL_NONE);
}

void make_roles(Role* R) {
  int nl = 0, ch = 0;
  for (int gi = 0; gi < 8; gi++)
    for (int b = 0; b < 132; b++) {
      const int c = b >> 1, rank = b & 1;
      int g, idx;
      if (c < 4) { g = 0; idx = 4 + c; }
      else if (c < 36) { g = (c - 4) & 7; idx = (c - 4) >> 3; }
      else if (c < 64) { g = 1 + (c - 36) % 7; idx = 4 + (c - 36) / 7; }
      else { g = c - 58; idx = 8; }
      if (g != gi) continue;
      Role& r = R[b];
      r.sg = (int8_t)(idx < 8 ? 2 * (2 * g + (idx >> 2)) : -1);
      r.dk = (int8_t)((idx & 3) * 18 + rank * 9);
      r.ds = (int8_t)((idx & 3) * 18 + (rank ^ 1) * 9);
      if (idx < (g < 2 ? 6 : 7)) {
        const int c1 = (g < 2 ? 6 * g : 7 * g - 2) + idx;
        r.fg = (int8_t)((2 * (c1 / 3) + rank) * 2); r.at = (int8_t)(c1 % 3 * 5); r.ncv = NCV_REG;
      } else {
        r.fg = (int8_t)(3 * nl++); r.at = 15; r.ncv = idx < 8 ? NCV_LEFT : NCV_LONG;
      }
      r.ch = (int16_t)ch;
      ch += r.ncv;
    }
}

}

extern "C" void kernel_launch(void* const* d_in, const int* in_sizes, int n_in, void* d_out, int out_size) {
  static Params P;
  static Hot H;
  static const void* cached[5] = {nullptr, nullptr, nullptr, nullptr, nullptr};
  const void* now[5] = {d_in[0], d_in[1], d_in[2], d_in[7], d_in[9]};
  bool same = true;
  for (int i = 0; i < 5; i++) { same = same && cached[i] == now[i]; cached[i] = now[i]; }
  if (!same) {
    void* fp = nullptr;
    cudaDriverEntryPointQueryResult qr;
    cudaGetDriverEntryPoint("cuTensorMapEncodeTiled", &fp, cudaEnableDefault, &qr);
    EncodeFn fn = (EncodeFn)fp;
    void* ps;
    cudaGetSymbolAddress(&ps, g_scratch);
    H.S = (Scratch*)ps;
    const void *py = (char*)ps + offsetof(Scratch, y), *pb = (char*)ps + offsetof(Scratch, ub);
    { cuuint64_t d[3] = {64, S_, F_ / 64}, s[2] = {F_ * 2, 128}; cuuint32_t b[3] = {64, 64, 2}; make_map(fn, &P.m_w1, d_in[7], 3, d, s, b, CU_TENSOR_MAP_SWIZZLE_128B);
      b[2] = 3; make_map(fn, &P.m_w1l, d_in[7], 3, d, s, b, CU_TENSOR_MAP_SWIZZLE_128B); }
    { cuuint64_t d[3] = {64, F_, S_ / 64}, s[2] = {S_ * 2, 128}; cuuint32_t b[3] = {64, 64, 2}; make_map(fn, &P.m_w2, d_in[9], 3, d, s, b, CU_TENSOR_MAP_SWIZZLE_128B); }
    { cuuint64_t d[2] = {D_, S_}, s[1] = {D_ * 2}; cuuint32_t b[2] = {72, 16}; make_map(fn, &P.m_x, d_in[0], 2, d, s, b, CU_TENSOR_MAP_SWIZZLE_NONE);
      b[0] = 96; b[1] = 20; make_map(fn, &P.m_k, d_in[1], 2, d, s, b, CU_TENSOR_MAP_SWIZZLE_NONE);
      b[1] = 17; make_map(fn, &P.m_v, d_in[2], 2, d, s, b, CU_TENSOR_MAP_SWIZZLE_NONE); }
    { cuuint64_t d[3] = {64, D_, S_ / 64}, s[2] = {S_ * 2, 128}; cuuint32_t b[3] = {64, 72, 2}; make_map(fn, &P.m_y, py, 3, d, s, b, CU_TENSOR_MAP_SWIZZLE_128B); }
    { cuuint64_t d[3] = {2048, D_ / 2, 4}, s[2] = {16384, 4096}; cuuint32_t b[3] = {16, 48, 2}; make_map(fn, &P.m_ub, pb, 3, d, s, b, CU_TENSOR_MAP_SWIZZLE_32B); }
    make_roles(P.role);
    cudaFuncSetAttribute(fused_kernel, cudaFuncAttributeMaxDynamicSharedMemorySize, SM_TOTAL);
  }
  H.x = (const __nv_bfloat16*)d_in[0];
  H.shift_k = (const __nv_bfloat16*)d_in[3]; H.ssm_k = (const __nv_bfloat16*)d_in[4]; H.ssm_D = (const __nv_bfloat16*)d_in[5];
  H.b1 = (const __nv_bfloat16*)d_in[8]; P.b2 = (const __nv_bfloat16*)d_in[10]; P.out = (__nv_bfloat16*)d_out;
  fused_kernel<<<132, 384, SM_TOTAL>>>(H, P);
}
```

```cpp
#include <cuda_runtime.h>
#include <cuda.h>
#include <cuda_bf16.h>
#include <stddef.h>
#include <stdint.h>

namespace {

constexpr int S_ = 2048, D_ = 576, F_ = 4608;
constexpr int NSTAGE = 5, SLOT = 36864;
constexpr int G1_KB = 32, G2_KB = 36;
constexpr int G1_BYTES = 36864, G2_BYTES = 16384 + 18432;
#define NCV_LEFT 4
constexpr int NCV_REG = 4, NCV_LONG = (D_ - 108 * NCV_REG - 20 * NCV_LEFT) / 4;
static_assert(108 * NCV_REG + 20 * NCV_LEFT + 4 * NCV_LONG == D_, "conv split");
constexpr int KV_ROUNDS = 6;
#define XP 2
#define TUNED(name, idx, val) constexpr int name = val
constexpr int G1_TAIL = 4, G2_TAIL = 3;

constexpr int CV_K = 4224, CV_REDW = 2112 * 2;
constexpr int SM_DED = NSTAGE * SLOT;
constexpr int SM_CV = SM_DED + 20480;
constexpr int SM_ST1 = 0;
constexpr int SM_ST = SM_CV + 18432, SM_B2 = SM_ST + 2048;
constexpr int SM_B1 = SM_CV + 2 * (8192 + CV_K), SM_D = SM_B1 + 384;
constexpr int SM_BAR = SM_D + 1152;
constexpr int SM_TOTAL = SM_BAR + 768;
static_assert(G1_KB % NSTAGE == 2, "slots 0 and 1 hold the last GEMM1 k-blocks and the last two of the first GEMM2 stages");
static_assert(NCV_REG == 4 && NCV_LEFT == 4 && NCV_LONG % 4 == 0, "the last two channels use buffers 2 and 3");
constexpr int XSLOT = (G1_KB + G2_KB) % NSTAGE;
__device__ __forceinline__ uint32_t kv_buf(int q) { return q == 2 ? SM_DED : SM_CV + q * 8192; }
__device__ __forceinline__ uint32_t cv_red(int i, int n) { return i + 2 == n ? SM_CV : (i & 1) && i + 1 < n ? SLOT + 16384 : SM_DED; }
__device__ __forceinline__ uint32_t cv_in(int i) { return (i & 2 ? SLOT : SM_CV) + (i & 1) * 8192; }
__device__ __forceinline__ uint32_t cv_taps(int i) { return (i & 2 ? SM_ST1 + 24576 : SM_CV + 16384) + (i & 1) * CV_K; }
constexpr int bar_at(int i) { return SM_BAR + 8 * i; }
constexpr int B_FULL = bar_at(0)  , B_KFULL = bar_at(5)  , B_UFULL = bar_at(9)  , B_KVDONE = bar_at(13), B_STORED = bar_at(14)  ,
              B_XFULL = bar_at(16)  , B_XY = bar_at(20), B_MISC = bar_at(21),
              B_EMPTY = bar_at(22)  , B_XRDY = bar_at(27),
              B_SFREE = bar_at(28)  , B_PDONE = bar_at(30),
              B_CEMPTY = bar_at(31)  , B_STG = bar_at(35)  ,
              B_G1DONE = bar_at(39), B_DONE = bar_at(40);
constexpr int C_H = 0, C_KV = 1, C_U = 2  , C_Y = 4, C_SYNC = 5, C_EPOCH = 6, C_COUNT = 7;
constexpr uint32_t EPOCH = 128 * 33;

struct Scratch {
  uint32_t cnt[C_COUNT * 32];
  alignas(1024) uint4 stats[S_];
  alignas(1024) __nv_bfloat16 h[S_ * D_];
  alignas(1024) __nv_bfloat16 ub[D_ * 4096];
  alignas(1024) __nv_bfloat16 y[D_ * S_];
  alignas(1024) __nv_bfloat16 u[D_ * F_];
};
__device__ Scratch g_scratch;

struct Hot {
  const __nv_bfloat16 *x, *shift_k, *ssm_k, *ssm_D, *b1;
  Scratch* S;
};
struct Role {
  int8_t fg;
  int8_t at;
  int8_t sg;
  int8_t dk, ds;
  int8_t ncv;
  int16_t ch;
};
struct Params {
  const __nv_bfloat16* b2;
  __nv_bfloat16* out;
  Role role[132];
  CUtensorMap m_w1, m_w1l, m_w2, m_x, m_y, m_k, m_v, m_ub;
};

#define TLREC(i) do { } while (0)
#define TLEND() do { } while (0)

__device__ __forceinline__ uint32_t smem_u32(const void* p) { return (uint32_t)__cvta_generic_to_shared(p); }
__device__ __forceinline__ void mbar_init(uint32_t bar, uint32_t cnt) { asm volatile("mbarrier.init.shared::cta.b64 [%0], %1;" :: "r"(bar), "r"(cnt) : "memory"); }
__device__ __forceinline__ void mbar_expect_tx(uint32_t bar, uint32_t bytes) { asm volatile("mbarrier.arrive.expect_tx.shared::cta.b64 _, [%0], %1;" :: "r"(bar), "r"(bytes) : "memory"); }
__device__ __forceinline__ void mbar_arrive(uint32_t bar) { asm volatile("mbarrier.arrive.shared::cta.b64 _, [%0];" :: "r"(bar) : "memory"); }
__device__ __forceinline__ uint32_t mapa(uint32_t addr, uint32_t cta) { uint32_t r; asm volatile("mapa.shared::cluster.u32 %0, %1, %2;" : "=r"(r) : "r"(addr), "r"(cta)); return r; }
__device__ __forceinline__ void mbar_arrive_remote(uint32_t rbar) { asm volatile("mbarrier.arrive.shared::cluster.b64 _, [%0];" :: "r"(rbar) : "memory"); }
__device__ __forceinline__ uint32_t clk() { uint32_t c; asm volatile("mov.u32 %0, %%clock;" : "=r"(c)); return c; }
__device__ __forceinline__ bool elect_one() {
  uint32_t p; asm volatile("{ .reg .pred p; elect.sync _|p, 0xffffffff; selp.u32 %0, 1, 0, p; }" : "=r"(p)); return p;
}
__device__ __forceinline__ void guard(uint32_t t0) { if ((int32_t)(clk() - t0) < 0) __trap(); }
__device__ __forceinline__ void mbar_wait(uint32_t bar, uint32_t parity) {
  asm volatile("{\n .reg .pred p;\n W_%=:\n mbarrier.try_wait.parity.shared::cta.b64 p, [%0], %1;\n @!p bra W_%=;\n }" :: "r"(bar), "r"(parity) : "memory");
}
__device__ __forceinline__ void mbar_wait_cluster(uint32_t bar, uint32_t parity) {
  asm volatile("{\n .reg .pred p;\n W_%=:\n mbarrier.try_wait.parity.acquire.cluster.shared::cta.b64 p, [%0], %1;\n @!p bra W_%=;\n }" :: "r"(bar), "r"(parity) : "memory");
}
__device__ __forceinline__ bool mbar_try(uint32_t bar, uint32_t parity) {
  uint32_t ok;
  asm volatile("{ .reg .pred p; mbarrier.try_wait.parity.shared::cta.b64 p, [%1], %2, 100000; selp.u32 %0, 1, 0, p; }" : "=r"(ok) : "r"(bar), "r"(parity) : "memory");
  return ok;
}
__device__ __forceinline__ bool mbar_test(uint32_t bar, uint32_t parity) {
  uint32_t ok;
  asm volatile("{ .reg .pred p; mbarrier.test_wait.parity.shared::cta.b64 p, [%1], %2; selp.u32 %0, 1, 0, p; }" : "=r"(ok) : "r"(bar), "r"(parity) : "memory");
  return ok;
}
__device__ __forceinline__ void mbar_wait_guarded(uint32_t bar, uint32_t t0, uint32_t parity = 0) { while (!mbar_try(bar, parity)) guard(t0); }
__device__ __forceinline__ void tma2d(uint32_t dst, const CUtensorMap* m, int c0, int c1, uint32_t bar) {
  asm volatile("cp.async.bulk.tensor.2d.shared::cluster.global.mbarrier::complete_tx::bytes [%0], [%1, {%3, %4}], [%2];"
               :: "r"(dst), "l"(m), "r"(bar), "r"(c0), "r"(c1) : "memory");
}
__device__ __forceinline__ void tma3d(uint32_t dst, const CUtensorMap* m, int c0, int c1, int c2, uint32_t bar) {
  asm volatile("cp.async.bulk.tensor.3d.shared::cluster.global.mbarrier::complete_tx::bytes [%0], [%1, {%3, %4, %5}], [%2];"
               :: "r"(dst), "l"(m), "r"(bar), "r"(c0), "r"(c1), "r"(c2) : "memory");
}
__device__ __forceinline__ uint64_t evict_first() { uint64_t p; asm("createpolicy.fractional.L2::evict_first.b64 %0, 1.0;" : "=l"(p)); return p; }
__device__ __forceinline__ void tma3d_ef(uint32_t dst, const CUtensorMap* m, int c0, int c1, int c2, uint32_t bar) {
  asm volatile("cp.async.bulk.tensor.3d.shared::cluster.global.mbarrier::complete_tx::bytes.L2::cache_hint [%0], [%1, {%3, %4, %5}], [%2], %6;"
               :: "r"(dst), "l"(m), "r"(bar), "r"(c0), "r"(c1), "r"(c2), "l"(evict_first()) : "memory");
}
__device__ __forceinline__ void bulk_load_ef(uint32_t dst, const void* src, uint32_t bytes, uint32_t bar) {
  asm volatile("cp.async.bulk.shared::cluster.global.mbarrier::complete_tx::bytes.L2::cache_hint [%0], [%1], %2, [%3], %4;"
               :: "r"(dst), "l"(src), "r"(bytes), "r"(bar), "l"(evict_first()) : "memory");
}
__device__ __forceinline__ void bulk_store(void* dst, uint32_t src, uint32_t bytes) {
  asm volatile("cp.async.bulk.global.shared::cta.bulk_group [%0], [%1], %2;" :: "l"(dst), "r"(src), "r"(bytes) : "memory");
}
__device__ __forceinline__ void bulk_load(uint32_t dst, const void* src, uint32_t bytes, uint32_t bar) {
  asm volatile("cp.async.bulk.shared::cluster.global.mbarrier::complete_tx::bytes [%0], [%1], %2, [%3];" :: "r"(dst), "l"(src), "r"(bytes), "r"(bar) : "memory");
}
__device__ __forceinline__ void tma3d_store(const CUtensorMap* m, uint32_t src, int c0, int c1, int c2) {
  asm volatile("cp.async.bulk.tensor.3d.global.shared::cta.bulk_group [%0, {%2, %3, %4}], [%1];" :: "l"(m), "r"(src), "r"(c0), "r"(c1), "r"(c2) : "memory");
}
__device__ __forceinline__ void bulk_commit() { asm volatile("cp.async.bulk.commit_group;" ::: "memory"); }
__device__ __forceinline__ void bulk_wait_all() { asm volatile("cp.async.bulk.wait_group 0;" ::: "memory"); }
__device__ __forceinline__ void fence_async_smem() { asm volatile("fence.proxy.async.shared::cta;" ::: "memory"); }
__device__ __forceinline__ void fence_async_global() { asm volatile("fence.proxy.async.global;" ::: "memory"); }
__device__ __forceinline__ uint32_t ld_cnt(Scratch* S, int c) { uint32_t v; asm volatile("ld.relaxed.gpu.global.u32 %0, [%1];" : "=r"(v) : "l"(S->cnt + c * 32) : "memory"); return v; }
__device__ __forceinline__ void signal(Scratch* S, int c, uint32_t inc) { asm volatile("red.release.gpu.global.add.u32 [%0], %1;" :: "l"(S->cnt + c * 32), "r"(inc) : "memory"); }
__device__ __forceinline__ bool reached(Scratch* S, int c, uint32_t ep) { return ld_cnt(S, c) - ep >= EPOCH; }
__device__ __forceinline__ void await(Scratch* S, int c, uint32_t ep) { while (!reached(S, c, ep)) { } }
__device__ __forceinline__ void bar_sync(int id, int n) { asm volatile("bar.sync %0, %1;" :: "r"(id), "r"(n) : "memory"); }
__device__ __forceinline__ void bar_arrive(int id, int n) { asm volatile("bar.arrive %0, %1;" :: "r"(id), "r"(n) : "memory"); }
__device__ __forceinline__ void wg_fence() { asm volatile("wgmma.fence.sync.aligned;" ::: "memory"); }
__device__ __forceinline__ void wg_commit() { asm volatile("wgmma.commit_group.sync.aligned;" ::: "memory"); }
template <int N> __device__ __forceinline__ void wg_wait() { asm volatile("wgmma.wait_group.sync.aligned %0;" :: "n"(N) : "memory"); }
template <int N> __device__ __forceinline__ void pin_regs(float* a) {
#pragma unroll
  for (int i = 0; i < N; i++) asm volatile("" : "+f"(a[i]) :: "memory");
}
__device__ __forceinline__ uint64_t make_desc(uint32_t addr, uint32_t lbo, uint32_t sbo, uint32_t swz) {
  return (uint64_t)((addr & 0x3FFFF) >> 4) | ((uint64_t)(lbo >> 4) << 16) | ((uint64_t)(sbo >> 4) << 32) | ((uint64_t)swz << 62);
}
__device__ __forceinline__ uint32_t pack_bf16(float lo, float hi) { uint32_t r; asm("cvt.rn.bf16x2.f32 %0, %1, %2;" : "=r"(r) : "f"(hi), "f"(lo)); return r; }
__device__ __forceinline__ float bf_lo(uint32_t p) { return __uint_as_float(p << 16); }
__device__ __forceinline__ float bf_hi(uint32_t p) { return __uint_as_float(p & 0xffff0000u); }
__device__ __forceinline__ float round_bf16(float v) { return bf_lo(pack_bf16(v, 0.f)); }
__device__ __forceinline__ uint32_t bmul2(uint32_t a, uint32_t b) { uint32_t r; asm("mul.rn.bf16x2 %0, %1, %2;" : "=r"(r) : "r"(a), "r"(b)); return r; }
__device__ __forceinline__ uint32_t badd2(uint32_t a, uint32_t b) { uint32_t r; asm("add.rn.bf16x2 %0, %1, %2;" : "=r"(r) : "r"(a), "r"(b)); return r; }
__device__ __forceinline__ uint32_t bfma2(uint32_t a, uint32_t b, uint32_t c) { uint32_t r; asm("fma.rn.bf16x2 %0, %1, %2, %3;" : "=r"(r) : "r"(a), "r"(b), "r"(c)); return r; }
__device__ __forceinline__ uint32_t bsub2(uint32_t a, uint32_t b) { uint32_t r; asm("sub.rn.bf16x2 %0, %1, %2;" : "=r"(r) : "r"(a), "r"(b)); return r; }
__device__ __forceinline__ float tanh_fast(float v) { float r; asm("tanh.approx.f32 %0, %1;" : "=f"(r) : "f"(v)); return r; }
__device__ __forceinline__ float gelu_half(float h) {
  return fmaf(h, tanh_fast(h * fmaf(h * h, 8.0f * 0.7978845608028654f * 0.044715f, 2.0f * 0.7978845608028654f)), h);
}
__device__ __forceinline__ float silu_half(float h) { return fmaf(h, tanh_fast(h), h); }
__device__ __forceinline__ uint32_t ldg32(const void* p) { uint32_t v; asm volatile("ld.global.u32 %0, [%1];" : "=r"(v) : "l"(p) : "memory"); return v; }
__device__ __forceinline__ uint32_t lds32(uint32_t a) { uint32_t v; asm volatile("ld.shared.u32 %0, [%1];" : "=r"(v) : "r"(a) : "memory"); return v; }
__device__ __forceinline__ uint32_t lds16(uint32_t a) { uint32_t v; asm volatile("ld.shared.u16 %0, [%1];" : "=r"(v) : "r"(a) : "memory"); return v; }
__device__ __forceinline__ uint4 lds128(uint32_t a) { uint4 v; asm volatile("ld.shared.v4.u32 {%0,%1,%2,%3}, [%4];" : "=r"(v.x), "=r"(v.y), "=r"(v.z), "=r"(v.w) : "r"(a) : "memory"); return v; }
__device__ __forceinline__ void sts128(uint32_t a, uint32_t x, uint32_t y, uint32_t z, uint32_t w) {
  asm volatile("st.shared.v4.u32 [%0], {%1,%2,%3,%4};" :: "r"(a), "r"(x), "r"(y), "r"(z), "r"(w) : "memory");
}
__device__ __forceinline__ void sts32(uint32_t a, uint32_t v) { asm volatile("st.shared.u32 [%0], %1;" :: "r"(a), "r"(v) : "memory"); }
__device__ __forceinline__ void ldsm4(uint32_t* r, uint32_t a) {
  asm volatile("ldmatrix.sync.aligned.m8n8.x4.shared.b16 {%0,%1,%2,%3}, [%4];" : "=r"(r[0]), "=r"(r[1]), "=r"(r[2]), "=r"(r[3]) : "r"(a) : "memory");
}
__device__ __forceinline__ void ldsm2(uint32_t* r, uint32_t a) {
  asm volatile("ldmatrix.sync.aligned.m8n8.x2.shared.b16 {%0,%1}, [%2];" : "=r"(r[0]), "=r"(r[1]) : "r"(a) : "memory");
}
__device__ __forceinline__ void ldsm4t(uint32_t* r, uint32_t a) {
  asm volatile("ldmatrix.sync.aligned.m8n8.x4.trans.shared.b16 {%0,%1,%2,%3}, [%4];" : "=r"(r[0]), "=r"(r[1]), "=r"(r[2]), "=r"(r[3]) : "r"(a) : "memory");
}
__device__ __forceinline__ void ldsm2t(uint32_t* r, uint32_t a) {
  asm volatile("ldmatrix.sync.aligned.m8n8.x2.trans.shared.b16 {%0,%1}, [%2];" : "=r"(r[0]), "=r"(r[1]) : "r"(a) : "memory");
}
__device__ __forceinline__ void stsm4(uint32_t a, uint32_t r0, uint32_t r1, uint32_t r2, uint32_t r3) {
  asm volatile("stmatrix.sync.aligned.m8n8.x4.shared.b16 [%0], {%1,%2,%3,%4};" :: "r"(a), "r"(r0), "r"(r1), "r"(r2), "r"(r3) : "memory");
}
__device__ __forceinline__ void stsm2(uint32_t a, uint32_t r0, uint32_t r1) {
  asm volatile("stmatrix.sync.aligned.m8n8.x2.shared.b16 [%0], {%1,%2};" :: "r"(a), "r"(r0), "r"(r1) : "memory");
}
__device__ __forceinline__ void stsm4t(uint32_t a, uint32_t r0, uint32_t r1, uint32_t r2, uint32_t r3) {
  asm volatile("stmatrix.sync.aligned.m8n8.x4.trans.shared.b16 [%0], {%1,%2,%3,%4};" :: "r"(a), "r"(r0), "r"(r1), "r"(r2), "r"(r3) : "memory");
}

__device__ __forceinline__ void wgmma_ss_n144_t10(float* d, uint64_t da, uint64_t db, int sd) {
  asm volatile("{ .reg .pred p; setp.ne.b32 p, %74, 0;\n"
      "wgmma.mma_async.sync.aligned.m64n144k16.f32.bf16.bf16 {"
      "%0,%1,%2,%3,%4,%5,%6,%7,%8,%9,%10,%11,%12,%13,%14,%15,"
      "%16,%17,%18,%19,%20,%21,%22,%23,%24,%25,%26,%27,%28,%29,%30,%31,"
      "%32,%33,%34,%35,%36,%37,%38,%39,%40,%41,%42,%43,%44,%45,%46,%47,"
      "%48,%49,%50,%51,%52,%53,%54,%55,%56,%57,%58,%59,%60,%61,%62,%63,"
      "%64,%65,%66,%67,%68,%69,%70,%71"
      "}, %72, %73, p, 1, 1, 1, 0; }"
    : "+f"(d[0]), "+f"(d[1]), "+f"(d[2]), "+f"(d[3]), "+f"(d[4]), "+f"(d[5]), "+f"(d[6]), "+f"(d[7]),
      "+f"(d[8]), "+f"(d[9]), "+f"(d[10]), "+f"(d[11]), "+f"(d[12]), "+f"(d[13]), "+f"(d[14]), "+f"(d[15]),
      "+f"(d[16]), "+f"(d[17]), "+f"(d[18]), "+f"(d[19]), "+f"(d[20]), "+f"(d[21]), "+f"(d[22]), "+f"(d[23]),
      "+f"(d[24]), "+f"(d[25]), "+f"(d[26]), "+f"(d[27]), "+f"(d[28]), "+f"(d[29]), "+f"(d[30]), "+f"(d[31]),
      "+f"(d[32]), "+f"(d[33]), "+f"(d[34]), "+f"(d[35]), "+f"(d[36]), "+f"(d[37]), "+f"(d[38]), "+f"(d[39]),
      "+f"(d[40]), "+f"(d[41]), "+f"(d[42]), "+f"(d[43]), "+f"(d[44]), "+f"(d[45]), "+f"(d[46]), "+f"(d[47]),
      "+f"(d[48]), "+f"(d[49]), "+f"(d[50]), "+f"(d[51]), "+f"(d[52]), "+f"(d[53]), "+f"(d[54]), "+f"(d[55]),
      "+f"(d[56]), "+f"(d[57]), "+f"(d[58]), "+f"(d[59]), "+f"(d[60]), "+f"(d[61]), "+f"(d[62]), "+f"(d[63]),
      "+f"(d[64]), "+f"(d[65]), "+f"(d[66]), "+f"(d[67]), "+f"(d[68]), "+f"(d[69]), "+f"(d[70]), "+f"(d[71])
    : "l"(da), "l"(db), "r"(sd));
}

__device__ __forceinline__ void wgmma_ss_n160_t11(float* d, uint64_t da, uint64_t db, int sd) {
  asm volatile("{ .reg .pred p; setp.ne.b32 p, %82, 0;\n"
      "wgmma.mma_async.sync.aligned.m64n160k16.f32.bf16.bf16 {"
      "%0,%1,%2,%3,%4,%5,%6,%7,%8,%9,%10,%11,%12,%13,%14,%15,"
      "%16,%17,%18,%19,%20,%21,%22,%23,%24,%25,%26,%27,%28,%29,%30,%31,"
      "%32,%33,%34,%35,%36,%37,%38,%39,%40,%41,%42,%43,%44,%45,%46,%47,"
      "%48,%49,%50,%51,%52,%53,%54,%55,%56,%57,%58,%59,%60,%61,%62,%63,"
      "%64,%65,%66,%67,%68,%69,%70,%71,%72,%73,%74,%75,%76,%77,%78,%79"
      "}, %80, %81, p, 1, 1, 1, 1; }"
    : "+f"(d[0]), "+f"(d[1]), "+f"(d[2]), "+f"(d[3]), "+f"(d[4]), "+f"(d[5]), "+f"(d[6]), "+f"(d[7]),
      "+f"(d[8]), "+f"(d[9]), "+f"(d[10]), "+f"(d[11]), "+f"(d[12]), "+f"(d[13]), "+f"(d[14]), "+f"(d[15]),
      "+f"(d[16]), "+f"(d[17]), "+f"(d[18]), "+f"(d[19]), "+f"(d[20]), "+f"(d[21]), "+f"(d[22]), "+f"(d[23]),
      "+f"(d[24]), "+f"(d[25]), "+f"(d[26]), "+f"(d[27]), "+f"(d[28]), "+f"(d[29]), "+f"(d[30]), "+f"(d[31]),
      "+f"(d[32]), "+f"(d[33]), "+f"(d[34]), "+f"(d[35]), "+f"(d[36]), "+f"(d[37]), "+f"(d[38]), "+f"(d[39]),
      "+f"(d[40]), "+f"(d[41]), "+f"(d[42]), "+f"(d[43]), "+f"(d[44]), "+f"(d[45]), "+f"(d[46]), "+f"(d[47]),
      "+f"(d[48]), "+f"(d[49]), "+f"(d[50]), "+f"(d[51]), "+f"(d[52]), "+f"(d[53]), "+f"(d[54]), "+f"(d[55]),
      "+f"(d[56]), "+f"(d[57]), "+f"(d[58]), "+f"(d[59]), "+f"(d[60]), "+f"(d[61]), "+f"(d[62]), "+f"(d[63]),
      "+f"(d[64]), "+f"(d[65]), "+f"(d[66]), "+f"(d[67]), "+f"(d[68]), "+f"(d[69]), "+f"(d[70]), "+f"(d[71]),
      "+f"(d[72]), "+f"(d[73]), "+f"(d[74]), "+f"(d[75]), "+f"(d[76]), "+f"(d[77]), "+f"(d[78]), "+f"(d[79])
    : "l"(da), "l"(db), "r"(sd));
}

__device__ __forceinline__ void wgmma_ss_n96_t11(float* d, uint64_t da, uint64_t db, int sd) {
  asm volatile("{ .reg .pred p; setp.ne.b32 p, %50, 0;\n"
      "wgmma.mma_async.sync.aligned.m64n96k16.f32.bf16.bf16 {"
      "%0,%1,%2,%3,%4,%5,%6,%7,%8,%9,%10,%11,%12,%13,%14,%15,"
      "%16,%17,%18,%19,%20,%21,%22,%23,%24,%25,%26,%27,%28,%29,%30,%31,"
      "%32,%33,%34,%35,%36,%37,%38,%39,%40,%41,%42,%43,%44,%45,%46,%47"
      "}, %48, %49, p, 1, 1, 1, 1; }"
    : "+f"(d[0]), "+f"(d[1]), "+f"(d[2]), "+f"(d[3]), "+f"(d[4]), "+f"(d[5]), "+f"(d[6]), "+f"(d[7]),
      "+f"(d[8]), "+f"(d[9]), "+f"(d[10]), "+f"(d[11]), "+f"(d[12]), "+f"(d[13]), "+f"(d[14]), "+f"(d[15]),
      "+f"(d[16]), "+f"(d[17]), "+f"(d[18]), "+f"(d[19]), "+f"(d[20]), "+f"(d[21]), "+f"(d[22]), "+f"(d[23]),
      "+f"(d[24]), "+f"(d[25]), "+f"(d[26]), "+f"(d[27]), "+f"(d[28]), "+f"(d[29]), "+f"(d[30]), "+f"(d[31]),
      "+f"(d[32]), "+f"(d[33]), "+f"(d[34]), "+f"(d[35]), "+f"(d[36]), "+f"(d[37]), "+f"(d[38]), "+f"(d[39]),
      "+f"(d[40]), "+f"(d[41]), "+f"(d[42]), "+f"(d[43]), "+f"(d[44]), "+f"(d[45]), "+f"(d[46]), "+f"(d[47])
    : "l"(da), "l"(db), "r"(sd));
}

__device__ __forceinline__ void wgmma_rs_n16(float* d, const uint32_t* a, uint64_t db, int sd) {
  asm volatile("{ .reg .pred p; setp.ne.b32 p, %13, 0;\n"
      "wgmma.mma_async.sync.aligned.m64n16k16.f32.bf16.bf16 {"
      "%0,%1,%2,%3,%4,%5,%6,%7"
      "}, {%8,%9,%10,%11}, %12, p, 1, 1, 0; }"
    : "+f"(d[0]), "+f"(d[1]), "+f"(d[2]), "+f"(d[3]), "+f"(d[4]), "+f"(d[5]), "+f"(d[6]), "+f"(d[7])
    : "r"(a[0]), "r"(a[1]), "r"(a[2]), "r"(a[3]), "l"(db), "r"(sd));
}

__device__ __forceinline__ void wgmma_rs_n32(float* d, const uint32_t* a, uint64_t db, int sd) {
  asm volatile("{ .reg .pred p; setp.ne.b32 p, %21, 0;\n"
      "wgmma.mma_async.sync.aligned.m64n32k16.f32.bf16.bf16 {"
      "%0,%1,%2,%3,%4,%5,%6,%7,%8,%9,%10,%11,%12,%13,%14,%15"
      "}, {%16,%17,%18,%19}, %20, p, 1, 1, 0; }"
    : "+f"(d[0]), "+f"(d[1]), "+f"(d[2]), "+f"(d[3]), "+f"(d[4]), "+f"(d[5]), "+f"(d[6]), "+f"(d[7]),
      "+f"(d[8]), "+f"(d[9]), "+f"(d[10]), "+f"(d[11]), "+f"(d[12]), "+f"(d[13]), "+f"(d[14]), "+f"(d[15])
    : "r"(a[0]), "r"(a[1]), "r"(a[2]), "r"(a[3]), "l"(db), "r"(sd));
}

__device__ __forceinline__ void wgmma_rs_n48(float* d, const uint32_t* a, uint64_t db, int sd) {
  asm volatile("{ .reg .pred p; setp.ne.b32 p, %29, 0;\n"
      "wgmma.mma_async.sync.aligned.m64n48k16.f32.bf16.bf16 {"
      "%0,%1,%2,%3,%4,%5,%6,%7,%8,%9,%10,%11,%12,%13,%14,%15,"
      "%16,%17,%18,%19,%20,%21,%22,%23"
      "}, {%24,%25,%26,%27}, %28, p, 1, 1, 0; }"
    : "+f"(d[0]), "+f"(d[1]), "+f"(d[2]), "+f"(d[3]), "+f"(d[4]), "+f"(d[5]), "+f"(d[6]), "+f"(d[7]),
      "+f"(d[8]), "+f"(d[9]), "+f"(d[10]), "+f"(d[11]), "+f"(d[12]), "+f"(d[13]), "+f"(d[14]), "+f"(d[15]),
      "+f"(d[16]), "+f"(d[17]), "+f"(d[18]), "+f"(d[19]), "+f"(d[20]), "+f"(d[21]), "+f"(d[22]), "+f"(d[23])
    : "r"(a[0]), "r"(a[1]), "r"(a[2]), "r"(a[3]), "l"(db), "r"(sd));
}

__device__ __forceinline__ void wgmma_rs_n64(float* d, const uint32_t* a, uint64_t db, int sd) {
  asm volatile("{ .reg .pred p; setp.ne.b32 p, %37, 0;\n"
      "wgmma.mma_async.sync.aligned.m64n64k16.f32.bf16.bf16 {"
      "%0,%1,%2,%3,%4,%5,%6,%7,%8,%9,%10,%11,%12,%13,%14,%15,"
      "%16,%17,%18,%19,%20,%21,%22,%23,%24,%25,%26,%27,%28,%29,%30,%31"
      "}, {%32,%33,%34,%35}, %36, p, 1, 1, 0; }"
    : "+f"(d[0]), "+f"(d[1]), "+f"(d[2]), "+f"(d[3]), "+f"(d[4]), "+f"(d[5]), "+f"(d[6]), "+f"(d[7]),
      "+f"(d[8]), "+f"(d[9]), "+f"(d[10]), "+f"(d[11]), "+f"(d[12]), "+f"(d[13]), "+f"(d[14]), "+f"(d[15]),
      "+f"(d[16]), "+f"(d[17]), "+f"(d[18]), "+f"(d[19]), "+f"(d[20]), "+f"(d[21]), "+f"(d[22]), "+f"(d[23]),
      "+f"(d[24]), "+f"(d[25]), "+f"(d[26]), "+f"(d[27]), "+f"(d[28]), "+f"(d[29]), "+f"(d[30]), "+f"(d[31])
    : "r"(a[0]), "r"(a[1]), "r"(a[2]), "r"(a[3]), "l"(db), "r"(sd));
}

__device__ __forceinline__ void wgmma_rs_n80(float* d, const uint32_t* a, uint64_t db, int sd) {
  asm volatile("{ .reg .pred p; setp.ne.b32 p, %45, 0;\n"
      "wgmma.mma_async.sync.aligned.m64n80k16.f32.bf16.bf16 {"
      "%0,%1,%2,%3,%4,%5,%6,%7,%8,%9,%10,%11,%12,%13,%14,%15,"
      "%16,%17,%18,%19,%20,%21,%22,%23,%24,%25,%26,%27,%28,%29,%30,%31,"
      "%32,%33,%34,%35,%36,%37,%38,%39"
      "}, {%40,%41,%42,%43}, %44, p, 1, 1, 0; }"
    : "+f"(d[0]), "+f"(d[1]), "+f"(d[2]), "+f"(d[3]), "+f"(d[4]), "+f"(d[5]), "+f"(d[6]), "+f"(d[7]),
      "+f"(d[8]), "+f"(d[9]), "+f"(d[10]), "+f"(d[11]), "+f"(d[12]), "+f"(d[13]), "+f"(d[14]), "+f"(d[15]),
      "+f"(d[16]), "+f"(d[17]), "+f"(d[18]), "+f"(d[19]), "+f"(d[20]), "+f"(d[21]), "+f"(d[22]), "+f"(d[23]),
      "+f"(d[24]), "+f"(d[25]), "+f"(d[26]), "+f"(d[27]), "+f"(d[28]), "+f"(d[29]), "+f"(d[30]), "+f"(d[31]),
      "+f"(d[32]), "+f"(d[33]), "+f"(d[34]), "+f"(d[35]), "+f"(d[36]), "+f"(d[37]), "+f"(d[38]), "+f"(d[39])
    : "r"(a[0]), "r"(a[1]), "r"(a[2]), "r"(a[3]), "l"(db), "r"(sd));
}

__device__ __forceinline__ void wgmma_rs_n96(float* d, const uint32_t* a, uint64_t db, int sd) {
  asm volatile("{ .reg .pred p; setp.ne.b32 p, %53, 0;\n"
      "wgmma.mma_async.sync.aligned.m64n96k16.f32.bf16.bf16 {"
      "%0,%1,%2,%3,%4,%5,%6,%7,%8,%9,%10,%11,%12,%13,%14,%15,"
      "%16,%17,%18,%19,%20,%21,%22,%23,%24,%25,%26,%27,%28,%29,%30,%31,"
      "%32,%33,%34,%35,%36,%37,%38,%39,%40,%41,%42,%43,%44,%45,%46,%47"
      "}, {%48,%49,%50,%51}, %52, p, 1, 1, 0; }"
    : "+f"(d[0]), "+f"(d[1]), "+f"(d[2]), "+f"(d[3]), "+f"(d[4]), "+f"(d[5]), "+f"(d[6]), "+f"(d[7]),
      "+f"(d[8]), "+f"(d[9]), "+f"(d[10]), "+f"(d[11]), "+f"(d[12]), "+f"(d[13]), "+f"(d[14]), "+f"(d[15]),
      "+f"(d[16]), "+f"(d[17]), "+f"(d[18]), "+f"(d[19]), "+f"(d[20]), "+f"(d[21]), "+f"(d[22]), "+f"(d[23]),
      "+f"(d[24]), "+f"(d[25]), "+f"(d[26]), "+f"(d[27]), "+f"(d[28]), "+f"(d[29]), "+f"(d[30]), "+f"(d[31]),
      "+f"(d[32]), "+f"(d[33]), "+f"(d[34]), "+f"(d[35]), "+f"(d[36]), "+f"(d[37]), "+f"(d[38]), "+f"(d[39]),
      "+f"(d[40]), "+f"(d[41]), "+f"(d[42]), "+f"(d[43]), "+f"(d[44]), "+f"(d[45]), "+f"(d[46]), "+f"(d[47])
    : "r"(a[0]), "r"(a[1]), "r"(a[2]), "r"(a[3]), "l"(db), "r"(sd));
}

__device__ __forceinline__ void wgmma_rs_n112(float* d, const uint32_t* a, uint64_t db, int sd) {
  asm volatile("{ .reg .pred p; setp.ne.b32 p, %61, 0;\n"
      "wgmma.mma_async.sync.aligned.m64n112k16.f32.bf16.bf16 {"
      "%0,%1,%2,%3,%4,%5,%6,%7,%8,%9,%10,%11,%12,%13,%14,%15,"
      "%16,%17,%18,%19,%20,%21,%22,%23,%24,%25,%26,%27,%28,%29,%30,%31,"
      "%32,%33,%34,%35,%36,%37,%38,%39,%40,%41,%42,%43,%44,%45,%46,%47,"
      "%48,%49,%50,%51,%52,%53,%54,%55"
      "}, {%56,%57,%58,%59}, %60, p, 1, 1, 0; }"
    : "+f"(d[0]), "+f"(d[1]), "+f"(d[2]), "+f"(d[3]), "+f"(d[4]), "+f"(d[5]), "+f"(d[6]), "+f"(d[7]),
      "+f"(d[8]), "+f"(d[9]), "+f"(d[10]), "+f"(d[11]), "+f"(d[12]), "+f"(d[13]), "+f"(d[14]), "+f"(d[15]),
      "+f"(d[16]), "+f"(d[17]), "+f"(d[18]), "+f"(d[19]), "+f"(d[20]), "+f"(d[21]), "+f"(d[22]), "+f"(d[23]),
      "+f"(d[24]), "+f"(d[25]), "+f"(d[26]), "+f"(d[27]), "+f"(d[28]), "+f"(d[29]), "+f"(d[30]), "+f"(d[31]),
      "+f"(d[32]), "+f"(d[33]), "+f"(d[34]), "+f"(d[35]), "+f"(d[36]), "+f"(d[37]), "+f"(d[38]), "+f"(d[39]),
      "+f"(d[40]), "+f"(d[41]), "+f"(d[42]), "+f"(d[43]), "+f"(d[44]), "+f"(d[45]), "+f"(d[46]), "+f"(d[47]),
      "+f"(d[48]), "+f"(d[49]), "+f"(d[50]), "+f"(d[51]), "+f"(d[52]), "+f"(d[53]), "+f"(d[54]), "+f"(d[55])
    : "r"(a[0]), "r"(a[1]), "r"(a[2]), "r"(a[3]), "l"(db), "r"(sd));
}

__device__ __forceinline__ void wgmma_rs_n128(float* d, const uint32_t* a, uint64_t db, int sd) {
  asm volatile("{ .reg .pred p; setp.ne.b32 p, %69, 0;\n"
      "wgmma.mma_async.sync.aligned.m64n128k16.f32.bf16.bf16 {"
      "%0,%1,%2,%3,%4,%5,%6,%7,%8,%9,%10,%11,%12,%13,%14,%15,"
      "%16,%17,%18,%19,%20,%21,%22,%23,%24,%25,%26,%27,%28,%29,%30,%31,"
      "%32,%33,%34,%35,%36,%37,%38,%39,%40,%41,%42,%43,%44,%45,%46,%47,"
      "%48,%49,%50,%51,%52,%53,%54,%55,%56,%57,%58,%59,%60,%61,%62,%63"
      "}, {%64,%65,%66,%67}, %68, p, 1, 1, 0; }"
    : "+f"(d[0]), "+f"(d[1]), "+f"(d[2]), "+f"(d[3]), "+f"(d[4]), "+f"(d[5]), "+f"(d[6]), "+f"(d[7]),
      "+f"(d[8]), "+f"(d[9]), "+f"(d[10]), "+f"(d[11]), "+f"(d[12]), "+f"(d[13]), "+f"(d[14]), "+f"(d[15]),
      "+f"(d[16]), "+f"(d[17]), "+f"(d[18]), "+f"(d[19]), "+f"(d[20]), "+f"(d[21]), "+f"(d[22]), "+f"(d[23]),
      "+f"(d[24]), "+f"(d[25]), "+f"(d[26]), "+f"(d[27]), "+f"(d[28]), "+f"(d[29]), "+f"(d[30]), "+f"(d[31]),
      "+f"(d[32]), "+f"(d[33]), "+f"(d[34]), "+f"(d[35]), "+f"(d[36]), "+f"(d[37]), "+f"(d[38]), "+f"(d[39]),
      "+f"(d[40]), "+f"(d[41]), "+f"(d[42]), "+f"(d[43]), "+f"(d[44]), "+f"(d[45]), "+f"(d[46]), "+f"(d[47]),
      "+f"(d[48]), "+f"(d[49]), "+f"(d[50]), "+f"(d[51]), "+f"(d[52]), "+f"(d[53]), "+f"(d[54]), "+f"(d[55]),
      "+f"(d[56]), "+f"(d[57]), "+f"(d[58]), "+f"(d[59]), "+f"(d[60]), "+f"(d[61]), "+f"(d[62]), "+f"(d[63])
    : "r"(a[0]), "r"(a[1]), "r"(a[2]), "r"(a[3]), "l"(db), "r"(sd));
}

__device__ __forceinline__ void wgmma_rs_n144(float* d, const uint32_t* a, uint64_t db, int sd) {
  asm volatile("{ .reg .pred p; setp.ne.b32 p, %77, 0;\n"
      "wgmma.mma_async.sync.aligned.m64n144k16.f32.bf16.bf16 {"
      "%0,%1,%2,%3,%4,%5,%6,%7,%8,%9,%10,%11,%12,%13,%14,%15,"
      "%16,%17,%18,%19,%20,%21,%22,%23,%24,%25,%26,%27,%28,%29,%30,%31,"
      "%32,%33,%34,%35,%36,%37,%38,%39,%40,%41,%42,%43,%44,%45,%46,%47,"
      "%48,%49,%50,%51,%52,%53,%54,%55,%56,%57,%58,%59,%60,%61,%62,%63,"
      "%64,%65,%66,%67,%68,%69,%70,%71"
      "}, {%72,%73,%74,%75}, %76, p, 1, 1, 0; }"
    : "+f"(d[0]), "+f"(d[1]), "+f"(d[2]), "+f"(d[3]), "+f"(d[4]), "+f"(d[5]), "+f"(d[6]), "+f"(d[7]),
      "+f"(d[8]), "+f"(d[9]), "+f"(d[10]), "+f"(d[11]), "+f"(d[12]), "+f"(d[13]), "+f"(d[14]), "+f"(d[15]),
      "+f"(d[16]), "+f"(d[17]), "+f"(d[18]), "+f"(d[19]), "+f"(d[20]), "+f"(d[21]), "+f"(d[22]), "+f"(d[23]),
      "+f"(d[24]), "+f"(d[25]), "+f"(d[26]), "+f"(d[27]), "+f"(d[28]), "+f"(d[29]), "+f"(d[30]), "+f"(d[31]),
      "+f"(d[32]), "+f"(d[33]), "+f"(d[34]), "+f"(d[35]), "+f"(d[36]), "+f"(d[37]), "+f"(d[38]), "+f"(d[39]),
      "+f"(d[40]), "+f"(d[41]), "+f"(d[42]), "+f"(d[43]), "+f"(d[44]), "+f"(d[45]), "+f"(d[46]), "+f"(d[47]),
      "+f"(d[48]), "+f"(d[49]), "+f"(d[50]), "+f"(d[51]), "+f"(d[52]), "+f"(d[53]), "+f"(d[54]), "+f"(d[55]),
      "+f"(d[56]), "+f"(d[57]), "+f"(d[58]), "+f"(d[59]), "+f"(d[60]), "+f"(d[61]), "+f"(d[62]), "+f"(d[63]),
      "+f"(d[64]), "+f"(d[65]), "+f"(d[66]), "+f"(d[67]), "+f"(d[68]), "+f"(d[69]), "+f"(d[70]), "+f"(d[71])
    : "r"(a[0]), "r"(a[1]), "r"(a[2]), "r"(a[3]), "l"(db), "r"(sd));
}

__device__ __forceinline__ void wgmma_rs_n160(float* d, const uint32_t* a, uint64_t db, int sd) {
  asm volatile("{ .reg .pred p; setp.ne.b32 p, %85, 0;\n"
      "wgmma.mma_async.sync.aligned.m64n160k16.f32.bf16.bf16 {"
      "%0,%1,%2,%3,%4,%5,%6,%7,%8,%9,%10,%11,%12,%13,%14,%15,"
      "%16,%17,%18,%19,%20,%21,%22,%23,%24,%25,%26,%27,%28,%29,%30,%31,"
      "%32,%33,%34,%35,%36,%37,%38,%39,%40,%41,%42,%43,%44,%45,%46,%47,"
      "%48,%49,%50,%51,%52,%53,%54,%55,%56,%57,%58,%59,%60,%61,%62,%63,"
      "%64,%65,%66,%67,%68,%69,%70,%71,%72,%73,%74,%75,%76,%77,%78,%79"
      "}, {%80,%81,%82,%83}, %84, p, 1, 1, 0; }"
    : "+f"(d[0]), "+f"(d[1]), "+f"(d[2]), "+f"(d[3]), "+f"(d[4]), "+f"(d[5]), "+f"(d[6]), "+f"(d[7]),
      "+f"(d[8]), "+f"(d[9]), "+f"(d[10]), "+f"(d[11]), "+f"(d[12]), "+f"(d[13]), "+f"(d[14]), "+f"(d[15]),
      "+f"(d[16]), "+f"(d[17]), "+f"(d[18]), "+f"(d[19]), "+f"(d[20]), "+f"(d[21]), "+f"(d[22]), "+f"(d[23]),
      "+f"(d[24]), "+f"(d[25]), "+f"(d[26]), "+f"(d[27]), "+f"(d[28]), "+f"(d[29]), "+f"(d[30]), "+f"(d[31]),
      "+f"(d[32]), "+f"(d[33]), "+f"(d[34]), "+f"(d[35]), "+f"(d[36]), "+f"(d[37]), "+f"(d[38]), "+f"(d[39]),
      "+f"(d[40]), "+f"(d[41]), "+f"(d[42]), "+f"(d[43]), "+f"(d[44]), "+f"(d[45]), "+f"(d[46]), "+f"(d[47]),
      "+f"(d[48]), "+f"(d[49]), "+f"(d[50]), "+f"(d[51]), "+f"(d[52]), "+f"(d[53]), "+f"(d[54]), "+f"(d[55]),
      "+f"(d[56]), "+f"(d[57]), "+f"(d[58]), "+f"(d[59]), "+f"(d[60]), "+f"(d[61]), "+f"(d[62]), "+f"(d[63]),
      "+f"(d[64]), "+f"(d[65]), "+f"(d[66]), "+f"(d[67]), "+f"(d[68]), "+f"(d[69]), "+f"(d[70]), "+f"(d[71]),
      "+f"(d[72]), "+f"(d[73]), "+f"(d[74]), "+f"(d[75]), "+f"(d[76]), "+f"(d[77]), "+f"(d[78]), "+f"(d[79])
    : "r"(a[0]), "r"(a[1]), "r"(a[2]), "r"(a[3]), "l"(db), "r"(sd));
}

__device__ __forceinline__ void wgmma_rs_n176(float* d, const uint32_t* a, uint64_t db, int sd) {
  asm volatile("{ .reg .pred p; setp.ne.b32 p, %93, 0;\n"
      "wgmma.mma_async.sync.aligned.m64n176k16.f32.bf16.bf16 {"
      "%0,%1,%2,%3,%4,%5,%6,%7,%8,%9,%10,%11,%12,%13,%14,%15,"
      "%16,%17,%18,%19,%20,%21,%22,%23,%24,%25,%26,%27,%28,%29,%30,%31,"
      "%32,%33,%34,%35,%36,%37,%38,%39,%40,%41,%42,%43,%44,%45,%46,%47,"
      "%48,%49,%50,%51,%52,%53,%54,%55,%56,%57,%58,%59,%60,%61,%62,%63,"
      "%64,%65,%66,%67,%68,%69,%70,%71,%72,%73,%74,%75,%76,%77,%78,%79,"
      "%80,%81,%82,%83,%84,%85,%86,%87"
      "}, {%88,%89,%90,%91}, %92, p, 1, 1, 0; }"
    : "+f"(d[0]), "+f"(d[1]), "+f"(d[2]), "+f"(d[3]), "+f"(d[4]), "+f"(d[5]), "+f"(d[6]), "+f"(d[7]),
      "+f"(d[8]), "+f"(d[9]), "+f"(d[10]), "+f"(d[11]), "+f"(d[12]), "+f"(d[13]), "+f"(d[14]), "+f"(d[15]),
      "+f"(d[16]), "+f"(d[17]), "+f"(d[18]), "+f"(d[19]), "+f"(d[20]), "+f"(d[21]), "+f"(d[22]), "+f"(d[23]),
      "+f"(d[24]), "+f"(d[25]), "+f"(d[26]), "+f"(d[27]), "+f"(d[28]), "+f"(d[29]), "+f"(d[30]), "+f"(d[31]),
      "+f"(d[32]), "+f"(d[33]), "+f"(d[34]), "+f"(d[35]), "+f"(d[36]), "+f"(d[37]), "+f"(d[38]), "+f"(d[39]),
      "+f"(d[40]), "+f"(d[41]), "+f"(d[42]), "+f"(d[43]), "+f"(d[44]), "+f"(d[45]), "+f"(d[46]), "+f"(d[47]),
      "+f"(d[48]), "+f"(d[49]), "+f"(d[50]), "+f"(d[51]), "+f"(d[52]), "+f"(d[53]), "+f"(d[54]), "+f"(d[55]),
      "+f"(d[56]), "+f"(d[57]), "+f"(d[58]), "+f"(d[59]), "+f"(d[60]), "+f"(d[61]), "+f"(d[62]), "+f"(d[63]),
      "+f"(d[64]), "+f"(d[65]), "+f"(d[66]), "+f"(d[67]), "+f"(d[68]), "+f"(d[69]), "+f"(d[70]), "+f"(d[71]),
      "+f"(d[72]), "+f"(d[73]), "+f"(d[74]), "+f"(d[75]), "+f"(d[76]), "+f"(d[77]), "+f"(d[78]), "+f"(d[79]),
      "+f"(d[80]), "+f"(d[81]), "+f"(d[82]), "+f"(d[83]), "+f"(d[84]), "+f"(d[85]), "+f"(d[86]), "+f"(d[87])
    : "r"(a[0]), "r"(a[1]), "r"(a[2]), "r"(a[3]), "l"(db), "r"(sd));
}

__device__ __forceinline__ void wgmma_rs_n192(float* d, const uint32_t* a, uint64_t db, int sd) {
  asm volatile("{ .reg .pred p; setp.ne.b32 p, %101, 0;\n"
      "wgmma.mma_async.sync.aligned.m64n192k16.f32.bf16.bf16 {"
      "%0,%1,%2,%3,%4,%5,%6,%7,%8,%9,%10,%11,%12,%13,%14,%15,"
      "%16,%17,%18,%19,%20,%21,%22,%23,%24,%25,%26,%27,%28,%29,%30,%31,"
      "%32,%33,%34,%35,%36,%37,%38,%39,%40,%41,%42,%43,%44,%45,%46,%47,"
      "%48,%49,%50,%51,%52,%53,%54,%55,%56,%57,%58,%59,%60,%61,%62,%63,"
      "%64,%65,%66,%67,%68,%69,%70,%71,%72,%73,%74,%75,%76,%77,%78,%79,"
      "%80,%81,%82,%83,%84,%85,%86,%87,%88,%89,%90,%91,%92,%93,%94,%95"
      "}, {%96,%97,%98,%99}, %100, p, 1, 1, 0; }"
    : "+f"(d[0]), "+f"(d[1]), "+f"(d[2]), "+f"(d[3]), "+f"(d[4]), "+f"(d[5]), "+f"(d[6]), "+f"(d[7]),
      "+f"(d[8]), "+f"(d[9]), "+f"(d[10]), "+f"(d[11]), "+f"(d[12]), "+f"(d[13]), "+f"(d[14]), "+f"(d[15]),
      "+f"(d[16]), "+f"(d[17]), "+f"(d[18]), "+f"(d[19]), "+f"(d[20]), "+f"(d[21]), "+f"(d[22]), "+f"(d[23]),
      "+f"(d[24]), "+f"(d[25]), "+f"(d[26]), "+f"(d[27]), "+f"(d[28]), "+f"(d[29]), "+f"(d[30]), "+f"(d[31]),
      "+f"(d[32]), "+f"(d[33]), "+f"(d[34]), "+f"(d[35]), "+f"(d[36]), "+f"(d[37]), "+f"(d[38]), "+f"(d[39]),
      "+f"(d[40]), "+f"(d[41]), "+f"(d[42]), "+f"(d[43]), "+f"(d[44]), "+f"(d[45]), "+f"(d[46]), "+f"(d[47]),
      "+f"(d[48]), "+f"(d[49]), "+f"(d[50]), "+f"(d[51]), "+f"(d[52]), "+f"(d[53]), "+f"(d[54]), "+f"(d[55]),
      "+f"(d[56]), "+f"(d[57]), "+f"(d[58]), "+f"(d[59]), "+f"(d[60]), "+f"(d[61]), "+f"(d[62]), "+f"(d[63]),
      "+f"(d[64]), "+f"(d[65]), "+f"(d[66]), "+f"(d[67]), "+f"(d[68]), "+f"(d[69]), "+f"(d[70]), "+f"(d[71]),
      "+f"(d[72]), "+f"(d[73]), "+f"(d[74]), "+f"(d[75]), "+f"(d[76]), "+f"(d[77]), "+f"(d[78]), "+f"(d[79]),
      "+f"(d[80]), "+f"(d[81]), "+f"(d[82]), "+f"(d[83]), "+f"(d[84]), "+f"(d[85]), "+f"(d[86]), "+f"(d[87]),
      "+f"(d[88]), "+f"(d[89]), "+f"(d[90]), "+f"(d[91]), "+f"(d[92]), "+f"(d[93]), "+f"(d[94]), "+f"(d[95])
    : "r"(a[0]), "r"(a[1]), "r"(a[2]), "r"(a[3]), "l"(db), "r"(sd));
}

__device__ __forceinline__ void wgmma_rs_n208(float* d, const uint32_t* a, uint64_t db, int sd) {
  asm volatile("{ .reg .pred p; setp.ne.b32 p, %109, 0;\n"
      "wgmma.mma_async.sync.aligned.m64n208k16.f32.bf16.bf16 {"
      "%0,%1,%2,%3,%4,%5,%6,%7,%8,%9,%10,%11,%12,%13,%14,%15,"
      "%16,%17,%18,%19,%20,%21,%22,%23,%24,%25,%26,%27,%28,%29,%30,%31,"
      "%32,%33,%34,%35,%36,%37,%38,%39,%40,%41,%42,%43,%44,%45,%46,%47,"
      "%48,%49,%50,%51,%52,%53,%54,%55,%56,%57,%58,%59,%60,%61,%62,%63,"
      "%64,%65,%66,%67,%68,%69,%70,%71,%72,%73,%74,%75,%76,%77,%78,%79,"
      "%80,%81,%82,%83,%84,%85,%86,%87,%88,%89,%90,%91,%92,%93,%94,%95,"
      "%96,%97,%98,%99,%100,%101,%102,%103"
      "}, {%104,%105,%106,%107}, %108, p, 1, 1, 0; }"
    : "+f"(d[0]), "+f"(d[1]), "+f"(d[2]), "+f"(d[3]), "+f"(d[4]), "+f"(d[5]), "+f"(d[6]), "+f"(d[7]),
      "+f"(d[8]), "+f"(d[9]), "+f"(d[10]), "+f"(d[11]), "+f"(d[12]), "+f"(d[13]), "+f"(d[14]), "+f"(d[15]),
      "+f"(d[16]), "+f"(d[17]), "+f"(d[18]), "+f"(d[19]), "+f"(d[20]), "+f"(d[21]), "+f"(d[22]), "+f"(d[23]),
      "+f"(d[24]), "+f"(d[25]), "+f"(d[26]), "+f"(d[27]), "+f"(d[28]), "+f"(d[29]), "+f"(d[30]), "+f"(d[31]),
      "+f"(d[32]), "+f"(d[33]), "+f"(d[34]), "+f"(d[35]), "+f"(d[36]), "+f"(d[37]), "+f"(d[38]), "+f"(d[39]),
      "+f"(d[40]), "+f"(d[41]), "+f"(d[42]), "+f"(d[43]), "+f"(d[44]), "+f"(d[45]), "+f"(d[46]), "+f"(d[47]),
      "+f"(d[48]), "+f"(d[49]), "+f"(d[50]), "+f"(d[51]), "+f"(d[52]), "+f"(d[53]), "+f"(d[54]), "+f"(d[55]),
      "+f"(d[56]), "+f"(d[57]), "+f"(d[58]), "+f"(d[59]), "+f"(d[60]), "+f"(d[61]), "+f"(d[62]), "+f"(d[63]),
      "+f"(d[64]), "+f"(d[65]), "+f"(d[66]), "+f"(d[67]), "+f"(d[68]), "+f"(d[69]), "+f"(d[70]), "+f"(d[71]),
      "+f"(d[72]), "+f"(d[73]), "+f"(d[74]), "+f"(d[75]), "+f"(d[76]), "+f"(d[77]), "+f"(d[78]), "+f"(d[79]),
      "+f"(d[80]), "+f"(d[81]), "+f"(d[82]), "+f"(d[83]), "+f"(d[84]), "+f"(d[85]), "+f"(d[86]), "+f"(d[87]),
      "+f"(d[88]), "+f"(d[89]), "+f"(d[90]), "+f"(d[91]), "+f"(d[92]), "+f"(d[93]), "+f"(d[94]), "+f"(d[95]),
      "+f"(d[96]), "+f"(d[97]), "+f"(d[98]), "+f"(d[99]), "+f"(d[100]), "+f"(d[101]), "+f"(d[102]), "+f"(d[103])
    : "r"(a[0]), "r"(a[1]), "r"(a[2]), "r"(a[3]), "l"(db), "r"(sd));
}

__device__ __forceinline__ void wgmma_rs_n224(float* d, const uint32_t* a, uint64_t db, int sd) {
  asm volatile("{ .reg .pred p; setp.ne.b32 p, %117, 0;\n"
      "wgmma.mma_async.sync.aligned.m64n224k16.f32.bf16.bf16 {"
      "%0,%1,%2,%3,%4,%5,%6,%7,%8,%9,%10,%11,%12,%13,%14,%15,"
      "%16,%17,%18,%19,%20,%21,%22,%23,%24,%25,%26,%27,%28,%29,%30,%31,"
      "%32,%33,%34,%35,%36,%37,%38,%39,%40,%41,%42,%43,%44,%45,%46,%47,"
      "%48,%49,%50,%51,%52,%53,%54,%55,%56,%57,%58,%59,%60,%61,%62,%63,"
      "%64,%65,%66,%67,%68,%69,%70,%71,%72,%73,%74,%75,%76,%77,%78,%79,"
      "%80,%81,%82,%83,%84,%85,%86,%87,%88,%89,%90,%91,%92,%93,%94,%95,"
      "%96,%97,%98,%99,%100,%101,%102,%103,%104,%105,%106,%107,%108,%109,%110,%111"
      "}, {%112,%113,%114,%115}, %116, p, 1, 1, 0; }"
    : "+f"(d[0]), "+f"(d[1]), "+f"(d[2]), "+f"(d[3]), "+f"(d[4]), "+f"(d[5]), "+f"(d[6]), "+f"(d[7]),
      "+f"(d[8]), "+f"(d[9]), "+f"(d[10]), "+f"(d[11]), "+f"(d[12]), "+f"(d[13]), "+f"(d[14]), "+f"(d[15]),
      "+f"(d[16]), "+f"(d[17]), "+f"(d[18]), "+f"(d[19]), "+f"(d[20]), "+f"(d[21]), "+f"(d[22]), "+f"(d[23]),
      "+f"(d[24]), "+f"(d[25]), "+f"(d[26]), "+f"(d[27]), "+f"(d[28]), "+f"(d[29]), "+f"(d[30]), "+f"(d[31]),
      "+f"(d[32]), "+f"(d[33]), "+f"(d[34]), "+f"(d[35]), "+f"(d[36]), "+f"(d[37]), "+f"(d[38]), "+f"(d[39]),
      "+f"(d[40]), "+f"(d[41]), "+f"(d[42]), "+f"(d[43]), "+f"(d[44]), "+f"(d[45]), "+f"(d[46]), "+f"(d[47]),
      "+f"(d[48]), "+f"(d[49]), "+f"(d[50]), "+f"(d[51]), "+f"(d[52]), "+f"(d[53]), "+f"(d[54]), "+f"(d[55]),
      "+f"(d[56]), "+f"(d[57]), "+f"(d[58]), "+f"(d[59]), "+f"(d[60]), "+f"(d[61]), "+f"(d[62]), "+f"(d[63]),
      "+f"(d[64]), "+f"(d[65]), "+f"(d[66]), "+f"(d[67]), "+f"(d[68]), "+f"(d[69]), "+f"(d[70]), "+f"(d[71]),
      "+f"(d[72]), "+f"(d[73]), "+f"(d[74]), "+f"(d[75]), "+f"(d[76]), "+f"(d[77]), "+f"(d[78]), "+f"(d[79]),
      "+f"(d[80]), "+f"(d[81]), "+f"(d[82]), "+f"(d[83]), "+f"(d[84]), "+f"(d[85]), "+f"(d[86]), "+f"(d[87]),
      "+f"(d[88]), "+f"(d[89]), "+f"(d[90]), "+f"(d[91]), "+f"(d[92]), "+f"(d[93]), "+f"(d[94]), "+f"(d[95]),
      "+f"(d[96]), "+f"(d[97]), "+f"(d[98]), "+f"(d[99]), "+f"(d[100]), "+f"(d[101]), "+f"(d[102]), "+f"(d[103]),
      "+f"(d[104]), "+f"(d[105]), "+f"(d[106]), "+f"(d[107]), "+f"(d[108]), "+f"(d[109]), "+f"(d[110]), "+f"(d[111])
    : "r"(a[0]), "r"(a[1]), "r"(a[2]), "r"(a[3]), "l"(db), "r"(sd));
}

__device__ __forceinline__ void wgmma_rs_n240(float* d, const uint32_t* a, uint64_t db, int sd) {
  asm volatile("{ .reg .pred p; setp.ne.b32 p, %125, 0;\n"
      "wgmma.mma_async.sync.aligned.m64n240k16.f32.bf16.bf16 {"
      "%0,%1,%2,%3,%4,%5,%6,%7,%8,%9,%10,%11,%12,%13,%14,%15,"
      "%16,%17,%18,%19,%20,%21,%22,%23,%24,%25,%26,%27,%28,%29,%30,%31,"
      "%32,%33,%34,%35,%36,%37,%38,%39,%40,%41,%42,%43,%44,%45,%46,%47,"
      "%48,%49,%50,%51,%52,%53,%54,%55,%56,%57,%58,%59,%60,%61,%62,%63,"
      "%64,%65,%66,%67,%68,%69,%70,%71,%72,%73,%74,%75,%76,%77,%78,%79,"
      "%80,%81,%82,%83,%84,%85,%86,%87,%88,%89,%90,%91,%92,%93,%94,%95,"
      "%96,%97,%98,%99,%100,%101,%102,%103,%104,%105,%106,%107,%108,%109,%110,%111,"
      "%112,%113,%114,%115,%116,%117,%118,%119"
      "}, {%120,%121,%122,%123}, %124, p, 1, 1, 0; }"
    : "+f"(d[0]), "+f"(d[1]), "+f"(d[2]), "+f"(d[3]), "+f"(d[4]), "+f"(d[5]), "+f"(d[6]), "+f"(d[7]),
      "+f"(d[8]), "+f"(d[9]), "+f"(d[10]), "+f"(d[11]), "+f"(d[12]), "+f"(d[13]), "+f"(d[14]), "+f"(d[15]),
      "+f"(d[16]), "+f"(d[17]), "+f"(d[18]), "+f"(d[19]), "+f"(d[20]), "+f"(d[21]), "+f"(d[22]), "+f"(d[23]),
      "+f"(d[24]), "+f"(d[25]), "+f"(d[26]), "+f"(d[27]), "+f"(d[28]), "+f"(d[29]), "+f"(d[30]), "+f"(d[31]),
      "+f"(d[32]), "+f"(d[33]), "+f"(d[34]), "+f"(d[35]), "+f"(d[36]), "+f"(d[37]), "+f"(d[38]), "+f"(d[39]),
      "+f"(d[40]), "+f"(d[41]), "+f"(d[42]), "+f"(d[43]), "+f"(d[44]), "+f"(d[45]), "+f"(d[46]), "+f"(d[47]),
      "+f"(d[48]), "+f"(d[49]), "+f"(d[50]), "+f"(d[51]), "+f"(d[52]), "+f"(d[53]), "+f"(d[54]), "+f"(d[55]),
      "+f"(d[56]), "+f"(d[57]), "+f"(d[58]), "+f"(d[59]), "+f"(d[60]), "+f"(d[61]), "+f"(d[62]), "+f"(d[63]),
      "+f"(d[64]), "+f"(d[65]), "+f"(d[66]), "+f"(d[67]), "+f"(d[68]), "+f"(d[69]), "+f"(d[70]), "+f"(d[71]),
      "+f"(d[72]), "+f"(d[73]), "+f"(d[74]), "+f"(d[75]), "+f"(d[76]), "+f"(d[77]), "+f"(d[78]), "+f"(d[79]),
      "+f"(d[80]), "+f"(d[81]), "+f"(d[82]), "+f"(d[83]), "+f"(d[84]), "+f"(d[85]), "+f"(d[86]), "+f"(d[87]),
      "+f"(d[88]), "+f"(d[89]), "+f"(d[90]), "+f"(d[91]), "+f"(d[92]), "+f"(d[93]), "+f"(d[94]), "+f"(d[95]),
      "+f"(d[96]), "+f"(d[97]), "+f"(d[98]), "+f"(d[99]), "+f"(d[100]), "+f"(d[101]), "+f"(d[102]), "+f"(d[103]),
      "+f"(d[104]), "+f"(d[105]), "+f"(d[106]), "+f"(d[107]), "+f"(d[108]), "+f"(d[109]), "+f"(d[110]), "+f"(d[111]),
      "+f"(d[112]), "+f"(d[113]), "+f"(d[114]), "+f"(d[115]), "+f"(d[116]), "+f"(d[117]), "+f"(d[118]), "+f"(d[119])
    : "r"(a[0]), "r"(a[1]), "r"(a[2]), "r"(a[3]), "l"(db), "r"(sd));
}

__device__ __forceinline__ void wgmma_rs_n256(float* d, const uint32_t* a, uint64_t db, int sd) {
  asm volatile("{ .reg .pred p; setp.ne.b32 p, %133, 0;\n"
      "wgmma.mma_async.sync.aligned.m64n256k16.f32.bf16.bf16 {"
      "%0,%1,%2,%3,%4,%5,%6,%7,%8,%9,%10,%11,%12,%13,%14,%15,"
      "%16,%17,%18,%19,%20,%21,%22,%23,%24,%25,%26,%27,%28,%29,%30,%31,"
      "%32,%33,%34,%35,%36,%37,%38,%39,%40,%41,%42,%43,%44,%45,%46,%47,"
      "%48,%49,%50,%51,%52,%53,%54,%55,%56,%57,%58,%59,%60,%61,%62,%63,"
      "%64,%65,%66,%67,%68,%69,%70,%71,%72,%73,%74,%75,%76,%77,%78,%79,"
      "%80,%81,%82,%83,%84,%85,%86,%87,%88,%89,%90,%91,%92,%93,%94,%95,"
      "%96,%97,%98,%99,%100,%101,%102,%103,%104,%105,%106,%107,%108,%109,%110,%111,"
      "%112,%113,%114,%115,%116,%117,%118,%119,%120,%121,%122,%123,%124,%125,%126,%127"
      "}, {%128,%129,%130,%131}, %132, p, 1, 1, 0; }"
    : "+f"(d[0]), "+f"(d[1]), "+f"(d[2]), "+f"(d[3]), "+f"(d[4]), "+f"(d[5]), "+f"(d[6]), "+f"(d[7]),
      "+f"(d[8]), "+f"(d[9]), "+f"(d[10]), "+f"(d[11]), "+f"(d[12]), "+f"(d[13]), "+f"(d[14]), "+f"(d[15]),
      "+f"(d[16]), "+f"(d[17]), "+f"(d[18]), "+f"(d[19]), "+f"(d[20]), "+f"(d[21]), "+f"(d[22]), "+f"(d[23]),
      "+f"(d[24]), "+f"(d[25]), "+f"(d[26]), "+f"(d[27]), "+f"(d[28]), "+f"(d[29]), "+f"(d[30]), "+f"(d[31]),
      "+f"(d[32]), "+f"(d[33]), "+f"(d[34]), "+f"(d[35]), "+f"(d[36]), "+f"(d[37]), "+f"(d[38]), "+f"(d[39]),
      "+f"(d[40]), "+f"(d[41]), "+f"(d[42]), "+f"(d[43]), "+f"(d[44]), "+f"(d[45]), "+f"(d[46]), "+f"(d[47]),
      "+f"(d[48]), "+f"(d[49]), "+f"(d[50]), "+f"(d[51]), "+f"(d[52]), "+f"(d[53]), "+f"(d[54]), "+f"(d[55]),
      "+f"(d[56]), "+f"(d[57]), "+f"(d[58]), "+f"(d[59]), "+f"(d[60]), "+f"(d[61]), "+f"(d[62]), "+f"(d[63]),
      "+f"(d[64]), "+f"(d[65]), "+f"(d[66]), "+f"(d[67]), "+f"(d[68]), "+f"(d[69]), "+f"(d[70]), "+f"(d[71]),
      "+f"(d[72]), "+f"(d[73]), "+f"(d[74]), "+f"(d[75]), "+f"(d[76]), "+f"(d[77]), "+f"(d[78]), "+f"(d[79]),
      "+f"(d[80]), "+f"(d[81]), "+f"(d[82]), "+f"(d[83]), "+f"(d[84]), "+f"(d[85]), "+f"(d[86]), "+f"(d[87]),
      "+f"(d[88]), "+f"(d[89]), "+f"(d[90]), "+f"(d[91]), "+f"(d[92]), "+f"(d[93]), "+f"(d[94]), "+f"(d[95]),
      "+f"(d[96]), "+f"(d[97]), "+f"(d[98]), "+f"(d[99]), "+f"(d[100]), "+f"(d[101]), "+f"(d[102]), "+f"(d[103]),
      "+f"(d[104]), "+f"(d[105]), "+f"(d[106]), "+f"(d[107]), "+f"(d[108]), "+f"(d[109]), "+f"(d[110]), "+f"(d[111]),
      "+f"(d[112]), "+f"(d[113]), "+f"(d[114]), "+f"(d[115]), "+f"(d[116]), "+f"(d[117]), "+f"(d[118]), "+f"(d[119]),
      "+f"(d[120]), "+f"(d[121]), "+f"(d[122]), "+f"(d[123]), "+f"(d[124]), "+f"(d[125]), "+f"(d[126]), "+f"(d[127])
    : "r"(a[0]), "r"(a[1]), "r"(a[2]), "r"(a[3]), "l"(db), "r"(sd));
}

__device__ __forceinline__ void ln_finish(float mean, float var, float& mb, float& rinv) {
  mb = round_bf16(mean);
  float sd;
  asm("sqrt.approx.ftz.f32 %0, %1;" : "=f"(sd) : "f"(round_bf16(round_bf16(var) + 1e-5f)));
  asm("rcp.approx.ftz.f32 %0, %1;" : "=f"(rinv) : "f"(round_bf16(sd)));
}
__device__ __forceinline__ uint32_t sum4(uint32_t a, uint32_t b, uint32_t c, uint32_t d) { return badd2(badd2(badd2(d, c), b), a); }
struct Ring {
  uint32_t s, ph;
  __device__ __forceinline__ void next() { if (++s == NSTAGE) { s = 0; ph ^= 1; } }
};

template <int J> __device__ __forceinline__ void conv_lda(uint32_t* a, uint32_t base) {
  a[2 * J] = lds32(base + (J >> 1) * 256 + (J & 1) * 16); a[2 * J + 1] = lds32(base + (J >> 1) * 256 + (J & 1) * 16 + 128);
}
template <int J = 0> __device__ __forceinline__ void conv_lda_all(uint32_t* a, uint32_t base) {
  conv_lda<J>(a, base);
  if constexpr (J < 31) conv_lda_all<J + 1>(a, base);
}
__device__ __forceinline__ void conv_mma(float* acc, const uint32_t* a, uint64_t db) {
  wgmma_rs_n256(acc, a, db, 0);
  wgmma_rs_n240(acc, a + 4, db + 16, 1);
  wgmma_rs_n224(acc, a + 8, db + 32, 1);
  wgmma_rs_n208(acc, a + 12, db + 48, 1);
  wgmma_rs_n192(acc, a + 16, db + 64, 1);
  wgmma_rs_n176(acc, a + 20, db + 80, 1);
  wgmma_rs_n160(acc, a + 24, db + 96, 1);
  wgmma_rs_n144(acc, a + 28, db + 112, 1);
  wgmma_rs_n128(acc, a + 32, db + 128, 1);
  wgmma_rs_n112(acc, a + 36, db + 144, 1);
  wgmma_rs_n96(acc, a + 40, db + 160, 1);
  wgmma_rs_n80(acc, a + 44, db + 176, 1);
  wgmma_rs_n64(acc, a + 48, db + 192, 1);
  wgmma_rs_n48(acc, a + 52, db + 208, 1);
  wgmma_rs_n32(acc, a + 56, db + 224, 1);
  wgmma_rs_n16(acc, a + 60, db + 240, 1);
}
__device__ __forceinline__ uint32_t conv_part(const float* acc, int j) {
  const int q = 31 - j;
  return q == 31 ? pack_bf16(acc[124], acc[125]) : pack_bf16(acc[4 * q] + acc[(4 * q + 6) & 127], acc[4 * q + 1] + acc[(4 * q + 7) & 127]);
}
template <bool MORE, int J = 0> __device__ __forceinline__ void conv_drain(const float* acc, uint32_t wr, uint32_t* a, uint32_t ka) {
  if (MORE) conv_lda<J>(a, ka);
  sts32(wr + J * 128, conv_part(acc, J));
  if constexpr (J < 31) conv_drain<MORE, J + 1>(acc, wr, a, ka);
}
__device__ __forceinline__ uint4 conv_sum(const uint4* p) {
  return make_uint4(sum4(p[0].x, p[1].x, p[2].x, p[3].x), sum4(p[0].y, p[1].y, p[2].y, p[3].y), sum4(p[0].z, p[1].z, p[2].z, p[3].z),
                    sum4(p[0].w, p[1].w, p[2].w, p[3].w));
}
__device__ __forceinline__ int g2pos(int fb) { return fb / G2_KB * G2_KB + fb % 6 * 6 + fb % G2_KB / 6; }

template <int NV> __device__ __forceinline__ void gelu_stage(float* acc, const float* hb, uint32_t sa, int passes, uint32_t bar) {
#pragma unroll
  for (int i = 0; i < NV; i++) acc[i] = fmaf(acc[i], 0.5f, hb[(i >> 1) & 1]);
#pragma unroll 1
  for (; passes > 0; passes--, sa += NV * 256) {
#pragma unroll
    for (int i = 0; i < NV; i += 8)
      stsm4t(sa + i * 256, pack_bf16(gelu_half(acc[i]), gelu_half(acc[i + 1])), pack_bf16(gelu_half(acc[i + 2]), gelu_half(acc[i + 3])),
             pack_bf16(gelu_half(acc[i + 4]), gelu_half(acc[i + 5])), pack_bf16(gelu_half(acc[i + 6]), gelu_half(acc[i + 7])));
    __syncwarp();
    if (bar) mbar_arrive(bar);
    bar = 0;
    float half = 0.5f;
    asm volatile("" : "+f"(half));
#pragma unroll
    for (int i = 0; i < NV; i++) acc[i] = fmaf(acc[NV + i], half, hb[2 + ((i >> 1) & 1)]);
  }
}

__global__ void __cluster_dims__(2, 1, 1) __launch_bounds__(384, 1) fused_kernel(const __grid_constant__ Hot H, const __grid_constant__ Params P) {
  extern __shared__ __align__(1024) uint8_t smem_raw[];
  const uint32_t t0 = clk();
  const uint32_t sb = smem_u32(smem_raw);
  const int tid = threadIdx.x, lane = tid & 31;
  const int bid = blockIdx.x, rank = bid & 1;
  const Role& R = P.role[bid];
  Scratch* const S = H.S;
  uint32_t xr[18];
  const int row = bid * 16 + (tid >> 4);
  if (tid < 256 && bid < 128) {
    const char* src = reinterpret_cast<const char*>(H.x) + row * (D_ * 2) + (lane & 15) * 8;
#pragma unroll
    for (int j = 0; j < 9; j++) asm volatile("ld.global.nc.v2.u32 {%0,%1}, [%2];" : "=r"(xr[2 * j]), "=r"(xr[2 * j + 1]) : "l"(src + 128 * j));
  }
  if (tid == 256) asm volatile("prefetch.tensormap [%0];" :: "l"(&P.m_w1 + (R.at == 15)) : "memory");
  const int warp = __shfl_sync(0xffffffffu, tid >> 5, 0);

  if (warp >= 8) {
    const bool one = elect_one(), left = R.at == 15;
    if (warp == 8 && one) {
#pragma unroll
      for (int b = B_FULL; b < B_KFULL; b += 8) mbar_init(sb + b, 1);
      fence_async_smem();
      tma3d_ef(sb, &P.m_w1 + left, 0, 0, R.fg, sb + B_FULL);
#pragma unroll
      for (int s = 0; s < NSTAGE; s++) mbar_expect_tx(sb + B_FULL + 8 * s, G1_BYTES);
#pragma unroll
      for (int b = B_KFULL; b <= B_DONE; b += 8) mbar_init(sb + b, b < B_EMPTY ? 1 : b < B_SFREE ? 2 : b < B_CEMPTY ? 3 : b < B_G1DONE ? 4 : 8);
      asm volatile("fence.mbarrier_init.release.cluster;" ::: "memory");
    }
    __syncwarp();
    asm volatile("barrier.cluster.arrive.relaxed.aligned;" ::: "memory");
    asm volatile("setmaxnreg.dec.sync.aligned.u32 56;");
    asm volatile("barrier.cluster.wait.aligned;" ::: "memory");
    if (warp == 8) {
      const uint32_t ep = ldg32(S->cnt + C_EPOCH * 32);
      if (one) {
#pragma unroll 1
        for (int i = 0; i < 6; i++) asm volatile("prefetch.tensormap [%0];" :: "l"(&P.m_w2 + i) : "memory");
      }
      __syncwarp();
      if (bid < 128) bar_sync(2, 288);
      if (one) {
        const uint32_t boff = left ? 24576 : 16384, hbytes = G1_BYTES - boff;
        const CUtensorMap* const mw1 = &P.m_w1 + left;
        const int fg = R.fg;
        const char* hp = reinterpret_cast<const char*>(S->h) + R.at * 4096;
        TLREC(31);
        signal(S, C_H, EPOCH / 132);
        TLREC(1);
        tma3d_ef(sb + SLOT, mw1, 0, 64, fg, sb + B_FULL + 8);
        await(S, C_H, ep);
        fence_async_global();
        TLREC(2);
        const uint32_t tp = clk();
#pragma unroll 1
        for (int s = 0; s < NSTAGE; s++) {
          while ((int)(clk() - tp) < s * 400 - 100) { }
          if (s >= 1 && s + 1 < NSTAGE) tma3d_ef(sb + (s + 1) * SLOT, mw1, 0, (s + 1) * 64, fg, sb + B_FULL + 8 * (s + 1));
          bulk_load(sb + s * SLOT + boff, hp, hbytes, sb + B_FULL + 8 * s);
          hp += 73728;
        }
        int kr = bid < 128 ? -2 : KV_ROUNDS + 1, ks = 0;
        auto kv_step = [&]() {
          if (ks == 0) {
            bulk_wait_all();
            if (kr < KV_ROUNDS - 2) {
              const int q = (kr + 2) % 3;
              const uint32_t in = sb + kv_buf(q), fb = sb + B_UFULL + 8 * q;
              mbar_expect_tx(fb, 3840 + 3264 + 768);
              tma2d(in, &P.m_k, (kr + 2) * 96, bid * 16 - 4, fb);
              tma2d(in + 3840, &P.m_v, (kr + 2) * 96, bid * 16 - 1, fb);
              bulk_load(in + 7168, H.shift_k + (kr + 2) * 384, 768, fb);
            }
            if (kr == KV_ROUNDS) { mbar_arrive(sb + B_KVDONE); kr++; }
          } else if (kr >= 0) {
            if (!mbar_test(sb + B_KFULL + 8 * (kr % 3), kr >= 3)) return;
            fence_async_smem();
            tma3d_store(&P.m_ub, sb + kv_buf(kr % 3) + (ks - 1) * 3072, 16 * (127 - bid), kr * 48, 2 * ks - 2);
            bulk_commit();
          }
          if (++ks == 3) { kr++; ks = kr == KV_ROUNDS - 2 || kr == KV_ROUNDS - 1; }
        };
        if (bid >= 128) mbar_arrive(sb + B_KVDONE);
        uint32_t slot = sb, fb = sb + B_FULL, ph = 0;
        auto next = [&]() { slot += SLOT; fb += 8; if (fb == sb + B_FULL + 8 * NSTAGE) { slot = sb; fb = sb + B_FULL; ph ^= 1; } };
#pragma unroll 1
        for (int k0 = NSTAGE * 64; k0 < G1_KB * 64 || kr <= KV_ROUNDS; k0 += 64) {
          if (k0 < G1_KB * 64) {
            mbar_wait(fb + (B_EMPTY - B_FULL), ph);
            mbar_expect_tx(fb, G1_BYTES);
            tma3d_ef(slot, mw1, 0, k0, fg, fb);
            bulk_load(slot + boff, hp, hbytes, fb);
            hp += 73728;
            next();
            if (k0 == 23 * 64) {
#pragma unroll 1
              for (int i = 0; i < 2; i++) {
                sts128(sb + cv_taps(i), 0, 0, 0, 0); sts128(sb + cv_taps(i) + 16, 0, 0, 0, 0);
                bulk_load(sb + cv_taps(i) + 32, H.ssm_k + (R.ch + i) * S_, 4096, sb + B_MISC);
              }
              mbar_expect_tx(sb + B_MISC, boff / 64 + 1152 + 8192);
              bulk_load(sb + SM_B1, H.b1 + fg * 64, boff / 64, sb + B_MISC);
              bulk_load(sb + SM_D, H.ssm_D, 1152, sb + B_MISC);
            }
          }
          if (kr <= KV_ROUNDS) kv_step();
        }
        await(S, C_KV, ep);
        fence_async_global();
#pragma unroll 1
        for (int i = 0; i < R.ncv; i++) {
          if (i == 2) {
            if (R.sg >= 0) {
#pragma unroll 1
              for (int s = 2; s < NSTAGE; s++) {
                mbar_wait(sb + B_EMPTY + 8 * s, ((G1_KB / NSTAGE) - 1) & 1);
                mbar_expect_tx(sb + B_FULL + 8 * s, G2_BYTES);
                tma3d_ef(sb + s * SLOT, &P.m_w2, 0, (rank * G2_KB + 6 * (s - 2)) * 64, R.sg, sb + B_FULL + 8 * s);
              }
            }
            mbar_wait(sb + B_G1DONE, 0);
          }
          const uint32_t kt = sb + cv_taps(i), b8 = sb + 8 * (i & 3);
          mbar_wait(b8 + B_CEMPTY, ((i >> 2) & 1) ^ 1);
          if (i < 2) mbar_arrive(b8 + B_KFULL);
          else {
            sts128(kt, 0, 0, 0, 0); sts128(kt + 16, 0, 0, 0, 0);
            mbar_expect_tx(b8 + B_KFULL, 4096);
            bulk_load(kt + 32, H.ssm_k + (R.ch + i) * S_, 4096, b8 + B_KFULL);
          }
          mbar_expect_tx(b8 + B_UFULL, 8192);
          bulk_load(sb + cv_in(i), S->ub + (R.ch + i) * 4096, 8192, b8 + B_UFULL);
        }
        if (R.sg >= 0) {
          mbar_expect_tx(sb + B_XY, 2 * 18432 + 2048 + 256);
#pragma unroll
          for (int i = 0; i < 4; i++) mbar_expect_tx(sb + B_XFULL + 8 * i, i & 1 ? 9216 - XP * 2048 : XP * 2048);
          const int sg = R.sg, kend = (rank + 1) * G2_KB * 64;
          const char* us = reinterpret_cast<const char*>(S->u) + rank * G2_KB * 73728 + R.ds * 1024;
          const int dko = rank ? 9216 : -9216;
          await(S, C_U, ep);
          fence_async_global();
          TLREC(6);
#pragma unroll
          for (int s = 2; s < NSTAGE; s++) {
            bulk_load_ef(sb + s * SLOT + 16384, us + (s - 2) * 73728, 9216, sb + B_FULL + 8 * s);
            bulk_load_ef(sb + s * SLOT + 16384 + 9216, us + dko + (s - 2) * 73728, 9216, sb + B_FULL + 8 * s);
          }
          us += (NSTAGE - 2) * 73728;
          slot = sb; fb = sb + B_FULL; ph = (G1_KB / NSTAGE) & 1;
          int k0 = kend - (G2_KB - 6 * (NSTAGE - 2)) * 64;
#pragma unroll 1
          for (int kb = NSTAGE - 2; kb < G2_KB; kb++) {
            mbar_wait(fb + (B_EMPTY - B_FULL), ph);
            mbar_expect_tx(fb, G2_BYTES);
            tma3d_ef(slot, &P.m_w2, 0, k0, sg, fb);
            bulk_load_ef(slot + 16384, us, 9216, fb);
            bulk_load_ef(slot + 16384 + 9216, us + dko, 9216, fb);
            us += 73728;
            k0 += 6 * 64;
            if (k0 >= kend) k0 -= (G2_KB - 1) * 64;
            next();
            if (kb < 16) {
              TUNED(SYNCA, 0, 5); TUNED(SYNCKB, 1, 7);
              if (kb == 3) { await(S, C_U + 1, ep); fence_async_global(); }
              if (kb == SYNCA) asm volatile("red.relaxed.gpu.global.add.u32 [%0], %1;" :: "l"(S->cnt + C_SYNC * 32), "r"(EPOCH / 128) : "memory");
              if (kb == SYNCKB - 1) await(S, C_SYNC, ep);
              if (kb == 8) { mbar_wait(sb + B_KVDONE, 1); fence_async_smem(); }
              if (kb >= 8) tma2d(sb + SM_CV + (kb - 8) * 2304, &P.m_x, R.dk * 8, sg * 64 + (kb - 8) * 16, sb + B_XY);
            }
          }
          bulk_load(sb + SM_ST, S->stats + R.sg * 64, 2048, sb + B_XY);
          bulk_load(sb + SM_B2, P.b2 + R.sg * 64, 256, sb + B_XY);
          await(S, C_Y, ep);
          fence_async_global();
          TLREC(19);
          tma3d(sb + SM_DED, &P.m_y, 0, R.dk * 8, R.sg, sb + B_XY);
          if (bid == 0) asm volatile("red.relaxed.gpu.global.add.u32 [%0], %1;" :: "l"(S->cnt + C_EPOCH * 32), "r"(EPOCH) : "memory");
        }
      }
    } else {
      if (bid < 128) {
        const int ht = tid - 288, hf = ht >= 48, pr = ht - 48 * hf;
        const uint32_t st = (1 - hf) * 1536 + pr * 32, sw = (pr & 4) * 4;
#pragma unroll 1
        for (int r = 0; r < KV_ROUNDS; r++) {
          const int q = r % 3;
          const uint32_t in = sb + kv_buf(q);
          {
            mbar_wait_guarded(sb + B_UFULL + 8 * q, t0, r >= 3);
            uint32_t kk[12], vv[9];
#pragma unroll
            for (int j = 0; j < 12; j++) kk[j] = lds32(in + hf * 1536 + pr * 4 + j * 192);
#pragma unroll
            for (int j = 0; j < 9; j++) vv[j] = lds32(in + 3840 + hf * 1536 + pr * 4 + j * 192);
            const uint4 w = lds128(in + 7168 + pr * 16);
            const uint32_t w0 = __byte_perm(w.x, w.z, 0x5410), w1 = __byte_perm(w.x, w.z, 0x7632);
            const uint32_t w2 = __byte_perm(w.y, w.w, 0x5410), w3 = __byte_perm(w.y, w.w, 0x7632);
#pragma unroll
            for (int j = 0; j < 9; j++)
              vv[j] = bmul2(badd2(badd2(badd2(bmul2(kk[j], w3), bmul2(kk[j + 1], w2)), bmul2(kk[j + 2], w1)), bmul2(kk[j + 3], w0)), vv[j]);
            bar_sync(1, 96);
#pragma unroll
            for (int c = 0; c < 2; c++)
#pragma unroll
              for (int pi = 0; pi < 2; pi++) {
                const uint32_t sel = c ? 0x7632 : 0x5410;
                sts128(in + st + c * 3072 + (pi * 16 ^ sw), __byte_perm(vv[7 + pi], vv[6 + pi], sel), __byte_perm(vv[5 + pi], vv[4 + pi], sel),
                       __byte_perm(vv[3 + pi], vv[2 + pi], sel), __byte_perm(vv[1 + pi], vv[pi], sel));
              }
            bar_sync(1, 96);
            if (ht == 0) mbar_arrive(sb + B_KFULL + 8 * q);
          }
          __syncwarp();
        }
      }
      if (one) {
        if (warp < 11) {
          const int wg = warp - 9;
          const uint32_t bytes = left ? 12288 : 10240;
#pragma unroll 1
          for (int j = 0; j < 2; j++) {
            mbar_wait_guarded(sb + B_STG + 8 * wg + (j ? 0 : 16), t0);
            fence_async_smem();
            TLREC(13 + wg);
            if (!j || wg || !left)
              bulk_store(S->u + g2pos(R.fg + wg + (j && left)) * (64 * D_) + R.at * 2048 + (left ? 0 : j * 5120), sb + (wg ? SM_ST1 : SM_DED) + j * bytes, bytes);
          }
          bulk_commit();
          bulk_wait_all();
          mbar_arrive(sb + B_STORED + 8 * wg);
          if (wg) mbar_arrive(sb + B_EMPTY);
          asm volatile("mbarrier.arrive.shared::cta.b64 _, [%0], 3;" :: "r"(sb + B_SFREE + 8 * wg) : "memory");
          signal(S, C_U + wg, EPOCH / 132);
          TLREC(15 + wg);
        } else {
          mbar_wait_guarded(sb + B_KVDONE, t0);
          signal(S, C_KV, EPOCH / 132);
          TLREC(27);
        }
      }
      __syncwarp();
#pragma unroll 1
      for (int i = 0; i < R.ncv; i++) {
        const uint32_t red = sb + cv_red(i, R.ncv) + (tid - 288) * 16;
        uint4* yo = reinterpret_cast<uint4*>(S->y + (R.ch + i) * S_) + (tid - 288);
        mbar_wait_guarded(sb + B_STORED + 8 * (i & 1), t0);
        mbar_wait_guarded(sb + B_STG + 8 * (i & 1) + (i + 2 < R.ncv ? 0 : 16), t0, i + 2 >= R.ncv || !(i & 2));
        uint4 p[2][4];
#pragma unroll
        for (int x = 0; x < 8; x++) p[x >> 2][x & 3] = lds128(red + (x & 3) * CV_REDW + (x >> 2) * 1536);
        yo[0] = conv_sum(p[0]);
        if (warp < 11) {
#pragma unroll
          for (int x = 0; x < 4; x++) p[0][x] = lds128(red + x * CV_REDW + 3072);
          yo[192] = conv_sum(p[0]);
        }
        yo[96] = conv_sum(p[1]);
        __syncwarp();
        if (one) mbar_arrive(sb + (i + 4 == R.ncv ? B_PDONE : B_SFREE + 8 * (i & 1)));
        if (i + 3 == R.ncv) {
          bar_sync(1, 96);
          if (warp == 11 && one) { fence_async_smem(); mbar_arrive(sb + B_EMPTY + 8); }
          __syncwarp();
        }
      }
      bar_sync(1, 96);
      if (warp == 11 && one) {
        TLREC(7);
        mbar_arrive(sb + B_KVDONE);
        signal(S, C_Y, EPOCH / 132);
        if (R.sg >= 0) mbar_wait_guarded(sb + B_DONE, t0);
      }
    }
    TLEND();
  } else {
    asm volatile("barrier.cluster.arrive.relaxed.aligned;" ::: "memory");
    if (bid < 128) {
      float c[36], s[4];
#pragma unroll
      for (int i = 0; i < 18; i++) { c[2 * i] = bf_lo(xr[i]); c[2 * i + 1] = bf_hi(xr[i]); }
#pragma unroll
      for (int i = 0; i < 36; i++) s[i & 3] = i < 4 ? c[i] : s[i & 3] + c[i];
      const float ml = ((s[0] + s[1]) + (s[2] + s[3])) * (1.0f / 36.0f);
#pragma unroll
      for (int i = 0; i < 36; i++) { c[i] -= ml; s[i & 3] = i < 4 ? c[i] * c[i] : fmaf(c[i], c[i], s[i & 3]); }
      float m = ml, q = (s[0] + s[1]) + (s[2] + s[3]), n2 = 18.f;
#pragma unroll
      for (int o = 1; o < 16; o <<= 1) {
        const float mo = __shfl_xor_sync(0xffffffffu, m, o), qo = __shfl_xor_sync(0xffffffffu, q, o);
        const float dl = m - mo;
        q = fmaf(dl * dl, n2, q + qo);
        m = fmaf(dl, -0.5f, m);
        n2 *= 2.f;
      }
      const float var = q * (1.0f / 576.0f);
      float mb, rinv, mb2, rinv2;
      ln_finish(m, var, mb, rinv);
      ln_finish((m - mb) * rinv, var * rinv * rinv, mb2, rinv2);
      const float ca = rinv * rinv2, cb = fmaf(ml - mb, rinv, -mb2) * rinv2;
      uint2* dst = reinterpret_cast<uint2*>(S->h) + ((row >> 6) * 18 + ((lane >> 3) & 1)) * 512 + (row & 63) * 8 + ((lane & 7) ^ (row & 6));
#pragma unroll
      for (int j = 0; j < 9; j++)
        dst[1024 * j] = make_uint2(pack_bf16(fmaf(c[4 * j], ca, cb), fmaf(c[4 * j + 1], ca, cb)), pack_bf16(fmaf(c[4 * j + 2], ca, cb), fmaf(c[4 * j + 3], ca, cb)));
      const uint32_t rh = pack_bf16(rinv, rinv);
      if (!(lane & 15)) S->stats[row] = make_uint4(pack_bf16(mb, mb), rh, pack_bf16(rinv - bf_lo(rh), rinv - bf_lo(rh)), 0);
      __syncwarp();
      bar_arrive(2, 288);
    }
    asm volatile("setmaxnreg.inc.sync.aligned.u32 224;");
    asm volatile("barrier.cluster.wait.aligned;" ::: "memory");
    const int wg = warp >> 2, w = warp & 3, g = lane >> 2, t = lane & 3, wtid = tid & 127;
    const bool elect = wtid == 0;
    const uint64_t da0 = make_desc(sb + wg * 8192, 8192, 1024, 1);
    const uint32_t swz = ((lane >> 4) * 8 + (lane & 7)) * 128 + (((2 * w + ((lane >> 3) & 1)) ^ (lane & 7)) << 4);
    const uint32_t stg = sb + (wg ? SM_ST1 : SM_DED), ka0 = (8 * w + g + t + 1) * 4;
    uint32_t a[64];
    {
      auto mainloop = [&](auto&& mma) {
        Ring r{0, 0};
        uint32_t rel = 0;
#pragma unroll 1
        for (int kb = 0; kb < G1_KB; kb++, r.next()) {
          if (kb == G1_KB - G1_TAIL && wg) {
            wg_wait<0>();
            if (elect) mbar_arrive(rel);
            rel = 0;
            {
              mbar_wait(sb + B_MISC, 0);
              conv_lda_all(a, sb + SM_CV + 16384 + CV_K + ka0);
            }
            bar_sync(5, 256);
          }
          mbar_wait(sb + B_FULL + 8 * r.s, r.ph);
          if (kb == 0 && warp == 0) TLREC(3);
          wg_fence();
          mma(r.s * (SLOT >> 4), kb);
          wg_commit();
          if (kb == G1_KB - 1) break;
          wg_wait<1>();
          if (elect && rel) mbar_arrive(rel);
          rel = sb + B_EMPTY + 8 * r.s;
        }
        bar_arrive(5, 256);
        wg_wait<0>();
      };
      float hb[4];
      auto staged = [&](int second) {
        if (!w) TLREC(4 + wg);
        if (lane == 0) mbar_arrive(sb + B_G1DONE);
        mbar_wait(sb + B_MISC, 0);
#pragma unroll
        for (int i = 0; i < 4; i++) hb[i] = 0.5f * bf_lo(lds16(sb + SM_B1 + (warp * 16 + g + (i & 1) * 8 + (i >> 1) * second) * 2));
        mbar_wait(sb + B_KVDONE, 0);
        if (wg) mbar_wait(sb + B_G1DONE, 0);
      };
      if (R.at != 15) {
        const uint64_t db0 = make_desc(sb + 16384, 4096, 512, 2);
        float acc[80];
        mainloop([&](uint32_t o, int kb) {
#pragma unroll
          for (int k = 0; k < 4; k++) wgmma_ss_n160_t11(acc, da0 + o + k * 128, db0 + o + k * 64, k ? 1 : kb);
        });
        pin_regs<80>(acc);
        staged(0);
        gelu_stage<40>(acc, hb, stg + swz, 2, lane ? 0 : sb + B_STG + 8 * wg + 16);
      } else {
        const uint64_t db0 = make_desc(sb + 24576, 4096, 512, 2);
        float acc[96];
        auto block = [&](float* d, uint64_t da, uint64_t db, int kb) {
#pragma unroll
          for (int k = 0; k < 4; k++) wgmma_ss_n96_t11(d, da + k * 128, db + k * 64, k ? 1 : kb);
        };
        if (wg) mainloop([&](uint32_t o, int kb) { block(acc, da0 + o, db0 + o, kb); block(acc + 48, da0 + o + 512, db0 + o, kb); });
        else mainloop([&](uint32_t o, int kb) { block(acc, da0 + o, db0 + o, kb); });
        pin_regs<96>(acc);
        staged(64);
        gelu_stage<48>(acc, hb, stg + swz, 1 + wg, lane ? 0 : sb + B_STG + 8 * wg + 16);
      }
      __syncwarp();
      if (lane == 0) mbar_arrive(sb + B_STG + 8 * wg);
    }
    {
      if (!wg) conv_lda_all(a, sb + SM_CV + 16384 + wg * CV_K + ka0);
#pragma unroll 1
      for (int i = wg; i < R.ncv; i += 2) {
        const bool more = i + 2 < R.ncv;
        const uint32_t dd = lds16(sb + SM_D + (R.ch + i) * 2);
        a[0] = badd2(a[0], ka0 == 32 ? dd : 0); a[2] = badd2(a[2], ka0 == 16 ? dd : 0);
        float acc[128];
        mbar_wait(sb + B_UFULL + 8 * (i & 3), (i >> 2) & 1);
        bar_sync(5 + wg, 256);
        const bool last = i + 1 == R.ncv;
        if (last && elect) mbar_arrive(sb + B_EMPTY);
        if (!w && i < 4) TLREC(22 + i);
        wg_fence();
        conv_mma(acc, a, make_desc(sb + cv_in(i), 4096, 128, 0));
        wg_commit();
        if (!last) bar_arrive(5 + (wg ^ 1), 256);
        if (more) {
          mbar_wait(sb + B_SFREE + 8 * wg, (i >> 1) & 1);
          mbar_wait(sb + B_KFULL + 8 * ((i + 2) & 3), ((i + 2) >> 2) & 1);
        } else if (last) mbar_wait(sb + B_PDONE, 0);
        wg_wait<0>();
        pin_regs<128>(acc);
        if (lane == 0) mbar_arrive(sb + B_CEMPTY + 8 * (i & 3));
        if (last && elect) mbar_arrive(sb + B_EMPTY + 8);
        const uint32_t red = sb + cv_red(i, R.ncv), ka = sb + cv_taps(i + 2) + ka0;
        if (lane < 8 * w) sts32(red + w * CV_REDW + lane * 4, 0);
        const uint32_t wr = red + w * CV_REDW + (8 * (3 - t + w) + g) * 4;
        if (more) conv_drain<true>(acc, wr, a, ka); else conv_drain<false>(acc, wr, a, ka);
        __syncwarp();
        if (lane == 0) mbar_arrive(sb + B_STG + 8 * wg + (more ? 0 : 16));
      }
      if (!w) TLREC(20 + wg);
    }
    if (R.sg >= 0) {
      const int srow = R.sg * 64 + warp * 16;
      const uint64_t db0 = make_desc(sb + 16384, 16, 1024, 1);
      const uint32_t xo = sb + SM_CV + warp * 2304, xa = xo + (lane & 15) * 144;
      float acc[72];
      Ring r{G1_KB % NSTAGE, (G1_KB / NSTAGE) & 1};
      bar_sync(8, 256);
      uint32_t rel = 0;
#pragma unroll 1
      for (int kb = 0; kb < G2_KB; kb++, r.next()) {
        if (kb == G2_KB - G2_TAIL && wg) {
          wg_wait<0>();
          if (elect) mbar_arrive_remote(rel);
          rel = 0;
          bar_sync(7, 256);
        }
        mbar_wait(sb + B_FULL + 8 * r.s, r.ph);
        if (kb == 0 && !w) TLREC(17 + wg);
        if (kb == 8 && warp == 0) TLREC(26);
        if (kb == 20 && warp == 0) TLREC(8);
        if (kb == 27 && warp == 0) TLREC(30);
        const uint64_t da = da0 + r.s * (SLOT >> 4), db = db0 + r.s * (SLOT >> 4);
        wg_fence();
        wgmma_ss_n144_t10(acc, da, db, kb);
#pragma unroll
        for (int k = 1; k < 4; k++) wgmma_ss_n144_t10(acc, da + k * 128, db + k * 2, 1);
        wg_commit();
        if (kb == G2_KB - 1) break;
        wg_wait<1>();
        if (elect && rel) mbar_arrive_remote(rel);
        rel = kb == G2_KB - NSTAGE ? mapa(sb + B_XRDY, rank ^ 1) : sb + B_EMPTY + 8 * r.s;
      }
      if (!wg) bar_arrive(7, 256);
      const uint32_t xz = sb + XSLOT * SLOT + wg * 10240 + wtid * 16;
      const uint32_t rz = mapa(xz, rank ^ 1), rb = mapa(sb + B_XFULL + 16 * wg, rank ^ 1);
      mbar_wait(sb + B_XRDY, 0);
      wg_wait<0>();
      pin_regs<72>(acc);
      if (!w) TLREC(28 + wg);
#pragma unroll
      for (int i = 0; i < 32; i += 8)
        asm volatile("st.async.weak.shared::cluster.mbarrier::complete_tx::bytes.v4.b32 [%0], {%1,%2,%3,%4}, [%5];"
                     :: "r"(rz + i * 256), "r"(pack_bf16(acc[i], acc[i + 1])), "r"(pack_bf16(acc[i + 2], acc[i + 3])),
                        "r"(pack_bf16(acc[i + 4], acc[i + 5])), "r"(pack_bf16(acc[i + 6], acc[i + 7])), "r"(rb + (i < 8 * XP ? 0 : 8)) : "memory");
      asm volatile("st.async.weak.shared::cluster.mbarrier::complete_tx::bytes.v2.b32 [%0], {%1,%2}, [%3];"
                   :: "r"(rz + 8192), "r"(pack_bf16(acc[32], acc[33])), "r"(pack_bf16(acc[34], acc[35])), "r"(rb + 8) : "memory");
      uint32_t xx[18], ss[18];
      mbar_wait(sb + B_XY, 0);
      {
        const uint32_t ya = sb + SM_DED + wg * 9216 + swz;
        const uint4 st0 = lds128(sb + SM_ST + (warp * 16 + g) * 16), st1 = lds128(sb + SM_ST + (warp * 16 + g + 8) * 16);
        const float hb0 = 0.5f * bf_lo(lds16(sb + SM_B2 + (warp * 16 + g) * 2)), hb1 = 0.5f * bf_lo(lds16(sb + SM_B2 + (warp * 16 + g + 8) * 2));
#pragma unroll
        for (int q = 0; q < 8; q += 2) { ldsm4(xx + 2 * q, xa + (lane >> 4) * 16 + q * 16); ldsm4t(ss + 2 * q, ya + q * 1024); }
        ldsm2(xx + 16, xa + 128);
        ldsm2t(ss + 16, ya + 8 * 1024);
#pragma unroll
        for (int i = 0; i < 18; i++) {
          const uint4& st = (i & 1) ? st1 : st0;
          const uint32_t c = bsub2(xx[i], st.x);
          ss[i] = bmul2(bfma2(c, st.y, bmul2(c, st.z)), ss[i]);
        }
#pragma unroll
        for (int i = 36; i < 72; i++) acc[i] = fmaf(acc[i], 0.5f, (i & 2) ? hb1 : hb0);
      }
      char* const op = reinterpret_cast<char*>(P.out) + srow * (D_ * 2) + R.dk * 16 + lane * 16;
      uint32_t oo[5];
#pragma unroll
      for (int j = 0; j < 5; j++) oo[j] = ((lane + 32 * j) * 57 >> 9) * (D_ * 2 - 144) + j * 512;
      uint32_t pv[20];
#pragma unroll
      for (int pc = 0; pc < 2; pc++) {
        const int q0 = pc ? XP : 0, q1 = pc ? 5 : XP;
        mbar_wait_cluster(sb + B_XFULL + 16 * wg + 8 * pc, 0);
        if (!w && !pc) TLREC(9 + wg);
#pragma unroll
        for (int q = q0; q < q1; q++) { const uint4 v = lds128(xz + q * 2048); pv[4 * q] = v.x; pv[4 * q + 1] = v.y; pv[4 * q + 2] = v.z; pv[4 * q + 3] = v.w; }
#pragma unroll
        for (int i = 4 * q0; i < 4 * q1 && i < 18; i++)
          xx[i] = bfma2(ss[i], pack_bf16(silu_half(fmaf(bf_lo(pv[i]), 0.5f, acc[36 + 2 * i])), silu_half(fmaf(bf_hi(pv[i]), 0.5f, acc[37 + 2 * i]))), xx[i]);
      }
#pragma unroll
      for (int q = 0; q < 4; q++) stsm4(xa + (lane >> 4) * 16 + q * 32, xx[4 * q], xx[4 * q + 1], xx[4 * q + 2], xx[4 * q + 3]);
      stsm2(xa + 128, xx[16], xx[17]);
      __syncwarp();
      if (lane == 0) mbar_arrive(sb + B_DONE);
#pragma unroll
      for (int j = 0; j < 5; j++)
        if (j < 4 || lane < 16) *reinterpret_cast<uint4*>(op + oo[j]) = lds128(xo + (lane + 32 * j) * 16);
      if (!w) TLREC(11 + wg);
    }
    TLEND();
  }
}

typedef CUresult (*EncodeFn)(CUtensorMap*, CUtensorMapDataType, cuuint32_t, void*, const cuuint64_t*, const cuuint64_t*, const cuuint32_t*,
                             const cuuint32_t*, CUtensorMapInterleave, CUtensorMapSwizzle, CUtensorMapL2promotion, CUtensorMapFloatOOBfill);

void make_map(EncodeFn fn, CUtensorMap* m, const void* ptr, int rank, const cuuint64_t* dims, const cuuint64_t* strides, const cuuint32_t* box,
              CUtensorMapSwizzle sw) {
  const cuuint32_t es[3] = {1, 1, 1};
  fn(m, CU_TENSOR_MAP_DATA_TYPE_BFLOAT16, rank, const_cast<void*>(ptr), dims, strides, box, es, CU_TENSOR_MAP_INTERLEAVE_NONE, sw,
     CU_TENSOR_MAP_L2_PROMOTION_L2_256B, CU_TENSOR_MAP_FLOAT_OOB_FILL_NONE);
}

void make_roles(Role* R) {
  int nl = 0, ch = 0;
  for (int gi = 0; gi < 8; gi++)
    for (int b = 0; b < 132; b++) {
      const int c = b >> 1, rank = b & 1;
      int g, idx;
      if (c < 4) { g = 0; idx = 4 + c; }
      else if (c < 36) { g = (c - 4) & 7; idx = (c - 4) >> 3; }
      else if (c < 64) { g = 1 + (c - 36) % 7; idx = 4 + (c - 36) / 7; }
      else { g = c - 58; idx = 8; }
      if (g != gi) continue;
      Role& r = R[b];
      r.sg = (int8_t)(idx < 8 ? 2 * (2 * g + (idx >> 2)) : -1);
      r.dk = (int8_t)((idx & 3) * 18 + rank * 9);
      r.ds = (int8_t)((idx & 3) * 18 + (rank ^ 1) * 9);
      if (idx < (g < 2 ? 6 : 7)) {
        const int c1 = (g < 2 ? 6 * g : 7 * g - 2) + idx;
        r.fg = (int8_t)((2 * (c1 / 3) + rank) * 2); r.at = (int8_t)(c1 % 3 * 5); r.ncv = NCV_REG;
      } else {
        r.fg = (int8_t)(3 * nl++); r.at = 15; r.ncv = idx < 8 ? NCV_LEFT : NCV_LONG;
      }
      r.ch = (int16_t)ch;
      ch += r.ncv;
    }
}

}

extern "C" void kernel_launch(void* const* d_in, const int* in_sizes, int n_in, void* d_out, int out_size) {
  static Params P;
  static Hot H;
  static const void* cached[5] = {nullptr, nullptr, nullptr, nullptr, nullptr};
  const void* now[5] = {d_in[0], d_in[1], d_in[2], d_in[7], d_in[9]};
  bool same = true;
  for (int i = 0; i < 5; i++) { same = same && cached[i] == now[i]; cached[i] = now[i]; }
  if (!same) {
    void* fp = nullptr;
    cudaDriverEntryPointQueryResult qr;
    cudaGetDriverEntryPoint("cuTensorMapEncodeTiled", &fp, cudaEnableDefault, &qr);
    EncodeFn fn = (EncodeFn)fp;
    void* ps;
    cudaGetSymbolAddress(&ps, g_scratch);
    H.S = (Scratch*)ps;
    const void *py = (char*)ps + offsetof(Scratch, y), *pb = (char*)ps + offsetof(Scratch, ub);
    { cuuint64_t d[3] = {64, S_, F_ / 64}, s[2] = {F_ * 2, 128}; cuuint32_t b[3] = {64, 64, 2}; make_map(fn, &P.m_w1, d_in[7], 3, d, s, b, CU_TENSOR_MAP_SWIZZLE_128B);
      b[2] = 3; make_map(fn, &P.m_w1l, d_in[7], 3, d, s, b, CU_TENSOR_MAP_SWIZZLE_128B); }
    { cuuint64_t d[3] = {64, F_, S_ / 64}, s[2] = {S_ * 2, 128}; cuuint32_t b[3] = {64, 64, 2}; make_map(fn, &P.m_w2, d_in[9], 3, d, s, b, CU_TENSOR_MAP_SWIZZLE_128B); }
    { cuuint64_t d[2] = {D_, S_}, s[1] = {D_ * 2}; cuuint32_t b[2] = {72, 16}; make_map(fn, &P.m_x, d_in[0], 2, d, s, b, CU_TENSOR_MAP_SWIZZLE_NONE);
      b[0] = 96; b[1] = 20; make_map(fn, &P.m_k, d_in[1], 2, d, s, b, CU_TENSOR_MAP_SWIZZLE_NONE);
      b[1] = 17; make_map(fn, &P.m_v, d_in[2], 2, d, s, b, CU_TENSOR_MAP_SWIZZLE_NONE); }
    { cuuint64_t d[3] = {64, D_, S_ / 64}, s[2] = {S_ * 2, 128}; cuuint32_t b[3] = {64, 72, 2}; make_map(fn, &P.m_y, py, 3, d, s, b, CU_TENSOR_MAP_SWIZZLE_128B); }
    { cuuint64_t d[3] = {2048, D_ / 2, 4}, s[2] = {16384, 4096}; cuuint32_t b[3] = {16, 48, 2}; make_map(fn, &P.m_ub, pb, 3, d, s, b, CU_TENSOR_MAP_SWIZZLE_32B); }
    make_roles(P.role);
    cudaFuncSetAttribute(fused_kernel, cudaFuncAttributeMaxDynamicSharedMemorySize, SM_TOTAL);
  }
  H.x = (const __nv_bfloat16*)d_in[0];
  H.shift_k = (const __nv_bfloat16*)d_in[3]; H.ssm_k = (const __nv_bfloat16*)d_in[4]; H.ssm_D = (const __nv_bfloat16*)d_in[5];
  H.b1 = (const __nv_bfloat16*)d_in[8]; P.b2 = (const __nv_bfloat16*)d_in[10]; P.out = (__nv_bfloat16*)d_out;
  fused_kernel<<<132, 384, SM_TOTAL>>>(H, P);
}
```

```cpp
#include <cuda_runtime.h>
#include <cuda.h>
#include <cuda_bf16.h>
#include <stddef.h>
#include <stdint.h>

namespace {

constexpr int S_ = 2048, D_ = 576, F_ = 4608;
constexpr int NSTAGE = 5, SLOT = 36864;
constexpr int G1_KB = 32, G2_KB = 36;
constexpr int G1_BYTES = 36864, G2_BYTES = 16384 + 18432;
constexpr int NCV_REG = 4, NCV_LONG = 16;
static_assert(128 * NCV_REG + 4 * NCV_LONG == D_, "conv split");
constexpr int KV_ROUNDS = 6;
#define XP 2
#define TUNED(name, idx, val) constexpr int name = val
constexpr int G1_TAIL = 4, G2_TAIL = 3;

constexpr int CV_K = 4224, CV_REDW = 2112 * 2;
constexpr int SM_DED = NSTAGE * SLOT;
constexpr int SM_CV = SM_DED + 20480;
constexpr int SM_ST1 = 0;
constexpr int SM_ST = SM_CV + 18432, SM_B2 = SM_ST + 2048;
constexpr int SM_B1 = SM_CV + 2 * (8192 + CV_K), SM_D = SM_B1 + 384;
constexpr int SM_BAR = SM_D + 1152;
constexpr int SM_TOTAL = SM_BAR + 768;
static_assert(G1_KB % NSTAGE == 2, "slots 0 and 1 hold the last GEMM1 k-blocks and the last two of the first GEMM2 stages");
static_assert(NCV_REG % 4 == 0 && NCV_LONG % 4 == 0, "the last two channels use buffers 2 and 3");
constexpr int XSLOT = (G1_KB + G2_KB) % NSTAGE;
__device__ __forceinline__ uint32_t kv_buf(int q) { return q == 2 ? SM_DED : SM_CV + q * 8192; }
__device__ __forceinline__ uint32_t cv_red(int i, int n) { return i + 2 == n ? SM_CV : (i & 1) && i + 1 < n ? SLOT + 16384 : SM_DED; }
__device__ __forceinline__ uint32_t cv_in(int i) { return (i & 2 ? SLOT : SM_CV) + (i & 1) * 8192; }
__device__ __forceinline__ uint32_t cv_taps(int i) { return (i & 2 ? SM_ST1 + 24576 : SM_CV + 16384) + (i & 1) * CV_K; }
constexpr int bar_at(int i) { return SM_BAR + 8 * i; }
constexpr int B_FULL = bar_at(0)  , B_KFULL = bar_at(5)  , B_UFULL = bar_at(9)  , B_KVDONE = bar_at(13), B_STORED = bar_at(14)  ,
              B_XFULL = bar_at(16)  , B_XY = bar_at(20), B_MISC = bar_at(21),
              B_EMPTY = bar_at(22)  , B_XRDY = bar_at(27),
              B_SFREE = bar_at(28)  , B_PDONE = bar_at(30),
              B_CEMPTY = bar_at(31)  , B_STG = bar_at(35)  ,
              B_G1DONE = bar_at(39), B_DONE = bar_at(40);
constexpr int C_H = 0, C_KV = 1, C_U = 2  , C_Y = 4, C_SYNC = 5, C_EPOCH = 6, C_COUNT = 7;
constexpr uint32_t EPOCH = 128 * 33;

struct Scratch {
  uint32_t cnt[C_COUNT * 32];
  alignas(1024) uint4 stats[S_];
  alignas(1024) __nv_bfloat16 h[S_ * D_];
  alignas(1024) __nv_bfloat16 ub[D_ * 4096];
  alignas(1024) __nv_bfloat16 y[D_ * S_];
  alignas(1024) __nv_bfloat16 u[D_ * F_];
};
__device__ Scratch g_scratch;

struct Hot {
  const __nv_bfloat16 *x, *shift_k, *ssm_k, *ssm_D, *b1;
  Scratch* S;
};
struct Role {
  int8_t fg;
  int8_t at;
  int8_t sg;
  int8_t dk, ds;
  int8_t ncv;
  int16_t ch;
};
struct Params {
  const __nv_bfloat16* b2;
  __nv_bfloat16* out;
  Role role[132];
  CUtensorMap m_w1, m_w1l, m_w2, m_x, m_y, m_k, m_v, m_ub;
};

#define TLREC(i) do { } while (0)
#define TLEND() do { } while (0)

__device__ __forceinline__ uint32_t smem_u32(const void* p) { return (uint32_t)__cvta_generic_to_shared(p); }
__device__ __forceinline__ void mbar_init(uint32_t bar, uint32_t cnt) { asm volatile("mbarrier.init.shared::cta.b64 [%0], %1;" :: "r"(bar), "r"(cnt) : "memory"); }
__device__ __forceinline__ void mbar_expect_tx(uint32_t bar, uint32_t bytes) { asm volatile("mbarrier.arrive.expect_tx.shared::cta.b64 _, [%0], %1;" :: "r"(bar), "r"(bytes) : "memory"); }
__device__ __forceinline__ void mbar_arrive(uint32_t bar) { asm volatile("mbarrier.arrive.shared::cta.b64 _, [%0];" :: "r"(bar) : "memory"); }
__device__ __forceinline__ uint32_t mapa(uint32_t addr, uint32_t cta) { uint32_t r; asm volatile("mapa.shared::cluster.u32 %0, %1, %2;" : "=r"(r) : "r"(addr), "r"(cta)); return r; }
__device__ __forceinline__ void mbar_arrive_remote(uint32_t rbar) { asm volatile("mbarrier.arrive.shared::cluster.b64 _, [%0];" :: "r"(rbar) : "memory"); }
__device__ __forceinline__ uint32_t clk() { uint32_t c; asm volatile("mov.u32 %0, %%clock;" : "=r"(c)); return c; }
__device__ __forceinline__ bool elect_one() {
  uint32_t p; asm volatile("{ .reg .pred p; elect.sync _|p, 0xffffffff; selp.u32 %0, 1, 0, p; }" : "=r"(p)); return p;
}
__device__ __forceinline__ void guard(uint32_t t0) { if ((int32_t)(clk() - t0) < 0) __trap(); }
__device__ __forceinline__ void mbar_wait(uint32_t bar, uint32_t parity) {
  asm volatile("{\n .reg .pred p;\n W_%=:\n mbarrier.try_wait.parity.shared::cta.b64 p, [%0], %1;\n @!p bra W_%=;\n }" :: "r"(bar), "r"(parity) : "memory");
}
__device__ __forceinline__ void mbar_wait_cluster(uint32_t bar, uint32_t parity) {
  asm volatile("{\n .reg .pred p;\n W_%=:\n mbarrier.try_wait.parity.acquire.cluster.shared::cta.b64 p, [%0], %1;\n @!p bra W_%=;\n }" :: "r"(bar), "r"(parity) : "memory");
}
__device__ __forceinline__ bool mbar_try(uint32_t bar, uint32_t parity) {
  uint32_t ok;
  asm volatile("{ .reg .pred p; mbarrier.try_wait.parity.shared::cta.b64 p, [%1], %2, 100000; selp.u32 %0, 1, 0, p; }" : "=r"(ok) : "r"(bar), "r"(parity) : "memory");
  return ok;
}
__device__ __forceinline__ bool mbar_test(uint32_t bar, uint32_t parity) {
  uint32_t ok;
  asm volatile("{ .reg .pred p; mbarrier.test_wait.parity.shared::cta.b64 p, [%1], %2; selp.u32 %0, 1, 0, p; }" : "=r"(ok) : "r"(bar), "r"(parity) : "memory");
  return ok;
}
__device__ __forceinline__ void mbar_wait_guarded(uint32_t bar, uint32_t t0, uint32_t parity = 0) { while (!mbar_try(bar, parity)) guard(t0); }
__device__ __forceinline__ void tma2d(uint32_t dst, const CUtensorMap* m, int c0, int c1, uint32_t bar) {
  asm volatile("cp.async.bulk.tensor.2d.shared::cluster.global.mbarrier::complete_tx::bytes [%0], [%1, {%3, %4}], [%2];"
               :: "r"(dst), "l"(m), "r"(bar), "r"(c0), "r"(c1) : "memory");
}
__device__ __forceinline__ void tma3d(uint32_t dst, const CUtensorMap* m, int c0, int c1, int c2, uint32_t bar) {
  asm volatile("cp.async.bulk.tensor.3d.shared::cluster.global.mbarrier::complete_tx::bytes [%0], [%1, {%3, %4, %5}], [%2];"
               :: "r"(dst), "l"(m), "r"(bar), "r"(c0), "r"(c1), "r"(c2) : "memory");
}
__device__ __forceinline__ uint64_t evict_first() { uint64_t p; asm("createpolicy.fractional.L2::evict_first.b64 %0, 1.0;" : "=l"(p)); return p; }
__device__ __forceinline__ void tma3d_ef(uint32_t dst, const CUtensorMap* m, int c0, int c1, int c2, uint32_t bar) {
  asm volatile("cp.async.bulk.tensor.3d.shared::cluster.global.mbarrier::complete_tx::bytes.L2::cache_hint [%0], [%1, {%3, %4, %5}], [%2], %6;"
               :: "r"(dst), "l"(m), "r"(bar), "r"(c0), "r"(c1), "r"(c2), "l"(evict_first()) : "memory");
}
__device__ __forceinline__ void bulk_load_ef(uint32_t dst, const void* src, uint32_t bytes, uint32_t bar) {
  asm volatile("cp.async.bulk.shared::cluster.global.mbarrier::complete_tx::bytes.L2::cache_hint [%0], [%1], %2, [%3], %4;"
               :: "r"(dst), "l"(src), "r"(bytes), "r"(bar), "l"(evict_first()) : "memory");
}
__device__ __forceinline__ void bulk_store(void* dst, uint32_t src, uint32_t bytes) {
  asm volatile("cp.async.bulk.global.shared::cta.bulk_group [%0], [%1], %2;" :: "l"(dst), "r"(src), "r"(bytes) : "memory");
}
__device__ __forceinline__ void bulk_load(uint32_t dst, const void* src, uint32_t bytes, uint32_t bar) {
  asm volatile("cp.async.bulk.shared::cluster.global.mbarrier::complete_tx::bytes [%0], [%1], %2, [%3];" :: "r"(dst), "l"(src), "r"(bytes), "r"(bar) : "memory");
}
__device__ __forceinline__ void tma3d_store(const CUtensorMap* m, uint32_t src, int c0, int c1, int c2) {
  asm volatile("cp.async.bulk.tensor.3d.global.shared::cta.bulk_group [%0, {%2, %3, %4}], [%1];" :: "l"(m), "r"(src), "r"(c0), "r"(c1), "r"(c2) : "memory");
}
__device__ __forceinline__ void bulk_commit() { asm volatile("cp.async.bulk.commit_group;" ::: "memory"); }
__device__ __forceinline__ void bulk_wait_all() { asm volatile("cp.async.bulk.wait_group 0;" ::: "memory"); }
__device__ __forceinline__ void fence_async_smem() { asm volatile("fence.proxy.async.shared::cta;" ::: "memory"); }
__device__ __forceinline__ void fence_async_global() { asm volatile("fence.proxy.async.global;" ::: "memory"); }
__device__ __forceinline__ uint32_t ld_cnt(Scratch* S, int c) { uint32_t v; asm volatile("ld.relaxed.gpu.global.u32 %0, [%1];" : "=r"(v) : "l"(S->cnt + c * 32) : "memory"); return v; }
__device__ __forceinline__ void signal(Scratch* S, int c, uint32_t inc) { asm volatile("red.release.gpu.global.add.u32 [%0], %1;" :: "l"(S->cnt + c * 32), "r"(inc) : "memory"); }
__device__ __forceinline__ bool reached(Scratch* S, int c, uint32_t ep) { return ld_cnt(S, c) - ep >= EPOCH; }
__device__ __forceinline__ void await(Scratch* S, int c, uint32_t ep) { while (!reached(S, c, ep)) { } }
__device__ __forceinline__ void bar_sync(int id, int n) { asm volatile("bar.sync %0, %1;" :: "r"(id), "r"(n) : "memory"); }
__device__ __forceinline__ void bar_arrive(int id, int n) { asm volatile("bar.arrive %0, %1;" :: "r"(id), "r"(n) : "memory"); }
__device__ __forceinline__ void wg_fence() { asm volatile("wgmma.fence.sync.aligned;" ::: "memory"); }
__device__ __forceinline__ void wg_commit() { asm volatile("wgmma.commit_group.sync.aligned;" ::: "memory"); }
template <int N> __device__ __forceinline__ void wg_wait() { asm volatile("wgmma.wait_group.sync.aligned %0;" :: "n"(N) : "memory"); }
template <int N> __device__ __forceinline__ void pin_regs(float* a) {
#pragma unroll
  for (int i = 0; i < N; i++) asm volatile("" : "+f"(a[i]) :: "memory");
}
__device__ __forceinline__ uint64_t make_desc(uint32_t addr, uint32_t lbo, uint32_t sbo, uint32_t swz) {
  return (uint64_t)((addr & 0x3FFFF) >> 4) | ((uint64_t)(lbo >> 4) << 16) | ((uint64_t)(sbo >> 4) << 32) | ((uint64_t)swz << 62);
}
__device__ __forceinline__ uint32_t pack_bf16(float lo, float hi) { uint32_t r; asm("cvt.rn.bf16x2.f32 %0, %1, %2;" : "=r"(r) : "f"(hi), "f"(lo)); return r; }
__device__ __forceinline__ float bf_lo(uint32_t p) { return __uint_as_float(p << 16); }
__device__ __forceinline__ float bf_hi(uint32_t p) { return __uint_as_float(p & 0xffff0000u); }
__device__ __forceinline__ float round_bf16(float v) { return bf_lo(pack_bf16(v, 0.f)); }
__device__ __forceinline__ uint32_t bmul2(uint32_t a, uint32_t b) { uint32_t r; asm("mul.rn.bf16x2 %0, %1, %2;" : "=r"(r) : "r"(a), "r"(b)); return r; }
__device__ __forceinline__ uint32_t badd2(uint32_t a, uint32_t b) { uint32_t r; asm("add.rn.bf16x2 %0, %1, %2;" : "=r"(r) : "r"(a), "r"(b)); return r; }
__device__ __forceinline__ uint32_t bfma2(uint32_t a, uint32_t b, uint32_t c) { uint32_t r; asm("fma.rn.bf16x2 %0, %1, %2, %3;" : "=r"(r) : "r"(a), "r"(b), "r"(c)); return r; }
__device__ __forceinline__ uint32_t bsub2(uint32_t a, uint32_t b) { uint32_t r; asm("sub.rn.bf16x2 %0, %1, %2;" : "=r"(r) : "r"(a), "r"(b)); return r; }
__device__ __forceinline__ float tanh_fast(float v) { float r; asm("tanh.approx.f32 %0, %1;" : "=f"(r) : "f"(v)); return r; }
__device__ __forceinline__ float gelu_half(float h) {
  return fmaf(h, tanh_fast(h * fmaf(h * h, 8.0f * 0.7978845608028654f * 0.044715f, 2.0f * 0.7978845608028654f)), h);
}
__device__ __forceinline__ float silu_half(float h) { return fmaf(h, tanh_fast(h), h); }
__device__ __forceinline__ uint32_t ldg32(const void* p) { uint32_t v; asm volatile("ld.global.u32 %0, [%1];" : "=r"(v) : "l"(p) : "memory"); return v; }
__device__ __forceinline__ uint32_t lds32(uint32_t a) { uint32_t v; asm volatile("ld.shared.u32 %0, [%1];" : "=r"(v) : "r"(a) : "memory"); return v; }
__device__ __forceinline__ uint32_t lds16(uint32_t a) { uint32_t v; asm volatile("ld.shared.u16 %0, [%1];" : "=r"(v) : "r"(a) : "memory"); return v; }
__device__ __forceinline__ uint4 lds128(uint32_t a) { uint4 v; asm volatile("ld.shared.v4.u32 {%0,%1,%2,%3}, [%4];" : "=r"(v.x), "=r"(v.y), "=r"(v.z), "=r"(v.w) : "r"(a) : "memory"); return v; }
__device__ __forceinline__ void sts128(uint32_t a, uint32_t x, uint32_t y, uint32_t z, uint32_t w) {
  asm volatile("st.shared.v4.u32 [%0], {%1,%2,%3,%4};" :: "r"(a), "r"(x), "r"(y), "r"(z), "r"(w) : "memory");
}
__device__ __forceinline__ void sts32(uint32_t a, uint32_t v) { asm volatile("st.shared.u32 [%0], %1;" :: "r"(a), "r"(v) : "memory"); }
__device__ __forceinline__ void ldsm4(uint32_t* r, uint32_t a) {
  asm volatile("ldmatrix.sync.aligned.m8n8.x4.shared.b16 {%0,%1,%2,%3}, [%4];" : "=r"(r[0]), "=r"(r[1]), "=r"(r[2]), "=r"(r[3]) : "r"(a) : "memory");
}
__device__ __forceinline__ void ldsm2(uint32_t* r, uint32_t a) {
  asm volatile("ldmatrix.sync.aligned.m8n8.x2.shared.b16 {%0,%1}, [%2];" : "=r"(r[0]), "=r"(r[1]) : "r"(a) : "memory");
}
__device__ __forceinline__ void ldsm4t(uint32_t* r, uint32_t a) {
  asm volatile("ldmatrix.sync.aligned.m8n8.x4.trans.shared.b16 {%0,%1,%2,%3}, [%4];" : "=r"(r[0]), "=r"(r[1]), "=r"(r[2]), "=r"(r[3]) : "r"(a) : "memory");
}
__device__ __forceinline__ void ldsm2t(uint32_t* r, uint32_t a) {
  asm volatile("ldmatrix.sync.aligned.m8n8.x2.trans.shared.b16 {%0,%1}, [%2];" : "=r"(r[0]), "=r"(r[1]) : "r"(a) : "memory");
}
__device__ __forceinline__ void stsm4(uint32_t a, uint32_t r0, uint32_t r1, uint32_t r2, uint32_t r3) {
  asm volatile("stmatrix.sync.aligned.m8n8.x4.shared.b16 [%0], {%1,%2,%3,%4};" :: "r"(a), "r"(r0), "r"(r1), "r"(r2), "r"(r3) : "memory");
}
__device__ __forceinline__ void stsm2(uint32_t a, uint32_t r0, uint32_t r1) {
  asm volatile("stmatrix.sync.aligned.m8n8.x2.shared.b16 [%0], {%1,%2};" :: "r"(a), "r"(r0), "r"(r1) : "memory");
}
__device__ __forceinline__ void stsm4t(uint32_t a, uint32_t r0, uint32_t r1, uint32_t r2, uint32_t r3) {
  asm volatile("stmatrix.sync.aligned.m8n8.x4.trans.shared.b16 [%0], {%1,%2,%3,%4};" :: "r"(a), "r"(r0), "r"(r1), "r"(r2), "r"(r3) : "memory");
}

__device__ __forceinline__ void wgmma_ss_n144_t10(float* d, uint64_t da, uint64_t db, int sd) {
  asm volatile("{ .reg .pred p; setp.ne.b32 p, %74, 0;\n"
      "wgmma.mma_async.sync.aligned.m64n144k16.f32.bf16.bf16 {"
      "%0,%1,%2,%3,%4,%5,%6,%7,%8,%9,%10,%11,%12,%13,%14,%15,"
      "%16,%17,%18,%19,%20,%21,%22,%23,%24,%25,%26,%27,%28,%29,%30,%31,"
      "%32,%33,%34,%35,%36,%37,%38,%39,%40,%41,%42,%43,%44,%45,%46,%47,"
      "%48,%49,%50,%51,%52,%53,%54,%55,%56,%57,%58,%59,%60,%61,%62,%63,"
      "%64,%65,%66,%67,%68,%69,%70,%71"
      "}, %72, %73, p, 1, 1, 1, 0; }"
    : "+f"(d[0]), "+f"(d[1]), "+f"(d[2]), "+f"(d[3]), "+f"(d[4]), "+f"(d[5]), "+f"(d[6]), "+f"(d[7]),
      "+f"(d[8]), "+f"(d[9]), "+f"(d[10]), "+f"(d[11]), "+f"(d[12]), "+f"(d[13]), "+f"(d[14]), "+f"(d[15]),
      "+f"(d[16]), "+f"(d[17]), "+f"(d[18]), "+f"(d[19]), "+f"(d[20]), "+f"(d[21]), "+f"(d[22]), "+f"(d[23]),
      "+f"(d[24]), "+f"(d[25]), "+f"(d[26]), "+f"(d[27]), "+f"(d[28]), "+f"(d[29]), "+f"(d[30]), "+f"(d[31]),
      "+f"(d[32]), "+f"(d[33]), "+f"(d[34]), "+f"(d[35]), "+f"(d[36]), "+f"(d[37]), "+f"(d[38]), "+f"(d[39]),
      "+f"(d[40]), "+f"(d[41]), "+f"(d[42]), "+f"(d[43]), "+f"(d[44]), "+f"(d[45]), "+f"(d[46]), "+f"(d[47]),
      "+f"(d[48]), "+f"(d[49]), "+f"(d[50]), "+f"(d[51]), "+f"(d[52]), "+f"(d[53]), "+f"(d[54]), "+f"(d[55]),
      "+f"(d[56]), "+f"(d[57]), "+f"(d[58]), "+f"(d[59]), "+f"(d[60]), "+f"(d[61]), "+f"(d[62]), "+f"(d[63]),
      "+f"(d[64]), "+f"(d[65]), "+f"(d[66]), "+f"(d[67]), "+f"(d[68]), "+f"(d[69]), "+f"(d[70]), "+f"(d[71])
    : "l"(da), "l"(db), "r"(sd));
}

__device__ __forceinline__ void wgmma_ss_n160_t11(float* d, uint64_t da, uint64_t db, int sd) {
  asm volatile("{ .reg .pred p; setp.ne.b32 p, %82, 0;\n"
      "wgmma.mma_async.sync.aligned.m64n160k16.f32.bf16.bf16 {"
      "%0,%1,%2,%3,%4,%5,%6,%7,%8,%9,%10,%11,%12,%13,%14,%15,"
      "%16,%17,%18,%19,%20,%21,%22,%23,%24,%25,%26,%27,%28,%29,%30,%31,"
      "%32,%33,%34,%35,%36,%37,%38,%39,%40,%41,%42,%43,%44,%45,%46,%47,"
      "%48,%49,%50,%51,%52,%53,%54,%55,%56,%57,%58,%59,%60,%61,%62,%63,"
      "%64,%65,%66,%67,%68,%69,%70,%71,%72,%73,%74,%75,%76,%77,%78,%79"
      "}, %80, %81, p, 1, 1, 1, 1; }"
    : "+f"(d[0]), "+f"(d[1]), "+f"(d[2]), "+f"(d[3]), "+f"(d[4]), "+f"(d[5]), "+f"(d[6]), "+f"(d[7]),
      "+f"(d[8]), "+f"(d[9]), "+f"(d[10]), "+f"(d[11]), "+f"(d[12]), "+f"(d[13]), "+f"(d[14]), "+f"(d[15]),
      "+f"(d[16]), "+f"(d[17]), "+f"(d[18]), "+f"(d[19]), "+f"(d[20]), "+f"(d[21]), "+f"(d[22]), "+f"(d[23]),
      "+f"(d[24]), "+f"(d[25]), "+f"(d[26]), "+f"(d[27]), "+f"(d[28]), "+f"(d[29]), "+f"(d[30]), "+f"(d[31]),
      "+f"(d[32]), "+f"(d[33]), "+f"(d[34]), "+f"(d[35]), "+f"(d[36]), "+f"(d[37]), "+f"(d[38]), "+f"(d[39]),
      "+f"(d[40]), "+f"(d[41]), "+f"(d[42]), "+f"(d[43]), "+f"(d[44]), "+f"(d[45]), "+f"(d[46]), "+f"(d[47]),
      "+f"(d[48]), "+f"(d[49]), "+f"(d[50]), "+f"(d[51]), "+f"(d[52]), "+f"(d[53]), "+f"(d[54]), "+f"(d[55]),
      "+f"(d[56]), "+f"(d[57]), "+f"(d[58]), "+f"(d[59]), "+f"(d[60]), "+f"(d[61]), "+f"(d[62]), "+f"(d[63]),
      "+f"(d[64]), "+f"(d[65]), "+f"(d[66]), "+f"(d[67]), "+f"(d[68]), "+f"(d[69]), "+f"(d[70]), "+f"(d[71]),
      "+f"(d[72]), "+f"(d[73]), "+f"(d[74]), "+f"(d[75]), "+f"(d[76]), "+f"(d[77]), "+f"(d[78]), "+f"(d[79])
    : "l"(da), "l"(db), "r"(sd));
}

__device__ __forceinline__ void wgmma_ss_n96_t11(float* d, uint64_t da, uint64_t db, int sd) {
  asm volatile("{ .reg .pred p; setp.ne.b32 p, %50, 0;\n"
      "wgmma.mma_async.sync.aligned.m64n96k16.f32.bf16.bf16 {"
      "%0,%1,%2,%3,%4,%5,%6,%7,%8,%9,%10,%11,%12,%13,%14,%15,"
      "%16,%17,%18,%19,%20,%21,%22,%23,%24,%25,%26,%27,%28,%29,%30,%31,"
      "%32,%33,%34,%35,%36,%37,%38,%39,%40,%41,%42,%43,%44,%45,%46,%47"
      "}, %48, %49, p, 1, 1, 1, 1; }"
    : "+f"(d[0]), "+f"(d[1]), "+f"(d[2]), "+f"(d[3]), "+f"(d[4]), "+f"(d[5]), "+f"(d[6]), "+f"(d[7]),
      "+f"(d[8]), "+f"(d[9]), "+f"(d[10]), "+f"(d[11]), "+f"(d[12]), "+f"(d[13]), "+f"(d[14]), "+f"(d[15]),
      "+f"(d[16]), "+f"(d[17]), "+f"(d[18]), "+f"(d[19]), "+f"(d[20]), "+f"(d[21]), "+f"(d[22]), "+f"(d[23]),
      "+f"(d[24]), "+f"(d[25]), "+f"(d[26]), "+f"(d[27]), "+f"(d[28]), "+f"(d[29]), "+f"(d[30]), "+f"(d[31]),
      "+f"(d[32]), "+f"(d[33]), "+f"(d[34]), "+f"(d[35]), "+f"(d[36]), "+f"(d[37]), "+f"(d[38]), "+f"(d[39]),
      "+f"(d[40]), "+f"(d[41]), "+f"(d[42]), "+f"(d[43]), "+f"(d[44]), "+f"(d[45]), "+f"(d[46]), "+f"(d[47])
    : "l"(da), "l"(db), "r"(sd));
}

__device__ __forceinline__ void wgmma_rs_n16(float* d, const uint32_t* a, uint64_t db, int sd) {
  asm volatile("{ .reg .pred p; setp.ne.b32 p, %13, 0;\n"
      "wgmma.mma_async.sync.aligned.m64n16k16.f32.bf16.bf16 {"
      "%0,%1,%2,%3,%4,%5,%6,%7"
      "}, {%8,%9,%10,%11}, %12, p, 1, 1, 0; }"
    : "+f"(d[0]), "+f"(d[1]), "+f"(d[2]), "+f"(d[3]), "+f"(d[4]), "+f"(d[5]), "+f"(d[6]), "+f"(d[7])
    : "r"(a[0]), "r"(a[1]), "r"(a[2]), "r"(a[3]), "l"(db), "r"(sd));
}

__device__ __forceinline__ void wgmma_rs_n32(float* d, const uint32_t* a, uint64_t db, int sd) {
  asm volatile("{ .reg .pred p; setp.ne.b32 p, %21, 0;\n"
      "wgmma.mma_async.sync.aligned.m64n32k16.f32.bf16.bf16 {"
      "%0,%1,%2,%3,%4,%5,%6,%7,%8,%9,%10,%11,%12,%13,%14,%15"
      "}, {%16,%17,%18,%19}, %20, p, 1, 1, 0; }"
    : "+f"(d[0]), "+f"(d[1]), "+f"(d[2]), "+f"(d[3]), "+f"(d[4]), "+f"(d[5]), "+f"(d[6]), "+f"(d[7]),
      "+f"(d[8]), "+f"(d[9]), "+f"(d[10]), "+f"(d[11]), "+f"(d[12]), "+f"(d[13]), "+f"(d[14]), "+f"(d[15])
    : "r"(a[0]), "r"(a[1]), "r"(a[2]), "r"(a[3]), "l"(db), "r"(sd));
}

__device__ __forceinline__ void wgmma_rs_n48(float* d, const uint32_t* a, uint64_t db, int sd) {
  asm volatile("{ .reg .pred p; setp.ne.b32 p, %29, 0;\n"
      "wgmma.mma_async.sync.aligned.m64n48k16.f32.bf16.bf16 {"
      "%0,%1,%2,%3,%4,%5,%6,%7,%8,%9,%10,%11,%12,%13,%14,%15,"
      "%16,%17,%18,%19,%20,%21,%22,%23"
      "}, {%24,%25,%26,%27}, %28, p, 1, 1, 0; }"
    : "+f"(d[0]), "+f"(d[1]), "+f"(d[2]), "+f"(d[3]), "+f"(d[4]), "+f"(d[5]), "+f"(d[6]), "+f"(d[7]),
      "+f"(d[8]), "+f"(d[9]), "+f"(d[10]), "+f"(d[11]), "+f"(d[12]), "+f"(d[13]), "+f"(d[14]), "+f"(d[15]),
      "+f"(d[16]), "+f"(d[17]), "+f"(d[18]), "+f"(d[19]), "+f"(d[20]), "+f"(d[21]), "+f"(d[22]), "+f"(d[23])
    : "r"(a[0]), "r"(a[1]), "r"(a[2]), "r"(a[3]), "l"(db), "r"(sd));
}

__device__ __forceinline__ void wgmma_rs_n64(float* d, const uint32_t* a, uint64_t db, int sd) {
  asm volatile("{ .reg .pred p; setp.ne.b32 p, %37, 0;\n"
      "wgmma.mma_async.sync.aligned.m64n64k16.f32.bf16.bf16 {"
      "%0,%1,%2,%3,%4,%5,%6,%7,%8,%9,%10,%11,%12,%13,%14,%15,"
      "%16,%17,%18,%19,%20,%21,%22,%23,%24,%25,%26,%27,%28,%29,%30,%31"
      "}, {%32,%33,%34,%35}, %36, p, 1, 1, 0; }"
    : "+f"(d[0]), "+f"(d[1]), "+f"(d[2]), "+f"(d[3]), "+f"(d[4]), "+f"(d[5]), "+f"(d[6]), "+f"(d[7]),
      "+f"(d[8]), "+f"(d[9]), "+f"(d[10]), "+f"(d[11]), "+f"(d[12]), "+f"(d[13]), "+f"(d[14]), "+f"(d[15]),
      "+f"(d[16]), "+f"(d[17]), "+f"(d[18]), "+f"(d[19]), "+f"(d[20]), "+f"(d[21]), "+f"(d[22]), "+f"(d[23]),
      "+f"(d[24]), "+f"(d[25]), "+f"(d[26]), "+f"(d[27]), "+f"(d[28]), "+f"(d[29]), "+f"(d[30]), "+f"(d[31])
    : "r"(a[0]), "r"(a[1]), "r"(a[2]), "r"(a[3]), "l"(db), "r"(sd));
}

__device__ __forceinline__ void wgmma_rs_n80(float* d, const uint32_t* a, uint64_t db, int sd) {
  asm volatile("{ .reg .pred p; setp.ne.b32 p, %45, 0;\n"
      "wgmma.mma_async.sync.aligned.m64n80k16.f32.bf16.bf16 {"
      "%0,%1,%2,%3,%4,%5,%6,%7,%8,%9,%10,%11,%12,%13,%14,%15,"
      "%16,%17,%18,%19,%20,%21,%22,%23,%24,%25,%26,%27,%28,%29,%30,%31,"
      "%32,%33,%34,%35,%36,%37,%38,%39"
      "}, {%40,%41,%42,%43}, %44, p, 1, 1, 0; }"
    : "+f"(d[0]), "+f"(d[1]), "+f"(d[2]), "+f"(d[3]), "+f"(d[4]), "+f"(d[5]), "+f"(d[6]), "+f"(d[7]),
      "+f"(d[8]), "+f"(d[9]), "+f"(d[10]), "+f"(d[11]), "+f"(d[12]), "+f"(d[13]), "+f"(d[14]), "+f"(d[15]),
      "+f"(d[16]), "+f"(d[17]), "+f"(d[18]), "+f"(d[19]), "+f"(d[20]), "+f"(d[21]), "+f"(d[22]), "+f"(d[23]),
      "+f"(d[24]), "+f"(d[25]), "+f"(d[26]), "+f"(d[27]), "+f"(d[28]), "+f"(d[29]), "+f"(d[30]), "+f"(d[31]),
      "+f"(d[32]), "+f"(d[33]), "+f"(d[34]), "+f"(d[35]), "+f"(d[36]), "+f"(d[37]), "+f"(d[38]), "+f"(d[39])
    : "r"(a[0]), "r"(a[1]), "r"(a[2]), "r"(a[3]), "l"(db), "r"(sd));
}

__device__ __forceinline__ void wgmma_rs_n96(float* d, const uint32_t* a, uint64_t db, int sd) {
  asm volatile("{ .reg .pred p; setp.ne.b32 p, %53, 0;\n"
      "wgmma.mma_async.sync.aligned.m64n96k16.f32.bf16.bf16 {"
      "%0,%1,%2,%3,%4,%5,%6,%7,%8,%9,%10,%11,%12,%13,%14,%15,"
      "%16,%17,%18,%19,%20,%21,%22,%23,%24,%25,%26,%27,%28,%29,%30,%31,"
      "%32,%33,%34,%35,%36,%37,%38,%39,%40,%41,%42,%43,%44,%45,%46,%47"
      "}, {%48,%49,%50,%51}, %52, p, 1, 1, 0; }"
    : "+f"(d[0]), "+f"(d[1]), "+f"(d[2]), "+f"(d[3]), "+f"(d[4]), "+f"(d[5]), "+f"(d[6]), "+f"(d[7]),
      "+f"(d[8]), "+f"(d[9]), "+f"(d[10]), "+f"(d[11]), "+f"(d[12]), "+f"(d[13]), "+f"(d[14]), "+f"(d[15]),
      "+f"(d[16]), "+f"(d[17]), "+f"(d[18]), "+f"(d[19]), "+f"(d[20]), "+f"(d[21]), "+f"(d[22]), "+f"(d[23]),
      "+f"(d[24]), "+f"(d[25]), "+f"(d[26]), "+f"(d[27]), "+f"(d[28]), "+f"(d[29]), "+f"(d[30]), "+f"(d[31]),
      "+f"(d[32]), "+f"(d[33]), "+f"(d[34]), "+f"(d[35]), "+f"(d[36]), "+f"(d[37]), "+f"(d[38]), "+f"(d[39]),
      "+f"(d[40]), "+f"(d[41]), "+f"(d[42]), "+f"(d[43]), "+f"(d[44]), "+f"(d[45]), "+f"(d[46]), "+f"(d[47])
    : "r"(a[0]), "r"(a[1]), "r"(a[2]), "r"(a[3]), "l"(db), "r"(sd));
}

__device__ __forceinline__ void wgmma_rs_n112(float* d, const uint32_t* a, uint64_t db, int sd) {
  asm volatile("{ .reg .pred p; setp.ne.b32 p, %61, 0;\n"
      "wgmma.mma_async.sync.aligned.m64n112k16.f32.bf16.bf16 {"
      "%0,%1,%2,%3,%4,%5,%6,%7,%8,%9,%10,%11,%12,%13,%14,%15,"
      "%16,%17,%18,%19,%20,%21,%22,%23,%24,%25,%26,%27,%28,%29,%30,%31,"
      "%32,%33,%34,%35,%36,%37,%38,%39,%40,%41,%42,%43,%44,%45,%46,%47,"
      "%48,%49,%50,%51,%52,%53,%54,%55"
      "}, {%56,%57,%58,%59}, %60, p, 1, 1, 0; }"
    : "+f"(d[0]), "+f"(d[1]), "+f"(d[2]), "+f"(d[3]), "+f"(d[4]), "+f"(d[5]), "+f"(d[6]), "+f"(d[7]),
      "+f"(d[8]), "+f"(d[9]), "+f"(d[10]), "+f"(d[11]), "+f"(d[12]), "+f"(d[13]), "+f"(d[14]), "+f"(d[15]),
      "+f"(d[16]), "+f"(d[17]), "+f"(d[18]), "+f"(d[19]), "+f"(d[20]), "+f"(d[21]), "+f"(d[22]), "+f"(d[23]),
      "+f"(d[24]), "+f"(d[25]), "+f"(d[26]), "+f"(d[27]), "+f"(d[28]), "+f"(d[29]), "+f"(d[30]), "+f"(d[31]),
      "+f"(d[32]), "+f"(d[33]), "+f"(d[34]), "+f"(d[35]), "+f"(d[36]), "+f"(d[37]), "+f"(d[38]), "+f"(d[39]),
      "+f"(d[40]), "+f"(d[41]), "+f"(d[42]), "+f"(d[43]), "+f"(d[44]), "+f"(d[45]), "+f"(d[46]), "+f"(d[47]),
      "+f"(d[48]), "+f"(d[49]), "+f"(d[50]), "+f"(d[51]), "+f"(d[52]), "+f"(d[53]), "+f"(d[54]), "+f"(d[55])
    : "r"(a[0]), "r"(a[1]), "r"(a[2]), "r"(a[3]), "l"(db), "r"(sd));
}

__device__ __forceinline__ void wgmma_rs_n128(float* d, const uint32_t* a, uint64_t db, int sd) {
  asm volatile("{ .reg .pred p; setp.ne.b32 p, %69, 0;\n"
      "wgmma.mma_async.sync.aligned.m64n128k16.f32.bf16.bf16 {"
      "%0,%1,%2,%3,%4,%5,%6,%7,%8,%9,%10,%11,%12,%13,%14,%15,"
      "%16,%17,%18,%19,%20,%21,%22,%23,%24,%25,%26,%27,%28,%29,%30,%31,"
      "%32,%33,%34,%35,%36,%37,%38,%39,%40,%41,%42,%43,%44,%45,%46,%47,"
      "%48,%49,%50,%51,%52,%53,%54,%55,%56,%57,%58,%59,%60,%61,%62,%63"
      "}, {%64,%65,%66,%67}, %68, p, 1, 1, 0; }"
    : "+f"(d[0]), "+f"(d[1]), "+f"(d[2]), "+f"(d[3]), "+f"(d[4]), "+f"(d[5]), "+f"(d[6]), "+f"(d[7]),
      "+f"(d[8]), "+f"(d[9]), "+f"(d[10]), "+f"(d[11]), "+f"(d[12]), "+f"(d[13]), "+f"(d[14]), "+f"(d[15]),
      "+f"(d[16]), "+f"(d[17]), "+f"(d[18]), "+f"(d[19]), "+f"(d[20]), "+f"(d[21]), "+f"(d[22]), "+f"(d[23]),
      "+f"(d[24]), "+f"(d[25]), "+f"(d[26]), "+f"(d[27]), "+f"(d[28]), "+f"(d[29]), "+f"(d[30]), "+f"(d[31]),
      "+f"(d[32]), "+f"(d[33]), "+f"(d[34]), "+f"(d[35]), "+f"(d[36]), "+f"(d[37]), "+f"(d[38]), "+f"(d[39]),
      "+f"(d[40]), "+f"(d[41]), "+f"(d[42]), "+f"(d[43]), "+f"(d[44]), "+f"(d[45]), "+f"(d[46]), "+f"(d[47]),
      "+f"(d[48]), "+f"(d[49]), "+f"(d[50]), "+f"(d[51]), "+f"(d[52]), "+f"(d[53]), "+f"(d[54]), "+f"(d[55]),
      "+f"(d[56]), "+f"(d[57]), "+f"(d[58]), "+f"(d[59]), "+f"(d[60]), "+f"(d[61]), "+f"(d[62]), "+f"(d[63])
    : "r"(a[0]), "r"(a[1]), "r"(a[2]), "r"(a[3]), "l"(db), "r"(sd));
}

__device__ __forceinline__ void wgmma_rs_n144(float* d, const uint32_t* a, uint64_t db, int sd) {
  asm volatile("{ .reg .pred p; setp.ne.b32 p, %77, 0;\n"
      "wgmma.mma_async.sync.aligned.m64n144k16.f32.bf16.bf16 {"
      "%0,%1,%2,%3,%4,%5,%6,%7,%8,%9,%10,%11,%12,%13,%14,%15,"
      "%16,%17,%18,%19,%20,%21,%22,%23,%24,%25,%26,%27,%28,%29,%30,%31,"
      "%32,%33,%34,%35,%36,%37,%38,%39,%40,%41,%42,%43,%44,%45,%46,%47,"
      "%48,%49,%50,%51,%52,%53,%54,%55,%56,%57,%58,%59,%60,%61,%62,%63,"
      "%64,%65,%66,%67,%68,%69,%70,%71"
      "}, {%72,%73,%74,%75}, %76, p, 1, 1, 0; }"
    : "+f"(d[0]), "+f"(d[1]), "+f"(d[2]), "+f"(d[3]), "+f"(d[4]), "+f"(d[5]), "+f"(d[6]), "+f"(d[7]),
      "+f"(d[8]), "+f"(d[9]), "+f"(d[10]), "+f"(d[11]), "+f"(d[12]), "+f"(d[13]), "+f"(d[14]), "+f"(d[15]),
      "+f"(d[16]), "+f"(d[17]), "+f"(d[18]), "+f"(d[19]), "+f"(d[20]), "+f"(d[21]), "+f"(d[22]), "+f"(d[23]),
      "+f"(d[24]), "+f"(d[25]), "+f"(d[26]), "+f"(d[27]), "+f"(d[28]), "+f"(d[29]), "+f"(d[30]), "+f"(d[31]),
      "+f"(d[32]), "+f"(d[33]), "+f"(d[34]), "+f"(d[35]), "+f"(d[36]), "+f"(d[37]), "+f"(d[38]), "+f"(d[39]),
      "+f"(d[40]), "+f"(d[41]), "+f"(d[42]), "+f"(d[43]), "+f"(d[44]), "+f"(d[45]), "+f"(d[46]), "+f"(d[47]),
      "+f"(d[48]), "+f"(d[49]), "+f"(d[50]), "+f"(d[51]), "+f"(d[52]), "+f"(d[53]), "+f"(d[54]), "+f"(d[55]),
      "+f"(d[56]), "+f"(d[57]), "+f"(d[58]), "+f"(d[59]), "+f"(d[60]), "+f"(d[61]), "+f"(d[62]), "+f"(d[63]),
      "+f"(d[64]), "+f"(d[65]), "+f"(d[66]), "+f"(d[67]), "+f"(d[68]), "+f"(d[69]), "+f"(d[70]), "+f"(d[71])
    : "r"(a[0]), "r"(a[1]), "r"(a[2]), "r"(a[3]), "l"(db), "r"(sd));
}

__device__ __forceinline__ void wgmma_rs_n160(float* d, const uint32_t* a, uint64_t db, int sd) {
  asm volatile("{ .reg .pred p; setp.ne.b32 p, %85, 0;\n"
      "wgmma.mma_async.sync.aligned.m64n160k16.f32.bf16.bf16 {"
      "%0,%1,%2,%3,%4,%5,%6,%7,%8,%9,%10,%11,%12,%13,%14,%15,"
      "%16,%17,%18,%19,%20,%21,%22,%23,%24,%25,%26,%27,%28,%29,%30,%31,"
      "%32,%33,%34,%35,%36,%37,%38,%39,%40,%41,%42,%43,%44,%45,%46,%47,"
      "%48,%49,%50,%51,%52,%53,%54,%55,%56,%57,%58,%59,%60,%61,%62,%63,"
      "%64,%65,%66,%67,%68,%69,%70,%71,%72,%73,%74,%75,%76,%77,%78,%79"
      "}, {%80,%81,%82,%83}, %84, p, 1, 1, 0; }"
    : "+f"(d[0]), "+f"(d[1]), "+f"(d[2]), "+f"(d[3]), "+f"(d[4]), "+f"(d[5]), "+f"(d[6]), "+f"(d[7]),
      "+f"(d[8]), "+f"(d[9]), "+f"(d[10]), "+f"(d[11]), "+f"(d[12]), "+f"(d[13]), "+f"(d[14]), "+f"(d[15]),
      "+f"(d[16]), "+f"(d[17]), "+f"(d[18]), "+f"(d[19]), "+f"(d[20]), "+f"(d[21]), "+f"(d[22]), "+f"(d[23]),
      "+f"(d[24]), "+f"(d[25]), "+f"(d[26]), "+f"(d[27]), "+f"(d[28]), "+f"(d[29]), "+f"(d[30]), "+f"(d[31]),
      "+f"(d[32]), "+f"(d[33]), "+f"(d[34]), "+f"(d[35]), "+f"(d[36]), "+f"(d[37]), "+f"(d[38]), "+f"(d[39]),
      "+f"(d[40]), "+f"(d[41]), "+f"(d[42]), "+f"(d[43]), "+f"(d[44]), "+f"(d[45]), "+f"(d[46]), "+f"(d[47]),
      "+f"(d[48]), "+f"(d[49]), "+f"(d[50]), "+f"(d[51]), "+f"(d[52]), "+f"(d[53]), "+f"(d[54]), "+f"(d[55]),
      "+f"(d[56]), "+f"(d[57]), "+f"(d[58]), "+f"(d[59]), "+f"(d[60]), "+f"(d[61]), "+f"(d[62]), "+f"(d[63]),
      "+f"(d[64]), "+f"(d[65]), "+f"(d[66]), "+f"(d[67]), "+f"(d[68]), "+f"(d[69]), "+f"(d[70]), "+f"(d[71]),
      "+f"(d[72]), "+f"(d[73]), "+f"(d[74]), "+f"(d[75]), "+f"(d[76]), "+f"(d[77]), "+f"(d[78]), "+f"(d[79])
    : "r"(a[0]), "r"(a[1]), "r"(a[2]), "r"(a[3]), "l"(db), "r"(sd));
}

__device__ __forceinline__ void wgmma_rs_n176(float* d, const uint32_t* a, uint64_t db, int sd) {
  asm volatile("{ .reg .pred p; setp.ne.b32 p, %93, 0;\n"
      "wgmma.mma_async.sync.aligned.m64n176k16.f32.bf16.bf16 {"
      "%0,%1,%2,%3,%4,%5,%6,%7,%8,%9,%10,%11,%12,%13,%14,%15,"
      "%16,%17,%18,%19,%20,%21,%22,%23,%24,%25,%26,%27,%28,%29,%30,%31,"
      "%32,%33,%34,%35,%36,%37,%38,%39,%40,%41,%42,%43,%44,%45,%46,%47,"
      "%48,%49,%50,%51,%52,%53,%54,%55,%56,%57,%58,%59,%60,%61,%62,%63,"
      "%64,%65,%66,%67,%68,%69,%70,%71,%72,%73,%74,%75,%76,%77,%78,%79,"
      "%80,%81,%82,%83,%84,%85,%86,%87"
      "}, {%88,%89,%90,%91}, %92, p, 1, 1, 0; }"
    : "+f"(d[0]), "+f"(d[1]), "+f"(d[2]), "+f"(d[3]), "+f"(d[4]), "+f"(d[5]), "+f"(d[6]), "+f"(d[7]),
      "+f"(d[8]), "+f"(d[9]), "+f"(d[10]), "+f"(d[11]), "+f"(d[12]), "+f"(d[13]), "+f"(d[14]), "+f"(d[15]),
      "+f"(d[16]), "+f"(d[17]), "+f"(d[18]), "+f"(d[19]), "+f"(d[20]), "+f"(d[21]), "+f"(d[22]), "+f"(d[23]),
      "+f"(d[24]), "+f"(d[25]), "+f"(d[26]), "+f"(d[27]), "+f"(d[28]), "+f"(d[29]), "+f"(d[30]), "+f"(d[31]),
      "+f"(d[32]), "+f"(d[33]), "+f"(d[34]), "+f"(d[35]), "+f"(d[36]), "+f"(d[37]), "+f"(d[38]), "+f"(d[39]),
      "+f"(d[40]), "+f"(d[41]), "+f"(d[42]), "+f"(d[43]), "+f"(d[44]), "+f"(d[45]), "+f"(d[46]), "+f"(d[47]),
      "+f"(d[48]), "+f"(d[49]), "+f"(d[50]), "+f"(d[51]), "+f"(d[52]), "+f"(d[53]), "+f"(d[54]), "+f"(d[55]),
      "+f"(d[56]), "+f"(d[57]), "+f"(d[58]), "+f"(d[59]), "+f"(d[60]), "+f"(d[61]), "+f"(d[62]), "+f"(d[63]),
      "+f"(d[64]), "+f"(d[65]), "+f"(d[66]), "+f"(d[67]), "+f"(d[68]), "+f"(d[69]), "+f"(d[70]), "+f"(d[71]),
      "+f"(d[72]), "+f"(d[73]), "+f"(d[74]), "+f"(d[75]), "+f"(d[76]), "+f"(d[77]), "+f"(d[78]), "+f"(d[79]),
      "+f"(d[80]), "+f"(d[81]), "+f"(d[82]), "+f"(d[83]), "+f"(d[84]), "+f"(d[85]), "+f"(d[86]), "+f"(d[87])
    : "r"(a[0]), "r"(a[1]), "r"(a[2]), "r"(a[3]), "l"(db), "r"(sd));
}

__device__ __forceinline__ void wgmma_rs_n192(float* d, const uint32_t* a, uint64_t db, int sd) {
  asm volatile("{ .reg .pred p; setp.ne.b32 p, %101, 0;\n"
      "wgmma.mma_async.sync.aligned.m64n192k16.f32.bf16.bf16 {"
      "%0,%1,%2,%3,%4,%5,%6,%7,%8,%9,%10,%11,%12,%13,%14,%15,"
      "%16,%17,%18,%19,%20,%21,%22,%23,%24,%25,%26,%27,%28,%29,%30,%31,"
      "%32,%33,%34,%35,%36,%37,%38,%39,%40,%41,%42,%43,%44,%45,%46,%47,"
      "%48,%49,%50,%51,%52,%53,%54,%55,%56,%57,%58,%59,%60,%61,%62,%63,"
      "%64,%65,%66,%67,%68,%69,%70,%71,%72,%73,%74,%75,%76,%77,%78,%79,"
      "%80,%81,%82,%83,%84,%85,%86,%87,%88,%89,%90,%91,%92,%93,%94,%95"
      "}, {%96,%97,%98,%99}, %100, p, 1, 1, 0; }"
    : "+f"(d[0]), "+f"(d[1]), "+f"(d[2]), "+f"(d[3]), "+f"(d[4]), "+f"(d[5]), "+f"(d[6]), "+f"(d[7]),
      "+f"(d[8]), "+f"(d[9]), "+f"(d[10]), "+f"(d[11]), "+f"(d[12]), "+f"(d[13]), "+f"(d[14]), "+f"(d[15]),
      "+f"(d[16]), "+f"(d[17]), "+f"(d[18]), "+f"(d[19]), "+f"(d[20]), "+f"(d[21]), "+f"(d[22]), "+f"(d[23]),
      "+f"(d[24]), "+f"(d[25]), "+f"(d[26]), "+f"(d[27]), "+f"(d[28]), "+f"(d[29]), "+f"(d[30]), "+f"(d[31]),
      "+f"(d[32]), "+f"(d[33]), "+f"(d[34]), "+f"(d[35]), "+f"(d[36]), "+f"(d[37]), "+f"(d[38]), "+f"(d[39]),
      "+f"(d[40]), "+f"(d[41]), "+f"(d[42]), "+f"(d[43]), "+f"(d[44]), "+f"(d[45]), "+f"(d[46]), "+f"(d[47]),
      "+f"(d[48]), "+f"(d[49]), "+f"(d[50]), "+f"(d[51]), "+f"(d[52]), "+f"(d[53]), "+f"(d[54]), "+f"(d[55]),
      "+f"(d[56]), "+f"(d[57]), "+f"(d[58]), "+f"(d[59]), "+f"(d[60]), "+f"(d[61]), "+f"(d[62]), "+f"(d[63]),
      "+f"(d[64]), "+f"(d[65]), "+f"(d[66]), "+f"(d[67]), "+f"(d[68]), "+f"(d[69]), "+f"(d[70]), "+f"(d[71]),
      "+f"(d[72]), "+f"(d[73]), "+f"(d[74]), "+f"(d[75]), "+f"(d[76]), "+f"(d[77]), "+f"(d[78]), "+f"(d[79]),
      "+f"(d[80]), "+f"(d[81]), "+f"(d[82]), "+f"(d[83]), "+f"(d[84]), "+f"(d[85]), "+f"(d[86]), "+f"(d[87]),
      "+f"(d[88]), "+f"(d[89]), "+f"(d[90]), "+f"(d[91]), "+f"(d[92]), "+f"(d[93]), "+f"(d[94]), "+f"(d[95])
    : "r"(a[0]), "r"(a[1]), "r"(a[2]), "r"(a[3]), "l"(db), "r"(sd));
}

__device__ __forceinline__ void wgmma_rs_n208(float* d, const uint32_t* a, uint64_t db, int sd) {
  asm volatile("{ .reg .pred p; setp.ne.b32 p, %109, 0;\n"
      "wgmma.mma_async.sync.aligned.m64n208k16.f32.bf16.bf16 {"
      "%0,%1,%2,%3,%4,%5,%6,%7,%8,%9,%10,%11,%12,%13,%14,%15,"
      "%16,%17,%18,%19,%20,%21,%22,%23,%24,%25,%26,%27,%28,%29,%30,%31,"
      "%32,%33,%34,%35,%36,%37,%38,%39,%40,%41,%42,%43,%44,%45,%46,%47,"
      "%48,%49,%50,%51,%52,%53,%54,%55,%56,%57,%58,%59,%60,%61,%62,%63,"
      "%64,%65,%66,%67,%68,%69,%70,%71,%72,%73,%74,%75,%76,%77,%78,%79,"
      "%80,%81,%82,%83,%84,%85,%86,%87,%88,%89,%90,%91,%92,%93,%94,%95,"
      "%96,%97,%98,%99,%100,%101,%102,%103"
      "}, {%104,%105,%106,%107}, %108, p, 1, 1, 0; }"
    : "+f"(d[0]), "+f"(d[1]), "+f"(d[2]), "+f"(d[3]), "+f"(d[4]), "+f"(d[5]), "+f"(d[6]), "+f"(d[7]),
      "+f"(d[8]), "+f"(d[9]), "+f"(d[10]), "+f"(d[11]), "+f"(d[12]), "+f"(d[13]), "+f"(d[14]), "+f"(d[15]),
      "+f"(d[16]), "+f"(d[17]), "+f"(d[18]), "+f"(d[19]), "+f"(d[20]), "+f"(d[21]), "+f"(d[22]), "+f"(d[23]),
      "+f"(d[24]), "+f"(d[25]), "+f"(d[26]), "+f"(d[27]), "+f"(d[28]), "+f"(d[29]), "+f"(d[30]), "+f"(d[31]),
      "+f"(d[32]), "+f"(d[33]), "+f"(d[34]), "+f"(d[35]), "+f"(d[36]), "+f"(d[37]), "+f"(d[38]), "+f"(d[39]),
      "+f"(d[40]), "+f"(d[41]), "+f"(d[42]), "+f"(d[43]), "+f"(d[44]), "+f"(d[45]), "+f"(d[46]), "+f"(d[47]),
      "+f"(d[48]), "+f"(d[49]), "+f"(d[50]), "+f"(d[51]), "+f"(d[52]), "+f"(d[53]), "+f"(d[54]), "+f"(d[55]),
      "+f"(d[56]), "+f"(d[57]), "+f"(d[58]), "+f"(d[59]), "+f"(d[60]), "+f"(d[61]), "+f"(d[62]), "+f"(d[63]),
      "+f"(d[64]), "+f"(d[65]), "+f"(d[66]), "+f"(d[67]), "+f"(d[68]), "+f"(d[69]), "+f"(d[70]), "+f"(d[71]),
      "+f"(d[72]), "+f"(d[73]), "+f"(d[74]), "+f"(d[75]), "+f"(d[76]), "+f"(d[77]), "+f"(d[78]), "+f"(d[79]),
      "+f"(d[80]), "+f"(d[81]), "+f"(d[82]), "+f"(d[83]), "+f"(d[84]), "+f"(d[85]), "+f"(d[86]), "+f"(d[87]),
      "+f"(d[88]), "+f"(d[89]), "+f"(d[90]), "+f"(d[91]), "+f"(d[92]), "+f"(d[93]), "+f"(d[94]), "+f"(d[95]),
      "+f"(d[96]), "+f"(d[97]), "+f"(d[98]), "+f"(d[99]), "+f"(d[100]), "+f"(d[101]), "+f"(d[102]), "+f"(d[103])
    : "r"(a[0]), "r"(a[1]), "r"(a[2]), "r"(a[3]), "l"(db), "r"(sd));
}

__device__ __forceinline__ void wgmma_rs_n224(float* d, const uint32_t* a, uint64_t db, int sd) {
  asm volatile("{ .reg .pred p; setp.ne.b32 p, %117, 0;\n"
      "wgmma.mma_async.sync.aligned.m64n224k16.f32.bf16.bf16 {"
      "%0,%1,%2,%3,%4,%5,%6,%7,%8,%9,%10,%11,%12,%13,%14,%15,"
      "%16,%17,%18,%19,%20,%21,%22,%23,%24,%25,%26,%27,%28,%29,%30,%31,"
      "%32,%33,%34,%35,%36,%37,%38,%39,%40,%41,%42,%43,%44,%45,%46,%47,"
      "%48,%49,%50,%51,%52,%53,%54,%55,%56,%57,%58,%59,%60,%61,%62,%63,"
      "%64,%65,%66,%67,%68,%69,%70,%71,%72,%73,%74,%75,%76,%77,%78,%79,"
      "%80,%81,%82,%83,%84,%85,%86,%87,%88,%89,%90,%91,%92,%93,%94,%95,"
      "%96,%97,%98,%99,%100,%101,%102,%103,%104,%105,%106,%107,%108,%109,%110,%111"
      "}, {%112,%113,%114,%115}, %116, p, 1, 1, 0; }"
    : "+f"(d[0]), "+f"(d[1]), "+f"(d[2]), "+f"(d[3]), "+f"(d[4]), "+f"(d[5]), "+f"(d[6]), "+f"(d[7]),
      "+f"(d[8]), "+f"(d[9]), "+f"(d[10]), "+f"(d[11]), "+f"(d[12]), "+f"(d[13]), "+f"(d[14]), "+f"(d[15]),
      "+f"(d[16]), "+f"(d[17]), "+f"(d[18]), "+f"(d[19]), "+f"(d[20]), "+f"(d[21]), "+f"(d[22]), "+f"(d[23]),
      "+f"(d[24]), "+f"(d[25]), "+f"(d[26]), "+f"(d[27]), "+f"(d[28]), "+f"(d[29]), "+f"(d[30]), "+f"(d[31]),
      "+f"(d[32]), "+f"(d[33]), "+f"(d[34]), "+f"(d[35]), "+f"(d[36]), "+f"(d[37]), "+f"(d[38]), "+f"(d[39]),
      "+f"(d[40]), "+f"(d[41]), "+f"(d[42]), "+f"(d[43]), "+f"(d[44]), "+f"(d[45]), "+f"(d[46]), "+f"(d[47]),
      "+f"(d[48]), "+f"(d[49]), "+f"(d[50]), "+f"(d[51]), "+f"(d[52]), "+f"(d[53]), "+f"(d[54]), "+f"(d[55]),
      "+f"(d[56]), "+f"(d[57]), "+f"(d[58]), "+f"(d[59]), "+f"(d[60]), "+f"(d[61]), "+f"(d[62]), "+f"(d[63]),
      "+f"(d[64]), "+f"(d[65]), "+f"(d[66]), "+f"(d[67]), "+f"(d[68]), "+f"(d[69]), "+f"(d[70]), "+f"(d[71]),
      "+f"(d[72]), "+f"(d[73]), "+f"(d[74]), "+f"(d[75]), "+f"(d[76]), "+f"(d[77]), "+f"(d[78]), "+f"(d[79]),
      "+f"(d[80]), "+f"(d[81]), "+f"(d[82]), "+f"(d[83]), "+f"(d[84]), "+f"(d[85]), "+f"(d[86]), "+f"(d[87]),
      "+f"(d[88]), "+f"(d[89]), "+f"(d[90]), "+f"(d[91]), "+f"(d[92]), "+f"(d[93]), "+f"(d[94]), "+f"(d[95]),
      "+f"(d[96]), "+f"(d[97]), "+f"(d[98]), "+f"(d[99]), "+f"(d[100]), "+f"(d[101]), "+f"(d[102]), "+f"(d[103]),
      "+f"(d[104]), "+f"(d[105]), "+f"(d[106]), "+f"(d[107]), "+f"(d[108]), "+f"(d[109]), "+f"(d[110]), "+f"(d[111])
    : "r"(a[0]), "r"(a[1]), "r"(a[2]), "r"(a[3]), "l"(db), "r"(sd));
}

__device__ __forceinline__ void wgmma_rs_n240(float* d, const uint32_t* a, uint64_t db, int sd) {
  asm volatile("{ .reg .pred p; setp.ne.b32 p, %125, 0;\n"
      "wgmma.mma_async.sync.aligned.m64n240k16.f32.bf16.bf16 {"
      "%0,%1,%2,%3,%4,%5,%6,%7,%8,%9,%10,%11,%12,%13,%14,%15,"
      "%16,%17,%18,%19,%20,%21,%22,%23,%24,%25,%26,%27,%28,%29,%30,%31,"
      "%32,%33,%34,%35,%36,%37,%38,%39,%40,%41,%42,%43,%44,%45,%46,%47,"
      "%48,%49,%50,%51,%52,%53,%54,%55,%56,%57,%58,%59,%60,%61,%62,%63,"
      "%64,%65,%66,%67,%68,%69,%70,%71,%72,%73,%74,%75,%76,%77,%78,%79,"
      "%80,%81,%82,%83,%84,%85,%86,%87,%88,%89,%90,%91,%92,%93,%94,%95,"
      "%96,%97,%98,%99,%100,%101,%102,%103,%104,%105,%106,%107,%108,%109,%110,%111,"
      "%112,%113,%114,%115,%116,%117,%118,%119"
      "}, {%120,%121,%122,%123}, %124, p, 1, 1, 0; }"
    : "+f"(d[0]), "+f"(d[1]), "+f"(d[2]), "+f"(d[3]), "+f"(d[4]), "+f"(d[5]), "+f"(d[6]), "+f"(d[7]),
      "+f"(d[8]), "+f"(d[9]), "+f"(d[10]), "+f"(d[11]), "+f"(d[12]), "+f"(d[13]), "+f"(d[14]), "+f"(d[15]),
      "+f"(d[16]), "+f"(d[17]), "+f"(d[18]), "+f"(d[19]), "+f"(d[20]), "+f"(d[21]), "+f"(d[22]), "+f"(d[23]),
      "+f"(d[24]), "+f"(d[25]), "+f"(d[26]), "+f"(d[27]), "+f"(d[28]), "+f"(d[29]), "+f"(d[30]), "+f"(d[31]),
      "+f"(d[32]), "+f"(d[33]), "+f"(d[34]), "+f"(d[35]), "+f"(d[36]), "+f"(d[37]), "+f"(d[38]), "+f"(d[39]),
      "+f"(d[40]), "+f"(d[41]), "+f"(d[42]), "+f"(d[43]), "+f"(d[44]), "+f"(d[45]), "+f"(d[46]), "+f"(d[47]),
      "+f"(d[48]), "+f"(d[49]), "+f"(d[50]), "+f"(d[51]), "+f"(d[52]), "+f"(d[53]), "+f"(d[54]), "+f"(d[55]),
      "+f"(d[56]), "+f"(d[57]), "+f"(d[58]), "+f"(d[59]), "+f"(d[60]), "+f"(d[61]), "+f"(d[62]), "+f"(d[63]),
      "+f"(d[64]), "+f"(d[65]), "+f"(d[66]), "+f"(d[67]), "+f"(d[68]), "+f"(d[69]), "+f"(d[70]), "+f"(d[71]),
      "+f"(d[72]), "+f"(d[73]), "+f"(d[74]), "+f"(d[75]), "+f"(d[76]), "+f"(d[77]), "+f"(d[78]), "+f"(d[79]),
      "+f"(d[80]), "+f"(d[81]), "+f"(d[82]), "+f"(d[83]), "+f"(d[84]), "+f"(d[85]), "+f"(d[86]), "+f"(d[87]),
      "+f"(d[88]), "+f"(d[89]), "+f"(d[90]), "+f"(d[91]), "+f"(d[92]), "+f"(d[93]), "+f"(d[94]), "+f"(d[95]),
      "+f"(d[96]), "+f"(d[97]), "+f"(d[98]), "+f"(d[99]), "+f"(d[100]), "+f"(d[101]), "+f"(d[102]), "+f"(d[103]),
      "+f"(d[104]), "+f"(d[105]), "+f"(d[106]), "+f"(d[107]), "+f"(d[108]), "+f"(d[109]), "+f"(d[110]), "+f"(d[111]),
      "+f"(d[112]), "+f"(d[113]), "+f"(d[114]), "+f"(d[115]), "+f"(d[116]), "+f"(d[117]), "+f"(d[118]), "+f"(d[119])
    : "r"(a[0]), "r"(a[1]), "r"(a[2]), "r"(a[3]), "l"(db), "r"(sd));
}

__device__ __forceinline__ void wgmma_rs_n256(float* d, const uint32_t* a, uint64_t db, int sd) {
  asm volatile("{ .reg .pred p; setp.ne.b32 p, %133, 0;\n"
      "wgmma.mma_async.sync.aligned.m64n256k16.f32.bf16.bf16 {"
      "%0,%1,%2,%3,%4,%5,%6,%7,%8,%9,%10,%11,%12,%13,%14,%15,"
      "%16,%17,%18,%19,%20,%21,%22,%23,%24,%25,%26,%27,%28,%29,%30,%31,"
      "%32,%33,%34,%35,%36,%37,%38,%39,%40,%41,%42,%43,%44,%45,%46,%47,"
      "%48,%49,%50,%51,%52,%53,%54,%55,%56,%57,%58,%59,%60,%61,%62,%63,"
      "%64,%65,%66,%67,%68,%69,%70,%71,%72,%73,%74,%75,%76,%77,%78,%79,"
      "%80,%81,%82,%83,%84,%85,%86,%87,%88,%89,%90,%91,%92,%93,%94,%95,"
      "%96,%97,%98,%99,%100,%101,%102,%103,%104,%105,%106,%107,%108,%109,%110,%111,"
      "%112,%113,%114,%115,%116,%117,%118,%119,%120,%121,%122,%123,%124,%125,%126,%127"
      "}, {%128,%129,%130,%131}, %132, p, 1, 1, 0; }"
    : "+f"(d[0]), "+f"(d[1]), "+f"(d[2]), "+f"(d[3]), "+f"(d[4]), "+f"(d[5]), "+f"(d[6]), "+f"(d[7]),
      "+f"(d[8]), "+f"(d[9]), "+f"(d[10]), "+f"(d[11]), "+f"(d[12]), "+f"(d[13]), "+f"(d[14]), "+f"(d[15]),
      "+f"(d[16]), "+f"(d[17]), "+f"(d[18]), "+f"(d[19]), "+f"(d[20]), "+f"(d[21]), "+f"(d[22]), "+f"(d[23]),
      "+f"(d[24]), "+f"(d[25]), "+f"(d[26]), "+f"(d[27]), "+f"(d[28]), "+f"(d[29]), "+f"(d[30]), "+f"(d[31]),
      "+f"(d[32]), "+f"(d[33]), "+f"(d[34]), "+f"(d[35]), "+f"(d[36]), "+f"(d[37]), "+f"(d[38]), "+f"(d[39]),
      "+f"(d[40]), "+f"(d[41]), "+f"(d[42]), "+f"(d[43]), "+f"(d[44]), "+f"(d[45]), "+f"(d[46]), "+f"(d[47]),
      "+f"(d[48]), "+f"(d[49]), "+f"(d[50]), "+f"(d[51]), "+f"(d[52]), "+f"(d[53]), "+f"(d[54]), "+f"(d[55]),
      "+f"(d[56]), "+f"(d[57]), "+f"(d[58]), "+f"(d[59]), "+f"(d[60]), "+f"(d[61]), "+f"(d[62]), "+f"(d[63]),
      "+f"(d[64]), "+f"(d[65]), "+f"(d[66]), "+f"(d[67]), "+f"(d[68]), "+f"(d[69]), "+f"(d[70]), "+f"(d[71]),
      "+f"(d[72]), "+f"(d[73]), "+f"(d[74]), "+f"(d[75]), "+f"(d[76]), "+f"(d[77]), "+f"(d[78]), "+f"(d[79]),
      "+f"(d[80]), "+f"(d[81]), "+f"(d[82]), "+f"(d[83]), "+f"(d[84]), "+f"(d[85]), "+f"(d[86]), "+f"(d[87]),
      "+f"(d[88]), "+f"(d[89]), "+f"(d[90]), "+f"(d[91]), "+f"(d[92]), "+f"(d[93]), "+f"(d[94]), "+f"(d[95]),
      "+f"(d[96]), "+f"(d[97]), "+f"(d[98]), "+f"(d[99]), "+f"(d[100]), "+f"(d[101]), "+f"(d[102]), "+f"(d[103]),
      "+f"(d[104]), "+f"(d[105]), "+f"(d[106]), "+f"(d[107]), "+f"(d[108]), "+f"(d[109]), "+f"(d[110]), "+f"(d[111]),
      "+f"(d[112]), "+f"(d[113]), "+f"(d[114]), "+f"(d[115]), "+f"(d[116]), "+f"(d[117]), "+f"(d[118]), "+f"(d[119]),
      "+f"(d[120]), "+f"(d[121]), "+f"(d[122]), "+f"(d[123]), "+f"(d[124]), "+f"(d[125]), "+f"(d[126]), "+f"(d[127])
    : "r"(a[0]), "r"(a[1]), "r"(a[2]), "r"(a[3]), "l"(db), "r"(sd));
}

__device__ __forceinline__ void ln_finish(float mean, float var, float& mb, float& rinv) {
  mb = round_bf16(mean);
  float sd;
  asm("sqrt.approx.ftz.f32 %0, %1;" : "=f"(sd) : "f"(round_bf16(round_bf16(var) + 1e-5f)));
  asm("rcp.approx.ftz.f32 %0, %1;" : "=f"(rinv) : "f"(round_bf16(sd)));
}
__device__ __forceinline__ uint32_t sum4(uint32_t a, uint32_t b, uint32_t c, uint32_t d) { return badd2(badd2(badd2(d, c), b), a); }
struct Ring {
  uint32_t s, ph;
  __device__ __forceinline__ void next() { if (++s == NSTAGE) { s = 0; ph ^= 1; } }
};

template <int J> __device__ __forceinline__ void conv_lda(uint32_t* a, uint32_t base) {
  a[2 * J] = lds32(base + (J >> 1) * 256 + (J & 1) * 16); a[2 * J + 1] = lds32(base + (J >> 1) * 256 + (J & 1) * 16 + 128);
}
template <int J = 0> __device__ __forceinline__ void conv_lda_all(uint32_t* a, uint32_t base) {
  conv_lda<J>(a, base);
  if constexpr (J < 31) conv_lda_all<J + 1>(a, base);
}
__device__ __forceinline__ void conv_mma(float* acc, const uint32_t* a, uint64_t db) {
  wgmma_rs_n256(acc, a, db, 0);
  wgmma_rs_n240(acc, a + 4, db + 16, 1);
  wgmma_rs_n224(acc, a + 8, db + 32, 1);
  wgmma_rs_n208(acc, a + 12, db + 48, 1);
  wgmma_rs_n192(acc, a + 16, db + 64, 1);
  wgmma_rs_n176(acc, a + 20, db + 80, 1);
  wgmma_rs_n160(acc, a + 24, db + 96, 1);
  wgmma_rs_n144(acc, a + 28, db + 112, 1);
  wgmma_rs_n128(acc, a + 32, db + 128, 1);
  wgmma_rs_n112(acc, a + 36, db + 144, 1);
  wgmma_rs_n96(acc, a + 40, db + 160, 1);
  wgmma_rs_n80(acc, a + 44, db + 176, 1);
  wgmma_rs_n64(acc, a + 48, db + 192, 1);
  wgmma_rs_n48(acc, a + 52, db + 208, 1);
  wgmma_rs_n32(acc, a + 56, db + 224, 1);
  wgmma_rs_n16(acc, a + 60, db + 240, 1);
}
__device__ __forceinline__ uint32_t conv_part(const float* acc, int j) {
  const int q = 31 - j;
  return q == 31 ? pack_bf16(acc[124], acc[125]) : pack_bf16(acc[4 * q] + acc[(4 * q + 6) & 127], acc[4 * q + 1] + acc[(4 * q + 7) & 127]);
}
template <bool MORE, int J = 0> __device__ __forceinline__ void conv_drain(const float* acc, uint32_t wr, uint32_t* a, uint32_t ka) {
  if (MORE) conv_lda<J>(a, ka);
  sts32(wr + J * 128, conv_part(acc, J));
  if constexpr (J < 31) conv_drain<MORE, J + 1>(acc, wr, a, ka);
}
__device__ __forceinline__ uint4 conv_sum(const uint4* p) {
  return make_uint4(sum4(p[0].x, p[1].x, p[2].x, p[3].x), sum4(p[0].y, p[1].y, p[2].y, p[3].y), sum4(p[0].z, p[1].z, p[2].z, p[3].z),
                    sum4(p[0].w, p[1].w, p[2].w, p[3].w));
}
__device__ __forceinline__ int g2pos(int fb) { return fb / G2_KB * G2_KB + fb % 6 * 6 + fb % G2_KB / 6; }

template <int NV> __device__ __forceinline__ void gelu_stage(float* acc, const float* hb, uint32_t sa, int passes, uint32_t bar) {
#pragma unroll
  for (int i = 0; i < NV; i++) acc[i] = fmaf(acc[i], 0.5f, hb[(i >> 1) & 1]);
#pragma unroll 1
  for (; passes > 0; passes--, sa += NV * 256) {
#pragma unroll
    for (int i = 0; i < NV; i += 8)
      stsm4t(sa + i * 256, pack_bf16(gelu_half(acc[i]), gelu_half(acc[i + 1])), pack_bf16(gelu_half(acc[i + 2]), gelu_half(acc[i + 3])),
             pack_bf16(gelu_half(acc[i + 4]), gelu_half(acc[i + 5])), pack_bf16(gelu_half(acc[i + 6]), gelu_half(acc[i + 7])));
    __syncwarp();
    if (bar) mbar_arrive(bar);
    bar = 0;
    float half = 0.5f;
    asm volatile("" : "+f"(half));
#pragma unroll
    for (int i = 0; i < NV; i++) acc[i] = fmaf(acc[NV + i], half, hb[2 + ((i >> 1) & 1)]);
  }
}

__global__ void __cluster_dims__(2, 1, 1) __launch_bounds__(384, 1) fused_kernel(const __grid_constant__ Hot H, const __grid_constant__ Params P) {
  extern __shared__ __align__(1024) uint8_t smem_raw[];
  const uint32_t t0 = clk();
  const uint32_t sb = smem_u32(smem_raw);
  const int tid = threadIdx.x, lane = tid & 31;
  const int bid = blockIdx.x, rank = bid & 1;
  const Role& R = P.role[bid];
  Scratch* const S = H.S;
  uint32_t xr[18];
  const int row = bid * 16 + (tid >> 4);
  if (tid < 256 && bid < 128) {
    const char* src = reinterpret_cast<const char*>(H.x) + row * (D_ * 2) + (lane & 15) * 8;
#pragma unroll
    for (int j = 0; j < 9; j++) asm volatile("ld.global.nc.v2.u32 {%0,%1}, [%2];" : "=r"(xr[2 * j]), "=r"(xr[2 * j + 1]) : "l"(src + 128 * j));
  }
  if (tid == 256) asm volatile("prefetch.tensormap [%0];" :: "l"(&P.m_w1 + (R.at == 15)) : "memory");
  const int warp = __shfl_sync(0xffffffffu, tid >> 5, 0);

  if (warp >= 8) {
    const bool one = elect_one(), left = R.at == 15;
    if (warp == 8 && one) {
#pragma unroll
      for (int b = B_FULL; b < B_KFULL; b += 8) mbar_init(sb + b, 1);
      fence_async_smem();
      tma3d_ef(sb, &P.m_w1 + left, 0, 0, R.fg, sb + B_FULL);
#pragma unroll
      for (int s = 0; s < NSTAGE; s++) mbar_expect_tx(sb + B_FULL + 8 * s, G1_BYTES);
#pragma unroll
      for (int b = B_KFULL; b <= B_DONE; b += 8) mbar_init(sb + b, b < B_EMPTY ? 1 : b < B_SFREE ? 2 : b < B_CEMPTY ? 3 : b < B_G1DONE ? 4 : 8);
      asm volatile("fence.mbarrier_init.release.cluster;" ::: "memory");
    }
    __syncwarp();
    asm volatile("barrier.cluster.arrive.relaxed.aligned;" ::: "memory");
    asm volatile("setmaxnreg.dec.sync.aligned.u32 56;");
    asm volatile("barrier.cluster.wait.aligned;" ::: "memory");
    if (warp == 8) {
      const uint32_t ep = ldg32(S->cnt + C_EPOCH * 32);
      if (one) {
#pragma unroll 1
        for (int i = 0; i < 6; i++) asm volatile("prefetch.tensormap [%0];" :: "l"(&P.m_w2 + i) : "memory");
      }
      __syncwarp();
      if (bid < 128) bar_sync(2, 288);
      if (one) {
        const uint32_t boff = left ? 24576 : 16384, hbytes = G1_BYTES - boff;
        const CUtensorMap* const mw1 = &P.m_w1 + left;
        const int fg = R.fg;
        const char* hp = reinterpret_cast<const char*>(S->h) + R.at * 4096;
        TLREC(31);
        signal(S, C_H, EPOCH / 132);
        TLREC(1);
        tma3d_ef(sb + SLOT, mw1, 0, 64, fg, sb + B_FULL + 8);
        await(S, C_H, ep);
        fence_async_global();
        TLREC(2);
        const uint32_t tp = clk();
#pragma unroll 1
        for (int s = 0; s < NSTAGE; s++) {
          while ((int)(clk() - tp) < s * 400 - 100) { }
          if (s >= 1 && s + 1 < NSTAGE) tma3d_ef(sb + (s + 1) * SLOT, mw1, 0, (s + 1) * 64, fg, sb + B_FULL + 8 * (s + 1));
          bulk_load(sb + s * SLOT + boff, hp, hbytes, sb + B_FULL + 8 * s);
          hp += 73728;
        }
        int kr = bid < 128 ? -2 : KV_ROUNDS + 1, ks = 0;
        auto kv_step = [&]() {
          if (ks == 0) {
            bulk_wait_all();
            if (kr < KV_ROUNDS - 2) {
              const int q = (kr + 2) % 3;
              const uint32_t in = sb + kv_buf(q), fb = sb + B_UFULL + 8 * q;
              mbar_expect_tx(fb, 3840 + 3264 + 768);
              tma2d(in, &P.m_k, (kr + 2) * 96, bid * 16 - 4, fb);
              tma2d(in + 3840, &P.m_v, (kr + 2) * 96, bid * 16 - 1, fb);
              bulk_load(in + 7168, H.shift_k + (kr + 2) * 384, 768, fb);
            }
            if (kr == KV_ROUNDS) { mbar_arrive(sb + B_KVDONE); kr++; }
          } else if (kr >= 0) {
            if (!mbar_test(sb + B_KFULL + 8 * (kr % 3), kr >= 3)) return;
            fence_async_smem();
            tma3d_store(&P.m_ub, sb + kv_buf(kr % 3) + (ks - 1) * 3072, 16 * (127 - bid), kr * 48, 2 * ks - 2);
            bulk_commit();
          }
          if (++ks == 3) { kr++; ks = kr == KV_ROUNDS - 2 || kr == KV_ROUNDS - 1; }
        };
        if (bid >= 128) mbar_arrive(sb + B_KVDONE);
        uint32_t slot = sb, fb = sb + B_FULL, ph = 0;
        auto next = [&]() { slot += SLOT; fb += 8; if (fb == sb + B_FULL + 8 * NSTAGE) { slot = sb; fb = sb + B_FULL; ph ^= 1; } };
#pragma unroll 1
        for (int k0 = NSTAGE * 64; k0 < G1_KB * 64 || kr <= KV_ROUNDS; k0 += 64) {
          if (k0 < G1_KB * 64) {
            mbar_wait(fb + (B_EMPTY - B_FULL), ph);
            mbar_expect_tx(fb, G1_BYTES);
            tma3d_ef(slot, mw1, 0, k0, fg, fb);
            bulk_load(slot + boff, hp, hbytes, fb);
            hp += 73728;
            next();
            if (k0 == 23 * 64) {
#pragma unroll 1
              for (int i = 0; i < 2; i++) {
                sts128(sb + cv_taps(i), 0, 0, 0, 0); sts128(sb + cv_taps(i) + 16, 0, 0, 0, 0);
                bulk_load(sb + cv_taps(i) + 32, H.ssm_k + (R.ch + i) * S_, 4096, sb + B_MISC);
              }
              mbar_expect_tx(sb + B_MISC, boff / 64 + 1152 + 8192);
              bulk_load(sb + SM_B1, H.b1 + fg * 64, boff / 64, sb + B_MISC);
              bulk_load(sb + SM_D, H.ssm_D, 1152, sb + B_MISC);
            }
          }
          if (kr <= KV_ROUNDS) kv_step();
        }
        await(S, C_KV, ep);
        fence_async_global();
#pragma unroll 1
        for (int i = 0; i < R.ncv; i++) {
          if (i == 2) {
            if (R.sg >= 0) {
#pragma unroll 1
              for (int s = 2; s < NSTAGE; s++) {
                mbar_wait(sb + B_EMPTY + 8 * s, ((G1_KB / NSTAGE) - 1) & 1);
                mbar_expect_tx(sb + B_FULL + 8 * s, G2_BYTES);
                tma3d_ef(sb + s * SLOT, &P.m_w2, 0, (rank * G2_KB + 6 * (s - 2)) * 64, R.sg, sb + B_FULL + 8 * s);
              }
            }
            mbar_wait(sb + B_G1DONE, 0);
          }
          const uint32_t kt = sb + cv_taps(i), b8 = sb + 8 * (i & 3);
          mbar_wait(b8 + B_CEMPTY, ((i >> 2) & 1) ^ 1);
          if (i < 2) mbar_arrive(b8 + B_KFULL);
          else {
            sts128(kt, 0, 0, 0, 0); sts128(kt + 16, 0, 0, 0, 0);
            mbar_expect_tx(b8 + B_KFULL, 4096);
            bulk_load(kt + 32, H.ssm_k + (R.ch + i) * S_, 4096, b8 + B_KFULL);
          }
          mbar_expect_tx(b8 + B_UFULL, 8192);
          bulk_load(sb + cv_in(i), S->ub + (R.ch + i) * 4096, 8192, b8 + B_UFULL);
        }
        if (R.sg >= 0) {
          mbar_expect_tx(sb + B_XY, 2 * 18432 + 2048 + 256);
#pragma unroll
          for (int i = 0; i < 4; i++) mbar_expect_tx(sb + B_XFULL + 8 * i, i & 1 ? 9216 - XP * 2048 : XP * 2048);
          const int sg = R.sg, kend = (rank + 1) * G2_KB * 64;
          const char* us = reinterpret_cast<const char*>(S->u) + rank * G2_KB * 73728 + R.ds * 1024;
          const int dko = rank ? 9216 : -9216;
          await(S, C_U, ep);
          fence_async_global();
          TLREC(6);
#pragma unroll
          for (int s = 2; s < NSTAGE; s++) {
            bulk_load_ef(sb + s * SLOT + 16384, us + (s - 2) * 73728, 9216, sb + B_FULL + 8 * s);
            bulk_load_ef(sb + s * SLOT + 16384 + 9216, us + dko + (s - 2) * 73728, 9216, sb + B_FULL + 8 * s);
          }
          us += (NSTAGE - 2) * 73728;
          slot = sb; fb = sb + B_FULL; ph = (G1_KB / NSTAGE) & 1;
          int k0 = kend - (G2_KB - 6 * (NSTAGE - 2)) * 64;
#pragma unroll 1
          for (int kb = NSTAGE - 2; kb < G2_KB; kb++) {
            mbar_wait(fb + (B_EMPTY - B_FULL), ph);
            mbar_expect_tx(fb, G2_BYTES);
            tma3d_ef(slot, &P.m_w2, 0, k0, sg, fb);
            bulk_load_ef(slot + 16384, us, 9216, fb);
            bulk_load_ef(slot + 16384 + 9216, us + dko, 9216, fb);
            us += 73728;
            k0 += 6 * 64;
            if (k0 >= kend) k0 -= (G2_KB - 1) * 64;
            next();
            if (kb < 16) {
              TUNED(SYNCA, 0, 5); TUNED(SYNCKB, 1, 7);
              if (kb == 3) { await(S, C_U + 1, ep); fence_async_global(); }
              if (kb == SYNCA) asm volatile("red.relaxed.gpu.global.add.u32 [%0], %1;" :: "l"(S->cnt + C_SYNC * 32), "r"(EPOCH / 128) : "memory");
              if (kb == SYNCKB - 1) await(S, C_SYNC, ep);
              if (kb == 8) { mbar_wait(sb + B_KVDONE, 1); fence_async_smem(); }
              if (kb >= 8) tma2d(sb + SM_CV + (kb - 8) * 2304, &P.m_x, R.dk * 8, sg * 64 + (kb - 8) * 16, sb + B_XY);
            }
          }
          bulk_load(sb + SM_ST, S->stats + R.sg * 64, 2048, sb + B_XY);
          bulk_load(sb + SM_B2, P.b2 + R.sg * 64, 256, sb + B_XY);
          await(S, C_Y, ep);
          fence_async_global();
          TLREC(19);
          tma3d(sb + SM_DED, &P.m_y, 0, R.dk * 8, R.sg, sb + B_XY);
          if (bid == 0) asm volatile("red.relaxed.gpu.global.add.u32 [%0], %1;" :: "l"(S->cnt + C_EPOCH * 32), "r"(EPOCH) : "memory");
        }
      }
    } else {
      if (bid < 128) {
        const int ht = tid - 288, hf = ht >= 48, pr = ht - 48 * hf;
        const uint32_t st = (1 - hf) * 1536 + pr * 32, sw = (pr & 4) * 4;
#pragma unroll 1
        for (int r = 0; r < KV_ROUNDS; r++) {
          const int q = r % 3;
          const uint32_t in = sb + kv_buf(q);
          {
            mbar_wait_guarded(sb + B_UFULL + 8 * q, t0, r >= 3);
            uint32_t kk[12], vv[9];
#pragma unroll
            for (int j = 0; j < 12; j++) kk[j] = lds32(in + hf * 1536 + pr * 4 + j * 192);
#pragma unroll
            for (int j = 0; j < 9; j++) vv[j] = lds32(in + 3840 + hf * 1536 + pr * 4 + j * 192);
            const uint4 w = lds128(in + 7168 + pr * 16);
            const uint32_t w0 = __byte_perm(w.x, w.z, 0x5410), w1 = __byte_perm(w.x, w.z, 0x7632);
            const uint32_t w2 = __byte_perm(w.y, w.w, 0x5410), w3 = __byte_perm(w.y, w.w, 0x7632);
#pragma unroll
            for (int j = 0; j < 9; j++)
              vv[j] = bmul2(badd2(badd2(badd2(bmul2(kk[j], w3), bmul2(kk[j + 1], w2)), bmul2(kk[j + 2], w1)), bmul2(kk[j + 3], w0)), vv[j]);
            bar_sync(1, 96);
#pragma unroll
            for (int c = 0; c < 2; c++)
#pragma unroll
              for (int pi = 0; pi < 2; pi++) {
                const uint32_t sel = c ? 0x7632 : 0x5410;
                sts128(in + st + c * 3072 + (pi * 16 ^ sw), __byte_perm(vv[7 + pi], vv[6 + pi], sel), __byte_perm(vv[5 + pi], vv[4 + pi], sel),
                       __byte_perm(vv[3 + pi], vv[2 + pi], sel), __byte_perm(vv[1 + pi], vv[pi], sel));
              }
            bar_sync(1, 96);
            if (ht == 0) mbar_arrive(sb + B_KFULL + 8 * q);
          }
          __syncwarp();
        }
      }
      if (one) {
        if (warp < 11) {
          const int wg = warp - 9;
          const uint32_t bytes = left ? 12288 : 10240;
#pragma unroll 1
          for (int j = 0; j < 2; j++) {
            mbar_wait_guarded(sb + B_STG + 8 * wg + (j ? 0 : 16), t0);
            fence_async_smem();
            TLREC(13 + wg);
            if (!j || wg || !left)
              bulk_store(S->u + g2pos(R.fg + wg + (j && left)) * (64 * D_) + R.at * 2048 + (left ? 0 : j * 5120), sb + (wg ? SM_ST1 : SM_DED) + j * bytes, bytes);
          }
          bulk_commit();
          bulk_wait_all();
          mbar_arrive(sb + B_STORED + 8 * wg);
          if (wg) mbar_arrive(sb + B_EMPTY);
          asm volatile("mbarrier.arrive.shared::cta.b64 _, [%0], 3;" :: "r"(sb + B_SFREE + 8 * wg) : "memory");
          signal(S, C_U + wg, EPOCH / 132);
          TLREC(15 + wg);
        } else {
          mbar_wait_guarded(sb + B_KVDONE, t0);
          signal(S, C_KV, EPOCH / 132);
          TLREC(27);
        }
      }
      __syncwarp();
#pragma unroll 1
      for (int i = 0; i < R.ncv; i++) {
        const uint32_t red = sb + cv_red(i, R.ncv) + (tid - 288) * 16;
        uint4* yo = reinterpret_cast<uint4*>(S->y + (R.ch + i) * S_) + (tid - 288);
        mbar_wait_guarded(sb + B_STORED + 8 * (i & 1), t0);
        mbar_wait_guarded(sb + B_STG + 8 * (i & 1) + (i + 2 < R.ncv ? 0 : 16), t0, i + 2 >= R.ncv || !(i & 2));
        uint4 p[2][4];
#pragma unroll
        for (int x = 0; x < 8; x++) p[x >> 2][x & 3] = lds128(red + (x & 3) * CV_REDW + (x >> 2) * 1536);
        yo[0] = conv_sum(p[0]);
        if (warp < 11) {
#pragma unroll
          for (int x = 0; x < 4; x++) p[0][x] = lds128(red + x * CV_REDW + 3072);
          yo[192] = conv_sum(p[0]);
        }
        yo[96] = conv_sum(p[1]);
        __syncwarp();
        if (one) mbar_arrive(sb + (i + 4 == R.ncv ? B_PDONE : B_SFREE + 8 * (i & 1)));
        if (i + 3 == R.ncv) {
          bar_sync(1, 96);
          if (warp == 11 && one) { fence_async_smem(); mbar_arrive(sb + B_EMPTY + 8); }
          __syncwarp();
        }
      }
      bar_sync(1, 96);
      if (warp == 11 && one) {
        TLREC(7);
        mbar_arrive(sb + B_KVDONE);
        signal(S, C_Y, EPOCH / 132);
        if (R.sg >= 0) mbar_wait_guarded(sb + B_DONE, t0);
      }
    }
    TLEND();
  } else {
    asm volatile("barrier.cluster.arrive.relaxed.aligned;" ::: "memory");
    if (bid < 128) {
      float c[36], s[4];
#pragma unroll
      for (int i = 0; i < 18; i++) { c[2 * i] = bf_lo(xr[i]); c[2 * i + 1] = bf_hi(xr[i]); }
#pragma unroll
      for (int i = 0; i < 36; i++) s[i & 3] = i < 4 ? c[i] : s[i & 3] + c[i];
      const float ml = ((s[0] + s[1]) + (s[2] + s[3])) * (1.0f / 36.0f);
#pragma unroll
      for (int i = 0; i < 36; i++) { c[i] -= ml; s[i & 3] = i < 4 ? c[i] * c[i] : fmaf(c[i], c[i], s[i & 3]); }
      float m = ml, q = (s[0] + s[1]) + (s[2] + s[3]), n2 = 18.f;
#pragma unroll
      for (int o = 1; o < 16; o <<= 1) {
        const float mo = __shfl_xor_sync(0xffffffffu, m, o), qo = __shfl_xor_sync(0xffffffffu, q, o);
        const float dl = m - mo;
        q = fmaf(dl * dl, n2, q + qo);
        m = fmaf(dl, -0.5f, m);
        n2 *= 2.f;
      }
      const float var = q * (1.0f / 576.0f);
      float mb, rinv, mb2, rinv2;
      ln_finish(m, var, mb, rinv);
      ln_finish((m - mb) * rinv, var * rinv * rinv, mb2, rinv2);
      const float ca = rinv * rinv2, cb = fmaf(ml - mb, rinv, -mb2) * rinv2;
      uint2* dst = reinterpret_cast<uint2*>(S->h) + ((row >> 6) * 18 + ((lane >> 3) & 1)) * 512 + (row & 63) * 8 + ((lane & 7) ^ (row & 6));
#pragma unroll
      for (int j = 0; j < 9; j++)
        dst[1024 * j] = make_uint2(pack_bf16(fmaf(c[4 * j], ca, cb), fmaf(c[4 * j + 1], ca, cb)), pack_bf16(fmaf(c[4 * j + 2], ca, cb), fmaf(c[4 * j + 3], ca, cb)));
      const uint32_t rh = pack_bf16(rinv, rinv);
      if (!(lane & 15)) S->stats[row] = make_uint4(pack_bf16(mb, mb), rh, pack_bf16(rinv - bf_lo(rh), rinv - bf_lo(rh)), 0);
      __syncwarp();
      bar_arrive(2, 288);
    }
    asm volatile("setmaxnreg.inc.sync.aligned.u32 224;");
    asm volatile("barrier.cluster.wait.aligned;" ::: "memory");
    const int wg = warp >> 2, w = warp & 3, g = lane >> 2, t = lane & 3, wtid = tid & 127;
    const bool elect = wtid == 0;
    const uint64_t da0 = make_desc(sb + wg * 8192, 8192, 1024, 1);
    const uint32_t swz = ((lane >> 4) * 8 + (lane & 7)) * 128 + (((2 * w + ((lane >> 3) & 1)) ^ (lane & 7)) << 4);
    const uint32_t stg = sb + (wg ? SM_ST1 : SM_DED), ka0 = (8 * w + g + t + 1) * 4;
    uint32_t a[64];
    {
      auto mainloop = [&](auto&& mma) {
        Ring r{0, 0};
        uint32_t rel = 0;
#pragma unroll 1
        for (int kb = 0; kb < G1_KB; kb++, r.next()) {
          if (kb == G1_KB - G1_TAIL && wg) {
            wg_wait<0>();
            if (elect) mbar_arrive(rel);
            rel = 0;
            {
              mbar_wait(sb + B_MISC, 0);
              conv_lda_all(a, sb + SM_CV + 16384 + CV_K + ka0);
            }
            bar_sync(5, 256);
          }
          mbar_wait(sb + B_FULL + 8 * r.s, r.ph);
          if (kb == 0 && warp == 0) TLREC(3);
          wg_fence();
          mma(r.s * (SLOT >> 4), kb);
          wg_commit();
          if (kb == G1_KB - 1) break;
          wg_wait<1>();
          if (elect && rel) mbar_arrive(rel);
          rel = sb + B_EMPTY + 8 * r.s;
        }
        bar_arrive(5, 256);
        wg_wait<0>();
      };
      float hb[4];
      auto staged = [&](int second) {
        if (!w) TLREC(4 + wg);
        if (lane == 0) mbar_arrive(sb + B_G1DONE);
        mbar_wait(sb + B_MISC, 0);
#pragma unroll
        for (int i = 0; i < 4; i++) hb[i] = 0.5f * bf_lo(lds16(sb + SM_B1 + (warp * 16 + g + (i & 1) * 8 + (i >> 1) * second) * 2));
        mbar_wait(sb + B_KVDONE, 0);
        if (wg) mbar_wait(sb + B_G1DONE, 0);
      };
      if (R.at != 15) {
        const uint64_t db0 = make_desc(sb + 16384, 4096, 512, 2);
        float acc[80];
        mainloop([&](uint32_t o, int kb) {
#pragma unroll
          for (int k = 0; k < 4; k++) wgmma_ss_n160_t11(acc, da0 + o + k * 128, db0 + o + k * 64, k ? 1 : kb);
        });
        pin_regs<80>(acc);
        staged(0);
        gelu_stage<40>(acc, hb, stg + swz, 2, lane ? 0 : sb + B_STG + 8 * wg + 16);
      } else {
        const uint64_t db0 = make_desc(sb + 24576, 4096, 512, 2);
        float acc[96];
        auto block = [&](float* d, uint64_t da, uint64_t db, int kb) {
#pragma unroll
          for (int k = 0; k < 4; k++) wgmma_ss_n96_t11(d, da + k * 128, db + k * 64, k ? 1 : kb);
        };
        if (wg) mainloop([&](uint32_t o, int kb) { block(acc, da0 + o, db0 + o, kb); block(acc + 48, da0 + o + 512, db0 + o, kb); });
        else mainloop([&](uint32_t o, int kb) { block(acc, da0 + o, db0 + o, kb); });
        pin_regs<96>(acc);
        staged(64);
        gelu_stage<48>(acc, hb, stg + swz, 1 + wg, lane ? 0 : sb + B_STG + 8 * wg + 16);
      }
      __syncwarp();
      if (lane == 0) mbar_arrive(sb + B_STG + 8 * wg);
    }
    {
      if (!wg) conv_lda_all(a, sb + SM_CV + 16384 + wg * CV_K + ka0);
#pragma unroll 1
      for (int i = wg; i < R.ncv; i += 2) {
        const bool more = i + 2 < R.ncv;
        const uint32_t dd = lds16(sb + SM_D + (R.ch + i) * 2);
        a[0] = badd2(a[0], ka0 == 32 ? dd : 0); a[2] = badd2(a[2], ka0 == 16 ? dd : 0);
        float acc[128];
        mbar_wait(sb + B_UFULL + 8 * (i & 3), (i >> 2) & 1);
        bar_sync(5 + wg, 256);
        const bool last = i + 1 == R.ncv;
        if (last && elect) mbar_arrive(sb + B_EMPTY);
        if (!w && i < 4) TLREC(22 + i);
        wg_fence();
        conv_mma(acc, a, make_desc(sb + cv_in(i), 4096, 128, 0));
        wg_commit();
        if (!last) bar_arrive(5 + (wg ^ 1), 256);
        if (more) {
          mbar_wait(sb + B_SFREE + 8 * wg, (i >> 1) & 1);
          mbar_wait(sb + B_KFULL + 8 * ((i + 2) & 3), ((i + 2) >> 2) & 1);
        } else if (last) mbar_wait(sb + B_PDONE, 0);
        wg_wait<0>();
        pin_regs<128>(acc);
        if (lane == 0) mbar_arrive(sb + B_CEMPTY + 8 * (i & 3));
        if (last && elect) mbar_arrive(sb + B_EMPTY + 8);
        const uint32_t red = sb + cv_red(i, R.ncv), ka = sb + cv_taps(i + 2) + ka0;
        if (lane < 8 * w) sts32(red + w * CV_REDW + lane * 4, 0);
        const uint32_t wr = red + w * CV_REDW + (8 * (3 - t + w) + g) * 4;
        if (more) conv_drain<true>(acc, wr, a, ka); else conv_drain<false>(acc, wr, a, ka);
        __syncwarp();
        if (lane == 0) mbar_arrive(sb + B_STG + 8 * wg + (more ? 0 : 16));
      }
      if (!w) TLREC(20 + wg);
    }
    if (R.sg >= 0) {
      const int srow = R.sg * 64 + warp * 16;
      const uint64_t db0 = make_desc(sb + 16384, 16, 1024, 1);
      const uint32_t xo = sb + SM_CV + warp * 2304, xa = xo + (lane & 15) * 144;
      float acc[72];
      Ring r{G1_KB % NSTAGE, (G1_KB / NSTAGE) & 1};
      bar_sync(8, 256);
      uint32_t rel = 0;
#pragma unroll 1
      for (int kb = 0; kb < G2_KB; kb++, r.next()) {
        if (kb == G2_KB - G2_TAIL && wg) {
          wg_wait<0>();
          if (elect) mbar_arrive_remote(rel);
          rel = 0;
          bar_sync(7, 256);
        }
        mbar_wait(sb + B_FULL + 8 * r.s, r.ph);
        if (kb == 0 && !w) TLREC(17 + wg);
        if (kb == 8 && warp == 0) TLREC(26);
        if (kb == 20 && warp == 0) TLREC(8);
        if (kb == 27 && warp == 0) TLREC(30);
        const uint64_t da = da0 + r.s * (SLOT >> 4), db = db0 + r.s * (SLOT >> 4);
        wg_fence();
        wgmma_ss_n144_t10(acc, da, db, kb);
#pragma unroll
        for (int k = 1; k < 4; k++) wgmma_ss_n144_t10(acc, da + k * 128, db + k * 2, 1);
        wg_commit();
        if (kb == G2_KB - 1) break;
        wg_wait<1>();
        if (elect && rel) mbar_arrive_remote(rel);
        rel = kb == G2_KB - NSTAGE ? mapa(sb + B_XRDY, rank ^ 1) : sb + B_EMPTY + 8 * r.s;
      }
      if (!wg) bar_arrive(7, 256);
      const uint32_t xz = sb + XSLOT * SLOT + wg * 10240 + wtid * 16;
      const uint32_t rz = mapa(xz, rank ^ 1), rb = mapa(sb + B_XFULL + 16 * wg, rank ^ 1);
      mbar_wait(sb + B_XRDY, 0);
      wg_wait<0>();
      pin_regs<72>(acc);
      if (!w) TLREC(28 + wg);
#pragma unroll
      for (int i = 0; i < 32; i += 8)
        asm volatile("st.async.weak.shared::cluster.mbarrier::complete_tx::bytes.v4.b32 [%0], {%1,%2,%3,%4}, [%5];"
                     :: "r"(rz + i * 256), "r"(pack_bf16(acc[i], acc[i + 1])), "r"(pack_bf16(acc[i + 2], acc[i + 3])),
                        "r"(pack_bf16(acc[i + 4], acc[i + 5])), "r"(pack_bf16(acc[i + 6], acc[i + 7])), "r"(rb + (i < 8 * XP ? 0 : 8)) : "memory");
      asm volatile("st.async.weak.shared::cluster.mbarrier::complete_tx::bytes.v2.b32 [%0], {%1,%2}, [%3];"
                   :: "r"(rz + 8192), "r"(pack_bf16(acc[32], acc[33])), "r"(pack_bf16(acc[34], acc[35])), "r"(rb + 8) : "memory");
      uint32_t xx[18], ss[18];
      mbar_wait(sb + B_XY, 0);
      {
        const uint32_t ya = sb + SM_DED + wg * 9216 + swz;
        const uint4 st0 = lds128(sb + SM_ST + (warp * 16 + g) * 16), st1 = lds128(sb + SM_ST + (warp * 16 + g + 8) * 16);
        const float hb0 = 0.5f * bf_lo(lds16(sb + SM_B2 + (warp * 16 + g) * 2)), hb1 = 0.5f * bf_lo(lds16(sb + SM_B2 + (warp * 16 + g + 8) * 2));
#pragma unroll
        for (int q = 0; q < 8; q += 2) { ldsm4(xx + 2 * q, xa + (lane >> 4) * 16 + q * 16); ldsm4t(ss + 2 * q, ya + q * 1024); }
        ldsm2(xx + 16, xa + 128);
        ldsm2t(ss + 16, ya + 8 * 1024);
#pragma unroll
        for (int i = 0; i < 18; i++) {
          const uint4& st = (i & 1) ? st1 : st0;
          const uint32_t c = bsub2(xx[i], st.x);
          ss[i] = bmul2(bfma2(c, st.y, bmul2(c, st.z)), ss[i]);
        }
#pragma unroll
        for (int i = 36; i < 72; i++) acc[i] = fmaf(acc[i], 0.5f, (i & 2) ? hb1 : hb0);
      }
      char* const op = reinterpret_cast<char*>(P.out) + srow * (D_ * 2) + R.dk * 16 + lane * 16;
      uint32_t oo[5];
#pragma unroll
      for (int j = 0; j < 5; j++) oo[j] = ((lane + 32 * j) * 57 >> 9) * (D_ * 2 - 144) + j * 512;
      uint32_t pv[20];
#pragma unroll
      for (int pc = 0; pc < 2; pc++) {
        const int q0 = pc ? XP : 0, q1 = pc ? 5 : XP;
        mbar_wait_cluster(sb + B_XFULL + 16 * wg + 8 * pc, 0);
        if (!w && !pc) TLREC(9 + wg);
#pragma unroll
        for (int q = q0; q < q1; q++) { const uint4 v = lds128(xz + q * 2048); pv[4 * q] = v.x; pv[4 * q + 1] = v.y; pv[4 * q + 2] = v.z; pv[4 * q + 3] = v.w; }
#pragma unroll
        for (int i = 4 * q0; i < 4 * q1 && i < 18; i++)
          xx[i] = bfma2(ss[i], pack_bf16(silu_half(fmaf(bf_lo(pv[i]), 0.5f, acc[36 + 2 * i])), silu_half(fmaf(bf_hi(pv[i]), 0.5f, acc[37 + 2 * i]))), xx[i]);
      }
#pragma unroll
      for (int q = 0; q < 4; q++) stsm4(xa + (lane >> 4) * 16 + q * 32, xx[4 * q], xx[4 * q + 1], xx[4 * q + 2], xx[4 * q + 3]);
      stsm2(xa + 128, xx[16], xx[17]);
      __syncwarp();
      if (lane == 0) mbar_arrive(sb + B_DONE);
#pragma unroll
      for (int j = 0; j < 5; j++)
        if (j < 4 || lane < 16) *reinterpret_cast<uint4*>(op + oo[j]) = lds128(xo + (lane + 32 * j) * 16);
      if (!w) TLREC(11 + wg);
    }
    TLEND();
  }
}

typedef CUresult (*EncodeFn)(CUtensorMap*, CUtensorMapDataType, cuuint32_t, void*, const cuuint64_t*, const cuuint64_t*, const cuuint32_t*,
                             const cuuint32_t*, CUtensorMapInterleave, CUtensorMapSwizzle, CUtensorMapL2promotion, CUtensorMapFloatOOBfill);

void make_map(EncodeFn fn, CUtensorMap* m, const void* ptr, int rank, const cuuint64_t* dims, const cuuint64_t* strides, const cuuint32_t* box,
              CUtensorMapSwizzle sw) {
  const cuuint32_t es[3] = {1, 1, 1};
  fn(m, CU_TENSOR_MAP_DATA_TYPE_BFLOAT16, rank, const_cast<void*>(ptr), dims, strides, box, es, CU_TENSOR_MAP_INTERLEAVE_NONE, sw,
     CU_TENSOR_MAP_L2_PROMOTION_L2_256B, CU_TENSOR_MAP_FLOAT_OOB_FILL_NONE);
}

void make_roles(Role* R) {
  int ch = 0;
  for (int gi = 0; gi < 8; gi++)
    for (int b = 0; b < 132; b++) {
      const int c = b >> 1, rank = b & 1;
      int g, idx;
      if (c < 4) { g = 0; idx = 4 + c; }
      else if (c < 36) { g = (c - 4) & 7; idx = (c - 4) >> 3; }
      else if (c < 64) { g = 1 + (c - 36) % 7; idx = 4 + (c - 36) / 7; }
      else { g = c - 58; idx = 8; }
      if (g != gi) continue;
      Role& r = R[b];
      r.sg = (int8_t)(idx < 8 ? 2 * (2 * g + (idx >> 2)) : -1);
      r.dk = (int8_t)((idx & 3) * 18 + rank * 9);
      r.ds = (int8_t)((idx & 3) * 18 + (rank ^ 1) * 9);
      if (g < 6 && (idx & 3) == 3) { r.fg = (int8_t)(12 * g + 6 * (idx >> 2) + 3 * rank); r.at = 15; }
      else {
        const bool third = (idx & 3) == 3 || idx == 8;
        const int tr = g < 6 ? 3 * g + (idx >> 2) : 3 * (3 * (g - 6) + (third ? 2 : idx >> 2)) + 2;
        r.fg = (int8_t)(4 * tr + 2 * rank); r.at = (int8_t)(5 * (third ? idx >> 2 : idx & 3));
      }
      r.ncv = idx < 8 ? NCV_REG : NCV_LONG;
      r.ch = (int16_t)ch;
      ch += r.ncv;
    }
}

}

extern "C" void kernel_launch(void* const* d_in, const int* in_sizes, int n_in, void* d_out, int out_size) {
  static Params P;
  static Hot H;
  static const void* cached[5] = {nullptr, nullptr, nullptr, nullptr, nullptr};
  const void* now[5] = {d_in[0], d_in[1], d_in[2], d_in[7], d_in[9]};
  bool same = true;
  for (int i = 0; i < 5; i++) { same = same && cached[i] == now[i]; cached[i] = now[i]; }
  if (!same) {
    void* fp = nullptr;
    cudaDriverEntryPointQueryResult qr;
    cudaGetDriverEntryPoint("cuTensorMapEncodeTiled", &fp, cudaEnableDefault, &qr);
    EncodeFn fn = (EncodeFn)fp;
    void* ps;
    cudaGetSymbolAddress(&ps, g_scratch);
    H.S = (Scratch*)ps;
    const void *py = (char*)ps + offsetof(Scratch, y), *pb = (char*)ps + offsetof(Scratch, ub);
    { cuuint64_t d[3] = {64, S_, F_ / 64}, s[2] = {F_ * 2, 128}; cuuint32_t b[3] = {64, 64, 2}; make_map(fn, &P.m_w1, d_in[7], 3, d, s, b, CU_TENSOR_MAP_SWIZZLE_128B);
      b[2] = 3; make_map(fn, &P.m_w1l, d_in[7], 3, d, s, b, CU_TENSOR_MAP_SWIZZLE_128B); }
    { cuuint64_t d[3] = {64, F_, S_ / 64}, s[2] = {S_ * 2, 128}; cuuint32_t b[3] = {64, 64, 2}; make_map(fn, &P.m_w2, d_in[9], 3, d, s, b, CU_TENSOR_MAP_SWIZZLE_128B); }
    { cuuint64_t d[2] = {D_, S_}, s[1] = {D_ * 2}; cuuint32_t b[2] = {72, 16}; make_map(fn, &P.m_x, d_in[0], 2, d, s, b, CU_TENSOR_MAP_SWIZZLE_NONE);
      b[0] = 96; b[1] = 20; make_map(fn, &P.m_k, d_in[1], 2, d, s, b, CU_TENSOR_MAP_SWIZZLE_NONE);
      b[1] = 17; make_map(fn, &P.m_v, d_in[2], 2, d, s, b, CU_TENSOR_MAP_SWIZZLE_NONE); }
    { cuuint64_t d[3] = {64, D_, S_ / 64}, s[2] = {S_ * 2, 128}; cuuint32_t b[3] = {64, 72, 2}; make_map(fn, &P.m_y, py, 3, d, s, b, CU_TENSOR_MAP_SWIZZLE_128B); }
    { cuuint64_t d[3] = {2048, D_ / 2, 4}, s[2] = {16384, 4096}; cuuint32_t b[3] = {16, 48, 2}; make_map(fn, &P.m_ub, pb, 3, d, s, b, CU_TENSOR_MAP_SWIZZLE_32B); }
    make_roles(P.role);
    cudaFuncSetAttribute(fused_kernel, cudaFuncAttributeMaxDynamicSharedMemorySize, SM_TOTAL);
  }
  H.x = (const __nv_bfloat16*)d_in[0];
  H.shift_k = (const __nv_bfloat16*)d_in[3]; H.ssm_k = (const __nv_bfloat16*)d_in[4]; H.ssm_D = (const __nv_bfloat16*)d_in[5];
  H.b1 = (const __nv_bfloat16*)d_in[8]; P.b2 = (const __nv_bfloat16*)d_in[10]; P.out = (__nv_bfloat16*)d_out;
  fused_kernel<<<132, 384, SM_TOTAL>>>(H, P);
}
```

```cpp
#include <cuda_runtime.h>
#include <cuda.h>
#include <cuda_bf16.h>
#include <stddef.h>
#include <stdint.h>

namespace {

constexpr int S_ = 2048, D_ = 576, F_ = 4608;
constexpr int NSTAGE = 5, SLOT = 36864;
constexpr int G1_KB = 32, G2_KB = 36;
constexpr int G1_BYTES = 36864, G2_BYTES = 16384 + 18432;
constexpr int NCV_REG = 4, NCV_LONG = 16;
static_assert(128 * NCV_REG + 4 * NCV_LONG == D_, "conv split");
constexpr int KV_ROUNDS = 6;
#define XP 2
#define TUNED(name, idx, val) constexpr int name = val
constexpr int G1_TAIL = 5, G2_TAIL = 3;

constexpr int CV_K = 4224, CV_REDW = 2112 * 2;
constexpr int SM_DED = NSTAGE * SLOT;
constexpr int SM_CV = SM_DED + 20480;
constexpr int SM_ST1 = 0;
constexpr int SM_ST = SM_CV + 18432, SM_B2 = SM_ST + 2048;
constexpr int SM_B1 = SM_CV + 2 * (8192 + CV_K), SM_D = SM_B1 + 384;
constexpr int SM_BAR = SM_D + 1152;
constexpr int SM_TOTAL = SM_BAR + 768;
static_assert(G1_KB % NSTAGE == 2, "slots 0 and 1 hold the last GEMM1 k-blocks and the last two of the first GEMM2 stages");
static_assert(NCV_REG % 4 == 0 && NCV_LONG % 4 == 0, "the last two channels use buffers 2 and 3");
constexpr int XSLOT = (G1_KB + G2_KB) % NSTAGE;
__device__ __forceinline__ uint32_t kv_buf(int q) { return q == 2 ? SM_DED : SM_CV + q * 8192; }
__device__ __forceinline__ uint32_t cv_red(int i, int n) { return i + 2 == n ? SM_CV : (i & 1) && i + 1 < n ? SLOT + 16384 : SM_DED; }
__device__ __forceinline__ uint32_t cv_in(int i) { return (i & 2 ? SLOT : SM_CV) + (i & 1) * 8192; }
__device__ __forceinline__ uint32_t cv_taps(int i) { return (i & 2 ? SM_ST1 + 24576 : SM_CV + 16384) + (i & 1) * CV_K; }
constexpr int bar_at(int i) { return SM_BAR + 8 * i; }
constexpr int B_FULL = bar_at(0)  , B_KFULL = bar_at(5)  , B_UFULL = bar_at(9)  , B_KVDONE = bar_at(13), B_STORED = bar_at(14)  ,
              B_XFULL = bar_at(16)  , B_XY = bar_at(20), B_MISC = bar_at(21),
              B_EMPTY = bar_at(22)  , B_XRDY = bar_at(27),
              B_SFREE = bar_at(28)  , B_PDONE = bar_at(30),
              B_CEMPTY = bar_at(31)  , B_STG = bar_at(35)  ,
              B_G1DONE = bar_at(39), B_DONE = bar_at(40);
constexpr int C_H = 0, C_KV = 1, C_U = 2  , C_Y = 4, C_SYNC = 5, C_EPOCH = 6, C_COUNT = 7;
constexpr uint32_t EPOCH = 128 * 33;

struct Scratch {
  uint32_t cnt[C_COUNT * 32];
  alignas(1024) uint4 stats[S_];
  alignas(1024) __nv_bfloat16 h[S_ * D_];
  alignas(1024) __nv_bfloat16 ub[D_ * 4096];
  alignas(1024) __nv_bfloat16 y[D_ * S_];
  alignas(1024) __nv_bfloat16 u[D_ * F_];
};
__device__ Scratch g_scratch;

struct Hot {
  const __nv_bfloat16 *x, *shift_k, *ssm_k, *b2;
  __nv_bfloat16* out;
  Scratch* S;
};
struct Role {
  int8_t fg;
  int8_t at;
  int8_t sg;
  int8_t dk, ds;
  int8_t ncv;
  int16_t ch;
};
struct Params {
  const __nv_bfloat16 *ssm_D, *b1;
  Role role[132];
  CUtensorMap m_w1, m_w1l, m_w2, m_x, m_y, m_k, m_v, m_ub;
};

#define TLREC(i) do { } while (0)
#define TLEND() do { } while (0)

__device__ __forceinline__ uint32_t smem_u32(const void* p) { return (uint32_t)__cvta_generic_to_shared(p); }
__device__ __forceinline__ void mbar_init(uint32_t bar, uint32_t cnt) { asm volatile("mbarrier.init.shared::cta.b64 [%0], %1;" :: "r"(bar), "r"(cnt) : "memory"); }
__device__ __forceinline__ void mbar_expect_tx(uint32_t bar, uint32_t bytes) { asm volatile("mbarrier.arrive.expect_tx.shared::cta.b64 _, [%0], %1;" :: "r"(bar), "r"(bytes) : "memory"); }
__device__ __forceinline__ void mbar_arrive(uint32_t bar) { asm volatile("mbarrier.arrive.shared::cta.b64 _, [%0];" :: "r"(bar) : "memory"); }
__device__ __forceinline__ uint32_t mapa(uint32_t addr, uint32_t cta) { uint32_t r; asm volatile("mapa.shared::cluster.u32 %0, %1, %2;" : "=r"(r) : "r"(addr), "r"(cta)); return r; }
__device__ __forceinline__ void mbar_arrive_remote(uint32_t rbar) { asm volatile("mbarrier.arrive.shared::cluster.b64 _, [%0];" :: "r"(rbar) : "memory"); }
__device__ __forceinline__ uint32_t clk() { uint32_t c; asm volatile("mov.u32 %0, %%clock;" : "=r"(c)); return c; }
__device__ __forceinline__ bool elect_one() {
  uint32_t p; asm volatile("{ .reg .pred p; elect.sync _|p, 0xffffffff; selp.u32 %0, 1, 0, p; }" : "=r"(p)); return p;
}
__device__ __forceinline__ void guard(uint32_t t0) { if ((int32_t)(clk() - t0) < 0) __trap(); }
__device__ __forceinline__ void mbar_wait(uint32_t bar, uint32_t parity) {
  asm volatile("{\n .reg .pred p;\n W_%=:\n mbarrier.try_wait.parity.shared::cta.b64 p, [%0], %1;\n @!p bra W_%=;\n }" :: "r"(bar), "r"(parity) : "memory");
}
__device__ __forceinline__ void mbar_wait_cluster(uint32_t bar, uint32_t parity) {
  asm volatile("{\n .reg .pred p;\n W_%=:\n mbarrier.try_wait.parity.relaxed.cluster.shared::cta.b64 p, [%0], %1;\n @!p bra W_%=;\n"
               " fence.acquire.sync_restrict::shared::cluster.cluster;\n }" :: "r"(bar), "r"(parity) : "memory");
}
__device__ __forceinline__ bool mbar_try(uint32_t bar, uint32_t parity) {
  uint32_t ok;
  asm volatile("{ .reg .pred p; mbarrier.try_wait.parity.shared::cta.b64 p, [%1], %2, 100000; selp.u32 %0, 1, 0, p; }" : "=r"(ok) : "r"(bar), "r"(parity) : "memory");
  return ok;
}
__device__ __forceinline__ bool mbar_test(uint32_t bar, uint32_t parity) {
  uint32_t ok;
  asm volatile("{ .reg .pred p; mbarrier.test_wait.parity.shared::cta.b64 p, [%1], %2; selp.u32 %0, 1, 0, p; }" : "=r"(ok) : "r"(bar), "r"(parity) : "memory");
  return ok;
}
__device__ __forceinline__ void mbar_wait_guarded(uint32_t bar, uint32_t t0, uint32_t parity = 0) { while (!mbar_try(bar, parity)) guard(t0); }
__device__ __forceinline__ void tma2d(uint32_t dst, const CUtensorMap* m, int c0, int c1, uint32_t bar) {
  asm volatile("cp.async.bulk.tensor.2d.shared::cluster.global.mbarrier::complete_tx::bytes [%0], [%1, {%3, %4}], [%2];"
               :: "r"(dst), "l"(m), "r"(bar), "r"(c0), "r"(c1) : "memory");
}
__device__ __forceinline__ void tma3d(uint32_t dst, const CUtensorMap* m, int c0, int c1, int c2, uint32_t bar) {
  asm volatile("cp.async.bulk.tensor.3d.shared::cluster.global.mbarrier::complete_tx::bytes [%0], [%1, {%3, %4, %5}], [%2];"
               :: "r"(dst), "l"(m), "r"(bar), "r"(c0), "r"(c1), "r"(c2) : "memory");
}
__device__ __forceinline__ uint64_t evict_first() { uint64_t p; asm("createpolicy.fractional.L2::evict_first.b64 %0, 1.0;" : "=l"(p)); return p; }
__device__ __forceinline__ void tma3d_ef(uint32_t dst, const CUtensorMap* m, int c0, int c1, int c2, uint32_t bar) {
  asm volatile("cp.async.bulk.tensor.3d.shared::cluster.global.mbarrier::complete_tx::bytes.L2::cache_hint [%0], [%1, {%3, %4, %5}], [%2], %6;"
               :: "r"(dst), "l"(m), "r"(bar), "r"(c0), "r"(c1), "r"(c2), "l"(evict_first()) : "memory");
}
__device__ __forceinline__ void bulk_load_ef(uint32_t dst, const void* src, uint32_t bytes, uint32_t bar) {
  asm volatile("cp.async.bulk.shared::cluster.global.mbarrier::complete_tx::bytes.L2::cache_hint [%0], [%1], %2, [%3], %4;"
               :: "r"(dst), "l"(src), "r"(bytes), "r"(bar), "l"(evict_first()) : "memory");
}
__device__ __forceinline__ void bulk_store(void* dst, uint32_t src, uint32_t bytes) {
  asm volatile("cp.async.bulk.global.shared::cta.bulk_group [%0], [%1], %2;" :: "l"(dst), "r"(src), "r"(bytes) : "memory");
}
__device__ __forceinline__ void bulk_load(uint32_t dst, const void* src, uint32_t bytes, uint32_t bar) {
  asm volatile("cp.async.bulk.shared::cluster.global.mbarrier::complete_tx::bytes [%0], [%1], %2, [%3];" :: "r"(dst), "l"(src), "r"(bytes), "r"(bar) : "memory");
}
__device__ __forceinline__ void tma3d_store(const CUtensorMap* m, uint32_t src, int c0, int c1, int c2) {
  asm volatile("cp.async.bulk.tensor.3d.global.shared::cta.bulk_group [%0, {%2, %3, %4}], [%1];" :: "l"(m), "r"(src), "r"(c0), "r"(c1), "r"(c2) : "memory");
}
__device__ __forceinline__ void bulk_commit() { asm volatile("cp.async.bulk.commit_group;" ::: "memory"); }
__device__ __forceinline__ void bulk_wait_all() { asm volatile("cp.async.bulk.wait_group 0;" ::: "memory"); }
__device__ __forceinline__ void fence_async_smem() { asm volatile("fence.proxy.async.shared::cta;" ::: "memory"); }
__device__ __forceinline__ void fence_async_global() { asm volatile("fence.proxy.async.global;" ::: "memory"); }
__device__ __forceinline__ uint32_t ld_cnt(Scratch* S, int c) { uint32_t v; asm volatile("ld.relaxed.gpu.global.u32 %0, [%1];" : "=r"(v) : "l"(S->cnt + c * 32) : "memory"); return v; }
__device__ __forceinline__ void signal(Scratch* S, int c, uint32_t inc) { asm volatile("red.release.gpu.global.add.u32 [%0], %1;" :: "l"(S->cnt + c * 32), "r"(inc) : "memory"); }
__device__ __forceinline__ bool reached(Scratch* S, int c, uint32_t ep) { return ld_cnt(S, c) - ep >= EPOCH; }
__device__ __forceinline__ void await(Scratch* S, int c, uint32_t ep) { while (!reached(S, c, ep)) { } }
__device__ __forceinline__ void bar_sync(int id, int n) { asm volatile("bar.sync %0, %1;" :: "r"(id), "r"(n) : "memory"); }
__device__ __forceinline__ void bar_arrive(int id, int n) { asm volatile("bar.arrive %0, %1;" :: "r"(id), "r"(n) : "memory"); }
__device__ __forceinline__ void wg_fence() { asm volatile("wgmma.fence.sync.aligned;" ::: "memory"); }
__device__ __forceinline__ void wg_commit() { asm volatile("wgmma.commit_group.sync.aligned;" ::: "memory"); }
template <int N> __device__ __forceinline__ void wg_wait() { asm volatile("wgmma.wait_group.sync.aligned %0;" :: "n"(N) : "memory"); }
template <int N> __device__ __forceinline__ void pin_regs(float* a) {
#pragma unroll
  for (int i = 0; i < N; i++) asm volatile("" : "+f"(a[i]) :: "memory");
}
__device__ __forceinline__ uint64_t make_desc(uint32_t addr, uint32_t lbo, uint32_t sbo, uint32_t swz) {
  return (uint64_t)((addr & 0x3FFFF) >> 4) | ((uint64_t)(lbo >> 4) << 16) | ((uint64_t)(sbo >> 4) << 32) | ((uint64_t)swz << 62);
}
__device__ __forceinline__ uint32_t pack_bf16(float lo, float hi) { uint32_t r; asm("cvt.rn.bf16x2.f32 %0, %1, %2;" : "=r"(r) : "f"(hi), "f"(lo)); return r; }
__device__ __forceinline__ float bf_lo(uint32_t p) { return __uint_as_float(p << 16); }
__device__ __forceinline__ float bf_hi(uint32_t p) { return __uint_as_float(p & 0xffff0000u); }
__device__ __forceinline__ float round_bf16(float v) { return bf_lo(pack_bf16(v, 0.f)); }
__device__ __forceinline__ uint32_t bmul2(uint32_t a, uint32_t b) { uint32_t r; asm("mul.rn.bf16x2 %0, %1, %2;" : "=r"(r) : "r"(a), "r"(b)); return r; }
__device__ __forceinline__ uint32_t badd2(uint32_t a, uint32_t b) { uint32_t r; asm("add.rn.bf16x2 %0, %1, %2;" : "=r"(r) : "r"(a), "r"(b)); return r; }
__device__ __forceinline__ uint32_t bfma2(uint32_t a, uint32_t b, uint32_t c) { uint32_t r; asm("fma.rn.bf16x2 %0, %1, %2, %3;" : "=r"(r) : "r"(a), "r"(b), "r"(c)); return r; }
__device__ __forceinline__ uint32_t bsub2(uint32_t a, uint32_t b) { uint32_t r; asm("sub.rn.bf16x2 %0, %1, %2;" : "=r"(r) : "r"(a), "r"(b)); return r; }
__device__ __forceinline__ float tanh_fast(float v) { float r; asm("tanh.approx.f32 %0, %1;" : "=f"(r) : "f"(v)); return r; }
__device__ __forceinline__ float gelu_half(float h) {
  return fmaf(h, tanh_fast(h * fmaf(h * h, 8.0f * 0.7978845608028654f * 0.044715f, 2.0f * 0.7978845608028654f)), h);
}
__device__ __forceinline__ float silu_half(float h) { return fmaf(h, tanh_fast(h), h); }
__device__ __forceinline__ uint32_t ldg32(const void* p) { uint32_t v; asm volatile("ld.global.u32 %0, [%1];" : "=r"(v) : "l"(p) : "memory"); return v; }
__device__ __forceinline__ uint32_t lds32(uint32_t a) { uint32_t v; asm volatile("ld.shared.u32 %0, [%1];" : "=r"(v) : "r"(a) : "memory"); return v; }
__device__ __forceinline__ uint32_t lds16(uint32_t a) { uint32_t v; asm volatile("ld.shared.u16 %0, [%1];" : "=r"(v) : "r"(a) : "memory"); return v; }
__device__ __forceinline__ uint4 lds128(uint32_t a) { uint4 v; asm volatile("ld.shared.v4.u32 {%0,%1,%2,%3}, [%4];" : "=r"(v.x), "=r"(v.y), "=r"(v.z), "=r"(v.w) : "r"(a) : "memory"); return v; }
__device__ __forceinline__ void sts128(uint32_t a, uint32_t x, uint32_t y, uint32_t z, uint32_t w) {
  asm volatile("st.shared.v4.u32 [%0], {%1,%2,%3,%4};" :: "r"(a), "r"(x), "r"(y), "r"(z), "r"(w) : "memory");
}
__device__ __forceinline__ void sts32(uint32_t a, uint32_t v) { asm volatile("st.shared.u32 [%0], %1;" :: "r"(a), "r"(v) : "memory"); }
__device__ __forceinline__ void ldsm4(uint32_t* r, uint32_t a) {
  asm volatile("ldmatrix.sync.aligned.m8n8.x4.shared.b16 {%0,%1,%2,%3}, [%4];" : "=r"(r[0]), "=r"(r[1]), "=r"(r[2]), "=r"(r[3]) : "r"(a) : "memory");
}
__device__ __forceinline__ void ldsm2(uint32_t* r, uint32_t a) {
  asm volatile("ldmatrix.sync.aligned.m8n8.x2.shared.b16 {%0,%1}, [%2];" : "=r"(r[0]), "=r"(r[1]) : "r"(a) : "memory");
}
__device__ __forceinline__ void ldsm4t(uint32_t* r, uint32_t a) {
  asm volatile("ldmatrix.sync.aligned.m8n8.x4.trans.shared.b16 {%0,%1,%2,%3}, [%4];" : "=r"(r[0]), "=r"(r[1]), "=r"(r[2]), "=r"(r[3]) : "r"(a) : "memory");
}
__device__ __forceinline__ void ldsm2t(uint32_t* r, uint32_t a) {
  asm volatile("ldmatrix.sync.aligned.m8n8.x2.trans.shared.b16 {%0,%1}, [%2];" : "=r"(r[0]), "=r"(r[1]) : "r"(a) : "memory");
}
__device__ __forceinline__ void stsm4(uint32_t a, uint32_t r0, uint32_t r1, uint32_t r2, uint32_t r3) {
  asm volatile("stmatrix.sync.aligned.m8n8.x4.shared.b16 [%0], {%1,%2,%3,%4};" :: "r"(a), "r"(r0), "r"(r1), "r"(r2), "r"(r3) : "memory");
}
__device__ __forceinline__ void stsm2(uint32_t a, uint32_t r0, uint32_t r1) {
  asm volatile("stmatrix.sync.aligned.m8n8.x2.shared.b16 [%0], {%1,%2};" :: "r"(a), "r"(r0), "r"(r1) : "memory");
}
__device__ __forceinline__ void stsm4t(uint32_t a, uint32_t r0, uint32_t r1, uint32_t r2, uint32_t r3) {
  asm volatile("stmatrix.sync.aligned.m8n8.x4.trans.shared.b16 [%0], {%1,%2,%3,%4};" :: "r"(a), "r"(r0), "r"(r1), "r"(r2), "r"(r3) : "memory");
}

__device__ __forceinline__ void wgmma_ss_n144_t10(float* d, uint64_t da, uint64_t db, int sd) {
  asm volatile("{ .reg .pred p; setp.ne.b32 p, %74, 0;\n"
      "wgmma.mma_async.sync.aligned.m64n144k16.f32.bf16.bf16 {"
      "%0,%1,%2,%3,%4,%5,%6,%7,%8,%9,%10,%11,%12,%13,%14,%15,"
      "%16,%17,%18,%19,%20,%21,%22,%23,%24,%25,%26,%27,%28,%29,%30,%31,"
      "%32,%33,%34,%35,%36,%37,%38,%39,%40,%41,%42,%43,%44,%45,%46,%47,"
      "%48,%49,%50,%51,%52,%53,%54,%55,%56,%57,%58,%59,%60,%61,%62,%63,"
      "%64,%65,%66,%67,%68,%69,%70,%71"
      "}, %72, %73, p, 1, 1, 1, 0; }"
    : "+f"(d[0]), "+f"(d[1]), "+f"(d[2]), "+f"(d[3]), "+f"(d[4]), "+f"(d[5]), "+f"(d[6]), "+f"(d[7]),
      "+f"(d[8]), "+f"(d[9]), "+f"(d[10]), "+f"(d[11]), "+f"(d[12]), "+f"(d[13]), "+f"(d[14]), "+f"(d[15]),
      "+f"(d[16]), "+f"(d[17]), "+f"(d[18]), "+f"(d[19]), "+f"(d[20]), "+f"(d[21]), "+f"(d[22]), "+f"(d[23]),
      "+f"(d[24]), "+f"(d[25]), "+f"(d[26]), "+f"(d[27]), "+f"(d[28]), "+f"(d[29]), "+f"(d[30]), "+f"(d[31]),
      "+f"(d[32]), "+f"(d[33]), "+f"(d[34]), "+f"(d[35]), "+f"(d[36]), "+f"(d[37]), "+f"(d[38]), "+f"(d[39]),
      "+f"(d[40]), "+f"(d[41]), "+f"(d[42]), "+f"(d[43]), "+f"(d[44]), "+f"(d[45]), "+f"(d[46]), "+f"(d[47]),
      "+f"(d[48]), "+f"(d[49]), "+f"(d[50]), "+f"(d[51]), "+f"(d[52]), "+f"(d[53]), "+f"(d[54]), "+f"(d[55]),
      "+f"(d[56]), "+f"(d[57]), "+f"(d[58]), "+f"(d[59]), "+f"(d[60]), "+f"(d[61]), "+f"(d[62]), "+f"(d[63]),
      "+f"(d[64]), "+f"(d[65]), "+f"(d[66]), "+f"(d[67]), "+f"(d[68]), "+f"(d[69]), "+f"(d[70]), "+f"(d[71])
    : "l"(da), "l"(db), "r"(sd));
}

__device__ __forceinline__ void wgmma_ss_n160_t11(float* d, uint64_t da, uint64_t db, int sd) {
  asm volatile("{ .reg .pred p; setp.ne.b32 p, %82, 0;\n"
      "wgmma.mma_async.sync.aligned.m64n160k16.f32.bf16.bf16 {"
      "%0,%1,%2,%3,%4,%5,%6,%7,%8,%9,%10,%11,%12,%13,%14,%15,"
      "%16,%17,%18,%19,%20,%21,%22,%23,%24,%25,%26,%27,%28,%29,%30,%31,"
      "%32,%33,%34,%35,%36,%37,%38,%39,%40,%41,%42,%43,%44,%45,%46,%47,"
      "%48,%49,%50,%51,%52,%53,%54,%55,%56,%57,%58,%59,%60,%61,%62,%63,"
      "%64,%65,%66,%67,%68,%69,%70,%71,%72,%73,%74,%75,%76,%77,%78,%79"
      "}, %80, %81, p, 1, 1, 1, 1; }"
    : "+f"(d[0]), "+f"(d[1]), "+f"(d[2]), "+f"(d[3]), "+f"(d[4]), "+f"(d[5]), "+f"(d[6]), "+f"(d[7]),
      "+f"(d[8]), "+f"(d[9]), "+f"(d[10]), "+f"(d[11]), "+f"(d[12]), "+f"(d[13]), "+f"(d[14]), "+f"(d[15]),
      "+f"(d[16]), "+f"(d[17]), "+f"(d[18]), "+f"(d[19]), "+f"(d[20]), "+f"(d[21]), "+f"(d[22]), "+f"(d[23]),
      "+f"(d[24]), "+f"(d[25]), "+f"(d[26]), "+f"(d[27]), "+f"(d[28]), "+f"(d[29]), "+f"(d[30]), "+f"(d[31]),
      "+f"(d[32]), "+f"(d[33]), "+f"(d[34]), "+f"(d[35]), "+f"(d[36]), "+f"(d[37]), "+f"(d[38]), "+f"(d[39]),
      "+f"(d[40]), "+f"(d[41]), "+f"(d[42]), "+f"(d[43]), "+f"(d[44]), "+f"(d[45]), "+f"(d[46]), "+f"(d[47]),
      "+f"(d[48]), "+f"(d[49]), "+f"(d[50]), "+f"(d[51]), "+f"(d[52]), "+f"(d[53]), "+f"(d[54]), "+f"(d[55]),
      "+f"(d[56]), "+f"(d[57]), "+f"(d[58]), "+f"(d[59]), "+f"(d[60]), "+f"(d[61]), "+f"(d[62]), "+f"(d[63]),
      "+f"(d[64]), "+f"(d[65]), "+f"(d[66]), "+f"(d[67]), "+f"(d[68]), "+f"(d[69]), "+f"(d[70]), "+f"(d[71]),
      "+f"(d[72]), "+f"(d[73]), "+f"(d[74]), "+f"(d[75]), "+f"(d[76]), "+f"(d[77]), "+f"(d[78]), "+f"(d[79])
    : "l"(da), "l"(db), "r"(sd));
}

__device__ __forceinline__ void wgmma_ss_n96_t11(float* d, uint64_t da, uint64_t db, int sd) {
  asm volatile("{ .reg .pred p; setp.ne.b32 p, %50, 0;\n"
      "wgmma.mma_async.sync.aligned.m64n96k16.f32.bf16.bf16 {"
      "%0,%1,%2,%3,%4,%5,%6,%7,%8,%9,%10,%11,%12,%13,%14,%15,"
      "%16,%17,%18,%19,%20,%21,%22,%23,%24,%25,%26,%27,%28,%29,%30,%31,"
      "%32,%33,%34,%35,%36,%37,%38,%39,%40,%41,%42,%43,%44,%45,%46,%47"
      "}, %48, %49, p, 1, 1, 1, 1; }"
    : "+f"(d[0]), "+f"(d[1]), "+f"(d[2]), "+f"(d[3]), "+f"(d[4]), "+f"(d[5]), "+f"(d[6]), "+f"(d[7]),
      "+f"(d[8]), "+f"(d[9]), "+f"(d[10]), "+f"(d[11]), "+f"(d[12]), "+f"(d[13]), "+f"(d[14]), "+f"(d[15]),
      "+f"(d[16]), "+f"(d[17]), "+f"(d[18]), "+f"(d[19]), "+f"(d[20]), "+f"(d[21]), "+f"(d[22]), "+f"(d[23]),
      "+f"(d[24]), "+f"(d[25]), "+f"(d[26]), "+f"(d[27]), "+f"(d[28]), "+f"(d[29]), "+f"(d[30]), "+f"(d[31]),
      "+f"(d[32]), "+f"(d[33]), "+f"(d[34]), "+f"(d[35]), "+f"(d[36]), "+f"(d[37]), "+f"(d[38]), "+f"(d[39]),
      "+f"(d[40]), "+f"(d[41]), "+f"(d[42]), "+f"(d[43]), "+f"(d[44]), "+f"(d[45]), "+f"(d[46]), "+f"(d[47])
    : "l"(da), "l"(db), "r"(sd));
}

__device__ __forceinline__ void wgmma_rs_n16(float* d, const uint32_t* a, uint64_t db, int sd) {
  asm volatile("{ .reg .pred p; setp.ne.b32 p, %13, 0;\n"
      "wgmma.mma_async.sync.aligned.m64n16k16.f32.bf16.bf16 {"
      "%0,%1,%2,%3,%4,%5,%6,%7"
      "}, {%8,%9,%10,%11}, %12, p, 1, 1, 0; }"
    : "+f"(d[0]), "+f"(d[1]), "+f"(d[2]), "+f"(d[3]), "+f"(d[4]), "+f"(d[5]), "+f"(d[6]), "+f"(d[7])
    : "r"(a[0]), "r"(a[1]), "r"(a[2]), "r"(a[3]), "l"(db), "r"(sd));
}

__device__ __forceinline__ void wgmma_rs_n32(float* d, const uint32_t* a, uint64_t db, int sd) {
  asm volatile("{ .reg .pred p; setp.ne.b32 p, %21, 0;\n"
      "wgmma.mma_async.sync.aligned.m64n32k16.f32.bf16.bf16 {"
      "%0,%1,%2,%3,%4,%5,%6,%7,%8,%9,%10,%11,%12,%13,%14,%15"
      "}, {%16,%17,%18,%19}, %20, p, 1, 1, 0; }"
    : "+f"(d[0]), "+f"(d[1]), "+f"(d[2]), "+f"(d[3]), "+f"(d[4]), "+f"(d[5]), "+f"(d[6]), "+f"(d[7]),
      "+f"(d[8]), "+f"(d[9]), "+f"(d[10]), "+f"(d[11]), "+f"(d[12]), "+f"(d[13]), "+f"(d[14]), "+f"(d[15])
    : "r"(a[0]), "r"(a[1]), "r"(a[2]), "r"(a[3]), "l"(db), "r"(sd));
}

__device__ __forceinline__ void wgmma_rs_n48(float* d, const uint32_t* a, uint64_t db, int sd) {
  asm volatile("{ .reg .pred p; setp.ne.b32 p, %29, 0;\n"
      "wgmma.mma_async.sync.aligned.m64n48k16.f32.bf16.bf16 {"
      "%0,%1,%2,%3,%4,%5,%6,%7,%8,%9,%10,%11,%12,%13,%14,%15,"
      "%16,%17,%18,%19,%20,%21,%22,%23"
      "}, {%24,%25,%26,%27}, %28, p, 1, 1, 0; }"
    : "+f"(d[0]), "+f"(d[1]), "+f"(d[2]), "+f"(d[3]), "+f"(d[4]), "+f"(d[5]), "+f"(d[6]), "+f"(d[7]),
      "+f"(d[8]), "+f"(d[9]), "+f"(d[10]), "+f"(d[11]), "+f"(d[12]), "+f"(d[13]), "+f"(d[14]), "+f"(d[15]),
      "+f"(d[16]), "+f"(d[17]), "+f"(d[18]), "+f"(d[19]), "+f"(d[20]), "+f"(d[21]), "+f"(d[22]), "+f"(d[23])
    : "r"(a[0]), "r"(a[1]), "r"(a[2]), "r"(a[3]), "l"(db), "r"(sd));
}

__device__ __forceinline__ void wgmma_rs_n64(float* d, const uint32_t* a, uint64_t db, int sd) {
  asm volatile("{ .reg .pred p; setp.ne.b32 p, %37, 0;\n"
      "wgmma.mma_async.sync.aligned.m64n64k16.f32.bf16.bf16 {"
      "%0,%1,%2,%3,%4,%5,%6,%7,%8,%9,%10,%11,%12,%13,%14,%15,"
      "%16,%17,%18,%19,%20,%21,%22,%23,%24,%25,%26,%27,%28,%29,%30,%31"
      "}, {%32,%33,%34,%35}, %36, p, 1, 1, 0; }"
    : "+f"(d[0]), "+f"(d[1]), "+f"(d[2]), "+f"(d[3]), "+f"(d[4]), "+f"(d[5]), "+f"(d[6]), "+f"(d[7]),
      "+f"(d[8]), "+f"(d[9]), "+f"(d[10]), "+f"(d[11]), "+f"(d[12]), "+f"(d[13]), "+f"(d[14]), "+f"(d[15]),
      "+f"(d[16]), "+f"(d[17]), "+f"(d[18]), "+f"(d[19]), "+f"(d[20]), "+f"(d[21]), "+f"(d[22]), "+f"(d[23]),
      "+f"(d[24]), "+f"(d[25]), "+f"(d[26]), "+f"(d[27]), "+f"(d[28]), "+f"(d[29]), "+f"(d[30]), "+f"(d[31])
    : "r"(a[0]), "r"(a[1]), "r"(a[2]), "r"(a[3]), "l"(db), "r"(sd));
}

__device__ __forceinline__ void wgmma_rs_n80(float* d, const uint32_t* a, uint64_t db, int sd) {
  asm volatile("{ .reg .pred p; setp.ne.b32 p, %45, 0;\n"
      "wgmma.mma_async.sync.aligned.m64n80k16.f32.bf16.bf16 {"
      "%0,%1,%2,%3,%4,%5,%6,%7,%8,%9,%10,%11,%12,%13,%14,%15,"
      "%16,%17,%18,%19,%20,%21,%22,%23,%24,%25,%26,%27,%28,%29,%30,%31,"
      "%32,%33,%34,%35,%36,%37,%38,%39"
      "}, {%40,%41,%42,%43}, %44, p, 1, 1, 0; }"
    : "+f"(d[0]), "+f"(d[1]), "+f"(d[2]), "+f"(d[3]), "+f"(d[4]), "+f"(d[5]), "+f"(d[6]), "+f"(d[7]),
      "+f"(d[8]), "+f"(d[9]), "+f"(d[10]), "+f"(d[11]), "+f"(d[12]), "+f"(d[13]), "+f"(d[14]), "+f"(d[15]),
      "+f"(d[16]), "+f"(d[17]), "+f"(d[18]), "+f"(d[19]), "+f"(d[20]), "+f"(d[21]), "+f"(d[22]), "+f"(d[23]),
      "+f"(d[24]), "+f"(d[25]), "+f"(d[26]), "+f"(d[27]), "+f"(d[28]), "+f"(d[29]), "+f"(d[30]), "+f"(d[31]),
      "+f"(d[32]), "+f"(d[33]), "+f"(d[34]), "+f"(d[35]), "+f"(d[36]), "+f"(d[37]), "+f"(d[38]), "+f"(d[39])
    : "r"(a[0]), "r"(a[1]), "r"(a[2]), "r"(a[3]), "l"(db), "r"(sd));
}

__device__ __forceinline__ void wgmma_rs_n96(float* d, const uint32_t* a, uint64_t db, int sd) {
  asm volatile("{ .reg .pred p; setp.ne.b32 p, %53, 0;\n"
      "wgmma.mma_async.sync.aligned.m64n96k16.f32.bf16.bf16 {"
      "%0,%1,%2,%3,%4,%5,%6,%7,%8,%9,%10,%11,%12,%13,%14,%15,"
      "%16,%17,%18,%19,%20,%21,%22,%23,%24,%25,%26,%27,%28,%29,%30,%31,"
      "%32,%33,%34,%35,%36,%37,%38,%39,%40,%41,%42,%43,%44,%45,%46,%47"
      "}, {%48,%49,%50,%51}, %52, p, 1, 1, 0; }"
    : "+f"(d[0]), "+f"(d[1]), "+f"(d[2]), "+f"(d[3]), "+f"(d[4]), "+f"(d[5]), "+f"(d[6]), "+f"(d[7]),
      "+f"(d[8]), "+f"(d[9]), "+f"(d[10]), "+f"(d[11]), "+f"(d[12]), "+f"(d[13]), "+f"(d[14]), "+f"(d[15]),
      "+f"(d[16]), "+f"(d[17]), "+f"(d[18]), "+f"(d[19]), "+f"(d[20]), "+f"(d[21]), "+f"(d[22]), "+f"(d[23]),
      "+f"(d[24]), "+f"(d[25]), "+f"(d[26]), "+f"(d[27]), "+f"(d[28]), "+f"(d[29]), "+f"(d[30]), "+f"(d[31]),
      "+f"(d[32]), "+f"(d[33]), "+f"(d[34]), "+f"(d[35]), "+f"(d[36]), "+f"(d[37]), "+f"(d[38]), "+f"(d[39]),
      "+f"(d[40]), "+f"(d[41]), "+f"(d[42]), "+f"(d[43]), "+f"(d[44]), "+f"(d[45]), "+f"(d[46]), "+f"(d[47])
    : "r"(a[0]), "r"(a[1]), "r"(a[2]), "r"(a[3]), "l"(db), "r"(sd));
}

__device__ __forceinline__ void wgmma_rs_n112(float* d, const uint32_t* a, uint64_t db, int sd) {
  asm volatile("{ .reg .pred p; setp.ne.b32 p, %61, 0;\n"
      "wgmma.mma_async.sync.aligned.m64n112k16.f32.bf16.bf16 {"
      "%0,%1,%2,%3,%4,%5,%6,%7,%8,%9,%10,%11,%12,%13,%14,%15,"
      "%16,%17,%18,%19,%20,%21,%22,%23,%24,%25,%26,%27,%28,%29,%30,%31,"
      "%32,%33,%34,%35,%36,%37,%38,%39,%40,%41,%42,%43,%44,%45,%46,%47,"
      "%48,%49,%50,%51,%52,%53,%54,%55"
      "}, {%56,%57,%58,%59}, %60, p, 1, 1, 0; }"
    : "+f"(d[0]), "+f"(d[1]), "+f"(d[2]), "+f"(d[3]), "+f"(d[4]), "+f"(d[5]), "+f"(d[6]), "+f"(d[7]),
      "+f"(d[8]), "+f"(d[9]), "+f"(d[10]), "+f"(d[11]), "+f"(d[12]), "+f"(d[13]), "+f"(d[14]), "+f"(d[15]),
      "+f"(d[16]), "+f"(d[17]), "+f"(d[18]), "+f"(d[19]), "+f"(d[20]), "+f"(d[21]), "+f"(d[22]), "+f"(d[23]),
      "+f"(d[24]), "+f"(d[25]), "+f"(d[26]), "+f"(d[27]), "+f"(d[28]), "+f"(d[29]), "+f"(d[30]), "+f"(d[31]),
      "+f"(d[32]), "+f"(d[33]), "+f"(d[34]), "+f"(d[35]), "+f"(d[36]), "+f"(d[37]), "+f"(d[38]), "+f"(d[39]),
      "+f"(d[40]), "+f"(d[41]), "+f"(d[42]), "+f"(d[43]), "+f"(d[44]), "+f"(d[45]), "+f"(d[46]), "+f"(d[47]),
      "+f"(d[48]), "+f"(d[49]), "+f"(d[50]), "+f"(d[51]), "+f"(d[52]), "+f"(d[53]), "+f"(d[54]), "+f"(d[55])
    : "r"(a[0]), "r"(a[1]), "r"(a[2]), "r"(a[3]), "l"(db), "r"(sd));
}

__device__ __forceinline__ void wgmma_rs_n128(float* d, const uint32_t* a, uint64_t db, int sd) {
  asm volatile("{ .reg .pred p; setp.ne.b32 p, %69, 0;\n"
      "wgmma.mma_async.sync.aligned.m64n128k16.f32.bf16.bf16 {"
      "%0,%1,%2,%3,%4,%5,%6,%7,%8,%9,%10,%11,%12,%13,%14,%15,"
      "%16,%17,%18,%19,%20,%21,%22,%23,%24,%25,%26,%27,%28,%29,%30,%31,"
      "%32,%33,%34,%35,%36,%37,%38,%39,%40,%41,%42,%43,%44,%45,%46,%47,"
      "%48,%49,%50,%51,%52,%53,%54,%55,%56,%57,%58,%59,%60,%61,%62,%63"
      "}, {%64,%65,%66,%67}, %68, p, 1, 1, 0; }"
    : "+f"(d[0]), "+f"(d[1]), "+f"(d[2]), "+f"(d[3]), "+f"(d[4]), "+f"(d[5]), "+f"(d[6]), "+f"(d[7]),
      "+f"(d[8]), "+f"(d[9]), "+f"(d[10]), "+f"(d[11]), "+f"(d[12]), "+f"(d[13]), "+f"(d[14]), "+f"(d[15]),
      "+f"(d[16]), "+f"(d[17]), "+f"(d[18]), "+f"(d[19]), "+f"(d[20]), "+f"(d[21]), "+f"(d[22]), "+f"(d[23]),
      "+f"(d[24]), "+f"(d[25]), "+f"(d[26]), "+f"(d[27]), "+f"(d[28]), "+f"(d[29]), "+f"(d[30]), "+f"(d[31]),
      "+f"(d[32]), "+f"(d[33]), "+f"(d[34]), "+f"(d[35]), "+f"(d[36]), "+f"(d[37]), "+f"(d[38]), "+f"(d[39]),
      "+f"(d[40]), "+f"(d[41]), "+f"(d[42]), "+f"(d[43]), "+f"(d[44]), "+f"(d[45]), "+f"(d[46]), "+f"(d[47]),
      "+f"(d[48]), "+f"(d[49]), "+f"(d[50]), "+f"(d[51]), "+f"(d[52]), "+f"(d[53]), "+f"(d[54]), "+f"(d[55]),
      "+f"(d[56]), "+f"(d[57]), "+f"(d[58]), "+f"(d[59]), "+f"(d[60]), "+f"(d[61]), "+f"(d[62]), "+f"(d[63])
    : "r"(a[0]), "r"(a[1]), "r"(a[2]), "r"(a[3]), "l"(db), "r"(sd));
}

__device__ __forceinline__ void wgmma_rs_n144(float* d, const uint32_t* a, uint64_t db, int sd) {
  asm volatile("{ .reg .pred p; setp.ne.b32 p, %77, 0;\n"
      "wgmma.mma_async.sync.aligned.m64n144k16.f32.bf16.bf16 {"
      "%0,%1,%2,%3,%4,%5,%6,%7,%8,%9,%10,%11,%12,%13,%14,%15,"
      "%16,%17,%18,%19,%20,%21,%22,%23,%24,%25,%26,%27,%28,%29,%30,%31,"
      "%32,%33,%34,%35,%36,%37,%38,%39,%40,%41,%42,%43,%44,%45,%46,%47,"
      "%48,%49,%50,%51,%52,%53,%54,%55,%56,%57,%58,%59,%60,%61,%62,%63,"
      "%64,%65,%66,%67,%68,%69,%70,%71"
      "}, {%72,%73,%74,%75}, %76, p, 1, 1, 0; }"
    : "+f"(d[0]), "+f"(d[1]), "+f"(d[2]), "+f"(d[3]), "+f"(d[4]), "+f"(d[5]), "+f"(d[6]), "+f"(d[7]),
      "+f"(d[8]), "+f"(d[9]), "+f"(d[10]), "+f"(d[11]), "+f"(d[12]), "+f"(d[13]), "+f"(d[14]), "+f"(d[15]),
      "+f"(d[16]), "+f"(d[17]), "+f"(d[18]), "+f"(d[19]), "+f"(d[20]), "+f"(d[21]), "+f"(d[22]), "+f"(d[23]),
      "+f"(d[24]), "+f"(d[25]), "+f"(d[26]), "+f"(d[27]), "+f"(d[28]), "+f"(d[29]), "+f"(d[30]), "+f"(d[31]),
      "+f"(d[32]), "+f"(d[33]), "+f"(d[34]), "+f"(d[35]), "+f"(d[36]), "+f"(d[37]), "+f"(d[38]), "+f"(d[39]),
      "+f"(d[40]), "+f"(d[41]), "+f"(d[42]), "+f"(d[43]), "+f"(d[44]), "+f"(d[45]), "+f"(d[46]), "+f"(d[47]),
      "+f"(d[48]), "+f"(d[49]), "+f"(d[50]), "+f"(d[51]), "+f"(d[52]), "+f"(d[53]), "+f"(d[54]), "+f"(d[55]),
      "+f"(d[56]), "+f"(d[57]), "+f"(d[58]), "+f"(d[59]), "+f"(d[60]), "+f"(d[61]), "+f"(d[62]), "+f"(d[63]),
      "+f"(d[64]), "+f"(d[65]), "+f"(d[66]), "+f"(d[67]), "+f"(d[68]), "+f"(d[69]), "+f"(d[70]), "+f"(d[71])
    : "r"(a[0]), "r"(a[1]), "r"(a[2]), "r"(a[3]), "l"(db), "r"(sd));
}

__device__ __forceinline__ void wgmma_rs_n160(float* d, const uint32_t* a, uint64_t db, int sd) {
  asm volatile("{ .reg .pred p; setp.ne.b32 p, %85, 0;\n"
      "wgmma.mma_async.sync.aligned.m64n160k16.f32.bf16.bf16 {"
      "%0,%1,%2,%3,%4,%5,%6,%7,%8,%9,%10,%11,%12,%13,%14,%15,"
      "%16,%17,%18,%19,%20,%21,%22,%23,%24,%25,%26,%27,%28,%29,%30,%31,"
      "%32,%33,%34,%35,%36,%37,%38,%39,%40,%41,%42,%43,%44,%45,%46,%47,"
      "%48,%49,%50,%51,%52,%53,%54,%55,%56,%57,%58,%59,%60,%61,%62,%63,"
      "%64,%65,%66,%67,%68,%69,%70,%71,%72,%73,%74,%75,%76,%77,%78,%79"
      "}, {%80,%81,%82,%83}, %84, p, 1, 1, 0; }"
    : "+f"(d[0]), "+f"(d[1]), "+f"(d[2]), "+f"(d[3]), "+f"(d[4]), "+f"(d[5]), "+f"(d[6]), "+f"(d[7]),
      "+f"(d[8]), "+f"(d[9]), "+f"(d[10]), "+f"(d[11]), "+f"(d[12]), "+f"(d[13]), "+f"(d[14]), "+f"(d[15]),
      "+f"(d[16]), "+f"(d[17]), "+f"(d[18]), "+f"(d[19]), "+f"(d[20]), "+f"(d[21]), "+f"(d[22]), "+f"(d[23]),
      "+f"(d[24]), "+f"(d[25]), "+f"(d[26]), "+f"(d[27]), "+f"(d[28]), "+f"(d[29]), "+f"(d[30]), "+f"(d[31]),
      "+f"(d[32]), "+f"(d[33]), "+f"(d[34]), "+f"(d[35]), "+f"(d[36]), "+f"(d[37]), "+f"(d[38]), "+f"(d[39]),
      "+f"(d[40]), "+f"(d[41]), "+f"(d[42]), "+f"(d[43]), "+f"(d[44]), "+f"(d[45]), "+f"(d[46]), "+f"(d[47]),
      "+f"(d[48]), "+f"(d[49]), "+f"(d[50]), "+f"(d[51]), "+f"(d[52]), "+f"(d[53]), "+f"(d[54]), "+f"(d[55]),
      "+f"(d[56]), "+f"(d[57]), "+f"(d[58]), "+f"(d[59]), "+f"(d[60]), "+f"(d[61]), "+f"(d[62]), "+f"(d[63]),
      "+f"(d[64]), "+f"(d[65]), "+f"(d[66]), "+f"(d[67]), "+f"(d[68]), "+f"(d[69]), "+f"(d[70]), "+f"(d[71]),
      "+f"(d[72]), "+f"(d[73]), "+f"(d[74]), "+f"(d[75]), "+f"(d[76]), "+f"(d[77]), "+f"(d[78]), "+f"(d[79])
    : "r"(a[0]), "r"(a[1]), "r"(a[2]), "r"(a[3]), "l"(db), "r"(sd));
}

__device__ __forceinline__ void wgmma_rs_n176(float* d, const uint32_t* a, uint64_t db, int sd) {
  asm volatile("{ .reg .pred p; setp.ne.b32 p, %93, 0;\n"
      "wgmma.mma_async.sync.aligned.m64n176k16.f32.bf16.bf16 {"
      "%0,%1,%2,%3,%4,%5,%6,%7,%8,%9,%10,%11,%12,%13,%14,%15,"
      "%16,%17,%18,%19,%20,%21,%22,%23,%24,%25,%26,%27,%28,%29,%30,%31,"
      "%32,%33,%34,%35,%36,%37,%38,%39,%40,%41,%42,%43,%44,%45,%46,%47,"
      "%48,%49,%50,%51,%52,%53,%54,%55,%56,%57,%58,%59,%60,%61,%62,%63,"
      "%64,%65,%66,%67,%68,%69,%70,%71,%72,%73,%74,%75,%76,%77,%78,%79,"
      "%80,%81,%82,%83,%84,%85,%86,%87"
      "}, {%88,%89,%90,%91}, %92, p, 1, 1, 0; }"
    : "+f"(d[0]), "+f"(d[1]), "+f"(d[2]), "+f"(d[3]), "+f"(d[4]), "+f"(d[5]), "+f"(d[6]), "+f"(d[7]),
      "+f"(d[8]), "+f"(d[9]), "+f"(d[10]), "+f"(d[11]), "+f"(d[12]), "+f"(d[13]), "+f"(d[14]), "+f"(d[15]),
      "+f"(d[16]), "+f"(d[17]), "+f"(d[18]), "+f"(d[19]), "+f"(d[20]), "+f"(d[21]), "+f"(d[22]), "+f"(d[23]),
      "+f"(d[24]), "+f"(d[25]), "+f"(d[26]), "+f"(d[27]), "+f"(d[28]), "+f"(d[29]), "+f"(d[30]), "+f"(d[31]),
      "+f"(d[32]), "+f"(d[33]), "+f"(d[34]), "+f"(d[35]), "+f"(d[36]), "+f"(d[37]), "+f"(d[38]), "+f"(d[39]),
      "+f"(d[40]), "+f"(d[41]), "+f"(d[42]), "+f"(d[43]), "+f"(d[44]), "+f"(d[45]), "+f"(d[46]), "+f"(d[47]),
      "+f"(d[48]), "+f"(d[49]), "+f"(d[50]), "+f"(d[51]), "+f"(d[52]), "+f"(d[53]), "+f"(d[54]), "+f"(d[55]),
      "+f"(d[56]), "+f"(d[57]), "+f"(d[58]), "+f"(d[59]), "+f"(d[60]), "+f"(d[61]), "+f"(d[62]), "+f"(d[63]),
      "+f"(d[64]), "+f"(d[65]), "+f"(d[66]), "+f"(d[67]), "+f"(d[68]), "+f"(d[69]), "+f"(d[70]), "+f"(d[71]),
      "+f"(d[72]), "+f"(d[73]), "+f"(d[74]), "+f"(d[75]), "+f"(d[76]), "+f"(d[77]), "+f"(d[78]), "+f"(d[79]),
      "+f"(d[80]), "+f"(d[81]), "+f"(d[82]), "+f"(d[83]), "+f"(d[84]), "+f"(d[85]), "+f"(d[86]), "+f"(d[87])
    : "r"(a[0]), "r"(a[1]), "r"(a[2]), "r"(a[3]), "l"(db), "r"(sd));
}

__device__ __forceinline__ void wgmma_rs_n192(float* d, const uint32_t* a, uint64_t db, int sd) {
  asm volatile("{ .reg .pred p; setp.ne.b32 p, %101, 0;\n"
      "wgmma.mma_async.sync.aligned.m64n192k16.f32.bf16.bf16 {"
      "%0,%1,%2,%3,%4,%5,%6,%7,%8,%9,%10,%11,%12,%13,%14,%15,"
      "%16,%17,%18,%19,%20,%21,%22,%23,%24,%25,%26,%27,%28,%29,%30,%31,"
      "%32,%33,%34,%35,%36,%37,%38,%39,%40,%41,%42,%43,%44,%45,%46,%47,"
      "%48,%49,%50,%51,%52,%53,%54,%55,%56,%57,%58,%59,%60,%61,%62,%63,"
      "%64,%65,%66,%67,%68,%69,%70,%71,%72,%73,%74,%75,%76,%77,%78,%79,"
      "%80,%81,%82,%83,%84,%85,%86,%87,%88,%89,%90,%91,%92,%93,%94,%95"
      "}, {%96,%97,%98,%99}, %100, p, 1, 1, 0; }"
    : "+f"(d[0]), "+f"(d[1]), "+f"(d[2]), "+f"(d[3]), "+f"(d[4]), "+f"(d[5]), "+f"(d[6]), "+f"(d[7]),
      "+f"(d[8]), "+f"(d[9]), "+f"(d[10]), "+f"(d[11]), "+f"(d[12]), "+f"(d[13]), "+f"(d[14]), "+f"(d[15]),
      "+f"(d[16]), "+f"(d[17]), "+f"(d[18]), "+f"(d[19]), "+f"(d[20]), "+f"(d[21]), "+f"(d[22]), "+f"(d[23]),
      "+f"(d[24]), "+f"(d[25]), "+f"(d[26]), "+f"(d[27]), "+f"(d[28]), "+f"(d[29]), "+f"(d[30]), "+f"(d[31]),
      "+f"(d[32]), "+f"(d[33]), "+f"(d[34]), "+f"(d[35]), "+f"(d[36]), "+f"(d[37]), "+f"(d[38]), "+f"(d[39]),
      "+f"(d[40]), "+f"(d[41]), "+f"(d[42]), "+f"(d[43]), "+f"(d[44]), "+f"(d[45]), "+f"(d[46]), "+f"(d[47]),
      "+f"(d[48]), "+f"(d[49]), "+f"(d[50]), "+f"(d[51]), "+f"(d[52]), "+f"(d[53]), "+f"(d[54]), "+f"(d[55]),
      "+f"(d[56]), "+f"(d[57]), "+f"(d[58]), "+f"(d[59]), "+f"(d[60]), "+f"(d[61]), "+f"(d[62]), "+f"(d[63]),
      "+f"(d[64]), "+f"(d[65]), "+f"(d[66]), "+f"(d[67]), "+f"(d[68]), "+f"(d[69]), "+f"(d[70]), "+f"(d[71]),
      "+f"(d[72]), "+f"(d[73]), "+f"(d[74]), "+f"(d[75]), "+f"(d[76]), "+f"(d[77]), "+f"(d[78]), "+f"(d[79]),
      "+f"(d[80]), "+f"(d[81]), "+f"(d[82]), "+f"(d[83]), "+f"(d[84]), "+f"(d[85]), "+f"(d[86]), "+f"(d[87]),
      "+f"(d[88]), "+f"(d[89]), "+f"(d[90]), "+f"(d[91]), "+f"(d[92]), "+f"(d[93]), "+f"(d[94]), "+f"(d[95])
    : "r"(a[0]), "r"(a[1]), "r"(a[2]), "r"(a[3]), "l"(db), "r"(sd));
}

__device__ __forceinline__ void wgmma_rs_n208(float* d, const uint32_t* a, uint64_t db, int sd) {
  asm volatile("{ .reg .pred p; setp.ne.b32 p, %109, 0;\n"
      "wgmma.mma_async.sync.aligned.m64n208k16.f32.bf16.bf16 {"
      "%0,%1,%2,%3,%4,%5,%6,%7,%8,%9,%10,%11,%12,%13,%14,%15,"
      "%16,%17,%18,%19,%20,%21,%22,%23,%24,%25,%26,%27,%28,%29,%30,%31,"
      "%32,%33,%34,%35,%36,%37,%38,%39,%40,%41,%42,%43,%44,%45,%46,%47,"
      "%48,%49,%50,%51,%52,%53,%54,%55,%56,%57,%58,%59,%60,%61,%62,%63,"
      "%64,%65,%66,%67,%68,%69,%70,%71,%72,%73,%74,%75,%76,%77,%78,%79,"
      "%80,%81,%82,%83,%84,%85,%86,%87,%88,%89,%90,%91,%92,%93,%94,%95,"
      "%96,%97,%98,%99,%100,%101,%102,%103"
      "}, {%104,%105,%106,%107}, %108, p, 1, 1, 0; }"
    : "+f"(d[0]), "+f"(d[1]), "+f"(d[2]), "+f"(d[3]), "+f"(d[4]), "+f"(d[5]), "+f"(d[6]), "+f"(d[7]),
      "+f"(d[8]), "+f"(d[9]), "+f"(d[10]), "+f"(d[11]), "+f"(d[12]), "+f"(d[13]), "+f"(d[14]), "+f"(d[15]),
      "+f"(d[16]), "+f"(d[17]), "+f"(d[18]), "+f"(d[19]), "+f"(d[20]), "+f"(d[21]), "+f"(d[22]), "+f"(d[23]),
      "+f"(d[24]), "+f"(d[25]), "+f"(d[26]), "+f"(d[27]), "+f"(d[28]), "+f"(d[29]), "+f"(d[30]), "+f"(d[31]),
      "+f"(d[32]), "+f"(d[33]), "+f"(d[34]), "+f"(d[35]), "+f"(d[36]), "+f"(d[37]), "+f"(d[38]), "+f"(d[39]),
      "+f"(d[40]), "+f"(d[41]), "+f"(d[42]), "+f"(d[43]), "+f"(d[44]), "+f"(d[45]), "+f"(d[46]), "+f"(d[47]),
      "+f"(d[48]), "+f"(d[49]), "+f"(d[50]), "+f"(d[51]), "+f"(d[52]), "+f"(d[53]), "+f"(d[54]), "+f"(d[55]),
      "+f"(d[56]), "+f"(d[57]), "+f"(d[58]), "+f"(d[59]), "+f"(d[60]), "+f"(d[61]), "+f"(d[62]), "+f"(d[63]),
      "+f"(d[64]), "+f"(d[65]), "+f"(d[66]), "+f"(d[67]), "+f"(d[68]), "+f"(d[69]), "+f"(d[70]), "+f"(d[71]),
      "+f"(d[72]), "+f"(d[73]), "+f"(d[74]), "+f"(d[75]), "+f"(d[76]), "+f"(d[77]), "+f"(d[78]), "+f"(d[79]),
      "+f"(d[80]), "+f"(d[81]), "+f"(d[82]), "+f"(d[83]), "+f"(d[84]), "+f"(d[85]), "+f"(d[86]), "+f"(d[87]),
      "+f"(d[88]), "+f"(d[89]), "+f"(d[90]), "+f"(d[91]), "+f"(d[92]), "+f"(d[93]), "+f"(d[94]), "+f"(d[95]),
      "+f"(d[96]), "+f"(d[97]), "+f"(d[98]), "+f"(d[99]), "+f"(d[100]), "+f"(d[101]), "+f"(d[102]), "+f"(d[103])
    : "r"(a[0]), "r"(a[1]), "r"(a[2]), "r"(a[3]), "l"(db), "r"(sd));
}

__device__ __forceinline__ void wgmma_rs_n224(float* d, const uint32_t* a, uint64_t db, int sd) {
  asm volatile("{ .reg .pred p; setp.ne.b32 p, %117, 0;\n"
      "wgmma.mma_async.sync.aligned.m64n224k16.f32.bf16.bf16 {"
      "%0,%1,%2,%3,%4,%5,%6,%7,%8,%9,%10,%11,%12,%13,%14,%15,"
      "%16,%17,%18,%19,%20,%21,%22,%23,%24,%25,%26,%27,%28,%29,%30,%31,"
      "%32,%33,%34,%35,%36,%37,%38,%39,%40,%41,%42,%43,%44,%45,%46,%47,"
      "%48,%49,%50,%51,%52,%53,%54,%55,%56,%57,%58,%59,%60,%61,%62,%63,"
      "%64,%65,%66,%67,%68,%69,%70,%71,%72,%73,%74,%75,%76,%77,%78,%79,"
      "%80,%81,%82,%83,%84,%85,%86,%87,%88,%89,%90,%91,%92,%93,%94,%95,"
      "%96,%97,%98,%99,%100,%101,%102,%103,%104,%105,%106,%107,%108,%109,%110,%111"
      "}, {%112,%113,%114,%115}, %116, p, 1, 1, 0; }"
    : "+f"(d[0]), "+f"(d[1]), "+f"(d[2]), "+f"(d[3]), "+f"(d[4]), "+f"(d[5]), "+f"(d[6]), "+f"(d[7]),
      "+f"(d[8]), "+f"(d[9]), "+f"(d[10]), "+f"(d[11]), "+f"(d[12]), "+f"(d[13]), "+f"(d[14]), "+f"(d[15]),
      "+f"(d[16]), "+f"(d[17]), "+f"(d[18]), "+f"(d[19]), "+f"(d[20]), "+f"(d[21]), "+f"(d[22]), "+f"(d[23]),
      "+f"(d[24]), "+f"(d[25]), "+f"(d[26]), "+f"(d[27]), "+f"(d[28]), "+f"(d[29]), "+f"(d[30]), "+f"(d[31]),
      "+f"(d[32]), "+f"(d[33]), "+f"(d[34]), "+f"(d[35]), "+f"(d[36]), "+f"(d[37]), "+f"(d[38]), "+f"(d[39]),
      "+f"(d[40]), "+f"(d[41]), "+f"(d[42]), "+f"(d[43]), "+f"(d[44]), "+f"(d[45]), "+f"(d[46]), "+f"(d[47]),
      "+f"(d[48]), "+f"(d[49]), "+f"(d[50]), "+f"(d[51]), "+f"(d[52]), "+f"(d[53]), "+f"(d[54]), "+f"(d[55]),
      "+f"(d[56]), "+f"(d[57]), "+f"(d[58]), "+f"(d[59]), "+f"(d[60]), "+f"(d[61]), "+f"(d[62]), "+f"(d[63]),
      "+f"(d[64]), "+f"(d[65]), "+f"(d[66]), "+f"(d[67]), "+f"(d[68]), "+f"(d[69]), "+f"(d[70]), "+f"(d[71]),
      "+f"(d[72]), "+f"(d[73]), "+f"(d[74]), "+f"(d[75]), "+f"(d[76]), "+f"(d[77]), "+f"(d[78]), "+f"(d[79]),
      "+f"(d[80]), "+f"(d[81]), "+f"(d[82]), "+f"(d[83]), "+f"(d[84]), "+f"(d[85]), "+f"(d[86]), "+f"(d[87]),
      "+f"(d[88]), "+f"(d[89]), "+f"(d[90]), "+f"(d[91]), "+f"(d[92]), "+f"(d[93]), "+f"(d[94]), "+f"(d[95]),
      "+f"(d[96]), "+f"(d[97]), "+f"(d[98]), "+f"(d[99]), "+f"(d[100]), "+f"(d[101]), "+f"(d[102]), "+f"(d[103]),
      "+f"(d[104]), "+f"(d[105]), "+f"(d[106]), "+f"(d[107]), "+f"(d[108]), "+f"(d[109]), "+f"(d[110]), "+f"(d[111])
    : "r"(a[0]), "r"(a[1]), "r"(a[2]), "r"(a[3]), "l"(db), "r"(sd));
}

__device__ __forceinline__ void wgmma_rs_n240(float* d, const uint32_t* a, uint64_t db, int sd) {
  asm volatile("{ .reg .pred p; setp.ne.b32 p, %125, 0;\n"
      "wgmma.mma_async.sync.aligned.m64n240k16.f32.bf16.bf16 {"
      "%0,%1,%2,%3,%4,%5,%6,%7,%8,%9,%10,%11,%12,%13,%14,%15,"
      "%16,%17,%18,%19,%20,%21,%22,%23,%24,%25,%26,%27,%28,%29,%30,%31,"
      "%32,%33,%34,%35,%36,%37,%38,%39,%40,%41,%42,%43,%44,%45,%46,%47,"
      "%48,%49,%50,%51,%52,%53,%54,%55,%56,%57,%58,%59,%60,%61,%62,%63,"
      "%64,%65,%66,%67,%68,%69,%70,%71,%72,%73,%74,%75,%76,%77,%78,%79,"
      "%80,%81,%82,%83,%84,%85,%86,%87,%88,%89,%90,%91,%92,%93,%94,%95,"
      "%96,%97,%98,%99,%100,%101,%102,%103,%104,%105,%106,%107,%108,%109,%110,%111,"
      "%112,%113,%114,%115,%116,%117,%118,%119"
      "}, {%120,%121,%122,%123}, %124, p, 1, 1, 0; }"
    : "+f"(d[0]), "+f"(d[1]), "+f"(d[2]), "+f"(d[3]), "+f"(d[4]), "+f"(d[5]), "+f"(d[6]), "+f"(d[7]),
      "+f"(d[8]), "+f"(d[9]), "+f"(d[10]), "+f"(d[11]), "+f"(d[12]), "+f"(d[13]), "+f"(d[14]), "+f"(d[15]),
      "+f"(d[16]), "+f"(d[17]), "+f"(d[18]), "+f"(d[19]), "+f"(d[20]), "+f"(d[21]), "+f"(d[22]), "+f"(d[23]),
      "+f"(d[24]), "+f"(d[25]), "+f"(d[26]), "+f"(d[27]), "+f"(d[28]), "+f"(d[29]), "+f"(d[30]), "+f"(d[31]),
      "+f"(d[32]), "+f"(d[33]), "+f"(d[34]), "+f"(d[35]), "+f"(d[36]), "+f"(d[37]), "+f"(d[38]), "+f"(d[39]),
      "+f"(d[40]), "+f"(d[41]), "+f"(d[42]), "+f"(d[43]), "+f"(d[44]), "+f"(d[45]), "+f"(d[46]), "+f"(d[47]),
      "+f"(d[48]), "+f"(d[49]), "+f"(d[50]), "+f"(d[51]), "+f"(d[52]), "+f"(d[53]), "+f"(d[54]), "+f"(d[55]),
      "+f"(d[56]), "+f"(d[57]), "+f"(d[58]), "+f"(d[59]), "+f"(d[60]), "+f"(d[61]), "+f"(d[62]), "+f"(d[63]),
      "+f"(d[64]), "+f"(d[65]), "+f"(d[66]), "+f"(d[67]), "+f"(d[68]), "+f"(d[69]), "+f"(d[70]), "+f"(d[71]),
      "+f"(d[72]), "+f"(d[73]), "+f"(d[74]), "+f"(d[75]), "+f"(d[76]), "+f"(d[77]), "+f"(d[78]), "+f"(d[79]),
      "+f"(d[80]), "+f"(d[81]), "+f"(d[82]), "+f"(d[83]), "+f"(d[84]), "+f"(d[85]), "+f"(d[86]), "+f"(d[87]),
      "+f"(d[88]), "+f"(d[89]), "+f"(d[90]), "+f"(d[91]), "+f"(d[92]), "+f"(d[93]), "+f"(d[94]), "+f"(d[95]),
      "+f"(d[96]), "+f"(d[97]), "+f"(d[98]), "+f"(d[99]), "+f"(d[100]), "+f"(d[101]), "+f"(d[102]), "+f"(d[103]),
      "+f"(d[104]), "+f"(d[105]), "+f"(d[106]), "+f"(d[107]), "+f"(d[108]), "+f"(d[109]), "+f"(d[110]), "+f"(d[111]),
      "+f"(d[112]), "+f"(d[113]), "+f"(d[114]), "+f"(d[115]), "+f"(d[116]), "+f"(d[117]), "+f"(d[118]), "+f"(d[119])
    : "r"(a[0]), "r"(a[1]), "r"(a[2]), "r"(a[3]), "l"(db), "r"(sd));
}

__device__ __forceinline__ void wgmma_rs_n256(float* d, const uint32_t* a, uint64_t db, int sd) {
  asm volatile("{ .reg .pred p; setp.ne.b32 p, %133, 0;\n"
      "wgmma.mma_async.sync.aligned.m64n256k16.f32.bf16.bf16 {"
      "%0,%1,%2,%3,%4,%5,%6,%7,%8,%9,%10,%11,%12,%13,%14,%15,"
      "%16,%17,%18,%19,%20,%21,%22,%23,%24,%25,%26,%27,%28,%29,%30,%31,"
      "%32,%33,%34,%35,%36,%37,%38,%39,%40,%41,%42,%43,%44,%45,%46,%47,"
      "%48,%49,%50,%51,%52,%53,%54,%55,%56,%57,%58,%59,%60,%61,%62,%63,"
      "%64,%65,%66,%67,%68,%69,%70,%71,%72,%73,%74,%75,%76,%77,%78,%79,"
      "%80,%81,%82,%83,%84,%85,%86,%87,%88,%89,%90,%91,%92,%93,%94,%95,"
      "%96,%97,%98,%99,%100,%101,%102,%103,%104,%105,%106,%107,%108,%109,%110,%111,"
      "%112,%113,%114,%115,%116,%117,%118,%119,%120,%121,%122,%123,%124,%125,%126,%127"
      "}, {%128,%129,%130,%131}, %132, p, 1, 1, 0; }"
    : "+f"(d[0]), "+f"(d[1]), "+f"(d[2]), "+f"(d[3]), "+f"(d[4]), "+f"(d[5]), "+f"(d[6]), "+f"(d[7]),
      "+f"(d[8]), "+f"(d[9]), "+f"(d[10]), "+f"(d[11]), "+f"(d[12]), "+f"(d[13]), "+f"(d[14]), "+f"(d[15]),
      "+f"(d[16]), "+f"(d[17]), "+f"(d[18]), "+f"(d[19]), "+f"(d[20]), "+f"(d[21]), "+f"(d[22]), "+f"(d[23]),
      "+f"(d[24]), "+f"(d[25]), "+f"(d[26]), "+f"(d[27]), "+f"(d[28]), "+f"(d[29]), "+f"(d[30]), "+f"(d[31]),
      "+f"(d[32]), "+f"(d[33]), "+f"(d[34]), "+f"(d[35]), "+f"(d[36]), "+f"(d[37]), "+f"(d[38]), "+f"(d[39]),
      "+f"(d[40]), "+f"(d[41]), "+f"(d[42]), "+f"(d[43]), "+f"(d[44]), "+f"(d[45]), "+f"(d[46]), "+f"(d[47]),
      "+f"(d[48]), "+f"(d[49]), "+f"(d[50]), "+f"(d[51]), "+f"(d[52]), "+f"(d[53]), "+f"(d[54]), "+f"(d[55]),
      "+f"(d[56]), "+f"(d[57]), "+f"(d[58]), "+f"(d[59]), "+f"(d[60]), "+f"(d[61]), "+f"(d[62]), "+f"(d[63]),
      "+f"(d[64]), "+f"(d[65]), "+f"(d[66]), "+f"(d[67]), "+f"(d[68]), "+f"(d[69]), "+f"(d[70]), "+f"(d[71]),
      "+f"(d[72]), "+f"(d[73]), "+f"(d[74]), "+f"(d[75]), "+f"(d[76]), "+f"(d[77]), "+f"(d[78]), "+f"(d[79]),
      "+f"(d[80]), "+f"(d[81]), "+f"(d[82]), "+f"(d[83]), "+f"(d[84]), "+f"(d[85]), "+f"(d[86]), "+f"(d[87]),
      "+f"(d[88]), "+f"(d[89]), "+f"(d[90]), "+f"(d[91]), "+f"(d[92]), "+f"(d[93]), "+f"(d[94]), "+f"(d[95]),
      "+f"(d[96]), "+f"(d[97]), "+f"(d[98]), "+f"(d[99]), "+f"(d[100]), "+f"(d[101]), "+f"(d[102]), "+f"(d[103]),
      "+f"(d[104]), "+f"(d[105]), "+f"(d[106]), "+f"(d[107]), "+f"(d[108]), "+f"(d[109]), "+f"(d[110]), "+f"(d[111]),
      "+f"(d[112]), "+f"(d[113]), "+f"(d[114]), "+f"(d[115]), "+f"(d[116]), "+f"(d[117]), "+f"(d[118]), "+f"(d[119]),
      "+f"(d[120]), "+f"(d[121]), "+f"(d[122]), "+f"(d[123]), "+f"(d[124]), "+f"(d[125]), "+f"(d[126]), "+f"(d[127])
    : "r"(a[0]), "r"(a[1]), "r"(a[2]), "r"(a[3]), "l"(db), "r"(sd));
}

__device__ __forceinline__ void ln_finish(float mean, float var, float& mb, float& rinv) {
  mb = round_bf16(mean);
  float sd;
  asm("sqrt.approx.ftz.f32 %0, %1;" : "=f"(sd) : "f"(round_bf16(round_bf16(var) + 1e-5f)));
  asm("rcp.approx.ftz.f32 %0, %1;" : "=f"(rinv) : "f"(round_bf16(sd)));
}
__device__ __forceinline__ uint32_t sum4(uint32_t a, uint32_t b, uint32_t c, uint32_t d) { return badd2(badd2(badd2(d, c), b), a); }
struct Ring {
  uint32_t s, ph;
  __device__ __forceinline__ void next() { if (++s == NSTAGE) { s = 0; ph ^= 1; } }
};

template <int J> __device__ __forceinline__ void conv_lda(uint32_t* a, uint32_t base) {
  a[2 * J] = lds32(base + (J >> 1) * 256 + (J & 1) * 16); a[2 * J + 1] = lds32(base + (J >> 1) * 256 + (J & 1) * 16 + 128);
}
template <int J = 0> __device__ __forceinline__ void conv_lda_all(uint32_t* a, uint32_t base) {
  conv_lda<J>(a, base);
  if constexpr (J < 31) conv_lda_all<J + 1>(a, base);
}
__device__ __forceinline__ void conv_mma(float* acc, const uint32_t* a, uint64_t db) {
  wgmma_rs_n256(acc, a, db, 0);
  wgmma_rs_n240(acc, a + 4, db + 16, 1);
  wgmma_rs_n224(acc, a + 8, db + 32, 1);
  wgmma_rs_n208(acc, a + 12, db + 48, 1);
  wgmma_rs_n192(acc, a + 16, db + 64, 1);
  wgmma_rs_n176(acc, a + 20, db + 80, 1);
  wgmma_rs_n160(acc, a + 24, db + 96, 1);
  wgmma_rs_n144(acc, a + 28, db + 112, 1);
  wgmma_rs_n128(acc, a + 32, db + 128, 1);
  wgmma_rs_n112(acc, a + 36, db + 144, 1);
  wgmma_rs_n96(acc, a + 40, db + 160, 1);
  wgmma_rs_n80(acc, a + 44, db + 176, 1);
  wgmma_rs_n64(acc, a + 48, db + 192, 1);
  wgmma_rs_n48(acc, a + 52, db + 208, 1);
  wgmma_rs_n32(acc, a + 56, db + 224, 1);
  wgmma_rs_n16(acc, a + 60, db + 240, 1);
}
__device__ __forceinline__ uint32_t conv_part(const float* acc, int j) {
  const int q = 31 - j;
  return q == 31 ? pack_bf16(acc[124], acc[125]) : pack_bf16(acc[4 * q] + acc[(4 * q + 6) & 127], acc[4 * q + 1] + acc[(4 * q + 7) & 127]);
}
template <bool MORE, int J = 0> __device__ __forceinline__ void conv_drain(const float* acc, uint32_t wr, uint32_t* a, uint32_t ka) {
  if (MORE) conv_lda<J>(a, ka);
  sts32(wr + J * 128, conv_part(acc, J));
  if constexpr (J < 31) conv_drain<MORE, J + 1>(acc, wr, a, ka);
}
__device__ __forceinline__ uint4 conv_sum(const uint4* p) {
  return make_uint4(sum4(p[0].x, p[1].x, p[2].x, p[3].x), sum4(p[0].y, p[1].y, p[2].y, p[3].y), sum4(p[0].z, p[1].z, p[2].z, p[3].z),
                    sum4(p[0].w, p[1].w, p[2].w, p[3].w));
}
__device__ __forceinline__ int g2pos(int fb) { return fb / G2_KB * G2_KB + fb % 6 * 6 + fb % G2_KB / 6; }

template <int NV> __device__ __forceinline__ void gelu_stage(float* acc, const float* hb, uint32_t sa, int passes, uint32_t bar) {
#pragma unroll
  for (int i = 0; i < NV; i++) acc[i] = fmaf(acc[i], 0.5f, hb[(i >> 1) & 1]);
#pragma unroll 1
  for (; passes > 0; passes--, sa += NV * 256) {
#pragma unroll
    for (int i = 0; i < NV; i += 8)
      stsm4t(sa + i * 256, pack_bf16(gelu_half(acc[i]), gelu_half(acc[i + 1])), pack_bf16(gelu_half(acc[i + 2]), gelu_half(acc[i + 3])),
             pack_bf16(gelu_half(acc[i + 4]), gelu_half(acc[i + 5])), pack_bf16(gelu_half(acc[i + 6]), gelu_half(acc[i + 7])));
    __syncwarp();
    if (bar) mbar_arrive(bar);
    bar = 0;
    float half = 0.5f;
    asm volatile("" : "+f"(half));
#pragma unroll
    for (int i = 0; i < NV; i++) acc[i] = fmaf(acc[NV + i], half, hb[2 + ((i >> 1) & 1)]);
  }
}

__global__ void __cluster_dims__(2, 1, 1) __launch_bounds__(384, 1) fused_kernel(const __grid_constant__ Hot H, const __grid_constant__ Params P) {
  extern __shared__ __align__(1024) uint8_t smem_raw[];
  const uint32_t t0 = clk();
  const uint32_t sb = smem_u32(smem_raw);
  const int tid = threadIdx.x, lane = tid & 31;
  const int bid = blockIdx.x, rank = bid & 1;
  const Role& R = P.role[bid];
  Scratch* const S = H.S;
  uint32_t xr[18];
  const int row = bid * 16 + (tid >> 4);
  if (tid < 256 && bid < 128) {
    const char* src = reinterpret_cast<const char*>(H.x) + row * (D_ * 2) + (lane & 15) * 8;
#pragma unroll
    for (int j = 0; j < 9; j++) asm volatile("ld.global.nc.v2.u32 {%0,%1}, [%2];" : "=r"(xr[2 * j]), "=r"(xr[2 * j + 1]) : "l"(src + 128 * j));
  }
  if (tid == 256) asm volatile("prefetch.tensormap [%0];" :: "l"(&P.m_w1 + (R.at == 15)) : "memory");
  const int warp = __shfl_sync(0xffffffffu, tid >> 5, 0);

  if (warp >= 8) {
    const bool one = elect_one(), left = R.at == 15;
    if (warp == 8 && one) {
#pragma unroll
      for (int b = B_FULL; b < B_KFULL; b += 8) mbar_init(sb + b, 1);
      fence_async_smem();
      tma3d_ef(sb, &P.m_w1 + left, 0, 0, R.fg, sb + B_FULL);
#pragma unroll
      for (int s = 0; s < NSTAGE; s++) mbar_expect_tx(sb + B_FULL + 8 * s, G1_BYTES);
#pragma unroll
      for (int b = B_KFULL; b <= B_DONE; b += 8) mbar_init(sb + b, b < B_EMPTY ? 1 : b < B_SFREE ? 2 : b < B_CEMPTY ? 3 : b < B_G1DONE ? 4 : 8);
      asm volatile("fence.mbarrier_init.release.cluster;" ::: "memory");
    }
    __syncwarp();
    asm volatile("barrier.cluster.arrive.relaxed.aligned;" ::: "memory");
    asm volatile("setmaxnreg.dec.sync.aligned.u32 56;");
    asm volatile("barrier.cluster.wait.aligned;" ::: "memory");
    if (warp == 8) {
      const uint32_t ep = ldg32(S->cnt + C_EPOCH * 32);
      if (one) {
#pragma unroll 1
        for (int i = 0; i < 6; i++) asm volatile("prefetch.tensormap [%0];" :: "l"(&P.m_w2 + i) : "memory");
      }
      __syncwarp();
      if (bid < 128) bar_sync(2, 288);
      if (one) {
        const uint32_t boff = left ? 24576 : 16384, hbytes = G1_BYTES - boff;
        const CUtensorMap* const mw1 = &P.m_w1 + left;
        const int fg = R.fg;
        const char* hp = reinterpret_cast<const char*>(S->h) + R.at * 4096;
        TLREC(31);
        signal(S, C_H, EPOCH / 132);
        TLREC(1);
        tma3d_ef(sb + SLOT, mw1, 0, 64, fg, sb + B_FULL + 8);
        await(S, C_H, ep);
        fence_async_global();
        TLREC(2);
        const uint32_t tp = clk();
#pragma unroll 1
        for (int s = 0; s < NSTAGE; s++) {
          while ((int)(clk() - tp) < s * 400 - 100) { }
          if (s >= 1 && s + 1 < NSTAGE) tma3d_ef(sb + (s + 1) * SLOT, mw1, 0, (s + 1) * 64, fg, sb + B_FULL + 8 * (s + 1));
          bulk_load(sb + s * SLOT + boff, hp, hbytes, sb + B_FULL + 8 * s);
          hp += 73728;
        }
        int kr = bid < 128 ? -2 : KV_ROUNDS + 1, ks = 0;
        auto kv_step = [&]() {
          if (ks == 0) {
            bulk_wait_all();
            if (kr < KV_ROUNDS - 2) {
              const int q = (kr + 2) % 3;
              const uint32_t in = sb + kv_buf(q), fb = sb + B_UFULL + 8 * q;
              mbar_expect_tx(fb, 3840 + 3264 + 768);
              tma2d(in, &P.m_k, (kr + 2) * 96, bid * 16 - 4, fb);
              tma2d(in + 3840, &P.m_v, (kr + 2) * 96, bid * 16 - 1, fb);
              bulk_load(in + 7168, H.shift_k + (kr + 2) * 384, 768, fb);
            }
            if (kr == KV_ROUNDS) { mbar_arrive(sb + B_KVDONE); kr++; }
          } else if (kr >= 0) {
            if (!mbar_test(sb + B_KFULL + 8 * (kr % 3), kr >= 3)) return;
            fence_async_smem();
            tma3d_store(&P.m_ub, sb + kv_buf(kr % 3) + (ks - 1) * 3072, 16 * (127 - bid), kr * 48, 2 * ks - 2);
            bulk_commit();
          }
          if (++ks == 3) { kr++; ks = kr == KV_ROUNDS - 2 || kr == KV_ROUNDS - 1; }
        };
        if (bid >= 128) mbar_arrive(sb + B_KVDONE);
        uint32_t slot = sb, fb = sb + B_FULL, ph = 0;
        auto next = [&]() { slot += SLOT; fb += 8; if (fb == sb + B_FULL + 8 * NSTAGE) { slot = sb; fb = sb + B_FULL; ph ^= 1; } };
#pragma unroll 1
        for (int k0 = NSTAGE * 64; k0 < G1_KB * 64 || kr <= KV_ROUNDS; k0 += 64) {
          if (k0 < G1_KB * 64) {
            mbar_wait(fb + (B_EMPTY - B_FULL), ph);
            mbar_expect_tx(fb, G1_BYTES);
            tma3d_ef(slot, mw1, 0, k0, fg, fb);
            bulk_load(slot + boff, hp, hbytes, fb);
            hp += 73728;
            next();
            if (k0 == 23 * 64) {
#pragma unroll 1
              for (int i = 0; i < 2; i++) {
                sts128(sb + cv_taps(i), 0, 0, 0, 0); sts128(sb + cv_taps(i) + 16, 0, 0, 0, 0);
                bulk_load(sb + cv_taps(i) + 32, H.ssm_k + (R.ch + i) * S_, 4096, sb + B_MISC);
              }
              mbar_expect_tx(sb + B_MISC, boff / 64 + 1152 + 8192);
              bulk_load(sb + SM_B1, P.b1 + fg * 64, boff / 64, sb + B_MISC);
              bulk_load(sb + SM_D, P.ssm_D, 1152, sb + B_MISC);
            }
          }
          if (kr <= KV_ROUNDS) kv_step();
        }
        await(S, C_KV, ep);
        fence_async_global();
#pragma unroll 1
        for (int i = 0; i < R.ncv; i++) {
          if (i == 2) {
            if (R.sg >= 0) {
#pragma unroll 1
              for (int s = 2; s < NSTAGE; s++) {
                mbar_wait(sb + B_EMPTY + 8 * s, ((G1_KB / NSTAGE) - 1) & 1);
                mbar_expect_tx(sb + B_FULL + 8 * s, G2_BYTES);
                tma3d_ef(sb + s * SLOT, &P.m_w2, 0, (rank * G2_KB + 6 * (s - 2)) * 64, R.sg, sb + B_FULL + 8 * s);
              }
            }
            mbar_wait(sb + B_G1DONE, 0);
          }
          const uint32_t kt = sb + cv_taps(i), b8 = sb + 8 * (i & 3);
          mbar_wait(b8 + B_CEMPTY, ((i >> 2) & 1) ^ 1);
          if (i < 2) mbar_arrive(b8 + B_KFULL);
          else {
            sts128(kt, 0, 0, 0, 0); sts128(kt + 16, 0, 0, 0, 0);
            mbar_expect_tx(b8 + B_KFULL, 4096);
            bulk_load(kt + 32, H.ssm_k + (R.ch + i) * S_, 4096, b8 + B_KFULL);
          }
          mbar_expect_tx(b8 + B_UFULL, 8192);
          bulk_load(sb + cv_in(i), S->ub + (R.ch + i) * 4096, 8192, b8 + B_UFULL);
        }
        if (R.sg >= 0) {
          mbar_expect_tx(sb + B_XY, 2 * 18432 + 2048 + 256);
#pragma unroll
          for (int i = 0; i < 4; i++) mbar_expect_tx(sb + B_XFULL + 8 * i, i & 1 ? 9216 - XP * 2048 : XP * 2048);
          const int sg = R.sg, kend = (rank + 1) * G2_KB * 64;
          const char* us = reinterpret_cast<const char*>(S->u) + rank * G2_KB * 73728 + R.ds * 1024;
          const int dko = rank ? 9216 : -9216;
          await(S, C_U, ep);
          fence_async_global();
          TLREC(6);
#pragma unroll
          for (int s = 2; s < NSTAGE; s++) {
            bulk_load_ef(sb + s * SLOT + 16384, us + (s - 2) * 73728, 9216, sb + B_FULL + 8 * s);
            bulk_load_ef(sb + s * SLOT + 16384 + 9216, us + dko + (s - 2) * 73728, 9216, sb + B_FULL + 8 * s);
          }
          us += (NSTAGE - 2) * 73728;
          slot = sb; fb = sb + B_FULL; ph = (G1_KB / NSTAGE) & 1;
          int k0 = kend - (G2_KB - 6 * (NSTAGE - 2)) * 64;
#pragma unroll 1
          for (int kb = NSTAGE - 2; kb < G2_KB; kb++) {
            mbar_wait(fb + (B_EMPTY - B_FULL), ph);
            mbar_expect_tx(fb, G2_BYTES);
            tma3d_ef(slot, &P.m_w2, 0, k0, sg, fb);
            bulk_load_ef(slot + 16384, us, 9216, fb);
            bulk_load_ef(slot + 16384 + 9216, us + dko, 9216, fb);
            us += 73728;
            k0 += 6 * 64;
            if (k0 >= kend) k0 -= (G2_KB - 1) * 64;
            next();
            if (kb < 16) {
              TUNED(SYNCA, 0, 5); TUNED(SYNCKB, 1, 7);
              if (kb == 3) { await(S, C_U + 1, ep); fence_async_global(); }
              if (kb == SYNCA) asm volatile("red.relaxed.gpu.global.add.u32 [%0], %1;" :: "l"(S->cnt + C_SYNC * 32), "r"(EPOCH / 128) : "memory");
              if (kb == SYNCKB - 1) await(S, C_SYNC, ep);
              if (kb == 8) { mbar_wait(sb + B_KVDONE, 1); fence_async_smem(); }
              if (kb >= 8) tma2d(sb + SM_CV + (kb - 8) * 2304, &P.m_x, R.dk * 8, sg * 64 + (kb - 8) * 16, sb + B_XY);
            }
          }
          bulk_load(sb + SM_ST, S->stats + R.sg * 64, 2048, sb + B_XY);
          bulk_load(sb + SM_B2, H.b2 + R.sg * 64, 256, sb + B_XY);
          await(S, C_Y, ep);
          fence_async_global();
          TLREC(19);
          tma3d(sb + SM_DED, &P.m_y, 0, R.dk * 8, R.sg, sb + B_XY);
          if (bid == 0) asm volatile("red.relaxed.gpu.global.add.u32 [%0], %1;" :: "l"(S->cnt + C_EPOCH * 32), "r"(EPOCH) : "memory");
        }
      }
    } else {
      if (bid < 128) {
        const int ht = tid - 288, hf = ht >= 48, pr = ht - 48 * hf;
        const uint32_t st = (1 - hf) * 1536 + pr * 32, sw = (pr & 4) * 4;
#pragma unroll 1
        for (int r = 0; r < KV_ROUNDS; r++) {
          const int q = r % 3;
          const uint32_t in = sb + kv_buf(q);
          {
            mbar_wait_guarded(sb + B_UFULL + 8 * q, t0, r >= 3);
            uint32_t kk[12], vv[9];
#pragma unroll
            for (int j = 0; j < 12; j++) kk[j] = lds32(in + hf * 1536 + pr * 4 + j * 192);
#pragma unroll
            for (int j = 0; j < 9; j++) vv[j] = lds32(in + 3840 + hf * 1536 + pr * 4 + j * 192);
            const uint4 w = lds128(in + 7168 + pr * 16);
            const uint32_t w0 = __byte_perm(w.x, w.z, 0x5410), w1 = __byte_perm(w.x, w.z, 0x7632);
            const uint32_t w2 = __byte_perm(w.y, w.w, 0x5410), w3 = __byte_perm(w.y, w.w, 0x7632);
#pragma unroll
            for (int j = 0; j < 9; j++)
              vv[j] = bmul2(badd2(badd2(badd2(bmul2(kk[j], w3), bmul2(kk[j + 1], w2)), bmul2(kk[j + 2], w1)), bmul2(kk[j + 3], w0)), vv[j]);
            bar_sync(1, 96);
#pragma unroll
            for (int c = 0; c < 2; c++)
#pragma unroll
              for (int pi = 0; pi < 2; pi++) {
                const uint32_t sel = c ? 0x7632 : 0x5410;
                sts128(in + st + c * 3072 + (pi * 16 ^ sw), __byte_perm(vv[7 + pi], vv[6 + pi], sel), __byte_perm(vv[5 + pi], vv[4 + pi], sel),
                       __byte_perm(vv[3 + pi], vv[2 + pi], sel), __byte_perm(vv[1 + pi], vv[pi], sel));
              }
            bar_sync(1, 96);
            if (ht == 0) mbar_arrive(sb + B_KFULL + 8 * q);
          }
          __syncwarp();
        }
      }
      if (one) {
        if (warp < 11) {
          const int wg = warp - 9;
          const uint32_t bytes = left ? 12288 : 10240;
#pragma unroll 1
          for (int j = 0; j < 2; j++) {
            mbar_wait_guarded(sb + B_STG + 8 * wg + (j ? 0 : 16), t0);
            fence_async_smem();
            TLREC(13 + wg);
            if (!j || wg || !left)
              bulk_store(S->u + g2pos(R.fg + wg + (j && left)) * (64 * D_) + R.at * 2048 + (left ? 0 : j * 5120), sb + (wg ? SM_ST1 : SM_DED) + j * bytes, bytes);
          }
          bulk_commit();
          bulk_wait_all();
          mbar_arrive(sb + B_STORED + 8 * wg);
          if (wg) mbar_arrive(sb + B_EMPTY);
          asm volatile("mbarrier.arrive.shared::cta.b64 _, [%0], 3;" :: "r"(sb + B_SFREE + 8 * wg) : "memory");
          signal(S, C_U + wg, EPOCH / 132);
          TLREC(15 + wg);
        } else {
          mbar_wait_guarded(sb + B_KVDONE, t0);
          signal(S, C_KV, EPOCH / 132);
          TLREC(27);
        }
      }
      __syncwarp();
#pragma unroll 1
      for (int i = 0; i < R.ncv; i++) {
        const uint32_t red = sb + cv_red(i, R.ncv) + (tid - 288) * 16;
        uint4* yo = reinterpret_cast<uint4*>(S->y + (R.ch + i) * S_) + (tid - 288);
        mbar_wait_guarded(sb + B_STORED + 8 * (i & 1), t0);
        mbar_wait_guarded(sb + B_STG + 8 * (i & 1) + (i + 2 < R.ncv ? 0 : 16), t0, i + 2 >= R.ncv || !(i & 2));
        uint4 p[2][4];
#pragma unroll
        for (int x = 0; x < 8; x++) p[x >> 2][x & 3] = lds128(red + (x & 3) * CV_REDW + (x >> 2) * 1536);
        yo[0] = conv_sum(p[0]);
        if (warp < 11) {
#pragma unroll
          for (int x = 0; x < 4; x++) p[0][x] = lds128(red + x * CV_REDW + 3072);
          yo[192] = conv_sum(p[0]);
        }
        yo[96] = conv_sum(p[1]);
        __syncwarp();
        if (one) mbar_arrive(sb + (i + 4 == R.ncv ? B_PDONE : B_SFREE + 8 * (i & 1)));
        if (i + 3 == R.ncv) {
          bar_sync(1, 96);
          if (warp == 11 && one) { fence_async_smem(); mbar_arrive(sb + B_EMPTY + 8); }
          __syncwarp();
        }
      }
      bar_sync(1, 96);
      if (warp == 11 && one) {
        TLREC(7);
        mbar_arrive(sb + B_KVDONE);
        signal(S, C_Y, EPOCH / 132);
        if (R.sg >= 0) mbar_wait_guarded(sb + B_DONE, t0);
      }
    }
    TLEND();
  } else {
    asm volatile("barrier.cluster.arrive.relaxed.aligned;" ::: "memory");
    if (bid < 128) {
      float c[36], s[4];
#pragma unroll
      for (int i = 0; i < 18; i++) { c[2 * i] = bf_lo(xr[i]); c[2 * i + 1] = bf_hi(xr[i]); }
#pragma unroll
      for (int i = 0; i < 36; i++) s[i & 3] = i < 4 ? c[i] : s[i & 3] + c[i];
      const float ml = ((s[0] + s[1]) + (s[2] + s[3])) * (1.0f / 36.0f);
#pragma unroll
      for (int i = 0; i < 36; i++) { c[i] -= ml; s[i & 3] = i < 4 ? c[i] * c[i] : fmaf(c[i], c[i], s[i & 3]); }
      float m = ml, q = (s[0] + s[1]) + (s[2] + s[3]), n2 = 18.f;
#pragma unroll
      for (int o = 1; o < 16; o <<= 1) {
        const float mo = __shfl_xor_sync(0xffffffffu, m, o), qo = __shfl_xor_sync(0xffffffffu, q, o);
        const float dl = m - mo;
        q = fmaf(dl * dl, n2, q + qo);
        m = fmaf(dl, -0.5f, m);
        n2 *= 2.f;
      }
      const float var = q * (1.0f / 576.0f);
      float mb, rinv, mb2, rinv2;
      ln_finish(m, var, mb, rinv);
      ln_finish((m - mb) * rinv, var * rinv * rinv, mb2, rinv2);
      const float ca = rinv * rinv2, cb = fmaf(ml - mb, rinv, -mb2) * rinv2;
      uint2* dst = reinterpret_cast<uint2*>(S->h) + ((row >> 6) * 18 + ((lane >> 3) & 1)) * 512 + (row & 63) * 8 + ((lane & 7) ^ (row & 6));
#pragma unroll
      for (int j = 0; j < 9; j++)
        dst[1024 * j] = make_uint2(pack_bf16(fmaf(c[4 * j], ca, cb), fmaf(c[4 * j + 1], ca, cb)), pack_bf16(fmaf(c[4 * j + 2], ca, cb), fmaf(c[4 * j + 3], ca, cb)));
      const uint32_t rh = pack_bf16(rinv, rinv);
      if (!(lane & 15)) S->stats[row] = make_uint4(pack_bf16(mb, mb), rh, pack_bf16(rinv - bf_lo(rh), rinv - bf_lo(rh)), 0);
      __syncwarp();
      bar_arrive(2, 288);
    }
    asm volatile("setmaxnreg.inc.sync.aligned.u32 224;");
    asm volatile("barrier.cluster.wait.aligned;" ::: "memory");
    const int wg = warp >> 2, w = warp & 3, g = lane >> 2, t = lane & 3, wtid = tid & 127;
    const bool elect = wtid == 0;
    const uint64_t da0 = make_desc(sb + wg * 8192, 8192, 1024, 1);
    const uint32_t swz = ((lane >> 4) * 8 + (lane & 7)) * 128 + (((2 * w + ((lane >> 3) & 1)) ^ (lane & 7)) << 4);
    const uint32_t stg = sb + (wg ? SM_ST1 : SM_DED), ka0 = (8 * w + g + t + 1) * 4;
    uint32_t a[64];
    {
      auto mainloop = [&](auto&& mma) {
        Ring r{0, 0};
        uint32_t rel = 0;
#pragma unroll 1
        for (int kb = 0; kb < G1_KB; kb++, r.next()) {
          if (kb == G1_KB - G1_TAIL && wg) {
            wg_wait<0>();
            if (elect) mbar_arrive(rel);
            rel = 0;
            {
              mbar_wait(sb + B_MISC, 0);
              conv_lda_all(a, sb + SM_CV + 16384 + CV_K + ka0);
            }
            bar_sync(5, 256);
          }
          mbar_wait(sb + B_FULL + 8 * r.s, r.ph);
          if (kb == 0 && warp == 0) TLREC(3);
          wg_fence();
          mma(r.s * (SLOT >> 4), kb);
          wg_commit();
          if (kb == G1_KB - 1) break;
          wg_wait<1>();
          if (elect && rel) mbar_arrive(rel);
          rel = sb + B_EMPTY + 8 * r.s;
        }
        bar_arrive(5, 256);
        wg_wait<0>();
      };
      float hb[4];
      auto staged = [&](int second) {
        if (!w) TLREC(4 + wg);
        if (lane == 0) mbar_arrive(sb + B_G1DONE);
        mbar_wait(sb + B_MISC, 0);
#pragma unroll
        for (int i = 0; i < 4; i++) hb[i] = 0.5f * bf_lo(lds16(sb + SM_B1 + (warp * 16 + g + (i & 1) * 8 + (i >> 1) * second) * 2));
        mbar_wait(sb + B_KVDONE, 0);
        if (wg) mbar_wait(sb + B_G1DONE, 0);
      };
      if (R.at != 15) {
        const uint64_t db0 = make_desc(sb + 16384, 4096, 512, 2);
        float acc[80];
        mainloop([&](uint32_t o, int kb) {
#pragma unroll
          for (int k = 0; k < 4; k++) wgmma_ss_n160_t11(acc, da0 + o + k * 128, db0 + o + k * 64, k ? 1 : kb);
        });
        pin_regs<80>(acc);
        staged(0);
        gelu_stage<40>(acc, hb, stg + swz, 2, lane ? 0 : sb + B_STG + 8 * wg + 16);
      } else {
        const uint64_t db0 = make_desc(sb + 24576, 4096, 512, 2);
        float acc[96];
        auto block = [&](float* d, uint64_t da, uint64_t db, int kb) {
#pragma unroll
          for (int k = 0; k < 4; k++) wgmma_ss_n96_t11(d, da + k * 128, db + k * 64, k ? 1 : kb);
        };
        if (wg) mainloop([&](uint32_t o, int kb) { block(acc, da0 + o, db0 + o, kb); block(acc + 48, da0 + o + 512, db0 + o, kb); });
        else mainloop([&](uint32_t o, int kb) { block(acc, da0 + o, db0 + o, kb); });
        pin_regs<96>(acc);
        staged(64);
        gelu_stage<48>(acc, hb, stg + swz, 1 + wg, lane ? 0 : sb + B_STG + 8 * wg + 16);
      }
      __syncwarp();
      if (lane == 0) mbar_arrive(sb + B_STG + 8 * wg);
    }
    {
      if (!wg) conv_lda_all(a, sb + SM_CV + 16384 + wg * CV_K + ka0);
#pragma unroll 1
      for (int i = wg; i < R.ncv; i += 2) {
        const bool more = i + 2 < R.ncv;
        const uint32_t dd = lds16(sb + SM_D + (R.ch + i) * 2);
        a[0] = badd2(a[0], ka0 == 32 ? dd : 0); a[2] = badd2(a[2], ka0 == 16 ? dd : 0);
        float acc[128];
        mbar_wait(sb + B_UFULL + 8 * (i & 3), (i >> 2) & 1);
        bar_sync(5 + wg, 256);
        const bool last = i + 1 == R.ncv;
        if (last && elect) mbar_arrive(sb + B_EMPTY);
        if (!w && i < 4) TLREC(22 + i);
        wg_fence();
        conv_mma(acc, a, make_desc(sb + cv_in(i), 4096, 128, 0));
        wg_commit();
        if (!last) bar_arrive(5 + (wg ^ 1), 256);
        if (more) {
          mbar_wait(sb + B_SFREE + 8 * wg, (i >> 1) & 1);
          mbar_wait(sb + B_KFULL + 8 * ((i + 2) & 3), ((i + 2) >> 2) & 1);
        } else if (last) mbar_wait(sb + B_PDONE, 0);
        wg_wait<0>();
        pin_regs<128>(acc);
        if (lane == 0) mbar_arrive(sb + B_CEMPTY + 8 * (i & 3));
        if (last && elect) mbar_arrive(sb + B_EMPTY + 8);
        const uint32_t red = sb + cv_red(i, R.ncv), ka = sb + cv_taps(i + 2) + ka0;
        if (lane < 8 * w) sts32(red + w * CV_REDW + lane * 4, 0);
        const uint32_t wr = red + w * CV_REDW + (8 * (3 - t + w) + g) * 4;
        if (more) conv_drain<true>(acc, wr, a, ka); else conv_drain<false>(acc, wr, a, ka);
        __syncwarp();
        if (lane == 0) mbar_arrive(sb + B_STG + 8 * wg + (more ? 0 : 16));
      }
      if (!w) TLREC(20 + wg);
    }
    if (R.sg >= 0) {
      const int srow = R.sg * 64 + warp * 16;
      const uint64_t db0 = make_desc(sb + 16384, 16, 1024, 1);
      const uint32_t xo = sb + SM_CV + warp * 2304, xa = xo + (lane & 15) * 144;
      float acc[72];
      Ring r{G1_KB % NSTAGE, (G1_KB / NSTAGE) & 1};
      bar_sync(8, 256);
      uint32_t rel = 0;
#pragma unroll 1
      for (int kb = 0; kb < G2_KB; kb++, r.next()) {
        if (kb == G2_KB - G2_TAIL && wg) {
          wg_wait<0>();
          if (elect) mbar_arrive_remote(rel);
          rel = 0;
          bar_sync(7, 256);
        }
        mbar_wait(sb + B_FULL + 8 * r.s, r.ph);
        if (kb == 0 && !w) TLREC(17 + wg);
        if (kb == 8 && warp == 0) TLREC(26);
        if (kb == 20 && warp == 0) TLREC(8);
        if (kb == 27 && warp == 0) TLREC(30);
        const uint64_t da = da0 + r.s * (SLOT >> 4), db = db0 + r.s * (SLOT >> 4);
        wg_fence();
        wgmma_ss_n144_t10(acc, da, db, kb);
#pragma unroll
        for (int k = 1; k < 4; k++) wgmma_ss_n144_t10(acc, da + k * 128, db + k * 2, 1);
        wg_commit();
        if (kb == G2_KB - 1) break;
        wg_wait<1>();
        if (elect && rel) mbar_arrive_remote(rel);
        rel = kb == G2_KB - NSTAGE ? mapa(sb + B_XRDY, rank ^ 1) : sb + B_EMPTY + 8 * r.s;
      }
      if (!wg) bar_arrive(7, 256);
      const uint32_t xz = sb + XSLOT * SLOT + wg * 10240 + wtid * 16;
      const uint32_t rz = mapa(xz, rank ^ 1), rb = mapa(sb + B_XFULL + 16 * wg, rank ^ 1);
      mbar_wait(sb + B_XRDY, 0);
      wg_wait<0>();
      pin_regs<72>(acc);
      if (!w) TLREC(28 + wg);
#pragma unroll
      for (int i = 0; i < 32; i += 8)
        asm volatile("st.async.weak.shared::cluster.mbarrier::complete_tx::bytes.v4.b32 [%0], {%1,%2,%3,%4}, [%5];"
                     :: "r"(rz + i * 256), "r"(pack_bf16(acc[i], acc[i + 1])), "r"(pack_bf16(acc[i + 2], acc[i + 3])),
                        "r"(pack_bf16(acc[i + 4], acc[i + 5])), "r"(pack_bf16(acc[i + 6], acc[i + 7])), "r"(rb + (i < 8 * XP ? 0 : 8)) : "memory");
      asm volatile("st.async.weak.shared::cluster.mbarrier::complete_tx::bytes.v2.b32 [%0], {%1,%2}, [%3];"
                   :: "r"(rz + 8192), "r"(pack_bf16(acc[32], acc[33])), "r"(pack_bf16(acc[34], acc[35])), "r"(rb + 8) : "memory");
      uint32_t xx[18], ss[18];
      mbar_wait(sb + B_XY, 0);
      {
        const uint32_t ya = sb + SM_DED + wg * 9216 + swz;
        const uint4 st0 = lds128(sb + SM_ST + (warp * 16 + g) * 16), st1 = lds128(sb + SM_ST + (warp * 16 + g + 8) * 16);
        const float hb0 = 0.5f * bf_lo(lds16(sb + SM_B2 + (warp * 16 + g) * 2)), hb1 = 0.5f * bf_lo(lds16(sb + SM_B2 + (warp * 16 + g + 8) * 2));
#pragma unroll
        for (int q = 0; q < 8; q += 2) { ldsm4(xx + 2 * q, xa + (lane >> 4) * 16 + q * 16); ldsm4t(ss + 2 * q, ya + q * 1024); }
        ldsm2(xx + 16, xa + 128);
        ldsm2t(ss + 16, ya + 8 * 1024);
#pragma unroll
        for (int i = 0; i < 18; i++) {
          const uint4& st = (i & 1) ? st1 : st0;
          const uint32_t c = bsub2(xx[i], st.x);
          ss[i] = bmul2(bfma2(c, st.y, bmul2(c, st.z)), ss[i]);
        }
#pragma unroll
        for (int i = 36; i < 72; i++) acc[i] = fmaf(acc[i], 0.5f, (i & 2) ? hb1 : hb0);
      }
      char* const op = reinterpret_cast<char*>(H.out) + srow * (D_ * 2) + R.dk * 16 + lane * 16 + (lane * 57 >> 9) * (D_ * 2 - 144);
      uint32_t pv[20];
#pragma unroll
      for (int pc = 0; pc < 2; pc++) {
        const int q0 = pc ? XP : 0, q1 = pc ? 5 : XP;
        mbar_wait_cluster(sb + B_XFULL + 16 * wg + 8 * pc, 0);
        if (pc && lane == 0) mbar_arrive(sb + B_DONE);
        if (!w && !pc) TLREC(9 + wg);
#pragma unroll
        for (int q = q0; q < q1; q++) { const uint4 v = lds128(xz + q * 2048); pv[4 * q] = v.x; pv[4 * q + 1] = v.y; pv[4 * q + 2] = v.z; pv[4 * q + 3] = v.w; }
#pragma unroll
        for (int i = 4 * q0; i < 4 * q1 && i < 18; i++)
          xx[i] = bfma2(ss[i], pack_bf16(silu_half(fmaf(bf_lo(pv[i]), 0.5f, acc[36 + 2 * i])), silu_half(fmaf(bf_hi(pv[i]), 0.5f, acc[37 + 2 * i]))), xx[i]);
      }
#pragma unroll
      for (int q = 0; q < 4; q++) stsm4(xa + (lane >> 4) * 16 + q * 32, xx[4 * q], xx[4 * q + 1], xx[4 * q + 2], xx[4 * q + 3]);
      stsm2(xa + 128, xx[16], xx[17]);
      __syncwarp();
      if (lane < 27) {
        uint4 v[6];
#pragma unroll
        for (int j = 0; j < 6; j++) v[j] = lds128(xo + lane * 16 + j * 432);
#pragma unroll
        for (int j = 0; j < 6; j++)
          if (j < 5 || lane < 9) *reinterpret_cast<uint4*>(op + j * (3 * D_ * 2)) = v[j];
      }
      if (!w) TLREC(11 + wg);
    }
    TLEND();
  }
}

typedef CUresult (*EncodeFn)(CUtensorMap*, CUtensorMapDataType, cuuint32_t, void*, const cuuint64_t*, const cuuint64_t*, const cuuint32_t*,
                             const cuuint32_t*, CUtensorMapInterleave, CUtensorMapSwizzle, CUtensorMapL2promotion, CUtensorMapFloatOOBfill);

void make_map(EncodeFn fn, CUtensorMap* m, const void* ptr, int rank, const cuuint64_t* dims, const cuuint64_t* strides, const cuuint32_t* box,
              CUtensorMapSwizzle sw) {
  const cuuint32_t es[3] = {1, 1, 1};
  fn(m, CU_TENSOR_MAP_DATA_TYPE_BFLOAT16, rank, const_cast<void*>(ptr), dims, strides, box, es, CU_TENSOR_MAP_INTERLEAVE_NONE, sw,
     CU_TENSOR_MAP_L2_PROMOTION_L2_256B, CU_TENSOR_MAP_FLOAT_OOB_FILL_NONE);
}

void make_roles(Role* R) {
  int ch = 0;
  for (int gi = 0; gi < 8; gi++)
    for (int b = 0; b < 132; b++) {
      const int c = b >> 1, rank = b & 1;
      int g, idx;
      if (c < 4) { g = 0; idx = 4 + c; }
      else if (c < 36) { g = (c - 4) & 7; idx = (c - 4) >> 3; }
      else if (c < 64) { g = 1 + (c - 36) % 7; idx = 4 + (c - 36) / 7; }
      else { g = c - 58; idx = 8; }
      if (g != gi) continue;
      Role& r = R[b];
      r.sg = (int8_t)(idx < 8 ? 2 * (2 * g + (idx >> 2)) : -1);
      r.dk = (int8_t)((idx & 3) * 18 + rank * 9);
      r.ds = (int8_t)((idx & 3) * 18 + (rank ^ 1) * 9);
      if (g < 6 && (idx & 3) == 3) { r.fg = (int8_t)(12 * g + 6 * (idx >> 2) + 3 * rank); r.at = 15; }
      else {
        const bool third = (idx & 3) == 3 || idx == 8;
        const int tr = g < 6 ? 3 * g + (idx >> 2) : 3 * (3 * (g - 6) + (third ? 2 : idx >> 2)) + 2;
        r.fg = (int8_t)(4 * tr + 2 * rank); r.at = (int8_t)(5 * (third ? idx >> 2 : idx & 3));
      }
      r.ncv = idx < 8 ? NCV_REG : NCV_LONG;
      r.ch = (int16_t)ch;
      ch += r.ncv;
    }
}

}

extern "C" void kernel_launch(void* const* d_in, const int* in_sizes, int n_in, void* d_out, int out_size) {
  static Params P;
  static Hot H;
  static const void* cached[5] = {nullptr, nullptr, nullptr, nullptr, nullptr};
  const void* now[5] = {d_in[0], d_in[1], d_in[2], d_in[7], d_in[9]};
  bool same = true;
  for (int i = 0; i < 5; i++) { same = same && cached[i] == now[i]; cached[i] = now[i]; }
  if (!same) {
    void* fp = nullptr;
    cudaDriverEntryPointQueryResult qr;
    cudaGetDriverEntryPoint("cuTensorMapEncodeTiled", &fp, cudaEnableDefault, &qr);
    EncodeFn fn = (EncodeFn)fp;
    void* ps;
    cudaGetSymbolAddress(&ps, g_scratch);
    H.S = (Scratch*)ps;
    const void *py = (char*)ps + offsetof(Scratch, y), *pb = (char*)ps + offsetof(Scratch, ub);
    { cuuint64_t d[3] = {64, S_, F_ / 64}, s[2] = {F_ * 2, 128}; cuuint32_t b[3] = {64, 64, 2}; make_map(fn, &P.m_w1, d_in[7], 3, d, s, b, CU_TENSOR_MAP_SWIZZLE_128B);
      b[2] = 3; make_map(fn, &P.m_w1l, d_in[7], 3, d, s, b, CU_TENSOR_MAP_SWIZZLE_128B); }
    { cuuint64_t d[3] = {64, F_, S_ / 64}, s[2] = {S_ * 2, 128}; cuuint32_t b[3] = {64, 64, 2}; make_map(fn, &P.m_w2, d_in[9], 3, d, s, b, CU_TENSOR_MAP_SWIZZLE_128B); }
    { cuuint64_t d[2] = {D_, S_}, s[1] = {D_ * 2}; cuuint32_t b[2] = {72, 16}; make_map(fn, &P.m_x, d_in[0], 2, d, s, b, CU_TENSOR_MAP_SWIZZLE_NONE);
      b[0] = 96; b[1] = 20; make_map(fn, &P.m_k, d_in[1], 2, d, s, b, CU_TENSOR_MAP_SWIZZLE_NONE);
      b[1] = 17; make_map(fn, &P.m_v, d_in[2], 2, d, s, b, CU_TENSOR_MAP_SWIZZLE_NONE); }
    { cuuint64_t d[3] = {64, D_, S_ / 64}, s[2] = {S_ * 2, 128}; cuuint32_t b[3] = {64, 72, 2}; make_map(fn, &P.m_y, py, 3, d, s, b, CU_TENSOR_MAP_SWIZZLE_128B); }
    { cuuint64_t d[3] = {2048, D_ / 2, 4}, s[2] = {16384, 4096}; cuuint32_t b[3] = {16, 48, 2}; make_map(fn, &P.m_ub, pb, 3, d, s, b, CU_TENSOR_MAP_SWIZZLE_32B); }
    make_roles(P.role);
    cudaFuncSetAttribute(fused_kernel, cudaFuncAttributeMaxDynamicSharedMemorySize, SM_TOTAL);
  }
  H.x = (const __nv_bfloat16*)d_in[0];
  H.shift_k = (const __nv_bfloat16*)d_in[3]; H.ssm_k = (const __nv_bfloat16*)d_in[4]; P.ssm_D = (const __nv_bfloat16*)d_in[5];
  P.b1 = (const __nv_bfloat16*)d_in[8]; H.b2 = (const __nv_bfloat16*)d_in[10]; H.out = (__nv_bfloat16*)d_out;
  fused_kernel<<<132, 384, SM_TOTAL>>>(H, P);
}
```
